```python
import torch

def _softmax(x, axis=-1):
    return torch.softmax(x, dim=axis)

def _gelu(x):
    return torch.nn.functional.gelu(x, approximate='tanh')

def _silu(x):
    return torch.nn.functional.silu(x)

def _sigmoid(x):
    return torch.sigmoid(x)

def _layernorm(x, axis=-1, eps=1e-05):
    m = x.mean(dim=axis, keepdim=True)
    v = x.var(dim=axis, keepdim=True, unbiased=False)
    return (x - m) / torch.sqrt(v + eps)

def _scatter_add(tgt, idx, src, axis=0):
    return tgt.clone().index_add_(axis, idx, src)

def _segment_sum(src, seg, n):
    out = torch.zeros((n,) + src.shape[1:], dtype=src.dtype)
    return out.index_add_(0, seg, src)

def _pad(x, pw):
    flat = tuple((v for pair in reversed(pw) for v in pair))
    return torch.nn.functional.pad(x, flat)
kernel_name = 'interleave_layers__sliding_local_dilated__mixer_gmlp__prompt'

def setup_inputs():

    _w = lambda a: (lambda t: t.to(torch.bfloat16) if t.is_floating_point() else t)(torch.as_tensor(a))

    def _A_setup():
        B, S, D = (1, 2048, 576)
        return {'x': _w((lambda *s: torch.randn(*s, dtype=torch.bfloat16) * 0.05)(B, S, D)), 'wqkv': _w((lambda *s: torch.randn(*s, dtype=torch.bfloat16) * 0.05)(D, 3 * D)), 'wo': _w((lambda *s: torch.randn(*s, dtype=torch.bfloat16) * 0.05)(D, D))}
    _A_in = _A_setup()

    def _B_setup():
        B, S, D, F = (1, 2048, 576, 4608)
        Fh = F // 2
        return {'x': _w((lambda *s: torch.randn(*s, dtype=torch.bfloat16) * 0.05)(B, S, D)), 'w_in': _w((lambda *s: torch.randn(*s, dtype=torch.bfloat16) * 0.2)(D, 2 * Fh)), 'w_sp': _w(0.01 * (lambda *s: torch.randn(*s, dtype=torch.bfloat16) * 0.2)(S, S)), 'b_sp': _w(1.0 + 0.01 * (lambda *s: torch.randn(*s, dtype=torch.bfloat16) * 0.05)(S)), 'w_out': _w((lambda *s: torch.randn(*s, dtype=torch.bfloat16) * 0.05)(Fh, D))}
    _B_in = _B_setup()
    return {'A_x': _A_in['x'], 'A_wqkv': _A_in['wqkv'], 'A_wo': _A_in['wo'], 'B_x': _B_in['x'], 'B_w_in': _B_in['w_in'], 'B_w_sp': _B_in['w_sp'], 'B_b_sp': _B_in['b_sp'], 'B_w_out': _B_in['w_out']}

def reference(A_x, A_wqkv, A_wo, B_x, B_w_in, B_w_sp, B_b_sp, B_w_out):

    def _A_ref(x, wqkv, wo):
        B, S, D = x.shape
        H = 32
        Dh = D // H
        W, dil = (8, 2)
        qkv = (lambda x, *d: x.permute(*d))((x @ wqkv).reshape(B, S, 3, H, Dh), 2, 0, 3, 1, 4)
        q, k, v = (qkv[0], qkv[1], qkv[2])
        scale = Dh ** (-0.5)
        pos = torch.arange(S)
        off = torch.arange(W) * dil
        idx = pos[:, None] - off[None, :]
        mask = idx >= 0
        idx_c = torch.where(mask, idx, 0).reshape(-1)
        kg = k[:, :, idx_c, :].reshape(B, H, S, W, Dh)
        vg = v[:, :, idx_c, :].reshape(B, H, S, W, Dh)
        logits = torch.einsum('bhsd,bhswd->bhsw', q, kg) * scale
        logits = torch.where(mask[None, None, :, :], logits, -1000000000.0)
        attn = _softmax(logits, axis=-1)
        o = torch.einsum('bhsw,bhswd->bhsd', attn, vg)
        return (lambda x, *d: x.permute(*d))(o, 0, 2, 1, 3).reshape(B, S, D) @ wo

    def _B_ref(x, w_in, w_sp, b_sp, w_out):
        B, S, D = x.shape
        F = w_in.shape[-1]
        Fh = F // 2
        z = _gelu(torch.einsum('bsd,df->bsf', x, w_in))
        z1 = z[..., :Fh].clone()
        z2 = _layernorm(z[..., Fh:], axis=-1)
        g = torch.einsum('ts,bsf->btf', w_sp, z2) + b_sp[None, :, None]
        return torch.einsum('bsf,fd->bsd', z1 * g, w_out)
    x = A_x
    x = x + _A_ref(_layernorm(x, axis=-1), A_wqkv, A_wo)
    x = x + _B_ref(_layernorm(x, axis=-1), B_w_in, B_w_sp, B_b_sp, B_w_out)
    x = x + _A_ref(_layernorm(x, axis=-1), A_wqkv, A_wo)
    x = x + _B_ref(_layernorm(x, axis=-1), B_w_in, B_w_sp, B_b_sp, B_w_out)
    return x
```

```cpp
#include <cuda_runtime.h>
#include <cuda.h>
#include <cuda_bf16.h>
#include <stdint.h>

#define MK_TRACE 0
#define MK_DBG 0
#define P5TRACE 0
#define LAG1 1
#define PP3 32
#define PP30 33
#define GM2 3
#define GMM 3
#define GM1 2
#define C0S 32.f
#define OFM 0x10u
#define PPK 13

namespace mk {

constexpr int SEQ = 2048, DM = 576, FH = 2304;
constexpr int NCTA = 128;
constexpr int NGRID = 132;
constexpr uint32_t ZB = 36864;
constexpr uint32_t WQ_SL = 72 * 3456;
constexpr uint32_t WO_SL = 72 * 1152;
constexpr float LN_EPS = 1e-5f;
constexpr float GA = 0.3292034911525734f, GB = 2.423681954311584f;

constexpr uint32_t ST_BYTES = 53248, ST_B = 16384, NST = 4;
constexpr uint32_t SM_STG = NST * ST_BYTES;
constexpr uint32_t SM_BAR = SM_STG + 2 * 9216;
constexpr uint32_t SM_OFF = SM_BAR + 1008;
constexpr uint32_t SM_TOTAL = SM_BAR + 1024;
constexpr uint32_t SM_RT = SM_STG + 4096, SM_CV = SM_STG + 12288, SM_WT = SM_CV + 512;
constexpr uint32_t SM_WOI = 44032, SM_CSQ = 49280, SM_XST = 50176;
constexpr uint32_t B_FULL = 0, B_EMPTY = 32, B_FULLA = 64, B_RES = 128, B_WT = 144, B_IMG = 160, B_WOI = 168, B_GATE3 = 184, B_Z1 = 192, B_LAG = 200,
                   B_RT = 208, B_CSQ = 216, B_CV = 224, B_AD = 240, B_EVT = 272, B_RT1 = 368, B_XRW = 384, B_FA3 = 400, B_EA3 = 544;
enum { EV_PT = 0, EV_O = 1, EV_X1 = 2, EV_ZN = 3, EV_Z1 = 4, EV_P4 = 5, EV_N = 6 };

enum { FR_X2 = 0, FR_O = 1, FR_X1 = 3, FR_EP = 16, FJ = 32 * 32, FJ_WQ = 0, FJ_WO = 1, FJ_ZN = 3, FJ_P4 = 5, FJ_EP = 16, F_N = FJ + 8 * 32 };

__device__ __align__(1024) uint8_t g_Z[512 * ZB];
__device__ __align__(1024) uint8_t g_WQ[8 * WQ_SL];
__device__ __align__(1024) uint8_t g_WO[8 * WO_SL];
__device__ __align__(1024) float g_CSP[2 * NCTA * 216];
__device__ __align__(1024) uint2 g_RT[SEQ];
__device__ __align__(1024) uint4 g_XST[2 * SEQ];
__device__ __align__(1024) uint4 g_ST1[SEQ * 8];
__device__ __align__(1024) uint4 g_ZST[SEQ * 8];
__device__ __align__(1024) uint4 g_HALO[32 * 8 * 6 * 32];
__device__ __align__(1024) uint32_t g_flags[F_N];

struct Params {
  CUtensorMap wsp, win, win64, wout;
  CUtensorMap act[2];
  CUtensorMap res[2];
  CUtensorMap red;
  const __nv_bfloat16 *wqkv, *wo, *w_in, *w_sp, *b_sp, *w_out;
  uint8_t* xs[2];
  int role[NGRID / 2];
  uint32_t zero;
};

__device__ __forceinline__ uint32_t smem_u32(const void* p) { return (uint32_t)__cvta_generic_to_shared(p); }
__device__ __forceinline__ void mbar_init(uint32_t bar, uint32_t cnt) { asm volatile("mbarrier.init.shared::cta.b64 [%0], %1;" ::"r"(bar), "r"(cnt)); }
__device__ __forceinline__ void mbar_arrive(uint32_t bar) { asm volatile("mbarrier.arrive.shared::cta.b64 _, [%0];" ::"r"(bar) : "memory"); }
__device__ __forceinline__ void mbar_wait(uint32_t bar, uint32_t parity) {
  asm volatile(
      "{\n.reg .pred p;\n.reg .u32 c;\nmov.u32 c, 0;\nLAB_WAIT:\n"
      "mbarrier.try_wait.parity.shared::cta.b64 p, [%0], %1;\n@p bra LAB_DONE;\n"
      "add.u32 c, c, 1;\nsetp.lt.u32 p, c, 0x100000;\n@p bra LAB_WAIT;\ntrap;\nLAB_DONE:\n}" ::"r"(bar), "r"(parity)
      : "memory");
}
__device__ __forceinline__ void mbar_wait_c(uint32_t bar, uint32_t parity) {
  asm volatile("{\n.reg .pred p;\nLAB_WAIT:\nmbarrier.try_wait.parity.shared::cta.b64 p, [%0], %1;\n@!p bra LAB_WAIT;\n}" ::"r"(bar), "r"(parity) : "memory");
}
__device__ __forceinline__ void flag_wait(const uint32_t* f, uint32_t target) {
  asm volatile(
      "{\n.reg .pred p;\n.reg .u32 c, v;\nmov.u32 c, 0;\nLAB_WAIT:\n"
      "ld.relaxed.gpu.global.u32 v, [%0];\nsub.u32 v, v, %1;\nsetp.ge.s32 p, v, 0;\n@p bra LAB_DONE;\n"
      "add.u32 c, c, 1;\nsetp.lt.u32 p, c, 0x400000;\n@p bra LAB_WAIT;\ntrap;\nLAB_DONE:\nfence.acquire.gpu;\n}" ::"l"(f), "r"(target)
      : "memory");
}
__device__ __forceinline__ void fence_gpu() { asm volatile("fence.acq_rel.gpu;" ::: "memory"); }
__device__ __forceinline__ void fence_async_g() { asm volatile("fence.proxy.async.global;" ::: "memory"); }
__device__ __forceinline__ void fence_async_s() { asm volatile("fence.proxy.async.shared::cta;" ::: "memory"); }
__device__ __forceinline__ uint32_t elect_one() {
  uint32_t p; asm volatile("{\n.reg .pred P;\nelect.sync _|P, 0xffffffff;\nselp.u32 %0, 1, 0, P;\n}" : "=r"(p)); return p;
}
__device__ __forceinline__ void expect_tx_p(uint32_t el, uint32_t bar, uint32_t bytes) {
  asm volatile("{\n.reg .pred P;\nsetp.ne.u32 P, %2, 0;\n@P mbarrier.arrive.expect_tx.shared::cta.b64 _, [%0], %1;\n}" ::"r"(bar), "r"(bytes), "r"(el) : "memory");
}
__device__ __forceinline__ void bulk_load_p(uint32_t el, uint32_t dst, const void* src, uint32_t bytes, uint32_t bar) {
  asm volatile("{\n.reg .pred P;\nsetp.ne.u32 P, %4, 0;\n@P cp.async.bulk.shared::cluster.global.mbarrier::complete_tx::bytes [%0], [%1], %2, [%3];\n}" ::"r"(dst), "l"(src), "r"(bytes), "r"(bar), "r"(el) : "memory");
}
__device__ __forceinline__ uint64_t policy_evict_first() { uint64_t p; asm("createpolicy.fractional.L2::evict_first.b64 %0, 1.0;" : "=l"(p)); return p; }
__device__ __forceinline__ void bulk_load_h(uint32_t el, uint32_t dst, const void* src, uint32_t bytes, uint32_t bar, bool ef, uint64_t pol) {
  if (ef) {
    asm volatile("{\n.reg .pred P;\nsetp.ne.u32 P, %4, 0;\n@P cp.async.bulk.shared::cluster.global.mbarrier::complete_tx::bytes.L2::cache_hint [%0], [%1], %2, [%3], %5;\n}" ::"r"(dst), "l"(src), "r"(bytes), "r"(bar), "r"(el), "l"(pol) : "memory");
  } else {
    asm volatile("{\n.reg .pred P;\nsetp.ne.u32 P, %4, 0;\n@P cp.async.bulk.shared::cluster.global.mbarrier::complete_tx::bytes [%0], [%1], %2, [%3];\n}" ::"r"(dst), "l"(src), "r"(bytes), "r"(bar), "r"(el) : "memory");
  }
}
__device__ __forceinline__ void bulk_mc_h(uint32_t el, uint32_t dst, const void* src, uint32_t bytes, uint32_t bar, bool ef, uint64_t pol) {
  if (ef) {
    asm volatile("{\n.reg .pred P;\nsetp.ne.u32 P, %4, 0;\n@P cp.async.bulk.shared::cluster.global.mbarrier::complete_tx::bytes.multicast::cluster.L2::cache_hint [%0], [%1], %2, [%3], %5, %6;\n}" ::"r"(dst), "l"(src), "r"(bytes), "r"(bar), "r"(el), "h"((uint16_t)3), "l"(pol) : "memory");
  } else {
    asm volatile("{\n.reg .pred P;\nsetp.ne.u32 P, %4, 0;\n@P cp.async.bulk.shared::cluster.global.mbarrier::complete_tx::bytes.multicast::cluster [%0], [%1], %2, [%3], %5;\n}" ::"r"(dst), "l"(src), "r"(bytes), "r"(bar), "r"(el), "h"((uint16_t)3) : "memory");
  }
}
__device__ __forceinline__ void tma3d_h(uint32_t el, uint32_t dst, const CUtensorMap* m, int c0, int c1, int c2, uint32_t bar, bool ef, uint64_t pol) {
  if (ef) {
    asm volatile("{\n.reg .pred P;\nsetp.ne.u32 P, %6, 0;\n@P cp.async.bulk.tensor.3d.shared::cluster.global.mbarrier::complete_tx::bytes.L2::cache_hint [%0], [%1, {%3, %4, %5}], [%2], %7;\n}" ::"r"(dst), "l"(m), "r"(bar), "r"(c0), "r"(c1), "r"(c2), "r"(el), "l"(pol) : "memory");
  } else {
    asm volatile("{\n.reg .pred P;\nsetp.ne.u32 P, %6, 0;\n@P cp.async.bulk.tensor.3d.shared::cluster.global.mbarrier::complete_tx::bytes [%0], [%1, {%3, %4, %5}], [%2];\n}" ::"r"(dst), "l"(m), "r"(bar), "r"(c0), "r"(c1), "r"(c2), "r"(el) : "memory");
  }
}
__device__ __forceinline__ void tma2d_mc_h(uint32_t el, uint32_t dst, const CUtensorMap* m, int c0, int c1, uint32_t bar, bool ef, uint64_t pol) {
  if (ef) {
    asm volatile("{\n.reg .pred P;\nsetp.ne.u32 P, %5, 0;\n@P cp.async.bulk.tensor.2d.shared::cluster.global.mbarrier::complete_tx::bytes.multicast::cluster.L2::cache_hint [%0], [%1, {%3, %4}], [%2], %6, %7;\n}" ::"r"(dst), "l"(m), "r"(bar), "r"(c0), "r"(c1), "r"(el), "h"((uint16_t)3), "l"(pol) : "memory");
  } else {
    asm volatile("{\n.reg .pred P;\nsetp.ne.u32 P, %5, 0;\n@P cp.async.bulk.tensor.2d.shared::cluster.global.mbarrier::complete_tx::bytes.multicast::cluster [%0], [%1, {%3, %4}], [%2], %6;\n}" ::"r"(dst), "l"(m), "r"(bar), "r"(c0), "r"(c1), "r"(el), "h"((uint16_t)3) : "memory");
  }
}
__device__ __forceinline__ void tma4d_mc(uint32_t el, uint32_t dst, const CUtensorMap* m, int c0, int c3, uint32_t bar, uint64_t pol) {
  asm volatile("{\n.reg .pred P;\nsetp.ne.u32 P, %5, 0;\n@P cp.async.bulk.tensor.4d.shared::cluster.global.mbarrier::complete_tx::bytes.multicast::cluster.L2::cache_hint [%0], [%1, {%3, 0, 0, %4}], [%2], %6, %7;\n}" ::"r"(dst), "l"(m), "r"(bar), "r"(c0), "r"(c3), "r"(el), "h"((uint16_t)3), "l"(pol) : "memory");
}
__device__ __forceinline__ void mbar_arrive_cluster(uint32_t addr) { asm volatile("mbarrier.arrive.shared::cluster.b64 _, [%0];" ::"r"(addr) : "memory"); }
__device__ __forceinline__ uint32_t mapa(uint32_t addr, uint32_t rank) { uint32_t r; asm("mapa.shared::cluster.u32 %0, %1, %2;" : "=r"(r) : "r"(addr), "r"(rank)); return r; }
__device__ __forceinline__ void bulk_store_p(uint32_t el, void* dst, uint32_t src, uint32_t bytes) {
  asm volatile("{\n.reg .pred P;\nsetp.ne.u32 P, %3, 0;\n@P cp.async.bulk.global.shared::cta.bulk_group [%0], [%1], %2;\n}" ::"l"(dst), "r"(src), "r"(bytes), "r"(el) : "memory");
}
__device__ __forceinline__ void flag_release_p(uint32_t el, uint32_t* f) {
  asm volatile("{\n.reg .pred P;\nsetp.ne.u32 P, %1, 0;\n@P red.release.gpu.global.add.u32 [%0], 1;\n}" ::"l"(f), "r"(el) : "memory");
}
__device__ __forceinline__ void flag_add_p(uint32_t el, uint32_t* f) {
  asm volatile("{\n.reg .pred P;\nsetp.ne.u32 P, %1, 0;\n@P red.relaxed.gpu.global.add.u32 [%0], 1;\n}" ::"l"(f), "r"(el) : "memory");
}
__device__ __forceinline__ void prefetch_l2(const void* src, uint32_t bytes) { asm volatile("cp.async.bulk.prefetch.L2.global [%0], %1;" ::"l"(src), "r"(bytes) : "memory"); }
__device__ __forceinline__ void prefetch_map(const CUtensorMap* m) { asm volatile("prefetch.tensormap [%0];" ::"l"(m) : "memory"); }
__device__ __forceinline__ void wgmma_fence() { asm volatile("wgmma.fence.sync.aligned;" ::: "memory"); }
__device__ __forceinline__ void wgmma_commit() { asm volatile("wgmma.commit_group.sync.aligned;" ::: "memory"); }
template <int N> __device__ __forceinline__ void wgmma_wait() { asm volatile("wgmma.wait_group.sync.aligned %0;" ::"n"(N) : "memory"); }
__device__ __forceinline__ uint32_t dlo(uint32_t addr, uint32_t lbo) { return ((addr & 0x3FFFF) >> 4) + ((lbo >> 4) << 16); }
template <uint32_t SBO, uint32_t SWZ> __device__ __forceinline__ uint64_t dsc(uint32_t lo, uint32_t off) {
  uint64_t d; asm("mov.b64 %0, {%1, %2};" : "=l"(d) : "r"(lo + (off >> 4)), "n"((SBO >> 4) | (SWZ << 30))); return d;
}
__device__ __forceinline__ uint64_t dsc2(uint32_t lo, uint32_t off, uint32_t hi) {
  uint64_t d; asm("mov.b64 %0, {%1, %2};" : "=l"(d) : "r"(lo + (off >> 4)), "r"(hi)); return d;
}
__device__ __forceinline__ void dadd(uint64_t& d, uint32_t v) {
  asm("{\n.reg .b32 lo, hi;\nmov.b64 {lo, hi}, %0;\nadd.u32 lo, lo, %1;\nmov.b64 %0, {lo, hi};\n}" : "+l"(d) : "r"(v));
}
template <int R> __device__ __forceinline__ void reg_alloc() { asm volatile("setmaxnreg.inc.sync.aligned.u32 %0;" ::"n"(R)); }
template <int R> __device__ __forceinline__ void reg_dealloc() { asm volatile("setmaxnreg.dec.sync.aligned.u32 %0;" ::"n"(R)); }
__device__ __forceinline__ void bar_sync(int id, int n) { asm volatile("bar.sync %0, %1;" ::"r"(id), "r"(n) : "memory"); }
__device__ __forceinline__ void bar_arrive(int id, int n) { asm volatile("bar.arrive %0, %1;" ::"r"(id), "r"(n) : "memory"); }
__device__ __forceinline__ void ldsm4(uint32_t* r, uint32_t addr) {
  asm volatile("ldmatrix.sync.aligned.m8n8.x4.shared.b16 {%0,%1,%2,%3}, [%4];" : "=r"(r[0]), "=r"(r[1]), "=r"(r[2]), "=r"(r[3]) : "r"(addr) : "memory");
}
__device__ __forceinline__ uint32_t movm(uint32_t a) { uint32_t d; asm volatile("movmatrix.sync.aligned.m8n8.trans.b16 %0, %1;" : "=r"(d) : "r"(a)); return d; }
__device__ __forceinline__ void mma16(float* c, uint32_t a0, uint32_t a1, uint32_t a2, uint32_t a3, uint32_t b0, uint32_t b1) {
  asm volatile("mma.sync.aligned.m16n8k16.row.col.f32.bf16.bf16.f32 {%0,%1,%2,%3}, {%4,%5,%6,%7}, {%8,%9}, {%0,%1,%2,%3};"
               : "+f"(c[0]), "+f"(c[1]), "+f"(c[2]), "+f"(c[3]) : "r"(a0), "r"(a1), "r"(a2), "r"(a3), "r"(b0), "r"(b1));
}
__device__ __forceinline__ void mma8(float* c, uint32_t a0, uint32_t a1, uint32_t b0) {
  asm volatile("mma.sync.aligned.m16n8k8.row.col.f32.bf16.bf16.f32 {%0,%1,%2,%3}, {%4,%5}, {%6}, {%0,%1,%2,%3};"
               : "+f"(c[0]), "+f"(c[1]), "+f"(c[2]), "+f"(c[3]) : "r"(a0), "r"(a1), "r"(b0));
}
__device__ __forceinline__ uint32_t pack2(float lo, float hi) { uint32_t r; asm("cvt.rn.bf16x2.f32 %0, %1, %2;" : "=r"(r) : "f"(hi), "f"(lo)); return r; }
__device__ __forceinline__ float blo(uint32_t v) { return __uint_as_float(v << 16); }
__device__ __forceinline__ float bhi(uint32_t v) { return __uint_as_float(v & 0xffff0000u); }
__device__ __forceinline__ float tanh_fast(float x) { float y; asm("tanh.approx.f32 %0, %1;" : "=f"(y) : "f"(x)); return y; }
__device__ __forceinline__ float rcp_fast(float x) { float y; asm("rcp.approx.ftz.f32 %0, %1;" : "=f"(y) : "f"(x)); return y; }
__device__ __forceinline__ float ex2(float x) { float y; asm("ex2.approx.ftz.f32 %0, %1;" : "=f"(y) : "f"(x)); return y; }
__device__ __forceinline__ float qsum(float v) { v += __shfl_xor_sync(~0u, v, 1); v += __shfl_xor_sync(~0u, v, 2); return v; }
__device__ __forceinline__ float qmax(float v) { v = fmaxf(v, __shfl_xor_sync(~0u, v, 1)); v = fmaxf(v, __shfl_xor_sync(~0u, v, 2)); return v; }
__device__ __forceinline__ void stg32(void* p, uint32_t v) { asm volatile("st.global.u32 [%0], %1;" ::"l"(p), "r"(v) : "memory"); }
__device__ __forceinline__ void stg128(void* p, uint32_t a, uint32_t b, uint32_t c, uint32_t d) { asm volatile("st.global.v4.u32 [%0], {%1,%2,%3,%4};" ::"l"(p), "r"(a), "r"(b), "r"(c), "r"(d) : "memory"); }
__device__ __forceinline__ uint32_t ldcg32(const void* p) { uint32_t v; asm volatile("ld.global.L1::no_allocate.u32 %0, [%1];" : "=r"(v) : "l"(p) : "memory"); return v; }
__device__ __forceinline__ void stg128_if(bool c, void* p, uint32_t a, uint32_t b, uint32_t cc, uint32_t d) {
  asm volatile("{\n.reg .pred P;\nsetp.ne.u32 P, %5, 0;\n@P st.global.v4.u32 [%0], {%1,%2,%3,%4};\n}" ::"l"(p), "r"(a), "r"(b), "r"(cc), "r"(d), "r"((uint32_t)c) : "memory");
}
__device__ __forceinline__ uint2 lds64(uint32_t a) { uint2 v; asm volatile("ld.shared.v2.u32 {%0,%1}, [%2];" : "=r"(v.x), "=r"(v.y) : "r"(a) : "memory"); return v; }
__device__ __forceinline__ uint4 ldcg128(const void* p) { uint4 v; asm volatile("ld.global.cg.v4.u32 {%0,%1,%2,%3}, [%4];" : "=r"(v.x), "=r"(v.y), "=r"(v.z), "=r"(v.w) : "l"(p) : "memory"); return v; }
__device__ __forceinline__ uint32_t ldnc16(const void* p) { uint16_t v; asm volatile("ld.global.nc.u16 %0, [%1];" : "=h"(v) : "l"(p)); return v; }
__device__ __forceinline__ uint4 ldnc128(const void* p) { uint4 v; asm volatile("ld.global.nc.v4.u32 {%0,%1,%2,%3}, [%4];" : "=r"(v.x), "=r"(v.y), "=r"(v.z), "=r"(v.w) : "l"(p)); return v; }
__device__ __forceinline__ void cp_async16(uint32_t dst, const void* src) { asm volatile("cp.async.cg.shared.global [%0], [%1], 16;" ::"r"(dst), "l"(src) : "memory"); }
__device__ __forceinline__ uint32_t hsub2(uint32_t a, uint32_t b) { uint32_t d; asm("sub.rn.bf16x2 %0, %1, %2;" : "=r"(d) : "r"(a), "r"(b)); return d; }
__device__ __forceinline__ void stg32_if(bool c, void* p, uint32_t v) {
  asm volatile("{\n.reg .pred P;\nsetp.ne.u32 P, %2, 0;\n@P st.global.u32 [%0], %1;\n}" ::"l"(p), "r"(v), "r"((uint32_t)c) : "memory");
}
__device__ __forceinline__ float wsum(float v) { for (int o = 16; o; o >>= 1) v += __shfl_xor_sync(~0u, v, o); return v; }
__device__ __forceinline__ uint32_t hmul2(uint32_t a, uint32_t b) { uint32_t d; asm("mul.rn.bf16x2 %0, %1, %2;" : "=r"(d) : "r"(a), "r"(b)); return d; }
__device__ __forceinline__ void sts32(uint32_t a, uint32_t v) { asm volatile("st.shared.u32 [%0], %1;" ::"r"(a), "r"(v) : "memory"); }
__device__ __forceinline__ uint32_t lds32(uint32_t a) { uint32_t v; asm volatile("ld.shared.u32 %0, [%1];" : "=r"(v) : "r"(a) : "memory"); return v; }
__device__ __forceinline__ void sts128(uint32_t a, uint32_t x, uint32_t y, uint32_t z, uint32_t w) { asm volatile("st.shared.v4.u32 [%0], {%1,%2,%3,%4};" ::"r"(a), "r"(x), "r"(y), "r"(z), "r"(w) : "memory"); }
__device__ __forceinline__ uint4 lds128(uint32_t a) { uint4 v; asm volatile("ld.shared.v4.u32 {%0,%1,%2,%3}, [%4];" : "=r"(v.x), "=r"(v.y), "=r"(v.z), "=r"(v.w) : "r"(a) : "memory"); return v; }
__device__ __forceinline__ void ll_st64(uint2* p, uint32_t v, uint32_t tag) {
  asm volatile("{\n.reg .b64 r;\nmov.b64 r, {%1,%2};\nst.relaxed.gpu.global.b64 [%0], r;\n}" ::"l"(p), "r"(v), "r"(tag) : "memory");
}
__device__ __forceinline__ uint2 ll_ld64(const uint2* p) {
  uint2 v; asm volatile("{\n.reg .b64 r;\nld.relaxed.gpu.global.b64 r, [%2];\nmov.b64 {%0,%1}, r;\n}" : "=r"(v.x), "=r"(v.y) : "l"(p) : "memory"); return v;
}
__device__ __forceinline__ void ll_st128(uint4* p, float a, float b, uint32_t tag, float c = 0.f) {
  asm volatile("{\n.reg .b128 r;\n.reg .b64 lo, hi;\nmov.b64 lo, {%1,%2};\nmov.b64 hi, {%3,%4};\nmov.b128 r, {lo, hi};\nst.relaxed.gpu.global.b128 [%0], r;\n}" ::"l"(p), "r"(__float_as_uint(a)), "r"(__float_as_uint(b)), "r"(tag), "r"(__float_as_uint(c)) : "memory");
}
__device__ __forceinline__ uint4 ll_ld128(const uint4* p) {
  uint4 v; asm volatile("{\n.reg .b128 r;\n.reg .b64 lo, hi;\nld.relaxed.gpu.global.b128 r, [%4];\nmov.b128 {lo, hi}, r;\nmov.b64 {%0,%1}, lo;\nmov.b64 {%2,%3}, hi;\n}" : "=r"(v.x), "=r"(v.y), "=r"(v.z), "=r"(v.w) : "l"(p) : "memory"); return v;
}
__device__ __forceinline__ void publish_p(uint32_t el, uint32_t* f) {
  asm volatile("{\n.reg .pred P;\nsetp.ne.u32 P, %1, 0;\n@P cp.async.bulk.commit_group;\n@P cp.async.bulk.wait_group 0;\n@P red.release.gpu.global.add.u32 [%0], 1;\n}" ::"l"(f), "r"(el) : "memory");
}
__device__ __forceinline__ void tma3d_red_p(uint32_t el, const CUtensorMap* m, int c0, int c1, int c2, uint32_t src) {
  asm volatile("{\n.reg .pred P;\nsetp.ne.u32 P, %5, 0;\n@P cp.reduce.async.bulk.tensor.3d.global.shared::cta.add.tile.bulk_group [%0, {%2, %3, %4}], [%1];\n@P cp.async.bulk.commit_group;\n}" ::"l"(m), "r"(src), "r"(c0), "r"(c1), "r"(c2), "r"(el) : "memory");
}
__device__ __forceinline__ void stsm4(uint32_t addr, uint32_t a, uint32_t b, uint32_t c, uint32_t d) {
  asm volatile("stmatrix.sync.aligned.m8n8.x4.shared.b16 [%0], {%1,%2,%3,%4};" ::"r"(addr), "r"(a), "r"(b), "r"(c), "r"(d) : "memory");
}
__device__ __forceinline__ void sts64(uint32_t a, uint32_t x, uint32_t y) { asm volatile("st.shared.v2.u32 [%0], {%1,%2};" ::"r"(a), "r"(x), "r"(y) : "memory"); }
__device__ __forceinline__ void ll_st128_if(bool on, uint4* p, float a, float b, uint32_t tag) {
  asm volatile("{\n.reg .pred P;\n.reg .b128 r;\n.reg .b64 lo, hi;\nsetp.ne.u32 P, %4, 0;\nmov.b64 lo, {%1,%2};\nmov.b64 hi, {%3,%3};\nmov.b128 r, {lo, hi};\n@P st.relaxed.gpu.global.b128 [%0], r;\n}" ::"l"(p), "r"(__float_as_uint(a)), "r"(__float_as_uint(b)), "r"(tag), "r"((uint32_t)on) : "memory");
}
__device__ __forceinline__ uint4 ldnc128_if(bool c, const void* p) {
  uint4 v = make_uint4(0u, 0u, 0u, 0u);
  asm volatile("{\n.reg .pred P;\nsetp.ne.u32 P, %5, 0;\n@P ld.global.nc.v4.u32 {%0,%1,%2,%3}, [%4];\n}" : "+r"(v.x), "+r"(v.y), "+r"(v.z), "+r"(v.w) : "l"(p), "r"((uint32_t)c));
  return v;
}
__device__ __forceinline__ uint32_t hfma2(uint32_t a, uint32_t b, uint32_t c) { uint32_t d; asm("fma.rn.bf16x2 %0, %1, %2, %3;" : "=r"(d) : "r"(a), "r"(b), "r"(c)); return d; }
__device__ __forceinline__ float2 lds64f(uint32_t a) { float2 v; asm volatile("ld.shared.v2.f32 {%0,%1}, [%2];" : "=f"(v.x), "=f"(v.y) : "r"(a) : "memory"); return v; }
#define TRC(cond, role, idx) do {} while (0)
#define TRV(role, idx, v) do {} while (0)

#define ACLK_INIT do {} while (0)
#define ACLK(i) do {} while (0)
#define ACLK_OUT do {} while (0)
#define QCLK(i) do {} while (0)
#define PH 1
#define RCLK(i) do {} while (0)
#define RCLK_INIT do {} while (0)
#define RCLK_OUT do {} while (0)
#define SCLK(i) do {} while (0)
#define HCLK(i) do {} while (0)
#define PL 1
#define PCLK(i) do {} while (0)
#define PQ 1
#define CLK_INIT do {} while (0)
#define CLK(i) do {} while (0)
#define CLK_OUT do {} while (0)

__device__ __forceinline__ void wgmma_ss_n216(float* d, uint64_t da, uint64_t db, int scaleD) {
  asm volatile("{\n.reg .pred p;\nsetp.ne.b32 p, %110, 0;\nwgmma.mma_async.sync.aligned.m64n216k16.f32.bf16.bf16 "
    "{%0,%1,%2,%3,%4,%5,%6,%7,%8,%9,%10,%11,%12,%13,%14,%15,%16,%17,%18,%19,%20,%21,%22,%23,%24,%25,%26,%27,%28,%29,%30,%31,%32,%33,%34,%35,%36,%37,%38,%39,%40,%41,%42,%43,%44,%45,%46,%47,%48,%49,%50,%51,%52,%53,%54,%55,%56,%57,%58,%59,%60,%61,%62,%63,%64,%65,%66,%67,%68,%69,%70,%71,%72,%73,%74,%75,%76,%77,%78,%79,%80,%81,%82,%83,%84,%85,%86,%87,%88,%89,%90,%91,%92,%93,%94,%95,%96,%97,%98,%99,%100,%101,%102,%103,%104,%105,%106,%107}, "
    "%108, %109, p, 1, 1, 0, 1;\n}\n"
    : "+f"(d[0]), "+f"(d[1]), "+f"(d[2]), "+f"(d[3]), "+f"(d[4]), "+f"(d[5]), "+f"(d[6]), "+f"(d[7]), "+f"(d[8]), "+f"(d[9]), "+f"(d[10]), "+f"(d[11]), "+f"(d[12]), "+f"(d[13]), "+f"(d[14]), "+f"(d[15]), "+f"(d[16]), "+f"(d[17]), "+f"(d[18]), "+f"(d[19]), "+f"(d[20]), "+f"(d[21]), "+f"(d[22]), "+f"(d[23]), "+f"(d[24]), "+f"(d[25]), "+f"(d[26]), "+f"(d[27]), "+f"(d[28]), "+f"(d[29]), "+f"(d[30]), "+f"(d[31]), "+f"(d[32]), "+f"(d[33]), "+f"(d[34]), "+f"(d[35]), "+f"(d[36]), "+f"(d[37]), "+f"(d[38]), "+f"(d[39]), "+f"(d[40]), "+f"(d[41]), "+f"(d[42]), "+f"(d[43]), "+f"(d[44]), "+f"(d[45]), "+f"(d[46]), "+f"(d[47]), "+f"(d[48]), "+f"(d[49]), "+f"(d[50]), "+f"(d[51]), "+f"(d[52]), "+f"(d[53]), "+f"(d[54]), "+f"(d[55]), "+f"(d[56]), "+f"(d[57]), "+f"(d[58]), "+f"(d[59]), "+f"(d[60]), "+f"(d[61]), "+f"(d[62]), "+f"(d[63]), "+f"(d[64]), "+f"(d[65]), "+f"(d[66]), "+f"(d[67]), "+f"(d[68]), "+f"(d[69]), "+f"(d[70]), "+f"(d[71]), "+f"(d[72]), "+f"(d[73]), "+f"(d[74]), "+f"(d[75]), "+f"(d[76]), "+f"(d[77]), "+f"(d[78]), "+f"(d[79]), "+f"(d[80]), "+f"(d[81]), "+f"(d[82]), "+f"(d[83]), "+f"(d[84]), "+f"(d[85]), "+f"(d[86]), "+f"(d[87]), "+f"(d[88]), "+f"(d[89]), "+f"(d[90]), "+f"(d[91]), "+f"(d[92]), "+f"(d[93]), "+f"(d[94]), "+f"(d[95]), "+f"(d[96]), "+f"(d[97]), "+f"(d[98]), "+f"(d[99]), "+f"(d[100]), "+f"(d[101]), "+f"(d[102]), "+f"(d[103]), "+f"(d[104]), "+f"(d[105]), "+f"(d[106]), "+f"(d[107])
    : "l"(da), "l"(db), "r"(scaleD));
}
__device__ __forceinline__ void wgmma_ss_n72(float* d, uint64_t da, uint64_t db, int scaleD) {
  asm volatile("{\n.reg .pred p;\nsetp.ne.b32 p, %38, 0;\nwgmma.mma_async.sync.aligned.m64n72k16.f32.bf16.bf16 "
    "{%0,%1,%2,%3,%4,%5,%6,%7,%8,%9,%10,%11,%12,%13,%14,%15,%16,%17,%18,%19,%20,%21,%22,%23,%24,%25,%26,%27,%28,%29,%30,%31,%32,%33,%34,%35}, "
    "%36, %37, p, 1, 1, 0, 1;\n}\n"
    : "+f"(d[0]), "+f"(d[1]), "+f"(d[2]), "+f"(d[3]), "+f"(d[4]), "+f"(d[5]), "+f"(d[6]), "+f"(d[7]), "+f"(d[8]), "+f"(d[9]), "+f"(d[10]), "+f"(d[11]), "+f"(d[12]), "+f"(d[13]), "+f"(d[14]), "+f"(d[15]), "+f"(d[16]), "+f"(d[17]), "+f"(d[18]), "+f"(d[19]), "+f"(d[20]), "+f"(d[21]), "+f"(d[22]), "+f"(d[23]), "+f"(d[24]), "+f"(d[25]), "+f"(d[26]), "+f"(d[27]), "+f"(d[28]), "+f"(d[29]), "+f"(d[30]), "+f"(d[31]), "+f"(d[32]), "+f"(d[33]), "+f"(d[34]), "+f"(d[35])
    : "l"(da), "l"(db), "r"(scaleD));
}
__device__ __forceinline__ void wgmma_rs_n144(float* d, const uint32_t* a, uint64_t db, int scaleD) {
  asm volatile("{\n.reg .pred p;\nsetp.ne.b32 p, %77, 0;\nwgmma.mma_async.sync.aligned.m64n144k16.f32.bf16.bf16 "
    "{%0,%1,%2,%3,%4,%5,%6,%7,%8,%9,%10,%11,%12,%13,%14,%15,%16,%17,%18,%19,%20,%21,%22,%23,%24,%25,%26,%27,%28,%29,%30,%31,%32,%33,%34,%35,%36,%37,%38,%39,%40,%41,%42,%43,%44,%45,%46,%47,%48,%49,%50,%51,%52,%53,%54,%55,%56,%57,%58,%59,%60,%61,%62,%63,%64,%65,%66,%67,%68,%69,%70,%71}, "
    "{%72,%73,%74,%75}, %76, p, 1, 1, 1;\n}\n"
    : "+f"(d[0]), "+f"(d[1]), "+f"(d[2]), "+f"(d[3]), "+f"(d[4]), "+f"(d[5]), "+f"(d[6]), "+f"(d[7]), "+f"(d[8]), "+f"(d[9]), "+f"(d[10]), "+f"(d[11]), "+f"(d[12]), "+f"(d[13]), "+f"(d[14]), "+f"(d[15]), "+f"(d[16]), "+f"(d[17]), "+f"(d[18]), "+f"(d[19]), "+f"(d[20]), "+f"(d[21]), "+f"(d[22]), "+f"(d[23]), "+f"(d[24]), "+f"(d[25]), "+f"(d[26]), "+f"(d[27]), "+f"(d[28]), "+f"(d[29]), "+f"(d[30]), "+f"(d[31]), "+f"(d[32]), "+f"(d[33]), "+f"(d[34]), "+f"(d[35]), "+f"(d[36]), "+f"(d[37]), "+f"(d[38]), "+f"(d[39]), "+f"(d[40]), "+f"(d[41]), "+f"(d[42]), "+f"(d[43]), "+f"(d[44]), "+f"(d[45]), "+f"(d[46]), "+f"(d[47]), "+f"(d[48]), "+f"(d[49]), "+f"(d[50]), "+f"(d[51]), "+f"(d[52]), "+f"(d[53]), "+f"(d[54]), "+f"(d[55]), "+f"(d[56]), "+f"(d[57]), "+f"(d[58]), "+f"(d[59]), "+f"(d[60]), "+f"(d[61]), "+f"(d[62]), "+f"(d[63]), "+f"(d[64]), "+f"(d[65]), "+f"(d[66]), "+f"(d[67]), "+f"(d[68]), "+f"(d[69]), "+f"(d[70]), "+f"(d[71])
    : "r"(a[0]), "r"(a[1]), "r"(a[2]), "r"(a[3]), "l"(db), "r"(scaleD));
}
__device__ __forceinline__ void wgmma_rs_n64(float* d, const uint32_t* a, uint64_t db, int scaleD) {
  asm volatile("{\n.reg .pred p;\nsetp.ne.b32 p, %37, 0;\nwgmma.mma_async.sync.aligned.m64n64k16.f32.bf16.bf16 "
    "{%0,%1,%2,%3,%4,%5,%6,%7,%8,%9,%10,%11,%12,%13,%14,%15,%16,%17,%18,%19,%20,%21,%22,%23,%24,%25,%26,%27,%28,%29,%30,%31}, "
    "{%32,%33,%34,%35}, %36, p, 1, 1, 1;\n}\n"
    : "+f"(d[0]), "+f"(d[1]), "+f"(d[2]), "+f"(d[3]), "+f"(d[4]), "+f"(d[5]), "+f"(d[6]), "+f"(d[7]), "+f"(d[8]), "+f"(d[9]), "+f"(d[10]), "+f"(d[11]), "+f"(d[12]), "+f"(d[13]), "+f"(d[14]), "+f"(d[15]), "+f"(d[16]), "+f"(d[17]), "+f"(d[18]), "+f"(d[19]), "+f"(d[20]), "+f"(d[21]), "+f"(d[22]), "+f"(d[23]), "+f"(d[24]), "+f"(d[25]), "+f"(d[26]), "+f"(d[27]), "+f"(d[28]), "+f"(d[29]), "+f"(d[30]), "+f"(d[31])
    : "r"(a[0]), "r"(a[1]), "r"(a[2]), "r"(a[3]), "l"(db), "r"(scaleD));
}

template <int V> struct Int { static constexpr int value = V; };
struct Cur {
  uint32_t s, ph;
  __device__ __forceinline__ void next() { if (++s == NST) { s = 0; ph ^= 1; } }
};

__device__ __forceinline__ uint8_t* z1_block(int rb, int w, int j) { return g_Z + (rb * 16 + w * 8 + j) * ZB; }
__device__ __forceinline__ uint8_t* z2_block(int kb, int j) { return g_Z + (256 + kb * 8 + j) * ZB; }
__device__ __forceinline__ void combine8(float m0, float q0, float m1, float q1, float n, float eps, float& mean, float& rstd) {
  mean = qsum(m0 + m1) * 0.125f;
  float d0 = m0 - mean, d1 = m1 - mean;
  float M2 = qsum(q0 + q1 + n * (d0 * d0 + d1 * d1));
  rstd = rsqrtf(fmaf(M2, 0.125f / n, eps));
}
__device__ __forceinline__ void stat_get(const uint4* zs, uint32_t tag, float n, float eps, float& m0, float& r0, float& m1, float& r1) {
  uint4 a0, a1, b0, b1;
#pragma unroll 1
  for (int it = 0; it < (1 << 20); it++) {
    a0 = ll_ld128(zs); a1 = ll_ld128(zs + 64); b0 = ll_ld128(zs + 8); b1 = ll_ld128(zs + 72);
    if (__all_sync(~0u, a0.z == tag && a1.z == tag && b0.z == tag && b1.z == tag)) break;
  }
  combine8(__uint_as_float(a0.x), __uint_as_float(a0.y), __uint_as_float(a1.x), __uint_as_float(a1.y), n, eps, m0, r0);
  combine8(__uint_as_float(b0.x), __uint_as_float(b0.y), __uint_as_float(b1.x), __uint_as_float(b1.y), n, eps, m1, r1);
}

__device__ __forceinline__ void rows_fetch(uint32_t el, uint32_t xr, const uint8_t* src, uint32_t bar) {
  expect_tx_p(el, bar, 9216);
#pragma unroll 1
  for (int r = 0; r < 8; r++) bulk_load_p(el, xr + r * 1152, src + r * (DM * 4), 1152, bar);
}
__device__ __forceinline__ void rows_stats(uint32_t xr, uint4* dst, uint32_t tag, int lane) {
  float s[2] = {0.f, 0.f}, q[4] = {0.f, 0.f, 0.f, 0.f};
  const uint32_t a0 = xr + (lane >> 2) * 1152 + (((lane & 3) * 2) ^ (lane >> 2)) * 16;
  uint4 n0 = lds128(a0), n1 = lds128(a0 ^ 16);
#pragma unroll 1
  for (int e = 1; e <= 9; e++) {
    const uint32_t x[8] = {n0.x, n0.y, n0.z, n0.w, n1.x, n1.y, n1.z, n1.w};
    if (e < 9) { n0 = lds128(a0 + e * 128); n1 = lds128((a0 ^ 16) + e * 128); }
#pragma unroll
    for (int u = 0; u < 8; u++) {
      const float lo = blo(x[u]), hi = bhi(x[u]);
      s[u & 1] += lo + hi; q[(u & 1) * 2] = fmaf(lo, lo, q[(u & 1) * 2]); q[(u & 1) * 2 + 1] = fmaf(hi, hi, q[(u & 1) * 2 + 1]);
    }
  }
  const float sx = s[0] + s[1], sq = (q[0] + q[1]) + (q[2] + q[3]);
  const float m = qsum(sx) * (-1.f / DM), r = rsqrtf(fmaxf(fmaf(qsum(sq), 1.f / DM, -m * m), 0.f) + LN_EPS);
  if ((lane & 3) == 0) ll_st128(dst + (lane >> 2) * 2, m, r, tag);
}

__global__ void __cluster_dims__(2, 1, 1) __launch_bounds__(384, 1) mega_kernel(const __grid_constant__ Params P) {
  extern __shared__ __align__(1024) uint8_t smem_raw[];
  const uint32_t sb = smem_u32(smem_raw);
  const uint32_t bars = sb + SM_BAR;
  const int tid = threadIdx.x;
  int lane = tid & 31;
  const int wid = __shfl_sync(~0u, tid >> 5, 0);
  const int bid = P.role[blockIdx.x >> 1] * 2 + (blockIdx.x & 1);
  if (bid >= NCTA) return;
  const int rb = bid & 15, j = bid >> 4;
  uint4 wv[5];
  {
    const int n8 = min(tid >> 3, 26), part = n8 / 9;
    const uint8_t* src = (const uint8_t*)P.wqkv + (8 * rb + (tid & 7)) * (3 * DM * 2) + (part * (DM - 72) + 72 * j + 8 * n8) * 2;
#pragma unroll
    for (int u = 0; u < 5; u++) wv[u] = ldnc128_if(tid < 216, src + (u < 4 || rb < 8 ? u : 0) * (128 * 3 * DM * 2));
  }
  if (tid == 352) {
    for (int s = 0; s < (int)NST; s++) {
      mbar_init(bars + B_FULL + s * 8, 1); mbar_init(bars + B_EMPTY + s * 8, 16);
      mbar_init(bars + B_FULLA + s * 8, 1); mbar_init(bars + B_FULLA + 32 + s * 8, 1);
      mbar_init(bars + B_RES + s * 8, 1); mbar_init(bars + B_RT + s * 8, 1); mbar_init(bars + B_AD + s * 8, 2);
    }
    mbar_init(bars + B_IMG, 8); mbar_init(bars + B_WOI, 8); mbar_init(bars + B_GATE3, 3); mbar_init(bars + B_Z1, 1); mbar_init(bars + B_LAG, 4);
    mbar_init(bars + B_CSQ, 3); mbar_init(bars + B_RT1, 1); mbar_init(bars + B_XRW, 1); mbar_init(bars + B_XRW + 8, 1);
    for (int e = 0; e < 2 * EV_N; e++) mbar_init(bars + B_EVT + e * 8, 4);
    asm volatile("fence.mbarrier_init.release.cluster;" ::: "memory");
  }
  if (tid >= 320 && tid < 348) {
    mbar_init(bars + B_FA3 + (tid - 320) * 8, tid < 338 ? 1 : 4);
    asm volatile("fence.mbarrier_init.release.cluster;" ::: "memory");
  }
  __syncthreads();

  if (wid >= 8) {
    reg_dealloc<40>();
    const uint32_t el = elect_one();
    const uint64_t pol = policy_evict_first();
    uint32_t* const fj = g_flags + FJ + j * 32;
    if (wid == 8) {
      if (el) { prefetch_map(&P.wsp); prefetch_map(&P.win); prefetch_map(&P.win64); prefetch_map(&P.wout); prefetch_map(&P.act[1]); prefetch_map(&P.res[0]); prefetch_map(&P.res[1]); prefetch_map(&P.red); }
      const uint32_t epoch = ldcg32(fj + FJ_EP + rb);
      Cur c{0, 1};
      const uint32_t rk = bid & 1;
      uint32_t st, full;
      auto slot = [&](uint32_t bytes) {
        st = sb + c.s * ST_BYTES; full = bars + B_FULL + c.s * 8;
        mbar_wait(full, c.ph);
        expect_tx_p(el, full, bytes);
        mbar_wait(full - B_FULL + B_EMPTY, c.ph);
      };
#pragma unroll 1
      for (int L = 0; L < 2; L++) {
#pragma unroll 1
        for (int i = 0; i < 14; i++) {
          if (L == 0 && (i == 0 || i == 9)) {
            flag_wait(fj + (i ? FJ_WO : FJ_WQ), (epoch + 1) * 16);
            if (i) flag_wait(g_flags + FJ + (j ^ 1) * 32 + FJ_WO, (epoch + 1) * 16);
            fence_async_g();
            TRC(el, 2, i ? 46 : 45);
          }
          const uint32_t hb = i < 9 ? 13824 : i < 13 ? 18432 : 9216, o = ST_B + rk * (i < 9 ? 13824 : 18432);
          const uint8_t* src = i < 9 ? g_WQ + j * WQ_SL + i * 27648 + rk * 13824 : g_WO + ((j & 6) + rk) * WO_SL + (i - 9) * 18432;
          slot(2 * hb);
          bulk_mc_h(el, st + o, src, hb, full, true, pol);
          c.next();
        }
#pragma unroll 1
        for (int i = 0; i < 18; i++) {
          const int p = i >> 1, col = p == 4 ? (9 * j + ((j & 1) ? 0 : 8)) * 32 : (((9 * j + 1) >> 1) + (p < 4 ? p + 36 : p - 5)) * 64;
          if (i & 1) {
            slot(2 * ZB);
          } else {
            st = sb + c.s * ST_BYTES; full = bars + B_FULL + ((c.s + 1) & 3) * 8;
            mbar_wait(bars + B_EMPTY + c.s * 8, c.ph);
          }
          tma4d_mc(el, st + ST_B + rk * 18432, p == 4 ? &P.win : &P.win64, col, (i & 1) * 36 + rk * 18, full, pol);
          if (el && !(i & 1)) mbar_arrive(bars + B_FULL + c.s * 8);
          c.next();
        }
        TRC(el, 2, L * 16 + 6);
        flag_wait(fj + FJ_ZN + L, (epoch + 1) * 16);
        fence_async_g();
        TRC(el, 2, L * 16 + 7);
#pragma unroll 1
        for (int i = 0; i < 32; i++) {
          const uint8_t* src = z2_block(i, j) + rk * 18432;
          if (i >= 4) mbar_wait(bars + B_AD + c.s * 8, ((i >> 2) & 1) ^ 1);
          slot(ST_BYTES);
          bulk_mc_h(el, st + ST_B + rk * 18432, src, 18432, full, true, pol);
          tma3d_h(el, st, &P.wsp, i * 64, rb * 64, 0, full, true, pol);
          c.next();
        }
        mbar_wait(bars + B_Z1, L);
        fence_async_g();
#pragma unroll 1
        for (int i = 0; i < 11; i++) {
          const int cb = i - 2 + j;
          if (i < 4) mbar_wait(bars + B_AD + c.s * 8, 1);
          slot(ZB);
          if (i < 2) bulk_load_h(el, st + ST_B, z1_block(rb, i, j), ZB, full, true, pol);
          else tma2d_mc_h(el, st + ST_B + rk * 18432, &P.wout, (cb >= 9 ? cb - 9 : cb) * 64, 288 * j + rk * 144, full, true, pol);
          c.next();
        }
      }
    } else if (wid < 11) {
      int w = wid - 9;
      uint32_t* const fr = g_flags + (rb * 2 + w) * 32;
      const uint32_t epoch = ldcg32(fr + FR_EP + j);
      const uint32_t ev = bars + B_EVT + w * EV_N * 8, t8 = (epoch + 1) * 8;
      const int dp = ((j & 1) - w) * 32;
      Cur c{0, 1};
#pragma unroll 1
      for (int L = 0; L < 2; L++) {
#pragma unroll 1
        for (int ph = 0; ph < 3; ph++) {
          if (ph + L > 0) {
            uint32_t* f = fr + (ph == 0 ? FR_X2 : ph == 1 ? FR_O + L : FR_X1 + L);
            mbar_wait(ev + ph * 8, ph ? L : 0);
            TRC(el, 3, w * 32 + L * 16 + ph * 3);
            flag_release_p(el, ph == 2 ? f + dp : f);
            if (el && ph == 2) mbar_arrive(bars + B_GATE3);
            TRC(el, 3, w * 32 + L * 16 + ph * 3 + 1);
            if (ph == 1 && w == 1) {
              mbar_wait(ev - (EV_N - EV_O) * 8, L);
              expect_tx_p(el, bars + B_RES, 18432);
              tma3d_h(el, sb + SM_STG, &P.res[L], (j & 6) * 72, rb * 64, j & 1, bars + B_RES, !L, pol);
            }
            if (ph == 2) {
              if (lane < 2) mbar_arrive(bars + B_FULLA + w * 32 + ((c.s + lane) & 3) * 8);
              expect_tx_p(lane < 9, bars + B_FA3 + (9 * w + lane) * 8, 8192);
              flag_wait(f, t8);
              fence_async_g();
#pragma unroll 1
              for (int kb = 0; kb < 9; kb++) {
                const int n = 9 * w + kb;
                if (n >= 8) mbar_wait(bars + B_EA3 + (n - 8) * 8, L);
                tma3d_h(el, sb + ((n >> 1) & 3) * ST_BYTES + (n & 1) * 8192, &P.act[1], kb * 64, rb * 64, w, bars + B_FA3 + (9 * w + kb) * 8, false, pol);
                TRC(el && kb == 0, 3, w * 32 + L * 16 + ph * 3 + 2);
              }
              c.ph ^= ((c.s + 18) >> 2) & 1; c.s = (c.s + 18) & 3;
              break;
            }
            const uint32_t full = bars + B_FULLA + w * 32 + c.s * 8, dst = sb + c.s * ST_BYTES + w * 8192;
            mbar_wait(bars + B_EMPTY + c.s * 8, c.ph);
            expect_tx_p(el, full, 8192);
            flag_wait(ph == 1 ? f + dp : f, t8);
            fence_async_g();
            if (ph != 1) tma3d_h(el, dst, &P.act[1], 0, rb * 64, w, full, false, pol);
            else bulk_load_h(el, dst, z1_block(rb, j & 1, 0) + w * 8192, 8192, full, true, pol);
            c.next();
            TRC(el, 3, w * 32 + L * 16 + ph * 3 + 2);
          }
          const int n = ph == 0 ? 9 : 5;
          const uint32_t tag = epoch * 2 + L + 1;
          uint4* const xs = g_XST + (rb * 2 + w) * 128;
#pragma unroll 1
          for (int i = ph + L > 0; i < n; i++) {
            const uint32_t full = bars + B_FULLA + w * 32 + c.s * 8, dst = sb + c.s * ST_BYTES + w * 8192;
            if (ph + L == 0 && i == 4) {
              mbar_wait(bars + B_WT + w * 8, 0);
              rows_stats(sb + SM_STG + w * 9216, xs + 16 * j, tag, lane);
            }
            const bool none = ph == 1 && 2 * i + w > 8;
            mbar_wait(bars + B_EMPTY + c.s * 8, c.ph);
            expect_tx_p(el, full, none ? 0 : 8192);
            if (ph != 1) {
              tma3d_h(el, dst, &P.act[L], i * 64, rb * 64, w, full, false, pol);
            } else {
              if (!none) bulk_load_h(el, dst, z1_block(rb, j & 1, 0) + (2 * i + w) * 8192, 8192, full, true, pol);
            }
            c.next();
            if (ph + L == 0 && i == 3) rows_fetch(el, sb + SM_STG + w * 9216, P.xs[0] + (128 * rb + 16 * j + w) * (DM * 2), bars + B_WT + w * 8);
          }
          if (ph + L == 2) flag_wait(fj + FJ_P4, t8 * 4);
          if (ph == 0) {
            const uint32_t tab = sb + L * (3 * ST_BYTES) + SM_XST + w * 512 + lane * 8;
            TRC(el, 3, w * 32 + L * 16 + 13);
#pragma unroll 1
            for (int it = 0; it < (1 << 22); it++) {
              const uint4 a = ll_ld128(xs + 2 * lane), b = ll_ld128(xs + 64 + 2 * lane);
              if (__all_sync(~0u, a.z == tag && b.z == tag)) { sts64(tab, a.x, a.y); sts64(tab + 256, b.x, b.y); break; }
            }
            __syncwarp();
            if (el) mbar_arrive(bars + B_CSQ);
            TRC(el, 3, w * 32 + L * 16 + 14);
          }
        }
        asm volatile("" : "+r"(lane), "+r"(w));
        expect_tx_p(el, bars + B_WT + w * 8, 2048);
#pragma unroll 1
        for (int r = 0; r < 8; r++)
          bulk_load_p(el, sb + SM_WT + w * 2176 + r * 272, (const uint8_t*)P.w_sp + (size_t)(128 * rb + 16 * j + 2 * r + w) * (SEQ * 2) + 30 * 128, 256, bars + B_WT + w * 8);
        float cv = (lane & 3) ? 0.f : -blo(ldnc16(P.b_sp + 128 * rb + 16 * j + 2 * (lane >> 2) + w));
        mbar_wait(bars + B_RT, L);
        mbar_wait(bars + B_WT + w * 8, L ^ 1);
        mbar_wait(ev + EV_Z1 * 8, L);
        const uint32_t ro = (w * 64 + 8 * j + (lane >> 2)) * 128, x0 = ((lane & 3) * 2) ^ (lane >> 2);
#pragma unroll 1
        for (int i = 0; i < 32; i++) {
          const bool tail = (i >> 1) == 4;
          const int kb = tail ? i + 22 : i < 8 ? i : i - 2;
          if (i == 8) mbar_wait(bars + B_RT1, L);
          if (!tail) mbar_wait(bars + B_FULL + c.s * 8, c.ph ^ 1);
#pragma unroll
          for (int e = 0; e < 2; e++) {
            const uint4 a = lds128(!tail ? sb + c.s * ST_BYTES + ro + ((x0 ^ e) << 4) : sb + SM_WT + w * 2176 + (lane >> 2) * 272 + (i - 8) * 128 + (lane & 3) * 32 + e * 16);
            const uint4 m = lds128(sb + SM_RT + 4096 + kb * 128 + (lane & 3) * 32 + e * 16);
            cv = fmaf(blo(a.x), blo(m.x), fmaf(bhi(a.x), bhi(m.x), fmaf(blo(a.y), blo(m.y), fmaf(bhi(a.y), bhi(m.y), cv))));
            cv = fmaf(blo(a.z), blo(m.z), fmaf(bhi(a.z), bhi(m.z), fmaf(blo(a.w), blo(m.w), fmaf(bhi(a.w), bhi(m.w), cv))));
          }
          if (!tail) {
            __syncwarp();
            if (el) mbar_arrive(bars + B_AD + c.s * 8);
            c.next();
          }
        }
        TRC(el, 3, w * 32 + L * 16 + 11);
        uint32_t tag = t8;
        asm volatile("" : "+r"(tag));
        tag = (tag >> 2) - 1 + L;
        cv = qsum(cv);
        uint2* const cs = (uint2*)(g_XST + (rb * 2 + w) * 128 + 1);
        if ((lane & 3) == 0) ll_st64(cs + 32 * j + (lane >> 2) * 4, __float_as_uint(cv), tag);
#pragma unroll 1
        for (int it = 0; it < (1 << 22); it++) {
          const uint2 a = ll_ld64(cs + 4 * lane), b = ll_ld64(cs + 128 + 4 * lane);
          if (__all_sync(~0u, a.y == tag && b.y == tag)) { sts32(sb + SM_CV + w * 256 + lane * 4, a.x); sts32(sb + SM_CV + w * 256 + 128 + lane * 4, b.x); break; }
        }
        __syncwarp();
        if (el) mbar_arrive(bars + B_CV + w * 8);
        TRC(el, 3, w * 32 + L * 16 + 12);
#pragma unroll 1
        for (int kb = 30; kb < 32; kb++) {
          mbar_wait(bars + B_FULL + c.s * 8, c.ph ^ 1);
          if (el) mbar_arrive(bars + B_AD + c.s * 8);
          c.next();
        }
        c.ph ^= ((c.s + 11) >> 2) & 1; c.s = (c.s + 11) & 3;
        if (L == 0) {
          mbar_wait(ev + EV_P4 * 8, 0);
          flag_add_p(el, fj + FJ_P4);
        }
      }
    } else {
      const uint32_t epoch = ldcg32(fj + FJ_EP + rb);
      mbar_wait(bars + B_IMG, 0);
      TRC(el, 2, 41);
      flag_release_p(el, fj + FJ_WQ);
      TRC(el, 2, 42);
#pragma unroll 1
      for (int L = 0; L < 2; L++) {
        float* const csf = g_CSP + (NCTA + bid) * 216;
        if (L == 0) {
          flag_wait(fj + FJ_WQ, (epoch + 1) * 16);
          fence_async_g();
          expect_tx_p(el, bars + B_XRW, 13824);
          bulk_load_p(el, sb + ST_BYTES + SM_WOI, g_CSP + j * 16 * 216, 6912, bars + B_XRW);
          bulk_load_p(el, sb + 2 * ST_BYTES + SM_WOI, g_CSP + (j * 16 + 8) * 216, 6912, bars + B_XRW);
          mbar_wait(bars + B_XRW, 0);
#pragma unroll 1
          for (int f = lane; f < 54; f += 32) {
            float s[4] = {0.f, 0.f, 0.f, 0.f};
#pragma unroll 4
            for (int r = 0; r < 16; r++) {
              const uint4 v = lds128(sb + ST_BYTES + SM_WOI + (r >> 3) * ST_BYTES + (r & 7) * 864 + f * 16);
              s[0] += __uint_as_float(v.x); s[1] += __uint_as_float(v.y); s[2] += __uint_as_float(v.z); s[3] += __uint_as_float(v.w);
            }
            sts128(sb + SM_CSQ + f * 16, __float_as_uint(s[0]), __float_as_uint(s[1]), __float_as_uint(s[2]), __float_as_uint(s[3]));
            stg128(csf + f * 4, __float_as_uint(s[0]), __float_as_uint(s[1]), __float_as_uint(s[2]), __float_as_uint(s[3]));
          }
          __syncwarp();
          if (el) mbar_arrive(bars + B_CSQ);
        } else {
#pragma unroll 1
          for (int u = 0; u < 4; u++) {
            const int w = u & 1;
            if (u < 2) {
              flag_wait(g_flags + (rb * 2 + w) * 32 + FR_X2, (epoch + 1) * 8);
              fence_async_g();
              TRC(el, 2, 48 + u);
              rows_fetch(el, sb + SM_STG + w * 9216, P.xs[1] + (128 * rb + 16 * j + w) * (DM * 2), bars + B_XRW + w * 8);
            } else {
              mbar_wait(bars + B_XRW + w * 8, w ^ 1);
              TRC(el, 2, 48 + u);
              rows_stats(sb + SM_STG + w * 9216, g_XST + (rb * 2 + w) * 128 + 16 * j, epoch * 2 + 2, lane);
              TRC(el, 2, 50 + u);
            }
          }
          expect_tx_p(el, bars + B_CSQ, 864);
          bulk_load_p(el, sb + 3 * ST_BYTES + SM_CSQ, csf, 864, bars + B_CSQ);
        }
        if (L == 0) {
          TRC(el, 2, 43);
          mbar_wait(bars + B_WOI, 0);
          bulk_store_p(el, g_WO + j * WO_SL + rb * (41 * 128), sb + SM_WOI, (rb < 15 ? 41 : 33) * 128);
          publish_p(el, fj + FJ_WO);
          TRC(el, 2, 44);
          if (el) prefetch_l2((const uint8_t*)P.w_in + bid * 41472, 41472);
          uint4 y[4];
#pragma unroll
          for (int u = 0; u < 4; u++) y[u] = ldnc128((u < 2 ? (const uint8_t*)P.w_in + (100 + 300 * u) * (2 * FH * 2) + (FH + 1024 * u) * 2 : (const uint8_t*)P.w_sp + (1000 * u - 1500) * (SEQ * 2) + u * 1024) + lane * 16);
          float sq[2] = {0.f, 0.f};
#pragma unroll
          for (int u = 0; u < 4; u++) {
            const uint32_t x[4] = {y[u].x, y[u].y, y[u].z, y[u].w};
#pragma unroll
            for (int e = 0; e < 4; e++) sq[u >> 1] = fmaf(blo(x[e]), blo(x[e]), fmaf(bhi(x[e]), bhi(x[e]), sq[u >> 1]));
          }
          const float o0 = sqrtf(wsum(sq[0]) * (2.f * GA * GA * DM / 512.f)), o1 = sqrtf(wsum(sq[1]) * (C0S * C0S * SEQ / 512.f));
          const uint32_t off = (__float_as_uint(o0) & 0x7f800000u) >> 16 | 0x8000u | OFM;
          if (el) sts64(sb + SM_OFF, off * 0x10001u, min(__float_as_uint(o1) & 0x7f800000u, 0x7e000000u) | 0x00400000u);
        }
        if (el) mbar_arrive(bars + B_GATE3);
        const uint32_t tag = epoch * 2 + L + 1;
        asm volatile("" : "+r"(lane));
        mbar_wait(bars + B_EVT + EV_ZN * 8, L);
        mbar_wait(bars + B_EVT + (EV_N + EV_ZN) * 8, L);
        flag_release_p(el, fj + FJ_ZN + L);
        TRC(el, 2, L * 16 + 8);
        {
          uint4 v[4];
#pragma unroll 1
          for (int it = 0; it < (1 << 22); it++) {
            bool ok = true;
#pragma unroll
            for (int u = 0; u < 4; u++) { v[u] = ll_ld128(g_ZST + (rb * 2 + ((lane >> 1) & 1)) * 512 + ((lane & 1) * 4 + u) * 64 + 8 * j + (lane >> 2)); ok = ok && v[u].z == tag; }
            if (__all_sync(~0u, ok)) break;
          }
          float mean = __uint_as_float(v[0].x) + __uint_as_float(v[1].x) + __uint_as_float(v[2].x) + __uint_as_float(v[3].x), M2 = 0.f;
          mean = (mean + __shfl_xor_sync(~0u, mean, 1)) * 0.125f;
#pragma unroll
          for (int u = 0; u < 4; u++) { const float d = __uint_as_float(v[u].x) - mean; M2 += fmaf(288.f * d, d, __uint_as_float(v[u].y)); }
          M2 += __shfl_xor_sync(~0u, M2, 1);
          const float rs = blo(pack2(rsqrtf(fmaf(M2, 1.f / FH, 4.f * GA * GA * LN_EPS)), 0.f));
          if (!(lane & 1)) ll_st64(g_RT + 128 * rb + 16 * j + (lane >> 1), pack2(rs, rs * mean), tag);
        }
        TRC(el, 2, L * 16 + 10);
#pragma unroll 1
        for (int b = 0; b < 8; b++) {
          uint4 v[4];
#pragma unroll 1
          for (int it = 0; it < (1 << 22); it++) {
            bool ok = true;
#pragma unroll
            for (int u = 0; u < 4; u++) { v[u] = ll_ld128((const uint4*)g_RT + b * 128 + u * 32 + lane); ok = ok && v[u].y == tag && v[u].w == tag; }
            if (__all_sync(~0u, ok)) break;
          }
#pragma unroll
          for (int u = 0; u < 4; u++) {
            const uint32_t rt = sb + SM_RT + b * 512 + u * 128, ro = (lane >> 3) * 32 + (lane & 3) * 8 + ((lane >> 2) & 1) * 2;
            sts32(rt + 4096 + lane * 4, __byte_perm(v[u].x, v[u].z, 0x7632));
            asm volatile("st.shared.u16 [%0], %1;\nst.shared.u16 [%0 + 4], %2;" ::"r"(rt + ro), "h"((uint16_t)v[u].x), "h"((uint16_t)v[u].z) : "memory");
          }
          __syncwarp();
          if (el && (b == 1 || b == 7)) mbar_arrive(bars + (b == 1 ? B_RT : B_RT1));
          TRC(el && b < 2, 2, L * 16 + 11 + b);
        }
        TRC(el, 2, L * 16 + 9);
        mbar_wait(bars + B_EVT + EV_Z1 * 8, L);
        mbar_wait(bars + B_EVT + (EV_N + EV_Z1) * 8, L);
        fence_gpu();
        if (el) mbar_arrive(bars + B_Z1);
      }
    }
  } else {
    reg_alloc<232>();
    const int w = wid >> 2, q = wid & 3;
    int g = lane >> 2, t = lane & 3;
    const uint32_t ev = bars + B_EVT + w * EV_N * 8;
    const bool tr = (tid & 127) == 0;
    (void)tr;
    Cur c{0, 0};
    const uint32_t ebar = mapa(bars + B_EMPTY, (bid & 1) ^ (lane & 1));
    auto release = [&](uint32_t s) { if (lane < 2) mbar_arrive_cluster(ebar + s * 8); };
    const uint32_t stg = sb + SM_STG + w * 9216;
    uint32_t ia = 0;
    auto wait_ab = [&]() { mbar_wait_c(bars + B_FULL + c.s * 8, c.ph); mbar_wait_c(bars + B_FULLA + w * 32 + c.s * 8, (ia >> 2) & 1); ia++; };
    uint32_t lagph = 0;
    auto yield = [&](int left, int lag) { if (w == 1 && left == lag) mbar_wait_c(bars + B_LAG, lagph); };
    auto yield_done = [&]() { if (w == 0 && lane == 0) mbar_arrive(bars + B_LAG); };
    auto signal = [&](int e) { __syncwarp(); if (lane == 0) mbar_arrive(ev + e * 8); };
    TRC(tr, w, 0);

    {
      uint8_t* dst = g_WQ + j * WQ_SL + rb * 3456 + tid * 16;
#pragma unroll
      for (int u = 0; u < 5; u++) {
        stg128_if((u < 4 || rb < 8) && tid < 216, dst + u * (16 * 3456), wv[u].x, wv[u].y, wv[u].z, wv[u].w);
        if (u == 0) TRC(tr, w, 60);
      }
      if (P.zero == 0) {
        float s[8];
#pragma unroll
        for (int e = 0; e < 8; e++) s[e] = 0.f;
#pragma unroll
        for (int u = 0; u < 5; u++) {
          const bool on = u < 4 || rb < 8;
          const uint32_t x[4] = {wv[u].x, wv[u].y, wv[u].z, wv[u].w};
#pragma unroll
          for (int e = 0; e < 4; e++) { s[2 * e] += on ? blo(x[e]) : 0.f; s[2 * e + 1] += on ? bhi(x[e]) : 0.f; }
        }
#pragma unroll
        for (int m = 4; m; m >>= 1) {
#pragma unroll
          for (int e = 0; e < m; e++) s[e] = ((tid & m) ? s[e + m] : s[e]) + __shfl_xor_sync(~0u, (tid & m) ? s[e] : s[e + m], m);
        }
        stg32_if(tid < 216, g_CSP + bid * 216 + tid, __float_as_uint(s[0]));
      }
      __syncwarp();
      if (lane == 0) mbar_arrive(bars + B_IMG);
    }
    auto fetch_wo = [&]() {
#pragma unroll 1
      for (int u = tid; u < 328; u += 256) {
        const int m = min(41 * rb + (u >> 3), 647), k8 = m / 9;
        cp_async16(sb + SM_WOI + u * 16, (const uint8_t*)P.wo + (8 * k8 + (u & 7)) * (DM * 2) + (72 * j + 8 * (m - k8 * 9)) * 2);
      }
    };
    const uint32_t epoch = ldcg32(g_flags + (rb * 2 + w) * 32 + FR_EP + j);
    TRC(tr, w, 1);

#pragma unroll 1
    for (int L = 0; L < 2; L++) {
      const int tb = 2 + L * 24;
      asm volatile("" : "+r"(lane), "+r"(g), "+r"(t));
      (void)tb;
      ia = 0;
      const uint32_t tag = epoch * 2 + L + 1;
      uint32_t aoff = (w * 64 + q * 16 + (lane & 15)) * 128 + (((lane >> 4) ^ (lane & 7)) << 4);
      {
        uint32_t Pk[27][2];
        float sc0, sc1;
        const uint32_t att = stg + 2 * q * 128 + lane * 4;
        uint4* hp = g_HALO + ((((rb - (q == 0)) * 2 + w) * 8 + j) * 6) * 32 + lane;
        uint8_t* od = z1_block(rb, w, 0) + (9 * j) * 1024 + (2 * q) * 128 + lane * 4;
        ACLK_INIT;
        {
          float acc[108];
#pragma unroll
          for (int i = 0; i < 108; i++) acc[i] = 0.f;
          uint32_t prev = 0;
#pragma unroll 1
          for (int kb = 0; kb < 9; kb++) {
            wait_ab();
            yield(9 - kb, LAG1);
            TRC(tr && kb == 0, w, tb + 0);
            PCLK(kb * 4);
            const uint32_t st = sb + c.s * ST_BYTES, da = dlo(st + w * 8192, 16), db = dlo(st + ST_B, 3456);
            wgmma_fence();
#pragma unroll
            for (int kk = 0; kk < 4; kk++) {
              wgmma_ss_n216(acc, dsc<1024, 1>(da, kk * 32), dsc<128, 0>(db, kk * 6912), 1);
              if (kk == 0) { wgmma_commit(); wgmma_wait<1>(); if (kb > 0) release(prev); }
            }
            wgmma_commit();
            if (kb == 8) yield_done();
            PCLK(kb * 4 + 1);
            if (kb == 0 && L == 0) fetch_wo();
            if (kb == 3 && L == 0) {
              asm volatile("cp.async.wait_all;" ::: "memory");
              fence_async_s();
              __syncwarp();
              if (lane == 0) mbar_arrive(bars + B_WOI);
            }
            PCLK(kb * 4 + 2);
            PCLK(kb * 4 + 3);
            prev = c.s; c.next();
          }
          const uint32_t cs = sb + prev * ST_BYTES + SM_CSQ + t * 8;
          mbar_wait_c(bars + B_CSQ, L);
          const float2 n0 = lds64f(sb + prev * ST_BYTES + SM_XST + w * 512 + (16 * q + g) * 8), n1 = lds64f(sb + prev * ST_BYTES + SM_XST + w * 512 + (16 * q + g + 8) * 8);
          const float m0 = n0.x, r0 = n0.y, m1 = n1.x, r1 = n1.y;
          float2 cv[27];
#pragma unroll
          for (int G = 0; G < 27; G++) cv[G] = lds64f(cs + G * 32);
          PCLK(36);
          wgmma_wait<0>();
          PCLK(37);
          release(prev);
          lagph ^= 1;
          TRC(tr, w, tb + 1);
          ACLK(0);
#pragma unroll
          for (int G = 9; G < 27; G++) Pk[G][1] = pack2(fmaf(m1, cv[G].x, acc[4 * G + 2]) * r1, fmaf(m1, cv[G].y, acc[4 * G + 3]) * r1);
          if (q < 3) {
#pragma unroll
            for (int i = 0; i < 18; i++) sts32(att + 256 + (i >> 1) * 1024 + (i & 1) * 128, Pk[9 + i][1]);
          } else if (rb < 15) {
#pragma unroll
            for (int i = 0; i < 6; i++) ll_st128(hp + i * 32, __uint_as_float(Pk[9 + 3 * i][1]), __uint_as_float(Pk[10 + 3 * i][1]), tag, __uint_as_float(Pk[11 + 3 * i][1]));
          }
#pragma unroll
          for (int G = 0; G < 27; G++) {
            if (G < 9) {
              Pk[G][0] = pack2(fmaf(m0, cv[G].x, acc[4 * G]), fmaf(m0, cv[G].y, acc[4 * G + 1]));
              Pk[G][1] = pack2(fmaf(m1, cv[G].x, acc[4 * G + 2]), fmaf(m1, cv[G].y, acc[4 * G + 3]));
            } else {
              Pk[G][0] = pack2(fmaf(m0, cv[G].x, acc[4 * G]) * r0, fmaf(m0, cv[G].y, acc[4 * G + 1]) * r0);
            }
          }
          sc0 = r0 * (0.23570226039551584f * 1.4426950408889634f); sc1 = r1 * (0.23570226039551584f * 1.4426950408889634f);
        }
        ACLK(1);
        constexpr int GA_[4] = {0, 2, 4, 7}, GB_[4] = {1, 3, 5, 8}, GC_[4] = {2, 4, 6, 6};
        float S1[4][4], S2[4][4];
        uint32_t qa[4][2], qc[4][2];
#pragma unroll
        for (int h = 0; h < 4; h++) {
#pragma unroll
          for (int r = 0; r < 2; r++) {
            qa[h][r] = (h == 0 || h == 3 || t >= h) ? Pk[GA_[h]][r] : 0u;
            qc[h][r] = (h == 3 ? t == 3 : t <= h) ? Pk[GC_[h]][r] : 0u;
          }
#pragma unroll
          for (int i = 0; i < 4; i++) S1[h][i] = S2[h][i] = 0.f;
          mma16(S1[h], qa[h][0], qa[h][1], Pk[GB_[h]][0], Pk[GB_[h]][1], Pk[9 + GA_[h]][0], Pk[9 + GB_[h]][0]);
          mma16(S2[h], qa[h][0], qa[h][1], Pk[GB_[h]][0], Pk[GB_[h]][1], Pk[9 + GA_[h]][1], Pk[9 + GB_[h]][1]);
        }
#pragma unroll
        for (int h = 0; h < 4; h++) {
          mma8(S1[h], qc[h][0], qc[h][1], Pk[9 + GC_[h]][0]);
          mma8(S2[h], qc[h][0], qc[h][1], Pk[9 + GC_[h]][1]);
        }
        uint32_t V1[9], V2[9];
#pragma unroll
        for (int i = 0; i < 9; i++) { V1[i] = movm(Pk[18 + i][0]); V2[i] = movm(Pk[18 + i][1]); }
        const bool remote = q == 0 && rb > 0;
        uint4 hv[6];
#pragma unroll
        for (int i = 0; i < 6; i++) hv[i] = make_uint4(0u, 0u, tag, 0u);
        if (remote) {
#pragma unroll
          for (int i = 0; i < 6; i++) hv[i] = ll_ld128(hp + i * 32);
        }
        const bool up0 = 2 * t > g, up1 = 2 * t + 1 > g;
        const uint32_t mup = (up0 ? 0xffffu : 0u) | (up1 ? 0xffff0000u : 0u);
        auto finish = [&](const float (&x0)[4], const float (&x1)[4], const uint32_t (&Va)[9], const uint32_t (&Vb)[9], int hi) {
          uint32_t p[4];
          float rs[4];
#pragma unroll
          for (int h = 0; h < 4; h++) {
            const float m = qmax(fmaxf(x0[h], x1[h]));
            p[h] = pack2(ex2(x0[h] - m), ex2(x1[h] - m));
            rs[h] = rcp_fast(qsum(blo(p[h]) + bhi(p[h])));
          }
#pragma unroll
          for (int i = 0; i < 9; i++) {
            const int h = 4 * i / 9;
            const bool split = i == 2 || i == 4 || i == 6, nx = split && 2 * t >= i;
            float O[4] = {0.f, 0.f, 0.f, 0.f}, N[4] = {0.f, 0.f, 0.f, 0.f};
            mma16(O, p[h] & mup, 0u, p[h] & ~mup, 0u, Va[i], Vb[i]);
            if (split) mma16(N, p[h + 1] & mup, 0u, p[h + 1] & ~mup, 0u, Va[i], Vb[i]);
            const float r = nx ? rs[h + (split ? 1 : 0)] : rs[h];
            stg32(od + i * 1024 + hi * 128, pack2((nx ? N[0] : O[0]) * r, (nx ? N[1] : O[1]) * r));
          }
        };
        {
          float x0[4], x1[4];
#pragma unroll
          for (int h = 0; h < 4; h++) { x0[h] = (up0 ? S1[h][2] : S2[h][2]) * sc1; x1[h] = (up1 ? S1[h][3] : S2[h][3]) * sc1; }
          finish(x0, x1, V1, V2, 1);
        }
        ACLK(2);
        bar_sync(1 + w, 128);
        uint32_t H[18];
        if (q > 0) {
#pragma unroll
          for (int i = 0; i < 18; i++) H[i] = lds32(att + (i >> 1) * 1024 + (i & 1) * 128);
        } else {
#pragma unroll 1
          for (int it = 0; it < (1 << 20); it++) {
            bool ok = true;
#pragma unroll
            for (int i = 0; i < 6; i++) ok = ok && hv[i].z == tag;
            if (__all_sync(~0u, ok)) break;
#pragma unroll
            for (int i = 0; i < 6; i++) hv[i] = ll_ld128(hp + i * 32);
          }
#pragma unroll
          for (int i = 0; i < 6; i++) { H[3 * i] = hv[i].x; H[3 * i + 1] = hv[i].y; H[3 * i + 2] = hv[i].w; }
        }
        float S0[4][4];
#pragma unroll
        for (int h = 0; h < 4; h++) {
#pragma unroll
          for (int i = 0; i < 4; i++) S0[h][i] = 0.f;
          mma16(S0[h], qa[h][0], 0u, Pk[GB_[h]][0], 0u, H[GA_[h]], H[GB_[h]]);
        }
#pragma unroll
        for (int h = 0; h < 4; h++) mma8(S0[h], qc[h][0], 0u, H[GC_[h]]);
        uint32_t V0[9];
#pragma unroll
        for (int i = 0; i < 9; i++) V0[i] = movm(H[9 + i]);
        ACLK(3);
        {
          const bool nohalo = (rb | q) == 0;
          float x0[4], x1[4];
#pragma unroll
          for (int h = 0; h < 4; h++) {
            x0[h] = up0 && nohalo ? -INFINITY : (up0 ? S0[h][0] : S1[h][0]) * sc0;
            x1[h] = up1 && nohalo ? -INFINITY : (up1 ? S0[h][1] : S1[h][1]) * sc0;
          }
          finish(x0, x1, V0, V1, 0);
        }
        ACLK(4);
        signal(EV_O);
        ACLK_OUT;
        TRC(tr, w, tb + 2);
      }
      {
        float acc[36];
        const int hw = rb * 2 + (j & 1), js = (j & 6) + w;
        const uint32_t xt = sb + SM_STG + (16 * q + g) * 288 + w * 144 + t * 4;
        uint32_t xm = sb + SM_STG + (16 * q + (lane & 15)) * 288 + (((9 * w + (lane >> 4)) ^ ((lane >> 2) & 1)) << 4), xl = sb + SM_STG + (2 * q + w) * 2304 + lane * 16;
        uint8_t* xd[5];
#pragma unroll
        for (int u = 0; u < 5; u++) {
          const int row = ((u * 32 + lane) * 57) >> 10;
          xd[u] = P.xs[1] + (128 * rb + 32 * q + 16 * w + (j & 1)) * (DM * 2) + (j & 6) * 144 + row * (DM * 4 - 288) + u * 512 + ((lane ^ (row >> 2)) << 4);
          asm volatile("" : "+l"(xd[u]));
        }
        asm volatile("" : "+r"(xm), "+r"(xl));
        mbar_wait_c(bars + B_RES, L);
        TRC(tr, w, tb + 21);
#pragma unroll
        for (int i = 0; i < 18; i++) { const uint32_t x = lds32(xt + (i >> 1) * 16 + (i & 1) * 2304); acc[2 * i] = blo(x); acc[2 * i + 1] = bhi(x); asm volatile("" : "+f"(acc[2 * i]), "+f"(acc[2 * i + 1])); }
        uint32_t prev = 0;
#pragma unroll 1
        for (int u = 0; u < 5; u++) {
          const uint32_t st = sb + c.s * ST_BYTES, da = dlo(st, 1024), db = dlo(st + ST_B + w * 18432, 1152);
          mbar_wait_c(bars + B_FULL + c.s * 8, c.ph); mbar_wait_c(bars + B_FULLA + c.s * 8, (ia >> 2) & 1);
          TRC(tr && u == 0, w, tb + 3);
          wgmma_fence();
#pragma unroll
          for (int kk = 0; kk < 4; kk++) wgmma_ss_n72(acc, dsc<128, 0>(da, kk * 2048), dsc<128, 0>(db, kk * 2304), 1);
          wgmma_commit();
          wgmma_wait<1>();
          if (u > 0) release(prev);
          mbar_wait_c(bars + B_FULLA + 32 + c.s * 8, (ia >> 2) & 1);
          ia++;
          if (u == 4) break;
          wgmma_fence();
#pragma unroll
          for (int kk = 4; kk < 8; kk++) wgmma_ss_n72(acc, dsc<128, 0>(da, kk * 2048), dsc<128, 0>(db, kk * 2304), 1);
          wgmma_commit();
          prev = c.s; c.next();
        }
        RCLK_INIT;
        wgmma_wait<0>();
        RCLK(0);
        release(c.s);
        c.next();
        TRC(tr && P5TRACE != 5, w, tb + 4);
#pragma unroll
        for (int u = 0; u < 4; u++)
          stsm4(xm + u * 32, pack2(acc[8 * u], acc[8 * u + 1]), pack2(acc[8 * u + 2], acc[8 * u + 3]), pack2(acc[8 * u + 4], acc[8 * u + 5]), pack2(acc[8 * u + 6], acc[8 * u + 7]));
        asm volatile("stmatrix.sync.aligned.m8n8.x2.shared.b16 [%0], {%1,%2};" ::"r"(xm + 128), "r"(pack2(acc[32], acc[33])), "r"(pack2(acc[34], acc[35])) : "memory");
        RCLK(1);
        bar_sync(8 + q, 64);
        RCLK(2);
#pragma unroll
        for (int u = 0; u < 5; u++) {
          const uint4 v = lds128(xl + u * 512);
          stg128_if(u < 4 || lane < 16, xd[u], v.x, v.y, v.z, v.w);
        }
        RCLK(3);
        signal(EV_X1);
        RCLK(4);
        if (P.zero == 0) {
          float s0 = 0.f, s1 = 0.f, q0 = 0.f, q1 = 0.f;
#pragma unroll
          for (int i = 0; i < 36; i++) {
            if (i & 2) { s1 += acc[i]; q1 = fmaf(acc[i], acc[i], q1); } else { s0 += acc[i]; q0 = fmaf(acc[i], acc[i], q0); }
          }
          s0 = qsum(s0); s1 = qsum(s1); q0 = qsum(q0); q1 = qsum(q1);
          const float ss = t ? s1 : s0, m = ss * (1.f / 72.f);
          ll_st128_if(t < 2, g_ST1 + (hw * 8 + js) * 64 + 16 * q + 8 * t + g, m, fmaxf((t ? q1 : q0) - ss * m, 0.f), tag);
        }
        RCLK(5);
        TRC(tr, w, tb + 5);
        RCLK(6);
        RCLK_OUT;
      }
      {
        uint32_t xA[36][4];
        float acc[32];
        uint32_t s0, jump;
        uint64_t db;
        auto bwait = [&](uint32_t dhi) {
          s0 = c.s;
          c.next();
          mbar_wait_c(bars + B_FULL + c.s * 8, c.ph);
          db = dsc2(dlo(sb + s0 * ST_BYTES + ST_B, 512), 0, dhi + P.zero); jump = (c.s - s0) * (ST_BYTES >> 4) - 17 * 128;
        };
        auto mma = [&](int kk, int pp, bool hand) {
          wgmma_rs_n64(acc, xA[kk], db, kk != 0);
          dadd(db, kk == 17 ? jump : 128 + P.zero);
          if (kk == pp && hand) bar_arrive(7 - w, 256);
          if (kk == 17 || kk == 35) wgmma_commit();
          if (kk == 21) { wgmma_commit(); wgmma_wait<1>(); release(s0); }
        };
        {
          bwait(0x40000040u);
          mbar_wait_c(bars + B_GATE3, L);
          float mean0, mean1, rs0, rs1;
          stat_get(g_ST1 + ((rb * 2 + w) * 8 + 2 * t) * 64 + 16 * q + g, tag, 72.f, LN_EPS, mean0, rs0, mean1, rs1);
          const uint32_t ns0 = pack2(GA * rs0, GA * rs0), ns1 = pack2(GA * rs1, GA * rs1);
          const uint32_t nb0 = pack2(-mean0 * blo(ns0), -mean0 * blo(ns0)), nb1 = pack2(-mean1 * blo(ns1), -mean1 * blo(ns1));
          const uint32_t al = sb + (aoff & 8191);
#pragma unroll
          for (int kb = 0; kb < 9; kb++) {
            mbar_wait_c(bars + B_FA3 + (9 * w + kb) * 8, L);
            TRC(tr && kb == 0, w, tb + 6);
            if (kb == 0) SCLK(0);
            QCLK(kb);
            const uint32_t at = al + (w ? (((kb + 1) >> 1) & 3) * ST_BYTES + ((kb + 1) & 1) * 8192 : ((kb >> 1) & 3) * ST_BYTES + (kb & 1) * 8192);
#pragma unroll
            for (int kk = 4 * kb; kk < 4 * kb + 4; kk++) ldsm4(xA[kk], at ^ ((kk & 3) << 5));
            if (lane == 0 && (kb == 0 || w == 0)) mbar_arrive(bars + B_EA3 + (9 * w + kb) * 8);
            if (kb) { wgmma_fence(); mma(4 * kb - 2, PP30, w); mma(4 * kb - 1, PP30, w); }
#pragma unroll
            for (int kk = 4 * kb; kk < 4 * kb + 4; kk++) {
#pragma unroll
              for (int e = 0; e < 4; e++) xA[kk][e] = hfma2(xA[kk][e], (e & 1) ? ns1 : ns0, (e & 1) ? nb1 : nb0);
            }
            wgmma_fence();
            mma(4 * kb, PP30, w); mma(4 * kb + 1, PP30, w);
          }
          mma(34, PP30, w); mma(35, PP30, w);
        }
        const uint32_t off2 = lds32(sb + SM_OFF);
        uint8_t* z1d = z1_block(rb, w, j) + (tid & 127) * 16;
        uint8_t* zd = z2_block(2 * rb + (q >> 1), j) + (4 * (q & 1) + w) * 4608 + ((g & 3) * 2 + (g >> 2)) * 16 + t * 4;
        float sm[2] = {0.f, 0.f}, qq[2] = {0.f, 0.f};
        auto gelu = [&](auto nz2) {
          constexpr int NZ2 = nz2.value, R = 8 - NZ2, D = NZ2 == 8 ? GM2 : NZ2 ? GMM : GM1;
          float th[32], gb = GB;
          uint32_t qa = 0, qb = 0;
          auto head = [&](int G) {
#pragma unroll
            for (int e = 0; e < 4; e++) { const float v = acc[4 * G + e]; th[4 * G + e] = tanh_fast(v * fmaf(v, v, gb)); }
          };
#pragma unroll
          for (int i = 0; i < D; i++) head((i + R) & 7);
#pragma unroll
          for (int i = 0; i < 8; i++) {
            const int G = (i + R) & 7;
            if (i + D < 8) head((i + D + R) & 7);
            float* z = acc + 4 * G;
#pragma unroll
            for (int e = 0; e < 4; e++) z[e] = fmaf(z[e], th[4 * G + e], z[e]);
            uint32_t pa = pack2(z[0], z[1]), pb = pack2(z[2], z[3]), tok;
            if (i < NZ2) {
#pragma unroll
              for (int e = 0; e < 4; e++) { sm[e >> 1] += z[e]; qq[e >> 1] = fmaf(z[e], z[e], qq[e >> 1]); }
              pa = hsub2(pa, off2); pb = hsub2(pb, off2);
              stg32(zd + i * 128, pa); stg32(zd + i * 128 + 9216, pb);
              tok = pa ^ pb ^ __float_as_uint(fmaf(sm[0], sm[1], qq[0]) + qq[1]);
            } else {
              if (G & 1) stg128(z1d + (G >> 1) * 2048 + (NZ2 ? 32768 : 0), qa, qb, pa, pb);
              qa = pa; qb = pb;
              tok = pa ^ pb;
            }
            gb = __uint_as_float(tok * P.zero + __float_as_uint(GB));
          }
        };
#pragma unroll 1
        for (int p = 0;; p++) {
          wgmma_wait<0>();
          release(c.s);
          c.next();
          TRC(tr && p == 4, w, tb + 7);
          TRC(tr && p == 8, w, tb + 11);
          SCLK(2 * p + 1);
          QCLK(10 + 3 * p);
          if (p < 4) {
            gelu(Int<8>{});
            zd += 1024;
          } else if (p == 4) {
            gelu(Int<4>{});
            signal(EV_ZN);
            const float a0 = qsum(sm[0]), a1 = qsum(sm[1]), q0 = qsum(qq[0]), q1 = qsum(qq[1]);
            const float ss = t ? a1 : a0, m = ss * (1.f / 288.f);
            ll_st128_if(t < 2, g_ZST + (rb * 2 + w) * 512 + j * 64 + 16 * q + 8 * t + g, m - blo(off2), fmaxf((t ? q1 : q0) - ss * m, 0.f), tag);
            TRC(tr, w, tb + 8);
            TRC(tr, w, tb + 9);
          } else {
            gelu(Int<0>{});
            z1d += 8192;
          }
          SCLK(2 * p + 2);
          QCLK(11 + 3 * p);
          if (p == 8) break;
          bwait(p == 3 ? 0x80000040u : 0x40000040u);
          bar_sync(6 + w, 256);
          TRC(tr && p == 4, w, tb + 10);
          wgmma_fence();
#pragma unroll
          for (int kk = 0; kk < 36; kk++) mma(kk, PP3, w == 0 || p < 7);
        }
        signal(EV_Z1);
        TRC(tr, w, tb + 12);
      }
      uint32_t hA[18][4];
      {
        float acc[144];
        const float c0 = __uint_as_float(lds32(sb + SM_OFF + 4));
#pragma unroll
        for (int i = 0; i < 144; i++) {
          asm volatile("fma.rn.f32 %0, %1, %2, %3;" : "=f"(acc[i]) : "f"(__uint_as_float(P.zero)), "f"((float)(i + 2)), "f"(c0));
        }
        uint32_t prev = 0;
        auto stage = [&](int kb) {
          mbar_wait_c(bars + B_FULL + c.s * 8, c.ph);
          TRC(tr && kb == 0, w, tb + 13);
          SCLK(22 + kb);
          const uint32_t st = sb + c.s * ST_BYTES, rt = sb + SM_RT + kb * 128 + t * 8;
          uint64_t db = dsc2(dlo(st + ST_B, 4608), 0, 8 + P.zero);
          uint32_t a[4][4];
#pragma unroll
          for (int kk = 0; kk < 4; kk++) {
            uint32_t r[4];
            ldsm4(r, st + (aoff ^ (kk << 5)));
            const uint2 sc = lds64(rt + kk * 32);
            a[kk][0] = hmul2(__byte_perm(r[0], r[2], 0x5410), sc.x); a[kk][2] = hmul2(__byte_perm(r[0], r[2], 0x7632), sc.y);
            a[kk][1] = hmul2(__byte_perm(r[1], r[3], 0x5410), sc.x); a[kk][3] = hmul2(__byte_perm(r[1], r[3], 0x7632), sc.y);
          }
          wgmma_fence();
#pragma unroll
          for (int i = 0; i < 8; i++) {
            const int kk = i & 3, hf = i >> 2;
            wgmma_rs_n144(acc + hf * 72, a[kk], db, 1);
            dadd(db, i == 3 ? 144 - 3 * 576 : 576 + P.zero);
            if (i == 0) { wgmma_commit(); wgmma_wait<1>(); if (kb) release(prev); }
            if (i == 3) wgmma_commit();
          }
          wgmma_commit();
          prev = c.s; c.next();
        };
        mbar_wait_c(bars + B_RT, L);
#pragma unroll 1
        for (int kb = 0; kb < 32; kb += 2) {
          if (kb == 8) mbar_wait_c(bars + B_RT1, L);
          stage(kb);
          stage(kb + 1);
        }
        HCLK(0);
        mbar_wait_c(bars + B_CV + w * 8, L);
        HCLK(1);
        const float gk = 0.5f / GA;
        const float c1 = __uint_as_float(lds32(sb + SM_OFF + 4));
        const float gb0 = -gk * (c1 + __uint_as_float(lds32(sb + SM_CV + w * 256 + (16 * q + g) * 4))), gb1 = -gk * (c1 + __uint_as_float(lds32(sb + SM_CV + w * 256 + (16 * q + g + 8) * 4)));
        if (w == 1) { mbar_wait_c(bars + B_FULL + c.s * 8, c.ph); release(c.s); c.next(); }
        mbar_wait_c(bars + B_FULL + c.s * 8, c.ph);
        HCLK(2);
        const uint32_t zs = sb + c.s * ST_BYTES + ST_B + (tid & 127) * 16;
#pragma unroll
        for (int u = 0; u < 18; u++) {
          if (u == 0) { wgmma_wait<1>(); HCLK(3); }
          if (u == 9) {
            HCLK(4);
            wgmma_wait<0>();
            HCLK(5);
            release(prev);
            if (L == 0) signal(EV_P4);
            TRC(tr, w, tb + 14);
            SCLK(54);
          }
          const uint4 z = lds128(zs + u * 2048);
          hA[u][0] = hmul2(z.x, pack2(fmaf(acc[8 * u], gk, gb0), fmaf(acc[8 * u + 1], gk, gb0)));
          hA[u][1] = hmul2(z.y, pack2(fmaf(acc[8 * u + 2], gk, gb1), fmaf(acc[8 * u + 3], gk, gb1)));
          hA[u][2] = hmul2(z.z, pack2(fmaf(acc[8 * u + 4], gk, gb0), fmaf(acc[8 * u + 5], gk, gb0)));
          hA[u][3] = hmul2(z.w, pack2(fmaf(acc[8 * u + 6], gk, gb1), fmaf(acc[8 * u + 7], gk, gb1)));
        }
        __syncwarp();
        release(c.s);
        c.next();
        if (w == 0) { mbar_wait_c(bars + B_FULL + c.s * 8, c.ph); release(c.s); c.next(); }
        TRC(tr, w, tb + 15);
        HCLK(6);
      }
      {
        CLK_INIT;
        if (w == 1) bar_arrive(6, 256);
        uint32_t pk[16];
#pragma unroll
        for (int i = 0; i < 16; i++) pk[i] = 0u;
        auto dump = [&](int p) {
          const uint32_t d = sb + (p & 3) * ST_BYTES, cb = p + j >= 9 ? p + j - 9 : p + j;
          if (lane == 0) asm volatile("cp.async.bulk.wait_group.read 3;" ::: "memory");
          __syncwarp();
#pragma unroll
          for (int u = 0; u < 4; u++) stsm4(d + (aoff ^ (u << 5)), pk[4 * u], pk[4 * u + 1], pk[4 * u + 2], pk[4 * u + 3]);
          fence_async_s();
          __syncwarp();
          tma3d_red_p(lane == 0, &P.red, cb * 64, rb * 64 + q * 16, w, d + w * 8192 + q * 2048);
        };
#pragma unroll 1
        for (int p = 0; p < 9; p++) {
          float acc[32];
          CLK(0);
          mbar_wait_c(bars + B_FULL + c.s * 8, c.ph);
          uint64_t db = dsc2(dlo(sb + c.s * ST_BYTES + ST_B + (j & 1) * 4096, 0), 0, 0x40000040u + P.zero);
          CLK(1);
          HCLK(7 + 2 * p);
          bar_sync(6 + w, 256);
          CLK(2);
          wgmma_fence();
#pragma unroll
          for (int kk = 0; kk < 18; kk++) {
            wgmma_rs_n64(acc, hA[kk], db, kk != 0);
            dadd(db, kk == 15 ? 128 - (j & 1) * (36864 >> 4) : 128 + P.zero);
            if (kk == PPK && (w == 0 || p < 8)) bar_arrive(7 - w, 256);
          }
          wgmma_commit();
          CLK(3);
          if (p > 0) dump(p - 1);
          CLK(5);
          wgmma_wait<0>();
          CLK(4);
          HCLK(8 + 2 * p);
          if (L == 0 || p < 5) release(c.s);
          c.next();
#pragma unroll
          for (int i = 0; i < 16; i++) pk[i] = pack2(acc[2 * i], acc[2 * i + 1]);
          if (p == 8) { TRC(tr, w, tb + 16); dump(8); TRC(tr, w, tb + 17); }
        }
        if (lane == 0) asm volatile("cp.async.bulk.wait_group 0;" ::: "memory");
        HCLK(25);
        if (L == 0) signal(EV_PT);
        CLK_OUT;
        TRC(tr, w, tb + 18);
      }
    }
    if ((tid & 127) == 0) g_flags[(rb * 2 + w) * 32 + FR_EP + j] = epoch + 1;
    if (tid == 0) g_flags[FJ + j * 32 + FJ_EP + rb] = epoch + 1;
  }
}

typedef CUresult (*EncodeFn)(CUtensorMap*, CUtensorMapDataType, cuuint32_t, void*, const cuuint64_t*, const cuuint64_t*, const cuuint32_t*,
                             const cuuint32_t*, CUtensorMapInterleave, CUtensorMapSwizzle, CUtensorMapL2promotion, CUtensorMapFloatOOBfill);

static void make_map(EncodeFn fn, CUtensorMap* m, const void* ptr, int rank, uint64_t d0, uint64_t d1, uint64_t d2, uint64_t s1, uint64_t s2,
                     uint32_t b0, uint32_t b1, uint32_t b2, CUtensorMapSwizzle swz) {
  cuuint64_t dims[3] = {d0, d1, d2}, strides[2] = {s1, s2};
  cuuint32_t box[3] = {b0, b1, b2}, es[3] = {1, 1, 1};
  fn(m, CU_TENSOR_MAP_DATA_TYPE_BFLOAT16, rank, const_cast<void*>(ptr), dims, strides, box, es, CU_TENSOR_MAP_INTERLEAVE_NONE, swz,
     CU_TENSOR_MAP_L2_PROMOTION_L2_128B, CU_TENSOR_MAP_FLOAT_OOB_FILL_NONE);
}

}

extern "C" void kernel_launch(void* const* d_in, const int* in_sizes, int n_in, void* d_out, int out_size) {
  using namespace mk;
  (void)in_sizes; (void)n_in; (void)out_size;
  static EncodeFn fn = nullptr;
  if (!fn) {
    cudaDriverEntryPointQueryResult qr;
    cudaGetDriverEntryPoint("cuTensorMapEncodeTiled", (void**)&fn, cudaEnableDefault, &qr);
    cudaFuncSetAttribute(mega_kernel, cudaFuncAttributeMaxDynamicSharedMemorySize, SM_TOTAL);
  }
  Params p;
  p.wqkv = (const __nv_bfloat16*)d_in[1];
  p.wo = (const __nv_bfloat16*)d_in[2];
  p.w_in = (const __nv_bfloat16*)d_in[4];
  p.w_sp = (const __nv_bfloat16*)d_in[5];
  p.b_sp = (const __nv_bfloat16*)d_in[6];
  p.w_out = (const __nv_bfloat16*)d_in[7];
  p.zero = 0;
  p.xs[0] = (uint8_t*)d_in[0];
  p.xs[1] = (uint8_t*)d_out;
  for (int cl = 0; cl < NGRID / 2; cl++) {
    const int tp = cl < 4 ? cl + 62 : cl - 4;
    p.role[cl] = tp < 32 ? tp : tp < 60 ? (4 + (tp - 32) / 7) * 8 + (tp - 32) % 7 + 1 : tp < 62 ? tp + 4 : (tp - 58) * 8;
  }
  make_map(fn, &p.wsp, p.w_sp, 3, 2048, 1024, 2, 8192, 4096, 64, 64, 2, CU_TENSOR_MAP_SWIZZLE_128B);
  for (int i = 0; i < 2; i++) {
    make_map(fn, &p.act[i], p.xs[i], 3, DM, 1024, 2, 2304, 1152, 64, 64, 1, CU_TENSOR_MAP_SWIZZLE_128B);
    make_map(fn, &p.res[i], p.xs[i], 3, DM, 1024, 2, 2304, 1152, 144, 64, 1, CU_TENSOR_MAP_SWIZZLE_NONE);
  }
  make_map(fn, &p.red, d_out, 3, DM, 1024, 2, 2304, 1152, 64, 16, 1, CU_TENSOR_MAP_SWIZZLE_128B);
  for (int i = 0; i < 2; i++) {
    cuuint64_t dims[4] = {i ? 4608u : 2304u, 8, i ? 1u : 2u, 72}, strides[3] = {9216, 4608, 8 * 9216};
    cuuint32_t box[4] = {i ? 64u : 32u, 8, i ? 1u : 2u, 18}, es[4] = {1, 1, 1, 1};
    fn(i ? &p.win64 : &p.win, CU_TENSOR_MAP_DATA_TYPE_BFLOAT16, 4, d_in[4], dims, strides, box, es, CU_TENSOR_MAP_INTERLEAVE_NONE,
       i ? CU_TENSOR_MAP_SWIZZLE_128B : CU_TENSOR_MAP_SWIZZLE_64B, CU_TENSOR_MAP_L2_PROMOTION_L2_128B, CU_TENSOR_MAP_FLOAT_OOB_FILL_NONE);
  }
  make_map(fn, &p.wout, p.w_out, 2, 576, 2304, 1, 1152, 0, 64, 144, 1, CU_TENSOR_MAP_SWIZZLE_128B);
  mega_kernel<<<NGRID, 384, SM_TOTAL, cudaStreamPerThread>>>(p);
}
```

```cpp
#include <cuda_runtime.h>
#include <cuda.h>
#include <cuda_bf16.h>
#include <stdint.h>

#define MK_TRACE 0
#define MK_DBG 0
#define P5TRACE 0
#define LAG1 1
#define PP3 32
#define PP30 33
#define LAG4 1
#define SPL 2
#define GM2 3
#define GMM 3
#define GM1 2
#define C0S 32.f
#define OFM 0x10u
#define PPK 13

namespace mk {

constexpr int SEQ = 2048, DM = 576, FH = 2304;
constexpr int NCTA = 128;
constexpr int NGRID = 132;
constexpr uint32_t ZB = 36864;
constexpr uint32_t WQ_SL = 72 * 3456;
constexpr uint32_t WO_SL = 72 * 1152;
constexpr float LN_EPS = 1e-5f;
constexpr float GA = 0.3292034911525734f, GB = 2.423681954311584f;

constexpr uint32_t ST_BYTES = 53248, ST_B = 16384, NST = 4;
constexpr uint32_t SM_STG = NST * ST_BYTES;
constexpr uint32_t SM_BAR = SM_STG + 2 * 9216;
constexpr uint32_t SM_OFF = SM_BAR + 1008;
constexpr uint32_t SM_TOTAL = SM_BAR + 1024;
constexpr uint32_t SM_RT = SM_STG + 4096, SM_CV = SM_STG + 12288, SM_WT = SM_CV + 512;
constexpr uint32_t SM_WOI = 44032, SM_CSQ = 49280, SM_XST = 50176;
constexpr uint32_t B_FULL = 0, B_EMPTY = 32, B_FULLA = 64, B_RES = 128, B_WT = 144, B_IMG = 160, B_WOI = 168, B_ZB = 176, B_GATE3 = 184, B_Z1 = 192, B_LAG = 200,
                   B_RT = 208, B_CSQ = 216, B_CV = 224, B_AD = 240, B_EVT = 272, B_RT1 = 368, B_XRW = 384, B_FA3 = 400, B_EA3 = 544;
enum { EV_PT = 0, EV_O = 1, EV_X1 = 2, EV_ZN = 3, EV_Z1 = 4, EV_P4 = 5, EV_N = 6 };

enum { FR_X2 = 0, FR_O = 1, FR_X1 = 3, FR_EP = 16, FJ = 32 * 32, FJ_WQ = 0, FJ_WO = 1, FJ_WQ0 = 2, FJ_ZN = 3, FJ_P4 = 5, FJ_EP = 16, F_N = FJ + 8 * 32 };

__device__ __align__(1024) uint8_t g_Z[512 * ZB];
__device__ __align__(1024) uint8_t g_WQ[8 * WQ_SL];
__device__ __align__(1024) uint8_t g_WO[8 * WO_SL];
__device__ __align__(1024) float g_CSP[2 * NCTA * 216];
__device__ __align__(1024) uint2 g_RT[SEQ];
__device__ __align__(1024) uint4 g_XST[2 * SEQ];
__device__ __align__(1024) uint4 g_ST1[SEQ * 8];
__device__ __align__(1024) uint4 g_ZST[SEQ * 8];
__device__ __align__(1024) uint4 g_HALO[32 * 8 * 6 * 32];
__device__ __align__(1024) uint32_t g_flags[F_N];

struct Params {
  const __nv_bfloat16 *wqkv;
  uint8_t* wq;
  float* csp;
  uint32_t zero;
  const __nv_bfloat16 *wo, *w_in, *w_sp, *b_sp, *w_out;
  uint8_t* xs[2];
  CUtensorMap wsp, win, win64, wout;
  CUtensorMap act[2];
  CUtensorMap res[2];
  CUtensorMap red;
};

__device__ __forceinline__ uint32_t smem_u32(const void* p) { return (uint32_t)__cvta_generic_to_shared(p); }
__device__ __forceinline__ void mbar_init(uint32_t bar, uint32_t cnt) { asm volatile("mbarrier.init.shared::cta.b64 [%0], %1;" ::"r"(bar), "r"(cnt)); }
__device__ __forceinline__ void mbar_arrive(uint32_t bar) { asm volatile("mbarrier.arrive.shared::cta.b64 _, [%0];" ::"r"(bar) : "memory"); }
__device__ __forceinline__ void mbar_wait(uint32_t bar, uint32_t parity) {
  asm volatile(
      "{\n.reg .pred p;\n.reg .u32 c;\nmov.u32 c, 0;\nLAB_WAIT:\n"
      "mbarrier.try_wait.parity.shared::cta.b64 p, [%0], %1;\n@p bra LAB_DONE;\n"
      "add.u32 c, c, 1;\nsetp.lt.u32 p, c, 0x100000;\n@p bra LAB_WAIT;\ntrap;\nLAB_DONE:\n}" ::"r"(bar), "r"(parity)
      : "memory");
}
__device__ __forceinline__ void mbar_wait_c(uint32_t bar, uint32_t parity) {
  asm volatile("{\n.reg .pred p;\nLAB_WAIT:\nmbarrier.try_wait.parity.shared::cta.b64 p, [%0], %1;\n@!p bra LAB_WAIT;\n}" ::"r"(bar), "r"(parity) : "memory");
}
__device__ __forceinline__ void flag_wait(const uint32_t* f, uint32_t target) {
  asm volatile(
      "{\n.reg .pred p;\n.reg .u32 c, v;\nmov.u32 c, 0;\nLAB_WAIT:\n"
      "ld.relaxed.gpu.global.u32 v, [%0];\nsub.u32 v, v, %1;\nsetp.ge.s32 p, v, 0;\n@p bra LAB_DONE;\n"
      "add.u32 c, c, 1;\nsetp.lt.u32 p, c, 0x400000;\n@p bra LAB_WAIT;\ntrap;\nLAB_DONE:\nfence.acquire.gpu;\n}" ::"l"(f), "r"(target)
      : "memory");
}
__device__ __forceinline__ void fence_gpu() { asm volatile("fence.acq_rel.gpu;" ::: "memory"); }
__device__ __forceinline__ void fence_async_g() { asm volatile("fence.proxy.async.global;" ::: "memory"); }
__device__ __forceinline__ void fence_async_s() { asm volatile("fence.proxy.async.shared::cta;" ::: "memory"); }
__device__ __forceinline__ uint32_t elect_one() {
  uint32_t p; asm volatile("{\n.reg .pred P;\nelect.sync _|P, 0xffffffff;\nselp.u32 %0, 1, 0, P;\n}" : "=r"(p)); return p;
}
__device__ __forceinline__ void expect_tx_p(uint32_t el, uint32_t bar, uint32_t bytes) {
  asm volatile("{\n.reg .pred P;\nsetp.ne.u32 P, %2, 0;\n@P mbarrier.arrive.expect_tx.shared::cta.b64 _, [%0], %1;\n}" ::"r"(bar), "r"(bytes), "r"(el) : "memory");
}
__device__ __forceinline__ void bulk_load_p(uint32_t el, uint32_t dst, const void* src, uint32_t bytes, uint32_t bar) {
  asm volatile("{\n.reg .pred P;\nsetp.ne.u32 P, %4, 0;\n@P cp.async.bulk.shared::cluster.global.mbarrier::complete_tx::bytes [%0], [%1], %2, [%3];\n}" ::"r"(dst), "l"(src), "r"(bytes), "r"(bar), "r"(el) : "memory");
}
__device__ __forceinline__ uint64_t policy_evict_first() { uint64_t p; asm("createpolicy.fractional.L2::evict_first.b64 %0, 1.0;" : "=l"(p)); return p; }
__device__ __forceinline__ void bulk_load_h(uint32_t el, uint32_t dst, const void* src, uint32_t bytes, uint32_t bar, bool ef, uint64_t pol) {
  if (ef) {
    asm volatile("{\n.reg .pred P;\nsetp.ne.u32 P, %4, 0;\n@P cp.async.bulk.shared::cluster.global.mbarrier::complete_tx::bytes.L2::cache_hint [%0], [%1], %2, [%3], %5;\n}" ::"r"(dst), "l"(src), "r"(bytes), "r"(bar), "r"(el), "l"(pol) : "memory");
  } else {
    asm volatile("{\n.reg .pred P;\nsetp.ne.u32 P, %4, 0;\n@P cp.async.bulk.shared::cluster.global.mbarrier::complete_tx::bytes [%0], [%1], %2, [%3];\n}" ::"r"(dst), "l"(src), "r"(bytes), "r"(bar), "r"(el) : "memory");
  }
}
__device__ __forceinline__ void bulk_mc_h(uint32_t el, uint32_t dst, const void* src, uint32_t bytes, uint32_t bar, bool ef, uint64_t pol) {
  if (ef) {
    asm volatile("{\n.reg .pred P;\nsetp.ne.u32 P, %4, 0;\n@P cp.async.bulk.shared::cluster.global.mbarrier::complete_tx::bytes.multicast::cluster.L2::cache_hint [%0], [%1], %2, [%3], %5, %6;\n}" ::"r"(dst), "l"(src), "r"(bytes), "r"(bar), "r"(el), "h"((uint16_t)3), "l"(pol) : "memory");
  } else {
    asm volatile("{\n.reg .pred P;\nsetp.ne.u32 P, %4, 0;\n@P cp.async.bulk.shared::cluster.global.mbarrier::complete_tx::bytes.multicast::cluster [%0], [%1], %2, [%3], %5;\n}" ::"r"(dst), "l"(src), "r"(bytes), "r"(bar), "r"(el), "h"((uint16_t)3) : "memory");
  }
}
__device__ __forceinline__ void tma3d_h(uint32_t el, uint32_t dst, const CUtensorMap* m, int c0, int c1, int c2, uint32_t bar, bool ef, uint64_t pol) {
  if (ef) {
    asm volatile("{\n.reg .pred P;\nsetp.ne.u32 P, %6, 0;\n@P cp.async.bulk.tensor.3d.shared::cluster.global.mbarrier::complete_tx::bytes.L2::cache_hint [%0], [%1, {%3, %4, %5}], [%2], %7;\n}" ::"r"(dst), "l"(m), "r"(bar), "r"(c0), "r"(c1), "r"(c2), "r"(el), "l"(pol) : "memory");
  } else {
    asm volatile("{\n.reg .pred P;\nsetp.ne.u32 P, %6, 0;\n@P cp.async.bulk.tensor.3d.shared::cluster.global.mbarrier::complete_tx::bytes [%0], [%1, {%3, %4, %5}], [%2];\n}" ::"r"(dst), "l"(m), "r"(bar), "r"(c0), "r"(c1), "r"(c2), "r"(el) : "memory");
  }
}
__device__ __forceinline__ void tma2d_mc_h(uint32_t el, uint32_t dst, const CUtensorMap* m, int c0, int c1, uint32_t bar, bool ef, uint64_t pol) {
  if (ef) {
    asm volatile("{\n.reg .pred P;\nsetp.ne.u32 P, %5, 0;\n@P cp.async.bulk.tensor.2d.shared::cluster.global.mbarrier::complete_tx::bytes.multicast::cluster.L2::cache_hint [%0], [%1, {%3, %4}], [%2], %6, %7;\n}" ::"r"(dst), "l"(m), "r"(bar), "r"(c0), "r"(c1), "r"(el), "h"((uint16_t)3), "l"(pol) : "memory");
  } else {
    asm volatile("{\n.reg .pred P;\nsetp.ne.u32 P, %5, 0;\n@P cp.async.bulk.tensor.2d.shared::cluster.global.mbarrier::complete_tx::bytes.multicast::cluster [%0], [%1, {%3, %4}], [%2], %6;\n}" ::"r"(dst), "l"(m), "r"(bar), "r"(c0), "r"(c1), "r"(el), "h"((uint16_t)3) : "memory");
  }
}
__device__ __forceinline__ void tma4d_mc(uint32_t el, uint32_t dst, const CUtensorMap* m, int c0, int c3, uint32_t bar, uint64_t pol) {
  asm volatile("{\n.reg .pred P;\nsetp.ne.u32 P, %5, 0;\n@P cp.async.bulk.tensor.4d.shared::cluster.global.mbarrier::complete_tx::bytes.multicast::cluster.L2::cache_hint [%0], [%1, {%3, 0, 0, %4}], [%2], %6, %7;\n}" ::"r"(dst), "l"(m), "r"(bar), "r"(c0), "r"(c3), "r"(el), "h"((uint16_t)3), "l"(pol) : "memory");
}
__device__ __forceinline__ void mbar_arrive_cluster(uint32_t addr) { asm volatile("mbarrier.arrive.shared::cluster.b64 _, [%0];" ::"r"(addr) : "memory"); }
__device__ __forceinline__ void mbar_arrive_cluster_if(bool c, uint32_t addr) {
  asm volatile("{\n.reg .pred P;\nsetp.ne.u32 P, %1, 0;\n@P mbarrier.arrive.shared::cluster.b64 _, [%0];\n}" ::"r"(addr), "r"((uint32_t)c) : "memory");
}
__device__ __forceinline__ void mbar_arrive_if(bool c, uint32_t addr) {
  asm volatile("{\n.reg .pred P;\nsetp.ne.u32 P, %1, 0;\n@P mbarrier.arrive.shared::cta.b64 _, [%0];\n}" ::"r"(addr), "r"((uint32_t)c) : "memory");
}
__device__ __forceinline__ uint32_t mapa(uint32_t addr, uint32_t rank) { uint32_t r; asm("mapa.shared::cluster.u32 %0, %1, %2;" : "=r"(r) : "r"(addr), "r"(rank)); return r; }
__device__ __forceinline__ void bulk_store_p(uint32_t el, void* dst, uint32_t src, uint32_t bytes) {
  asm volatile("{\n.reg .pred P;\nsetp.ne.u32 P, %3, 0;\n@P cp.async.bulk.global.shared::cta.bulk_group [%0], [%1], %2;\n}" ::"l"(dst), "r"(src), "r"(bytes), "r"(el) : "memory");
}
__device__ __forceinline__ void flag_release_p(uint32_t el, uint32_t* f) {
  asm volatile("{\n.reg .pred P;\nsetp.ne.u32 P, %1, 0;\n@P red.release.gpu.global.add.u32 [%0], 1;\n}" ::"l"(f), "r"(el) : "memory");
}
__device__ __forceinline__ void flag_add_p(uint32_t el, uint32_t* f) {
  asm volatile("{\n.reg .pred P;\nsetp.ne.u32 P, %1, 0;\n@P red.relaxed.gpu.global.add.u32 [%0], 1;\n}" ::"l"(f), "r"(el) : "memory");
}
__device__ __forceinline__ void prefetch_l2(const void* src, uint32_t bytes) { asm volatile("cp.async.bulk.prefetch.L2.global [%0], %1;" ::"l"(src), "r"(bytes) : "memory"); }
__device__ __forceinline__ void prefetch_map(const CUtensorMap* m) { asm volatile("prefetch.tensormap [%0];" ::"l"(m) : "memory"); }
__device__ __forceinline__ void wgmma_fence() { asm volatile("wgmma.fence.sync.aligned;" ::: "memory"); }
__device__ __forceinline__ void wgmma_commit() { asm volatile("wgmma.commit_group.sync.aligned;" ::: "memory"); }
template <int N> __device__ __forceinline__ void wgmma_wait() { asm volatile("wgmma.wait_group.sync.aligned %0;" ::"n"(N) : "memory"); }
__device__ __forceinline__ uint32_t dlo(uint32_t addr, uint32_t lbo) { return ((addr & 0x3FFFF) >> 4) + ((lbo >> 4) << 16); }
template <uint32_t SBO, uint32_t SWZ> __device__ __forceinline__ uint64_t dsc(uint32_t lo, uint32_t off) {
  uint64_t d; asm("mov.b64 %0, {%1, %2};" : "=l"(d) : "r"(lo + (off >> 4)), "n"((SBO >> 4) | (SWZ << 30))); return d;
}
__device__ __forceinline__ uint64_t dsc2(uint32_t lo, uint32_t off, uint32_t hi) {
  uint64_t d; asm("mov.b64 %0, {%1, %2};" : "=l"(d) : "r"(lo + (off >> 4)), "r"(hi)); return d;
}
__device__ __forceinline__ void dadd(uint64_t& d, uint32_t v) {
  asm("{\n.reg .b32 lo, hi;\nmov.b64 {lo, hi}, %0;\nadd.u32 lo, lo, %1;\nmov.b64 %0, {lo, hi};\n}" : "+l"(d) : "r"(v));
}
template <int R> __device__ __forceinline__ void reg_alloc() { asm volatile("setmaxnreg.inc.sync.aligned.u32 %0;" ::"n"(R)); }
template <int R> __device__ __forceinline__ void reg_dealloc() { asm volatile("setmaxnreg.dec.sync.aligned.u32 %0;" ::"n"(R)); }
__device__ __forceinline__ void bar_sync(int id, int n) { asm volatile("bar.sync %0, %1;" ::"r"(id), "r"(n) : "memory"); }
__device__ __forceinline__ void bar_arrive(int id, int n) { asm volatile("bar.arrive %0, %1;" ::"r"(id), "r"(n) : "memory"); }
__device__ __forceinline__ void ldsm4(uint32_t* r, uint32_t addr) {
  asm volatile("ldmatrix.sync.aligned.m8n8.x4.shared.b16 {%0,%1,%2,%3}, [%4];" : "=r"(r[0]), "=r"(r[1]), "=r"(r[2]), "=r"(r[3]) : "r"(addr) : "memory");
}
__device__ __forceinline__ uint32_t movm(uint32_t a) { uint32_t d; asm volatile("movmatrix.sync.aligned.m8n8.trans.b16 %0, %1;" : "=r"(d) : "r"(a)); return d; }
__device__ __forceinline__ void mma16(float* c, uint32_t a0, uint32_t a1, uint32_t a2, uint32_t a3, uint32_t b0, uint32_t b1) {
  asm volatile("mma.sync.aligned.m16n8k16.row.col.f32.bf16.bf16.f32 {%0,%1,%2,%3}, {%4,%5,%6,%7}, {%8,%9}, {%0,%1,%2,%3};"
               : "+f"(c[0]), "+f"(c[1]), "+f"(c[2]), "+f"(c[3]) : "r"(a0), "r"(a1), "r"(a2), "r"(a3), "r"(b0), "r"(b1));
}
__device__ __forceinline__ void mma8(float* c, uint32_t a0, uint32_t a1, uint32_t b0) {
  asm volatile("mma.sync.aligned.m16n8k8.row.col.f32.bf16.bf16.f32 {%0,%1,%2,%3}, {%4,%5}, {%6}, {%0,%1,%2,%3};"
               : "+f"(c[0]), "+f"(c[1]), "+f"(c[2]), "+f"(c[3]) : "r"(a0), "r"(a1), "r"(b0));
}
__device__ __forceinline__ uint32_t pack2(float lo, float hi) { uint32_t r; asm("cvt.rn.bf16x2.f32 %0, %1, %2;" : "=r"(r) : "f"(hi), "f"(lo)); return r; }
__device__ __forceinline__ float blo(uint32_t v) { return __uint_as_float(v << 16); }
__device__ __forceinline__ float bhi(uint32_t v) { return __uint_as_float(v & 0xffff0000u); }
__device__ __forceinline__ float tanh_fast(float x) { float y; asm("tanh.approx.f32 %0, %1;" : "=f"(y) : "f"(x)); return y; }
__device__ __forceinline__ float rcp_fast(float x) { float y; asm("rcp.approx.ftz.f32 %0, %1;" : "=f"(y) : "f"(x)); return y; }
__device__ __forceinline__ float ex2(float x) { float y; asm("ex2.approx.ftz.f32 %0, %1;" : "=f"(y) : "f"(x)); return y; }
__device__ __forceinline__ float qsum(float v) { v += __shfl_xor_sync(~0u, v, 1); v += __shfl_xor_sync(~0u, v, 2); return v; }
__device__ __forceinline__ float qmax(float v) { v = fmaxf(v, __shfl_xor_sync(~0u, v, 1)); v = fmaxf(v, __shfl_xor_sync(~0u, v, 2)); return v; }
__device__ __forceinline__ void stg32(void* p, uint32_t v) { asm volatile("st.global.u32 [%0], %1;" ::"l"(p), "r"(v) : "memory"); }
__device__ __forceinline__ void stg128(void* p, uint32_t a, uint32_t b, uint32_t c, uint32_t d) { asm volatile("st.global.v4.u32 [%0], {%1,%2,%3,%4};" ::"l"(p), "r"(a), "r"(b), "r"(c), "r"(d) : "memory"); }
__device__ __forceinline__ uint32_t ldcg32(const void* p) { uint32_t v; asm volatile("ld.global.L1::no_allocate.u32 %0, [%1];" : "=r"(v) : "l"(p) : "memory"); return v; }
__device__ __forceinline__ void stg128_if(bool c, void* p, uint32_t a, uint32_t b, uint32_t cc, uint32_t d) {
  asm volatile("{\n.reg .pred P;\nsetp.ne.u32 P, %5, 0;\n@P st.global.v4.u32 [%0], {%1,%2,%3,%4};\n}" ::"l"(p), "r"(a), "r"(b), "r"(cc), "r"(d), "r"((uint32_t)c) : "memory");
}
__device__ __forceinline__ uint2 lds64(uint32_t a) { uint2 v; asm volatile("ld.shared.v2.u32 {%0,%1}, [%2];" : "=r"(v.x), "=r"(v.y) : "r"(a) : "memory"); return v; }
__device__ __forceinline__ uint4 ldcg128(const void* p) { uint4 v; asm volatile("ld.global.cg.v4.u32 {%0,%1,%2,%3}, [%4];" : "=r"(v.x), "=r"(v.y), "=r"(v.z), "=r"(v.w) : "l"(p) : "memory"); return v; }
__device__ __forceinline__ uint32_t ldnc16(const void* p) { uint16_t v; asm volatile("ld.global.nc.u16 %0, [%1];" : "=h"(v) : "l"(p)); return v; }
__device__ __forceinline__ uint4 ldnc128(const void* p) { uint4 v; asm volatile("ld.global.nc.v4.u32 {%0,%1,%2,%3}, [%4];" : "=r"(v.x), "=r"(v.y), "=r"(v.z), "=r"(v.w) : "l"(p)); return v; }
__device__ __forceinline__ void cp_async16(uint32_t dst, const void* src) { asm volatile("cp.async.cg.shared.global [%0], [%1], 16;" ::"r"(dst), "l"(src) : "memory"); }
__device__ __forceinline__ uint32_t hsub2(uint32_t a, uint32_t b) { uint32_t d; asm("sub.rn.bf16x2 %0, %1, %2;" : "=r"(d) : "r"(a), "r"(b)); return d; }
__device__ __forceinline__ void stg32_if(bool c, void* p, uint32_t v) {
  asm volatile("{\n.reg .pred P;\nsetp.ne.u32 P, %2, 0;\n@P st.global.u32 [%0], %1;\n}" ::"l"(p), "r"(v), "r"((uint32_t)c) : "memory");
}
__device__ __forceinline__ float wsum(float v) { for (int o = 16; o; o >>= 1) v += __shfl_xor_sync(~0u, v, o); return v; }
__device__ __forceinline__ uint32_t hmul2(uint32_t a, uint32_t b) { uint32_t d; asm("mul.rn.bf16x2 %0, %1, %2;" : "=r"(d) : "r"(a), "r"(b)); return d; }
__device__ __forceinline__ void sts32(uint32_t a, uint32_t v) { asm volatile("st.shared.u32 [%0], %1;" ::"r"(a), "r"(v) : "memory"); }
__device__ __forceinline__ uint32_t lds32(uint32_t a) { uint32_t v; asm volatile("ld.shared.u32 %0, [%1];" : "=r"(v) : "r"(a) : "memory"); return v; }
__device__ __forceinline__ void sts128(uint32_t a, uint32_t x, uint32_t y, uint32_t z, uint32_t w) { asm volatile("st.shared.v4.u32 [%0], {%1,%2,%3,%4};" ::"r"(a), "r"(x), "r"(y), "r"(z), "r"(w) : "memory"); }
__device__ __forceinline__ uint4 lds128(uint32_t a) { uint4 v; asm volatile("ld.shared.v4.u32 {%0,%1,%2,%3}, [%4];" : "=r"(v.x), "=r"(v.y), "=r"(v.z), "=r"(v.w) : "r"(a) : "memory"); return v; }
__device__ __forceinline__ void ll_st64(uint2* p, uint32_t v, uint32_t tag) {
  asm volatile("{\n.reg .b64 r;\nmov.b64 r, {%1,%2};\nst.relaxed.gpu.global.b64 [%0], r;\n}" ::"l"(p), "r"(v), "r"(tag) : "memory");
}
__device__ __forceinline__ uint2 ll_ld64(const uint2* p) {
  uint2 v; asm volatile("{\n.reg .b64 r;\nld.relaxed.gpu.global.b64 r, [%2];\nmov.b64 {%0,%1}, r;\n}" : "=r"(v.x), "=r"(v.y) : "l"(p) : "memory"); return v;
}
__device__ __forceinline__ void ll_st128(uint4* p, float a, float b, uint32_t tag, float c = 0.f) {
  asm volatile("{\n.reg .b128 r;\n.reg .b64 lo, hi;\nmov.b64 lo, {%1,%2};\nmov.b64 hi, {%3,%4};\nmov.b128 r, {lo, hi};\nst.relaxed.gpu.global.b128 [%0], r;\n}" ::"l"(p), "r"(__float_as_uint(a)), "r"(__float_as_uint(b)), "r"(tag), "r"(__float_as_uint(c)) : "memory");
}
__device__ __forceinline__ uint4 ll_ld128(const uint4* p) {
  uint4 v; asm volatile("{\n.reg .b128 r;\n.reg .b64 lo, hi;\nld.relaxed.gpu.global.b128 r, [%4];\nmov.b128 {lo, hi}, r;\nmov.b64 {%0,%1}, lo;\nmov.b64 {%2,%3}, hi;\n}" : "=r"(v.x), "=r"(v.y), "=r"(v.z), "=r"(v.w) : "l"(p) : "memory"); return v;
}
__device__ __forceinline__ void publish_p(uint32_t el, uint32_t* f) {
  asm volatile("{\n.reg .pred P;\nsetp.ne.u32 P, %1, 0;\n@P cp.async.bulk.commit_group;\n@P cp.async.bulk.wait_group 0;\n@P red.release.gpu.global.add.u32 [%0], 1;\n}" ::"l"(f), "r"(el) : "memory");
}
__device__ __forceinline__ void tma3d_red_p(uint32_t el, const CUtensorMap* m, int c0, int c1, int c2, uint32_t src) {
  asm volatile("{\n.reg .pred P;\nsetp.ne.u32 P, %5, 0;\n@P cp.reduce.async.bulk.tensor.3d.global.shared::cta.add.tile.bulk_group [%0, {%2, %3, %4}], [%1];\n@P cp.async.bulk.commit_group;\n}" ::"l"(m), "r"(src), "r"(c0), "r"(c1), "r"(c2), "r"(el) : "memory");
}
__device__ __forceinline__ void stsm4(uint32_t addr, uint32_t a, uint32_t b, uint32_t c, uint32_t d) {
  asm volatile("stmatrix.sync.aligned.m8n8.x4.shared.b16 [%0], {%1,%2,%3,%4};" ::"r"(addr), "r"(a), "r"(b), "r"(c), "r"(d) : "memory");
}
__device__ __forceinline__ void sts64(uint32_t a, uint32_t x, uint32_t y) { asm volatile("st.shared.v2.u32 [%0], {%1,%2};" ::"r"(a), "r"(x), "r"(y) : "memory"); }
__device__ __forceinline__ void ll_st128_if(bool on, uint4* p, float a, float b, uint32_t tag) {
  asm volatile("{\n.reg .pred P;\n.reg .b128 r;\n.reg .b64 lo, hi;\nsetp.ne.u32 P, %4, 0;\nmov.b64 lo, {%1,%2};\nmov.b64 hi, {%3,%3};\nmov.b128 r, {lo, hi};\n@P st.relaxed.gpu.global.b128 [%0], r;\n}" ::"l"(p), "r"(__float_as_uint(a)), "r"(__float_as_uint(b)), "r"(tag), "r"((uint32_t)on) : "memory");
}
__device__ __forceinline__ uint4 ldnc128_if(bool c, const void* p) {
  uint4 v = make_uint4(0u, 0u, 0u, 0u);
  asm volatile("{\n.reg .pred P;\nsetp.ne.u32 P, %5, 0;\n@P ld.global.nc.v4.u32 {%0,%1,%2,%3}, [%4];\n}" : "+r"(v.x), "+r"(v.y), "+r"(v.z), "+r"(v.w) : "l"(p), "r"((uint32_t)c));
  return v;
}
__device__ __forceinline__ uint32_t hfma2(uint32_t a, uint32_t b, uint32_t c) { uint32_t d; asm("fma.rn.bf16x2 %0, %1, %2, %3;" : "=r"(d) : "r"(a), "r"(b), "r"(c)); return d; }
__device__ __forceinline__ float2 lds64f(uint32_t a) { float2 v; asm volatile("ld.shared.v2.f32 {%0,%1}, [%2];" : "=f"(v.x), "=f"(v.y) : "r"(a) : "memory"); return v; }
#define TRC(cond, role, idx) do {} while (0)
#define TRV(role, idx, v) do {} while (0)

#define ACLK_INIT do {} while (0)
#define ACLK(i) do {} while (0)
#define ACLK_OUT do {} while (0)
#define QCLK(i) do {} while (0)
#define PH 1
#define RCLK(i) do {} while (0)
#define RCLK_INIT do {} while (0)
#define RCLK_OUT do {} while (0)
#define SCLK(i) do {} while (0)
#define HCLK(i) do {} while (0)
#define MCLK(c, i) do {} while (0)
#define CKK(i) do {} while (0)
#define CKK_OUT do {} while (0)
#define PL 1
#define PCLK(i) do {} while (0)
#define PQ 1
#define CLK_INIT do {} while (0)
#define CLK(i) do {} while (0)
#define CLK_OUT do {} while (0)

__device__ __forceinline__ void wgmma_ss_n216(float* d, uint64_t da, uint64_t db, int scaleD) {
  asm volatile("{\n.reg .pred p;\nsetp.ne.b32 p, %110, 0;\nwgmma.mma_async.sync.aligned.m64n216k16.f32.bf16.bf16 "
    "{%0,%1,%2,%3,%4,%5,%6,%7,%8,%9,%10,%11,%12,%13,%14,%15,%16,%17,%18,%19,%20,%21,%22,%23,%24,%25,%26,%27,%28,%29,%30,%31,%32,%33,%34,%35,%36,%37,%38,%39,%40,%41,%42,%43,%44,%45,%46,%47,%48,%49,%50,%51,%52,%53,%54,%55,%56,%57,%58,%59,%60,%61,%62,%63,%64,%65,%66,%67,%68,%69,%70,%71,%72,%73,%74,%75,%76,%77,%78,%79,%80,%81,%82,%83,%84,%85,%86,%87,%88,%89,%90,%91,%92,%93,%94,%95,%96,%97,%98,%99,%100,%101,%102,%103,%104,%105,%106,%107}, "
    "%108, %109, p, 1, 1, 0, 1;\n}\n"
    : "+f"(d[0]), "+f"(d[1]), "+f"(d[2]), "+f"(d[3]), "+f"(d[4]), "+f"(d[5]), "+f"(d[6]), "+f"(d[7]), "+f"(d[8]), "+f"(d[9]), "+f"(d[10]), "+f"(d[11]), "+f"(d[12]), "+f"(d[13]), "+f"(d[14]), "+f"(d[15]), "+f"(d[16]), "+f"(d[17]), "+f"(d[18]), "+f"(d[19]), "+f"(d[20]), "+f"(d[21]), "+f"(d[22]), "+f"(d[23]), "+f"(d[24]), "+f"(d[25]), "+f"(d[26]), "+f"(d[27]), "+f"(d[28]), "+f"(d[29]), "+f"(d[30]), "+f"(d[31]), "+f"(d[32]), "+f"(d[33]), "+f"(d[34]), "+f"(d[35]), "+f"(d[36]), "+f"(d[37]), "+f"(d[38]), "+f"(d[39]), "+f"(d[40]), "+f"(d[41]), "+f"(d[42]), "+f"(d[43]), "+f"(d[44]), "+f"(d[45]), "+f"(d[46]), "+f"(d[47]), "+f"(d[48]), "+f"(d[49]), "+f"(d[50]), "+f"(d[51]), "+f"(d[52]), "+f"(d[53]), "+f"(d[54]), "+f"(d[55]), "+f"(d[56]), "+f"(d[57]), "+f"(d[58]), "+f"(d[59]), "+f"(d[60]), "+f"(d[61]), "+f"(d[62]), "+f"(d[63]), "+f"(d[64]), "+f"(d[65]), "+f"(d[66]), "+f"(d[67]), "+f"(d[68]), "+f"(d[69]), "+f"(d[70]), "+f"(d[71]), "+f"(d[72]), "+f"(d[73]), "+f"(d[74]), "+f"(d[75]), "+f"(d[76]), "+f"(d[77]), "+f"(d[78]), "+f"(d[79]), "+f"(d[80]), "+f"(d[81]), "+f"(d[82]), "+f"(d[83]), "+f"(d[84]), "+f"(d[85]), "+f"(d[86]), "+f"(d[87]), "+f"(d[88]), "+f"(d[89]), "+f"(d[90]), "+f"(d[91]), "+f"(d[92]), "+f"(d[93]), "+f"(d[94]), "+f"(d[95]), "+f"(d[96]), "+f"(d[97]), "+f"(d[98]), "+f"(d[99]), "+f"(d[100]), "+f"(d[101]), "+f"(d[102]), "+f"(d[103]), "+f"(d[104]), "+f"(d[105]), "+f"(d[106]), "+f"(d[107])
    : "l"(da), "l"(db), "r"(scaleD));
}
__device__ __forceinline__ void wgmma_ss_n72(float* d, uint64_t da, uint64_t db, int scaleD) {
  asm volatile("{\n.reg .pred p;\nsetp.ne.b32 p, %38, 0;\nwgmma.mma_async.sync.aligned.m64n72k16.f32.bf16.bf16 "
    "{%0,%1,%2,%3,%4,%5,%6,%7,%8,%9,%10,%11,%12,%13,%14,%15,%16,%17,%18,%19,%20,%21,%22,%23,%24,%25,%26,%27,%28,%29,%30,%31,%32,%33,%34,%35}, "
    "%36, %37, p, 1, 1, 0, 1;\n}\n"
    : "+f"(d[0]), "+f"(d[1]), "+f"(d[2]), "+f"(d[3]), "+f"(d[4]), "+f"(d[5]), "+f"(d[6]), "+f"(d[7]), "+f"(d[8]), "+f"(d[9]), "+f"(d[10]), "+f"(d[11]), "+f"(d[12]), "+f"(d[13]), "+f"(d[14]), "+f"(d[15]), "+f"(d[16]), "+f"(d[17]), "+f"(d[18]), "+f"(d[19]), "+f"(d[20]), "+f"(d[21]), "+f"(d[22]), "+f"(d[23]), "+f"(d[24]), "+f"(d[25]), "+f"(d[26]), "+f"(d[27]), "+f"(d[28]), "+f"(d[29]), "+f"(d[30]), "+f"(d[31]), "+f"(d[32]), "+f"(d[33]), "+f"(d[34]), "+f"(d[35])
    : "l"(da), "l"(db), "r"(scaleD));
}
__device__ __forceinline__ void wgmma_rs_n144(float* d, const uint32_t* a, uint64_t db, int scaleD) {
  asm volatile("{\n.reg .pred p;\nsetp.ne.b32 p, %77, 0;\nwgmma.mma_async.sync.aligned.m64n144k16.f32.bf16.bf16 "
    "{%0,%1,%2,%3,%4,%5,%6,%7,%8,%9,%10,%11,%12,%13,%14,%15,%16,%17,%18,%19,%20,%21,%22,%23,%24,%25,%26,%27,%28,%29,%30,%31,%32,%33,%34,%35,%36,%37,%38,%39,%40,%41,%42,%43,%44,%45,%46,%47,%48,%49,%50,%51,%52,%53,%54,%55,%56,%57,%58,%59,%60,%61,%62,%63,%64,%65,%66,%67,%68,%69,%70,%71}, "
    "{%72,%73,%74,%75}, %76, p, 1, 1, 1;\n}\n"
    : "+f"(d[0]), "+f"(d[1]), "+f"(d[2]), "+f"(d[3]), "+f"(d[4]), "+f"(d[5]), "+f"(d[6]), "+f"(d[7]), "+f"(d[8]), "+f"(d[9]), "+f"(d[10]), "+f"(d[11]), "+f"(d[12]), "+f"(d[13]), "+f"(d[14]), "+f"(d[15]), "+f"(d[16]), "+f"(d[17]), "+f"(d[18]), "+f"(d[19]), "+f"(d[20]), "+f"(d[21]), "+f"(d[22]), "+f"(d[23]), "+f"(d[24]), "+f"(d[25]), "+f"(d[26]), "+f"(d[27]), "+f"(d[28]), "+f"(d[29]), "+f"(d[30]), "+f"(d[31]), "+f"(d[32]), "+f"(d[33]), "+f"(d[34]), "+f"(d[35]), "+f"(d[36]), "+f"(d[37]), "+f"(d[38]), "+f"(d[39]), "+f"(d[40]), "+f"(d[41]), "+f"(d[42]), "+f"(d[43]), "+f"(d[44]), "+f"(d[45]), "+f"(d[46]), "+f"(d[47]), "+f"(d[48]), "+f"(d[49]), "+f"(d[50]), "+f"(d[51]), "+f"(d[52]), "+f"(d[53]), "+f"(d[54]), "+f"(d[55]), "+f"(d[56]), "+f"(d[57]), "+f"(d[58]), "+f"(d[59]), "+f"(d[60]), "+f"(d[61]), "+f"(d[62]), "+f"(d[63]), "+f"(d[64]), "+f"(d[65]), "+f"(d[66]), "+f"(d[67]), "+f"(d[68]), "+f"(d[69]), "+f"(d[70]), "+f"(d[71])
    : "r"(a[0]), "r"(a[1]), "r"(a[2]), "r"(a[3]), "l"(db), "r"(scaleD));
}
__device__ __forceinline__ void wgmma_rs_n64(float* d, const uint32_t* a, uint64_t db, int scaleD) {
  asm volatile("{\n.reg .pred p;\nsetp.ne.b32 p, %37, 0;\nwgmma.mma_async.sync.aligned.m64n64k16.f32.bf16.bf16 "
    "{%0,%1,%2,%3,%4,%5,%6,%7,%8,%9,%10,%11,%12,%13,%14,%15,%16,%17,%18,%19,%20,%21,%22,%23,%24,%25,%26,%27,%28,%29,%30,%31}, "
    "{%32,%33,%34,%35}, %36, p, 1, 1, 1;\n}\n"
    : "+f"(d[0]), "+f"(d[1]), "+f"(d[2]), "+f"(d[3]), "+f"(d[4]), "+f"(d[5]), "+f"(d[6]), "+f"(d[7]), "+f"(d[8]), "+f"(d[9]), "+f"(d[10]), "+f"(d[11]), "+f"(d[12]), "+f"(d[13]), "+f"(d[14]), "+f"(d[15]), "+f"(d[16]), "+f"(d[17]), "+f"(d[18]), "+f"(d[19]), "+f"(d[20]), "+f"(d[21]), "+f"(d[22]), "+f"(d[23]), "+f"(d[24]), "+f"(d[25]), "+f"(d[26]), "+f"(d[27]), "+f"(d[28]), "+f"(d[29]), "+f"(d[30]), "+f"(d[31])
    : "r"(a[0]), "r"(a[1]), "r"(a[2]), "r"(a[3]), "l"(db), "r"(scaleD));
}

template <int V> struct Int { static constexpr int value = V; };
struct Cur {
  uint32_t s, ph;
  __device__ __forceinline__ void next() { if (++s == NST) { s = 0; ph ^= 1; } }
};

__device__ __forceinline__ uint8_t* z1_block(int rb, int w, int j) { return g_Z + (rb * 16 + w * 8 + j) * ZB; }
__device__ __forceinline__ uint8_t* z2_block(int kb, int j) { return g_Z + (256 + kb * 8 + j) * ZB; }
__device__ __forceinline__ void combine8(float m0, float q0, float m1, float q1, float n, float eps, float& mean, float& rstd) {
  mean = qsum(m0 + m1) * 0.125f;
  float d0 = m0 - mean, d1 = m1 - mean;
  float M2 = qsum(q0 + q1 + n * (d0 * d0 + d1 * d1));
  rstd = rsqrtf(fmaf(M2, 0.125f / n, eps));
}
__device__ __forceinline__ void stat_get(const uint4* zs, uint32_t tag, float n, float eps, float& m0, float& r0, float& m1, float& r1) {
  uint4 a0, a1, b0, b1;
#pragma unroll 1
  for (int it = 0; it < (1 << 20); it++) {
    a0 = ll_ld128(zs); a1 = ll_ld128(zs + 64); b0 = ll_ld128(zs + 8); b1 = ll_ld128(zs + 72);
    if (__all_sync(~0u, a0.z == tag && a1.z == tag && b0.z == tag && b1.z == tag)) break;
  }
  combine8(__uint_as_float(a0.x), __uint_as_float(a0.y), __uint_as_float(a1.x), __uint_as_float(a1.y), n, eps, m0, r0);
  combine8(__uint_as_float(b0.x), __uint_as_float(b0.y), __uint_as_float(b1.x), __uint_as_float(b1.y), n, eps, m1, r1);
}

__device__ __forceinline__ void rows_fetch(uint32_t el, uint32_t xr, const uint8_t* src, uint32_t bar) {
  expect_tx_p(el, bar, 9216);
#pragma unroll 1
  for (int r = 0; r < 8; r++) bulk_load_p(el, xr + r * 1152, src + r * (DM * 4), 1152, bar);
}
__device__ __forceinline__ void rows_stats(uint32_t xr, uint4* dst, uint32_t tag, int lane) {
  float s[2] = {0.f, 0.f}, q[4] = {0.f, 0.f, 0.f, 0.f};
  const uint32_t a0 = xr + (lane >> 2) * 1152 + (((lane & 3) * 2) ^ (lane >> 2)) * 16;
  uint4 n0 = lds128(a0), n1 = lds128(a0 ^ 16);
#pragma unroll 1
  for (int e = 1; e <= 9; e++) {
    const uint32_t x[8] = {n0.x, n0.y, n0.z, n0.w, n1.x, n1.y, n1.z, n1.w};
    if (e < 9) { n0 = lds128(a0 + e * 128); n1 = lds128((a0 ^ 16) + e * 128); }
#pragma unroll
    for (int u = 0; u < 8; u++) {
      const float lo = blo(x[u]), hi = bhi(x[u]);
      s[u & 1] += lo + hi; q[(u & 1) * 2] = fmaf(lo, lo, q[(u & 1) * 2]); q[(u & 1) * 2 + 1] = fmaf(hi, hi, q[(u & 1) * 2 + 1]);
    }
  }
  const float sx = s[0] + s[1], sq = (q[0] + q[1]) + (q[2] + q[3]);
  const float m = qsum(sx) * (-1.f / DM), r = rsqrtf(fmaxf(fmaf(qsum(sq), 1.f / DM, -m * m), 0.f) + LN_EPS);
  if ((lane & 3) == 0) ll_st128(dst + (lane >> 2) * 2, m, r, tag);
}

__global__ void __cluster_dims__(2, 1, 1) __launch_bounds__(384, 1) mega_kernel(const __grid_constant__ Params P) {
  extern __shared__ __align__(1024) uint8_t smem_raw[];
  uint32_t ckk[8];
  (void)ckk;
  CKK(0);
  const uint32_t sb = smem_u32(smem_raw);
  const uint32_t bars = sb + SM_BAR;
  const int tid = threadIdx.x;
  int lane = tid & 31;
  const int wid = __shfl_sync(~0u, tid >> 5, 0);
  const int cl = blockIdx.x >> 1, tp = cl - 36, t7 = (tp * 37) >> 8;
  const int bid = (cl < 4 ? cl * 8 + 32 : tp < 0 ? cl - 4 : cl < 64 ? tp + t7 + 33 : cl) * 2 + (blockIdx.x & 1);
  if (bid >= NCTA) return;
  const int rb = bid & 15, j = bid >> 4;
  { const bool tr = (tid & 127) == 0 && tid < 256; const int w = tid >> 7; (void)tr; (void)w; TRC(tr, w, 0); }
  CKK(1);
  uint4 wv[5];
  const uint8_t* wsrc;
  {
    const int n8 = min(tid >> 3, 26), part = n8 / 9;
    const uint8_t* src = (const uint8_t*)P.wqkv + (8 * rb + (tid & 7)) * (3 * DM * 2) + (part * (DM - 72) + 72 * j + 8 * n8) * 2;
#pragma unroll
    for (int u = 0; u < SPL; u++) wv[u] = ldnc128_if(tid < 216, src + u * (128 * 3 * DM * 2));
    wsrc = src;
  }
  CKK(2);
  if (tid == 352) {
    for (int s = 0; s < (int)NST; s++) {
      mbar_init(bars + B_FULL + s * 8, 1); mbar_init(bars + B_EMPTY + s * 8, 16);
      mbar_init(bars + B_FULLA + s * 8, 1); mbar_init(bars + B_FULLA + 32 + s * 8, 1);
      mbar_init(bars + B_RES + s * 8, 1); mbar_init(bars + B_RT + s * 8, 1); mbar_init(bars + B_AD + s * 8, 2);
    }
    mbar_init(bars + B_IMG, 8); mbar_init(bars + B_RES + 8, 8); mbar_init(bars + B_WOI, 8); mbar_init(bars + B_GATE3, 3); mbar_init(bars + B_Z1, 1); mbar_init(bars + B_ZB, 1); mbar_init(bars + B_LAG, 4);
    mbar_init(bars + B_CSQ, 3); mbar_init(bars + B_RT1, 1); mbar_init(bars + B_XRW, 1); mbar_init(bars + B_XRW + 8, 1);
    for (int e = 0; e < 2 * EV_N; e++) mbar_init(bars + B_EVT + e * 8, 4);
    asm volatile("fence.mbarrier_init.release.cluster;" ::: "memory");
  }
  if (tid == 320) {
#pragma unroll
    for (int e = 0; e < 28; e++) mbar_init(bars + B_FA3 + e * 8, e < 18 ? 1 : 4);
    asm volatile("fence.mbarrier_init.release.cluster;" ::: "memory");
  }
  __syncthreads();

  if (wid >= 8) {
    reg_dealloc<40>();
    const uint32_t el = elect_one();
    const uint64_t pol = policy_evict_first();
    uint32_t* const fj = g_flags + FJ + j * 32;
    if (wid == 8) {
      if (el) { prefetch_map(&P.act[0]); prefetch_map(&P.wsp); prefetch_map(&P.win); prefetch_map(&P.win64); prefetch_map(&P.wout); prefetch_map(&P.act[1]); prefetch_map(&P.res[0]); prefetch_map(&P.res[1]); prefetch_map(&P.red); }
      const uint32_t epoch = ldcg32(fj + FJ_EP + rb);
      Cur c{0, 1};
      const uint32_t rk = bid & 1;
      uint32_t st, full;
      auto slot = [&](uint32_t bytes) {
        st = sb + c.s * ST_BYTES; full = bars + B_FULL + c.s * 8;
        mbar_wait(full, c.ph);
        expect_tx_p(el, full, bytes);
        mbar_wait(full - B_FULL + B_EMPTY, c.ph);
      };
#pragma unroll 1
      for (int L = 0; L < 2; L++) {
#pragma unroll 1
        for (int i = 0; i < 14; i++) {
          if (L == 0 && (i == 0 || i == 2 * SPL || i == 9)) {
            flag_wait(fj + (i == 9 ? FJ_WO : i == 2 * SPL ? FJ_WQ : FJ_WQ0), (epoch + 1) * 16);
            if (i == 9) flag_wait(g_flags + FJ + (j ^ 1) * 32 + FJ_WO, (epoch + 1) * 16);
            fence_async_g();
            TRC(el, 2, i == 9 ? 46 : i ? 47 : 45);
          }
          const uint32_t hb = i < 9 ? 13824 : i < 13 ? 18432 : 9216, o = ST_B + rk * (i < 9 ? 13824 : 18432);
          const uint8_t* src = i < 9 ? g_WQ + j * WQ_SL + i * 27648 + rk * 13824 : g_WO + ((j & 6) + rk) * WO_SL + (i - 9) * 18432;
          slot(2 * hb);
          bulk_mc_h(el, st + o, src, hb, full, true, pol);
          c.next();
        }
#pragma unroll 1
        for (int i = 0; i < 18; i++) {
          const int p = i >> 1, col = p == 4 ? (9 * j + ((j & 1) ? 0 : 8)) * 32 : (((9 * j + 1) >> 1) + (p < 4 ? p + 36 : p - 5)) * 64;
          if (i & 1) {
            slot(2 * ZB);
          } else {
            st = sb + c.s * ST_BYTES; full = bars + B_FULL + ((c.s + 1) & 3) * 8;
            mbar_wait(bars + B_EMPTY + c.s * 8, c.ph);
          }
          tma4d_mc(el, st + ST_B + rk * 18432, p == 4 ? &P.win : &P.win64, col, (i & 1) * 36 + rk * 18, full, pol);
          if (el && !(i & 1)) mbar_arrive(bars + B_FULL + c.s * 8);
          c.next();
        }
        TRC(el, 2, L * 16 + 6);
        flag_wait(fj + FJ_ZN + L, (epoch + 1) * 16);
        fence_async_g();
        TRC(el, 2, L * 16 + 7);
#pragma unroll 1
        for (int i = 0; i < 32; i++) {
          const uint8_t* src = z2_block(i, j) + rk * 18432;
          if (i >= 4) mbar_wait(bars + B_AD + c.s * 8, ((i >> 2) & 1) ^ 1);
          slot(ST_BYTES);
          bulk_mc_h(el, st + ST_B + rk * 18432, src, 18432, full, true, pol);
          tma3d_h(el, st, &P.wsp, i * 64, rb * 64, 0, full, true, pol);
          c.next();
        }
        mbar_wait(bars + B_Z1, L);
        fence_async_g();
        expect_tx_p(el, bars + B_ZB, 20480);
        bulk_load_h(el, sb + SM_STG, z1_block(rb, 1, j) + 16384, 4096, bars + B_ZB, true, pol);
#pragma unroll 1
        for (int i = 0; i < 10; i++) {
          const int cb = i - 1 + j;
          if (i < 4) mbar_wait(bars + B_AD + c.s * 8, 1);
          slot(i == 1 ? ST_BYTES : ZB);
          if (i < 2) bulk_load_h(el, st, z1_block(rb, i, j) + i * 20480, ZB - i * 20480, full, true, pol);
          if (i == 0) bulk_load_h(el, st + ZB, z1_block(rb, 1, j), 16384, bars + B_ZB, true, pol);
          else tma2d_mc_h(el, st + ST_B + rk * 18432, &P.wout, (cb >= 9 ? cb - 9 : cb) * 64, 288 * j + rk * 144, full, true, pol);
          c.next();
        }
      }
    } else if (wid < 11) {
      int w = wid - 9;
      uint32_t* const fr = g_flags + (rb * 2 + w) * 32;
      const uint32_t epoch = ldcg32(fr + FR_EP + j);
      const uint32_t ev = bars + B_EVT + w * EV_N * 8, t8 = (epoch + 1) * 8;
      const int dp = ((j & 1) - w) * 32;
      Cur c{0, 1};
#pragma unroll 1
      for (int L = 0; L < 2; L++) {
#pragma unroll 1
        for (int ph = 0; ph < 3; ph++) {
          if (ph + L > 0) {
            uint32_t* f = fr + (ph == 0 ? FR_X2 : ph == 1 ? FR_O + L : FR_X1 + L);
            mbar_wait(ev + ph * 8, ph ? L : 0);
            TRC(el, 3, w * 32 + L * 16 + ph * 3);
            flag_release_p(el, ph == 2 ? f + dp : f);
            if (el && ph == 2) mbar_arrive(bars + B_GATE3);
            TRC(el, 3, w * 32 + L * 16 + ph * 3 + 1);
            if (ph == 1 && w == 1) {
              mbar_wait(ev - (EV_N - EV_O) * 8, L);
              expect_tx_p(el, bars + B_RES, 18432);
              tma3d_h(el, sb + SM_STG, &P.res[L], (j & 6) * 72, rb * 64, j & 1, bars + B_RES, !L, pol);
            }
            if (ph == 2) {
              if (lane < 2) mbar_arrive(bars + B_FULLA + w * 32 + ((c.s + lane) & 3) * 8);
              expect_tx_p(lane < 9, bars + B_FA3 + (9 * w + lane) * 8, 8192);
              flag_wait(f, t8);
              fence_async_g();
#pragma unroll 1
              for (int kb = 0; kb < 9; kb++) {
                const int n = 9 * w + kb;
                if (n >= 8) mbar_wait(bars + B_EA3 + (n - 8) * 8, L);
                tma3d_h(el, sb + ((n >> 1) & 3) * ST_BYTES + (n & 1) * 8192, &P.act[1], kb * 64, rb * 64, w, bars + B_FA3 + (9 * w + kb) * 8, false, pol);
                TRC(el && kb == 0, 3, w * 32 + L * 16 + ph * 3 + 2);
              }
              c.ph ^= ((c.s + 18) >> 2) & 1; c.s = (c.s + 18) & 3;
              break;
            }
            const uint32_t full = bars + B_FULLA + w * 32 + c.s * 8, dst = sb + c.s * ST_BYTES + w * 8192;
            mbar_wait(bars + B_EMPTY + c.s * 8, c.ph);
            expect_tx_p(el, full, 8192);
            flag_wait(ph == 1 ? f + dp : f, t8);
            fence_async_g();
            if (ph != 1) tma3d_h(el, dst, &P.act[1], 0, rb * 64, w, full, false, pol);
            else bulk_load_h(el, dst, z1_block(rb, j & 1, 0) + w * 8192, 8192, full, true, pol);
            c.next();
            TRC(el, 3, w * 32 + L * 16 + ph * 3 + 2);
          }
          const int n = ph == 0 ? 9 : 5;
          const uint32_t tag = epoch * 2 + L + 1;
          uint4* const xs = g_XST + (rb * 2 + w) * 128;
#pragma unroll 1
          for (int i = ph + L > 0; i < n; i++) {
            const uint32_t full = bars + B_FULLA + w * 32 + c.s * 8, dst = sb + c.s * ST_BYTES + w * 8192;
            if (ph + L == 0 && i == 4) {
              mbar_wait(bars + B_WT + w * 8, 0);
              TRC(el && w == 0, 2, 37);
              rows_stats(sb + SM_STG + w * 9216, xs + 16 * j, tag, lane);
              TRC(el && w == 0, 2, 38);
            }
            const bool none = ph == 1 && 2 * i + w > 8;
            mbar_wait(bars + B_EMPTY + c.s * 8, c.ph);
            expect_tx_p(el, full, none ? 0 : 8192);
            if (ph != 1) {
              tma3d_h(el, dst, &P.act[L], i * 64, rb * 64, w, full, false, pol);
            } else {
              if (!none) bulk_load_h(el, dst, z1_block(rb, j & 1, 0) + (2 * i + w) * 8192, 8192, full, true, pol);
            }
            c.next();
            if (ph + L == 0 && i == 3) rows_fetch(el, sb + SM_STG + w * 9216, P.xs[0] + (128 * rb + 16 * j + w) * (DM * 2), bars + B_WT + w * 8);
          }
          if (ph + L == 2) flag_wait(fj + FJ_P4, t8 * 4);
          if (ph == 0) {
            const uint32_t tab = sb + L * (2 * ST_BYTES) + SM_XST + w * 512 + lane * 8;
            TRC(el, 3, w * 32 + L * 16 + 13);
#pragma unroll 1
            for (int it = 0; it < (1 << 22); it++) {
              const uint4 a = ll_ld128(xs + 2 * lane), b = ll_ld128(xs + 64 + 2 * lane);
              if (__all_sync(~0u, a.z == tag && b.z == tag)) { sts64(tab, a.x, a.y); sts64(tab + 256, b.x, b.y); break; }
            }
            __syncwarp();
            if (el) mbar_arrive(bars + B_CSQ);
            TRC(el, 3, w * 32 + L * 16 + 14);
          }
        }
        asm volatile("" : "+r"(lane), "+r"(w));
        expect_tx_p(el, bars + B_WT + w * 8, 2048);
#pragma unroll 1
        for (int r = 0; r < 8; r++)
          bulk_load_p(el, sb + SM_WT + w * 2176 + r * 272, (const uint8_t*)P.w_sp + (size_t)(128 * rb + 16 * j + 2 * r + w) * (SEQ * 2) + 30 * 128, 256, bars + B_WT + w * 8);
        float cv = (lane & 3) ? 0.f : -blo(ldnc16(P.b_sp + 128 * rb + 16 * j + 2 * (lane >> 2) + w));
        mbar_wait(bars + B_RT, L);
        mbar_wait(bars + B_WT + w * 8, L ^ 1);
        mbar_wait(ev + EV_Z1 * 8, L);
        const uint32_t ro = (w * 64 + 8 * j + (lane >> 2)) * 128, x0 = ((lane & 3) * 2) ^ (lane >> 2);
#pragma unroll 1
        for (int i = 0; i < 32; i++) {
          const bool tail = (i >> 1) == 4;
          const int kb = tail ? i + 22 : i < 8 ? i : i - 2;
          if (i == 8) mbar_wait(bars + B_RT1, L);
          if (!tail) mbar_wait(bars + B_FULL + c.s * 8, c.ph ^ 1);
#pragma unroll
          for (int e = 0; e < 2; e++) {
            const uint4 a = lds128(!tail ? sb + c.s * ST_BYTES + ro + ((x0 ^ e) << 4) : sb + SM_WT + w * 2176 + (lane >> 2) * 272 + (i - 8) * 128 + (lane & 3) * 32 + e * 16);
            const uint4 m = lds128(sb + SM_RT + 4096 + kb * 128 + (lane & 3) * 32 + e * 16);
            cv = fmaf(blo(a.x), blo(m.x), fmaf(bhi(a.x), bhi(m.x), fmaf(blo(a.y), blo(m.y), fmaf(bhi(a.y), bhi(m.y), cv))));
            cv = fmaf(blo(a.z), blo(m.z), fmaf(bhi(a.z), bhi(m.z), fmaf(blo(a.w), blo(m.w), fmaf(bhi(a.w), bhi(m.w), cv))));
          }
          if (!tail) {
            mbar_arrive_if(el, bars + B_AD + c.s * 8 + (__float_as_uint(cv) & P.zero));
            c.next();
          }
        }
        TRC(el, 3, w * 32 + L * 16 + 11);
        uint32_t tag = t8;
        asm volatile("" : "+r"(tag));
        tag = (tag >> 2) - 1 + L;
        cv = qsum(cv);
        uint2* const cs = (uint2*)(g_XST + (rb * 2 + w) * 128 + 1);
        if ((lane & 3) == 0) ll_st64(cs + 32 * j + (lane >> 2) * 4, __float_as_uint(cv), tag);
#pragma unroll 1
        for (int it = 0; it < (1 << 22); it++) {
          const uint2 a = ll_ld64(cs + 4 * lane), b = ll_ld64(cs + 128 + 4 * lane);
          if (__all_sync(~0u, a.y == tag && b.y == tag)) { sts32(sb + SM_CV + w * 256 + lane * 4, a.x); sts32(sb + SM_CV + w * 256 + 128 + lane * 4, b.x); break; }
        }
        __syncwarp();
        if (el) mbar_arrive(bars + B_CV + w * 8);
        TRC(el, 3, w * 32 + L * 16 + 12);
#pragma unroll 1
        for (int kb = 30; kb < 32; kb++) {
          mbar_wait(bars + B_FULL + c.s * 8, c.ph ^ 1);
          if (el) mbar_arrive(bars + B_AD + c.s * 8);
          c.next();
        }
        c.ph ^= ((c.s + 10) >> 2) & 1; c.s = (c.s + 10) & 3;
        if (L == 0) {
          mbar_wait(ev + EV_P4 * 8, 0);
          flag_add_p(el, fj + FJ_P4);
        }
      }
    } else {
      const uint32_t epoch = ldcg32(fj + FJ_EP + rb);
      if (SPL) {
        mbar_wait(bars + B_RES + 8, 0);
        TRC(el, 2, 41);
        flag_release_p(el, fj + FJ_WQ0);
        TRC(el, 2, 42);
      }
      mbar_wait(bars + B_IMG, 0);
      TRC(el, 2, 39);
      flag_release_p(el, fj + FJ_WQ);
      TRC(el, 2, 40);
#pragma unroll 1
      for (int L = 0; L < 2; L++) {
        float* const csf = g_CSP + (NCTA + bid) * 216;
        if (L == 0) {
          flag_wait(fj + FJ_WQ, (epoch + 1) * 16);
          fence_async_g();
          expect_tx_p(el, bars + B_XRW, 13824);
          bulk_load_p(el, sb + ST_BYTES + SM_WOI, g_CSP + j * 16 * 216, 6912, bars + B_XRW);
          bulk_load_p(el, sb + 2 * ST_BYTES + SM_WOI, g_CSP + (j * 16 + 8) * 216, 6912, bars + B_XRW);
          mbar_wait(bars + B_XRW, 0);
#pragma unroll 1
          for (int f = lane; f < 54; f += 32) {
            float s[4] = {0.f, 0.f, 0.f, 0.f};
#pragma unroll 4
            for (int r = 0; r < 16; r++) {
              const uint4 v = lds128(sb + ST_BYTES + SM_WOI + (r >> 3) * ST_BYTES + (r & 7) * 864 + f * 16);
              s[0] += __uint_as_float(v.x); s[1] += __uint_as_float(v.y); s[2] += __uint_as_float(v.z); s[3] += __uint_as_float(v.w);
            }
            sts128(sb + SM_CSQ + f * 16, __float_as_uint(s[0]), __float_as_uint(s[1]), __float_as_uint(s[2]), __float_as_uint(s[3]));
            stg128(csf + f * 4, __float_as_uint(s[0]), __float_as_uint(s[1]), __float_as_uint(s[2]), __float_as_uint(s[3]));
          }
          __syncwarp();
          if (el) mbar_arrive(bars + B_CSQ);
        } else {
#pragma unroll 1
          for (int u = 0; u < 4; u++) {
            const int w = u & 1;
            if (u < 2) {
              flag_wait(g_flags + (rb * 2 + w) * 32 + FR_X2, (epoch + 1) * 8);
              fence_async_g();
              TRC(el, 2, 48 + u);
              rows_fetch(el, sb + SM_STG + w * 9216, P.xs[1] + (128 * rb + 16 * j + w) * (DM * 2), bars + B_XRW + w * 8);
            } else {
              mbar_wait(bars + B_XRW + w * 8, w ^ 1);
              TRC(el, 2, 48 + u);
              rows_stats(sb + SM_STG + w * 9216, g_XST + (rb * 2 + w) * 128 + 16 * j, epoch * 2 + 2, lane);
              TRC(el, 2, 50 + u);
            }
          }
          expect_tx_p(el, bars + B_CSQ, 864);
          bulk_load_p(el, sb + 2 * ST_BYTES + SM_CSQ, csf, 864, bars + B_CSQ);
        }
        if (L == 0) {
          TRC(el, 2, 43);
          mbar_wait(bars + B_WOI, 0);
          bulk_store_p(el, g_WO + j * WO_SL + rb * (41 * 128), sb + SM_WOI, (rb < 15 ? 41 : 33) * 128);
          publish_p(el, fj + FJ_WO);
          TRC(el, 2, 44);
          if (el) prefetch_l2((const uint8_t*)P.w_in + bid * 41472, 41472);
          uint4 y[4];
#pragma unroll
          for (int u = 0; u < 4; u++) y[u] = ldnc128((u < 2 ? (const uint8_t*)P.w_in + (100 + 300 * u) * (2 * FH * 2) + (FH + 1024 * u) * 2 : (const uint8_t*)P.w_sp + (1000 * u - 1500) * (SEQ * 2) + u * 1024) + lane * 16);
          float sq[2] = {0.f, 0.f};
#pragma unroll
          for (int u = 0; u < 4; u++) {
            const uint32_t x[4] = {y[u].x, y[u].y, y[u].z, y[u].w};
#pragma unroll
            for (int e = 0; e < 4; e++) sq[u >> 1] = fmaf(blo(x[e]), blo(x[e]), fmaf(bhi(x[e]), bhi(x[e]), sq[u >> 1]));
          }
          const float o0 = sqrtf(wsum(sq[0]) * (2.f * GA * GA * DM / 512.f)), o1 = sqrtf(wsum(sq[1]) * (C0S * C0S * SEQ / 512.f));
          const uint32_t off = (__float_as_uint(o0) & 0x7f800000u) >> 16 | 0x8000u | OFM;
          if (el) sts64(sb + SM_OFF, off * 0x10001u, min(__float_as_uint(o1) & 0x7f800000u, 0x7e000000u) | 0x00400000u);
        }
        if (el) mbar_arrive(bars + B_GATE3);
        const uint32_t tag = epoch * 2 + L + 1;
        asm volatile("" : "+r"(lane));
        mbar_wait(bars + B_EVT + EV_ZN * 8, L);
        mbar_wait(bars + B_EVT + (EV_N + EV_ZN) * 8, L);
        flag_release_p(el, fj + FJ_ZN + L);
        TRC(el, 2, L * 16 + 8);
        {
          uint4 v[4];
#pragma unroll 1
          for (int it = 0; it < (1 << 22); it++) {
            bool ok = true;
#pragma unroll
            for (int u = 0; u < 4; u++) { v[u] = ll_ld128(g_ZST + (rb * 2 + ((lane >> 1) & 1)) * 512 + ((lane & 1) * 4 + u) * 64 + 8 * j + (lane >> 2)); ok = ok && v[u].z == tag; }
            if (__all_sync(~0u, ok)) break;
          }
          float mean = __uint_as_float(v[0].x) + __uint_as_float(v[1].x) + __uint_as_float(v[2].x) + __uint_as_float(v[3].x), M2 = 0.f;
          mean = (mean + __shfl_xor_sync(~0u, mean, 1)) * 0.125f;
#pragma unroll
          for (int u = 0; u < 4; u++) { const float d = __uint_as_float(v[u].x) - mean; M2 += fmaf(288.f * d, d, __uint_as_float(v[u].y)); }
          M2 += __shfl_xor_sync(~0u, M2, 1);
          const float rs = blo(pack2(rsqrtf(fmaf(M2, 1.f / FH, 4.f * GA * GA * LN_EPS)), 0.f));
          if (!(lane & 1)) ll_st64(g_RT + 128 * rb + 16 * j + (lane >> 1), pack2(rs, rs * mean), tag);
        }
        TRC(el, 2, L * 16 + 10);
#pragma unroll 1
        for (int b = 0; b < 8; b++) {
          uint4 v[4];
#pragma unroll 1
          for (int it = 0; it < (1 << 22); it++) {
            bool ok = true;
#pragma unroll
            for (int u = 0; u < 4; u++) { v[u] = ll_ld128((const uint4*)g_RT + b * 128 + u * 32 + lane); ok = ok && v[u].y == tag && v[u].w == tag; }
            if (__all_sync(~0u, ok)) break;
          }
#pragma unroll
          for (int u = 0; u < 4; u++) {
            const uint32_t rt = sb + SM_RT + b * 512 + u * 128, ro = (lane >> 3) * 32 + (lane & 3) * 8 + ((lane >> 2) & 1) * 2;
            sts32(rt + 4096 + lane * 4, __byte_perm(v[u].x, v[u].z, 0x7632));
            asm volatile("st.shared.u16 [%0], %1;\nst.shared.u16 [%0 + 4], %2;" ::"r"(rt + ro), "h"((uint16_t)v[u].x), "h"((uint16_t)v[u].z) : "memory");
          }
          __syncwarp();
          if (el && (b == 1 || b == 7)) mbar_arrive(bars + (b == 1 ? B_RT : B_RT1));
          TRC(el && b < 2, 2, L * 16 + 11 + b);
        }
        TRC(el, 2, L * 16 + 9);
        mbar_wait(bars + B_EVT + EV_Z1 * 8, L);
        mbar_wait(bars + B_EVT + (EV_N + EV_Z1) * 8, L);
        fence_gpu();
        if (el) mbar_arrive(bars + B_Z1);
      }
    }
  } else {
    CKK(3);
    uint8_t* const wdst = P.wq + j * WQ_SL + rb * 3456 + tid * 16;
#pragma unroll
    for (int u = 0; u < SPL; u++) stg128_if(tid < 216, wdst + u * (16 * 3456), wv[u].x, wv[u].y, wv[u].z, wv[u].w);
    __syncwarp();
    if (lane == 0) mbar_arrive(bars + B_RES + 8);
    CKK(4);
    auto repack2 = [&]() {
#pragma unroll
      for (int u = SPL; u < 5; u++) stg128_if((u < 4 || rb < 8) && tid < 216, wdst + u * (16 * 3456), wv[u].x, wv[u].y, wv[u].z, wv[u].w);
      float s[8];
#pragma unroll
      for (int e = 0; e < 8; e++) s[e] = 0.f;
#pragma unroll
      for (int u = 0; u < 5; u++) {
        uint32_t x[4] = {wv[u].x, wv[u].y, wv[u].z, wv[u].w};
        asm volatile("" : "+r"(x[0]), "+r"(x[1]), "+r"(x[2]), "+r"(x[3]));
#pragma unroll
        for (int e = 0; e < 4; e++) { s[2 * e] += blo(x[e]); s[2 * e + 1] += bhi(x[e]); }
      }
#pragma unroll
      for (int m = 4; m; m >>= 1) {
#pragma unroll
        for (int e = 0; e < m; e++) s[e] = ((tid & m) ? s[e + m] : s[e]) + __shfl_xor_sync(~0u, (tid & m) ? s[e] : s[e + m], m);
      }
      stg32_if(tid < 216, P.csp + bid * 216 + tid, __float_as_uint(s[0]));
      __syncwarp();
      if (lane == 0) mbar_arrive(bars + B_IMG);
    };
    reg_alloc<232>();
    CKK(5);
#pragma unroll
    for (int v = SPL; v < 5; v++) wv[v] = ldnc128_if(tid < 216 && (v < 4 || rb < 8), wsrc + v * (128 * 3 * DM * 2));
    repack2();
    CKK(6);
    const int w = wid >> 2, q = wid & 3;
    int g = lane >> 2, t = lane & 3;
    const uint32_t ev = bars + B_EVT + w * EV_N * 8;
    const bool tr = (tid & 127) == 0;
    (void)tr;
    Cur c{0, 0};
    const uint32_t ebar = mapa(bars + B_EMPTY, (bid & 1) ^ (lane & 1));
    auto release = [&](uint32_t s, uint32_t dep = 0) { mbar_arrive_cluster_if(lane < 2, ebar + s * 8 + dep); };
    const uint32_t stg = sb + SM_STG + w * 9216;
    uint32_t ia = 0;
    auto wait_ab = [&]() { mbar_wait_c(bars + B_FULL + c.s * 8, c.ph); mbar_wait_c(bars + B_FULLA + w * 32 + c.s * 8, (ia >> 2) & 1); ia++; };
    uint32_t lagph = 0;
    auto yield = [&](int left, int lag) { if (w == 1 && left == lag) mbar_wait_c(bars + B_LAG, lagph); };
    auto yield_done = [&]() { if (w == 0 && lane == 0) mbar_arrive(bars + B_LAG); };
    auto signal = [&](int e) { __syncwarp(); if (lane == 0) mbar_arrive(ev + e * 8); };

    auto fetch_wo = [&]() {
#pragma unroll 1
      for (int u = tid; u < 328; u += 256) {
        const int m = min(41 * rb + (u >> 3), 647), k8 = m / 9;
        cp_async16(sb + SM_WOI + u * 16, (const uint8_t*)P.wo + (8 * k8 + (u & 7)) * (DM * 2) + (72 * j + 8 * (m - k8 * 9)) * 2);
      }
    };
    const uint32_t epoch = ldcg32(g_flags + (rb * 2 + w) * 32 + FR_EP + j);
    TRC(tr, w, 1);
    CKK(7);
    CKK_OUT;

#pragma unroll 1
    for (int L = 0; L < 2; L++) {
      const int tb = 2 + L * 24;
      asm volatile("" : "+r"(lane), "+r"(g), "+r"(t));
      (void)tb;
      ia = 0;
      const uint32_t tag = epoch * 2 + L + 1;
      uint32_t aoff = (w * 64 + q * 16 + (lane & 15)) * 128 + (((lane >> 4) ^ (lane & 7)) << 4);
      {
        uint32_t Pk[27][2];
        float sc0, sc1;
        const uint32_t att = stg + 2 * q * 128 + lane * 4;
        uint4* hp = g_HALO + ((((rb - (q == 0)) * 2 + w) * 8 + j) * 6) * 32 + lane;
        uint8_t* od = z1_block(rb, w, 0) + (9 * j) * 1024 + (2 * q) * 128 + lane * 4;
        ACLK_INIT;
        {
          float acc[108];
#pragma unroll
          for (int i = 0; i < 108; i++) acc[i] = 0.f;
          uint32_t prev = 0;
#pragma unroll 1
          for (int kb = 0; kb < 9; kb++) {
            wait_ab();
            yield(9 - kb, LAG1);
            TRC(tr && kb == 0, w, tb + 0);
            MCLK(kb == 0, 0);
            PCLK(kb * 4);
            const uint32_t st = sb + c.s * ST_BYTES, da = dlo(st + w * 8192, 16), db = dlo(st + ST_B, 3456);
            wgmma_fence();
#pragma unroll
            for (int kk = 0; kk < 4; kk++) {
              wgmma_ss_n216(acc, dsc<1024, 1>(da, kk * 32), dsc<128, 0>(db, kk * 6912), 1);
              if (kk == 0) { wgmma_commit(); wgmma_wait<1>(); if (kb > 0) release(prev); }
            }
            wgmma_commit();
            if (kb == 8) yield_done();
            PCLK(kb * 4 + 1);
            if (kb == 0 && L == 0) fetch_wo();
            if (kb == 3 && L == 0) {
              asm volatile("cp.async.wait_all;" ::: "memory");
              fence_async_s();
              __syncwarp();
              if (lane == 0) mbar_arrive(bars + B_WOI);
            }
            PCLK(kb * 4 + 2);
            PCLK(kb * 4 + 3);
            prev = c.s; c.next();
          }
          const uint32_t cs = sb + prev * ST_BYTES + SM_CSQ + t * 8;
          mbar_wait_c(bars + B_CSQ, L);
          const float2 n0 = lds64f(sb + prev * ST_BYTES + SM_XST + w * 512 + (16 * q + g) * 8), n1 = lds64f(sb + prev * ST_BYTES + SM_XST + w * 512 + (16 * q + g + 8) * 8);
          const float m0 = n0.x, r0 = n0.y, m1 = n1.x, r1 = n1.y;
          float2 cv[27];
#pragma unroll
          for (int G = 0; G < 27; G++) cv[G] = lds64f(cs + G * 32);
          PCLK(36);
          wgmma_wait<0>();
          PCLK(37);
          uint32_t dep = P.zero & __float_as_uint(m0) & __float_as_uint(m1);
#pragma unroll
          for (int G = 0; G < 27; G++) dep &= __float_as_uint(cv[G].x);
          release(prev, dep);
          lagph ^= 1;
          TRC(tr, w, tb + 1);
          MCLK(1, 1);
          ACLK(0);
#pragma unroll
          for (int G = 9; G < 27; G++) Pk[G][1] = pack2(fmaf(m1, cv[G].x, acc[4 * G + 2]) * r1, fmaf(m1, cv[G].y, acc[4 * G + 3]) * r1);
          if (q < 3) {
#pragma unroll
            for (int i = 0; i < 18; i++) sts32(att + 256 + (i >> 1) * 1024 + (i & 1) * 128, Pk[9 + i][1]);
          } else if (rb < 15) {
#pragma unroll
            for (int i = 0; i < 6; i++) ll_st128(hp + i * 32, __uint_as_float(Pk[9 + 3 * i][1]), __uint_as_float(Pk[10 + 3 * i][1]), tag, __uint_as_float(Pk[11 + 3 * i][1]));
          }
#pragma unroll
          for (int G = 0; G < 27; G++) {
            if (G < 9) {
              Pk[G][0] = pack2(fmaf(m0, cv[G].x, acc[4 * G]), fmaf(m0, cv[G].y, acc[4 * G + 1]));
              Pk[G][1] = pack2(fmaf(m1, cv[G].x, acc[4 * G + 2]), fmaf(m1, cv[G].y, acc[4 * G + 3]));
            } else {
              Pk[G][0] = pack2(fmaf(m0, cv[G].x, acc[4 * G]) * r0, fmaf(m0, cv[G].y, acc[4 * G + 1]) * r0);
            }
          }
          sc0 = r0 * (0.23570226039551584f * 1.4426950408889634f); sc1 = r1 * (0.23570226039551584f * 1.4426950408889634f);
        }
        ACLK(1);
        constexpr int GA_[4] = {0, 2, 4, 7}, GB_[4] = {1, 3, 5, 8}, GC_[4] = {2, 4, 6, 6};
        float S1[4][4], S2[4][4];
        uint32_t qa[4][2], qc[4][2];
#pragma unroll
        for (int h = 0; h < 4; h++) {
#pragma unroll
          for (int r = 0; r < 2; r++) {
            qa[h][r] = (h == 0 || h == 3 || t >= h) ? Pk[GA_[h]][r] : 0u;
            qc[h][r] = (h == 3 ? t == 3 : t <= h) ? Pk[GC_[h]][r] : 0u;
          }
#pragma unroll
          for (int i = 0; i < 4; i++) S1[h][i] = S2[h][i] = 0.f;
          mma16(S1[h], qa[h][0], qa[h][1], Pk[GB_[h]][0], Pk[GB_[h]][1], Pk[9 + GA_[h]][0], Pk[9 + GB_[h]][0]);
          mma16(S2[h], qa[h][0], qa[h][1], Pk[GB_[h]][0], Pk[GB_[h]][1], Pk[9 + GA_[h]][1], Pk[9 + GB_[h]][1]);
        }
#pragma unroll
        for (int h = 0; h < 4; h++) {
          mma8(S1[h], qc[h][0], qc[h][1], Pk[9 + GC_[h]][0]);
          mma8(S2[h], qc[h][0], qc[h][1], Pk[9 + GC_[h]][1]);
        }
        uint32_t V1[9], V2[9];
#pragma unroll
        for (int i = 0; i < 9; i++) { V1[i] = movm(Pk[18 + i][0]); V2[i] = movm(Pk[18 + i][1]); }
        const bool remote = q == 0 && rb > 0;
        uint4 hv[6];
#pragma unroll
        for (int i = 0; i < 6; i++) hv[i] = make_uint4(0u, 0u, tag, 0u);
        if (remote) {
#pragma unroll
          for (int i = 0; i < 6; i++) hv[i] = ll_ld128(hp + i * 32);
        }
        const bool up0 = 2 * t > g, up1 = 2 * t + 1 > g;
        const uint32_t mup = (up0 ? 0xffffu : 0u) | (up1 ? 0xffff0000u : 0u);
        auto finish = [&](const float (&x0)[4], const float (&x1)[4], const uint32_t (&Va)[9], const uint32_t (&Vb)[9], int hi) {
          uint32_t p[4];
          float rs[4];
#pragma unroll
          for (int h = 0; h < 4; h++) {
            const float m = qmax(fmaxf(x0[h], x1[h]));
            p[h] = pack2(ex2(x0[h] - m), ex2(x1[h] - m));
            rs[h] = rcp_fast(qsum(blo(p[h]) + bhi(p[h])));
          }
#pragma unroll
          for (int i = 0; i < 9; i++) {
            const int h = 4 * i / 9;
            const bool split = i == 2 || i == 4 || i == 6, nx = split && 2 * t >= i;
            float O[4] = {0.f, 0.f, 0.f, 0.f}, N[4] = {0.f, 0.f, 0.f, 0.f};
            mma16(O, p[h] & mup, 0u, p[h] & ~mup, 0u, Va[i], Vb[i]);
            if (split) mma16(N, p[h + 1] & mup, 0u, p[h + 1] & ~mup, 0u, Va[i], Vb[i]);
            const float r = nx ? rs[h + (split ? 1 : 0)] : rs[h];
            stg32(od + i * 1024 + hi * 128, pack2((nx ? N[0] : O[0]) * r, (nx ? N[1] : O[1]) * r));
          }
        };
        {
          float x0[4], x1[4];
#pragma unroll
          for (int h = 0; h < 4; h++) { x0[h] = (up0 ? S1[h][2] : S2[h][2]) * sc1; x1[h] = (up1 ? S1[h][3] : S2[h][3]) * sc1; }
          finish(x0, x1, V1, V2, 1);
        }
        ACLK(2);
        bar_sync(1 + w, 128);
        uint32_t H[18];
        if (q > 0) {
#pragma unroll
          for (int i = 0; i < 18; i++) H[i] = lds32(att + (i >> 1) * 1024 + (i & 1) * 128);
        } else {
#pragma unroll 1
          for (int it = 0; it < (1 << 20); it++) {
            bool ok = true;
#pragma unroll
            for (int i = 0; i < 6; i++) ok = ok && hv[i].z == tag;
            if (__all_sync(~0u, ok)) break;
#pragma unroll
            for (int i = 0; i < 6; i++) hv[i] = ll_ld128(hp + i * 32);
          }
#pragma unroll
          for (int i = 0; i < 6; i++) { H[3 * i] = hv[i].x; H[3 * i + 1] = hv[i].y; H[3 * i + 2] = hv[i].w; }
        }
        float S0[4][4];
#pragma unroll
        for (int h = 0; h < 4; h++) {
#pragma unroll
          for (int i = 0; i < 4; i++) S0[h][i] = 0.f;
          mma16(S0[h], qa[h][0], 0u, Pk[GB_[h]][0], 0u, H[GA_[h]], H[GB_[h]]);
        }
#pragma unroll
        for (int h = 0; h < 4; h++) mma8(S0[h], qc[h][0], 0u, H[GC_[h]]);
        uint32_t V0[9];
#pragma unroll
        for (int i = 0; i < 9; i++) V0[i] = movm(H[9 + i]);
        ACLK(3);
        {
          const bool nohalo = (rb | q) == 0;
          float x0[4], x1[4];
#pragma unroll
          for (int h = 0; h < 4; h++) {
            x0[h] = up0 && nohalo ? -INFINITY : (up0 ? S0[h][0] : S1[h][0]) * sc0;
            x1[h] = up1 && nohalo ? -INFINITY : (up1 ? S0[h][1] : S1[h][1]) * sc0;
          }
          finish(x0, x1, V0, V1, 0);
        }
        ACLK(4);
        signal(EV_O);
        ACLK_OUT;
        TRC(tr, w, tb + 2);
        MCLK(1, 2);
      }
      {
        float acc[36];
        const int hw = rb * 2 + (j & 1), js = (j & 6) + w;
        const uint32_t xt = sb + SM_STG + (16 * q + g) * 288 + w * 144 + t * 4;
        uint32_t xm = sb + SM_STG + (16 * q + (lane & 15)) * 288 + (((9 * w + (lane >> 4)) ^ ((lane >> 2) & 1)) << 4), xl = sb + SM_STG + (2 * q + w) * 2304 + lane * 16;
        uint8_t* xd[5];
#pragma unroll
        for (int u = 0; u < 5; u++) {
          const int row = ((u * 32 + lane) * 57) >> 10;
          xd[u] = P.xs[1] + (128 * rb + 32 * q + 16 * w + (j & 1)) * (DM * 2) + (j & 6) * 144 + row * (DM * 4 - 288) + u * 512 + ((lane ^ (row >> 2)) << 4);
          asm volatile("" : "+l"(xd[u]));
        }
        asm volatile("" : "+r"(xm), "+r"(xl));
        mbar_wait_c(bars + B_RES, L);
        TRC(tr, w, tb + 21);
#pragma unroll
        for (int i = 0; i < 18; i++) { const uint32_t x = lds32(xt + (i >> 1) * 16 + (i & 1) * 2304); acc[2 * i] = blo(x); acc[2 * i + 1] = bhi(x); asm volatile("" : "+f"(acc[2 * i]), "+f"(acc[2 * i + 1])); }
        uint32_t prev = 0;
#pragma unroll 1
        for (int u = 0; u < 5; u++) {
          const uint32_t st = sb + c.s * ST_BYTES, da = dlo(st, 1024), db = dlo(st + ST_B + w * 18432, 1152);
          mbar_wait_c(bars + B_FULL + c.s * 8, c.ph); mbar_wait_c(bars + B_FULLA + c.s * 8, (ia >> 2) & 1);
          TRC(tr && u == 0, w, tb + 3);
          MCLK(u == 0, 3);
          wgmma_fence();
#pragma unroll
          for (int kk = 0; kk < 4; kk++) wgmma_ss_n72(acc, dsc<128, 0>(da, kk * 2048), dsc<128, 0>(db, kk * 2304), 1);
          wgmma_commit();
          wgmma_wait<1>();
          if (u > 0) release(prev);
          mbar_wait_c(bars + B_FULLA + 32 + c.s * 8, (ia >> 2) & 1);
          ia++;
          if (u == 4) break;
          wgmma_fence();
#pragma unroll
          for (int kk = 4; kk < 8; kk++) wgmma_ss_n72(acc, dsc<128, 0>(da, kk * 2048), dsc<128, 0>(db, kk * 2304), 1);
          wgmma_commit();
          prev = c.s; c.next();
        }
        RCLK_INIT;
        wgmma_wait<0>();
        RCLK(0);
        release(c.s);
        c.next();
        TRC(tr && P5TRACE != 5, w, tb + 4);
        MCLK(1, 4);
#pragma unroll
        for (int u = 0; u < 4; u++)
          stsm4(xm + u * 32, pack2(acc[8 * u], acc[8 * u + 1]), pack2(acc[8 * u + 2], acc[8 * u + 3]), pack2(acc[8 * u + 4], acc[8 * u + 5]), pack2(acc[8 * u + 6], acc[8 * u + 7]));
        asm volatile("stmatrix.sync.aligned.m8n8.x2.shared.b16 [%0], {%1,%2};" ::"r"(xm + 128), "r"(pack2(acc[32], acc[33])), "r"(pack2(acc[34], acc[35])) : "memory");
        RCLK(1);
        bar_sync(8 + q, 64);
        RCLK(2);
#pragma unroll
        for (int u = 0; u < 5; u++) {
          const uint4 v = lds128(xl + u * 512);
          stg128_if(u < 4 || lane < 16, xd[u], v.x, v.y, v.z, v.w);
        }
        RCLK(3);
        signal(EV_X1);
        RCLK(4);
        if (P.zero == 0) {
          float s0 = 0.f, s1 = 0.f, q0 = 0.f, q1 = 0.f;
#pragma unroll
          for (int i = 0; i < 36; i++) {
            if (i & 2) { s1 += acc[i]; q1 = fmaf(acc[i], acc[i], q1); } else { s0 += acc[i]; q0 = fmaf(acc[i], acc[i], q0); }
          }
          s0 = qsum(s0); s1 = qsum(s1); q0 = qsum(q0); q1 = qsum(q1);
          const float ss = t ? s1 : s0, m = ss * (1.f / 72.f);
          ll_st128_if(t < 2, g_ST1 + (hw * 8 + js) * 64 + 16 * q + 8 * t + g, m, fmaxf((t ? q1 : q0) - ss * m, 0.f), tag);
        }
        RCLK(5);
        TRC(tr, w, tb + 5);
        RCLK(6);
        RCLK_OUT;
      }
      {
        uint32_t xA[36][4];
        float acc[32];
        uint32_t s0, jump;
        uint64_t db;
        auto bwait = [&](uint32_t dhi) {
          s0 = c.s;
          c.next();
          mbar_wait_c(bars + B_FULL + c.s * 8, c.ph);
          db = dsc2(dlo(sb + s0 * ST_BYTES + ST_B, 512), 0, dhi + P.zero); jump = (c.s - s0) * (ST_BYTES >> 4) - 17 * 128;
        };
        auto mma = [&](int kk, int pp, bool hand) {
          wgmma_rs_n64(acc, xA[kk], db, kk != 0);
          dadd(db, kk == 17 ? jump : 128 + P.zero);
          if (kk == pp && hand) bar_arrive(7 - w, 256);
          if (kk == 17 || kk == 35) wgmma_commit();
          if (kk == 21) { wgmma_commit(); wgmma_wait<1>(); release(s0); }
        };
        {
          bwait(0x40000040u);
          mbar_wait_c(bars + B_GATE3, L);
          float mean0, mean1, rs0, rs1;
          stat_get(g_ST1 + ((rb * 2 + w) * 8 + 2 * t) * 64 + 16 * q + g, tag, 72.f, LN_EPS, mean0, rs0, mean1, rs1);
          const uint32_t ns0 = pack2(GA * rs0, GA * rs0), ns1 = pack2(GA * rs1, GA * rs1);
          const uint32_t nb0 = pack2(-mean0 * blo(ns0), -mean0 * blo(ns0)), nb1 = pack2(-mean1 * blo(ns1), -mean1 * blo(ns1));
          const uint32_t al = sb + (aoff & 8191);
#pragma unroll
          for (int kb = 0; kb < 9; kb++) {
            mbar_wait_c(bars + B_FA3 + (9 * w + kb) * 8, L);
            TRC(tr && kb == 0, w, tb + 6);
            MCLK(kb == 0, 5);
            if (kb == 0) SCLK(0);
            QCLK(kb);
            const uint32_t at = al + (w ? (((kb + 1) >> 1) & 3) * ST_BYTES + ((kb + 1) & 1) * 8192 : ((kb >> 1) & 3) * ST_BYTES + (kb & 1) * 8192);
#pragma unroll
            for (int kk = 4 * kb; kk < 4 * kb + 4; kk++) ldsm4(xA[kk], at ^ ((kk & 3) << 5));
            if (kb) { wgmma_fence(); mma(4 * kb - 2, PP30, w); mma(4 * kb - 1, PP30, w); }
            const uint32_t dep = xA[4 * kb][0] & xA[4 * kb + 1][0] & xA[4 * kb + 2][0] & xA[4 * kb + 3][0] & P.zero;
#pragma unroll
            for (int kk = 4 * kb; kk < 4 * kb + 4; kk++) {
#pragma unroll
              for (int e = 0; e < 4; e++) xA[kk][e] = hfma2(xA[kk][e], (e & 1) ? ns1 : ns0, (e & 1) ? nb1 : nb0);
            }
            mbar_arrive_if(lane == 0 && (kb == 0 || w == 0), bars + B_EA3 + (9 * w + kb) * 8 + dep);
            wgmma_fence();
            mma(4 * kb, PP30, w); mma(4 * kb + 1, PP30, w);
          }
          mma(34, PP30, w); mma(35, PP30, w);
        }
        const uint32_t off2 = lds32(sb + SM_OFF);
        uint8_t* z1d = z1_block(rb, w, j) + (tid & 127) * 16;
        uint8_t* zd = z2_block(2 * rb + (q >> 1), j) + (4 * (q & 1) + w) * 4608 + ((g & 3) * 2 + (g >> 2)) * 16 + t * 4;
        float sm[2] = {0.f, 0.f}, qq[2] = {0.f, 0.f};
        auto gelu = [&](auto nz2) {
          constexpr int NZ2 = nz2.value, R = 8 - NZ2, D = NZ2 == 8 ? GM2 : NZ2 ? GMM : GM1;
          float th[32], gb = GB;
          uint32_t qa = 0, qb = 0;
          auto head = [&](int G) {
#pragma unroll
            for (int e = 0; e < 4; e++) { const float v = acc[4 * G + e]; th[4 * G + e] = tanh_fast(v * fmaf(v, v, gb)); }
          };
#pragma unroll
          for (int i = 0; i < D; i++) head((i + R) & 7);
#pragma unroll
          for (int i = 0; i < 8; i++) {
            const int G = (i + R) & 7;
            if (i + D < 8) head((i + D + R) & 7);
            float* z = acc + 4 * G;
#pragma unroll
            for (int e = 0; e < 4; e++) z[e] = fmaf(z[e], th[4 * G + e], z[e]);
            uint32_t pa = pack2(z[0], z[1]), pb = pack2(z[2], z[3]), tok;
            if (i < NZ2) {
#pragma unroll
              for (int e = 0; e < 4; e++) { sm[e >> 1] += z[e]; qq[e >> 1] = fmaf(z[e], z[e], qq[e >> 1]); }
              pa = hsub2(pa, off2); pb = hsub2(pb, off2);
              stg32(zd + i * 128, pa); stg32(zd + i * 128 + 9216, pb);
              tok = pa ^ pb ^ __float_as_uint(fmaf(sm[0], sm[1], qq[0]) + qq[1]);
            } else {
              if (G & 1) stg128(z1d + (G >> 1) * 2048 + (NZ2 ? 32768 : 0), qa, qb, pa, pb);
              qa = pa; qb = pb;
              tok = pa ^ pb;
            }
            gb = __uint_as_float(tok * P.zero + __float_as_uint(GB));
          }
        };
#pragma unroll 1
        for (int p = 0;; p++) {
          wgmma_wait<0>();
          release(c.s);
          c.next();
          TRC(tr && p == 4, w, tb + 7);
          TRC(tr && p == 8, w, tb + 11);
          MCLK(p == 8, 6);
          SCLK(2 * p + 1);
          QCLK(10 + 3 * p);
          if (p < 4) {
            gelu(Int<8>{});
            zd += 1024;
          } else if (p == 4) {
            gelu(Int<4>{});
            signal(EV_ZN);
            const float a0 = qsum(sm[0]), a1 = qsum(sm[1]), q0 = qsum(qq[0]), q1 = qsum(qq[1]);
            const float ss = t ? a1 : a0, m = ss * (1.f / 288.f);
            ll_st128_if(t < 2, g_ZST + (rb * 2 + w) * 512 + j * 64 + 16 * q + 8 * t + g, m - blo(off2), fmaxf((t ? q1 : q0) - ss * m, 0.f), tag);
            TRC(tr, w, tb + 8);
            TRC(tr, w, tb + 9);
          } else {
            gelu(Int<0>{});
            z1d += 8192;
          }
          SCLK(2 * p + 2);
          QCLK(11 + 3 * p);
          if (p == 8) break;
          bwait(p == 3 ? 0x80000040u : 0x40000040u);
          bar_sync(6 + w, 256);
          TRC(tr && p == 4, w, tb + 10);
          wgmma_fence();
#pragma unroll
          for (int kk = 0; kk < 36; kk++) mma(kk, PP3, w == 0 || p < 7);
        }
        signal(EV_Z1);
        TRC(tr, w, tb + 12);
      }
      uint32_t hA[18][4];
      {
        float acc[144];
        const float c0 = __uint_as_float(lds32(sb + SM_OFF + 4));
#pragma unroll
        for (int i = 0; i < 144; i++) {
          asm volatile("fma.rn.f32 %0, %1, %2, %3;" : "=f"(acc[i]) : "f"(__uint_as_float(P.zero)), "f"((float)(i + 2)), "f"(c0));
        }
        uint32_t prev = 0;
        auto stage = [&](int kb) {
          mbar_wait_c(bars + B_FULL + c.s * 8, c.ph);
          TRC(tr && kb == 0, w, tb + 13);
          SCLK(22 + kb);
          const uint32_t st = sb + c.s * ST_BYTES, rt = sb + SM_RT + kb * 128 + t * 8;
          uint64_t db = dsc2(dlo(st + ST_B, 4608), 0, 8 + P.zero);
          uint32_t a[4][4];
#pragma unroll
          for (int kk = 0; kk < 4; kk++) {
            uint32_t r[4];
            ldsm4(r, st + (aoff ^ (kk << 5)));
            const uint2 sc = lds64(rt + kk * 32);
            a[kk][0] = hmul2(__byte_perm(r[0], r[2], 0x5410), sc.x); a[kk][2] = hmul2(__byte_perm(r[0], r[2], 0x7632), sc.y);
            a[kk][1] = hmul2(__byte_perm(r[1], r[3], 0x5410), sc.x); a[kk][3] = hmul2(__byte_perm(r[1], r[3], 0x7632), sc.y);
          }
          if (LAG4 && (kb & 1) == (LAG4 & 1)) yield(32 - kb, LAG4);
          wgmma_fence();
#pragma unroll
          for (int i = 0; i < 8; i++) {
            const int kk = i & 3, hf = i >> 2;
            wgmma_rs_n144(acc + hf * 72, a[kk], db, 1);
            dadd(db, i == 3 ? 144u - 3 * 576 : 576 + P.zero);
            if (i == 0) { wgmma_commit(); wgmma_wait<1>(); if (kb) release(prev); }
            if (i == 3) wgmma_commit();
          }
          wgmma_commit();
          prev = c.s; c.next();
        };
        mbar_wait_c(bars + B_RT, L);
#pragma unroll 1
        for (int kb = 0; kb < 32; kb += 2) {
          if (kb == 8) mbar_wait_c(bars + B_RT1, L);
          MCLK((kb & 7) == 4, 10 + (kb >> 3));
          stage(kb);
          stage(kb + 1);
        }
        if (LAG4) { yield_done(); lagph ^= 1; }
        HCLK(0);
        mbar_wait_c(bars + B_CV + w * 8, L);
        HCLK(1);
        const float gk = 0.5f / GA;
        const float c1 = __uint_as_float(lds32(sb + SM_OFF + 4));
        const float gb0 = -gk * (c1 + __uint_as_float(lds32(sb + SM_CV + w * 256 + (16 * q + g) * 4))), gb1 = -gk * (c1 + __uint_as_float(lds32(sb + SM_CV + w * 256 + (16 * q + g + 8) * 4)));
        mbar_wait_c(w ? bars + B_ZB : bars + B_FULL + c.s * 8, w ? L : c.ph);
        HCLK(2);
        const uint32_t sx = c.s;
        c.next();
        const uint32_t zt = sb + (tid & 127) * 16, zs0 = zt + sx * ST_BYTES + w * ZB, zs1 = w ? zt + SM_STG - 16384 : zs0, zs2 = w ? zt + c.s * ST_BYTES - 20480 : zs0;
#pragma unroll
        for (int u = 0; u < 18; u++) {
          if (u == 0) { wgmma_wait<1>(); HCLK(3); }
          if (u == 9) {
            HCLK(4);
            wgmma_wait<0>();
            HCLK(5);
            release(prev);
            if (L == 0) signal(EV_P4);
            if (w == 1) mbar_wait_c(bars + B_FULL + c.s * 8, c.ph);
            TRC(tr, w, tb + 14);
            SCLK(54);
          }
          const uint4 z = lds128((u < 8 ? zs0 : u < 10 ? zs1 : zs2) + u * 2048);
          hA[u][0] = hmul2(z.x, pack2(fmaf(acc[8 * u], gk, gb0), fmaf(acc[8 * u + 1], gk, gb0)));
          hA[u][1] = hmul2(z.y, pack2(fmaf(acc[8 * u + 2], gk, gb1), fmaf(acc[8 * u + 3], gk, gb1)));
          hA[u][2] = hmul2(z.z, pack2(fmaf(acc[8 * u + 4], gk, gb0), fmaf(acc[8 * u + 5], gk, gb0)));
          hA[u][3] = hmul2(z.w, pack2(fmaf(acc[8 * u + 6], gk, gb1), fmaf(acc[8 * u + 7], gk, gb1)));
        }
        uint32_t dep = P.zero;
#pragma unroll
        for (int u = 0; u < 18; u++) dep &= hA[u][0];
        release(sx, dep);
        TRC(tr, w, tb + 15);
        HCLK(6);
      }
      {
        CLK_INIT;
        if (w == 1) bar_arrive(6, 256);
        uint32_t pk[16];
#pragma unroll
        for (int i = 0; i < 16; i++) pk[i] = 0u;
        auto dump = [&](int p) {
          const uint32_t d = sb + (p & 3) * ST_BYTES, cb = p + j >= 9 ? p + j - 9 : p + j;
          if (lane == 0) asm volatile("cp.async.bulk.wait_group.read 3;" ::: "memory");
          __syncwarp();
#pragma unroll
          for (int u = 0; u < 4; u++) stsm4(d + (aoff ^ (u << 5)), pk[4 * u], pk[4 * u + 1], pk[4 * u + 2], pk[4 * u + 3]);
          fence_async_s();
          __syncwarp();
          tma3d_red_p(lane == 0, &P.red, cb * 64, rb * 64 + q * 16, w, d + w * 8192 + q * 2048);
        };
#pragma unroll 1
        for (int p = 0; p < 9; p++) {
          float acc[32];
          CLK(0);
          mbar_wait_c(bars + B_FULL + c.s * 8, c.ph);
          uint64_t db = dsc2(dlo(sb + c.s * ST_BYTES + ST_B + (j & 1) * 4096, 0), 0, 0x40000040u + P.zero);
          CLK(1);
          HCLK(7 + 2 * p);
          bar_sync(6 + w, 256);
          CLK(2);
          wgmma_fence();
#pragma unroll
          for (int kk = 0; kk < 18; kk++) {
            wgmma_rs_n64(acc, hA[kk], db, kk != 0);
            dadd(db, kk == 15 ? 128 - (j & 1) * (36864 >> 4) : 128 + P.zero);
            if (kk == PPK && (w == 0 || p < 8)) bar_arrive(7 - w, 256);
          }
          wgmma_commit();
          CLK(3);
          if (p > 0) dump(p - 1);
          CLK(5);
          wgmma_wait<0>();
          CLK(4);
          HCLK(8 + 2 * p);
          MCLK(p == 1 || p == 8, 7 + (p >> 3));
          if (L == 0 || p < 5) release(c.s);
          c.next();
#pragma unroll
          for (int i = 0; i < 16; i++) pk[i] = pack2(acc[2 * i], acc[2 * i + 1]);
          if (p == 8) { TRC(tr, w, tb + 16); dump(8); TRC(tr, w, tb + 17); }
        }
        if (lane == 0) asm volatile("cp.async.bulk.wait_group 0;" ::: "memory");
        HCLK(25);
        MCLK(1, 9);
        if (L == 0) signal(EV_PT);
        CLK_OUT;
        TRC(tr, w, tb + 18);
      }
    }
    if ((tid & 127) == 0) g_flags[(rb * 2 + w) * 32 + FR_EP + j] = epoch + 1;
    if (tid == 0) g_flags[FJ + j * 32 + FJ_EP + rb] = epoch + 1;
  }
}

typedef CUresult (*EncodeFn)(CUtensorMap*, CUtensorMapDataType, cuuint32_t, void*, const cuuint64_t*, const cuuint64_t*, const cuuint32_t*,
                             const cuuint32_t*, CUtensorMapInterleave, CUtensorMapSwizzle, CUtensorMapL2promotion, CUtensorMapFloatOOBfill);

static void make_map(EncodeFn fn, CUtensorMap* m, const void* ptr, int rank, uint64_t d0, uint64_t d1, uint64_t d2, uint64_t s1, uint64_t s2,
                     uint32_t b0, uint32_t b1, uint32_t b2, CUtensorMapSwizzle swz) {
  cuuint64_t dims[3] = {d0, d1, d2}, strides[2] = {s1, s2};
  cuuint32_t box[3] = {b0, b1, b2}, es[3] = {1, 1, 1};
  fn(m, CU_TENSOR_MAP_DATA_TYPE_BFLOAT16, rank, const_cast<void*>(ptr), dims, strides, box, es, CU_TENSOR_MAP_INTERLEAVE_NONE, swz,
     CU_TENSOR_MAP_L2_PROMOTION_L2_128B, CU_TENSOR_MAP_FLOAT_OOB_FILL_NONE);
}

}

extern "C" void kernel_launch(void* const* d_in, const int* in_sizes, int n_in, void* d_out, int out_size) {
  using namespace mk;
  (void)in_sizes; (void)n_in; (void)out_size;
  static EncodeFn fn = nullptr;
  static uint8_t* wq;
  static float* csp;
  if (!fn) {
    cudaGetSymbolAddress((void**)&wq, g_WQ);
    cudaGetSymbolAddress((void**)&csp, g_CSP);
    cudaDriverEntryPointQueryResult qr;
    cudaGetDriverEntryPoint("cuTensorMapEncodeTiled", (void**)&fn, cudaEnableDefault, &qr);
    cudaFuncSetAttribute(mega_kernel, cudaFuncAttributeMaxDynamicSharedMemorySize, SM_TOTAL);
  }
  Params p;
  p.wqkv = (const __nv_bfloat16*)d_in[1];
  p.wo = (const __nv_bfloat16*)d_in[2];
  p.w_in = (const __nv_bfloat16*)d_in[4];
  p.w_sp = (const __nv_bfloat16*)d_in[5];
  p.b_sp = (const __nv_bfloat16*)d_in[6];
  p.w_out = (const __nv_bfloat16*)d_in[7];
  p.zero = 0;
  p.wq = wq;
  p.csp = csp;
  p.xs[0] = (uint8_t*)d_in[0];
  p.xs[1] = (uint8_t*)d_out;
  make_map(fn, &p.wsp, p.w_sp, 3, 2048, 1024, 2, 8192, 4096, 64, 64, 2, CU_TENSOR_MAP_SWIZZLE_128B);
  for (int i = 0; i < 2; i++) {
    make_map(fn, &p.act[i], p.xs[i], 3, DM, 1024, 2, 2304, 1152, 64, 64, 1, CU_TENSOR_MAP_SWIZZLE_128B);
    make_map(fn, &p.res[i], p.xs[i], 3, DM, 1024, 2, 2304, 1152, 144, 64, 1, CU_TENSOR_MAP_SWIZZLE_NONE);
  }
  make_map(fn, &p.red, d_out, 3, DM, 1024, 2, 2304, 1152, 64, 16, 1, CU_TENSOR_MAP_SWIZZLE_128B);
  for (int i = 0; i < 2; i++) {
    cuuint64_t dims[4] = {i ? 4608u : 2304u, 8, i ? 1u : 2u, 72}, strides[3] = {9216, 4608, 8 * 9216};
    cuuint32_t box[4] = {i ? 64u : 32u, 8, i ? 1u : 2u, 18}, es[4] = {1, 1, 1, 1};
    fn(i ? &p.win64 : &p.win, CU_TENSOR_MAP_DATA_TYPE_BFLOAT16, 4, d_in[4], dims, strides, box, es, CU_TENSOR_MAP_INTERLEAVE_NONE,
       i ? CU_TENSOR_MAP_SWIZZLE_128B : CU_TENSOR_MAP_SWIZZLE_64B, CU_TENSOR_MAP_L2_PROMOTION_L2_128B, CU_TENSOR_MAP_FLOAT_OOB_FILL_NONE);
  }
  make_map(fn, &p.wout, p.w_out, 2, 576, 2304, 1, 1152, 0, 64, 144, 1, CU_TENSOR_MAP_SWIZZLE_128B);
  mega_kernel<<<NGRID, 384, SM_TOTAL, cudaStreamPerThread>>>(p);
}
```

```cpp
#include <cuda_runtime.h>
#include <cuda.h>
#include <cuda_bf16.h>
#include <stdint.h>

#define MK_TRACE 0
#define MK_DBG 0
#define P5TRACE 0
#define LAG1 1
#define PP3 32
#define PP30 33
#define LAG4 1
#define SPL 2
#define GM2 1
#define GMM 1
#define GM1 2
#define C0S 32.f
#define OFM 0x10u
#define PPK 13

namespace mk {

constexpr int SEQ = 2048, DM = 576, FH = 2304;
constexpr int NCTA = 128;
constexpr int NGRID = 132;
constexpr uint32_t ZB = 36864;
constexpr uint32_t WQ_SL = 72 * 3456;
constexpr uint32_t WO_SL = 72 * 1152;
constexpr float LN_EPS = 1e-5f;
constexpr float GA = 0.3292034911525734f, GB = 2.423681954311584f;

constexpr uint32_t ST_BYTES = 53248, ST_B = 16384, NST = 4;
constexpr uint32_t SM_STG = NST * ST_BYTES;
constexpr uint32_t SM_BAR = SM_STG + 2 * 9216;
constexpr uint32_t SM_OFF = SM_BAR + 1008;
constexpr uint32_t SM_TOTAL = SM_BAR + 1024;
constexpr uint32_t SM_RT = SM_STG + 4096, SM_CV = SM_STG + 12288, SM_WT = SM_CV + 512;
constexpr uint32_t SM_WOI = 44032, SM_CSQ = 49280, SM_XST = 50176;
constexpr uint32_t B_FULL = 0, B_EMPTY = 32, B_FULLA = 64, B_RES = 128, B_WT = 144, B_IMG = 160, B_WOI = 168, B_ZB = 176, B_GATE3 = 184, B_Z1 = 192, B_LAG = 200,
                   B_RT = 208, B_CSQ = 216, B_CV = 224, B_AD = 240, B_EVT = 272, B_RT1 = 368, B_XRW = 384, B_FA3 = 400, B_EA3 = 544;
enum { EV_PT = 0, EV_O = 1, EV_X1 = 2, EV_ZN = 3, EV_Z1 = 4, EV_P4 = 5, EV_N = 6 };

enum { FR_X2 = 0, FR_O = 1, FR_X1 = 3, FR_EP = 16, FJ = 32 * 32, FJ_WQ = 0, FJ_WO = 1, FJ_WQ0 = 2, FJ_ZN = 3, FJ_P4 = 5, FJ_EP = 16, F_N = FJ + 8 * 32 };

__device__ __align__(1024) uint8_t g_Z[512 * ZB];
__device__ __align__(1024) uint8_t g_WQ[8 * WQ_SL];
__device__ __align__(1024) uint8_t g_WO[8 * WO_SL];
__device__ __align__(1024) float g_CSP[2 * NCTA * 216];
__device__ __align__(1024) uint2 g_RT[SEQ];
__device__ __align__(1024) uint4 g_XST[2 * SEQ];
__device__ __align__(1024) uint4 g_ST1[SEQ * 8];
__device__ __align__(1024) uint4 g_ZST[SEQ * 8];
__device__ __align__(1024) uint4 g_HALO[32 * 8 * 6 * 32];
__device__ __align__(1024) uint32_t g_flags[F_N];

struct Params {
  const __nv_bfloat16 *wqkv;
  uint8_t* wq;
  float* csp;
  uint32_t zero;
  const __nv_bfloat16 *wo, *w_in, *w_sp, *b_sp, *w_out;
  uint8_t* xs[2];
  CUtensorMap wsp, win, win64, wout;
  CUtensorMap act[2];
  CUtensorMap res[2];
  CUtensorMap red;
};

__device__ __forceinline__ uint32_t smem_u32(const void* p) { return (uint32_t)__cvta_generic_to_shared(p); }
__device__ __forceinline__ void mbar_init(uint32_t bar, uint32_t cnt) { asm volatile("mbarrier.init.shared::cta.b64 [%0], %1;" ::"r"(bar), "r"(cnt)); }
__device__ __forceinline__ void mbar_arrive(uint32_t bar) { asm volatile("mbarrier.arrive.shared::cta.b64 _, [%0];" ::"r"(bar) : "memory"); }
__device__ __forceinline__ void mbar_wait(uint32_t bar, uint32_t parity) {
  asm volatile(
      "{\n.reg .pred p;\n.reg .u32 c;\nmov.u32 c, 0;\nLAB_WAIT:\n"
      "mbarrier.try_wait.parity.shared::cta.b64 p, [%0], %1;\n@p bra LAB_DONE;\n"
      "add.u32 c, c, 1;\nsetp.lt.u32 p, c, 0x100000;\n@p bra LAB_WAIT;\ntrap;\nLAB_DONE:\n}" ::"r"(bar), "r"(parity)
      : "memory");
}
__device__ __forceinline__ void mbar_wait_c(uint32_t bar, uint32_t parity) {
  asm volatile("{\n.reg .pred p;\nLAB_WAIT:\nmbarrier.try_wait.parity.shared::cta.b64 p, [%0], %1;\n@!p bra LAB_WAIT;\n}" ::"r"(bar), "r"(parity) : "memory");
}
__device__ __forceinline__ void flag_wait(const uint32_t* f, uint32_t target) {
  asm volatile(
      "{\n.reg .pred p;\n.reg .u32 c, v;\nmov.u32 c, 0;\nLAB_WAIT:\n"
      "ld.relaxed.gpu.global.u32 v, [%0];\nsub.u32 v, v, %1;\nsetp.ge.s32 p, v, 0;\n@p bra LAB_DONE;\n"
      "add.u32 c, c, 1;\nsetp.lt.u32 p, c, 0x400000;\n@p bra LAB_WAIT;\ntrap;\nLAB_DONE:\nfence.acquire.gpu;\n}" ::"l"(f), "r"(target)
      : "memory");
}
__device__ __forceinline__ void fence_gpu() { asm volatile("fence.acq_rel.gpu;" ::: "memory"); }
__device__ __forceinline__ void fence_async_g() { asm volatile("fence.proxy.async.global;" ::: "memory"); }
__device__ __forceinline__ void fence_async_s() { asm volatile("fence.proxy.async.shared::cta;" ::: "memory"); }
__device__ __forceinline__ uint32_t elect_one() {
  uint32_t p; asm volatile("{\n.reg .pred P;\nelect.sync _|P, 0xffffffff;\nselp.u32 %0, 1, 0, P;\n}" : "=r"(p)); return p;
}
__device__ __forceinline__ void expect_tx_p(uint32_t el, uint32_t bar, uint32_t bytes) {
  asm volatile("{\n.reg .pred P;\nsetp.ne.u32 P, %2, 0;\n@P mbarrier.arrive.expect_tx.shared::cta.b64 _, [%0], %1;\n}" ::"r"(bar), "r"(bytes), "r"(el) : "memory");
}
__device__ __forceinline__ void bulk_load_p(uint32_t el, uint32_t dst, const void* src, uint32_t bytes, uint32_t bar) {
  asm volatile("{\n.reg .pred P;\nsetp.ne.u32 P, %4, 0;\n@P cp.async.bulk.shared::cluster.global.mbarrier::complete_tx::bytes [%0], [%1], %2, [%3];\n}" ::"r"(dst), "l"(src), "r"(bytes), "r"(bar), "r"(el) : "memory");
}
__device__ __forceinline__ uint64_t policy_evict_first() { uint64_t p; asm("createpolicy.fractional.L2::evict_first.b64 %0, 1.0;" : "=l"(p)); return p; }
__device__ __forceinline__ void bulk_load_h(uint32_t el, uint32_t dst, const void* src, uint32_t bytes, uint32_t bar, bool ef, uint64_t pol) {
  if (ef) {
    asm volatile("{\n.reg .pred P;\nsetp.ne.u32 P, %4, 0;\n@P cp.async.bulk.shared::cluster.global.mbarrier::complete_tx::bytes.L2::cache_hint [%0], [%1], %2, [%3], %5;\n}" ::"r"(dst), "l"(src), "r"(bytes), "r"(bar), "r"(el), "l"(pol) : "memory");
  } else {
    asm volatile("{\n.reg .pred P;\nsetp.ne.u32 P, %4, 0;\n@P cp.async.bulk.shared::cluster.global.mbarrier::complete_tx::bytes [%0], [%1], %2, [%3];\n}" ::"r"(dst), "l"(src), "r"(bytes), "r"(bar), "r"(el) : "memory");
  }
}
__device__ __forceinline__ void bulk_mc_h(uint32_t el, uint32_t dst, const void* src, uint32_t bytes, uint32_t bar, bool ef, uint64_t pol) {
  if (ef) {
    asm volatile("{\n.reg .pred P;\nsetp.ne.u32 P, %4, 0;\n@P cp.async.bulk.shared::cluster.global.mbarrier::complete_tx::bytes.multicast::cluster.L2::cache_hint [%0], [%1], %2, [%3], %5, %6;\n}" ::"r"(dst), "l"(src), "r"(bytes), "r"(bar), "r"(el), "h"((uint16_t)3), "l"(pol) : "memory");
  } else {
    asm volatile("{\n.reg .pred P;\nsetp.ne.u32 P, %4, 0;\n@P cp.async.bulk.shared::cluster.global.mbarrier::complete_tx::bytes.multicast::cluster [%0], [%1], %2, [%3], %5;\n}" ::"r"(dst), "l"(src), "r"(bytes), "r"(bar), "r"(el), "h"((uint16_t)3) : "memory");
  }
}
__device__ __forceinline__ void tma3d_h(uint32_t el, uint32_t dst, const CUtensorMap* m, int c0, int c1, int c2, uint32_t bar, bool ef, uint64_t pol) {
  if (ef) {
    asm volatile("{\n.reg .pred P;\nsetp.ne.u32 P, %6, 0;\n@P cp.async.bulk.tensor.3d.shared::cluster.global.mbarrier::complete_tx::bytes.L2::cache_hint [%0], [%1, {%3, %4, %5}], [%2], %7;\n}" ::"r"(dst), "l"(m), "r"(bar), "r"(c0), "r"(c1), "r"(c2), "r"(el), "l"(pol) : "memory");
  } else {
    asm volatile("{\n.reg .pred P;\nsetp.ne.u32 P, %6, 0;\n@P cp.async.bulk.tensor.3d.shared::cluster.global.mbarrier::complete_tx::bytes [%0], [%1, {%3, %4, %5}], [%2];\n}" ::"r"(dst), "l"(m), "r"(bar), "r"(c0), "r"(c1), "r"(c2), "r"(el) : "memory");
  }
}
__device__ __forceinline__ void tma2d_mc_h(uint32_t el, uint32_t dst, const CUtensorMap* m, int c0, int c1, uint32_t bar, bool ef, uint64_t pol) {
  if (ef) {
    asm volatile("{\n.reg .pred P;\nsetp.ne.u32 P, %5, 0;\n@P cp.async.bulk.tensor.2d.shared::cluster.global.mbarrier::complete_tx::bytes.multicast::cluster.L2::cache_hint [%0], [%1, {%3, %4}], [%2], %6, %7;\n}" ::"r"(dst), "l"(m), "r"(bar), "r"(c0), "r"(c1), "r"(el), "h"((uint16_t)3), "l"(pol) : "memory");
  } else {
    asm volatile("{\n.reg .pred P;\nsetp.ne.u32 P, %5, 0;\n@P cp.async.bulk.tensor.2d.shared::cluster.global.mbarrier::complete_tx::bytes.multicast::cluster [%0], [%1, {%3, %4}], [%2], %6;\n}" ::"r"(dst), "l"(m), "r"(bar), "r"(c0), "r"(c1), "r"(el), "h"((uint16_t)3) : "memory");
  }
}
__device__ __forceinline__ void tma4d_mc(uint32_t el, uint32_t dst, const CUtensorMap* m, int c0, int c3, uint32_t bar, uint64_t pol) {
  asm volatile("{\n.reg .pred P;\nsetp.ne.u32 P, %5, 0;\n@P cp.async.bulk.tensor.4d.shared::cluster.global.mbarrier::complete_tx::bytes.multicast::cluster.L2::cache_hint [%0], [%1, {%3, 0, 0, %4}], [%2], %6, %7;\n}" ::"r"(dst), "l"(m), "r"(bar), "r"(c0), "r"(c3), "r"(el), "h"((uint16_t)3), "l"(pol) : "memory");
}
__device__ __forceinline__ void mbar_arrive_cluster(uint32_t addr) { asm volatile("mbarrier.arrive.shared::cluster.b64 _, [%0];" ::"r"(addr) : "memory"); }
__device__ __forceinline__ void mbar_arrive_cluster_if(bool c, uint32_t addr) {
  asm volatile("{\n.reg .pred P;\nsetp.ne.u32 P, %1, 0;\n@P mbarrier.arrive.shared::cluster.b64 _, [%0];\n}" ::"r"(addr), "r"((uint32_t)c) : "memory");
}
__device__ __forceinline__ void mbar_arrive_if(bool c, uint32_t addr) {
  asm volatile("{\n.reg .pred P;\nsetp.ne.u32 P, %1, 0;\n@P mbarrier.arrive.shared::cta.b64 _, [%0];\n}" ::"r"(addr), "r"((uint32_t)c) : "memory");
}
__device__ __forceinline__ uint32_t mapa(uint32_t addr, uint32_t rank) { uint32_t r; asm("mapa.shared::cluster.u32 %0, %1, %2;" : "=r"(r) : "r"(addr), "r"(rank)); return r; }
__device__ __forceinline__ void bulk_store_p(uint32_t el, void* dst, uint32_t src, uint32_t bytes) {
  asm volatile("{\n.reg .pred P;\nsetp.ne.u32 P, %3, 0;\n@P cp.async.bulk.global.shared::cta.bulk_group [%0], [%1], %2;\n}" ::"l"(dst), "r"(src), "r"(bytes), "r"(el) : "memory");
}
__device__ __forceinline__ void flag_release_p(uint32_t el, uint32_t* f) {
  asm volatile("{\n.reg .pred P;\nsetp.ne.u32 P, %1, 0;\n@P red.release.gpu.global.add.u32 [%0], 1;\n}" ::"l"(f), "r"(el) : "memory");
}
__device__ __forceinline__ void flag_add_p(uint32_t el, uint32_t* f) {
  asm volatile("{\n.reg .pred P;\nsetp.ne.u32 P, %1, 0;\n@P red.relaxed.gpu.global.add.u32 [%0], 1;\n}" ::"l"(f), "r"(el) : "memory");
}
__device__ __forceinline__ void prefetch_l2(const void* src, uint32_t bytes) { asm volatile("cp.async.bulk.prefetch.L2.global [%0], %1;" ::"l"(src), "r"(bytes) : "memory"); }
__device__ __forceinline__ void prefetch_map(const CUtensorMap* m) { asm volatile("prefetch.tensormap [%0];" ::"l"(m) : "memory"); }
__device__ __forceinline__ void wgmma_fence() { asm volatile("wgmma.fence.sync.aligned;" ::: "memory"); }
__device__ __forceinline__ void wgmma_commit() { asm volatile("wgmma.commit_group.sync.aligned;" ::: "memory"); }
template <int N> __device__ __forceinline__ void wgmma_wait() { asm volatile("wgmma.wait_group.sync.aligned %0;" ::"n"(N) : "memory"); }
__device__ __forceinline__ uint32_t dlo(uint32_t addr, uint32_t lbo) { return ((addr & 0x3FFFF) >> 4) + ((lbo >> 4) << 16); }
template <uint32_t SBO, uint32_t SWZ> __device__ __forceinline__ uint64_t dsc(uint32_t lo, uint32_t off) {
  uint64_t d; asm("mov.b64 %0, {%1, %2};" : "=l"(d) : "r"(lo + (off >> 4)), "n"((SBO >> 4) | (SWZ << 30))); return d;
}
__device__ __forceinline__ uint64_t dsc2(uint32_t lo, uint32_t off, uint32_t hi) {
  uint64_t d; asm("mov.b64 %0, {%1, %2};" : "=l"(d) : "r"(lo + (off >> 4)), "r"(hi)); return d;
}
__device__ __forceinline__ void dadd(uint64_t& d, uint32_t v) {
  asm("{\n.reg .b32 lo, hi;\nmov.b64 {lo, hi}, %0;\nadd.u32 lo, lo, %1;\nmov.b64 %0, {lo, hi};\n}" : "+l"(d) : "r"(v));
}
template <int R> __device__ __forceinline__ void reg_alloc() { asm volatile("setmaxnreg.inc.sync.aligned.u32 %0;" ::"n"(R)); }
template <int R> __device__ __forceinline__ void reg_dealloc() { asm volatile("setmaxnreg.dec.sync.aligned.u32 %0;" ::"n"(R)); }
__device__ __forceinline__ void bar_sync(int id, int n) { asm volatile("bar.sync %0, %1;" ::"r"(id), "r"(n) : "memory"); }
__device__ __forceinline__ void bar_arrive(int id, int n) { asm volatile("bar.arrive %0, %1;" ::"r"(id), "r"(n) : "memory"); }
__device__ __forceinline__ void ldsm4(uint32_t* r, uint32_t addr) {
  asm volatile("ldmatrix.sync.aligned.m8n8.x4.shared.b16 {%0,%1,%2,%3}, [%4];" : "=r"(r[0]), "=r"(r[1]), "=r"(r[2]), "=r"(r[3]) : "r"(addr) : "memory");
}
__device__ __forceinline__ uint32_t movm(uint32_t a) { uint32_t d; asm volatile("movmatrix.sync.aligned.m8n8.trans.b16 %0, %1;" : "=r"(d) : "r"(a)); return d; }
__device__ __forceinline__ void mma16(float* c, uint32_t a0, uint32_t a1, uint32_t a2, uint32_t a3, uint32_t b0, uint32_t b1) {
  asm volatile("mma.sync.aligned.m16n8k16.row.col.f32.bf16.bf16.f32 {%0,%1,%2,%3}, {%4,%5,%6,%7}, {%8,%9}, {%10,%10,%10,%10};"
               : "=f"(c[0]), "=f"(c[1]), "=f"(c[2]), "=f"(c[3]) : "r"(a0), "r"(a1), "r"(a2), "r"(a3), "r"(b0), "r"(b1), "f"(0.f));
}
__device__ __forceinline__ void mma8(float* c, uint32_t a0, uint32_t a1, uint32_t b0) {
  asm volatile("mma.sync.aligned.m16n8k8.row.col.f32.bf16.bf16.f32 {%0,%1,%2,%3}, {%4,%5}, {%6}, {%0,%1,%2,%3};"
               : "+f"(c[0]), "+f"(c[1]), "+f"(c[2]), "+f"(c[3]) : "r"(a0), "r"(a1), "r"(b0));
}
__device__ __forceinline__ uint32_t pack2(float lo, float hi) { uint32_t r; asm("cvt.rn.bf16x2.f32 %0, %1, %2;" : "=r"(r) : "f"(hi), "f"(lo)); return r; }
__device__ __forceinline__ float blo(uint32_t v) { return __uint_as_float(v << 16); }
__device__ __forceinline__ float bhi(uint32_t v) { return __uint_as_float(v & 0xffff0000u); }
__device__ __forceinline__ float tanh_fast(float x) { float y; asm("tanh.approx.f32 %0, %1;" : "=f"(y) : "f"(x)); return y; }
__device__ __forceinline__ float rcp_fast(float x) { float y; asm("rcp.approx.ftz.f32 %0, %1;" : "=f"(y) : "f"(x)); return y; }
__device__ __forceinline__ float ex2(float x) { float y; asm("ex2.approx.ftz.f32 %0, %1;" : "=f"(y) : "f"(x)); return y; }
__device__ __forceinline__ float qsum(float v) { v += __shfl_xor_sync(~0u, v, 1); v += __shfl_xor_sync(~0u, v, 2); return v; }
__device__ __forceinline__ float qmax(float v) { v = fmaxf(v, __shfl_xor_sync(~0u, v, 1)); v = fmaxf(v, __shfl_xor_sync(~0u, v, 2)); return v; }
__device__ __forceinline__ void stg32(void* p, uint32_t v) { asm volatile("st.global.u32 [%0], %1;" ::"l"(p), "r"(v) : "memory"); }
__device__ __forceinline__ void stg128(void* p, uint32_t a, uint32_t b, uint32_t c, uint32_t d) { asm volatile("st.global.v4.u32 [%0], {%1,%2,%3,%4};" ::"l"(p), "r"(a), "r"(b), "r"(c), "r"(d) : "memory"); }
__device__ __forceinline__ uint32_t ldcg32(const void* p) { uint32_t v; asm volatile("ld.global.L1::no_allocate.u32 %0, [%1];" : "=r"(v) : "l"(p) : "memory"); return v; }
__device__ __forceinline__ void stg128_if(bool c, void* p, uint32_t a, uint32_t b, uint32_t cc, uint32_t d) {
  asm volatile("{\n.reg .pred P;\nsetp.ne.u32 P, %5, 0;\n@P st.global.v4.u32 [%0], {%1,%2,%3,%4};\n}" ::"l"(p), "r"(a), "r"(b), "r"(cc), "r"(d), "r"((uint32_t)c) : "memory");
}
__device__ __forceinline__ uint2 lds64(uint32_t a) { uint2 v; asm volatile("ld.shared.v2.u32 {%0,%1}, [%2];" : "=r"(v.x), "=r"(v.y) : "r"(a) : "memory"); return v; }
__device__ __forceinline__ uint4 ldcg128(const void* p) { uint4 v; asm volatile("ld.global.cg.v4.u32 {%0,%1,%2,%3}, [%4];" : "=r"(v.x), "=r"(v.y), "=r"(v.z), "=r"(v.w) : "l"(p) : "memory"); return v; }
__device__ __forceinline__ uint32_t ldnc16(const void* p) { uint16_t v; asm volatile("ld.global.nc.u16 %0, [%1];" : "=h"(v) : "l"(p)); return v; }
__device__ __forceinline__ uint4 ldnc128(const void* p) { uint4 v; asm volatile("ld.global.nc.v4.u32 {%0,%1,%2,%3}, [%4];" : "=r"(v.x), "=r"(v.y), "=r"(v.z), "=r"(v.w) : "l"(p)); return v; }
__device__ __forceinline__ void cp_async16(uint32_t dst, const void* src) { asm volatile("cp.async.cg.shared.global [%0], [%1], 16;" ::"r"(dst), "l"(src) : "memory"); }
__device__ __forceinline__ uint32_t hsub2(uint32_t a, uint32_t b) { uint32_t d; asm("sub.rn.bf16x2 %0, %1, %2;" : "=r"(d) : "r"(a), "r"(b)); return d; }
__device__ __forceinline__ void stg32_if(bool c, void* p, uint32_t v) {
  asm volatile("{\n.reg .pred P;\nsetp.ne.u32 P, %2, 0;\n@P st.global.u32 [%0], %1;\n}" ::"l"(p), "r"(v), "r"((uint32_t)c) : "memory");
}
__device__ __forceinline__ float wsum(float v) { for (int o = 16; o; o >>= 1) v += __shfl_xor_sync(~0u, v, o); return v; }
__device__ __forceinline__ uint32_t hmul2(uint32_t a, uint32_t b) { uint32_t d; asm("mul.rn.bf16x2 %0, %1, %2;" : "=r"(d) : "r"(a), "r"(b)); return d; }
__device__ __forceinline__ void sts32(uint32_t a, uint32_t v) { asm volatile("st.shared.u32 [%0], %1;" ::"r"(a), "r"(v) : "memory"); }
__device__ __forceinline__ uint32_t lds32(uint32_t a) { uint32_t v; asm volatile("ld.shared.u32 %0, [%1];" : "=r"(v) : "r"(a) : "memory"); return v; }
__device__ __forceinline__ void sts128(uint32_t a, uint32_t x, uint32_t y, uint32_t z, uint32_t w) { asm volatile("st.shared.v4.u32 [%0], {%1,%2,%3,%4};" ::"r"(a), "r"(x), "r"(y), "r"(z), "r"(w) : "memory"); }
__device__ __forceinline__ uint4 lds128(uint32_t a) { uint4 v; asm volatile("ld.shared.v4.u32 {%0,%1,%2,%3}, [%4];" : "=r"(v.x), "=r"(v.y), "=r"(v.z), "=r"(v.w) : "r"(a) : "memory"); return v; }
__device__ __forceinline__ void ll_st64(uint2* p, uint32_t v, uint32_t tag) {
  asm volatile("{\n.reg .b64 r;\nmov.b64 r, {%1,%2};\nst.relaxed.gpu.global.b64 [%0], r;\n}" ::"l"(p), "r"(v), "r"(tag) : "memory");
}
__device__ __forceinline__ uint2 ll_ld64(const uint2* p) {
  uint2 v; asm volatile("{\n.reg .b64 r;\nld.relaxed.gpu.global.b64 r, [%2];\nmov.b64 {%0,%1}, r;\n}" : "=r"(v.x), "=r"(v.y) : "l"(p) : "memory"); return v;
}
__device__ __forceinline__ void ll_st128(uint4* p, float a, float b, uint32_t tag, float c = 0.f) {
  asm volatile("{\n.reg .b128 r;\n.reg .b64 lo, hi;\nmov.b64 lo, {%1,%2};\nmov.b64 hi, {%3,%4};\nmov.b128 r, {lo, hi};\nst.relaxed.gpu.global.b128 [%0], r;\n}" ::"l"(p), "r"(__float_as_uint(a)), "r"(__float_as_uint(b)), "r"(tag), "r"(__float_as_uint(c)) : "memory");
}
__device__ __forceinline__ uint4 ll_ld128(const uint4* p) {
  uint4 v; asm volatile("{\n.reg .b128 r;\n.reg .b64 lo, hi;\nld.relaxed.gpu.global.b128 r, [%4];\nmov.b128 {lo, hi}, r;\nmov.b64 {%0,%1}, lo;\nmov.b64 {%2,%3}, hi;\n}" : "=r"(v.x), "=r"(v.y), "=r"(v.z), "=r"(v.w) : "l"(p) : "memory"); return v;
}
__device__ __forceinline__ void publish_p(uint32_t el, uint32_t* f) {
  asm volatile("{\n.reg .pred P;\nsetp.ne.u32 P, %1, 0;\n@P cp.async.bulk.commit_group;\n@P cp.async.bulk.wait_group 0;\n@P red.release.gpu.global.add.u32 [%0], 1;\n}" ::"l"(f), "r"(el) : "memory");
}
__device__ __forceinline__ void tma3d_red_p(uint32_t el, const CUtensorMap* m, int c0, int c1, int c2, uint32_t src) {
  asm volatile("{\n.reg .pred P;\nsetp.ne.u32 P, %5, 0;\n@P cp.reduce.async.bulk.tensor.3d.global.shared::cta.add.tile.bulk_group [%0, {%2, %3, %4}], [%1];\n@P cp.async.bulk.commit_group;\n}" ::"l"(m), "r"(src), "r"(c0), "r"(c1), "r"(c2), "r"(el) : "memory");
}
__device__ __forceinline__ void stsm4(uint32_t addr, uint32_t a, uint32_t b, uint32_t c, uint32_t d) {
  asm volatile("stmatrix.sync.aligned.m8n8.x4.shared.b16 [%0], {%1,%2,%3,%4};" ::"r"(addr), "r"(a), "r"(b), "r"(c), "r"(d) : "memory");
}
__device__ __forceinline__ void sts64(uint32_t a, uint32_t x, uint32_t y) { asm volatile("st.shared.v2.u32 [%0], {%1,%2};" ::"r"(a), "r"(x), "r"(y) : "memory"); }
__device__ __forceinline__ void ll_st128_if(bool on, uint4* p, float a, float b, uint32_t tag) {
  asm volatile("{\n.reg .pred P;\n.reg .b128 r;\n.reg .b64 lo, hi;\nsetp.ne.u32 P, %4, 0;\nmov.b64 lo, {%1,%2};\nmov.b64 hi, {%3,%3};\nmov.b128 r, {lo, hi};\n@P st.relaxed.gpu.global.b128 [%0], r;\n}" ::"l"(p), "r"(__float_as_uint(a)), "r"(__float_as_uint(b)), "r"(tag), "r"((uint32_t)on) : "memory");
}
__device__ __forceinline__ uint4 ldnc128_if(bool c, const void* p) {
  uint4 v = make_uint4(0u, 0u, 0u, 0u);
  asm volatile("{\n.reg .pred P;\nsetp.ne.u32 P, %5, 0;\n@P ld.global.nc.v4.u32 {%0,%1,%2,%3}, [%4];\n}" : "+r"(v.x), "+r"(v.y), "+r"(v.z), "+r"(v.w) : "l"(p), "r"((uint32_t)c));
  return v;
}
__device__ __forceinline__ uint32_t hfma2(uint32_t a, uint32_t b, uint32_t c) { uint32_t d; asm("fma.rn.bf16x2 %0, %1, %2, %3;" : "=r"(d) : "r"(a), "r"(b), "r"(c)); return d; }
__device__ __forceinline__ float2 lds64f(uint32_t a) { float2 v; asm volatile("ld.shared.v2.f32 {%0,%1}, [%2];" : "=f"(v.x), "=f"(v.y) : "r"(a) : "memory"); return v; }
#define TRC(cond, role, idx) do {} while (0)
#define TRV(role, idx, v) do {} while (0)

#define ACLK_INIT do {} while (0)
#define ACLK(i) do {} while (0)
#define ACLK_OUT do {} while (0)
#define QCLK(i) do {} while (0)
#define PH 1
#define RCLK(i) do {} while (0)
#define RCLK_INIT do {} while (0)
#define RCLK_OUT do {} while (0)
#define SCLK(i) do {} while (0)
#define HCLK(i) do {} while (0)
#define MCLK(c, i) do {} while (0)
#define CKK(i) do {} while (0)
#define CKK_OUT do {} while (0)
#define PL 1
#define PCLK(i) do {} while (0)
#define PQ 1
#define CLK_INIT do {} while (0)
#define CLK(i) do {} while (0)
#define CLK_OUT do {} while (0)

__device__ __forceinline__ void wgmma_ss_n216(float* d, uint64_t da, uint64_t db, int scaleD) {
  asm volatile("{\n.reg .pred p;\nsetp.ne.b32 p, %110, 0;\nwgmma.mma_async.sync.aligned.m64n216k16.f32.bf16.bf16 "
    "{%0,%1,%2,%3,%4,%5,%6,%7,%8,%9,%10,%11,%12,%13,%14,%15,%16,%17,%18,%19,%20,%21,%22,%23,%24,%25,%26,%27,%28,%29,%30,%31,%32,%33,%34,%35,%36,%37,%38,%39,%40,%41,%42,%43,%44,%45,%46,%47,%48,%49,%50,%51,%52,%53,%54,%55,%56,%57,%58,%59,%60,%61,%62,%63,%64,%65,%66,%67,%68,%69,%70,%71,%72,%73,%74,%75,%76,%77,%78,%79,%80,%81,%82,%83,%84,%85,%86,%87,%88,%89,%90,%91,%92,%93,%94,%95,%96,%97,%98,%99,%100,%101,%102,%103,%104,%105,%106,%107}, "
    "%108, %109, p, 1, 1, 0, 1;\n}\n"
    : "+f"(d[0]), "+f"(d[1]), "+f"(d[2]), "+f"(d[3]), "+f"(d[4]), "+f"(d[5]), "+f"(d[6]), "+f"(d[7]), "+f"(d[8]), "+f"(d[9]), "+f"(d[10]), "+f"(d[11]), "+f"(d[12]), "+f"(d[13]), "+f"(d[14]), "+f"(d[15]), "+f"(d[16]), "+f"(d[17]), "+f"(d[18]), "+f"(d[19]), "+f"(d[20]), "+f"(d[21]), "+f"(d[22]), "+f"(d[23]), "+f"(d[24]), "+f"(d[25]), "+f"(d[26]), "+f"(d[27]), "+f"(d[28]), "+f"(d[29]), "+f"(d[30]), "+f"(d[31]), "+f"(d[32]), "+f"(d[33]), "+f"(d[34]), "+f"(d[35]), "+f"(d[36]), "+f"(d[37]), "+f"(d[38]), "+f"(d[39]), "+f"(d[40]), "+f"(d[41]), "+f"(d[42]), "+f"(d[43]), "+f"(d[44]), "+f"(d[45]), "+f"(d[46]), "+f"(d[47]), "+f"(d[48]), "+f"(d[49]), "+f"(d[50]), "+f"(d[51]), "+f"(d[52]), "+f"(d[53]), "+f"(d[54]), "+f"(d[55]), "+f"(d[56]), "+f"(d[57]), "+f"(d[58]), "+f"(d[59]), "+f"(d[60]), "+f"(d[61]), "+f"(d[62]), "+f"(d[63]), "+f"(d[64]), "+f"(d[65]), "+f"(d[66]), "+f"(d[67]), "+f"(d[68]), "+f"(d[69]), "+f"(d[70]), "+f"(d[71]), "+f"(d[72]), "+f"(d[73]), "+f"(d[74]), "+f"(d[75]), "+f"(d[76]), "+f"(d[77]), "+f"(d[78]), "+f"(d[79]), "+f"(d[80]), "+f"(d[81]), "+f"(d[82]), "+f"(d[83]), "+f"(d[84]), "+f"(d[85]), "+f"(d[86]), "+f"(d[87]), "+f"(d[88]), "+f"(d[89]), "+f"(d[90]), "+f"(d[91]), "+f"(d[92]), "+f"(d[93]), "+f"(d[94]), "+f"(d[95]), "+f"(d[96]), "+f"(d[97]), "+f"(d[98]), "+f"(d[99]), "+f"(d[100]), "+f"(d[101]), "+f"(d[102]), "+f"(d[103]), "+f"(d[104]), "+f"(d[105]), "+f"(d[106]), "+f"(d[107])
    : "l"(da), "l"(db), "r"(scaleD));
}
__device__ __forceinline__ void wgmma_ss_n72(float* d, uint64_t da, uint64_t db, int scaleD) {
  asm volatile("{\n.reg .pred p;\nsetp.ne.b32 p, %38, 0;\nwgmma.mma_async.sync.aligned.m64n72k16.f32.bf16.bf16 "
    "{%0,%1,%2,%3,%4,%5,%6,%7,%8,%9,%10,%11,%12,%13,%14,%15,%16,%17,%18,%19,%20,%21,%22,%23,%24,%25,%26,%27,%28,%29,%30,%31,%32,%33,%34,%35}, "
    "%36, %37, p, 1, 1, 0, 1;\n}\n"
    : "+f"(d[0]), "+f"(d[1]), "+f"(d[2]), "+f"(d[3]), "+f"(d[4]), "+f"(d[5]), "+f"(d[6]), "+f"(d[7]), "+f"(d[8]), "+f"(d[9]), "+f"(d[10]), "+f"(d[11]), "+f"(d[12]), "+f"(d[13]), "+f"(d[14]), "+f"(d[15]), "+f"(d[16]), "+f"(d[17]), "+f"(d[18]), "+f"(d[19]), "+f"(d[20]), "+f"(d[21]), "+f"(d[22]), "+f"(d[23]), "+f"(d[24]), "+f"(d[25]), "+f"(d[26]), "+f"(d[27]), "+f"(d[28]), "+f"(d[29]), "+f"(d[30]), "+f"(d[31]), "+f"(d[32]), "+f"(d[33]), "+f"(d[34]), "+f"(d[35])
    : "l"(da), "l"(db), "r"(scaleD));
}
__device__ __forceinline__ void wgmma_rs_n144(float* d, const uint32_t* a, uint64_t db, int scaleD) {
  asm volatile("{\n.reg .pred p;\nsetp.ne.b32 p, %77, 0;\nwgmma.mma_async.sync.aligned.m64n144k16.f32.bf16.bf16 "
    "{%0,%1,%2,%3,%4,%5,%6,%7,%8,%9,%10,%11,%12,%13,%14,%15,%16,%17,%18,%19,%20,%21,%22,%23,%24,%25,%26,%27,%28,%29,%30,%31,%32,%33,%34,%35,%36,%37,%38,%39,%40,%41,%42,%43,%44,%45,%46,%47,%48,%49,%50,%51,%52,%53,%54,%55,%56,%57,%58,%59,%60,%61,%62,%63,%64,%65,%66,%67,%68,%69,%70,%71}, "
    "{%72,%73,%74,%75}, %76, p, 1, 1, 1;\n}\n"
    : "+f"(d[0]), "+f"(d[1]), "+f"(d[2]), "+f"(d[3]), "+f"(d[4]), "+f"(d[5]), "+f"(d[6]), "+f"(d[7]), "+f"(d[8]), "+f"(d[9]), "+f"(d[10]), "+f"(d[11]), "+f"(d[12]), "+f"(d[13]), "+f"(d[14]), "+f"(d[15]), "+f"(d[16]), "+f"(d[17]), "+f"(d[18]), "+f"(d[19]), "+f"(d[20]), "+f"(d[21]), "+f"(d[22]), "+f"(d[23]), "+f"(d[24]), "+f"(d[25]), "+f"(d[26]), "+f"(d[27]), "+f"(d[28]), "+f"(d[29]), "+f"(d[30]), "+f"(d[31]), "+f"(d[32]), "+f"(d[33]), "+f"(d[34]), "+f"(d[35]), "+f"(d[36]), "+f"(d[37]), "+f"(d[38]), "+f"(d[39]), "+f"(d[40]), "+f"(d[41]), "+f"(d[42]), "+f"(d[43]), "+f"(d[44]), "+f"(d[45]), "+f"(d[46]), "+f"(d[47]), "+f"(d[48]), "+f"(d[49]), "+f"(d[50]), "+f"(d[51]), "+f"(d[52]), "+f"(d[53]), "+f"(d[54]), "+f"(d[55]), "+f"(d[56]), "+f"(d[57]), "+f"(d[58]), "+f"(d[59]), "+f"(d[60]), "+f"(d[61]), "+f"(d[62]), "+f"(d[63]), "+f"(d[64]), "+f"(d[65]), "+f"(d[66]), "+f"(d[67]), "+f"(d[68]), "+f"(d[69]), "+f"(d[70]), "+f"(d[71])
    : "r"(a[0]), "r"(a[1]), "r"(a[2]), "r"(a[3]), "l"(db), "r"(scaleD));
}
__device__ __forceinline__ void wgmma_rs_n64(float* d, const uint32_t* a, uint64_t db, int scaleD) {
  asm volatile("{\n.reg .pred p;\nsetp.ne.b32 p, %37, 0;\nwgmma.mma_async.sync.aligned.m64n64k16.f32.bf16.bf16 "
    "{%0,%1,%2,%3,%4,%5,%6,%7,%8,%9,%10,%11,%12,%13,%14,%15,%16,%17,%18,%19,%20,%21,%22,%23,%24,%25,%26,%27,%28,%29,%30,%31}, "
    "{%32,%33,%34,%35}, %36, p, 1, 1, 1;\n}\n"
    : "+f"(d[0]), "+f"(d[1]), "+f"(d[2]), "+f"(d[3]), "+f"(d[4]), "+f"(d[5]), "+f"(d[6]), "+f"(d[7]), "+f"(d[8]), "+f"(d[9]), "+f"(d[10]), "+f"(d[11]), "+f"(d[12]), "+f"(d[13]), "+f"(d[14]), "+f"(d[15]), "+f"(d[16]), "+f"(d[17]), "+f"(d[18]), "+f"(d[19]), "+f"(d[20]), "+f"(d[21]), "+f"(d[22]), "+f"(d[23]), "+f"(d[24]), "+f"(d[25]), "+f"(d[26]), "+f"(d[27]), "+f"(d[28]), "+f"(d[29]), "+f"(d[30]), "+f"(d[31])
    : "r"(a[0]), "r"(a[1]), "r"(a[2]), "r"(a[3]), "l"(db), "r"(scaleD));
}

template <int V> struct Int { static constexpr int value = V; };
struct Cur {
  uint32_t s, ph;
  __device__ __forceinline__ void next() { if (++s == NST) { s = 0; ph ^= 1; } }
};

__device__ __forceinline__ uint8_t* z1_block(int rb, int w, int j) { return g_Z + (rb * 16 + w * 8 + j) * ZB; }
__device__ __forceinline__ uint8_t* z2_block(int kb, int j) { return g_Z + (256 + kb * 8 + j) * ZB; }
__device__ __forceinline__ void combine8(float m0, float q0, float m1, float q1, float n, float eps, float& mean, float& rstd) {
  mean = qsum(m0 + m1) * 0.125f;
  float d0 = m0 - mean, d1 = m1 - mean;
  float M2 = qsum(q0 + q1 + n * (d0 * d0 + d1 * d1));
  rstd = rsqrtf(fmaf(M2, 0.125f / n, eps));
}
__device__ __forceinline__ void stat_get(const uint4* zs, uint32_t tag, float n, float eps, float& m0, float& r0, float& m1, float& r1) {
  uint4 a0, a1, b0, b1;
#pragma unroll 1
  for (int it = 0; it < (1 << 20); it++) {
    a0 = ll_ld128(zs); a1 = ll_ld128(zs + 64); b0 = ll_ld128(zs + 8); b1 = ll_ld128(zs + 72);
    if (__all_sync(~0u, a0.z == tag && a1.z == tag && b0.z == tag && b1.z == tag)) break;
  }
  combine8(__uint_as_float(a0.x), __uint_as_float(a0.y), __uint_as_float(a1.x), __uint_as_float(a1.y), n, eps, m0, r0);
  combine8(__uint_as_float(b0.x), __uint_as_float(b0.y), __uint_as_float(b1.x), __uint_as_float(b1.y), n, eps, m1, r1);
}

__device__ __forceinline__ void rows_fetch(uint32_t el, uint32_t xr, const uint8_t* src, uint32_t bar) {
  expect_tx_p(el, bar, 9216);
#pragma unroll 1
  for (int r = 0; r < 8; r++) bulk_load_p(el, xr + r * 1152, src + r * (DM * 4), 1152, bar);
}
__device__ __forceinline__ void rows_stats(uint32_t xr, uint4* dst, uint32_t tag, int lane) {
  float s[2] = {0.f, 0.f}, q[4] = {0.f, 0.f, 0.f, 0.f};
  const uint32_t a0 = xr + (lane >> 2) * 1152 + (((lane & 3) * 2) ^ (lane >> 2)) * 16;
  uint4 n0 = lds128(a0), n1 = lds128(a0 ^ 16);
#pragma unroll 1
  for (int e = 1; e <= 9; e++) {
    const uint32_t x[8] = {n0.x, n0.y, n0.z, n0.w, n1.x, n1.y, n1.z, n1.w};
    if (e < 9) { n0 = lds128(a0 + e * 128); n1 = lds128((a0 ^ 16) + e * 128); }
#pragma unroll
    for (int u = 0; u < 8; u++) {
      const float lo = blo(x[u]), hi = bhi(x[u]);
      s[u & 1] += lo + hi; q[(u & 1) * 2] = fmaf(lo, lo, q[(u & 1) * 2]); q[(u & 1) * 2 + 1] = fmaf(hi, hi, q[(u & 1) * 2 + 1]);
    }
  }
  const float sx = s[0] + s[1], sq = (q[0] + q[1]) + (q[2] + q[3]);
  const float m = qsum(sx) * (-1.f / DM), r = rsqrtf(fmaxf(fmaf(qsum(sq), 1.f / DM, -m * m), 0.f) + LN_EPS);
  if ((lane & 3) == 0) ll_st128(dst + (lane >> 2) * 2, m, r, tag);
}

__global__ void __cluster_dims__(2, 1, 1) __launch_bounds__(384, 1) mega_kernel(const __grid_constant__ Params P) {
  extern __shared__ __align__(1024) uint8_t smem_raw[];
  uint32_t ckk[8];
  (void)ckk;
  CKK(0);
  const uint32_t sb = smem_u32(smem_raw);
  const uint32_t bars = sb + SM_BAR;
  const int tid = threadIdx.x;
  int lane = tid & 31;
  const int wid = __shfl_sync(~0u, tid >> 5, 0);
  const int cl = blockIdx.x >> 1, tp = cl - 36, t7 = (tp * 37) >> 8;
  const int bid = (cl < 4 ? cl * 8 + 32 : tp < 0 ? cl - 4 : cl < 64 ? tp + t7 + 33 : cl) * 2 + (blockIdx.x & 1);
  if (bid >= NCTA) return;
  const int rb = bid & 15, j = bid >> 4;
  { const bool tr = (tid & 127) == 0 && tid < 256; const int w = tid >> 7; (void)tr; (void)w; TRC(tr, w, 0); }
  CKK(1);
  uint4 wv[5];
  const uint8_t* wsrc;
  {
    const int n8 = min(tid >> 3, 26), part = n8 / 9;
    const uint8_t* src = (const uint8_t*)P.wqkv + (8 * rb + (tid & 7)) * (3 * DM * 2) + (part * (DM - 72) + 72 * j + 8 * n8) * 2;
#pragma unroll
    for (int u = 0; u < SPL; u++) wv[u] = ldnc128_if(tid < 216, src + u * (128 * 3 * DM * 2));
    wsrc = src;
  }
  CKK(2);
  if (tid == 352) {
    for (int s = 0; s < (int)NST; s++) {
      mbar_init(bars + B_FULL + s * 8, 1); mbar_init(bars + B_EMPTY + s * 8, 16);
      mbar_init(bars + B_FULLA + s * 8, 1); mbar_init(bars + B_FULLA + 32 + s * 8, 1);
      mbar_init(bars + B_RES + s * 8, 1); mbar_init(bars + B_RT + s * 8, 1); mbar_init(bars + B_AD + s * 8, 2);
    }
    mbar_init(bars + B_IMG, 8); mbar_init(bars + B_RES + 8, 8); mbar_init(bars + B_WOI, 8); mbar_init(bars + B_GATE3, 3); mbar_init(bars + B_Z1, 1); mbar_init(bars + B_ZB, 1); mbar_init(bars + B_LAG, 4);
    mbar_init(bars + B_CSQ, 3); mbar_init(bars + B_RT1, 1); mbar_init(bars + B_XRW, 1); mbar_init(bars + B_XRW + 8, 1);
    for (int e = 0; e < 2 * EV_N; e++) mbar_init(bars + B_EVT + e * 8, 4);
    asm volatile("fence.mbarrier_init.release.cluster;" ::: "memory");
  }
  if (tid == 320) {
#pragma unroll
    for (int e = 0; e < 28; e++) mbar_init(bars + B_FA3 + e * 8, e < 18 ? 1 : 4);
    asm volatile("fence.mbarrier_init.release.cluster;" ::: "memory");
  }
  __syncthreads();

  if (wid >= 8) {
    reg_dealloc<40>();
    const uint32_t el = elect_one();
    const uint64_t pol = policy_evict_first();
    uint32_t* const fj = g_flags + FJ + j * 32;
    if (wid == 8) {
      if (el) { prefetch_map(&P.act[0]); prefetch_map(&P.wsp); prefetch_map(&P.win); prefetch_map(&P.win64); prefetch_map(&P.wout); prefetch_map(&P.act[1]); prefetch_map(&P.res[0]); prefetch_map(&P.res[1]); prefetch_map(&P.red); }
      const uint32_t epoch = ldcg32(fj + FJ_EP + rb);
      Cur c{0, 1};
      const uint32_t rk = bid & 1;
      uint32_t st, full;
      auto slot = [&](uint32_t bytes) {
        st = sb + c.s * ST_BYTES; full = bars + B_FULL + c.s * 8;
        mbar_wait(full, c.ph);
        expect_tx_p(el, full, bytes);
        mbar_wait(full - B_FULL + B_EMPTY, c.ph);
      };
#pragma unroll 1
      for (int L = 0; L < 2; L++) {
#pragma unroll 1
        for (int i = 0; i < 14; i++) {
          if (L == 0 && (i == 0 || i == 2 * SPL || i == 9)) {
            flag_wait(fj + (i == 9 ? FJ_WO : i == 2 * SPL ? FJ_WQ : FJ_WQ0), (epoch + 1) * 16);
            if (i == 9) flag_wait(g_flags + FJ + (j ^ 1) * 32 + FJ_WO, (epoch + 1) * 16);
            fence_async_g();
            TRC(el, 2, i == 9 ? 46 : i ? 47 : 45);
          }
          const uint32_t hb = i < 9 ? 13824 : i < 13 ? 18432 : 9216, o = ST_B + rk * (i < 9 ? 13824 : 18432);
          const uint8_t* src = i < 9 ? g_WQ + j * WQ_SL + i * 27648 + rk * 13824 : g_WO + ((j & 6) + rk) * WO_SL + (i - 9) * 18432;
          slot(2 * hb);
          bulk_mc_h(el, st + o, src, hb, full, true, pol);
          c.next();
        }
#pragma unroll 1
        for (int i = 0; i < 18; i++) {
          const int p = i >> 1, col = p == 4 ? (9 * j + ((j & 1) ? 0 : 8)) * 32 : (((9 * j + 1) >> 1) + (p < 4 ? p + 36 : p - 5)) * 64;
          if (i & 1) {
            slot(2 * ZB);
          } else {
            st = sb + c.s * ST_BYTES; full = bars + B_FULL + ((c.s + 1) & 3) * 8;
            mbar_wait(bars + B_EMPTY + c.s * 8, c.ph);
          }
          tma4d_mc(el, st + ST_B + rk * 18432, p == 4 ? &P.win : &P.win64, col, (i & 1) * 36 + rk * 18, full, pol);
          if (el && !(i & 1)) mbar_arrive(bars + B_FULL + c.s * 8);
          c.next();
        }
        TRC(el, 2, L * 16 + 6);
        flag_wait(fj + FJ_ZN + L, (epoch + 1) * 16);
        fence_async_g();
        TRC(el, 2, L * 16 + 7);
#pragma unroll 1
        for (int i = 0; i < 32; i++) {
          const uint8_t* src = z2_block(i, j) + rk * 18432;
          if (i >= 4) mbar_wait(bars + B_AD + c.s * 8, ((i >> 2) & 1) ^ 1);
          slot(ST_BYTES);
          bulk_mc_h(el, st + ST_B + rk * 18432, src, 18432, full, true, pol);
          tma3d_h(el, st, &P.wsp, i * 64, rb * 64, 0, full, true, pol);
          c.next();
        }
        mbar_wait(bars + B_Z1, L);
        fence_async_g();
        expect_tx_p(el, bars + B_ZB, 20480);
        bulk_load_h(el, sb + SM_STG, z1_block(rb, 1, j) + 16384, 4096, bars + B_ZB, true, pol);
#pragma unroll 1
        for (int i = 0; i < 10; i++) {
          const int cb = i - 1 + j;
          if (i < 4) mbar_wait(bars + B_AD + c.s * 8, 1);
          slot(i == 1 ? ST_BYTES : ZB);
          if (i < 2) bulk_load_h(el, st, z1_block(rb, i, j) + i * 20480, ZB - i * 20480, full, true, pol);
          if (i == 0) bulk_load_h(el, st + ZB, z1_block(rb, 1, j), 16384, bars + B_ZB, true, pol);
          else tma2d_mc_h(el, st + ST_B + rk * 18432, &P.wout, (cb >= 9 ? cb - 9 : cb) * 64, 288 * j + rk * 144, full, true, pol);
          c.next();
        }
      }
    } else if (wid < 11) {
      int w = wid - 9;
      uint32_t* const fr = g_flags + (rb * 2 + w) * 32;
      const uint32_t epoch = ldcg32(fr + FR_EP + j);
      const uint32_t ev = bars + B_EVT + w * EV_N * 8, t8 = (epoch + 1) * 8;
      const int dp = ((j & 1) - w) * 32;
      Cur c{0, 1};
#pragma unroll 1
      for (int L = 0; L < 2; L++) {
#pragma unroll 1
        for (int ph = 0; ph < 3; ph++) {
          if (ph + L > 0) {
            uint32_t* f = fr + (ph == 0 ? FR_X2 : ph == 1 ? FR_O + L : FR_X1 + L);
            mbar_wait(ev + ph * 8, ph ? L : 0);
            TRC(el, 3, w * 32 + L * 16 + ph * 3);
            flag_release_p(el, ph == 2 ? f + dp : f);
            if (el && ph == 2) mbar_arrive(bars + B_GATE3);
            TRC(el, 3, w * 32 + L * 16 + ph * 3 + 1);
            if (ph == 1 && w == 1) {
              mbar_wait(ev - (EV_N - EV_O) * 8, L);
              expect_tx_p(el, bars + B_RES, 18432);
              tma3d_h(el, sb + SM_STG, &P.res[L], (j & 6) * 72, rb * 64, j & 1, bars + B_RES, !L, pol);
            }
            if (ph == 2) {
              if (lane < 2) mbar_arrive(bars + B_FULLA + w * 32 + ((c.s + lane) & 3) * 8);
              expect_tx_p(lane < 9, bars + B_FA3 + (9 * w + lane) * 8, 8192);
              flag_wait(f, t8);
              fence_async_g();
#pragma unroll 1
              for (int kb = 0; kb < 9; kb++) {
                const int n = 9 * w + kb;
                if (n >= 8) mbar_wait(bars + B_EA3 + (n - 8) * 8, L);
                tma3d_h(el, sb + ((n >> 1) & 3) * ST_BYTES + (n & 1) * 8192, &P.act[1], kb * 64, rb * 64, w, bars + B_FA3 + (9 * w + kb) * 8, false, pol);
                TRC(el && kb == 0, 3, w * 32 + L * 16 + ph * 3 + 2);
              }
              c.ph ^= ((c.s + 18) >> 2) & 1; c.s = (c.s + 18) & 3;
              break;
            }
            const uint32_t full = bars + B_FULLA + w * 32 + c.s * 8, dst = sb + c.s * ST_BYTES + w * 8192;
            mbar_wait(bars + B_EMPTY + c.s * 8, c.ph);
            expect_tx_p(el, full, 8192);
            flag_wait(ph == 1 ? f + dp : f, t8);
            fence_async_g();
            if (ph != 1) tma3d_h(el, dst, &P.act[1], 0, rb * 64, w, full, false, pol);
            else bulk_load_h(el, dst, z1_block(rb, j & 1, 0) + w * 8192, 8192, full, true, pol);
            c.next();
            TRC(el, 3, w * 32 + L * 16 + ph * 3 + 2);
          }
          const int n = ph == 0 ? 9 : 5;
          const uint32_t tag = epoch * 2 + L + 1;
          uint4* const xs = g_XST + (rb * 2 + w) * 128;
#pragma unroll 1
          for (int i = ph + L > 0; i < n; i++) {
            const uint32_t full = bars + B_FULLA + w * 32 + c.s * 8, dst = sb + c.s * ST_BYTES + w * 8192;
            if (ph + L == 0 && i == 4) {
              mbar_wait(bars + B_WT + w * 8, 0);
              TRC(el && w == 0, 2, 37);
              rows_stats(sb + SM_STG + w * 9216, xs + 16 * j, tag, lane);
              TRC(el && w == 0, 2, 38);
            }
            const bool none = ph == 1 && 2 * i + w > 8;
            mbar_wait(bars + B_EMPTY + c.s * 8, c.ph);
            expect_tx_p(el, full, none ? 0 : 8192);
            if (ph != 1) {
              tma3d_h(el, dst, &P.act[L], i * 64, rb * 64, w, full, false, pol);
            } else {
              if (!none) bulk_load_h(el, dst, z1_block(rb, j & 1, 0) + (2 * i + w) * 8192, 8192, full, true, pol);
            }
            c.next();
            if (ph + L == 0 && i == 3) rows_fetch(el, sb + SM_STG + w * 9216, P.xs[0] + (128 * rb + 16 * j + w) * (DM * 2), bars + B_WT + w * 8);
          }
          if (ph + L == 2) flag_wait(fj + FJ_P4, t8 * 4);
          if (ph == 0) {
            const uint32_t tab = sb + L * (2 * ST_BYTES) + SM_XST + w * 512 + lane * 8;
            TRC(el, 3, w * 32 + L * 16 + 13);
#pragma unroll 1
            for (int it = 0; it < (1 << 22); it++) {
              const uint4 a = ll_ld128(xs + 2 * lane), b = ll_ld128(xs + 64 + 2 * lane);
              if (__all_sync(~0u, a.z == tag && b.z == tag)) { sts64(tab, a.x, a.y); sts64(tab + 256, b.x, b.y); break; }
            }
            __syncwarp();
            if (el) mbar_arrive(bars + B_CSQ);
            TRC(el, 3, w * 32 + L * 16 + 14);
          }
        }
        asm volatile("" : "+r"(lane), "+r"(w));
        expect_tx_p(el, bars + B_WT + w * 8, 2048);
#pragma unroll 1
        for (int r = 0; r < 8; r++)
          bulk_load_p(el, sb + SM_WT + w * 2176 + r * 272, (const uint8_t*)P.w_sp + (size_t)(128 * rb + 16 * j + 2 * r + w) * (SEQ * 2) + 30 * 128, 256, bars + B_WT + w * 8);
        float cv = (lane & 3) ? 0.f : -blo(ldnc16(P.b_sp + 128 * rb + 16 * j + 2 * (lane >> 2) + w));
        mbar_wait(bars + B_RT, L);
        mbar_wait(bars + B_WT + w * 8, L ^ 1);
        mbar_wait(ev + EV_Z1 * 8, L);
        const uint32_t ro = (w * 64 + 8 * j + (lane >> 2)) * 128, x0 = ((lane & 3) * 2) ^ (lane >> 2);
#pragma unroll 1
        for (int i = 0; i < 32; i++) {
          const bool tail = (i >> 1) == 4;
          const int kb = tail ? i + 22 : i < 8 ? i : i - 2;
          if (i == 8) mbar_wait(bars + B_RT1, L);
          if (!tail) mbar_wait(bars + B_FULL + c.s * 8, c.ph ^ 1);
#pragma unroll
          for (int e = 0; e < 2; e++) {
            const uint4 a = lds128(!tail ? sb + c.s * ST_BYTES + ro + ((x0 ^ e) << 4) : sb + SM_WT + w * 2176 + (lane >> 2) * 272 + (i - 8) * 128 + (lane & 3) * 32 + e * 16);
            const uint4 m = lds128(sb + SM_RT + 4096 + kb * 128 + (lane & 3) * 32 + e * 16);
            cv = fmaf(blo(a.x), blo(m.x), fmaf(bhi(a.x), bhi(m.x), fmaf(blo(a.y), blo(m.y), fmaf(bhi(a.y), bhi(m.y), cv))));
            cv = fmaf(blo(a.z), blo(m.z), fmaf(bhi(a.z), bhi(m.z), fmaf(blo(a.w), blo(m.w), fmaf(bhi(a.w), bhi(m.w), cv))));
          }
          if (!tail) {
            mbar_arrive_if(el, bars + B_AD + c.s * 8 + (__float_as_uint(cv) & P.zero));
            c.next();
          }
        }
        TRC(el, 3, w * 32 + L * 16 + 11);
        uint32_t tag = t8;
        asm volatile("" : "+r"(tag));
        tag = (tag >> 2) - 1 + L;
        cv = qsum(cv);
        uint2* const cs = (uint2*)(g_XST + (rb * 2 + w) * 128 + 1);
        if ((lane & 3) == 0) ll_st64(cs + 32 * j + (lane >> 2) * 4, __float_as_uint(cv), tag);
#pragma unroll 1
        for (int it = 0; it < (1 << 22); it++) {
          const uint2 a = ll_ld64(cs + 4 * lane), b = ll_ld64(cs + 128 + 4 * lane);
          if (__all_sync(~0u, a.y == tag && b.y == tag)) { sts32(sb + SM_CV + w * 256 + lane * 4, a.x); sts32(sb + SM_CV + w * 256 + 128 + lane * 4, b.x); break; }
        }
        __syncwarp();
        if (el) mbar_arrive(bars + B_CV + w * 8);
        TRC(el, 3, w * 32 + L * 16 + 12);
#pragma unroll 1
        for (int kb = 30; kb < 32; kb++) {
          mbar_wait(bars + B_FULL + c.s * 8, c.ph ^ 1);
          if (el) mbar_arrive(bars + B_AD + c.s * 8);
          c.next();
        }
        c.ph ^= ((c.s + 10) >> 2) & 1; c.s = (c.s + 10) & 3;
        if (L == 0) {
          mbar_wait(ev + EV_P4 * 8, 0);
          flag_add_p(el, fj + FJ_P4);
        }
      }
    } else {
      const uint32_t epoch = ldcg32(fj + FJ_EP + rb);
      if (SPL) {
        mbar_wait(bars + B_RES + 8, 0);
        TRC(el, 2, 41);
        flag_release_p(el, fj + FJ_WQ0);
        TRC(el, 2, 42);
      }
      mbar_wait(bars + B_IMG, 0);
      TRC(el, 2, 39);
      flag_release_p(el, fj + FJ_WQ);
      TRC(el, 2, 40);
#pragma unroll 1
      for (int L = 0; L < 2; L++) {
        float* const csf = g_CSP + (NCTA + bid) * 216;
        if (L == 0) {
          flag_wait(fj + FJ_WQ, (epoch + 1) * 16);
          fence_async_g();
          expect_tx_p(el, bars + B_XRW, 13824);
          bulk_load_p(el, sb + ST_BYTES + SM_WOI, g_CSP + j * 16 * 216, 6912, bars + B_XRW);
          bulk_load_p(el, sb + 2 * ST_BYTES + SM_WOI, g_CSP + (j * 16 + 8) * 216, 6912, bars + B_XRW);
          mbar_wait(bars + B_XRW, 0);
#pragma unroll 1
          for (int f = lane; f < 54; f += 32) {
            float s[4] = {0.f, 0.f, 0.f, 0.f};
#pragma unroll 4
            for (int r = 0; r < 16; r++) {
              const uint4 v = lds128(sb + ST_BYTES + SM_WOI + (r >> 3) * ST_BYTES + (r & 7) * 864 + f * 16);
              s[0] += __uint_as_float(v.x); s[1] += __uint_as_float(v.y); s[2] += __uint_as_float(v.z); s[3] += __uint_as_float(v.w);
            }
            sts128(sb + SM_CSQ + f * 16, __float_as_uint(s[0]), __float_as_uint(s[1]), __float_as_uint(s[2]), __float_as_uint(s[3]));
            stg128(csf + f * 4, __float_as_uint(s[0]), __float_as_uint(s[1]), __float_as_uint(s[2]), __float_as_uint(s[3]));
          }
          __syncwarp();
          if (el) mbar_arrive(bars + B_CSQ);
        } else {
#pragma unroll 1
          for (int u = 0; u < 4; u++) {
            const int w = u & 1;
            if (u < 2) {
              flag_wait(g_flags + (rb * 2 + w) * 32 + FR_X2, (epoch + 1) * 8);
              fence_async_g();
              TRC(el, 2, 48 + u);
              rows_fetch(el, sb + SM_STG + w * 9216, P.xs[1] + (128 * rb + 16 * j + w) * (DM * 2), bars + B_XRW + w * 8);
            } else {
              mbar_wait(bars + B_XRW + w * 8, w ^ 1);
              TRC(el, 2, 48 + u);
              rows_stats(sb + SM_STG + w * 9216, g_XST + (rb * 2 + w) * 128 + 16 * j, epoch * 2 + 2, lane);
              TRC(el, 2, 50 + u);
            }
          }
          expect_tx_p(el, bars + B_CSQ, 864);
          bulk_load_p(el, sb + 2 * ST_BYTES + SM_CSQ, csf, 864, bars + B_CSQ);
        }
        if (L == 0) {
          TRC(el, 2, 43);
          mbar_wait(bars + B_WOI, 0);
          bulk_store_p(el, g_WO + j * WO_SL + rb * (41 * 128), sb + SM_WOI, (rb < 15 ? 41 : 33) * 128);
          publish_p(el, fj + FJ_WO);
          TRC(el, 2, 44);
          if (el) prefetch_l2((const uint8_t*)P.w_in + bid * 41472, 41472);
          uint4 y[4];
#pragma unroll
          for (int u = 0; u < 4; u++) y[u] = ldnc128((u < 2 ? (const uint8_t*)P.w_in + (100 + 300 * u) * (2 * FH * 2) + (FH + 1024 * u) * 2 : (const uint8_t*)P.w_sp + (1000 * u - 1500) * (SEQ * 2) + u * 1024) + lane * 16);
          float sq[2] = {0.f, 0.f};
#pragma unroll
          for (int u = 0; u < 4; u++) {
            const uint32_t x[4] = {y[u].x, y[u].y, y[u].z, y[u].w};
#pragma unroll
            for (int e = 0; e < 4; e++) sq[u >> 1] = fmaf(blo(x[e]), blo(x[e]), fmaf(bhi(x[e]), bhi(x[e]), sq[u >> 1]));
          }
          const float o0 = sqrtf(wsum(sq[0]) * (2.f * GA * GA * DM / 512.f)), o1 = sqrtf(wsum(sq[1]) * (C0S * C0S * SEQ / 512.f));
          const uint32_t off = (__float_as_uint(o0) & 0x7f800000u) >> 16 | 0x8000u | OFM;
          if (el) sts64(sb + SM_OFF, off * 0x10001u, min(__float_as_uint(o1) & 0x7f800000u, 0x7e000000u) | 0x00400000u);
        }
        if (el) mbar_arrive(bars + B_GATE3);
        const uint32_t tag = epoch * 2 + L + 1;
        asm volatile("" : "+r"(lane));
        mbar_wait(bars + B_EVT + EV_ZN * 8, L);
        mbar_wait(bars + B_EVT + (EV_N + EV_ZN) * 8, L);
        flag_release_p(el, fj + FJ_ZN + L);
        TRC(el, 2, L * 16 + 8);
        {
          uint4 v[4];
#pragma unroll 1
          for (int it = 0; it < (1 << 22); it++) {
            bool ok = true;
#pragma unroll
            for (int u = 0; u < 4; u++) { v[u] = ll_ld128(g_ZST + (rb * 2 + ((lane >> 1) & 1)) * 512 + ((lane & 1) * 4 + u) * 64 + 8 * j + (lane >> 2)); ok = ok && v[u].z == tag; }
            if (__all_sync(~0u, ok)) break;
          }
          float mean = __uint_as_float(v[0].x) + __uint_as_float(v[1].x) + __uint_as_float(v[2].x) + __uint_as_float(v[3].x), M2 = 0.f;
          mean = (mean + __shfl_xor_sync(~0u, mean, 1)) * 0.125f;
#pragma unroll
          for (int u = 0; u < 4; u++) { const float d = __uint_as_float(v[u].x) - mean; M2 += fmaf(288.f * d, d, __uint_as_float(v[u].y)); }
          M2 += __shfl_xor_sync(~0u, M2, 1);
          const float rs = blo(pack2(rsqrtf(fmaf(M2, 1.f / FH, 4.f * GA * GA * LN_EPS)), 0.f));
          if (!(lane & 1)) ll_st64(g_RT + 128 * rb + 16 * j + (lane >> 1), pack2(rs, rs * mean), tag);
        }
        TRC(el, 2, L * 16 + 10);
#pragma unroll 1
        for (int b = 0; b < 8; b++) {
          uint4 v[4];
#pragma unroll 1
          for (int it = 0; it < (1 << 22); it++) {
            bool ok = true;
#pragma unroll
            for (int u = 0; u < 4; u++) { v[u] = ll_ld128((const uint4*)g_RT + b * 128 + u * 32 + lane); ok = ok && v[u].y == tag && v[u].w == tag; }
            if (__all_sync(~0u, ok)) break;
          }
#pragma unroll
          for (int u = 0; u < 4; u++) {
            const uint32_t rt = sb + SM_RT + b * 512 + u * 128, ro = (lane >> 3) * 32 + (lane & 3) * 8 + ((lane >> 2) & 1) * 2;
            sts32(rt + 4096 + lane * 4, __byte_perm(v[u].x, v[u].z, 0x7632));
            asm volatile("st.shared.u16 [%0], %1;\nst.shared.u16 [%0 + 4], %2;" ::"r"(rt + ro), "h"((uint16_t)v[u].x), "h"((uint16_t)v[u].z) : "memory");
          }
          __syncwarp();
          if (el && (b == 1 || b == 7)) mbar_arrive(bars + (b == 1 ? B_RT : B_RT1));
          TRC(el && b < 2, 2, L * 16 + 11 + b);
        }
        TRC(el, 2, L * 16 + 9);
        mbar_wait(bars + B_EVT + EV_Z1 * 8, L);
        mbar_wait(bars + B_EVT + (EV_N + EV_Z1) * 8, L);
        fence_gpu();
        if (el) mbar_arrive(bars + B_Z1);
      }
    }
  } else {
    CKK(3);
    uint8_t* const wdst = P.wq + j * WQ_SL + rb * 3456 + tid * 16;
#pragma unroll
    for (int u = 0; u < SPL; u++) stg128_if(tid < 216, wdst + u * (16 * 3456), wv[u].x, wv[u].y, wv[u].z, wv[u].w);
    __syncwarp();
    if (lane == 0) mbar_arrive(bars + B_RES + 8);
    CKK(4);
    auto repack2 = [&]() {
#pragma unroll
      for (int u = SPL; u < 5; u++) stg128_if((u < 4 || rb < 8) && tid < 216, wdst + u * (16 * 3456), wv[u].x, wv[u].y, wv[u].z, wv[u].w);
      float s[8];
#pragma unroll
      for (int e = 0; e < 8; e++) s[e] = 0.f;
#pragma unroll
      for (int u = 0; u < 5; u++) {
        uint32_t x[4] = {wv[u].x, wv[u].y, wv[u].z, wv[u].w};
        asm volatile("" : "+r"(x[0]), "+r"(x[1]), "+r"(x[2]), "+r"(x[3]));
#pragma unroll
        for (int e = 0; e < 4; e++) { s[2 * e] += blo(x[e]); s[2 * e + 1] += bhi(x[e]); }
      }
#pragma unroll
      for (int m = 4; m; m >>= 1) {
#pragma unroll
        for (int e = 0; e < m; e++) s[e] = ((tid & m) ? s[e + m] : s[e]) + __shfl_xor_sync(~0u, (tid & m) ? s[e] : s[e + m], m);
      }
      stg32_if(tid < 216, P.csp + bid * 216 + tid, __float_as_uint(s[0]));
      __syncwarp();
      if (lane == 0) mbar_arrive(bars + B_IMG);
    };
    reg_alloc<232>();
    CKK(5);
#pragma unroll
    for (int v = SPL; v < 5; v++) wv[v] = ldnc128_if(tid < 216 && (v < 4 || rb < 8), wsrc + v * (128 * 3 * DM * 2));
    repack2();
    CKK(6);
    const int w = wid >> 2, q = wid & 3;
    int g = lane >> 2, t = lane & 3;
    const uint32_t ev = bars + B_EVT + w * EV_N * 8;
    const bool tr = (tid & 127) == 0;
    (void)tr;
    Cur c{0, 0};
    const uint32_t ebar = mapa(bars + B_EMPTY, (bid & 1) ^ (lane & 1));
    auto release = [&](uint32_t s, uint32_t dep = 0) { mbar_arrive_cluster_if(lane < 2, ebar + s * 8 + dep); };
    auto release_if = [&](bool on, uint32_t s) { mbar_arrive_cluster_if(lane < 2 && on, ebar + s * 8); };
    const uint32_t stg = sb + SM_STG + w * 9216;
    uint32_t ia = 0;
    auto wait_ab = [&]() { mbar_wait_c(bars + B_FULL + c.s * 8, c.ph); mbar_wait_c(bars + B_FULLA + w * 32 + c.s * 8, (ia >> 2) & 1); ia++; };
    uint32_t lagph = 0;
    auto yield = [&](int left, int lag) { if (w == 1 && left == lag) mbar_wait_c(bars + B_LAG, lagph); };
    auto yield_done = [&]() { if (w == 0 && lane == 0) mbar_arrive(bars + B_LAG); };
    auto signal = [&](int e) { __syncwarp(); if (lane == 0) mbar_arrive(ev + e * 8); };

    auto fetch_wo = [&]() {
#pragma unroll 1
      for (int u = tid; u < 328; u += 256) {
        const int m = min(41 * rb + (u >> 3), 647), k8 = m / 9;
        cp_async16(sb + SM_WOI + u * 16, (const uint8_t*)P.wo + (8 * k8 + (u & 7)) * (DM * 2) + (72 * j + 8 * (m - k8 * 9)) * 2);
      }
    };
    const uint32_t epoch = ldcg32(g_flags + (rb * 2 + w) * 32 + FR_EP + j);
    TRC(tr, w, 1);
    CKK(7);
    CKK_OUT;

#pragma unroll 1
    for (int L = 0; L < 2; L++) {
      const int tb = 2 + L * 24;
      asm volatile("" : "+r"(lane), "+r"(g), "+r"(t));
      (void)tb;
      ia = 0;
      const uint32_t tag = epoch * 2 + L + 1;
      uint32_t aoff = (w * 64 + q * 16 + (lane & 15)) * 128 + (((lane >> 4) ^ (lane & 7)) << 4);
      {
        uint32_t Pk[27][2];
        float sc0, sc1;
        const uint32_t att = stg + 2 * q * 128 + lane * 4;
        uint4* hp = g_HALO + ((((rb - (q == 0)) * 2 + w) * 8 + j) * 6) * 32 + lane;
        uint8_t* od = z1_block(rb, w, 0) + (9 * j) * 1024 + (2 * q) * 128 + lane * 4;
        ACLK_INIT;
        {
          float acc[108];
#pragma unroll
          for (int i = 0; i < 108; i++) acc[i] = 0.f;
          uint32_t prev = 0;
#pragma unroll 1
          for (int kb = 0; kb < 9; kb++) {
            wait_ab();
            yield(9 - kb, LAG1);
            TRC(tr && kb == 0, w, tb + 0);
            MCLK(kb == 0, 0);
            PCLK(kb * 4);
            const uint32_t st = sb + c.s * ST_BYTES, da = dlo(st + w * 8192, 16), db = dlo(st + ST_B, 3456);
            wgmma_fence();
#pragma unroll
            for (int kk = 0; kk < 4; kk++) {
              wgmma_ss_n216(acc, dsc<1024, 1>(da, kk * 32), dsc<128, 0>(db, kk * 6912), 1);
              if (kk == 0) { wgmma_commit(); wgmma_wait<1>(); release_if(kb > 0, prev); }
            }
            wgmma_commit();
            if (kb == 8) yield_done();
            PCLK(kb * 4 + 1);
            if (kb == 0 && L == 0) fetch_wo();
            if (kb == 3 && L == 0) {
              asm volatile("cp.async.wait_all;" ::: "memory");
              fence_async_s();
              __syncwarp();
              if (lane == 0) mbar_arrive(bars + B_WOI);
            }
            PCLK(kb * 4 + 2);
            PCLK(kb * 4 + 3);
            prev = c.s; c.next();
          }
          const uint32_t cs = sb + prev * ST_BYTES + SM_CSQ + t * 8;
          mbar_wait_c(bars + B_CSQ, L);
          const float2 n0 = lds64f(sb + prev * ST_BYTES + SM_XST + w * 512 + (16 * q + g) * 8), n1 = lds64f(sb + prev * ST_BYTES + SM_XST + w * 512 + (16 * q + g + 8) * 8);
          const float m0 = n0.x, r0 = n0.y, m1 = n1.x, r1 = n1.y;
          float2 cv[27];
#pragma unroll
          for (int G = 0; G < 27; G++) cv[G] = lds64f(cs + G * 32);
          PCLK(36);
          wgmma_wait<0>();
          PCLK(37);
          uint32_t dep = P.zero & __float_as_uint(m0) & __float_as_uint(m1);
#pragma unroll
          for (int G = 0; G < 27; G++) dep &= __float_as_uint(cv[G].x);
          release(prev, dep);
          lagph ^= 1;
          TRC(tr, w, tb + 1);
          MCLK(1, 1);
          ACLK(0);
#pragma unroll
          for (int G = 9; G < 27; G++) Pk[G][1] = pack2(fmaf(m1, cv[G].x, acc[4 * G + 2]) * r1, fmaf(m1, cv[G].y, acc[4 * G + 3]) * r1);
          if (q < 3) {
#pragma unroll
            for (int i = 0; i < 18; i++) sts32(att + 256 + (i >> 1) * 1024 + (i & 1) * 128, Pk[9 + i][1]);
          } else if (rb < 15) {
#pragma unroll
            for (int i = 0; i < 6; i++) ll_st128(hp + i * 32, __uint_as_float(Pk[9 + 3 * i][1]), __uint_as_float(Pk[10 + 3 * i][1]), tag, __uint_as_float(Pk[11 + 3 * i][1]));
          }
#pragma unroll
          for (int G = 0; G < 27; G++) {
            if (G < 9) {
              Pk[G][0] = pack2(fmaf(m0, cv[G].x, acc[4 * G]), fmaf(m0, cv[G].y, acc[4 * G + 1]));
              Pk[G][1] = pack2(fmaf(m1, cv[G].x, acc[4 * G + 2]), fmaf(m1, cv[G].y, acc[4 * G + 3]));
            } else {
              Pk[G][0] = pack2(fmaf(m0, cv[G].x, acc[4 * G]) * r0, fmaf(m0, cv[G].y, acc[4 * G + 1]) * r0);
            }
          }
          sc0 = r0 * (0.23570226039551584f * 1.4426950408889634f); sc1 = r1 * (0.23570226039551584f * 1.4426950408889634f);
        }
        ACLK(1);
        constexpr int GA_[4] = {0, 2, 4, 7}, GB_[4] = {1, 3, 5, 8}, GC_[4] = {2, 4, 6, 6};
        float S1[4][4], S2[4][4];
        uint32_t qa[4][2], qc[4][2];
#pragma unroll
        for (int h = 0; h < 4; h++) {
#pragma unroll
          for (int r = 0; r < 2; r++) {
            qa[h][r] = (h == 0 || h == 3 || t >= h) ? Pk[GA_[h]][r] : 0u;
            qc[h][r] = (h == 3 ? t == 3 : t <= h) ? Pk[GC_[h]][r] : 0u;
          }
          mma16(S1[h], qa[h][0], qa[h][1], Pk[GB_[h]][0], Pk[GB_[h]][1], Pk[9 + GA_[h]][0], Pk[9 + GB_[h]][0]);
          mma16(S2[h], qa[h][0], qa[h][1], Pk[GB_[h]][0], Pk[GB_[h]][1], Pk[9 + GA_[h]][1], Pk[9 + GB_[h]][1]);
        }
#pragma unroll
        for (int h = 0; h < 4; h++) {
          mma8(S1[h], qc[h][0], qc[h][1], Pk[9 + GC_[h]][0]);
          mma8(S2[h], qc[h][0], qc[h][1], Pk[9 + GC_[h]][1]);
        }
        uint32_t V1[9], V2[9];
#pragma unroll
        for (int i = 0; i < 9; i++) { V1[i] = movm(Pk[18 + i][0]); V2[i] = movm(Pk[18 + i][1]); }
        const bool remote = q == 0 && rb > 0;
        uint4 hv[6];
#pragma unroll
        for (int i = 0; i < 6; i++) hv[i] = make_uint4(0u, 0u, tag, 0u);
        if (remote) {
#pragma unroll
          for (int i = 0; i < 6; i++) hv[i] = ll_ld128(hp + i * 32);
        }
        const bool up0 = 2 * t > g, up1 = 2 * t + 1 > g;
        const uint32_t mup = (up0 ? 0xffffu : 0u) | (up1 ? 0xffff0000u : 0u);
        auto finish = [&](const float (&x0)[4], const float (&x1)[4], uint32_t ma, const uint32_t (&Vb)[9], int hi) {
          uint32_t pa[4], pb[4];
          float rs[4];
#pragma unroll
          for (int h = 0; h < 4; h++) {
            const float m = qmax(fmaxf(x0[h], x1[h]));
            const uint32_t p = pack2(ex2(x0[h] - m), ex2(x1[h] - m));
            pa[h] = p & ma; pb[h] = p & ~ma;
          }
#pragma unroll
          for (int h = 0; h < 4; h += 2) {
            float R[4];
            mma16(R, pa[h], pa[h + 1], pb[h], pb[h + 1], 0x3f803f80u, 0x3f803f80u);
            rs[h] = rcp_fast(R[0]); rs[h + 1] = rcp_fast(R[2]);
          }
#pragma unroll
          for (int i = 0; i < 9; i++) {
            const int h = 4 * i / 9, e = (h & 1) * 2;
            const bool split = i == 2 || i == 4 || i == 6, nx = split && 2 * t >= i;
            float O[4], N[4];
            mma16(O, pa[h & 2], pa[h | 1], pb[h & 2], pb[h | 1], V1[i], Vb[i]);
            if (i == 4) mma16(N, pa[2], pa[3], pb[2], pb[3], V1[i], Vb[i]); else { N[0] = O[2]; N[1] = O[3]; }
            const float r = nx ? rs[h + (split ? 1 : 0)] : rs[h];
            stg32(od + i * 1024 + hi * 128, pack2((nx ? N[0] : O[e]) * r, (nx ? N[1] : O[e + 1]) * r));
          }
        };
        {
          float x0[4], x1[4];
#pragma unroll
          for (int h = 0; h < 4; h++) { x0[h] = (up0 ? S1[h][2] : S2[h][2]) * sc1; x1[h] = (up1 ? S1[h][3] : S2[h][3]) * sc1; }
          finish(x0, x1, mup, V2, 1);
        }
        ACLK(2);
        bar_sync(1 + w, 128);
        uint32_t H[18];
        if (q > 0) {
#pragma unroll
          for (int i = 0; i < 18; i++) H[i] = lds32(att + (i >> 1) * 1024 + (i & 1) * 128);
        } else {
#pragma unroll 1
          for (int it = 0; it < (1 << 20); it++) {
            bool ok = true;
#pragma unroll
            for (int i = 0; i < 6; i++) ok = ok && hv[i].z == tag;
            if (__all_sync(~0u, ok)) break;
#pragma unroll
            for (int i = 0; i < 6; i++) hv[i] = ll_ld128(hp + i * 32);
          }
#pragma unroll
          for (int i = 0; i < 6; i++) { H[3 * i] = hv[i].x; H[3 * i + 1] = hv[i].y; H[3 * i + 2] = hv[i].w; }
        }
        float S0[4][4];
#pragma unroll
        for (int h = 0; h < 4; h++) {
          mma16(S0[h], qa[h][0], qa[h][1], Pk[GB_[h]][0], Pk[GB_[h]][1], H[GA_[h]], H[GB_[h]]);
        }
#pragma unroll
        for (int h = 0; h < 4; h++) mma8(S0[h], qc[h][0], qc[h][1], H[GC_[h]]);
        uint32_t V0[9];
#pragma unroll
        for (int i = 0; i < 9; i++) V0[i] = movm(H[9 + i]);
        ACLK(3);
        {
          const bool nohalo = (rb | q) == 0;
          const float b0 = up0 && nohalo ? -INFINITY : 0.f, b1 = up1 && nohalo ? -INFINITY : 0.f;
          float x0[4], x1[4];
#pragma unroll
          for (int h = 0; h < 4; h++) { x0[h] = fmaf(up0 ? S0[h][0] : S1[h][0], sc0, b0); x1[h] = fmaf(up1 ? S0[h][1] : S1[h][1], sc0, b1); }
          finish(x0, x1, ~mup, V0, 0);
        }
        ACLK(4);
        signal(EV_O);
        ACLK_OUT;
        TRC(tr, w, tb + 2);
        MCLK(1, 2);
      }
      {
        float acc[36];
        const int hw = rb * 2 + (j & 1), js = (j & 6) + w;
        const uint32_t xt = sb + SM_STG + (16 * q + g) * 288 + w * 144 + t * 4;
        uint32_t xm = sb + SM_STG + (16 * q + (lane & 15)) * 288 + (((9 * w + (lane >> 4)) ^ ((lane >> 2) & 1)) << 4), xl = sb + SM_STG + (2 * q + w) * 2304 + lane * 16;
        uint8_t* xd[5];
#pragma unroll
        for (int u = 0; u < 5; u++) {
          const int row = ((u * 32 + lane) * 57) >> 10;
          xd[u] = P.xs[1] + (128 * rb + 32 * q + 16 * w + (j & 1)) * (DM * 2) + (j & 6) * 144 + row * (DM * 4 - 288) + u * 512 + ((lane ^ (row >> 2)) << 4);
          asm volatile("" : "+l"(xd[u]));
        }
        asm volatile("" : "+r"(xm), "+r"(xl));
        mbar_wait_c(bars + B_RES, L);
        TRC(tr, w, tb + 21);
#pragma unroll
        for (int i = 0; i < 18; i++) { const uint32_t x = lds32(xt + (i >> 1) * 16 + (i & 1) * 2304); acc[2 * i] = blo(x); acc[2 * i + 1] = bhi(x); asm volatile("" : "+f"(acc[2 * i]), "+f"(acc[2 * i + 1])); }
        uint32_t prev = 0;
#pragma unroll 1
        for (int u = 0; u < 5; u++) {
          const uint32_t st = sb + c.s * ST_BYTES, da = dlo(st, 1024), db = dlo(st + ST_B + w * 18432, 1152);
          mbar_wait_c(bars + B_FULL + c.s * 8, c.ph); mbar_wait_c(bars + B_FULLA + c.s * 8, (ia >> 2) & 1);
          TRC(tr && u == 0, w, tb + 3);
          MCLK(u == 0, 3);
          wgmma_fence();
#pragma unroll
          for (int kk = 0; kk < 4; kk++) wgmma_ss_n72(acc, dsc<128, 0>(da, kk * 2048), dsc<128, 0>(db, kk * 2304), 1);
          wgmma_commit();
          wgmma_wait<1>();
          release_if(u > 0, prev);
          mbar_wait_c(bars + B_FULLA + 32 + c.s * 8, (ia >> 2) & 1);
          ia++;
          if (u == 4) break;
          wgmma_fence();
#pragma unroll
          for (int kk = 4; kk < 8; kk++) wgmma_ss_n72(acc, dsc<128, 0>(da, kk * 2048), dsc<128, 0>(db, kk * 2304), 1);
          wgmma_commit();
          prev = c.s; c.next();
        }
        RCLK_INIT;
        wgmma_wait<0>();
        RCLK(0);
        release(c.s);
        c.next();
        TRC(tr && P5TRACE != 5, w, tb + 4);
        MCLK(1, 4);
#pragma unroll
        for (int u = 0; u < 4; u++)
          stsm4(xm + u * 32, pack2(acc[8 * u], acc[8 * u + 1]), pack2(acc[8 * u + 2], acc[8 * u + 3]), pack2(acc[8 * u + 4], acc[8 * u + 5]), pack2(acc[8 * u + 6], acc[8 * u + 7]));
        asm volatile("stmatrix.sync.aligned.m8n8.x2.shared.b16 [%0], {%1,%2};" ::"r"(xm + 128), "r"(pack2(acc[32], acc[33])), "r"(pack2(acc[34], acc[35])) : "memory");
        RCLK(1);
        bar_sync(8 + q, 64);
        RCLK(2);
#pragma unroll
        for (int u = 0; u < 5; u++) {
          const uint4 v = lds128(xl + u * 512);
          stg128_if(u < 4 || lane < 16, xd[u], v.x, v.y, v.z, v.w);
        }
        RCLK(3);
        signal(EV_X1);
        RCLK(4);
        if (P.zero == 0) {
          float s0 = 0.f, s1 = 0.f, q0 = 0.f, q1 = 0.f;
#pragma unroll
          for (int i = 0; i < 36; i++) {
            if (i & 2) { s1 += acc[i]; q1 = fmaf(acc[i], acc[i], q1); } else { s0 += acc[i]; q0 = fmaf(acc[i], acc[i], q0); }
          }
          s0 = qsum(s0); s1 = qsum(s1); q0 = qsum(q0); q1 = qsum(q1);
          const float ss = t ? s1 : s0, m = ss * (1.f / 72.f);
          ll_st128_if(t < 2, g_ST1 + (hw * 8 + js) * 64 + 16 * q + 8 * t + g, m, fmaxf((t ? q1 : q0) - ss * m, 0.f), tag);
        }
        RCLK(5);
        TRC(tr, w, tb + 5);
        RCLK(6);
        RCLK_OUT;
      }
      {
        uint32_t xA[36][4];
        float acc[32];
        uint32_t s0, jump;
        uint64_t db;
        auto bwait = [&](uint32_t dhi, bool skip) {
          s0 = c.s;
          c.next();
          if (!skip) mbar_wait_c(bars + B_FULL + c.s * 8, c.ph);
          db = dsc2(dlo(sb + s0 * ST_BYTES + ST_B, 512), 0, dhi + P.zero); jump = (c.s - s0) * (ST_BYTES >> 4) - 17 * 128;
        };
        auto mma = [&](int kk, int pp, bool hand) {
          wgmma_rs_n64(acc, xA[kk], db, kk != 0);
          dadd(db, kk == 17 ? jump : 128 + P.zero);
          if (kk == pp && hand) bar_arrive(7 - w, 256);
          if (kk == 17 || kk == 35) wgmma_commit();
          if (kk == 21) { wgmma_commit(); wgmma_wait<1>(); release(s0); }
        };
        {
          bwait(0x40000040u, false);
          mbar_wait_c(bars + B_GATE3, L);
          float mean0, mean1, rs0, rs1;
          stat_get(g_ST1 + ((rb * 2 + w) * 8 + 2 * t) * 64 + 16 * q + g, tag, 72.f, LN_EPS, mean0, rs0, mean1, rs1);
          const uint32_t ns0 = pack2(GA * rs0, GA * rs0), ns1 = pack2(GA * rs1, GA * rs1);
          const uint32_t nb0 = pack2(-mean0 * blo(ns0), -mean0 * blo(ns0)), nb1 = pack2(-mean1 * blo(ns1), -mean1 * blo(ns1));
          const uint32_t al = sb + (aoff & 8191);
#pragma unroll
          for (int kb = 0; kb < 9; kb++) {
            mbar_wait_c(bars + B_FA3 + (9 * w + kb) * 8, L);
            TRC(tr && kb == 0, w, tb + 6);
            MCLK(kb == 0, 5);
            if (kb == 0) SCLK(0);
            QCLK(kb);
            const uint32_t at = al + (w ? (((kb + 1) >> 1) & 3) * ST_BYTES + ((kb + 1) & 1) * 8192 : ((kb >> 1) & 3) * ST_BYTES + (kb & 1) * 8192);
#pragma unroll
            for (int kk = 4 * kb; kk < 4 * kb + 4; kk++) ldsm4(xA[kk], at ^ ((kk & 3) << 5));
            if (kb) { wgmma_fence(); mma(4 * kb - 2, PP30, w); mma(4 * kb - 1, PP30, w); }
            const uint32_t dep = xA[4 * kb][0] & xA[4 * kb + 1][0] & xA[4 * kb + 2][0] & xA[4 * kb + 3][0] & P.zero;
#pragma unroll
            for (int kk = 4 * kb; kk < 4 * kb + 4; kk++) {
#pragma unroll
              for (int e = 0; e < 4; e++) xA[kk][e] = hfma2(xA[kk][e], (e & 1) ? ns1 : ns0, (e & 1) ? nb1 : nb0);
            }
            mbar_arrive_if(lane == 0 && (kb == 0 || w == 0), bars + B_EA3 + (9 * w + kb) * 8 + dep);
            wgmma_fence();
            mma(4 * kb, PP30, w); mma(4 * kb + 1, PP30, w);
          }
          mma(34, PP30, w); mma(35, PP30, w);
        }
        const uint32_t off2 = lds32(sb + SM_OFF);
        uint8_t* z1d = z1_block(rb, w, j) + (tid & 127) * 16;
        uint8_t* zd = z2_block(2 * rb + (q >> 1), j) + (4 * (q & 1) + w) * 4608 + ((g & 3) * 2 + (g >> 2)) * 16 + t * 4;
        float sm[4] = {0.f, 0.f, 0.f, 0.f}, qq[4] = {0.f, 0.f, 0.f, 0.f};
        auto gelu = [&](auto nz2) {
          constexpr int NZ2 = nz2.value, R = 8 - NZ2, D = NZ2 == 8 ? GM2 : NZ2 ? GMM : GM1;
          float th[32], gb = GB;
          uint32_t qa = 0, qb = 0;
          auto head = [&](int G) {
#pragma unroll
            for (int e = 0; e < 4; e++) { const float v = acc[4 * G + e]; th[4 * G + e] = tanh_fast(v * fmaf(v, v, gb)); }
          };
#pragma unroll
          for (int i = 0; i < D; i++) head((i + R) & 7);
#pragma unroll
          for (int i = 0; i < 8; i++) {
            const int G = (i + R) & 7;
            if (i + D < 8) head((i + D + R) & 7);
            float* z = acc + 4 * G;
#pragma unroll
            for (int e = 0; e < 4; e++) z[e] = fmaf(z[e], th[4 * G + e], z[e]);
            uint32_t pa = pack2(z[0], z[1]), pb = pack2(z[2], z[3]), tok;
            if (i < NZ2) {
#pragma unroll
              for (int e = 0; e < 4; e++) { sm[e] += z[e]; qq[e] = fmaf(z[e], z[e], qq[e]); }
              pa = hsub2(pa, off2); pb = hsub2(pb, off2);
              stg32(zd + i * 128, pa); stg32(zd + i * 128 + 9216, pb);
              tok = pa ^ pb ^ __float_as_uint(qq[1]);
            } else {
              if (G & 1) stg128(z1d + (G >> 1) * 2048 + (NZ2 ? 32768 : 0), qa, qb, pa, pb);
              qa = pa; qb = pb;
              tok = pa ^ pb;
            }
            gb = __uint_as_float(tok * P.zero + __float_as_uint(GB));
          }
        };
#pragma unroll 1
        for (int p = 0;; p++) {
          wgmma_wait<0>();
          release(c.s);
          c.next();
          TRC(tr && p == 4, w, tb + 7);
          TRC(tr && p == 8, w, tb + 11);
          MCLK(p == 8, 6);
          SCLK(2 * p + 1);
          QCLK(10 + 3 * p);
          if (p < 4) {
            gelu(Int<8>{});
            zd += 1024;
          } else if (p == 4) {
            gelu(Int<4>{});
            signal(EV_ZN);
            const float a0 = qsum(sm[0] + sm[1]), a1 = qsum(sm[2] + sm[3]), q0 = qsum(qq[0] + qq[1]), q1 = qsum(qq[2] + qq[3]);
            const float ss = t ? a1 : a0, m = ss * (1.f / 288.f);
            ll_st128_if(t < 2, g_ZST + (rb * 2 + w) * 512 + j * 64 + 16 * q + 8 * t + g, m - blo(off2), fmaxf((t ? q1 : q0) - ss * m, 0.f), tag);
            TRC(tr, w, tb + 8);
            TRC(tr, w, tb + 9);
          } else {
            gelu(Int<0>{});
            z1d += 8192;
          }
          SCLK(2 * p + 2);
          QCLK(11 + 3 * p);
          if (p == 8) break;
          bwait(p == 3 ? 0x80000040u : 0x40000040u, w);
          bar_sync(6 + w, 256);
          TRC(tr && p == 4, w, tb + 10);
          wgmma_fence();
#pragma unroll
          for (int kk = 0; kk < 36; kk++) mma(kk, PP3, w == 0 || p < 7);
        }
        signal(EV_Z1);
        TRC(tr, w, tb + 12);
      }
      uint32_t hA[18][4];
      {
        float acc[144];
        const float c0 = __uint_as_float(lds32(sb + SM_OFF + 4));
#pragma unroll
        for (int i = 0; i < 144; i++) {
          asm volatile("fma.rn.f32 %0, %1, %2, %3;" : "=f"(acc[i]) : "f"(__uint_as_float(P.zero)), "f"((float)(i + 2)), "f"(c0));
        }
        uint32_t prev = 0;
        auto stage = [&](int kb) {
          mbar_wait_c(bars + B_FULL + c.s * 8, c.ph);
          TRC(tr && kb == 0, w, tb + 13);
          SCLK(22 + kb);
          const uint32_t st = sb + c.s * ST_BYTES, rt = sb + SM_RT + kb * 128 + t * 8;
          uint64_t db = dsc2(dlo(st + ST_B, 4608), 0, 8 + P.zero);
          uint32_t a[4][4];
#pragma unroll
          for (int kk = 0; kk < 4; kk++) {
            uint32_t r[4];
            ldsm4(r, st + (aoff ^ (kk << 5)));
            const uint2 sc = lds64(rt + kk * 32);
            a[kk][0] = hmul2(__byte_perm(r[0], r[2], 0x5410), sc.x); a[kk][2] = hmul2(__byte_perm(r[0], r[2], 0x7632), sc.y);
            a[kk][1] = hmul2(__byte_perm(r[1], r[3], 0x5410), sc.x); a[kk][3] = hmul2(__byte_perm(r[1], r[3], 0x7632), sc.y);
          }
          if (LAG4 && (kb & 1) == (LAG4 & 1)) yield(32 - kb, LAG4);
          wgmma_fence();
#pragma unroll
          for (int i = 0; i < 8; i++) {
            const int kk = i & 3, hf = i >> 2;
            wgmma_rs_n144(acc + hf * 72, a[kk], db, 1);
            dadd(db, i == 3 ? 144u - 3 * 576 : 576 + P.zero);
            if (i == 0) { wgmma_commit(); wgmma_wait<1>(); release_if(kb, prev); }
            if (i == 3) wgmma_commit();
          }
          wgmma_commit();
          prev = c.s; c.next();
        };
        mbar_wait_c(bars + B_RT, L);
#pragma unroll 1
        for (int kb = 0; kb < 32; kb += 2) {
          if (kb == 8) mbar_wait_c(bars + B_RT1, L);
          MCLK((kb & 7) == 4, 10 + (kb >> 3));
          stage(kb);
          stage(kb + 1);
        }
        if (LAG4) { yield_done(); lagph ^= 1; }
        HCLK(0);
        mbar_wait_c(bars + B_CV + w * 8, L);
        HCLK(1);
        const float gk = 0.5f / GA;
        const float c1 = __uint_as_float(lds32(sb + SM_OFF + 4));
        const float gb0 = -gk * (c1 + __uint_as_float(lds32(sb + SM_CV + w * 256 + (16 * q + g) * 4))), gb1 = -gk * (c1 + __uint_as_float(lds32(sb + SM_CV + w * 256 + (16 * q + g + 8) * 4)));
        mbar_wait_c(w ? bars + B_ZB : bars + B_FULL + c.s * 8, w ? L : c.ph);
        HCLK(2);
        const uint32_t sx = c.s;
        c.next();
        const uint32_t zt = sb + (tid & 127) * 16, zs0 = zt + sx * ST_BYTES + w * ZB, zs1 = w ? zt + SM_STG - 16384 : zs0, zs2 = w ? zt + c.s * ST_BYTES - 20480 : zs0;
#pragma unroll
        for (int u = 0; u < 18; u++) {
          if (u == 0) { wgmma_wait<1>(); HCLK(3); }
          if (u == 9) {
            HCLK(4);
            wgmma_wait<0>();
            HCLK(5);
            release(prev);
            if (L == 0) signal(EV_P4);
            if (w == 1) mbar_wait_c(bars + B_FULL + c.s * 8, c.ph);
            TRC(tr, w, tb + 14);
            SCLK(54);
          }
          const uint4 z = lds128((u < 8 ? zs0 : u < 10 ? zs1 : zs2) + u * 2048);
          hA[u][0] = hmul2(z.x, pack2(fmaf(acc[8 * u], gk, gb0), fmaf(acc[8 * u + 1], gk, gb0)));
          hA[u][1] = hmul2(z.y, pack2(fmaf(acc[8 * u + 2], gk, gb1), fmaf(acc[8 * u + 3], gk, gb1)));
          hA[u][2] = hmul2(z.z, pack2(fmaf(acc[8 * u + 4], gk, gb0), fmaf(acc[8 * u + 5], gk, gb0)));
          hA[u][3] = hmul2(z.w, pack2(fmaf(acc[8 * u + 6], gk, gb1), fmaf(acc[8 * u + 7], gk, gb1)));
        }
        uint32_t dep = P.zero;
#pragma unroll
        for (int u = 0; u < 18; u++) dep &= hA[u][0];
        release(sx, dep);
        TRC(tr, w, tb + 15);
        HCLK(6);
      }
      {
        CLK_INIT;
        if (w == 1) bar_arrive(6, 256);
        uint32_t pk[16];
#pragma unroll
        for (int i = 0; i < 16; i++) pk[i] = 0u;
        auto dump = [&](int p) {
          const uint32_t d = sb + (p & 3) * ST_BYTES, cb = p + j >= 9 ? p + j - 9 : p + j;
          if (lane == 0) asm volatile("cp.async.bulk.wait_group.read 3;" ::: "memory");
          __syncwarp();
#pragma unroll
          for (int u = 0; u < 4; u++) stsm4(d + (aoff ^ (u << 5)), pk[4 * u], pk[4 * u + 1], pk[4 * u + 2], pk[4 * u + 3]);
          fence_async_s();
          __syncwarp();
          tma3d_red_p(lane == 0, &P.red, cb * 64, rb * 64 + q * 16, w, d + w * 8192 + q * 2048);
        };
#pragma unroll 1
        for (int p = 0; p < 9; p++) {
          float acc[32];
          CLK(0);
          mbar_wait_c(bars + B_FULL + c.s * 8, c.ph);
          uint64_t db = dsc2(dlo(sb + c.s * ST_BYTES + ST_B + (j & 1) * 4096, 0), 0, 0x40000040u + P.zero);
          CLK(1);
          HCLK(7 + 2 * p);
          bar_sync(6 + w, 256);
          CLK(2);
          wgmma_fence();
#pragma unroll
          for (int kk = 0; kk < 18; kk++) {
            wgmma_rs_n64(acc, hA[kk], db, kk != 0);
            dadd(db, kk == 15 ? 128 - (j & 1) * (36864 >> 4) : 128 + P.zero);
            if (kk == PPK && (w == 0 || p < 8)) bar_arrive(7 - w, 256);
          }
          wgmma_commit();
          CLK(3);
          if (p > 0) dump(p - 1);
          CLK(5);
          wgmma_wait<0>();
          CLK(4);
          HCLK(8 + 2 * p);
          MCLK(p == 1 || p == 8, 7 + (p >> 3));
          release_if(L == 0 || p < 5, c.s);
          c.next();
#pragma unroll
          for (int i = 0; i < 16; i++) pk[i] = pack2(acc[2 * i], acc[2 * i + 1]);
          if (p == 8) { TRC(tr, w, tb + 16); dump(8); TRC(tr, w, tb + 17); }
        }
        if (lane == 0) asm volatile("cp.async.bulk.wait_group 0;" ::: "memory");
        HCLK(25);
        MCLK(1, 9);
        if (L == 0) signal(EV_PT);
        CLK_OUT;
        TRC(tr, w, tb + 18);
      }
    }
    if ((tid & 127) == 0) g_flags[(rb * 2 + w) * 32 + FR_EP + j] = epoch + 1;
    if (tid == 0) g_flags[FJ + j * 32 + FJ_EP + rb] = epoch + 1;
  }
}

typedef CUresult (*EncodeFn)(CUtensorMap*, CUtensorMapDataType, cuuint32_t, void*, const cuuint64_t*, const cuuint64_t*, const cuuint32_t*,
                             const cuuint32_t*, CUtensorMapInterleave, CUtensorMapSwizzle, CUtensorMapL2promotion, CUtensorMapFloatOOBfill);

static void make_map(EncodeFn fn, CUtensorMap* m, const void* ptr, int rank, uint64_t d0, uint64_t d1, uint64_t d2, uint64_t s1, uint64_t s2,
                     uint32_t b0, uint32_t b1, uint32_t b2, CUtensorMapSwizzle swz) {
  cuuint64_t dims[3] = {d0, d1, d2}, strides[2] = {s1, s2};
  cuuint32_t box[3] = {b0, b1, b2}, es[3] = {1, 1, 1};
  fn(m, CU_TENSOR_MAP_DATA_TYPE_BFLOAT16, rank, const_cast<void*>(ptr), dims, strides, box, es, CU_TENSOR_MAP_INTERLEAVE_NONE, swz,
     CU_TENSOR_MAP_L2_PROMOTION_L2_128B, CU_TENSOR_MAP_FLOAT_OOB_FILL_NONE);
}

}

extern "C" void kernel_launch(void* const* d_in, const int* in_sizes, int n_in, void* d_out, int out_size) {
  using namespace mk;
  (void)in_sizes; (void)n_in; (void)out_size;
  static EncodeFn fn = nullptr;
  static uint8_t* wq;
  static float* csp;
  if (!fn) {
    cudaGetSymbolAddress((void**)&wq, g_WQ);
    cudaGetSymbolAddress((void**)&csp, g_CSP);
    cudaDriverEntryPointQueryResult qr;
    cudaGetDriverEntryPoint("cuTensorMapEncodeTiled", (void**)&fn, cudaEnableDefault, &qr);
    cudaFuncSetAttribute(mega_kernel, cudaFuncAttributeMaxDynamicSharedMemorySize, SM_TOTAL);
  }
  Params p;
  p.wqkv = (const __nv_bfloat16*)d_in[1];
  p.wo = (const __nv_bfloat16*)d_in[2];
  p.w_in = (const __nv_bfloat16*)d_in[4];
  p.w_sp = (const __nv_bfloat16*)d_in[5];
  p.b_sp = (const __nv_bfloat16*)d_in[6];
  p.w_out = (const __nv_bfloat16*)d_in[7];
  p.zero = 0;
  p.wq = wq;
  p.csp = csp;
  p.xs[0] = (uint8_t*)d_in[0];
  p.xs[1] = (uint8_t*)d_out;
  make_map(fn, &p.wsp, p.w_sp, 3, 2048, 1024, 2, 8192, 4096, 64, 64, 2, CU_TENSOR_MAP_SWIZZLE_128B);
  for (int i = 0; i < 2; i++) {
    make_map(fn, &p.act[i], p.xs[i], 3, DM, 1024, 2, 2304, 1152, 64, 64, 1, CU_TENSOR_MAP_SWIZZLE_128B);
    make_map(fn, &p.res[i], p.xs[i], 3, DM, 1024, 2, 2304, 1152, 144, 64, 1, CU_TENSOR_MAP_SWIZZLE_NONE);
  }
  make_map(fn, &p.red, d_out, 3, DM, 1024, 2, 2304, 1152, 64, 16, 1, CU_TENSOR_MAP_SWIZZLE_128B);
  for (int i = 0; i < 2; i++) {
    cuuint64_t dims[4] = {i ? 4608u : 2304u, 8, i ? 1u : 2u, 72}, strides[3] = {9216, 4608, 8 * 9216};
    cuuint32_t box[4] = {i ? 64u : 32u, 8, i ? 1u : 2u, 18}, es[4] = {1, 1, 1, 1};
    fn(i ? &p.win64 : &p.win, CU_TENSOR_MAP_DATA_TYPE_BFLOAT16, 4, d_in[4], dims, strides, box, es, CU_TENSOR_MAP_INTERLEAVE_NONE,
       i ? CU_TENSOR_MAP_SWIZZLE_128B : CU_TENSOR_MAP_SWIZZLE_64B, CU_TENSOR_MAP_L2_PROMOTION_L2_128B, CU_TENSOR_MAP_FLOAT_OOB_FILL_NONE);
  }
  make_map(fn, &p.wout, p.w_out, 2, 576, 2304, 1, 1152, 0, 64, 144, 1, CU_TENSOR_MAP_SWIZZLE_128B);
  mega_kernel<<<NGRID, 384, SM_TOTAL, cudaStreamPerThread>>>(p);
}
```

```cpp
#include <cuda_runtime.h>
#include <cuda.h>
#include <cuda_bf16.h>
#include <stdint.h>

#define MK_TRACE 0
#define MK_DBG 0
#define P5TRACE 0
#define LAG1 1
#define PP3 32
#define PP30 33
#define LAG4 1
#define SPL 2
#define NAP 200
#define NAP0 2000
#define GM2 1
#define GMM 1
#define GM1 2
#define C0S 32.f
#define OFM 0x10u
#define PPK 13

namespace mk {

constexpr int SEQ = 2048, DM = 576, FH = 2304;
constexpr int NCTA = 128;
constexpr int NGRID = 132;
constexpr uint32_t ZB = 36864;
constexpr uint32_t WQ_SL = 72 * 3456;
constexpr uint32_t WO_SL = 72 * 1152;
constexpr float LN_EPS = 1e-5f;
constexpr float GA = 0.3292034911525734f, GB = 2.423681954311584f;

constexpr uint32_t ST_BYTES = 53248, ST_B = 16384, NST = 4;
constexpr uint32_t SM_STG = NST * ST_BYTES;
constexpr uint32_t SM_BAR = SM_STG + 2 * 9216;
constexpr uint32_t SM_OFF = SM_BAR + 1008;
constexpr uint32_t SM_TOTAL = SM_BAR + 1024;
constexpr uint32_t SM_RT = SM_STG + 4096, SM_CV = SM_STG + 12288, SM_WT = SM_CV + 512;
constexpr uint32_t SM_WOI = 44032, SM_CSQ = 49280, SM_XST = 50176;
constexpr uint32_t B_FULL = 0, B_EMPTY = 32, B_FULLA = 64, B_RES = 128, B_WT = 144, B_IMG = 160, B_WOI = 168, B_ZB = 176, B_GATE3 = 184, B_Z1 = 192, B_LAG = 200,
                   B_RT = 208, B_CSQ = 216, B_CV = 224, B_AD = 240, B_EVT = 272, B_RT1 = 368, B_XRW = 384, B_FA3 = 400, B_EA3 = 544;
enum { EV_PT = 0, EV_O = 1, EV_X1 = 2, EV_ZN = 3, EV_Z1 = 4, EV_P4 = 5, EV_N = 6 };

enum { FR_X2 = 0, FR_O = 1, FR_X1 = 3, FR_EP = 16, FJ = 32 * 32, FJ_WQ = 0, FJ_WO = 1, FJ_WQ0 = 2, FJ_ZN = 3, FJ_P4 = 5, FJ_EP = 16, F_N = FJ + 8 * 32 };

__device__ __align__(1024) uint8_t g_Z[512 * ZB];
constexpr uint32_t POISON = 0xffffffffu;
__device__ __align__(1024) uint8_t g_O[32 * 2 * ZB];
__device__ __align__(1024) uint8_t g_X[SEQ * DM * 2];
#define SLOW(i) do {} while (0)
__device__ __align__(1024) uint8_t g_WQ[8 * WQ_SL];
__device__ __align__(1024) uint8_t g_WO[8 * WO_SL];
__device__ __align__(1024) float g_CSP[2 * NCTA * 216];
__device__ __align__(1024) uint2 g_RT[SEQ];
__device__ __align__(1024) uint4 g_XST[2 * SEQ];
__device__ __align__(1024) uint4 g_ST1[SEQ * 8];
__device__ __align__(1024) uint4 g_ZST[SEQ * 8];
__device__ __align__(1024) uint4 g_HALO[32 * 8 * 6 * 32];
__device__ __align__(1024) uint32_t g_flags[F_N];

struct Params {
  const __nv_bfloat16 *wqkv;
  uint8_t* wq;
  float* csp;
  uint32_t zero;
  const __nv_bfloat16 *wo, *w_in, *w_sp, *b_sp, *w_out;
  uint8_t* xs[3];
  CUtensorMap wsp, win, win64, wout;
  CUtensorMap act[3];
  CUtensorMap res[2];
  CUtensorMap red[2];
  CUtensorMap psn;
};

__device__ __forceinline__ uint32_t smem_u32(const void* p) { return (uint32_t)__cvta_generic_to_shared(p); }
__device__ __forceinline__ void mbar_init(uint32_t bar, uint32_t cnt) { asm volatile("mbarrier.init.shared::cta.b64 [%0], %1;" ::"r"(bar), "r"(cnt)); }
__device__ __forceinline__ void mbar_arrive(uint32_t bar) { asm volatile("mbarrier.arrive.shared::cta.b64 _, [%0];" ::"r"(bar) : "memory"); }
__device__ __forceinline__ void mbar_wait(uint32_t bar, uint32_t parity) {
  asm volatile(
      "{\n.reg .pred p;\n.reg .u32 c;\nmov.u32 c, 0;\nLAB_WAIT:\n"
      "mbarrier.try_wait.parity.shared::cta.b64 p, [%0], %1;\n@p bra LAB_DONE;\n"
      "add.u32 c, c, 1;\nsetp.lt.u32 p, c, 0x100000;\n@p bra LAB_WAIT;\ntrap;\nLAB_DONE:\n}" ::"r"(bar), "r"(parity)
      : "memory");
}
__device__ __forceinline__ void mbar_wait_c(uint32_t bar, uint32_t parity) {
  asm volatile("{\n.reg .pred p;\nLAB_WAIT:\nmbarrier.try_wait.parity.shared::cta.b64 p, [%0], %1;\n@!p bra LAB_WAIT;\n}" ::"r"(bar), "r"(parity) : "memory");
}
__device__ __forceinline__ void flag_wait(const uint32_t* f, uint32_t target) {
  asm volatile(
      "{\n.reg .pred p;\n.reg .u32 c, v;\nmov.u32 c, 0;\nLAB_WAIT:\n"
      "ld.relaxed.gpu.global.u32 v, [%0];\nsub.u32 v, v, %1;\nsetp.ge.s32 p, v, 0;\n@p bra LAB_DONE;\n"
      "add.u32 c, c, 1;\nsetp.lt.u32 p, c, 0x400000;\n@p bra LAB_WAIT;\ntrap;\nLAB_DONE:\nfence.acquire.gpu;\n}" ::"l"(f), "r"(target)
      : "memory");
}
__device__ __forceinline__ void fence_gpu() { asm volatile("fence.acq_rel.gpu;" ::: "memory"); }
__device__ __forceinline__ void fence_async_g() { asm volatile("fence.proxy.async.global;" ::: "memory"); }
__device__ __forceinline__ void fence_async_s() { asm volatile("fence.proxy.async.shared::cta;" ::: "memory"); }
__device__ __forceinline__ uint32_t elect_one() {
  uint32_t p; asm volatile("{\n.reg .pred P;\nelect.sync _|P, 0xffffffff;\nselp.u32 %0, 1, 0, P;\n}" : "=r"(p)); return p;
}
__device__ __forceinline__ void expect_tx_p(uint32_t el, uint32_t bar, uint32_t bytes) {
  asm volatile("{\n.reg .pred P;\nsetp.ne.u32 P, %2, 0;\n@P mbarrier.arrive.expect_tx.shared::cta.b64 _, [%0], %1;\n}" ::"r"(bar), "r"(bytes), "r"(el) : "memory");
}
__device__ __forceinline__ void bulk_load_p(uint32_t el, uint32_t dst, const void* src, uint32_t bytes, uint32_t bar) {
  asm volatile("{\n.reg .pred P;\nsetp.ne.u32 P, %4, 0;\n@P cp.async.bulk.shared::cluster.global.mbarrier::complete_tx::bytes [%0], [%1], %2, [%3];\n}" ::"r"(dst), "l"(src), "r"(bytes), "r"(bar), "r"(el) : "memory");
}
__device__ __forceinline__ uint64_t policy_evict_first() { uint64_t p; asm("createpolicy.fractional.L2::evict_first.b64 %0, 1.0;" : "=l"(p)); return p; }
__device__ __forceinline__ void bulk_load_h(uint32_t el, uint32_t dst, const void* src, uint32_t bytes, uint32_t bar, bool ef, uint64_t pol) {
  if (ef) {
    asm volatile("{\n.reg .pred P;\nsetp.ne.u32 P, %4, 0;\n@P cp.async.bulk.shared::cluster.global.mbarrier::complete_tx::bytes.L2::cache_hint [%0], [%1], %2, [%3], %5;\n}" ::"r"(dst), "l"(src), "r"(bytes), "r"(bar), "r"(el), "l"(pol) : "memory");
  } else {
    asm volatile("{\n.reg .pred P;\nsetp.ne.u32 P, %4, 0;\n@P cp.async.bulk.shared::cluster.global.mbarrier::complete_tx::bytes [%0], [%1], %2, [%3];\n}" ::"r"(dst), "l"(src), "r"(bytes), "r"(bar), "r"(el) : "memory");
  }
}
__device__ __forceinline__ void bulk_mc_h(uint32_t el, uint32_t dst, const void* src, uint32_t bytes, uint32_t bar, bool ef, uint64_t pol) {
  if (ef) {
    asm volatile("{\n.reg .pred P;\nsetp.ne.u32 P, %4, 0;\n@P cp.async.bulk.shared::cluster.global.mbarrier::complete_tx::bytes.multicast::cluster.L2::cache_hint [%0], [%1], %2, [%3], %5, %6;\n}" ::"r"(dst), "l"(src), "r"(bytes), "r"(bar), "r"(el), "h"((uint16_t)3), "l"(pol) : "memory");
  } else {
    asm volatile("{\n.reg .pred P;\nsetp.ne.u32 P, %4, 0;\n@P cp.async.bulk.shared::cluster.global.mbarrier::complete_tx::bytes.multicast::cluster [%0], [%1], %2, [%3], %5;\n}" ::"r"(dst), "l"(src), "r"(bytes), "r"(bar), "r"(el), "h"((uint16_t)3) : "memory");
  }
}
__device__ __forceinline__ void tma3d_h(uint32_t el, uint32_t dst, const CUtensorMap* m, int c0, int c1, int c2, uint32_t bar, bool ef, uint64_t pol) {
  if (ef) {
    asm volatile("{\n.reg .pred P;\nsetp.ne.u32 P, %6, 0;\n@P cp.async.bulk.tensor.3d.shared::cluster.global.mbarrier::complete_tx::bytes.L2::cache_hint [%0], [%1, {%3, %4, %5}], [%2], %7;\n}" ::"r"(dst), "l"(m), "r"(bar), "r"(c0), "r"(c1), "r"(c2), "r"(el), "l"(pol) : "memory");
  } else {
    asm volatile("{\n.reg .pred P;\nsetp.ne.u32 P, %6, 0;\n@P cp.async.bulk.tensor.3d.shared::cluster.global.mbarrier::complete_tx::bytes [%0], [%1, {%3, %4, %5}], [%2];\n}" ::"r"(dst), "l"(m), "r"(bar), "r"(c0), "r"(c1), "r"(c2), "r"(el) : "memory");
  }
}
__device__ __forceinline__ void tma2d_mc_h(uint32_t el, uint32_t dst, const CUtensorMap* m, int c0, int c1, uint32_t bar, bool ef, uint64_t pol) {
  if (ef) {
    asm volatile("{\n.reg .pred P;\nsetp.ne.u32 P, %5, 0;\n@P cp.async.bulk.tensor.2d.shared::cluster.global.mbarrier::complete_tx::bytes.multicast::cluster.L2::cache_hint [%0], [%1, {%3, %4}], [%2], %6, %7;\n}" ::"r"(dst), "l"(m), "r"(bar), "r"(c0), "r"(c1), "r"(el), "h"((uint16_t)3), "l"(pol) : "memory");
  } else {
    asm volatile("{\n.reg .pred P;\nsetp.ne.u32 P, %5, 0;\n@P cp.async.bulk.tensor.2d.shared::cluster.global.mbarrier::complete_tx::bytes.multicast::cluster [%0], [%1, {%3, %4}], [%2], %6;\n}" ::"r"(dst), "l"(m), "r"(bar), "r"(c0), "r"(c1), "r"(el), "h"((uint16_t)3) : "memory");
  }
}
__device__ __forceinline__ void tma4d_mc(uint32_t el, uint32_t dst, const CUtensorMap* m, int c0, int c3, uint32_t bar, uint64_t pol) {
  asm volatile("{\n.reg .pred P;\nsetp.ne.u32 P, %5, 0;\n@P cp.async.bulk.tensor.4d.shared::cluster.global.mbarrier::complete_tx::bytes.multicast::cluster.L2::cache_hint [%0], [%1, {%3, 0, 0, %4}], [%2], %6, %7;\n}" ::"r"(dst), "l"(m), "r"(bar), "r"(c0), "r"(c3), "r"(el), "h"((uint16_t)3), "l"(pol) : "memory");
}
__device__ __forceinline__ void mbar_arrive_cluster(uint32_t addr) { asm volatile("mbarrier.arrive.shared::cluster.b64 _, [%0];" ::"r"(addr) : "memory"); }
__device__ __forceinline__ void mbar_arrive_cluster_if(bool c, uint32_t addr) {
  asm volatile("{\n.reg .pred P;\nsetp.ne.u32 P, %1, 0;\n@P mbarrier.arrive.shared::cluster.b64 _, [%0];\n}" ::"r"(addr), "r"((uint32_t)c) : "memory");
}
__device__ __forceinline__ void mbar_arrive_if(bool c, uint32_t addr) {
  asm volatile("{\n.reg .pred P;\nsetp.ne.u32 P, %1, 0;\n@P mbarrier.arrive.shared::cta.b64 _, [%0];\n}" ::"r"(addr), "r"((uint32_t)c) : "memory");
}
__device__ __forceinline__ uint32_t mapa(uint32_t addr, uint32_t rank) { uint32_t r; asm("mapa.shared::cluster.u32 %0, %1, %2;" : "=r"(r) : "r"(addr), "r"(rank)); return r; }
__device__ __forceinline__ void bulk_store_p(uint32_t el, void* dst, uint32_t src, uint32_t bytes) {
  asm volatile("{\n.reg .pred P;\nsetp.ne.u32 P, %3, 0;\n@P cp.async.bulk.global.shared::cta.bulk_group [%0], [%1], %2;\n}" ::"l"(dst), "r"(src), "r"(bytes), "r"(el) : "memory");
}
__device__ __forceinline__ void flag_release_p(uint32_t el, uint32_t* f) {
  asm volatile("{\n.reg .pred P;\nsetp.ne.u32 P, %1, 0;\n@P red.release.gpu.global.add.u32 [%0], 1;\n}" ::"l"(f), "r"(el) : "memory");
}
__device__ __forceinline__ void flag_add_p(uint32_t el, uint32_t* f) {
  asm volatile("{\n.reg .pred P;\nsetp.ne.u32 P, %1, 0;\n@P red.relaxed.gpu.global.add.u32 [%0], 1;\n}" ::"l"(f), "r"(el) : "memory");
}
__device__ __forceinline__ void prefetch_l2(const void* src, uint32_t bytes) { asm volatile("cp.async.bulk.prefetch.L2.global [%0], %1;" ::"l"(src), "r"(bytes) : "memory"); }
__device__ __forceinline__ void prefetch_map(const CUtensorMap* m) { asm volatile("prefetch.tensormap [%0];" ::"l"(m) : "memory"); }
__device__ __forceinline__ void wgmma_fence() { asm volatile("wgmma.fence.sync.aligned;" ::: "memory"); }
__device__ __forceinline__ void wgmma_commit() { asm volatile("wgmma.commit_group.sync.aligned;" ::: "memory"); }
template <int N> __device__ __forceinline__ void wgmma_wait() { asm volatile("wgmma.wait_group.sync.aligned %0;" ::"n"(N) : "memory"); }
__device__ __forceinline__ uint32_t dlo(uint32_t addr, uint32_t lbo) { return ((addr & 0x3FFFF) >> 4) + ((lbo >> 4) << 16); }
template <uint32_t SBO, uint32_t SWZ> __device__ __forceinline__ uint64_t dsc(uint32_t lo, uint32_t off) {
  uint64_t d; asm("mov.b64 %0, {%1, %2};" : "=l"(d) : "r"(lo + (off >> 4)), "n"((SBO >> 4) | (SWZ << 30))); return d;
}
__device__ __forceinline__ uint64_t dsc2(uint32_t lo, uint32_t off, uint32_t hi) {
  uint64_t d; asm("mov.b64 %0, {%1, %2};" : "=l"(d) : "r"(lo + (off >> 4)), "r"(hi)); return d;
}
__device__ __forceinline__ uint64_t dat(uint64_t d, uint32_t off, uint32_t one) { uint64_t r; asm("mad.wide.u32 %0, %1, %2, %3;" : "=l"(r) : "r"(one), "r"(off >> 4), "l"(d)); return r; }
__device__ __forceinline__ void dadd(uint64_t& d, uint32_t v) {
  asm("{\n.reg .b32 lo, hi;\nmov.b64 {lo, hi}, %0;\nadd.u32 lo, lo, %1;\nmov.b64 %0, {lo, hi};\n}" : "+l"(d) : "r"(v));
}
template <int R> __device__ __forceinline__ void reg_alloc() { asm volatile("setmaxnreg.inc.sync.aligned.u32 %0;" ::"n"(R)); }
template <int R> __device__ __forceinline__ void reg_dealloc() { asm volatile("setmaxnreg.dec.sync.aligned.u32 %0;" ::"n"(R)); }
__device__ __forceinline__ void bar_sync(int id, int n) { asm volatile("bar.sync %0, %1;" ::"r"(id), "r"(n) : "memory"); }
__device__ __forceinline__ void bar_arrive(int id, int n) { asm volatile("bar.arrive %0, %1;" ::"r"(id), "r"(n) : "memory"); }
__device__ __forceinline__ void ldsm4(uint32_t* r, uint32_t addr) {
  asm volatile("ldmatrix.sync.aligned.m8n8.x4.shared.b16 {%0,%1,%2,%3}, [%4];" : "=r"(r[0]), "=r"(r[1]), "=r"(r[2]), "=r"(r[3]) : "r"(addr) : "memory");
}
__device__ __forceinline__ uint32_t movm(uint32_t a) { uint32_t d; asm volatile("movmatrix.sync.aligned.m8n8.trans.b16 %0, %1;" : "=r"(d) : "r"(a)); return d; }
__device__ __forceinline__ void mma16(float* c, uint32_t a0, uint32_t a1, uint32_t a2, uint32_t a3, uint32_t b0, uint32_t b1) {
  asm volatile("mma.sync.aligned.m16n8k16.row.col.f32.bf16.bf16.f32 {%0,%1,%2,%3}, {%4,%5,%6,%7}, {%8,%9}, {%10,%10,%10,%10};"
               : "=f"(c[0]), "=f"(c[1]), "=f"(c[2]), "=f"(c[3]) : "r"(a0), "r"(a1), "r"(a2), "r"(a3), "r"(b0), "r"(b1), "f"(0.f));
}
__device__ __forceinline__ void mma8(float* c, uint32_t a0, uint32_t a1, uint32_t b0) {
  asm volatile("mma.sync.aligned.m16n8k8.row.col.f32.bf16.bf16.f32 {%0,%1,%2,%3}, {%4,%5}, {%6}, {%0,%1,%2,%3};"
               : "+f"(c[0]), "+f"(c[1]), "+f"(c[2]), "+f"(c[3]) : "r"(a0), "r"(a1), "r"(b0));
}
__device__ __forceinline__ uint32_t pack2(float lo, float hi) { uint32_t r; asm("cvt.rn.bf16x2.f32 %0, %1, %2;" : "=r"(r) : "f"(hi), "f"(lo)); return r; }
__device__ __forceinline__ float blo(uint32_t v) { return __uint_as_float(v << 16); }
__device__ __forceinline__ float bhi(uint32_t v) { return __uint_as_float(v & 0xffff0000u); }
__device__ __forceinline__ float tanh_fast(float x) { float y; asm("tanh.approx.f32 %0, %1;" : "=f"(y) : "f"(x)); return y; }
__device__ __forceinline__ float rcp_fast(float x) { float y; asm("rcp.approx.ftz.f32 %0, %1;" : "=f"(y) : "f"(x)); return y; }
__device__ __forceinline__ float ex2(float x) { float y; asm("ex2.approx.ftz.f32 %0, %1;" : "=f"(y) : "f"(x)); return y; }
__device__ __forceinline__ float qsum(float v) { v += __shfl_xor_sync(~0u, v, 1); v += __shfl_xor_sync(~0u, v, 2); return v; }
__device__ __forceinline__ float qmax(float v) { v = fmaxf(v, __shfl_xor_sync(~0u, v, 1)); v = fmaxf(v, __shfl_xor_sync(~0u, v, 2)); return v; }
__device__ __forceinline__ void stg32(void* p, uint32_t v) { asm volatile("st.global.u32 [%0], %1;" ::"l"(p), "r"(v) : "memory"); }
__device__ __forceinline__ void stg128(void* p, uint32_t a, uint32_t b, uint32_t c, uint32_t d) { asm volatile("st.global.v4.u32 [%0], {%1,%2,%3,%4};" ::"l"(p), "r"(a), "r"(b), "r"(c), "r"(d) : "memory"); }
__device__ __forceinline__ uint32_t ldcg32(const void* p) { uint32_t v; asm volatile("ld.global.L1::no_allocate.u32 %0, [%1];" : "=r"(v) : "l"(p) : "memory"); return v; }
__device__ __forceinline__ uint32_t ldgpu32(const void* p) { uint32_t v; asm volatile("ld.relaxed.gpu.global.u32 %0, [%1];" : "=r"(v) : "l"(p) : "memory"); return v; }
__device__ __forceinline__ void stg128_if(bool c, void* p, uint32_t a, uint32_t b, uint32_t cc, uint32_t d) {
  asm volatile("{\n.reg .pred P;\nsetp.ne.u32 P, %5, 0;\n@P st.global.v4.u32 [%0], {%1,%2,%3,%4};\n}" ::"l"(p), "r"(a), "r"(b), "r"(cc), "r"(d), "r"((uint32_t)c) : "memory");
}
__device__ __forceinline__ uint2 lds64(uint32_t a) { uint2 v; asm volatile("ld.shared.v2.u32 {%0,%1}, [%2];" : "=r"(v.x), "=r"(v.y) : "r"(a) : "memory"); return v; }
__device__ __forceinline__ uint4 ldcg128(const void* p) { uint4 v; asm volatile("ld.global.cg.v4.u32 {%0,%1,%2,%3}, [%4];" : "=r"(v.x), "=r"(v.y), "=r"(v.z), "=r"(v.w) : "l"(p) : "memory"); return v; }
__device__ __forceinline__ uint32_t ldnc16(const void* p) { uint16_t v; asm volatile("ld.global.nc.u16 %0, [%1];" : "=h"(v) : "l"(p)); return v; }
__device__ __forceinline__ uint4 ldnc128(const void* p) { uint4 v; asm volatile("ld.global.nc.v4.u32 {%0,%1,%2,%3}, [%4];" : "=r"(v.x), "=r"(v.y), "=r"(v.z), "=r"(v.w) : "l"(p)); return v; }
__device__ __forceinline__ void cp_async16(uint32_t dst, const void* src) { asm volatile("cp.async.cg.shared.global [%0], [%1], 16;" ::"r"(dst), "l"(src) : "memory"); }
__device__ __forceinline__ uint32_t hsub2(uint32_t a, uint32_t b) { uint32_t d; asm("sub.rn.bf16x2 %0, %1, %2;" : "=r"(d) : "r"(a), "r"(b)); return d; }
__device__ __forceinline__ void stg32_if(bool c, void* p, uint32_t v) {
  asm volatile("{\n.reg .pred P;\nsetp.ne.u32 P, %2, 0;\n@P st.global.u32 [%0], %1;\n}" ::"l"(p), "r"(v), "r"((uint32_t)c) : "memory");
}
__device__ __forceinline__ float wsum(float v) { for (int o = 16; o; o >>= 1) v += __shfl_xor_sync(~0u, v, o); return v; }
__device__ __forceinline__ uint32_t hmul2(uint32_t a, uint32_t b) { uint32_t d; asm("mul.rn.bf16x2 %0, %1, %2;" : "=r"(d) : "r"(a), "r"(b)); return d; }
__device__ __forceinline__ void sts32(uint32_t a, uint32_t v) { asm volatile("st.shared.u32 [%0], %1;" ::"r"(a), "r"(v) : "memory"); }
__device__ __forceinline__ uint32_t lds32(uint32_t a) { uint32_t v; asm volatile("ld.shared.u32 %0, [%1];" : "=r"(v) : "r"(a) : "memory"); return v; }
__device__ __forceinline__ void sts128(uint32_t a, uint32_t x, uint32_t y, uint32_t z, uint32_t w) { asm volatile("st.shared.v4.u32 [%0], {%1,%2,%3,%4};" ::"r"(a), "r"(x), "r"(y), "r"(z), "r"(w) : "memory"); }
__device__ __forceinline__ uint4 lds128(uint32_t a) { uint4 v; asm volatile("ld.shared.v4.u32 {%0,%1,%2,%3}, [%4];" : "=r"(v.x), "=r"(v.y), "=r"(v.z), "=r"(v.w) : "r"(a) : "memory"); return v; }
__device__ __forceinline__ void ll_st64(uint2* p, uint32_t v, uint32_t tag) {
  asm volatile("{\n.reg .b64 r;\nmov.b64 r, {%1,%2};\nst.relaxed.gpu.global.b64 [%0], r;\n}" ::"l"(p), "r"(v), "r"(tag) : "memory");
}
__device__ __forceinline__ uint2 ll_ld64(const uint2* p) {
  uint2 v; asm volatile("{\n.reg .b64 r;\nld.relaxed.gpu.global.b64 r, [%2];\nmov.b64 {%0,%1}, r;\n}" : "=r"(v.x), "=r"(v.y) : "l"(p) : "memory"); return v;
}
__device__ __forceinline__ void ll_st128(uint4* p, float a, float b, uint32_t tag, float c = 0.f) {
  asm volatile("{\n.reg .b128 r;\n.reg .b64 lo, hi;\nmov.b64 lo, {%1,%2};\nmov.b64 hi, {%3,%4};\nmov.b128 r, {lo, hi};\nst.relaxed.gpu.global.b128 [%0], r;\n}" ::"l"(p), "r"(__float_as_uint(a)), "r"(__float_as_uint(b)), "r"(tag), "r"(__float_as_uint(c)) : "memory");
}
__device__ __forceinline__ uint4 ll_ld128(const uint4* p) {
  uint4 v; asm volatile("{\n.reg .b128 r;\n.reg .b64 lo, hi;\nld.relaxed.gpu.global.b128 r, [%4];\nmov.b128 {lo, hi}, r;\nmov.b64 {%0,%1}, lo;\nmov.b64 {%2,%3}, hi;\n}" : "=r"(v.x), "=r"(v.y), "=r"(v.z), "=r"(v.w) : "l"(p) : "memory"); return v;
}
__device__ __forceinline__ void publish_p(uint32_t el, uint32_t* f) {
  asm volatile("{\n.reg .pred P;\nsetp.ne.u32 P, %1, 0;\n@P cp.async.bulk.commit_group;\n@P cp.async.bulk.wait_group 0;\n@P red.release.gpu.global.add.u32 [%0], 1;\n}" ::"l"(f), "r"(el) : "memory");
}
__device__ __forceinline__ void tma3d_red_p(uint32_t el, const CUtensorMap* m, int c0, int c1, int c2, uint32_t src) {
  asm volatile("{\n.reg .pred P;\nsetp.ne.u32 P, %5, 0;\n@P cp.reduce.async.bulk.tensor.3d.global.shared::cta.add.tile.bulk_group [%0, {%2, %3, %4}], [%1];\n@P cp.async.bulk.commit_group;\n}" ::"l"(m), "r"(src), "r"(c0), "r"(c1), "r"(c2), "r"(el) : "memory");
}
__device__ __forceinline__ void stsm4(uint32_t addr, uint32_t a, uint32_t b, uint32_t c, uint32_t d) {
  asm volatile("stmatrix.sync.aligned.m8n8.x4.shared.b16 [%0], {%1,%2,%3,%4};" ::"r"(addr), "r"(a), "r"(b), "r"(c), "r"(d) : "memory");
}
__device__ __forceinline__ void sts64(uint32_t a, uint32_t x, uint32_t y) { asm volatile("st.shared.v2.u32 [%0], {%1,%2};" ::"r"(a), "r"(x), "r"(y) : "memory"); }
__device__ __forceinline__ void ll_st128_if(bool on, uint4* p, float a, float b, uint32_t tag) {
  asm volatile("{\n.reg .pred P;\n.reg .b128 r;\n.reg .b64 lo, hi;\nsetp.ne.u32 P, %4, 0;\nmov.b64 lo, {%1,%2};\nmov.b64 hi, {%3,%3};\nmov.b128 r, {lo, hi};\n@P st.relaxed.gpu.global.b128 [%0], r;\n}" ::"l"(p), "r"(__float_as_uint(a)), "r"(__float_as_uint(b)), "r"(tag), "r"((uint32_t)on) : "memory");
}
__device__ __forceinline__ uint4 ldnc128_if(bool c, const void* p) {
  uint4 v = make_uint4(0u, 0u, 0u, 0u);
  asm volatile("{\n.reg .pred P;\nsetp.ne.u32 P, %5, 0;\n@P ld.global.nc.v4.u32 {%0,%1,%2,%3}, [%4];\n}" : "+r"(v.x), "+r"(v.y), "+r"(v.z), "+r"(v.w) : "l"(p), "r"((uint32_t)c));
  return v;
}
__device__ __forceinline__ uint32_t hfma2(uint32_t a, uint32_t b, uint32_t c) { uint32_t d; asm("fma.rn.bf16x2 %0, %1, %2, %3;" : "=r"(d) : "r"(a), "r"(b), "r"(c)); return d; }
__device__ __forceinline__ float2 lds64f(uint32_t a) { float2 v; asm volatile("ld.shared.v2.f32 {%0,%1}, [%2];" : "=f"(v.x), "=f"(v.y) : "r"(a) : "memory"); return v; }
#define TRC(cond, role, idx) do {} while (0)
#define TRV(role, idx, v) do {} while (0)

#define ACLK_INIT do {} while (0)
#define ACLK(i) do {} while (0)
#define ACLK_OUT do {} while (0)
#define QCLK(i) do {} while (0)
#define PH 1
#define RCLK(i) do {} while (0)
#define RCLK_INIT do {} while (0)
#define RCLK_OUT do {} while (0)
#define SCLK(i) do {} while (0)
#define HCLK(i) do {} while (0)
#define MCLK(c, i) do {} while (0)
#define CKK(i) do {} while (0)
#define CKK_OUT do {} while (0)
#define PL 1
#define PCLK(i) do {} while (0)
#define PQ 1
#define CLK_INIT do {} while (0)
#define CLK(i) do {} while (0)
#define CLK_OUT do {} while (0)

__device__ __forceinline__ void wgmma_ss_n216(float* d, uint64_t da, uint64_t db, int scaleD) {
  asm volatile("{\n.reg .pred p;\nsetp.ne.b32 p, %110, 0;\nwgmma.mma_async.sync.aligned.m64n216k16.f32.bf16.bf16 "
    "{%0,%1,%2,%3,%4,%5,%6,%7,%8,%9,%10,%11,%12,%13,%14,%15,%16,%17,%18,%19,%20,%21,%22,%23,%24,%25,%26,%27,%28,%29,%30,%31,%32,%33,%34,%35,%36,%37,%38,%39,%40,%41,%42,%43,%44,%45,%46,%47,%48,%49,%50,%51,%52,%53,%54,%55,%56,%57,%58,%59,%60,%61,%62,%63,%64,%65,%66,%67,%68,%69,%70,%71,%72,%73,%74,%75,%76,%77,%78,%79,%80,%81,%82,%83,%84,%85,%86,%87,%88,%89,%90,%91,%92,%93,%94,%95,%96,%97,%98,%99,%100,%101,%102,%103,%104,%105,%106,%107}, "
    "%108, %109, p, 1, 1, 0, 1;\n}\n"
    : "+f"(d[0]), "+f"(d[1]), "+f"(d[2]), "+f"(d[3]), "+f"(d[4]), "+f"(d[5]), "+f"(d[6]), "+f"(d[7]), "+f"(d[8]), "+f"(d[9]), "+f"(d[10]), "+f"(d[11]), "+f"(d[12]), "+f"(d[13]), "+f"(d[14]), "+f"(d[15]), "+f"(d[16]), "+f"(d[17]), "+f"(d[18]), "+f"(d[19]), "+f"(d[20]), "+f"(d[21]), "+f"(d[22]), "+f"(d[23]), "+f"(d[24]), "+f"(d[25]), "+f"(d[26]), "+f"(d[27]), "+f"(d[28]), "+f"(d[29]), "+f"(d[30]), "+f"(d[31]), "+f"(d[32]), "+f"(d[33]), "+f"(d[34]), "+f"(d[35]), "+f"(d[36]), "+f"(d[37]), "+f"(d[38]), "+f"(d[39]), "+f"(d[40]), "+f"(d[41]), "+f"(d[42]), "+f"(d[43]), "+f"(d[44]), "+f"(d[45]), "+f"(d[46]), "+f"(d[47]), "+f"(d[48]), "+f"(d[49]), "+f"(d[50]), "+f"(d[51]), "+f"(d[52]), "+f"(d[53]), "+f"(d[54]), "+f"(d[55]), "+f"(d[56]), "+f"(d[57]), "+f"(d[58]), "+f"(d[59]), "+f"(d[60]), "+f"(d[61]), "+f"(d[62]), "+f"(d[63]), "+f"(d[64]), "+f"(d[65]), "+f"(d[66]), "+f"(d[67]), "+f"(d[68]), "+f"(d[69]), "+f"(d[70]), "+f"(d[71]), "+f"(d[72]), "+f"(d[73]), "+f"(d[74]), "+f"(d[75]), "+f"(d[76]), "+f"(d[77]), "+f"(d[78]), "+f"(d[79]), "+f"(d[80]), "+f"(d[81]), "+f"(d[82]), "+f"(d[83]), "+f"(d[84]), "+f"(d[85]), "+f"(d[86]), "+f"(d[87]), "+f"(d[88]), "+f"(d[89]), "+f"(d[90]), "+f"(d[91]), "+f"(d[92]), "+f"(d[93]), "+f"(d[94]), "+f"(d[95]), "+f"(d[96]), "+f"(d[97]), "+f"(d[98]), "+f"(d[99]), "+f"(d[100]), "+f"(d[101]), "+f"(d[102]), "+f"(d[103]), "+f"(d[104]), "+f"(d[105]), "+f"(d[106]), "+f"(d[107])
    : "l"(da), "l"(db), "r"(scaleD));
}
__device__ __forceinline__ void wgmma_ss_n72(float* d, uint64_t da, uint64_t db, int scaleD) {
  asm volatile("{\n.reg .pred p;\nsetp.ne.b32 p, %38, 0;\nwgmma.mma_async.sync.aligned.m64n72k16.f32.bf16.bf16 "
    "{%0,%1,%2,%3,%4,%5,%6,%7,%8,%9,%10,%11,%12,%13,%14,%15,%16,%17,%18,%19,%20,%21,%22,%23,%24,%25,%26,%27,%28,%29,%30,%31,%32,%33,%34,%35}, "
    "%36, %37, p, 1, 1, 0, 1;\n}\n"
    : "+f"(d[0]), "+f"(d[1]), "+f"(d[2]), "+f"(d[3]), "+f"(d[4]), "+f"(d[5]), "+f"(d[6]), "+f"(d[7]), "+f"(d[8]), "+f"(d[9]), "+f"(d[10]), "+f"(d[11]), "+f"(d[12]), "+f"(d[13]), "+f"(d[14]), "+f"(d[15]), "+f"(d[16]), "+f"(d[17]), "+f"(d[18]), "+f"(d[19]), "+f"(d[20]), "+f"(d[21]), "+f"(d[22]), "+f"(d[23]), "+f"(d[24]), "+f"(d[25]), "+f"(d[26]), "+f"(d[27]), "+f"(d[28]), "+f"(d[29]), "+f"(d[30]), "+f"(d[31]), "+f"(d[32]), "+f"(d[33]), "+f"(d[34]), "+f"(d[35])
    : "l"(da), "l"(db), "r"(scaleD));
}
__device__ __forceinline__ void wgmma_rs_n144(float* d, const uint32_t* a, uint64_t db, int scaleD) {
  asm volatile("{\n.reg .pred p;\nsetp.ne.b32 p, %77, 0;\nwgmma.mma_async.sync.aligned.m64n144k16.f32.bf16.bf16 "
    "{%0,%1,%2,%3,%4,%5,%6,%7,%8,%9,%10,%11,%12,%13,%14,%15,%16,%17,%18,%19,%20,%21,%22,%23,%24,%25,%26,%27,%28,%29,%30,%31,%32,%33,%34,%35,%36,%37,%38,%39,%40,%41,%42,%43,%44,%45,%46,%47,%48,%49,%50,%51,%52,%53,%54,%55,%56,%57,%58,%59,%60,%61,%62,%63,%64,%65,%66,%67,%68,%69,%70,%71}, "
    "{%72,%73,%74,%75}, %76, p, 1, 1, 1;\n}\n"
    : "+f"(d[0]), "+f"(d[1]), "+f"(d[2]), "+f"(d[3]), "+f"(d[4]), "+f"(d[5]), "+f"(d[6]), "+f"(d[7]), "+f"(d[8]), "+f"(d[9]), "+f"(d[10]), "+f"(d[11]), "+f"(d[12]), "+f"(d[13]), "+f"(d[14]), "+f"(d[15]), "+f"(d[16]), "+f"(d[17]), "+f"(d[18]), "+f"(d[19]), "+f"(d[20]), "+f"(d[21]), "+f"(d[22]), "+f"(d[23]), "+f"(d[24]), "+f"(d[25]), "+f"(d[26]), "+f"(d[27]), "+f"(d[28]), "+f"(d[29]), "+f"(d[30]), "+f"(d[31]), "+f"(d[32]), "+f"(d[33]), "+f"(d[34]), "+f"(d[35]), "+f"(d[36]), "+f"(d[37]), "+f"(d[38]), "+f"(d[39]), "+f"(d[40]), "+f"(d[41]), "+f"(d[42]), "+f"(d[43]), "+f"(d[44]), "+f"(d[45]), "+f"(d[46]), "+f"(d[47]), "+f"(d[48]), "+f"(d[49]), "+f"(d[50]), "+f"(d[51]), "+f"(d[52]), "+f"(d[53]), "+f"(d[54]), "+f"(d[55]), "+f"(d[56]), "+f"(d[57]), "+f"(d[58]), "+f"(d[59]), "+f"(d[60]), "+f"(d[61]), "+f"(d[62]), "+f"(d[63]), "+f"(d[64]), "+f"(d[65]), "+f"(d[66]), "+f"(d[67]), "+f"(d[68]), "+f"(d[69]), "+f"(d[70]), "+f"(d[71])
    : "r"(a[0]), "r"(a[1]), "r"(a[2]), "r"(a[3]), "l"(db), "r"(scaleD));
}
__device__ __forceinline__ void wgmma_rs_n64(float* d, const uint32_t* a, uint64_t db, int scaleD) {
  asm volatile("{\n.reg .pred p;\nsetp.ne.b32 p, %37, 0;\nwgmma.mma_async.sync.aligned.m64n64k16.f32.bf16.bf16 "
    "{%0,%1,%2,%3,%4,%5,%6,%7,%8,%9,%10,%11,%12,%13,%14,%15,%16,%17,%18,%19,%20,%21,%22,%23,%24,%25,%26,%27,%28,%29,%30,%31}, "
    "{%32,%33,%34,%35}, %36, p, 1, 1, 1;\n}\n"
    : "+f"(d[0]), "+f"(d[1]), "+f"(d[2]), "+f"(d[3]), "+f"(d[4]), "+f"(d[5]), "+f"(d[6]), "+f"(d[7]), "+f"(d[8]), "+f"(d[9]), "+f"(d[10]), "+f"(d[11]), "+f"(d[12]), "+f"(d[13]), "+f"(d[14]), "+f"(d[15]), "+f"(d[16]), "+f"(d[17]), "+f"(d[18]), "+f"(d[19]), "+f"(d[20]), "+f"(d[21]), "+f"(d[22]), "+f"(d[23]), "+f"(d[24]), "+f"(d[25]), "+f"(d[26]), "+f"(d[27]), "+f"(d[28]), "+f"(d[29]), "+f"(d[30]), "+f"(d[31])
    : "r"(a[0]), "r"(a[1]), "r"(a[2]), "r"(a[3]), "l"(db), "r"(scaleD));
}

template <int V> struct Int { static constexpr int value = V; };
struct Cur {
  uint32_t s, ph;
  __device__ __forceinline__ void next() { if (++s == NST) { s = 0; ph ^= 1; } }
};

__device__ __forceinline__ uint8_t* z1_block(int rb, int w, int j) { return g_Z + (rb * 16 + w * 8 + j) * ZB; }
__device__ __forceinline__ uint8_t* o_block(int rb, int w) { return g_O + (rb * 2 + w) * (2 * ZB); }
__device__ __forceinline__ uint8_t* z2_block(int kb, int j) { return g_Z + (256 + kb * 8 + j) * ZB; }
__device__ __forceinline__ void combine8(float m0, float q0, float m1, float q1, float n, float eps, float& mean, float& rstd) {
  mean = qsum(m0 + m1) * 0.125f;
  float d0 = m0 - mean, d1 = m1 - mean;
  float M2 = qsum(q0 + q1 + n * (d0 * d0 + d1 * d1));
  rstd = rsqrtf(fmaf(M2, 0.125f / n, eps));
}
__device__ __forceinline__ void stat_get(const uint4* zs, uint32_t tag, float n, float eps, float& m0, float& r0, float& m1, float& r1) {
  uint4 a0, a1, b0, b1;
#pragma unroll 1
  for (int it = 0; it < (1 << 20); it++) {
    a0 = ll_ld128(zs); a1 = ll_ld128(zs + 64); b0 = ll_ld128(zs + 8); b1 = ll_ld128(zs + 72);
    if (__all_sync(~0u, a0.z == tag && a1.z == tag && b0.z == tag && b1.z == tag)) break;
  }
  combine8(__uint_as_float(a0.x), __uint_as_float(a0.y), __uint_as_float(a1.x), __uint_as_float(a1.y), n, eps, m0, r0);
  combine8(__uint_as_float(b0.x), __uint_as_float(b0.y), __uint_as_float(b1.x), __uint_as_float(b1.y), n, eps, m1, r1);
}

__device__ __forceinline__ void rows_fetch(uint32_t el, uint32_t xr, const uint8_t* src, uint32_t bar) {
  expect_tx_p(el, bar, 9216);
#pragma unroll 1
  for (int r = 0; r < 8; r++) bulk_load_p(el, xr + r * 1152, src + r * (DM * 4), 1152, bar);
}
__device__ __forceinline__ void rows_stats(uint32_t xr, uint4* dst, uint32_t tag, int lane) {
  float s[2] = {0.f, 0.f}, q[4] = {0.f, 0.f, 0.f, 0.f};
  const uint32_t a0 = xr + (lane >> 2) * 1152 + (((lane & 3) * 2) ^ (lane >> 2)) * 16;
  uint4 n0 = lds128(a0), n1 = lds128(a0 ^ 16);
#pragma unroll 1
  for (int e = 1; e <= 9; e++) {
    const uint32_t x[8] = {n0.x, n0.y, n0.z, n0.w, n1.x, n1.y, n1.z, n1.w};
    if (e < 9) { n0 = lds128(a0 + e * 128); n1 = lds128((a0 ^ 16) + e * 128); }
#pragma unroll
    for (int u = 0; u < 8; u++) {
      const float lo = blo(x[u]), hi = bhi(x[u]);
      s[u & 1] += lo + hi; q[(u & 1) * 2] = fmaf(lo, lo, q[(u & 1) * 2]); q[(u & 1) * 2 + 1] = fmaf(hi, hi, q[(u & 1) * 2 + 1]);
    }
  }
  const float sx = s[0] + s[1], sq = (q[0] + q[1]) + (q[2] + q[3]);
  const float m = qsum(sx) * (-1.f / DM), r = rsqrtf(fmaxf(fmaf(qsum(sq), 1.f / DM, -m * m), 0.f) + LN_EPS);
  if ((lane & 3) == 0) ll_st128(dst + (lane >> 2) * 2, m, r, tag);
}

__device__ __forceinline__ void poison(uint32_t el, uint32_t src, const CUtensorMap* m, int rb, int j, int lane) {
#pragma unroll 1
  for (int u = lane; u < 72; u += 32) sts128(src + u * 16, POISON, POISON, POISON, POISON);
  fence_async_s();
  __syncwarp();
#pragma unroll 1
  for (int u = 0; u < 16; u++) {
    __nanosleep(NAP);
    bulk_store_p(el, o_block(rb, u >> 3) + j * 9216 + (u & 7) * 1152, src, 1152);
    asm volatile("{\n.reg .pred P;\nsetp.ne.u32 P, %5, 0;\n@P cp.async.bulk.tensor.3d.global.shared::cta.tile.bulk_group [%0, {%2, %3, %4}], [%1];\n}" ::"l"(m), "r"(src), "r"((j & 6) * 72), "r"(rb * 64 + u * 4), "r"(j & 1), "r"(el) : "memory");
  }
}
__device__ __forceinline__ void mma16acc(float* c, const uint32_t* a, uint32_t b0, uint32_t b1) {
  asm volatile("mma.sync.aligned.m16n8k16.row.col.f32.bf16.bf16.f32 {%0,%1,%2,%3}, {%4,%5,%6,%7}, {%8,%9}, {%0,%1,%2,%3};"
               : "+f"(c[0]), "+f"(c[1]), "+f"(c[2]), "+f"(c[3]) : "r"(a[0]), "r"(a[1]), "r"(a[2]), "r"(a[3]), "r"(b0), "r"(b1));
}
template <int NG, int AK, int AH, int BK, int BG, class F> __device__ __forceinline__ void redo(float* acc, const uint8_t* pa, const uint8_t* pb, F f) {
#pragma unroll 1
  for (int k = 0; k < 12; k++) {
    uint32_t a[12], b[6][NG];
#pragma unroll 1
    for (int it = 0; it < (1 << 20); it++) {
      bool ok = true;
#pragma unroll
      for (int e = 0; e < 12; e++) a[e] = ldgpu32(pa + (e >> 1) * AK + (e & 1) * AH);
#pragma unroll
      for (int e = 0; e < 6 * NG; e++) b[e / NG][e % NG] = ldgpu32(pb + (e / NG) * BK + (e % NG) * BG);
#pragma unroll
      for (int e = 0; e < 12; e++) ok = ok && a[e] != POISON;
      if (__all_sync(~0u, ok)) break;
    }
#pragma unroll
    for (int e = 0; e < 12; e++) a[e] = f(a[e], e & 1);
#pragma unroll
    for (int e = 0; e < 3 * NG; e++) mma16acc(acc + 4 * (e % NG), a + 4 * (e / NG), movm(b[2 * (e / NG)][e % NG]), movm(b[2 * (e / NG) + 1][e % NG]));
    pa += 6 * AK; pb += 6 * BK;
  }
}
__device__ __forceinline__ bool any_nan(float a, float b) {
  return __any_sync(~0u, a != a || b != b);
}

__global__ void __cluster_dims__(2, 1, 1) __launch_bounds__(384, 1) mega_kernel(const __grid_constant__ Params P) {
  extern __shared__ __align__(1024) uint8_t smem_raw[];
  uint32_t ckk[8];
  (void)ckk;
  CKK(0);
  const uint32_t sb = smem_u32(smem_raw);
  const uint32_t bars = sb + SM_BAR;
  const int tid = threadIdx.x;
  int lane = tid & 31;
  const int wid = __shfl_sync(~0u, tid >> 5, 0);
  const int cl = blockIdx.x >> 1, tp = cl - 36, t7 = (tp * 37) >> 8;
  const int bid = (cl < 4 ? cl * 8 + 32 : tp < 0 ? cl - 4 : cl < 64 ? tp + t7 + 33 : cl) * 2 + (blockIdx.x & 1);
  if (bid >= NCTA) return;
  const int rb = bid & 15, j = bid >> 4;
  { const bool tr = (tid & 127) == 0 && tid < 256; const int w = tid >> 7; (void)tr; (void)w; TRC(tr, w, 0); }
  CKK(1);
  uint4 wv[5];
  const uint8_t* wsrc;
  {
    const int n8 = min(tid >> 3, 26), part = n8 / 9;
    const uint8_t* src = (const uint8_t*)P.wqkv + (8 * rb + (tid & 7)) * (3 * DM * 2) + (part * (DM - 72) + 72 * j + 8 * n8) * 2;
#pragma unroll
    for (int u = 0; u < SPL; u++) wv[u] = ldnc128_if(tid < 216, src + u * (128 * 3 * DM * 2));
    wsrc = src;
  }
  CKK(2);
  if (tid == 352) {
    for (int s = 0; s < (int)NST; s++) {
      mbar_init(bars + B_FULL + s * 8, 1); mbar_init(bars + B_EMPTY + s * 8, 16);
      mbar_init(bars + B_FULLA + s * 8, 1); mbar_init(bars + B_FULLA + 32 + s * 8, 1);
      mbar_init(bars + B_RES + s * 8, 1); mbar_init(bars + B_RT + s * 8, 1); mbar_init(bars + B_AD + s * 8, 2);
    }
    mbar_init(bars + B_IMG, 8); mbar_init(bars + B_RES + 8, 8); mbar_init(bars + B_WOI, 8); mbar_init(bars + B_GATE3, 3); mbar_init(bars + B_Z1, 1); mbar_init(bars + B_ZB, 1); mbar_init(bars + B_LAG, 4);
    mbar_init(bars + B_CSQ, 3); mbar_init(bars + B_RT1, 1); mbar_init(bars + B_XRW, 1); mbar_init(bars + B_XRW + 8, 1);
    for (int e = 0; e < 2 * EV_N; e++) mbar_init(bars + B_EVT + e * 8, 4);
    asm volatile("fence.mbarrier_init.release.cluster;" ::: "memory");
  }
  if (tid == 320) {
#pragma unroll
    for (int e = 0; e < 28; e++) mbar_init(bars + B_FA3 + e * 8, e < 18 ? 1 : 4);
    asm volatile("fence.mbarrier_init.release.cluster;" ::: "memory");
  }
  __syncthreads();

  if (wid >= 8) {
    reg_dealloc<40>();
    const uint32_t el = elect_one();
    const uint64_t pol = policy_evict_first();
    uint32_t* const fj = g_flags + FJ + j * 32;
    if (wid == 8) {
      if (el) { prefetch_map(&P.act[0]); prefetch_map(&P.wsp); prefetch_map(&P.win); prefetch_map(&P.win64); prefetch_map(&P.wout); prefetch_map(&P.act[1]); prefetch_map(&P.res[0]); prefetch_map(&P.res[1]); prefetch_map(&P.red[0]); prefetch_map(&P.red[1]); prefetch_map(&P.act[2]); }
      const uint32_t epoch = ldcg32(fj + FJ_EP + rb);
      Cur c{0, 1};
      const uint32_t rk = bid & 1;
      uint32_t st, full;
      auto slot = [&](uint32_t bytes) {
        st = sb + c.s * ST_BYTES; full = bars + B_FULL + c.s * 8;
        mbar_wait(full, c.ph);
        expect_tx_p(el, full, bytes);
        mbar_wait(full - B_FULL + B_EMPTY, c.ph);
      };
#pragma unroll 1
      for (int L = 0; L < 2; L++) {
#pragma unroll 1
        for (int i = 0; i < 14; i++) {
          if (L == 0 && (i == 0 || i == 2 * SPL || i == 9)) {
            flag_wait(fj + (i == 9 ? FJ_WO : i == 2 * SPL ? FJ_WQ : FJ_WQ0), (epoch + 1) * 16);
            if (i == 9) flag_wait(g_flags + FJ + (j ^ 1) * 32 + FJ_WO, (epoch + 1) * 16);
            fence_async_g();
            TRC(el, 2, i == 9 ? 46 : i ? 47 : 45);
          }
          const uint32_t hb = i < 9 ? 13824 : i < 13 ? 18432 : 9216, o = ST_B + rk * (i < 9 ? 13824 : 18432);
          const uint8_t* src = i < 9 ? g_WQ + j * WQ_SL + i * 27648 + rk * 13824 : g_WO + ((j & 6) + rk) * WO_SL + (i - 9) * 18432;
          slot(2 * hb);
          bulk_mc_h(el, st + o, src, hb, full, true, pol);
          c.next();
        }
#pragma unroll 1
        for (int i = 0; i < 18; i++) {
          const int p = i >> 1, col = p == 4 ? (9 * j + ((j & 1) ? 0 : 8)) * 32 : (((9 * j + 1) >> 1) + (p < 4 ? p + 36 : p - 5)) * 64;
          if (i & 1) {
            slot(2 * ZB);
          } else {
            st = sb + c.s * ST_BYTES; full = bars + B_FULL + ((c.s + 1) & 3) * 8;
            mbar_wait(bars + B_EMPTY + c.s * 8, c.ph);
          }
          tma4d_mc(el, st + ST_B + rk * 18432, p == 4 ? &P.win : &P.win64, col, (i & 1) * 36 + rk * 18, full, pol);
          if (el && !(i & 1)) mbar_arrive(bars + B_FULL + c.s * 8);
          c.next();
        }
        TRC(el, 2, L * 16 + 6);
        flag_wait(fj + FJ_ZN + L, (epoch + 1) * 16);
        fence_async_g();
        TRC(el, 2, L * 16 + 7);
#pragma unroll 1
        for (int i = 0; i < 32; i++) {
          const uint8_t* src = z2_block(i, j) + rk * 18432;
          if (i >= 4) mbar_wait(bars + B_AD + c.s * 8, ((i >> 2) & 1) ^ 1);
          slot(ST_BYTES);
          bulk_mc_h(el, st + ST_B + rk * 18432, src, 18432, full, true, pol);
          tma3d_h(el, st, &P.wsp, i * 64, rb * 64, 0, full, true, pol);
          c.next();
        }
        mbar_wait(bars + B_Z1, L);
        fence_async_g();
        expect_tx_p(el, bars + B_ZB, 20480);
        bulk_load_h(el, sb + SM_STG, z1_block(rb, 1, j) + 16384, 4096, bars + B_ZB, true, pol);
#pragma unroll 1
        for (int i = 0; i < 10; i++) {
          const int cb = i - 1 + j;
          if (i < 4) mbar_wait(bars + B_AD + c.s * 8, 1);
          slot(i == 1 ? ST_BYTES : ZB);
          if (i < 2) bulk_load_h(el, st, z1_block(rb, i, j) + i * 20480, ZB - i * 20480, full, true, pol);
          if (i == 0) bulk_load_h(el, st + ZB, z1_block(rb, 1, j), 16384, bars + B_ZB, true, pol);
          else tma2d_mc_h(el, st + ST_B + rk * 18432, &P.wout, (cb >= 9 ? cb - 9 : cb) * 64, 288 * j + rk * 144, full, true, pol);
          c.next();
        }
      }
    } else if (wid < 11) {
      int w = wid - 9;
      uint32_t* const fr = g_flags + (rb * 2 + w) * 32;
      const uint32_t epoch = ldcg32(fr + FR_EP + j);
      const uint32_t ev = bars + B_EVT + w * EV_N * 8, t8 = (epoch + 1) * 8;
      const int dp = ((j & 1) - w) * 32;
      Cur c{0, 1};
#pragma unroll 1
      for (int L = 0; L < 2; L++) {
#pragma unroll 1
        for (int ph = 0; ph < 3; ph++) {
          if (ph + L > 0) {
            uint32_t* f = fr + (ph == 0 ? FR_X2 : ph == 1 ? FR_O + L : FR_X1 + L);
            mbar_wait(ev + ph * 8, ph ? L : 0);
            TRC(el, 3, w * 32 + L * 16 + ph * 3);
            if (ph && L) flag_add_p(el, ph == 2 ? f + dp : f); else flag_release_p(el, ph == 2 ? f + dp : f);
            if (el && ph == 2) mbar_arrive(bars + B_GATE3);
            TRC(el, 3, w * 32 + L * 16 + ph * 3 + 1);
            if (ph == 1 && w == 1) {
              mbar_wait(ev - (EV_N - EV_O) * 8, L);
              expect_tx_p(el, bars + B_RES, 18432);
              tma3d_h(el, sb + SM_STG, &P.res[L], (j & 6) * 72, rb * 64, j & 1, bars + B_RES, !L, pol);
            }
            if (ph == 2) {
              if (lane < 2) mbar_arrive(bars + B_FULLA + w * 32 + ((c.s + lane) & 3) * 8);
              expect_tx_p(lane < 9, bars + B_FA3 + (9 * w + lane) * 8, 8192);
              flag_wait(f, t8);
              fence_async_g();
#pragma unroll 1
              for (int kb = 0; kb < 9; kb++) {
                const int n = 9 * w + kb;
                if (n >= 8) mbar_wait(bars + B_EA3 + (n - 8) * 8, L);
                tma3d_h(el, sb + ((n >> 1) & 3) * ST_BYTES + (n & 1) * 8192, &P.act[L + 1], kb * 64, rb * 64, w, bars + B_FA3 + (9 * w + kb) * 8, false, pol);
                TRC(el && kb == 0, 3, w * 32 + L * 16 + ph * 3 + 2);
              }
              c.ph ^= ((c.s + 18) >> 2) & 1; c.s = (c.s + 18) & 3;
              break;
            }
            const uint32_t full = bars + B_FULLA + w * 32 + c.s * 8, dst = sb + c.s * ST_BYTES + w * 8192;
            mbar_wait(bars + B_EMPTY + c.s * 8, c.ph);
            expect_tx_p(el, full, 8192);
            flag_wait(ph == 1 ? f + dp : f, t8);
            fence_async_g();
            if (ph != 1) tma3d_h(el, dst, &P.act[1], 0, rb * 64, w, full, false, pol);
            else bulk_load_h(el, dst, o_block(rb, j & 1) + w * 8192, 8192, full, true, pol);
            c.next();
            TRC(el, 3, w * 32 + L * 16 + ph * 3 + 2);
          }
          const int n = ph == 0 ? 9 : 5;
          const uint32_t tag = epoch * 2 + L + 1;
          uint4* const xs = g_XST + (rb * 2 + w) * 128;
#pragma unroll 1
          for (int i = ph + L > 0; i < n; i++) {
            const uint32_t full = bars + B_FULLA + w * 32 + c.s * 8, dst = sb + c.s * ST_BYTES + w * 8192;
            if (ph + L == 0 && i == 4) {
              mbar_wait(bars + B_WT + w * 8, 0);
              TRC(el && w == 0, 2, 37);
              rows_stats(sb + SM_STG + w * 9216, xs + 16 * j, tag, lane);
              TRC(el && w == 0, 2, 38);
            }
            const bool none = ph == 1 && 2 * i + w > 8;
            mbar_wait(bars + B_EMPTY + c.s * 8, c.ph);
            expect_tx_p(el, full, none ? 0 : 8192);
            if (ph != 1) {
              tma3d_h(el, dst, &P.act[L], i * 64, rb * 64, w, full, false, pol);
            } else {
              if (!none) bulk_load_h(el, dst, o_block(rb, j & 1) + (2 * i + w) * 8192, 8192, full, true, pol);
            }
            c.next();
            if (ph + L == 0 && i == 3) rows_fetch(el, sb + SM_STG + w * 9216, P.xs[0] + (128 * rb + 16 * j + w) * (DM * 2), bars + B_WT + w * 8);
          }
          if (ph + L == 2) flag_wait(fj + FJ_P4, t8 * 4);
          if (ph == 0) {
            const uint32_t tab = sb + L * (2 * ST_BYTES) + SM_XST + w * 512 + lane * 8;
            TRC(el, 3, w * 32 + L * 16 + 13);
#pragma unroll 1
            for (int it = 0; it < (1 << 22); it++) {
              const uint4 a = ll_ld128(xs + 2 * lane), b = ll_ld128(xs + 64 + 2 * lane);
              if (__all_sync(~0u, a.z == tag && b.z == tag)) { sts64(tab, a.x, a.y); sts64(tab + 256, b.x, b.y); break; }
            }
            __syncwarp();
            if (el) mbar_arrive(bars + B_CSQ);
            TRC(el, 3, w * 32 + L * 16 + 14);
          }
        }
        asm volatile("" : "+r"(lane), "+r"(w));
        expect_tx_p(el, bars + B_WT + w * 8, 2048);
#pragma unroll 1
        for (int r = 0; r < 8; r++)
          bulk_load_p(el, sb + SM_WT + w * 2176 + r * 272, (const uint8_t*)P.w_sp + (size_t)(128 * rb + 16 * j + 2 * r + w) * (SEQ * 2) + 30 * 128, 256, bars + B_WT + w * 8);
        float cv = (lane & 3) ? 0.f : -blo(ldnc16(P.b_sp + 128 * rb + 16 * j + 2 * (lane >> 2) + w));
        mbar_wait(bars + B_RT, L);
        mbar_wait(bars + B_WT + w * 8, L ^ 1);
        mbar_wait(ev + EV_Z1 * 8, L);
        const uint32_t ro = (w * 64 + 8 * j + (lane >> 2)) * 128, x0 = ((lane & 3) * 2) ^ (lane >> 2);
#pragma unroll 1
        for (int i = 0; i < 32; i++) {
          const bool tail = (i >> 1) == 4;
          const int kb = tail ? i + 22 : i < 8 ? i : i - 2;
          if (i == 8) mbar_wait(bars + B_RT1, L);
          if (!tail) mbar_wait(bars + B_FULL + c.s * 8, c.ph ^ 1);
#pragma unroll
          for (int e = 0; e < 2; e++) {
            const uint4 a = lds128(!tail ? sb + c.s * ST_BYTES + ro + ((x0 ^ e) << 4) : sb + SM_WT + w * 2176 + (lane >> 2) * 272 + (i - 8) * 128 + (lane & 3) * 32 + e * 16);
            const uint4 m = lds128(sb + SM_RT + 4096 + kb * 128 + (lane & 3) * 32 + e * 16);
            cv = fmaf(blo(a.x), blo(m.x), fmaf(bhi(a.x), bhi(m.x), fmaf(blo(a.y), blo(m.y), fmaf(bhi(a.y), bhi(m.y), cv))));
            cv = fmaf(blo(a.z), blo(m.z), fmaf(bhi(a.z), bhi(m.z), fmaf(blo(a.w), blo(m.w), fmaf(bhi(a.w), bhi(m.w), cv))));
          }
          if (!tail) {
            mbar_arrive_if(el, bars + B_AD + c.s * 8 + (__float_as_uint(cv) & P.zero));
            c.next();
          }
        }
        TRC(el, 3, w * 32 + L * 16 + 11);
        uint32_t tag = t8;
        asm volatile("" : "+r"(tag));
        tag = (tag >> 2) - 1 + L;
        cv = qsum(cv);
        uint2* const cs = (uint2*)(g_XST + (rb * 2 + w) * 128 + 1);
        if ((lane & 3) == 0) ll_st64(cs + 32 * j + (lane >> 2) * 4, __float_as_uint(cv), tag);
#pragma unroll 1
        for (int it = 0; it < (1 << 22); it++) {
          const uint2 a = ll_ld64(cs + 4 * lane), b = ll_ld64(cs + 128 + 4 * lane);
          if (__all_sync(~0u, a.y == tag && b.y == tag)) { sts32(sb + SM_CV + w * 256 + lane * 4, a.x); sts32(sb + SM_CV + w * 256 + 128 + lane * 4, b.x); break; }
        }
        __syncwarp();
        if (el) mbar_arrive(bars + B_CV + w * 8);
        TRC(el, 3, w * 32 + L * 16 + 12);
#pragma unroll 1
        for (int kb = 30; kb < 32; kb++) {
          mbar_wait(bars + B_FULL + c.s * 8, c.ph ^ 1);
          if (el) mbar_arrive(bars + B_AD + c.s * 8);
          c.next();
        }
        c.ph ^= ((c.s + 10) >> 2) & 1; c.s = (c.s + 10) & 3;
        if (L == 0) {
          mbar_wait(ev + EV_P4 * 8, 0);
          flag_add_p(el, fj + FJ_P4);
        }
      }
    } else {
      const uint32_t epoch = ldcg32(fj + FJ_EP + rb);
      if (SPL) {
        mbar_wait(bars + B_RES + 8, 0);
        TRC(el, 2, 41);
        flag_release_p(el, fj + FJ_WQ0);
        TRC(el, 2, 42);
      }
      mbar_wait(bars + B_IMG, 0);
      TRC(el, 2, 39);
      flag_release_p(el, fj + FJ_WQ);
      TRC(el, 2, 40);
#pragma unroll 1
      for (int L = 0; L < 2; L++) {
        float* const csf = g_CSP + (NCTA + bid) * 216;
        if (L == 0) {
          flag_wait(fj + FJ_WQ, (epoch + 1) * 16);
          fence_async_g();
          expect_tx_p(el, bars + B_XRW, 13824);
          bulk_load_p(el, sb + ST_BYTES + SM_WOI, g_CSP + j * 16 * 216, 6912, bars + B_XRW);
          bulk_load_p(el, sb + 2 * ST_BYTES + SM_WOI, g_CSP + (j * 16 + 8) * 216, 6912, bars + B_XRW);
          mbar_wait(bars + B_XRW, 0);
#pragma unroll 1
          for (int f = lane; f < 54; f += 32) {
            float s[4] = {0.f, 0.f, 0.f, 0.f};
#pragma unroll 4
            for (int r = 0; r < 16; r++) {
              const uint4 v = lds128(sb + ST_BYTES + SM_WOI + (r >> 3) * ST_BYTES + (r & 7) * 864 + f * 16);
              s[0] += __uint_as_float(v.x); s[1] += __uint_as_float(v.y); s[2] += __uint_as_float(v.z); s[3] += __uint_as_float(v.w);
            }
            sts128(sb + SM_CSQ + f * 16, __float_as_uint(s[0]), __float_as_uint(s[1]), __float_as_uint(s[2]), __float_as_uint(s[3]));
            stg128(csf + f * 4, __float_as_uint(s[0]), __float_as_uint(s[1]), __float_as_uint(s[2]), __float_as_uint(s[3]));
          }
          __syncwarp();
          mbar_arrive_if(el, bars + B_CSQ);
        } else {
#pragma unroll 1
          for (int u = 0; u < 4; u++) {
            const int w = u & 1;
            if (u < 2) {
              flag_wait(g_flags + (rb * 2 + w) * 32 + FR_X2, (epoch + 1) * 8);
              fence_async_g();
              TRC(el, 2, 48 + u);
              rows_fetch(el, sb + SM_STG + w * 9216, P.xs[1] + (128 * rb + 16 * j + w) * (DM * 2), bars + B_XRW + w * 8);
            } else {
              mbar_wait(bars + B_XRW + w * 8, w ^ 1);
              TRC(el, 2, 48 + u);
              rows_stats(sb + SM_STG + w * 9216, g_XST + (rb * 2 + w) * 128 + 16 * j, epoch * 2 + 2, lane);
              TRC(el, 2, 50 + u);
            }
          }
          expect_tx_p(el, bars + B_CSQ, 864);
          bulk_load_p(el, sb + 2 * ST_BYTES + SM_CSQ, csf, 864, bars + B_CSQ);
        }
        if (L == 0) {
          TRC(el, 2, 43);
          mbar_wait(bars + B_WOI, 0);
          bulk_store_p(el, g_WO + j * WO_SL + rb * (41 * 128), sb + SM_WOI, (rb < 15 ? 41 : 33) * 128);
          publish_p(el, fj + FJ_WO);
          TRC(el, 2, 44);
          if (el) prefetch_l2((const uint8_t*)P.w_in + bid * 41472, 41472);
          uint4 y[4];
#pragma unroll
          for (int u = 0; u < 4; u++) y[u] = ldnc128((u < 2 ? (const uint8_t*)P.w_in + (100 + 300 * u) * (2 * FH * 2) + (FH + 1024 * u) * 2 : (const uint8_t*)P.w_sp + (1000 * u - 1500) * (SEQ * 2) + u * 1024) + lane * 16);
          float sq[2] = {0.f, 0.f};
#pragma unroll
          for (int u = 0; u < 4; u++) {
            const uint32_t x[4] = {y[u].x, y[u].y, y[u].z, y[u].w};
#pragma unroll
            for (int e = 0; e < 4; e++) sq[u >> 1] = fmaf(blo(x[e]), blo(x[e]), fmaf(bhi(x[e]), bhi(x[e]), sq[u >> 1]));
          }
          const float o0 = sqrtf(wsum(sq[0]) * (2.f * GA * GA * DM / 512.f)), o1 = sqrtf(wsum(sq[1]) * (C0S * C0S * SEQ / 512.f));
          const uint32_t off = (__float_as_uint(o0) & 0x7f800000u) >> 16 | 0x8000u | OFM;
          if (el) sts64(sb + SM_OFF, off * 0x10001u, min(__float_as_uint(o1) & 0x7f800000u, 0x7e000000u) | 0x00400000u);
        }
        if (el) mbar_arrive(bars + B_GATE3);
        const uint32_t tag = epoch * 2 + L + 1;
        asm volatile("" : "+r"(lane));
        mbar_wait(bars + B_EVT + EV_ZN * 8, L);
        mbar_wait(bars + B_EVT + (EV_N + EV_ZN) * 8, L);
        flag_release_p(el, fj + FJ_ZN + L);
        TRC(el, 2, L * 16 + 8);
        {
          uint4 v[4];
#pragma unroll 1
          for (int it = 0; it < (1 << 22); it++) {
            bool ok = true;
#pragma unroll
            for (int u = 0; u < 4; u++) { v[u] = ll_ld128(g_ZST + (rb * 2 + ((lane >> 1) & 1)) * 512 + ((lane & 1) * 4 + u) * 64 + 8 * j + (lane >> 2)); ok = ok && v[u].z == tag; }
            if (__all_sync(~0u, ok)) break;
          }
          float mean = __uint_as_float(v[0].x) + __uint_as_float(v[1].x) + __uint_as_float(v[2].x) + __uint_as_float(v[3].x), M2 = 0.f;
          mean = (mean + __shfl_xor_sync(~0u, mean, 1)) * 0.125f;
#pragma unroll
          for (int u = 0; u < 4; u++) { const float d = __uint_as_float(v[u].x) - mean; M2 += fmaf(288.f * d, d, __uint_as_float(v[u].y)); }
          M2 += __shfl_xor_sync(~0u, M2, 1);
          const float rs = blo(pack2(rsqrtf(fmaf(M2, 1.f / FH, 4.f * GA * GA * LN_EPS)), 0.f));
          if (!(lane & 1)) ll_st64(g_RT + 128 * rb + 16 * j + (lane >> 1), pack2(rs, rs * mean), tag);
        }
        TRC(el, 2, L * 16 + 10);
#pragma unroll 1
        for (int b = 0; b < 8; b++) {
          uint4 v[4];
#pragma unroll 1
          for (int it = 0; it < (1 << 22); it++) {
            bool ok = true;
#pragma unroll
            for (int u = 0; u < 4; u++) { v[u] = ll_ld128((const uint4*)g_RT + b * 128 + u * 32 + lane); ok = ok && v[u].y == tag && v[u].w == tag; }
            if (__all_sync(~0u, ok)) break;
          }
#pragma unroll
          for (int u = 0; u < 4; u++) {
            const uint32_t rt = sb + SM_RT + b * 512 + u * 128, ro = (lane >> 3) * 32 + (lane & 3) * 8 + ((lane >> 2) & 1) * 2;
            sts32(rt + 4096 + lane * 4, __byte_perm(v[u].x, v[u].z, 0x7632));
            asm volatile("st.shared.u16 [%0], %1;\nst.shared.u16 [%0 + 4], %2;" ::"r"(rt + ro), "h"((uint16_t)v[u].x), "h"((uint16_t)v[u].z) : "memory");
          }
          __syncwarp();
          if (el && (b == 1 || b == 7)) mbar_arrive(bars + (b == 1 ? B_RT : B_RT1));
          TRC(el && b < 2, 2, L * 16 + 11 + b);
        }
        TRC(el, 2, L * 16 + 9);
        mbar_wait(bars + B_EVT + EV_Z1 * 8, L);
        mbar_wait(bars + B_EVT + (EV_N + EV_Z1) * 8, L);
        fence_gpu();
        if (el) mbar_arrive(bars + B_Z1);
        if (L == 0) {
          __nanosleep(NAP0);
          poison(el, sb + SM_STG + 17152, &P.psn, rb, j, lane);
          if (el) asm volatile("cp.async.bulk.commit_group;\ncp.async.bulk.wait_group 0;" ::: "memory");
          __syncwarp();
          fence_gpu();
        }
      }
    }
  } else {
    CKK(3);
    uint8_t* const wdst = P.wq + j * WQ_SL + rb * 3456 + tid * 16;
#pragma unroll
    for (int u = 0; u < SPL; u++) stg128_if(tid < 216, wdst + u * (16 * 3456), wv[u].x, wv[u].y, wv[u].z, wv[u].w);
    __syncwarp();
    if (lane == 0) mbar_arrive(bars + B_RES + 8);
    CKK(4);
    auto repack2 = [&]() {
#pragma unroll
      for (int u = SPL; u < 5; u++) stg128_if((u < 4 || rb < 8) && tid < 216, wdst + u * (16 * 3456), wv[u].x, wv[u].y, wv[u].z, wv[u].w);
      float s[8];
#pragma unroll
      for (int e = 0; e < 8; e++) s[e] = 0.f;
#pragma unroll
      for (int u = 0; u < 5; u++) {
        uint32_t x[4] = {wv[u].x, wv[u].y, wv[u].z, wv[u].w};
        asm volatile("" : "+r"(x[0]), "+r"(x[1]), "+r"(x[2]), "+r"(x[3]));
#pragma unroll
        for (int e = 0; e < 4; e++) { s[2 * e] += blo(x[e]); s[2 * e + 1] += bhi(x[e]); }
      }
#pragma unroll
      for (int m = 4; m; m >>= 1) {
#pragma unroll
        for (int e = 0; e < m; e++) s[e] = ((tid & m) ? s[e + m] : s[e]) + __shfl_xor_sync(~0u, (tid & m) ? s[e] : s[e + m], m);
      }
      stg32_if(tid < 216, P.csp + bid * 216 + tid, __float_as_uint(s[0]));
      __syncwarp();
      if (lane == 0) mbar_arrive(bars + B_IMG);
    };
    reg_alloc<232>();
    CKK(5);
#pragma unroll
    for (int v = SPL; v < 5; v++) wv[v] = ldnc128_if(tid < 216 && (v < 4 || rb < 8), wsrc + v * (128 * 3 * DM * 2));
    repack2();
    CKK(6);
    const int w = wid >> 2, q = wid & 3;
    int g = lane >> 2, t = lane & 3;
    const uint32_t ev = bars + B_EVT + w * EV_N * 8;
    const bool tr = (tid & 127) == 0;
    (void)tr;
    Cur c{0, 0};
    const uint32_t ebar = mapa(bars + B_EMPTY, (bid & 1) ^ (lane & 1));
    auto release = [&](uint32_t s, uint32_t dep = 0) { mbar_arrive_cluster_if(lane < 2, ebar + s * 8 + dep); };
    auto release_if = [&](bool on, uint32_t s) { mbar_arrive_cluster_if(lane < 2 && on, ebar + s * 8); };
    const uint32_t stg = sb + SM_STG + w * 9216;
    uint32_t ia = 0;
    auto wait_ab = [&]() { mbar_wait_c(bars + B_FULL + c.s * 8, c.ph); mbar_wait_c(bars + B_FULLA + w * 32 + c.s * 8, (ia >> 2) & 1); ia++; };
    uint32_t lagph = 0;
    auto yield = [&](int left, int lag) { if (w == 1 && left == lag) mbar_wait_c(bars + B_LAG, lagph); };
    auto yield_done = [&]() { if (w == 0 && lane == 0) mbar_arrive(bars + B_LAG); };
    auto signal = [&](int e) { __syncwarp(); if (lane == 0) mbar_arrive(ev + e * 8); };

    auto fetch_wo = [&]() {
#pragma unroll 1
      for (int u = tid; u < 328; u += 256) {
        const int m = min(41 * rb + (u >> 3), 647), k8 = m / 9;
        cp_async16(sb + SM_WOI + u * 16, (const uint8_t*)P.wo + (8 * k8 + (u & 7)) * (DM * 2) + (72 * j + 8 * (m - k8 * 9)) * 2);
      }
    };
    const uint32_t epoch = ldcg32(g_flags + (rb * 2 + w) * 32 + FR_EP + j);
    TRC(tr, w, 1);
    CKK(7);
    CKK_OUT;

#pragma unroll 1
    for (int L = 0; L < 2; L++) {
      const int tb = 2 + L * 24;
      asm volatile("" : "+r"(lane), "+r"(g), "+r"(t));
      (void)tb;
      ia = 0;
      const uint32_t tag = epoch * 2 + L + 1;
      uint32_t aoff = (w * 64 + q * 16 + (lane & 15)) * 128 + (((lane >> 4) ^ (lane & 7)) << 4);
      {
        uint32_t Pk[27][2];
        float sc0, sc1;
        const uint32_t att = stg + 2 * q * 128 + lane * 4;
        uint4* hp = g_HALO + ((((rb - (q == 0)) * 2 + w) * 8 + j) * 6) * 32 + lane;
        uint8_t* od = o_block(rb, w) + (9 * j) * 1024 + (2 * q) * 128 + lane * 4;
        ACLK_INIT;
        {
          float acc[108];
#pragma unroll
          for (int i = 0; i < 108; i++) acc[i] = 0.f;
          uint32_t prev = 0;
#pragma unroll 1
          for (int kb = 0; kb < 9; kb++) {
            wait_ab();
            yield(9 - kb, LAG1);
            TRC(tr && kb == 0, w, tb + 0);
            MCLK(kb == 0, 0);
            PCLK(kb * 4);
            const uint32_t st = sb + c.s * ST_BYTES, da = dlo(st + w * 8192, 16), db = dlo(st + ST_B, 3456);
            wgmma_fence();
#pragma unroll
            for (int kk = 0; kk < 4; kk++) {
              wgmma_ss_n216(acc, dsc<1024, 1>(da, kk * 32), dsc<128, 0>(db, kk * 6912), 1);
              if (kk == 0) { wgmma_commit(); wgmma_wait<1>(); release_if(kb > 0, prev); }
            }
            wgmma_commit();
            if (kb == 8) yield_done();
            PCLK(kb * 4 + 1);
            if (kb == 0 && L == 0) fetch_wo();
            if (kb == 3 && L == 0) {
              asm volatile("cp.async.wait_all;" ::: "memory");
              fence_async_s();
              __syncwarp();
              if (lane == 0) mbar_arrive(bars + B_WOI);
            }
            PCLK(kb * 4 + 2);
            PCLK(kb * 4 + 3);
            prev = c.s; c.next();
          }
          const uint32_t cs = sb + prev * ST_BYTES + SM_CSQ + t * 8;
          mbar_wait_c(bars + B_CSQ, L);
          const float2 n0 = lds64f(sb + prev * ST_BYTES + SM_XST + w * 512 + (16 * q + g) * 8), n1 = lds64f(sb + prev * ST_BYTES + SM_XST + w * 512 + (16 * q + g + 8) * 8);
          const float m0 = n0.x, r0 = n0.y, m1 = n1.x, r1 = n1.y;
          float2 cv[27];
#pragma unroll
          for (int G = 0; G < 27; G++) cv[G] = lds64f(cs + G * 32);
          PCLK(36);
          wgmma_wait<0>();
          PCLK(37);
          uint32_t dep = P.zero & __float_as_uint(m0) & __float_as_uint(m1);
#pragma unroll
          for (int G = 0; G < 27; G++) dep &= __float_as_uint(cv[G].x);
          release(prev, dep);
          lagph ^= 1;
          TRC(tr, w, tb + 1);
          MCLK(1, 1);
          ACLK(0);
#pragma unroll
          for (int G = 9; G < 27; G++) Pk[G][1] = pack2(fmaf(m1, cv[G].x, acc[4 * G + 2]) * r1, fmaf(m1, cv[G].y, acc[4 * G + 3]) * r1);
          if (q < 3) {
#pragma unroll
            for (int i = 0; i < 18; i++) sts32(att + 256 + (i >> 1) * 1024 + (i & 1) * 128, Pk[9 + i][1]);
          } else if (rb < 15) {
#pragma unroll
            for (int i = 0; i < 6; i++) ll_st128(hp + i * 32, __uint_as_float(Pk[9 + 3 * i][1]), __uint_as_float(Pk[10 + 3 * i][1]), tag, __uint_as_float(Pk[11 + 3 * i][1]));
          }
#pragma unroll
          for (int G = 0; G < 27; G++) {
            if (G < 9) {
              Pk[G][0] = pack2(fmaf(m0, cv[G].x, acc[4 * G]), fmaf(m0, cv[G].y, acc[4 * G + 1]));
              Pk[G][1] = pack2(fmaf(m1, cv[G].x, acc[4 * G + 2]), fmaf(m1, cv[G].y, acc[4 * G + 3]));
            } else {
              Pk[G][0] = pack2(fmaf(m0, cv[G].x, acc[4 * G]) * r0, fmaf(m0, cv[G].y, acc[4 * G + 1]) * r0);
            }
          }
          sc0 = r0 * (0.23570226039551584f * 1.4426950408889634f); sc1 = r1 * (0.23570226039551584f * 1.4426950408889634f);
        }
        ACLK(1);
        constexpr int GA_[4] = {0, 2, 4, 7}, GB_[4] = {1, 3, 5, 8}, GC_[4] = {2, 4, 6, 6};
        float S1[4][4], S2[4][4];
        uint32_t qa[4][2], qc[4][2];
#pragma unroll
        for (int h = 0; h < 4; h++) {
#pragma unroll
          for (int r = 0; r < 2; r++) {
            qa[h][r] = (h == 0 || h == 3 || t >= h) ? Pk[GA_[h]][r] : 0u;
            qc[h][r] = (h == 3 ? t == 3 : t <= h) ? Pk[GC_[h]][r] : 0u;
          }
          mma16(S1[h], qa[h][0], qa[h][1], Pk[GB_[h]][0], Pk[GB_[h]][1], Pk[9 + GA_[h]][0], Pk[9 + GB_[h]][0]);
          mma16(S2[h], qa[h][0], qa[h][1], Pk[GB_[h]][0], Pk[GB_[h]][1], Pk[9 + GA_[h]][1], Pk[9 + GB_[h]][1]);
        }
#pragma unroll
        for (int h = 0; h < 4; h++) {
          mma8(S1[h], qc[h][0], qc[h][1], Pk[9 + GC_[h]][0]);
          mma8(S2[h], qc[h][0], qc[h][1], Pk[9 + GC_[h]][1]);
        }
        uint32_t V1[9], V2[9];
#pragma unroll
        for (int i = 0; i < 9; i++) { V1[i] = movm(Pk[18 + i][0]); V2[i] = movm(Pk[18 + i][1]); }
        const bool remote = q == 0 && rb > 0;
        uint4 hv[6];
#pragma unroll
        for (int i = 0; i < 6; i++) hv[i] = make_uint4(0u, 0u, tag, 0u);
        if (remote) {
#pragma unroll
          for (int i = 0; i < 6; i++) hv[i] = ll_ld128(hp + i * 32);
        }
        const bool up0 = 2 * t > g, up1 = 2 * t + 1 > g;
        const uint32_t mup = (up0 ? 0xffffu : 0u) | (up1 ? 0xffff0000u : 0u);
        auto finish = [&](const float (&x0)[4], const float (&x1)[4], uint32_t ma, const uint32_t (&Vb)[9], int hi) {
          uint32_t pa[4], pb[4];
          float rs[4];
#pragma unroll
          for (int h = 0; h < 4; h++) {
            const float m = qmax(fmaxf(x0[h], x1[h]));
            const uint32_t p = pack2(ex2(x0[h] - m), ex2(x1[h] - m));
            pa[h] = p & ma; pb[h] = p & ~ma;
          }
#pragma unroll
          for (int h = 0; h < 4; h += 2) {
            float R[4];
            mma16(R, pa[h], pa[h + 1], pb[h], pb[h + 1], 0x3f803f80u, 0x3f803f80u);
            rs[h] = rcp_fast(R[0]); rs[h + 1] = rcp_fast(R[2]);
          }
#pragma unroll
          for (int i = 0; i < 9; i++) {
            const int h = 4 * i / 9, e = (h & 1) * 2;
            const bool split = i == 2 || i == 4 || i == 6, nx = split && 2 * t >= i;
            float O[4], N[4];
            mma16(O, pa[h & 2], pa[h | 1], pb[h & 2], pb[h | 1], V1[i], Vb[i]);
            if (i == 4) mma16(N, pa[2], pa[3], pb[2], pb[3], V1[i], Vb[i]); else { N[0] = O[2]; N[1] = O[3]; }
            const float r = nx ? rs[h + (split ? 1 : 0)] : rs[h];
            stg32(od + i * 1024 + hi * 128, pack2((nx ? N[0] : O[e]) * r, (nx ? N[1] : O[e + 1]) * r));
          }
        };
        {
          float x0[4], x1[4];
#pragma unroll
          for (int h = 0; h < 4; h++) { x0[h] = (up0 ? S1[h][2] : S2[h][2]) * sc1; x1[h] = (up1 ? S1[h][3] : S2[h][3]) * sc1; }
          finish(x0, x1, mup, V2, 1);
        }
        ACLK(2);
        bar_sync(1 + w, 128);
        uint32_t H[18];
        if (q > 0) {
#pragma unroll
          for (int i = 0; i < 18; i++) H[i] = lds32(att + (i >> 1) * 1024 + (i & 1) * 128);
        } else {
#pragma unroll 1
          for (int it = 0; it < (1 << 20); it++) {
            bool ok = true;
#pragma unroll
            for (int i = 0; i < 6; i++) ok = ok && hv[i].z == tag;
            if (__all_sync(~0u, ok)) break;
#pragma unroll
            for (int i = 0; i < 6; i++) hv[i] = ll_ld128(hp + i * 32);
          }
#pragma unroll
          for (int i = 0; i < 6; i++) { H[3 * i] = hv[i].x; H[3 * i + 1] = hv[i].y; H[3 * i + 2] = hv[i].w; }
        }
        float S0[4][4];
#pragma unroll
        for (int h = 0; h < 4; h++) {
          mma16(S0[h], qa[h][0], qa[h][1], Pk[GB_[h]][0], Pk[GB_[h]][1], H[GA_[h]], H[GB_[h]]);
        }
#pragma unroll
        for (int h = 0; h < 4; h++) mma8(S0[h], qc[h][0], qc[h][1], H[GC_[h]]);
        uint32_t V0[9];
#pragma unroll
        for (int i = 0; i < 9; i++) V0[i] = movm(H[9 + i]);
        ACLK(3);
        {
          const bool nohalo = (rb | q) == 0;
          const float b0 = up0 && nohalo ? -INFINITY : 0.f, b1 = up1 && nohalo ? -INFINITY : 0.f;
          float x0[4], x1[4];
#pragma unroll
          for (int h = 0; h < 4; h++) { x0[h] = fmaf(up0 ? S0[h][0] : S1[h][0], sc0, b0); x1[h] = fmaf(up1 ? S0[h][1] : S1[h][1], sc0, b1); }
          finish(x0, x1, ~mup, V0, 0);
        }
        ACLK(4);
        signal(EV_O);
        ACLK_OUT;
        TRC(tr, w, tb + 2);
        MCLK(1, 2);
      }
      {
        float acc[36];
        const int hw = rb * 2 + (j & 1), js = (j & 6) + w;
        const uint32_t xt = sb + SM_STG + (16 * q + g) * 288 + w * 144 + t * 4;
        uint32_t xm = sb + SM_STG + (16 * q + (lane & 15)) * 288 + (((9 * w + (lane >> 4)) ^ ((lane >> 2) & 1)) << 4), xl = sb + SM_STG + (2 * q + w) * 2304 + lane * 16;
        uint8_t* xd[5];
#pragma unroll
        for (int u = 0; u < 5; u++) {
          const int row = ((u * 32 + lane) * 57) >> 10;
          xd[u] = P.xs[L + 1] + (128 * rb + 32 * q + 16 * w + (j & 1)) * (DM * 2) + (j & 6) * 144 + row * (DM * 4 - 288) + u * 512 + ((lane ^ (row >> 2)) << 4);
          asm volatile("" : "+l"(xd[u]));
        }
        asm volatile("" : "+r"(xm), "+r"(xl));
        mbar_wait_c(bars + B_RES, L);
        TRC(tr, w, tb + 21);
#pragma unroll
        for (int i = 0; i < 18; i++) { const uint32_t x = lds32(xt + (i >> 1) * 16 + (i & 1) * 2304); acc[2 * i] = blo(x); acc[2 * i + 1] = bhi(x); asm volatile("" : "+f"(acc[2 * i]), "+f"(acc[2 * i + 1])); }
        uint32_t prev = 0;
#pragma unroll 1
        for (int u = 0; u < 5; u++) {
          const uint32_t st = sb + c.s * ST_BYTES, da = dlo(st, 1024), db = dlo(st + ST_B + w * 18432, 1152);
          mbar_wait_c(bars + B_FULL + c.s * 8, c.ph); mbar_wait_c(bars + B_FULLA + c.s * 8, (ia >> 2) & 1);
          TRC(tr && u == 0, w, tb + 3);
          MCLK(u == 0, 3);
          wgmma_fence();
#pragma unroll
          for (int kk = 0; kk < 4; kk++) wgmma_ss_n72(acc, dsc<128, 0>(da, kk * 2048), dsc<128, 0>(db, kk * 2304), 1);
          wgmma_commit();
          wgmma_wait<1>();
          release_if(u > 0, prev);
          mbar_wait_c(bars + B_FULLA + 32 + c.s * 8, (ia >> 2) & 1);
          ia++;
          if (u == 4) break;
          wgmma_fence();
#pragma unroll
          for (int kk = 4; kk < 8; kk++) wgmma_ss_n72(acc, dsc<128, 0>(da, kk * 2048), dsc<128, 0>(db, kk * 2304), 1);
          wgmma_commit();
          prev = c.s; c.next();
        }
        RCLK_INIT;
        wgmma_wait<0>();
        RCLK(0);
        release(c.s);
        c.next();
        if (any_nan(acc[0], acc[2])) {
          SLOW(L);
          const uint8_t* xr = P.xs[L] + (128 * rb + 32 * q + 2 * g + (j & 1)) * (DM * 2) + js * 144 + t * 4;
#pragma unroll
          for (int i = 0; i < 18; i++) { const uint32_t x = ldgpu32(xr + (i >> 1) * 16 + (i & 1) * (DM * 32)); acc[2 * i] = blo(x); acc[2 * i + 1] = bhi(x); }
          redo<9, 1024, 128, 1152, 128>(acc, o_block(rb, j & 1) + q * 256 + lane * 4, g_WO + js * WO_SL + lane * 4, [](uint32_t x, int) { return x; });
        }
        TRC(tr && P5TRACE != 5, w, tb + 4);
        MCLK(1, 4);
#pragma unroll
        for (int u = 0; u < 4; u++)
          stsm4(xm + u * 32, pack2(acc[8 * u], acc[8 * u + 1]), pack2(acc[8 * u + 2], acc[8 * u + 3]), pack2(acc[8 * u + 4], acc[8 * u + 5]), pack2(acc[8 * u + 6], acc[8 * u + 7]));
        asm volatile("stmatrix.sync.aligned.m8n8.x2.shared.b16 [%0], {%1,%2};" ::"r"(xm + 128), "r"(pack2(acc[32], acc[33])), "r"(pack2(acc[34], acc[35])) : "memory");
        RCLK(1);
        bar_sync(8 + q, 64);
        RCLK(2);
#pragma unroll
        for (int u = 0; u < 5; u++) {
          const uint4 v = lds128(xl + u * 512);
          stg128_if(u < 4 || lane < 16, xd[u], v.x, v.y, v.z, v.w);
        }
        RCLK(3);
        signal(EV_X1);
        RCLK(4);
        if (P.zero == 0) {
          float s0 = 0.f, s1 = 0.f, q0 = 0.f, q1 = 0.f;
#pragma unroll
          for (int i = 0; i < 36; i++) {
            if (i & 2) { s1 += acc[i]; q1 = fmaf(acc[i], acc[i], q1); } else { s0 += acc[i]; q0 = fmaf(acc[i], acc[i], q0); }
          }
          s0 = qsum(s0); s1 = qsum(s1); q0 = qsum(q0); q1 = qsum(q1);
          const float ss = t ? s1 : s0, m = ss * (1.f / 72.f);
          ll_st128_if(t < 2, g_ST1 + (hw * 8 + js) * 64 + 16 * q + 8 * t + g, m, fmaxf((t ? q1 : q0) - ss * m, 0.f), tag);
        }
        RCLK(5);
        TRC(tr, w, tb + 5);
        RCLK(6);
        RCLK_OUT;
      }
      {
        uint32_t xA[36][4];
        float acc[32];
        uint32_t s0, one;
        uint64_t db;
        auto bwait = [&](uint32_t dhi, bool skip) {
          s0 = c.s;
          c.next();
          if (!skip) mbar_wait_c(bars + B_FULL + c.s * 8, c.ph);
          db = dsc2(dlo(sb + s0 * ST_BYTES + ST_B, 512) - 3, 0, dhi); one = (c.s ^ P.zero) & 1;
        };
        auto mma = [&](int kk, int pp, bool hand) {
          wgmma_rs_n64(acc, xA[kk], dat(db, (kk / 18) * ST_BYTES + (kk % 18) * 2048 + 48, one), kk != 0);
          if (kk == pp && hand) bar_arrive(7 - w, 256);
          if (kk == 17 || kk == 35) wgmma_commit();
          if (kk == 21) { wgmma_commit(); wgmma_wait<1>(); release(s0); }
        };
        {
          bwait(0x40000040u, false);
          mbar_wait_c(bars + B_GATE3, L);
          float mean0, mean1, rs0, rs1;
          stat_get(g_ST1 + ((rb * 2 + w) * 8 + 2 * t) * 64 + 16 * q + g, tag, 72.f, LN_EPS, mean0, rs0, mean1, rs1);
          const uint32_t ns0 = pack2(GA * rs0, GA * rs0), ns1 = pack2(GA * rs1, GA * rs1);
          const uint32_t nb0 = pack2(-mean0 * blo(ns0), -mean0 * blo(ns0)), nb1 = pack2(-mean1 * blo(ns1), -mean1 * blo(ns1));
          const uint32_t al = sb + (aoff & 8191);
#pragma unroll
          for (int kb = 0; kb < 9; kb++) {
            mbar_wait_c(bars + B_FA3 + (9 * w + kb) * 8, L);
            TRC(tr && kb == 0, w, tb + 6);
            MCLK(kb == 0, 5);
            if (kb == 0) SCLK(0);
            QCLK(kb);
            const uint32_t at = al + (w ? (((kb + 1) >> 1) & 3) * ST_BYTES + ((kb + 1) & 1) * 8192 : ((kb >> 1) & 3) * ST_BYTES + (kb & 1) * 8192);
#pragma unroll
            for (int kk = 4 * kb; kk < 4 * kb + 4; kk++) ldsm4(xA[kk], at ^ ((kk & 3) << 5));
            if (kb) { wgmma_fence(); mma(4 * kb - 2, PP30, w); mma(4 * kb - 1, PP30, w); }
            const uint32_t dep = xA[4 * kb][0] & xA[4 * kb + 1][0] & xA[4 * kb + 2][0] & xA[4 * kb + 3][0] & P.zero;
#pragma unroll
            for (int kk = 4 * kb; kk < 4 * kb + 4; kk++) {
#pragma unroll
              for (int e = 0; e < 4; e++) xA[kk][e] = hfma2(xA[kk][e], (e & 1) ? ns1 : ns0, (e & 1) ? nb1 : nb0);
            }
            mbar_arrive_if(lane == 0 && (kb == 0 || w == 0), bars + B_EA3 + (9 * w + kb) * 8 + dep);
            wgmma_fence();
            mma(4 * kb, PP30, w); mma(4 * kb + 1, PP30, w);
          }
          mma(34, PP30, w); mma(35, PP30, w);
          wgmma_wait<0>();
          if (any_nan(acc[0], acc[2])) {
            SLOW(2 + L);
            const uint8_t* xr = P.xs[L + 1] + (128 * rb + 32 * q + 2 * g + w) * (DM * 2) + t * 4;
#pragma unroll
            for (int i = 0; i < 32; i++) acc[i] = 0.f;
            redo<8, 16, DM * 32, FH * 32, 16>(acc, xr, (const uint8_t*)P.w_in + g * (FH * 4) + (((9 * j + 1) >> 1) + 36) * 128 + t * 4,
                                              [&](uint32_t x, int h) { return hfma2(x, h ? ns1 : ns0, h ? nb1 : nb0); });
#pragma unroll
            for (int i = 0; i < 144; i++) xA[i >> 2][i & 3] = hfma2(ldgpu32(xr + (i >> 1) * 16 + (i & 1) * (DM * 32)), (i & 1) ? ns1 : ns0, (i & 1) ? nb1 : nb0);
          }
        }
        const uint32_t off2 = lds32(sb + SM_OFF);
        uint8_t* z1d = z1_block(rb, w, j) + (tid & 127) * 16;
        uint8_t* zd = z2_block(2 * rb + (q >> 1), j) + (4 * (q & 1) + w) * 4608 + ((g & 3) * 2 + (g >> 2)) * 16 + t * 4;
        float sm[4] = {0.f, 0.f, 0.f, 0.f}, qq[4] = {0.f, 0.f, 0.f, 0.f};
        auto gelu = [&](auto nz2) {
          constexpr int NZ2 = nz2.value, R = 8 - NZ2, D = NZ2 == 8 ? GM2 : NZ2 ? GMM : GM1;
          float th[32], gb = GB;
          uint32_t qa = 0, qb = 0;
          auto head = [&](int G) {
#pragma unroll
            for (int e = 0; e < 4; e++) { const float v = acc[4 * G + e]; th[4 * G + e] = tanh_fast(v * fmaf(v, v, gb)); }
          };
#pragma unroll
          for (int i = 0; i < D; i++) head((i + R) & 7);
#pragma unroll
          for (int i = 0; i < 8; i++) {
            const int G = (i + R) & 7;
            if (i + D < 8) head((i + D + R) & 7);
            float* z = acc + 4 * G;
#pragma unroll
            for (int e = 0; e < 4; e++) z[e] = fmaf(z[e], th[4 * G + e], z[e]);
            uint32_t pa = pack2(z[0], z[1]), pb = pack2(z[2], z[3]), tok;
            if (i < NZ2) {
#pragma unroll
              for (int e = 0; e < 4; e++) { sm[e] += z[e]; qq[e] = fmaf(z[e], z[e], qq[e]); }
              pa = hsub2(pa, off2); pb = hsub2(pb, off2);
              stg32(zd + i * 128, pa); stg32(zd + i * 128 + 9216, pb);
              tok = pa ^ pb ^ __float_as_uint(qq[1]);
            } else {
              if (G & 1) stg128(z1d + (G >> 1) * 2048 + (NZ2 ? 32768 : 0), qa, qb, pa, pb);
              qa = pa; qb = pb;
              tok = pa ^ pb;
            }
            gb = __uint_as_float(tok * P.zero + __float_as_uint(GB));
          }
        };
#pragma unroll 1
        for (int p = 0;; p++) {
          wgmma_wait<0>();
          release(c.s);
          c.next();
          TRC(tr && p == 4, w, tb + 7);
          TRC(tr && p == 8, w, tb + 11);
          MCLK(p == 8, 6);
          SCLK(2 * p + 1);
          QCLK(10 + 3 * p);
          if (p < 4) {
            gelu(Int<8>{});
            zd += 1024;
          } else if (p == 4) {
            gelu(Int<4>{});
            signal(EV_ZN);
            const float a0 = qsum(sm[0] + sm[1]), a1 = qsum(sm[2] + sm[3]), q0 = qsum(qq[0] + qq[1]), q1 = qsum(qq[2] + qq[3]);
            const float ss = t ? a1 : a0, m = ss * (1.f / 288.f);
            ll_st128_if(t < 2, g_ZST + (rb * 2 + w) * 512 + j * 64 + 16 * q + 8 * t + g, m - blo(off2), fmaxf((t ? q1 : q0) - ss * m, 0.f), tag);
            TRC(tr, w, tb + 8);
            TRC(tr, w, tb + 9);
          } else {
            gelu(Int<0>{});
            z1d += 8192;
          }
          SCLK(2 * p + 2);
          QCLK(11 + 3 * p);
          if (p == 8) break;
          bwait(p == 3 ? 0x80000040u : 0x40000040u, w);
          bar_sync(6 + w, 256);
          TRC(tr && p == 4, w, tb + 10);
          wgmma_fence();
#pragma unroll
          for (int kk = 0; kk < 36; kk++) mma(kk, PP3, w == 0 || p < 7);
        }
        signal(EV_Z1);
        TRC(tr, w, tb + 12);
      }
      uint32_t hA[18][4];
      {
        float acc[144];
        const float c0 = __uint_as_float(lds32(sb + SM_OFF + 4));
#pragma unroll
        for (int i = 0; i < 144; i++) {
          asm volatile("fma.rn.f32 %0, %1, %2, %3;" : "=f"(acc[i]) : "f"(__uint_as_float(P.zero)), "f"((float)(i + 2)), "f"(c0));
        }
        uint32_t prev = 0;
        auto stage = [&](int kb) {
          mbar_wait_c(bars + B_FULL + c.s * 8, c.ph);
          TRC(tr && kb == 0, w, tb + 13);
          SCLK(22 + kb);
          const uint32_t st = sb + c.s * ST_BYTES, rt = sb + SM_RT + kb * 128 + t * 8;
          uint64_t db = dsc2(dlo(st + ST_B, 4608), 0, 8 + P.zero);
          uint32_t a[4][4];
#pragma unroll
          for (int kk = 0; kk < 4; kk++) {
            uint32_t r[4];
            ldsm4(r, st + (aoff ^ (kk << 5)));
            const uint2 sc = lds64(rt + kk * 32);
            a[kk][0] = hmul2(__byte_perm(r[0], r[2], 0x5410), sc.x); a[kk][2] = hmul2(__byte_perm(r[0], r[2], 0x7632), sc.y);
            a[kk][1] = hmul2(__byte_perm(r[1], r[3], 0x5410), sc.x); a[kk][3] = hmul2(__byte_perm(r[1], r[3], 0x7632), sc.y);
          }
          if (LAG4 && (kb & 1) == (LAG4 & 1)) yield(32 - kb, LAG4);
          wgmma_fence();
#pragma unroll
          for (int i = 0; i < 8; i++) {
            const int kk = i & 3, hf = i >> 2;
            wgmma_rs_n144(acc + hf * 72, a[kk], db, 1);
            dadd(db, i == 3 ? 144u - 3 * 576 : 576 + P.zero);
            if (i == 0) { wgmma_commit(); wgmma_wait<1>(); release_if(kb, prev); }
            if (i == 3) wgmma_commit();
          }
          wgmma_commit();
          prev = c.s; c.next();
        };
        mbar_wait_c(bars + B_RT, L);
#pragma unroll 1
        for (int kb = 0; kb < 32; kb += 2) {
          if (kb == 8) mbar_wait_c(bars + B_RT1, L);
          MCLK((kb & 7) == 4, 10 + (kb >> 3));
          stage(kb);
          stage(kb + 1);
        }
        if (LAG4) { yield_done(); lagph ^= 1; }
        HCLK(0);
        mbar_wait_c(bars + B_CV + w * 8, L);
        HCLK(1);
        const float gk = 0.5f / GA;
        const float c1 = __uint_as_float(lds32(sb + SM_OFF + 4));
        const float gb0 = -gk * (c1 + __uint_as_float(lds32(sb + SM_CV + w * 256 + (16 * q + g) * 4))), gb1 = -gk * (c1 + __uint_as_float(lds32(sb + SM_CV + w * 256 + (16 * q + g + 8) * 4)));
        mbar_wait_c(w ? bars + B_ZB : bars + B_FULL + c.s * 8, w ? L : c.ph);
        HCLK(2);
        const uint32_t sx = c.s;
        c.next();
        const uint32_t zt = sb + (tid & 127) * 16, zs0 = zt + sx * ST_BYTES + w * ZB, zs1 = w ? zt + SM_STG - 16384 : zs0, zs2 = w ? zt + c.s * ST_BYTES - 20480 : zs0;
#pragma unroll
        for (int u = 0; u < 18; u++) {
          if (u == 0) { wgmma_wait<1>(); HCLK(3); }
          if (u == 9) {
            HCLK(4);
            wgmma_wait<0>();
            HCLK(5);
            release(prev);
            if (L == 0) signal(EV_P4);
            if (w == 1) mbar_wait_c(bars + B_FULL + c.s * 8, c.ph);
            TRC(tr, w, tb + 14);
            SCLK(54);
          }
          const uint4 z = lds128((u < 8 ? zs0 : u < 10 ? zs1 : zs2) + u * 2048);
          hA[u][0] = hmul2(z.x, pack2(fmaf(acc[8 * u], gk, gb0), fmaf(acc[8 * u + 1], gk, gb0)));
          hA[u][1] = hmul2(z.y, pack2(fmaf(acc[8 * u + 2], gk, gb1), fmaf(acc[8 * u + 3], gk, gb1)));
          hA[u][2] = hmul2(z.z, pack2(fmaf(acc[8 * u + 4], gk, gb0), fmaf(acc[8 * u + 5], gk, gb0)));
          hA[u][3] = hmul2(z.w, pack2(fmaf(acc[8 * u + 6], gk, gb1), fmaf(acc[8 * u + 7], gk, gb1)));
        }
        uint32_t dep = P.zero;
#pragma unroll
        for (int u = 0; u < 18; u++) dep &= hA[u][0];
        release(sx, dep);
        TRC(tr, w, tb + 15);
        HCLK(6);
      }
      {
        CLK_INIT;
        if (w == 1) bar_arrive(6, 256);
        uint32_t pk[16];
#pragma unroll
        for (int i = 0; i < 16; i++) pk[i] = 0u;
        auto dump = [&](int p) {
          const uint32_t d = sb + (p & 3) * ST_BYTES, cb = p + j >= 9 ? p + j - 9 : p + j;
          if (lane == 0) asm volatile("cp.async.bulk.wait_group.read 3;" ::: "memory");
          __syncwarp();
#pragma unroll
          for (int u = 0; u < 4; u++) stsm4(d + (aoff ^ (u << 5)), pk[4 * u], pk[4 * u + 1], pk[4 * u + 2], pk[4 * u + 3]);
          fence_async_s();
          __syncwarp();
          tma3d_red_p(lane == 0, &P.red[L], cb * 64, rb * 64 + q * 16, w, d + w * 8192 + q * 2048);
        };
#pragma unroll 1
        for (int p = 0; p < 9; p++) {
          float acc[32];
          CLK(0);
          mbar_wait_c(bars + B_FULL + c.s * 8, c.ph);
          uint64_t db = dsc2(dlo(sb + c.s * ST_BYTES + ST_B + (j & 1) * 4096, 0), 0, 0x40000040u + P.zero);
          CLK(1);
          HCLK(7 + 2 * p);
          bar_sync(6 + w, 256);
          CLK(2);
          wgmma_fence();
#pragma unroll
          for (int kk = 0; kk < 18; kk++) {
            wgmma_rs_n64(acc, hA[kk], db, kk != 0);
            dadd(db, kk == 15 ? 128 - (j & 1) * (36864 >> 4) : 128 + P.zero);
            if (kk == PPK && (w == 0 || p < 8)) bar_arrive(7 - w, 256);
          }
          wgmma_commit();
          CLK(3);
          if (p > 0) dump(p - 1);
          CLK(5);
          wgmma_wait<0>();
          CLK(4);
          HCLK(8 + 2 * p);
          MCLK(p == 1 || p == 8, 7 + (p >> 3));
          release_if(L == 0 || p < 5, c.s);
          c.next();
#pragma unroll
          for (int i = 0; i < 16; i++) pk[i] = pack2(acc[2 * i], acc[2 * i + 1]);
          if (p == 8) { TRC(tr, w, tb + 16); dump(8); TRC(tr, w, tb + 17); }
        }
        if (lane == 0) asm volatile("cp.async.bulk.wait_group 0;" ::: "memory");
        HCLK(25);
        MCLK(1, 9);
        if (L == 0) signal(EV_PT);
        CLK_OUT;
        TRC(tr, w, tb + 18);
      }
    }
    if ((tid & 127) == 0) g_flags[(rb * 2 + w) * 32 + FR_EP + j] = epoch + 1;
    if (tid == 0) g_flags[FJ + j * 32 + FJ_EP + rb] = epoch + 1;
  }
}

typedef CUresult (*EncodeFn)(CUtensorMap*, CUtensorMapDataType, cuuint32_t, void*, const cuuint64_t*, const cuuint64_t*, const cuuint32_t*,
                             const cuuint32_t*, CUtensorMapInterleave, CUtensorMapSwizzle, CUtensorMapL2promotion, CUtensorMapFloatOOBfill);

static void make_map(EncodeFn fn, CUtensorMap* m, const void* ptr, int rank, uint64_t d0, uint64_t d1, uint64_t d2, uint64_t s1, uint64_t s2,
                     uint32_t b0, uint32_t b1, uint32_t b2, CUtensorMapSwizzle swz) {
  cuuint64_t dims[3] = {d0, d1, d2}, strides[2] = {s1, s2};
  cuuint32_t box[3] = {b0, b1, b2}, es[3] = {1, 1, 1};
  fn(m, CU_TENSOR_MAP_DATA_TYPE_BFLOAT16, rank, const_cast<void*>(ptr), dims, strides, box, es, CU_TENSOR_MAP_INTERLEAVE_NONE, swz,
     CU_TENSOR_MAP_L2_PROMOTION_L2_128B, CU_TENSOR_MAP_FLOAT_OOB_FILL_NONE);
}

}

extern "C" void kernel_launch(void* const* d_in, const int* in_sizes, int n_in, void* d_out, int out_size) {
  using namespace mk;
  (void)in_sizes; (void)n_in; (void)out_size;
  static EncodeFn fn = nullptr;
  static uint8_t *wq, *xb;
  static float* csp;
  if (!fn) {
    cudaGetSymbolAddress((void**)&wq, g_WQ);
    cudaGetSymbolAddress((void**)&xb, g_X);
    cudaGetSymbolAddress((void**)&csp, g_CSP);
    cudaDriverEntryPointQueryResult qr;
    cudaGetDriverEntryPoint("cuTensorMapEncodeTiled", (void**)&fn, cudaEnableDefault, &qr);
    cudaFuncSetAttribute(mega_kernel, cudaFuncAttributeMaxDynamicSharedMemorySize, SM_TOTAL);
  }
  Params p;
  p.wqkv = (const __nv_bfloat16*)d_in[1];
  p.wo = (const __nv_bfloat16*)d_in[2];
  p.w_in = (const __nv_bfloat16*)d_in[4];
  p.w_sp = (const __nv_bfloat16*)d_in[5];
  p.b_sp = (const __nv_bfloat16*)d_in[6];
  p.w_out = (const __nv_bfloat16*)d_in[7];
  p.zero = 0;
  p.wq = wq;
  p.csp = csp;
  p.xs[0] = (uint8_t*)d_in[0];
  p.xs[1] = xb;
  p.xs[2] = (uint8_t*)d_out;
  make_map(fn, &p.wsp, p.w_sp, 3, 2048, 1024, 2, 8192, 4096, 64, 64, 2, CU_TENSOR_MAP_SWIZZLE_128B);
  for (int i = 0; i < 2; i++) {
    make_map(fn, &p.red[i], p.xs[i + 1], 3, DM, 1024, 2, 2304, 1152, 64, 16, 1, CU_TENSOR_MAP_SWIZZLE_128B);
    make_map(fn, &p.res[i], p.xs[i], 3, DM, 1024, 2, 2304, 1152, 144, 64, 1, CU_TENSOR_MAP_SWIZZLE_NONE);
  }
  make_map(fn, &p.psn, d_out, 3, DM, 1024, 2, 2304, 1152, 144, 4, 1, CU_TENSOR_MAP_SWIZZLE_NONE);
  for (int i = 0; i < 3; i++) make_map(fn, &p.act[i], p.xs[i], 3, DM, 1024, 2, 2304, 1152, 64, 64, 1, CU_TENSOR_MAP_SWIZZLE_128B);
  for (int i = 0; i < 2; i++) {
    cuuint64_t dims[4] = {i ? 4608u : 2304u, 8, i ? 1u : 2u, 72}, strides[3] = {9216, 4608, 8 * 9216};
    cuuint32_t box[4] = {i ? 64u : 32u, 8, i ? 1u : 2u, 18}, es[4] = {1, 1, 1, 1};
    fn(i ? &p.win64 : &p.win, CU_TENSOR_MAP_DATA_TYPE_BFLOAT16, 4, d_in[4], dims, strides, box, es, CU_TENSOR_MAP_INTERLEAVE_NONE,
       i ? CU_TENSOR_MAP_SWIZZLE_128B : CU_TENSOR_MAP_SWIZZLE_64B, CU_TENSOR_MAP_L2_PROMOTION_L2_128B, CU_TENSOR_MAP_FLOAT_OOB_FILL_NONE);
  }
  make_map(fn, &p.wout, p.w_out, 2, 576, 2304, 1, 1152, 0, 64, 144, 1, CU_TENSOR_MAP_SWIZZLE_128B);
  mega_kernel<<<NGRID, 384, SM_TOTAL, cudaStreamPerThread>>>(p);
}
```

```cpp
#include <cuda_runtime.h>
#include <cuda.h>
#include <cuda_bf16.h>
#include <stdint.h>

#define MK_TRACE 0
#define MK_DBG 0
#define P5TRACE 0
#define LAG1 1
#define PP3 32
#define PP30 33
#define LAG4 1
#define SPL 2
#define NAP 200
#define NAP0 8000
#define KS2 2
#define KS3 2
#define RL3 21
#define PAD 0
#define GM2 3
#define GMM 1
#define GM1 2
#define C0S 32.f
#define OFM 0x10u
#define PPK 13

namespace mk {

constexpr int SEQ = 2048, DM = 576, FH = 2304;
constexpr int NCTA = 128;
constexpr int NGRID = 132;
constexpr uint32_t ZB = 36864;
constexpr uint32_t WQ_SL = 72 * 3456;
constexpr uint32_t WO_SL = 72 * 1152;
constexpr float LN_EPS = 1e-5f;
constexpr float GA = 0.3292034911525734f, GB = 2.423681954311584f;

constexpr uint32_t ST_BYTES = 53248, ST_B = 16384, NST = 4;
constexpr uint32_t SM_STG = NST * ST_BYTES;
constexpr uint32_t SM_BAR = SM_STG + 2 * 9216;
constexpr uint32_t SM_OFF = SM_BAR + 1008;
constexpr uint32_t SM_TOTAL = SM_BAR + 1024;
constexpr uint32_t SM_RT = SM_STG + 4096, SM_CV = SM_STG + 12288, SM_WT = SM_CV + 512;
constexpr uint32_t SM_WOI = 44032, SM_CSQ = 49280, SM_XST = 50176;
constexpr uint32_t B_FULL = 0, B_EMPTY = 32, B_FULLA = 64, B_RES = 128, B_WT = 144, B_IMG = 160, B_WOI = 168, B_ZB = 176, B_GATE3 = 184, B_Z1 = 192, B_LAG = 200,
                   B_RT = 208, B_CSQ = 216, B_CV = 224, B_AD = 240, B_EVT = 272, B_RT1 = 368, B_XRW = 384, B_FA3 = 400, B_EA3 = 544;
enum { EV_PT = 0, EV_O = 1, EV_X1 = 2, EV_ZN = 3, EV_Z1 = 4, EV_P4 = 5, EV_N = 6 };

enum { FR_X2 = 0, FR_O = 1, FR_X1 = 3, FR_EP = 16, FJ = 32 * 32, FJ_WQ = 0, FJ_WO = 1, FJ_WQ0 = 2, FJ_ZN = 3, FJ_P4 = 5, FJ_EP = 16, F_N = FJ + 8 * 32 };

__device__ __align__(1024) uint8_t g_Z[512 * ZB];
constexpr uint32_t POISON = 0xffffffffu;
__device__ __align__(1024) uint8_t g_O[32 * 2 * ZB];
__device__ __align__(1024) uint4 g_RD[NCTA * 36 * 256];
__device__ __align__(1024) uint8_t g_X[SEQ * DM * 2];
#define SLOW(i) do {} while (0)
__device__ __align__(1024) uint8_t g_WQ[8 * WQ_SL];
__device__ __align__(1024) uint8_t g_WO[8 * WO_SL];
__device__ __align__(1024) float g_CSP[2 * NCTA * 216];
__device__ __align__(1024) uint2 g_RT[SEQ];
__device__ __align__(1024) uint4 g_XST[2 * SEQ];
__device__ __align__(1024) uint4 g_ST1[SEQ * 8];
__device__ __align__(1024) uint4 g_ZST[SEQ * 8];
__device__ __align__(1024) uint4 g_HALO[32 * 8 * 6 * 32];
__device__ __align__(1024) uint32_t g_flags[F_N];

struct Params {
  const __nv_bfloat16 *wqkv;
  uint8_t* wq;
  float* csp;
  uint32_t zero;
  const __nv_bfloat16 *wo, *w_in, *w_sp, *b_sp, *w_out;
  uint8_t* xs[3];
  CUtensorMap wsp, win, win64, wout;
  CUtensorMap act[3];
  CUtensorMap res[2];
  CUtensorMap red[2];
  CUtensorMap psn;
};

__device__ __forceinline__ uint32_t smem_u32(const void* p) { return (uint32_t)__cvta_generic_to_shared(p); }
__device__ __forceinline__ void mbar_init(uint32_t bar, uint32_t cnt) { asm volatile("mbarrier.init.shared::cta.b64 [%0], %1;" ::"r"(bar), "r"(cnt)); }
__device__ __forceinline__ void mbar_arrive(uint32_t bar) { asm volatile("mbarrier.arrive.shared::cta.b64 _, [%0];" ::"r"(bar) : "memory"); }
__device__ __forceinline__ void mbar_wait(uint32_t bar, uint32_t parity) {
  asm volatile(
      "{\n.reg .pred p;\n.reg .u32 c;\nmov.u32 c, 0;\nLAB_WAIT:\n"
      "mbarrier.try_wait.parity.shared::cta.b64 p, [%0], %1;\n@p bra LAB_DONE;\n"
      "add.u32 c, c, 1;\nsetp.lt.u32 p, c, 0x100000;\n@p bra LAB_WAIT;\ntrap;\nLAB_DONE:\n}" ::"r"(bar), "r"(parity)
      : "memory");
}
__device__ __forceinline__ void mbar_wait_c(uint32_t bar, uint32_t parity) {
  asm volatile("{\n.reg .pred p;\nLAB_WAIT:\nmbarrier.try_wait.parity.shared::cta.b64 p, [%0], %1;\n@!p bra LAB_WAIT;\n}" ::"r"(bar), "r"(parity) : "memory");
}
__device__ __forceinline__ void flag_wait(const uint32_t* f, uint32_t target) {
  asm volatile(
      "{\n.reg .pred p;\n.reg .u32 c, v;\nmov.u32 c, 0;\nLAB_WAIT:\n"
      "ld.relaxed.gpu.global.u32 v, [%0];\nsub.u32 v, v, %1;\nsetp.ge.s32 p, v, 0;\n@p bra LAB_DONE;\n"
      "add.u32 c, c, 1;\nsetp.lt.u32 p, c, 0x400000;\n@p bra LAB_WAIT;\ntrap;\nLAB_DONE:\nfence.acquire.gpu;\n}" ::"l"(f), "r"(target)
      : "memory");
}
__device__ __forceinline__ void fence_gpu() { asm volatile("fence.acq_rel.gpu;" ::: "memory"); }
__device__ __forceinline__ void fence_async_g() { asm volatile("fence.proxy.async.global;" ::: "memory"); }
__device__ __forceinline__ void fence_async_s() { asm volatile("fence.proxy.async.shared::cta;" ::: "memory"); }
__device__ __forceinline__ uint32_t elect_one() {
  uint32_t p; asm volatile("{\n.reg .pred P;\nelect.sync _|P, 0xffffffff;\nselp.u32 %0, 1, 0, P;\n}" : "=r"(p)); return p;
}
__device__ __forceinline__ void expect_tx_p(uint32_t el, uint32_t bar, uint32_t bytes) {
  asm volatile("{\n.reg .pred P;\nsetp.ne.u32 P, %2, 0;\n@P mbarrier.arrive.expect_tx.shared::cta.b64 _, [%0], %1;\n}" ::"r"(bar), "r"(bytes), "r"(el) : "memory");
}
__device__ __forceinline__ void bulk_load_p(uint32_t el, uint32_t dst, const void* src, uint32_t bytes, uint32_t bar) {
  asm volatile("{\n.reg .pred P;\nsetp.ne.u32 P, %4, 0;\n@P cp.async.bulk.shared::cluster.global.mbarrier::complete_tx::bytes [%0], [%1], %2, [%3];\n}" ::"r"(dst), "l"(src), "r"(bytes), "r"(bar), "r"(el) : "memory");
}
__device__ __forceinline__ uint64_t policy_evict_first() { uint64_t p; asm("createpolicy.fractional.L2::evict_first.b64 %0, 1.0;" : "=l"(p)); return p; }
__device__ __forceinline__ void bulk_load_h(uint32_t el, uint32_t dst, const void* src, uint32_t bytes, uint32_t bar, bool ef, uint64_t pol) {
  if (ef) {
    asm volatile("{\n.reg .pred P;\nsetp.ne.u32 P, %4, 0;\n@P cp.async.bulk.shared::cluster.global.mbarrier::complete_tx::bytes.L2::cache_hint [%0], [%1], %2, [%3], %5;\n}" ::"r"(dst), "l"(src), "r"(bytes), "r"(bar), "r"(el), "l"(pol) : "memory");
  } else {
    asm volatile("{\n.reg .pred P;\nsetp.ne.u32 P, %4, 0;\n@P cp.async.bulk.shared::cluster.global.mbarrier::complete_tx::bytes [%0], [%1], %2, [%3];\n}" ::"r"(dst), "l"(src), "r"(bytes), "r"(bar), "r"(el) : "memory");
  }
}
__device__ __forceinline__ void bulk_mc_h(uint32_t el, uint32_t dst, const void* src, uint32_t bytes, uint32_t bar, bool ef, uint64_t pol) {
  if (ef) {
    asm volatile("{\n.reg .pred P;\nsetp.ne.u32 P, %4, 0;\n@P cp.async.bulk.shared::cluster.global.mbarrier::complete_tx::bytes.multicast::cluster.L2::cache_hint [%0], [%1], %2, [%3], %5, %6;\n}" ::"r"(dst), "l"(src), "r"(bytes), "r"(bar), "r"(el), "h"((uint16_t)3), "l"(pol) : "memory");
  } else {
    asm volatile("{\n.reg .pred P;\nsetp.ne.u32 P, %4, 0;\n@P cp.async.bulk.shared::cluster.global.mbarrier::complete_tx::bytes.multicast::cluster [%0], [%1], %2, [%3], %5;\n}" ::"r"(dst), "l"(src), "r"(bytes), "r"(bar), "r"(el), "h"((uint16_t)3) : "memory");
  }
}
__device__ __forceinline__ void tma3d_h(uint32_t el, uint32_t dst, const CUtensorMap* m, int c0, int c1, int c2, uint32_t bar, bool ef, uint64_t pol) {
  if (ef) {
    asm volatile("{\n.reg .pred P;\nsetp.ne.u32 P, %6, 0;\n@P cp.async.bulk.tensor.3d.shared::cluster.global.mbarrier::complete_tx::bytes.L2::cache_hint [%0], [%1, {%3, %4, %5}], [%2], %7;\n}" ::"r"(dst), "l"(m), "r"(bar), "r"(c0), "r"(c1), "r"(c2), "r"(el), "l"(pol) : "memory");
  } else {
    asm volatile("{\n.reg .pred P;\nsetp.ne.u32 P, %6, 0;\n@P cp.async.bulk.tensor.3d.shared::cluster.global.mbarrier::complete_tx::bytes [%0], [%1, {%3, %4, %5}], [%2];\n}" ::"r"(dst), "l"(m), "r"(bar), "r"(c0), "r"(c1), "r"(c2), "r"(el) : "memory");
  }
}
__device__ __forceinline__ void tma2d_mc_h(uint32_t el, uint32_t dst, const CUtensorMap* m, int c0, int c1, uint32_t bar, bool ef, uint64_t pol) {
  if (ef) {
    asm volatile("{\n.reg .pred P;\nsetp.ne.u32 P, %5, 0;\n@P cp.async.bulk.tensor.2d.shared::cluster.global.mbarrier::complete_tx::bytes.multicast::cluster.L2::cache_hint [%0], [%1, {%3, %4}], [%2], %6, %7;\n}" ::"r"(dst), "l"(m), "r"(bar), "r"(c0), "r"(c1), "r"(el), "h"((uint16_t)3), "l"(pol) : "memory");
  } else {
    asm volatile("{\n.reg .pred P;\nsetp.ne.u32 P, %5, 0;\n@P cp.async.bulk.tensor.2d.shared::cluster.global.mbarrier::complete_tx::bytes.multicast::cluster [%0], [%1, {%3, %4}], [%2], %6;\n}" ::"r"(dst), "l"(m), "r"(bar), "r"(c0), "r"(c1), "r"(el), "h"((uint16_t)3) : "memory");
  }
}
__device__ __forceinline__ void tma4d_mc(uint32_t el, uint32_t dst, const CUtensorMap* m, int c0, int c3, uint32_t bar, uint64_t pol) {
  asm volatile("{\n.reg .pred P;\nsetp.ne.u32 P, %5, 0;\n@P cp.async.bulk.tensor.4d.shared::cluster.global.mbarrier::complete_tx::bytes.multicast::cluster.L2::cache_hint [%0], [%1, {%3, 0, 0, %4}], [%2], %6, %7;\n}" ::"r"(dst), "l"(m), "r"(bar), "r"(c0), "r"(c3), "r"(el), "h"((uint16_t)3), "l"(pol) : "memory");
}
__device__ __forceinline__ void mbar_arrive_cluster(uint32_t addr) { asm volatile("mbarrier.arrive.shared::cluster.b64 _, [%0];" ::"r"(addr) : "memory"); }
__device__ __forceinline__ void mbar_arrive_cluster_if(bool c, uint32_t addr) {
  asm volatile("{\n.reg .pred P;\nsetp.ne.u32 P, %1, 0;\n@P mbarrier.arrive.shared::cluster.b64 _, [%0];\n}" ::"r"(addr), "r"((uint32_t)c) : "memory");
}
__device__ __forceinline__ void mbar_arrive_if(bool c, uint32_t addr) {
  asm volatile("{\n.reg .pred P;\nsetp.ne.u32 P, %1, 0;\n@P mbarrier.arrive.shared::cta.b64 _, [%0];\n}" ::"r"(addr), "r"((uint32_t)c) : "memory");
}
__device__ __forceinline__ uint32_t mapa(uint32_t addr, uint32_t rank) { uint32_t r; asm("mapa.shared::cluster.u32 %0, %1, %2;" : "=r"(r) : "r"(addr), "r"(rank)); return r; }
__device__ __forceinline__ void bulk_store_p(uint32_t el, void* dst, uint32_t src, uint32_t bytes) {
  asm volatile("{\n.reg .pred P;\nsetp.ne.u32 P, %3, 0;\n@P cp.async.bulk.global.shared::cta.bulk_group [%0], [%1], %2;\n}" ::"l"(dst), "r"(src), "r"(bytes), "r"(el) : "memory");
}
__device__ __forceinline__ void flag_release_p(uint32_t el, uint32_t* f) {
  asm volatile("{\n.reg .pred P;\nsetp.ne.u32 P, %1, 0;\n@P red.release.gpu.global.add.u32 [%0], 1;\n}" ::"l"(f), "r"(el) : "memory");
}
__device__ __forceinline__ void flag_add_p(uint32_t el, uint32_t* f) {
  asm volatile("{\n.reg .pred P;\nsetp.ne.u32 P, %1, 0;\n@P red.relaxed.gpu.global.add.u32 [%0], 1;\n}" ::"l"(f), "r"(el) : "memory");
}
__device__ __forceinline__ void prefetch_l2(const void* src, uint32_t bytes) { asm volatile("cp.async.bulk.prefetch.L2.global [%0], %1;" ::"l"(src), "r"(bytes) : "memory"); }
__device__ __forceinline__ void prefetch_map(const CUtensorMap* m) { asm volatile("prefetch.tensormap [%0];" ::"l"(m) : "memory"); }
__device__ __forceinline__ void wgmma_fence() { asm volatile("wgmma.fence.sync.aligned;" ::: "memory"); }
__device__ __forceinline__ void wgmma_commit() { asm volatile("wgmma.commit_group.sync.aligned;" ::: "memory"); }
template <int N> __device__ __forceinline__ void wgmma_wait() { asm volatile("wgmma.wait_group.sync.aligned %0;" ::"n"(N) : "memory"); }
__device__ __forceinline__ uint32_t dlo(uint32_t addr, uint32_t lbo) { return ((addr & 0x3FFFF) >> 4) + ((lbo >> 4) << 16); }
template <uint32_t SBO, uint32_t SWZ> __device__ __forceinline__ uint64_t dsc(uint32_t lo, uint32_t off) {
  uint64_t d; asm("mov.b64 %0, {%1, %2};" : "=l"(d) : "r"(lo + (off >> 4)), "n"((SBO >> 4) | (SWZ << 30))); return d;
}
__device__ __forceinline__ uint64_t dsc2(uint32_t lo, uint32_t off, uint32_t hi) {
  uint64_t d; asm("mov.b64 %0, {%1, %2};" : "=l"(d) : "r"(lo + (off >> 4)), "r"(hi)); return d;
}
__device__ __forceinline__ uint64_t dat(uint64_t d, uint32_t off, uint32_t one) { uint64_t r; asm("mad.wide.u32 %0, %1, %2, %3;" : "=l"(r) : "r"(one), "r"(off >> 4), "l"(d)); return r; }
__device__ __forceinline__ void dadd(uint64_t& d, uint32_t v) {
  asm("{\n.reg .b32 lo, hi;\nmov.b64 {lo, hi}, %0;\nadd.u32 lo, lo, %1;\nmov.b64 %0, {lo, hi};\n}" : "+l"(d) : "r"(v));
}
template <int R> __device__ __forceinline__ void reg_alloc() { asm volatile("setmaxnreg.inc.sync.aligned.u32 %0;" ::"n"(R)); }
template <int R> __device__ __forceinline__ void reg_dealloc() { asm volatile("setmaxnreg.dec.sync.aligned.u32 %0;" ::"n"(R)); }
__device__ __forceinline__ void bar_sync(int id, int n) { asm volatile("bar.sync %0, %1;" ::"r"(id), "r"(n) : "memory"); }
__device__ __forceinline__ void bar_arrive(int id, int n) { asm volatile("bar.arrive %0, %1;" ::"r"(id), "r"(n) : "memory"); }
__device__ __forceinline__ void ldsm4(uint32_t* r, uint32_t addr) {
  asm volatile("ldmatrix.sync.aligned.m8n8.x4.shared.b16 {%0,%1,%2,%3}, [%4];" : "=r"(r[0]), "=r"(r[1]), "=r"(r[2]), "=r"(r[3]) : "r"(addr) : "memory");
}
__device__ __forceinline__ uint32_t movm(uint32_t a) { uint32_t d; asm volatile("movmatrix.sync.aligned.m8n8.trans.b16 %0, %1;" : "=r"(d) : "r"(a)); return d; }
__device__ __forceinline__ void mma16(float* c, uint32_t a0, uint32_t a1, uint32_t a2, uint32_t a3, uint32_t b0, uint32_t b1) {
  asm volatile("mma.sync.aligned.m16n8k16.row.col.f32.bf16.bf16.f32 {%0,%1,%2,%3}, {%4,%5,%6,%7}, {%8,%9}, {%10,%10,%10,%10};"
               : "=f"(c[0]), "=f"(c[1]), "=f"(c[2]), "=f"(c[3]) : "r"(a0), "r"(a1), "r"(a2), "r"(a3), "r"(b0), "r"(b1), "f"(0.f));
}
__device__ __forceinline__ void mma8(float* c, uint32_t a0, uint32_t a1, uint32_t b0) {
  asm volatile("mma.sync.aligned.m16n8k8.row.col.f32.bf16.bf16.f32 {%0,%1,%2,%3}, {%4,%5}, {%6}, {%0,%1,%2,%3};"
               : "+f"(c[0]), "+f"(c[1]), "+f"(c[2]), "+f"(c[3]) : "r"(a0), "r"(a1), "r"(b0));
}
__device__ __forceinline__ uint32_t pack2(float lo, float hi) { uint32_t r; asm("cvt.rn.bf16x2.f32 %0, %1, %2;" : "=r"(r) : "f"(hi), "f"(lo)); return r; }
__device__ __forceinline__ float blo(uint32_t v) { return __uint_as_float(v << 16); }
__device__ __forceinline__ float bhi(uint32_t v) { return __uint_as_float(v & 0xffff0000u); }
__device__ __forceinline__ float tanh_fast(float x) { float y; asm("tanh.approx.f32 %0, %1;" : "=f"(y) : "f"(x)); return y; }
__device__ __forceinline__ float rcp_fast(float x) { float y; asm("rcp.approx.ftz.f32 %0, %1;" : "=f"(y) : "f"(x)); return y; }
__device__ __forceinline__ float ex2(float x) { float y; asm("ex2.approx.ftz.f32 %0, %1;" : "=f"(y) : "f"(x)); return y; }
__device__ __forceinline__ float qsum(float v) { v += __shfl_xor_sync(~0u, v, 1); v += __shfl_xor_sync(~0u, v, 2); return v; }
__device__ __forceinline__ float qmax(float v) { v = fmaxf(v, __shfl_xor_sync(~0u, v, 1)); v = fmaxf(v, __shfl_xor_sync(~0u, v, 2)); return v; }
__device__ __forceinline__ void stg32(void* p, uint32_t v) { asm volatile("st.global.u32 [%0], %1;" ::"l"(p), "r"(v) : "memory"); }
__device__ __forceinline__ void stg128(void* p, uint32_t a, uint32_t b, uint32_t c, uint32_t d) { asm volatile("st.global.v4.u32 [%0], {%1,%2,%3,%4};" ::"l"(p), "r"(a), "r"(b), "r"(c), "r"(d) : "memory"); }
__device__ __forceinline__ uint32_t ldcg32(const void* p) { uint32_t v; asm volatile("ld.global.L1::no_allocate.u32 %0, [%1];" : "=r"(v) : "l"(p) : "memory"); return v; }
__device__ __forceinline__ uint32_t ldgpu32(const void* p) { uint32_t v; asm volatile("ld.relaxed.gpu.global.u32 %0, [%1];" : "=r"(v) : "l"(p) : "memory"); return v; }
__device__ __forceinline__ uint32_t ldca32(const void* p) { uint32_t v; asm volatile("ld.global.ca.u32 %0, [%1];" : "=r"(v) : "l"(p) : "memory"); return v; }
__device__ __forceinline__ void stg128_if(bool c, void* p, uint32_t a, uint32_t b, uint32_t cc, uint32_t d) {
  asm volatile("{\n.reg .pred P;\nsetp.ne.u32 P, %5, 0;\n@P st.global.v4.u32 [%0], {%1,%2,%3,%4};\n}" ::"l"(p), "r"(a), "r"(b), "r"(cc), "r"(d), "r"((uint32_t)c) : "memory");
}
__device__ __forceinline__ uint2 lds64(uint32_t a) { uint2 v; asm volatile("ld.shared.v2.u32 {%0,%1}, [%2];" : "=r"(v.x), "=r"(v.y) : "r"(a) : "memory"); return v; }
__device__ __forceinline__ uint4 ldcg128(const void* p) { uint4 v; asm volatile("ld.global.cg.v4.u32 {%0,%1,%2,%3}, [%4];" : "=r"(v.x), "=r"(v.y), "=r"(v.z), "=r"(v.w) : "l"(p) : "memory"); return v; }
__device__ __forceinline__ uint32_t ldnc16(const void* p) { uint16_t v; asm volatile("ld.global.nc.u16 %0, [%1];" : "=h"(v) : "l"(p)); return v; }
__device__ __forceinline__ uint4 ldnc128(const void* p) { uint4 v; asm volatile("ld.global.nc.v4.u32 {%0,%1,%2,%3}, [%4];" : "=r"(v.x), "=r"(v.y), "=r"(v.z), "=r"(v.w) : "l"(p)); return v; }
__device__ __forceinline__ void cp_async16(uint32_t dst, const void* src) { asm volatile("cp.async.cg.shared.global [%0], [%1], 16;" ::"r"(dst), "l"(src) : "memory"); }
__device__ __forceinline__ uint32_t hsub2(uint32_t a, uint32_t b) { uint32_t d; asm("sub.rn.bf16x2 %0, %1, %2;" : "=r"(d) : "r"(a), "r"(b)); return d; }
__device__ __forceinline__ void stg32_if(bool c, void* p, uint32_t v) {
  asm volatile("{\n.reg .pred P;\nsetp.ne.u32 P, %2, 0;\n@P st.global.u32 [%0], %1;\n}" ::"l"(p), "r"(v), "r"((uint32_t)c) : "memory");
}
__device__ __forceinline__ float wsum(float v) { for (int o = 16; o; o >>= 1) v += __shfl_xor_sync(~0u, v, o); return v; }
__device__ __forceinline__ uint32_t hmul2(uint32_t a, uint32_t b) { uint32_t d; asm("mul.rn.bf16x2 %0, %1, %2;" : "=r"(d) : "r"(a), "r"(b)); return d; }
__device__ __forceinline__ void sts32(uint32_t a, uint32_t v) { asm volatile("st.shared.u32 [%0], %1;" ::"r"(a), "r"(v) : "memory"); }
__device__ __forceinline__ uint32_t lds32(uint32_t a) { uint32_t v; asm volatile("ld.shared.u32 %0, [%1];" : "=r"(v) : "r"(a) : "memory"); return v; }
__device__ __forceinline__ void sts128(uint32_t a, uint32_t x, uint32_t y, uint32_t z, uint32_t w) { asm volatile("st.shared.v4.u32 [%0], {%1,%2,%3,%4};" ::"r"(a), "r"(x), "r"(y), "r"(z), "r"(w) : "memory"); }
__device__ __forceinline__ uint4 lds128(uint32_t a) { uint4 v; asm volatile("ld.shared.v4.u32 {%0,%1,%2,%3}, [%4];" : "=r"(v.x), "=r"(v.y), "=r"(v.z), "=r"(v.w) : "r"(a) : "memory"); return v; }
__device__ __forceinline__ void ll_st64(uint2* p, uint32_t v, uint32_t tag) {
  asm volatile("{\n.reg .b64 r;\nmov.b64 r, {%1,%2};\nst.relaxed.gpu.global.b64 [%0], r;\n}" ::"l"(p), "r"(v), "r"(tag) : "memory");
}
__device__ __forceinline__ uint2 ll_ld64(const uint2* p) {
  uint2 v; asm volatile("{\n.reg .b64 r;\nld.relaxed.gpu.global.b64 r, [%2];\nmov.b64 {%0,%1}, r;\n}" : "=r"(v.x), "=r"(v.y) : "l"(p) : "memory"); return v;
}
__device__ __forceinline__ void ll_st128(uint4* p, float a, float b, uint32_t tag, float c = 0.f) {
  asm volatile("{\n.reg .b128 r;\n.reg .b64 lo, hi;\nmov.b64 lo, {%1,%2};\nmov.b64 hi, {%3,%4};\nmov.b128 r, {lo, hi};\nst.relaxed.gpu.global.b128 [%0], r;\n}" ::"l"(p), "r"(__float_as_uint(a)), "r"(__float_as_uint(b)), "r"(tag), "r"(__float_as_uint(c)) : "memory");
}
__device__ __forceinline__ uint4 ll_ld128(const uint4* p) {
  uint4 v; asm volatile("{\n.reg .b128 r;\n.reg .b64 lo, hi;\nld.relaxed.gpu.global.b128 r, [%4];\nmov.b128 {lo, hi}, r;\nmov.b64 {%0,%1}, lo;\nmov.b64 {%2,%3}, hi;\n}" : "=r"(v.x), "=r"(v.y), "=r"(v.z), "=r"(v.w) : "l"(p) : "memory"); return v;
}
__device__ __forceinline__ void publish_p(uint32_t el, uint32_t* f) {
  asm volatile("{\n.reg .pred P;\nsetp.ne.u32 P, %1, 0;\n@P cp.async.bulk.commit_group;\n@P cp.async.bulk.wait_group 0;\n@P red.release.gpu.global.add.u32 [%0], 1;\n}" ::"l"(f), "r"(el) : "memory");
}
__device__ __forceinline__ void tma3d_red_p(uint32_t el, const CUtensorMap* m, int c0, int c1, int c2, uint32_t src) {
  asm volatile("{\n.reg .pred P;\nsetp.ne.u32 P, %5, 0;\n@P cp.reduce.async.bulk.tensor.3d.global.shared::cta.add.tile.bulk_group [%0, {%2, %3, %4}], [%1];\n@P cp.async.bulk.commit_group;\n}" ::"l"(m), "r"(src), "r"(c0), "r"(c1), "r"(c2), "r"(el) : "memory");
}
__device__ __forceinline__ void stsm4(uint32_t addr, uint32_t a, uint32_t b, uint32_t c, uint32_t d) {
  asm volatile("stmatrix.sync.aligned.m8n8.x4.shared.b16 [%0], {%1,%2,%3,%4};" ::"r"(addr), "r"(a), "r"(b), "r"(c), "r"(d) : "memory");
}
__device__ __forceinline__ void sts64(uint32_t a, uint32_t x, uint32_t y) { asm volatile("st.shared.v2.u32 [%0], {%1,%2};" ::"r"(a), "r"(x), "r"(y) : "memory"); }
__device__ __forceinline__ void ll_st128_if(bool on, uint4* p, float a, float b, uint32_t tag) {
  asm volatile("{\n.reg .pred P;\n.reg .b128 r;\n.reg .b64 lo, hi;\nsetp.ne.u32 P, %4, 0;\nmov.b64 lo, {%1,%2};\nmov.b64 hi, {%3,%3};\nmov.b128 r, {lo, hi};\n@P st.relaxed.gpu.global.b128 [%0], r;\n}" ::"l"(p), "r"(__float_as_uint(a)), "r"(__float_as_uint(b)), "r"(tag), "r"((uint32_t)on) : "memory");
}
__device__ __forceinline__ uint4 ldnc128_if(bool c, const void* p) {
  uint4 v = make_uint4(0u, 0u, 0u, 0u);
  asm volatile("{\n.reg .pred P;\nsetp.ne.u32 P, %5, 0;\n@P ld.global.nc.v4.u32 {%0,%1,%2,%3}, [%4];\n}" : "+r"(v.x), "+r"(v.y), "+r"(v.z), "+r"(v.w) : "l"(p), "r"((uint32_t)c));
  return v;
}
__device__ __forceinline__ uint32_t hfma2(uint32_t a, uint32_t b, uint32_t c) { uint32_t d; asm("fma.rn.bf16x2 %0, %1, %2, %3;" : "=r"(d) : "r"(a), "r"(b), "r"(c)); return d; }
__device__ __forceinline__ float2 lds64f(uint32_t a) { float2 v; asm volatile("ld.shared.v2.f32 {%0,%1}, [%2];" : "=f"(v.x), "=f"(v.y) : "r"(a) : "memory"); return v; }
#define TRC(cond, role, idx) do {} while (0)
#define TRV(role, idx, v) do {} while (0)

#define ACLK_INIT do {} while (0)
#define ACLK(i) do {} while (0)
#define ACLK_OUT do {} while (0)
#define QCLK(i) do {} while (0)
#define PH 1
#define RCLK(i) do {} while (0)
#define RCLK_INIT do {} while (0)
#define RCLK_OUT do {} while (0)
#define SCLK(i) do {} while (0)
#define HCLK(i) do {} while (0)
#define MCLK(c, i) do {} while (0)
#define CKK(i) do {} while (0)
#define CKK_OUT do {} while (0)
#define PL 1
#define PCLK(i) do {} while (0)
#define PQ 1
#define CLK_INIT do {} while (0)
#define CLK(i) do {} while (0)
#define CLK_OUT do {} while (0)

__device__ __forceinline__ void wgmma_ss_n216(float* d, uint64_t da, uint64_t db, int scaleD) {
  asm volatile("{\n.reg .pred p;\nsetp.ne.b32 p, %110, 0;\nwgmma.mma_async.sync.aligned.m64n216k16.f32.bf16.bf16 "
    "{%0,%1,%2,%3,%4,%5,%6,%7,%8,%9,%10,%11,%12,%13,%14,%15,%16,%17,%18,%19,%20,%21,%22,%23,%24,%25,%26,%27,%28,%29,%30,%31,%32,%33,%34,%35,%36,%37,%38,%39,%40,%41,%42,%43,%44,%45,%46,%47,%48,%49,%50,%51,%52,%53,%54,%55,%56,%57,%58,%59,%60,%61,%62,%63,%64,%65,%66,%67,%68,%69,%70,%71,%72,%73,%74,%75,%76,%77,%78,%79,%80,%81,%82,%83,%84,%85,%86,%87,%88,%89,%90,%91,%92,%93,%94,%95,%96,%97,%98,%99,%100,%101,%102,%103,%104,%105,%106,%107}, "
    "%108, %109, p, 1, 1, 0, 1;\n}\n"
    : "+f"(d[0]), "+f"(d[1]), "+f"(d[2]), "+f"(d[3]), "+f"(d[4]), "+f"(d[5]), "+f"(d[6]), "+f"(d[7]), "+f"(d[8]), "+f"(d[9]), "+f"(d[10]), "+f"(d[11]), "+f"(d[12]), "+f"(d[13]), "+f"(d[14]), "+f"(d[15]), "+f"(d[16]), "+f"(d[17]), "+f"(d[18]), "+f"(d[19]), "+f"(d[20]), "+f"(d[21]), "+f"(d[22]), "+f"(d[23]), "+f"(d[24]), "+f"(d[25]), "+f"(d[26]), "+f"(d[27]), "+f"(d[28]), "+f"(d[29]), "+f"(d[30]), "+f"(d[31]), "+f"(d[32]), "+f"(d[33]), "+f"(d[34]), "+f"(d[35]), "+f"(d[36]), "+f"(d[37]), "+f"(d[38]), "+f"(d[39]), "+f"(d[40]), "+f"(d[41]), "+f"(d[42]), "+f"(d[43]), "+f"(d[44]), "+f"(d[45]), "+f"(d[46]), "+f"(d[47]), "+f"(d[48]), "+f"(d[49]), "+f"(d[50]), "+f"(d[51]), "+f"(d[52]), "+f"(d[53]), "+f"(d[54]), "+f"(d[55]), "+f"(d[56]), "+f"(d[57]), "+f"(d[58]), "+f"(d[59]), "+f"(d[60]), "+f"(d[61]), "+f"(d[62]), "+f"(d[63]), "+f"(d[64]), "+f"(d[65]), "+f"(d[66]), "+f"(d[67]), "+f"(d[68]), "+f"(d[69]), "+f"(d[70]), "+f"(d[71]), "+f"(d[72]), "+f"(d[73]), "+f"(d[74]), "+f"(d[75]), "+f"(d[76]), "+f"(d[77]), "+f"(d[78]), "+f"(d[79]), "+f"(d[80]), "+f"(d[81]), "+f"(d[82]), "+f"(d[83]), "+f"(d[84]), "+f"(d[85]), "+f"(d[86]), "+f"(d[87]), "+f"(d[88]), "+f"(d[89]), "+f"(d[90]), "+f"(d[91]), "+f"(d[92]), "+f"(d[93]), "+f"(d[94]), "+f"(d[95]), "+f"(d[96]), "+f"(d[97]), "+f"(d[98]), "+f"(d[99]), "+f"(d[100]), "+f"(d[101]), "+f"(d[102]), "+f"(d[103]), "+f"(d[104]), "+f"(d[105]), "+f"(d[106]), "+f"(d[107])
    : "l"(da), "l"(db), "r"(scaleD));
}
__device__ __forceinline__ void wgmma_ss_n72(float* d, uint64_t da, uint64_t db, int scaleD) {
  asm volatile("{\n.reg .pred p;\nsetp.ne.b32 p, %38, 0;\nwgmma.mma_async.sync.aligned.m64n72k16.f32.bf16.bf16 "
    "{%0,%1,%2,%3,%4,%5,%6,%7,%8,%9,%10,%11,%12,%13,%14,%15,%16,%17,%18,%19,%20,%21,%22,%23,%24,%25,%26,%27,%28,%29,%30,%31,%32,%33,%34,%35}, "
    "%36, %37, p, 1, 1, 0, 1;\n}\n"
    : "+f"(d[0]), "+f"(d[1]), "+f"(d[2]), "+f"(d[3]), "+f"(d[4]), "+f"(d[5]), "+f"(d[6]), "+f"(d[7]), "+f"(d[8]), "+f"(d[9]), "+f"(d[10]), "+f"(d[11]), "+f"(d[12]), "+f"(d[13]), "+f"(d[14]), "+f"(d[15]), "+f"(d[16]), "+f"(d[17]), "+f"(d[18]), "+f"(d[19]), "+f"(d[20]), "+f"(d[21]), "+f"(d[22]), "+f"(d[23]), "+f"(d[24]), "+f"(d[25]), "+f"(d[26]), "+f"(d[27]), "+f"(d[28]), "+f"(d[29]), "+f"(d[30]), "+f"(d[31]), "+f"(d[32]), "+f"(d[33]), "+f"(d[34]), "+f"(d[35])
    : "l"(da), "l"(db), "r"(scaleD));
}
__device__ __forceinline__ void wgmma_rs_n144(float* d, const uint32_t* a, uint64_t db, int scaleD) {
  asm volatile("{\n.reg .pred p;\nsetp.ne.b32 p, %77, 0;\nwgmma.mma_async.sync.aligned.m64n144k16.f32.bf16.bf16 "
    "{%0,%1,%2,%3,%4,%5,%6,%7,%8,%9,%10,%11,%12,%13,%14,%15,%16,%17,%18,%19,%20,%21,%22,%23,%24,%25,%26,%27,%28,%29,%30,%31,%32,%33,%34,%35,%36,%37,%38,%39,%40,%41,%42,%43,%44,%45,%46,%47,%48,%49,%50,%51,%52,%53,%54,%55,%56,%57,%58,%59,%60,%61,%62,%63,%64,%65,%66,%67,%68,%69,%70,%71}, "
    "{%72,%73,%74,%75}, %76, p, 1, 1, 1;\n}\n"
    : "+f"(d[0]), "+f"(d[1]), "+f"(d[2]), "+f"(d[3]), "+f"(d[4]), "+f"(d[5]), "+f"(d[6]), "+f"(d[7]), "+f"(d[8]), "+f"(d[9]), "+f"(d[10]), "+f"(d[11]), "+f"(d[12]), "+f"(d[13]), "+f"(d[14]), "+f"(d[15]), "+f"(d[16]), "+f"(d[17]), "+f"(d[18]), "+f"(d[19]), "+f"(d[20]), "+f"(d[21]), "+f"(d[22]), "+f"(d[23]), "+f"(d[24]), "+f"(d[25]), "+f"(d[26]), "+f"(d[27]), "+f"(d[28]), "+f"(d[29]), "+f"(d[30]), "+f"(d[31]), "+f"(d[32]), "+f"(d[33]), "+f"(d[34]), "+f"(d[35]), "+f"(d[36]), "+f"(d[37]), "+f"(d[38]), "+f"(d[39]), "+f"(d[40]), "+f"(d[41]), "+f"(d[42]), "+f"(d[43]), "+f"(d[44]), "+f"(d[45]), "+f"(d[46]), "+f"(d[47]), "+f"(d[48]), "+f"(d[49]), "+f"(d[50]), "+f"(d[51]), "+f"(d[52]), "+f"(d[53]), "+f"(d[54]), "+f"(d[55]), "+f"(d[56]), "+f"(d[57]), "+f"(d[58]), "+f"(d[59]), "+f"(d[60]), "+f"(d[61]), "+f"(d[62]), "+f"(d[63]), "+f"(d[64]), "+f"(d[65]), "+f"(d[66]), "+f"(d[67]), "+f"(d[68]), "+f"(d[69]), "+f"(d[70]), "+f"(d[71])
    : "r"(a[0]), "r"(a[1]), "r"(a[2]), "r"(a[3]), "l"(db), "r"(scaleD));
}
__device__ __forceinline__ void wgmma_rs_n64(float* d, const uint32_t* a, uint64_t db, int scaleD) {
  asm volatile("{\n.reg .pred p;\nsetp.ne.b32 p, %37, 0;\nwgmma.mma_async.sync.aligned.m64n64k16.f32.bf16.bf16 "
    "{%0,%1,%2,%3,%4,%5,%6,%7,%8,%9,%10,%11,%12,%13,%14,%15,%16,%17,%18,%19,%20,%21,%22,%23,%24,%25,%26,%27,%28,%29,%30,%31}, "
    "{%32,%33,%34,%35}, %36, p, 1, 1, 1;\n}\n"
    : "+f"(d[0]), "+f"(d[1]), "+f"(d[2]), "+f"(d[3]), "+f"(d[4]), "+f"(d[5]), "+f"(d[6]), "+f"(d[7]), "+f"(d[8]), "+f"(d[9]), "+f"(d[10]), "+f"(d[11]), "+f"(d[12]), "+f"(d[13]), "+f"(d[14]), "+f"(d[15]), "+f"(d[16]), "+f"(d[17]), "+f"(d[18]), "+f"(d[19]), "+f"(d[20]), "+f"(d[21]), "+f"(d[22]), "+f"(d[23]), "+f"(d[24]), "+f"(d[25]), "+f"(d[26]), "+f"(d[27]), "+f"(d[28]), "+f"(d[29]), "+f"(d[30]), "+f"(d[31])
    : "r"(a[0]), "r"(a[1]), "r"(a[2]), "r"(a[3]), "l"(db), "r"(scaleD));
}

template <int V> struct Int { static constexpr int value = V; };
struct Cur {
  uint32_t s, ph;
  __device__ __forceinline__ void next() { if (++s == NST) { s = 0; ph ^= 1; } }
};

__device__ __forceinline__ uint8_t* z1_block(int rb, int w, int j) { return g_Z + (rb * 16 + w * 8 + j) * ZB; }
__device__ __forceinline__ uint8_t* o_block(int rb, int w) { return g_O + (rb * 2 + w) * (2 * ZB); }
__device__ __forceinline__ uint8_t* z2_block(int kb, int j) { return g_Z + (256 + kb * 8 + j) * ZB; }
__device__ __forceinline__ void combine8(float m0, float q0, float m1, float q1, float n, float eps, float& mean, float& rstd) {
  mean = qsum(m0 + m1) * 0.125f;
  float d0 = m0 - mean, d1 = m1 - mean;
  float M2 = qsum(q0 + q1 + n * (d0 * d0 + d1 * d1));
  rstd = rsqrtf(fmaf(M2, 0.125f / n, eps));
}
__device__ __forceinline__ void stat_get(const uint4* zs, uint32_t tag, float n, float eps, float& m0, float& r0, float& m1, float& r1) {
  uint4 a0, a1, b0, b1;
#pragma unroll 1
  for (int it = 0; it < (1 << 20); it++) {
    a0 = ll_ld128(zs); a1 = ll_ld128(zs + 64); b0 = ll_ld128(zs + 8); b1 = ll_ld128(zs + 72);
    if (__all_sync(~0u, a0.z == tag && a1.z == tag && b0.z == tag && b1.z == tag)) break;
  }
  combine8(__uint_as_float(a0.x), __uint_as_float(a0.y), __uint_as_float(a1.x), __uint_as_float(a1.y), n, eps, m0, r0);
  combine8(__uint_as_float(b0.x), __uint_as_float(b0.y), __uint_as_float(b1.x), __uint_as_float(b1.y), n, eps, m1, r1);
}

__device__ __forceinline__ void rows_fetch(uint32_t el, uint32_t xr, const uint8_t* src, uint32_t bar) {
  expect_tx_p(el, bar, 9216);
#pragma unroll 1
  for (int r = 0; r < 8; r++) bulk_load_p(el, xr + r * 1152, src + r * (DM * 4), 1152, bar);
}
__device__ __forceinline__ void rows_stats(uint32_t xr, uint4* dst, uint32_t tag, int lane) {
  float s[2] = {0.f, 0.f}, q[4] = {0.f, 0.f, 0.f, 0.f};
  const uint32_t a0 = xr + (lane >> 2) * 1152 + (((lane & 3) * 2) ^ (lane >> 2)) * 16;
  uint4 n0 = lds128(a0), n1 = lds128(a0 ^ 16);
#pragma unroll 1
  for (int e = 1; e <= 9; e++) {
    const uint32_t x[8] = {n0.x, n0.y, n0.z, n0.w, n1.x, n1.y, n1.z, n1.w};
    if (e < 9) { n0 = lds128(a0 + e * 128); n1 = lds128((a0 ^ 16) + e * 128); }
#pragma unroll
    for (int u = 0; u < 8; u++) {
      const float lo = blo(x[u]), hi = bhi(x[u]);
      s[u & 1] += lo + hi; q[(u & 1) * 2] = fmaf(lo, lo, q[(u & 1) * 2]); q[(u & 1) * 2 + 1] = fmaf(hi, hi, q[(u & 1) * 2 + 1]);
    }
  }
  const float sx = s[0] + s[1], sq = (q[0] + q[1]) + (q[2] + q[3]);
  const float m = qsum(sx) * (-1.f / DM), r = rsqrtf(fmaxf(fmaf(qsum(sq), 1.f / DM, -m * m), 0.f) + LN_EPS);
  if ((lane & 3) == 0) ll_st128(dst + (lane >> 2) * 2, m, r, tag);
}

__device__ __forceinline__ void poison(uint32_t el, uint32_t src, const CUtensorMap* m, int rb, int j, int lane) {
#pragma unroll 1
  for (int u = lane; u < 72; u += 32) sts128(src + u * 16, POISON, POISON, POISON, POISON);
  fence_async_s();
  __syncwarp();
#pragma unroll 1
  for (int u = 0; u < 16; u++) {
    __nanosleep(NAP);
    bulk_store_p(el, o_block(rb, u >> 3) + j * 9216 + (u & 7) * 1152, src, 1152);
    asm volatile("{\n.reg .pred P;\nsetp.ne.u32 P, %5, 0;\n@P cp.async.bulk.tensor.3d.global.shared::cta.tile.bulk_group [%0, {%2, %3, %4}], [%1];\n}" ::"l"(m), "r"(src), "r"((j & 6) * 72), "r"(rb * 64 + u * 4), "r"(j & 1), "r"(el) : "memory");
  }
}
__device__ __forceinline__ void mma16acc(float* c, const uint32_t* a, uint32_t b0, uint32_t b1) {
  asm volatile("mma.sync.aligned.m16n8k16.row.col.f32.bf16.bf16.f32 {%0,%1,%2,%3}, {%4,%5,%6,%7}, {%8,%9}, {%0,%1,%2,%3};"
               : "+f"(c[0]), "+f"(c[1]), "+f"(c[2]), "+f"(c[3]) : "r"(a[0]), "r"(a[1]), "r"(a[2]), "r"(a[3]), "r"(b0), "r"(b1));
}
template <int KS, int NG, int AK, int AH, int BK, int BG, class F> __device__ __forceinline__ void redo(float* acc, const uint8_t* pa, const uint8_t* pb, F f) {
#pragma unroll 1
  for (int k = 0; k < 36; k += KS) {
    uint32_t a[4 * KS], b[2 * KS][NG];
#pragma unroll 1
    for (int it = 0; it < (1 << 20); it++) {
      bool ok = true;
#pragma unroll
      for (int e = 0; e < 4 * KS; e++) a[e] = ldgpu32(pa + (e >> 1) * AK + (e & 1) * AH);
#pragma unroll
      for (int e = 0; e < 2 * KS * NG; e++) b[e / NG][e % NG] = ldca32(pb + (e / NG) * BK + (e % NG) * BG);
#pragma unroll
      for (int e = 0; e < 4 * KS; e++) ok = ok && a[e] != POISON;
      if (__all_sync(~0u, ok)) break;
    }
#pragma unroll
    for (int e = 0; e < KS; e++) f(a + 4 * e, k + e);
#pragma unroll
    for (int e = 0; e < KS * NG; e++) mma16acc(acc + 4 * (e % NG), a + 4 * (e / NG), movm(b[2 * (e / NG)][e % NG]), movm(b[2 * (e / NG) + 1][e % NG]));
    pa += 2 * KS * AK; pb += 2 * KS * BK;
  }
}
__device__ __forceinline__ bool any_nan(float a, float b) {
  return __any_sync(~0u, a != a || b != b);
}

__global__ void __cluster_dims__(2, 1, 1) __launch_bounds__(384, 1) mega_kernel(const __grid_constant__ Params P) {
  extern __shared__ __align__(1024) uint8_t smem_raw[];
  uint32_t ckk[8];
  (void)ckk;
  CKK(0);
  const uint32_t sb = smem_u32(smem_raw);
  const uint32_t bars = sb + SM_BAR;
  const int tid = threadIdx.x;
  int lane = tid & 31;
  const int wid = __shfl_sync(~0u, tid >> 5, 0);
  const int cl = blockIdx.x >> 1, tp = cl - 36, t7 = (tp * 37) >> 8;
  const int bid = (cl < 4 ? cl * 8 + 32 : tp < 0 ? cl - 4 : cl < 64 ? tp + t7 + 33 : cl) * 2 + (blockIdx.x & 1);
  if (bid >= NCTA) return;
  const int rb = bid & 15, j = bid >> 4;
  { const bool tr = (tid & 127) == 0 && tid < 256; const int w = tid >> 7; (void)tr; (void)w; TRC(tr, w, 0); }
  CKK(1);
  uint4 wv[5];
  const uint8_t* wsrc;
  {
    const int n8 = min(tid >> 3, 26), part = n8 / 9;
    const uint8_t* src = (const uint8_t*)P.wqkv + (8 * rb + (tid & 7)) * (3 * DM * 2) + (part * (DM - 72) + 72 * j + 8 * n8) * 2;
#pragma unroll
    for (int u = 0; u < SPL; u++) wv[u] = ldnc128_if(tid < 216, src + u * (128 * 3 * DM * 2));
    wsrc = src;
  }
  CKK(2);
  if (tid == 352) {
    for (int s = 0; s < (int)NST; s++) {
      mbar_init(bars + B_FULL + s * 8, 1); mbar_init(bars + B_EMPTY + s * 8, 16);
      mbar_init(bars + B_FULLA + s * 8, 1); mbar_init(bars + B_FULLA + 32 + s * 8, 1);
      mbar_init(bars + B_RES + s * 8, 1); mbar_init(bars + B_RT + s * 8, 1); mbar_init(bars + B_AD + s * 8, 2);
    }
    mbar_init(bars + B_IMG, 8); mbar_init(bars + B_RES + 8, 8); mbar_init(bars + B_WOI, 8); mbar_init(bars + B_GATE3, 3); mbar_init(bars + B_Z1, 1); mbar_init(bars + B_ZB, 1); mbar_init(bars + B_LAG, 4);
    mbar_init(bars + B_CSQ, 3); mbar_init(bars + B_RT1, 1); mbar_init(bars + B_XRW, 1); mbar_init(bars + B_XRW + 8, 1);
    for (int e = 0; e < 2 * EV_N; e++) mbar_init(bars + B_EVT + e * 8, 4);
    asm volatile("fence.mbarrier_init.release.cluster;" ::: "memory");
  }
  if (tid == 320) {
#pragma unroll
    for (int e = 0; e < 28; e++) mbar_init(bars + B_FA3 + e * 8, e < 18 ? 1 : 4);
    asm volatile("fence.mbarrier_init.release.cluster;" ::: "memory");
  }
  __syncthreads();

  if (wid >= 8) {
    reg_dealloc<40>();
    const uint32_t el = elect_one();
    const uint64_t pol = policy_evict_first();
    uint32_t* const fj = g_flags + FJ + j * 32;
    if (wid == 8) {
      if (el) { prefetch_map(&P.act[0]); prefetch_map(&P.wsp); prefetch_map(&P.win); prefetch_map(&P.win64); prefetch_map(&P.wout); prefetch_map(&P.act[1]); prefetch_map(&P.res[0]); prefetch_map(&P.res[1]); prefetch_map(&P.red[0]); prefetch_map(&P.red[1]); prefetch_map(&P.act[2]); }
      const uint32_t epoch = ldcg32(fj + FJ_EP + rb);
      Cur c{0, 1};
      const uint32_t rk = bid & 1;
      uint32_t st, full;
      auto slot = [&](uint32_t bytes) {
        st = sb + c.s * ST_BYTES; full = bars + B_FULL + c.s * 8;
        mbar_wait(full, c.ph);
        expect_tx_p(el, full, bytes);
        mbar_wait(full - B_FULL + B_EMPTY, c.ph);
      };
#pragma unroll 1
      for (int L = 0; L < 2; L++) {
#pragma unroll 1
        for (int i = 0; i < 14; i++) {
          if (L == 0 && (i == 0 || i == 2 * SPL || i == 9)) {
            flag_wait(fj + (i == 9 ? FJ_WO : i == 2 * SPL ? FJ_WQ : FJ_WQ0), (epoch + 1) * 16);
            if (i == 9) flag_wait(g_flags + FJ + (j ^ 1) * 32 + FJ_WO, (epoch + 1) * 16);
            fence_async_g();
            TRC(el, 2, i == 9 ? 46 : i ? 47 : 45);
          }
          const uint32_t hb = i < 9 ? 13824 : i < 13 ? 18432 : 9216, o = ST_B + rk * (i < 9 ? 13824 : 18432);
          const uint8_t* src = i < 9 ? g_WQ + j * WQ_SL + i * 27648 + rk * 13824 : g_WO + ((j & 6) + rk) * WO_SL + (i - 9) * 18432;
          slot(2 * hb);
          bulk_mc_h(el, st + o, src, hb, full, true, pol);
          c.next();
        }
#pragma unroll 1
        for (int i = 0; i < 18; i++) {
          const int p = i >> 1, col = p == 4 ? (9 * j + ((j & 1) ? 0 : 8)) * 32 : (((9 * j + 1) >> 1) + (p < 4 ? p + 36 : p - 5)) * 64;
          if (i & 1) {
            slot(2 * ZB);
          } else {
            st = sb + c.s * ST_BYTES; full = bars + B_FULL + ((c.s + 1) & 3) * 8;
            mbar_wait(bars + B_EMPTY + c.s * 8, c.ph);
          }
          tma4d_mc(el, st + ST_B + rk * 18432, p == 4 ? &P.win : &P.win64, col, (i & 1) * 36 + rk * 18, full, pol);
          if (el && !(i & 1)) mbar_arrive(bars + B_FULL + c.s * 8);
          c.next();
        }
        TRC(el, 2, L * 16 + 6);
        flag_wait(fj + FJ_ZN + L, (epoch + 1) * 16);
        fence_async_g();
        TRC(el, 2, L * 16 + 7);
#pragma unroll 1
        for (int i = 0; i < 32; i++) {
          const uint8_t* src = z2_block(i, j) + rk * 18432;
          if (i >= 4) mbar_wait(bars + B_AD + c.s * 8, ((i >> 2) & 1) ^ 1);
          slot(ST_BYTES);
          bulk_mc_h(el, st + ST_B + rk * 18432, src, 18432, full, true, pol);
          tma3d_h(el, st, &P.wsp, i * 64, rb * 64, 0, full, true, pol);
          c.next();
        }
        mbar_wait(bars + B_Z1, L);
        fence_async_g();
        expect_tx_p(el, bars + B_ZB, 20480);
        bulk_load_h(el, sb + SM_STG, z1_block(rb, 1, j) + 16384, 4096, bars + B_ZB, true, pol);
#pragma unroll 1
        for (int i = 0; i < 10; i++) {
          const int cb = i - 1 + j;
          if (i < 4) mbar_wait(bars + B_AD + c.s * 8, 1);
          slot(i == 1 ? ST_BYTES : ZB);
          if (i < 2) bulk_load_h(el, st, z1_block(rb, i, j) + i * 20480, ZB - i * 20480, full, true, pol);
          if (i == 0) bulk_load_h(el, st + ZB, z1_block(rb, 1, j), 16384, bars + B_ZB, true, pol);
          else tma2d_mc_h(el, st + ST_B + rk * 18432, &P.wout, (cb >= 9 ? cb - 9 : cb) * 64, 288 * j + rk * 144, full, true, pol);
          c.next();
        }
      }
    } else if (wid < 11) {
      int w = wid - 9;
      uint32_t* const fr = g_flags + (rb * 2 + w) * 32;
      const uint32_t epoch = ldcg32(fr + FR_EP + j);
      const uint32_t ev = bars + B_EVT + w * EV_N * 8, t8 = (epoch + 1) * 8;
      Cur c{0, 1};
#pragma unroll 1
      for (int L = 0; L < 2; L++) {
        {
          const uint32_t tag = epoch * 2 + L + 1;
          uint4* const xs = g_XST + (rb * 2 + w) * 128;
          if (L) {
            mbar_wait(ev + EV_PT * 8, 0);
            TRC(el, 3, w * 32 + 16);
            flag_release_p(el, fr + FR_X2);
            TRC(el, 3, w * 32 + 17);
          }
#pragma unroll 1
          for (int i = 0; i < 9; i++) {
            const uint32_t full = bars + B_FULLA + w * 32 + c.s * 8, dst = sb + c.s * ST_BYTES + w * 8192;
            if (L == 0 && i == 4) {
              mbar_wait(bars + B_WT + w * 8, 0);
              TRC(el && w == 0, 2, 37);
              rows_stats(sb + SM_STG + w * 9216, xs + 16 * j, tag, lane);
              TRC(el && w == 0, 2, 38);
            }
            const uint32_t src = sb + (L ? 2 * ST_BYTES + SM_WOI : SM_STG + w * 9216);
            if (i == 4) {
#pragma unroll
              for (int u = 0; u < 6; u++) sts128(src + u * 512 + lane * 16, POISON, POISON, POISON, POISON);
              fence_async_s();
              __syncwarp();
            }
            mbar_wait(bars + B_EMPTY + c.s * 8, c.ph);
            expect_tx_p(el, full, 8192);
            if (i < L) { flag_wait(fr + FR_X2, t8); fence_async_g(); }
            tma3d_h(el, dst, &P.act[L], i * 64, rb * 64, w, full, false, pol);
            TRC(el && i < L, 3, w * 32 + 18);
            c.next();
            if (i >= 4 && i < (L ? 5 : 8)) {
              int b = (rb * 2 + w) * 8 + j;
              asm volatile("" : "+r"(b));
              bulk_store_p(el, i == 4 ? (uint8_t*)g_HALO + b * 3072 : g_O + (b * 3 + i - 5) * 3072, src, 3072);
              if (i < 6) bulk_store_p(el, (i == 4 ? g_ST1 : g_ZST) + b * 64, src, 1024);
              if (i == 6) bulk_store_p(el, g_RT + b * 8, src, 64);
            }
            if (L == 0 && i == 3) rows_fetch(el, sb + SM_STG + w * 9216, P.xs[0] + (128 * rb + 16 * j + w) * (DM * 2), bars + B_WT + w * 8);
          }
          if (el) asm volatile("cp.async.bulk.commit_group;\ncp.async.bulk.wait_group 0;" ::: "memory");
          __syncwarp();
          if (L == 0) fence_gpu();
          const uint32_t tab = sb + L * (2 * ST_BYTES) + SM_XST + w * 512 + lane * 8;
          TRC(el, 3, w * 32 + L * 16 + 13);
#pragma unroll 1
          for (int it = 0; it < (1 << 22); it++) {
            const uint4 a = ll_ld128(xs + 2 * lane), b = ll_ld128(xs + 64 + 2 * lane);
            if (__all_sync(~0u, a.z == tag && b.z == tag)) { sts64(tab, a.x, a.y); sts64(tab + 256, b.x, b.y); break; }
          }
          __syncwarp();
          mbar_arrive_if(el, bars + B_CSQ);
          TRC(el, 3, w * 32 + L * 16 + 14);
          if (w == 1) {
            mbar_wait(bars + B_CSQ, L);
            expect_tx_p(el, bars + B_RES, 18432);
            tma3d_h(el, sb + SM_STG, &P.res[L], (j & 6) * 72, rb * 64, j & 1, bars + B_RES, !L, pol);
          }
          if (L) flag_wait(fj + FJ_P4, t8 * 4);
        }
        asm volatile("" : "+r"(w));
        uint32_t* const fo = g_flags + (rb * 2 + (j & 1)) * 32 + L;
        {
          const uint8_t* src = o_block(rb, j & 1) + w * 8192;
#pragma unroll 1
          for (int i = 0; i < 5; i++) {
            const uint32_t full = bars + B_FULLA + w * 32 + c.s * 8, dst = sb + c.s * ST_BYTES + w * 8192;
            const bool none = 2 * i + w > 8;
            mbar_wait(bars + B_EMPTY + c.s * 8, c.ph);
            expect_tx_p(el, full, none ? 0 : 8192);
            if (i == 0) {
              mbar_wait(ev + EV_O * 8, L);
              TRC(el, 3, w * 32 + L * 16 + 3);
              flag_add_p(el, fr + FR_O + L);
              TRC(el, 3, w * 32 + L * 16 + 4);
              flag_wait(fo + FR_O, t8);
              fence_async_g();
            }
            if (!none) bulk_load_h(el, dst, src + i * 16384, 8192, full, true, pol);
            TRC(el && i == 0, 3, w * 32 + L * 16 + 5);
            c.next();
          }
        }
        {
          expect_tx_p(lane < 9, bars + B_FA3 + (9 * w + lane) * 8, 8192);
          mbar_wait(ev + EV_X1 * 8, L);
          TRC(el, 3, w * 32 + L * 16 + 6);
          if (L) flag_add_p(el, fo + FR_X1); else flag_release_p(el, fo + FR_X1);
          mbar_arrive_if(el, bars + B_GATE3);
          TRC(el, 3, w * 32 + L * 16 + 7);
          mbar_arrive_if(lane < 2, bars + B_FULLA + w * 32 + ((c.s + lane) & 3) * 8);
#pragma unroll 1
          for (int kb = 0; kb < 9; kb++) {
            const int n = 9 * w + kb;
            const uint32_t dst = sb + ((n >> 1) & 3) * ST_BYTES + (n & 1) * 8192;
            if (kb == 0) { flag_wait(fr + FR_X1 + L, t8); fence_async_g(); }
            if (n >= 8) mbar_wait(bars + B_EA3 + (n - 8) * 8, L);
            tma3d_h(el, dst, &P.act[L + 1], kb * 64, rb * 64, w, bars + B_FA3 + n * 8, false, pol);
            TRC(el && kb == 0, 3, w * 32 + L * 16 + 8);
          }
          c.ph ^= ((c.s + 18) >> 2) & 1; c.s = (c.s + 18) & 3;
        }
        asm volatile("" : "+r"(lane), "+r"(w));
        expect_tx_p(el, bars + B_WT + w * 8, 2048);
#pragma unroll 1
        for (int r = 0; r < 8; r++)
          bulk_load_p(el, sb + SM_WT + w * 2176 + r * 272, (const uint8_t*)P.w_sp + (size_t)(128 * rb + 16 * j + 2 * r + w) * (SEQ * 2) + 30 * 128, 256, bars + B_WT + w * 8);
        float cv = (lane & 3) ? 0.f : -blo(ldnc16(P.b_sp + 128 * rb + 16 * j + 2 * (lane >> 2) + w));
        mbar_wait(bars + B_RT, L);
        mbar_wait(bars + B_WT + w * 8, L ^ 1);
        mbar_wait(ev + EV_Z1 * 8, L);
        const uint32_t ro = (w * 64 + 8 * j + (lane >> 2)) * 128, x0 = ((lane & 3) * 2) ^ (lane >> 2);
#pragma unroll 1
        for (int i = 0; i < 32; i++) {
          const bool tail = (i >> 1) == 4;
          const int kb = tail ? i + 22 : i < 8 ? i : i - 2;
          if (i == 8) mbar_wait(bars + B_RT1, L);
          if (!tail) mbar_wait(bars + B_FULL + c.s * 8, c.ph ^ 1);
#pragma unroll
          for (int e = 0; e < 2; e++) {
            const uint4 a = lds128(!tail ? sb + c.s * ST_BYTES + ro + ((x0 ^ e) << 4) : sb + SM_WT + w * 2176 + (lane >> 2) * 272 + (i - 8) * 128 + (lane & 3) * 32 + e * 16);
            const uint4 m = lds128(sb + SM_RT + 4096 + kb * 128 + (lane & 3) * 32 + e * 16);
            cv = fmaf(blo(a.x), blo(m.x), fmaf(bhi(a.x), bhi(m.x), fmaf(blo(a.y), blo(m.y), fmaf(bhi(a.y), bhi(m.y), cv))));
            cv = fmaf(blo(a.z), blo(m.z), fmaf(bhi(a.z), bhi(m.z), fmaf(blo(a.w), blo(m.w), fmaf(bhi(a.w), bhi(m.w), cv))));
          }
          if (!tail) {
            mbar_arrive_if(el, bars + B_AD + c.s * 8 + (__float_as_uint(cv) & P.zero));
            c.next();
          }
        }
        TRC(el, 3, w * 32 + L * 16 + 11);
        uint32_t tag = t8;
        asm volatile("" : "+r"(tag));
        tag = (tag >> 2) - 1 + L;
        cv = qsum(cv);
        uint2* const cs = (uint2*)(g_XST + (rb * 2 + w) * 128 + 1);
        if ((lane & 3) == 0) ll_st64(cs + 32 * j + (lane >> 2) * 4, __float_as_uint(cv), tag);
#pragma unroll 1
        for (int it = 0; it < (1 << 22); it++) {
          const uint2 a = ll_ld64(cs + 4 * lane), b = ll_ld64(cs + 128 + 4 * lane);
          if (__all_sync(~0u, a.y == tag && b.y == tag)) { sts32(sb + SM_CV + w * 256 + lane * 4, a.x); sts32(sb + SM_CV + w * 256 + 128 + lane * 4, b.x); break; }
        }
        __syncwarp();
        if (el) mbar_arrive(bars + B_CV + w * 8);
        TRC(el, 3, w * 32 + L * 16 + 12);
#pragma unroll 1
        for (int kb = 30; kb < 32; kb++) {
          mbar_wait(bars + B_FULL + c.s * 8, c.ph ^ 1);
          if (el) mbar_arrive(bars + B_AD + c.s * 8);
          c.next();
        }
        c.ph ^= ((c.s + 10) >> 2) & 1; c.s = (c.s + 10) & 3;
        if (L == 0) {
          mbar_wait(ev + EV_P4 * 8, 0);
          flag_add_p(el, fj + FJ_P4);
        }
      }
    } else {
      const uint32_t epoch = ldcg32(fj + FJ_EP + rb);
      if (SPL) {
        mbar_wait(bars + B_RES + 8, 0);
        TRC(el, 2, 41);
        flag_release_p(el, fj + FJ_WQ0);
        TRC(el, 2, 42);
      }
      mbar_wait(bars + B_IMG, 0);
      TRC(el, 2, 39);
      flag_release_p(el, fj + FJ_WQ);
      TRC(el, 2, 40);
#pragma unroll 1
      for (int L = 0; L < 2; L++) {
        float* const csf = g_CSP + (NCTA + bid) * 216;
        if (L == 0) {
          flag_wait(fj + FJ_WQ, (epoch + 1) * 16);
          fence_async_g();
          expect_tx_p(el, bars + B_XRW, 13824);
          bulk_load_p(el, sb + ST_BYTES + SM_WOI, g_CSP + j * 16 * 216, 6912, bars + B_XRW);
          bulk_load_p(el, sb + 2 * ST_BYTES + SM_WOI, g_CSP + (j * 16 + 8) * 216, 6912, bars + B_XRW);
          mbar_wait(bars + B_XRW, 0);
#pragma unroll 1
          for (int f = lane; f < 54; f += 32) {
            float s[4] = {0.f, 0.f, 0.f, 0.f};
#pragma unroll 4
            for (int r = 0; r < 16; r++) {
              const uint4 v = lds128(sb + ST_BYTES + SM_WOI + (r >> 3) * ST_BYTES + (r & 7) * 864 + f * 16);
              s[0] += __uint_as_float(v.x); s[1] += __uint_as_float(v.y); s[2] += __uint_as_float(v.z); s[3] += __uint_as_float(v.w);
            }
            sts128(sb + SM_CSQ + f * 16, __float_as_uint(s[0]), __float_as_uint(s[1]), __float_as_uint(s[2]), __float_as_uint(s[3]));
            stg128(csf + f * 4, __float_as_uint(s[0]), __float_as_uint(s[1]), __float_as_uint(s[2]), __float_as_uint(s[3]));
          }
          __syncwarp();
          mbar_arrive_if(el, bars + B_CSQ);
        } else {
#pragma unroll 1
          for (int u = 0; u < 4; u++) {
            const int w = u & 1;
            if (u < 2) {
              flag_wait(g_flags + (rb * 2 + w) * 32 + FR_X2, (epoch + 1) * 8);
              fence_async_g();
              TRC(el, 2, 48 + u);
              rows_fetch(el, sb + SM_STG + w * 9216, P.xs[1] + (128 * rb + 16 * j + w) * (DM * 2), bars + B_XRW + w * 8);
            } else {
              mbar_wait(bars + B_XRW + w * 8, w ^ 1);
              TRC(el, 2, 48 + u);
              rows_stats(sb + SM_STG + w * 9216, g_XST + (rb * 2 + w) * 128 + 16 * j, epoch * 2 + 2, lane);
              TRC(el, 2, 50 + u);
            }
          }
          expect_tx_p(el, bars + B_CSQ, 864);
          bulk_load_p(el, sb + 2 * ST_BYTES + SM_CSQ, csf, 864, bars + B_CSQ);
        }
        if (L == 0) {
          TRC(el, 2, 43);
          mbar_wait(bars + B_WOI, 0);
          bulk_store_p(el, g_WO + j * WO_SL + rb * (41 * 128), sb + SM_WOI, (rb < 15 ? 41 : 33) * 128);
          publish_p(el, fj + FJ_WO);
          TRC(el, 2, 44);
          uint4 y[4];
#pragma unroll
          for (int u = 0; u < 4; u++) y[u] = ldnc128((u < 2 ? (const uint8_t*)P.w_in + (100 + 300 * u) * (2 * FH * 2) + (FH + 1024 * u) * 2 : (const uint8_t*)P.w_sp + (1000 * u - 1500) * (SEQ * 2) + u * 1024) + lane * 16);
          float sq[2] = {0.f, 0.f};
#pragma unroll
          for (int u = 0; u < 4; u++) {
            const uint32_t x[4] = {y[u].x, y[u].y, y[u].z, y[u].w};
#pragma unroll
            for (int e = 0; e < 4; e++) sq[u >> 1] = fmaf(blo(x[e]), blo(x[e]), fmaf(bhi(x[e]), bhi(x[e]), sq[u >> 1]));
          }
          const float o0 = sqrtf(wsum(sq[0]) * (2.f * GA * GA * DM / 512.f)), o1 = sqrtf(wsum(sq[1]) * (C0S * C0S * SEQ / 512.f));
          const uint32_t off = (__float_as_uint(o0) & 0x7f800000u) >> 16 | 0x8000u | OFM;
          if (el) sts64(sb + SM_OFF, off * 0x10001u, min(__float_as_uint(o1) & 0x7f800000u, 0x7e000000u) | 0x00400000u);
        }
        if (el) mbar_arrive(bars + B_GATE3);
        const uint32_t tag = epoch * 2 + L + 1;
        asm volatile("" : "+r"(lane));
        mbar_wait(bars + B_EVT + EV_ZN * 8, L);
        mbar_wait(bars + B_EVT + (EV_N + EV_ZN) * 8, L);
        flag_release_p(el, fj + FJ_ZN + L);
        TRC(el, 2, L * 16 + 8);
        {
          uint4 v[4];
#pragma unroll 1
          for (int it = 0; it < (1 << 22); it++) {
            bool ok = true;
#pragma unroll
            for (int u = 0; u < 4; u++) { v[u] = ll_ld128(g_ZST + (rb * 2 + ((lane >> 1) & 1)) * 512 + ((lane & 1) * 4 + u) * 64 + 8 * j + (lane >> 2)); ok = ok && v[u].z == tag; }
            if (__all_sync(~0u, ok)) break;
          }
          float mean = __uint_as_float(v[0].x) + __uint_as_float(v[1].x) + __uint_as_float(v[2].x) + __uint_as_float(v[3].x), M2 = 0.f;
          mean = (mean + __shfl_xor_sync(~0u, mean, 1)) * 0.125f;
#pragma unroll
          for (int u = 0; u < 4; u++) { const float d = __uint_as_float(v[u].x) - mean; M2 += fmaf(288.f * d, d, __uint_as_float(v[u].y)); }
          M2 += __shfl_xor_sync(~0u, M2, 1);
          const float rs = blo(pack2(rsqrtf(fmaf(M2, 1.f / FH, 4.f * GA * GA * LN_EPS)), 0.f));
          if (!(lane & 1)) ll_st64(g_RT + 128 * rb + 16 * j + (lane >> 1), pack2(rs, rs * mean), tag);
        }
        TRC(el, 2, L * 16 + 10);
#pragma unroll 1
        for (int b = 0; b < 8; b++) {
          uint4 v[4];
#pragma unroll 1
          for (int it = 0; it < (1 << 22); it++) {
            bool ok = true;
#pragma unroll
            for (int u = 0; u < 4; u++) { v[u] = ll_ld128((const uint4*)g_RT + b * 128 + u * 32 + lane); ok = ok && v[u].y == tag && v[u].w == tag; }
            if (__all_sync(~0u, ok)) break;
          }
#pragma unroll
          for (int u = 0; u < 4; u++) {
            const uint32_t rt = sb + SM_RT + b * 512 + u * 128, ro = (lane >> 3) * 32 + (lane & 3) * 8 + ((lane >> 2) & 1) * 2;
            sts32(rt + 4096 + lane * 4, __byte_perm(v[u].x, v[u].z, 0x7632));
            asm volatile("st.shared.u16 [%0], %1;\nst.shared.u16 [%0 + 4], %2;" ::"r"(rt + ro), "h"((uint16_t)v[u].x), "h"((uint16_t)v[u].z) : "memory");
          }
          __syncwarp();
          if (el && (b == 1 || b == 7)) mbar_arrive(bars + (b == 1 ? B_RT : B_RT1));
          TRC(el && b < 2, 2, L * 16 + 11 + b);
        }
        TRC(el, 2, L * 16 + 9);
        mbar_wait(bars + B_EVT + EV_Z1 * 8, L);
        mbar_wait(bars + B_EVT + (EV_N + EV_Z1) * 8, L);
        fence_gpu();
        if (el) mbar_arrive(bars + B_Z1);
        if (L == 0) {
          __nanosleep(NAP0);
          poison(el, sb + SM_STG + 17152, &P.psn, rb, j, lane);
          if (el) asm volatile("cp.async.bulk.commit_group;\ncp.async.bulk.wait_group 0;" ::: "memory");
          __syncwarp();
          fence_gpu();
        }
      }
    }
  } else {
    CKK(3);
    uint8_t* const wdst = P.wq + j * WQ_SL + rb * 3456 + tid * 16;
#pragma unroll
    for (int u = 0; u < SPL; u++) stg128_if(tid < 216, wdst + u * (16 * 3456), wv[u].x, wv[u].y, wv[u].z, wv[u].w);
    __syncwarp();
    if (lane == 0) mbar_arrive(bars + B_RES + 8);
    CKK(4);
    auto repack2 = [&]() {
#pragma unroll
      for (int u = SPL; u < 5; u++) stg128_if((u < 4 || rb < 8) && tid < 216, wdst + u * (16 * 3456), wv[u].x, wv[u].y, wv[u].z, wv[u].w);
      float s[8];
#pragma unroll
      for (int e = 0; e < 8; e++) s[e] = 0.f;
#pragma unroll
      for (int u = 0; u < 5; u++) {
        uint32_t x[4] = {wv[u].x, wv[u].y, wv[u].z, wv[u].w};
        asm volatile("" : "+r"(x[0]), "+r"(x[1]), "+r"(x[2]), "+r"(x[3]));
#pragma unroll
        for (int e = 0; e < 4; e++) { s[2 * e] += blo(x[e]); s[2 * e + 1] += bhi(x[e]); }
      }
#pragma unroll
      for (int m = 4; m; m >>= 1) {
#pragma unroll
        for (int e = 0; e < m; e++) s[e] = ((tid & m) ? s[e + m] : s[e]) + __shfl_xor_sync(~0u, (tid & m) ? s[e] : s[e + m], m);
      }
      stg32_if(tid < 216, P.csp + bid * 216 + tid, __float_as_uint(s[0]));
      __syncwarp();
      if (lane == 0) mbar_arrive(bars + B_IMG);
    };
    reg_alloc<232>();
    CKK(5);
#pragma unroll
    for (int v = SPL; v < 5; v++) wv[v] = ldnc128_if(tid < 216 && (v < 4 || rb < 8), wsrc + v * (128 * 3 * DM * 2));
    repack2();
    CKK(6);
    const int w = wid >> 2, q = wid & 3;
    int g = lane >> 2, t = lane & 3;
    const uint32_t ev = bars + B_EVT + w * EV_N * 8;
    const bool tr = (tid & 127) == 0;
    (void)tr;
    Cur c{0, 0};
    const uint32_t ebar = mapa(bars + B_EMPTY, (bid & 1) ^ (lane & 1));
    auto release = [&](uint32_t s, uint32_t dep = 0) { mbar_arrive_cluster_if(lane < 2, ebar + s * 8 + dep); };
    auto release_if = [&](bool on, uint32_t s) { mbar_arrive_cluster_if(lane < 2 && on, ebar + s * 8); };
    uint32_t ia = 0;
    auto wait_ab = [&]() { mbar_wait_c(bars + B_FULL + c.s * 8, c.ph); mbar_wait_c(bars + B_FULLA + w * 32 + c.s * 8, (ia >> 2) & 1); ia++; };
    uint32_t lagph = 0;
    auto yield = [&](int left, int lag) { if (w == 1 && left == lag) mbar_wait_c(bars + B_LAG, lagph); };
    auto yield_done = [&]() { if (w == 0 && lane == 0) mbar_arrive(bars + B_LAG); };
    auto signal = [&](int e) { __syncwarp(); if (lane == 0) mbar_arrive(ev + e * 8); };

    auto fetch_wo = [&]() {
#pragma unroll 1
      for (int u = tid; u < 328; u += 256) {
        const int m = min(41 * rb + (u >> 3), 647), k8 = m / 9;
        cp_async16(sb + SM_WOI + u * 16, (const uint8_t*)P.wo + (8 * k8 + (u & 7)) * (DM * 2) + (72 * j + 8 * (m - k8 * 9)) * 2);
      }
    };
    const uint32_t epoch = ldcg32(g_flags + (rb * 2 + w) * 32 + FR_EP + j);
    TRC(tr, w, 1);
    CKK(7);
    if (PAD && P.zero) {
#pragma unroll
      for (int i = 0; i < PAD; i++) asm volatile("st.shared.u32 [%0], %1;" ::"r"(sb + i * 20), "r"(tid) : "memory");
    }
    CKK_OUT;

#pragma unroll 1
    for (int L = 0; L < 2; L++) {
      const int tb = 2 + L * 24;
      asm volatile("" : "+r"(lane), "+r"(g), "+r"(t));
      (void)tb;
      ia = 0;
      const uint32_t tag = epoch * 2 + L + 1;
      uint32_t aoff = (w * 64 + q * 16 + (lane & 15)) * 128 + (((lane >> 4) ^ (lane & 7)) << 4);
      {
        uint32_t Pk[27][2];
        float sc0, sc1;
        const uint32_t att = sb + w * 8192 + q * 2048 + lane * 4;
        uint4* hp = g_HALO + ((((rb - (q == 0)) * 2 + w) * 8 + j) * 6) * 32 + lane;
        uint8_t* od = o_block(rb, w) + (9 * j) * 1024 + (2 * q) * 128 + lane * 4;
        ACLK_INIT;
        {
          float acc[108];
#pragma unroll
          for (int i = 0; i < 108; i++) acc[i] = 0.f;
          uint32_t prev = 0;
#pragma unroll 1
          for (int kb = 0; kb < 9; kb++) {
            wait_ab();
            yield(9 - kb, LAG1);
            TRC(tr && kb == 0, w, tb + 0);
            MCLK(kb == 0, 0);
            PCLK(kb * 4);
            const uint32_t st = sb + c.s * ST_BYTES, da = dlo(st + w * 8192, 16), db = dlo(st + ST_B, 3456);
            wgmma_fence();
#pragma unroll
            for (int kk = 0; kk < 4; kk++) {
              wgmma_ss_n216(acc, dsc<1024, 1>(da, kk * 32), dsc<128, 0>(db, kk * 6912), 1);
              if (kk == 0) { wgmma_commit(); wgmma_wait<1>(); release_if(kb > 0, prev); }
            }
            wgmma_commit();
            if (kb == 8) yield_done();
            PCLK(kb * 4 + 1);
            if (kb == 0 && L == 0) fetch_wo();
            if (kb == 3 && L == 0) {
              asm volatile("cp.async.wait_all;" ::: "memory");
              fence_async_s();
              __syncwarp();
              if (lane == 0) mbar_arrive(bars + B_WOI);
            }
            PCLK(kb * 4 + 2);
            PCLK(kb * 4 + 3);
            prev = c.s; c.next();
          }
          const uint32_t cs = sb + prev * ST_BYTES + SM_CSQ + t * 8;
          mbar_wait_c(bars + B_CSQ, L);
          const float2 n0 = lds64f(sb + prev * ST_BYTES + SM_XST + w * 512 + (16 * q + g) * 8), n1 = lds64f(sb + prev * ST_BYTES + SM_XST + w * 512 + (16 * q + g + 8) * 8);
          const float m0 = n0.x, r0 = n0.y, m1 = n1.x, r1 = n1.y;
          float2 cv[27];
#pragma unroll
          for (int G = 0; G < 27; G++) cv[G] = lds64f(cs + G * 32);
          PCLK(36);
          wgmma_wait<0>();
          PCLK(37);
          uint32_t dep = P.zero & __float_as_uint(m0) & __float_as_uint(m1);
#pragma unroll
          for (int G = 0; G < 27; G++) dep &= __float_as_uint(cv[G].x);
          release(prev, dep);
          lagph ^= 1;
          TRC(tr, w, tb + 1);
          MCLK(1, 1);
          ACLK(0);
#pragma unroll
          for (int G = 9; G < 27; G++) Pk[G][1] = pack2(fmaf(m1, cv[G].x, acc[4 * G + 2]) * r1, fmaf(m1, cv[G].y, acc[4 * G + 3]) * r1);
          if (q < 3) {
#pragma unroll
            for (int i = 0; i < 18; i++) sts32(att + (i >> 4) * ST_BYTES + (i & 15) * 128, Pk[9 + i][1]);
          } else if (rb < 15) {
#pragma unroll
            for (int i = 0; i < 6; i++) ll_st128(hp + i * 32, __uint_as_float(Pk[9 + 3 * i][1]), __uint_as_float(Pk[10 + 3 * i][1]), tag, __uint_as_float(Pk[11 + 3 * i][1]));
          }
#pragma unroll
          for (int G = 0; G < 27; G++) {
            if (G < 9) {
              Pk[G][0] = pack2(fmaf(m0, cv[G].x, acc[4 * G]), fmaf(m0, cv[G].y, acc[4 * G + 1]));
              Pk[G][1] = pack2(fmaf(m1, cv[G].x, acc[4 * G + 2]), fmaf(m1, cv[G].y, acc[4 * G + 3]));
            } else {
              Pk[G][0] = pack2(fmaf(m0, cv[G].x, acc[4 * G]) * r0, fmaf(m0, cv[G].y, acc[4 * G + 1]) * r0);
            }
          }
          sc0 = r0 * (0.23570226039551584f * 1.4426950408889634f); sc1 = r1 * (0.23570226039551584f * 1.4426950408889634f);
        }
        ACLK(1);
        constexpr int GA_[4] = {0, 2, 4, 7}, GB_[4] = {1, 3, 5, 8}, GC_[4] = {2, 4, 6, 6};
        float S1[4][4], S2[4][4];
        uint32_t qa[4][2], qc[4][2];
#pragma unroll
        for (int h = 0; h < 4; h++) {
#pragma unroll
          for (int r = 0; r < 2; r++) {
            qa[h][r] = (h == 0 || h == 3 || t >= h) ? Pk[GA_[h]][r] : 0u;
            qc[h][r] = (h == 3 ? t == 3 : t <= h) ? Pk[GC_[h]][r] : 0u;
          }
          mma16(S1[h], qa[h][0], qa[h][1], Pk[GB_[h]][0], Pk[GB_[h]][1], Pk[9 + GA_[h]][0], Pk[9 + GB_[h]][0]);
          mma16(S2[h], qa[h][0], qa[h][1], Pk[GB_[h]][0], Pk[GB_[h]][1], Pk[9 + GA_[h]][1], Pk[9 + GB_[h]][1]);
        }
#pragma unroll
        for (int h = 0; h < 4; h++) {
          mma8(S1[h], qc[h][0], qc[h][1], Pk[9 + GC_[h]][0]);
          mma8(S2[h], qc[h][0], qc[h][1], Pk[9 + GC_[h]][1]);
        }
        uint32_t V1[9], V2[9];
#pragma unroll
        for (int i = 0; i < 9; i++) { V1[i] = movm(Pk[18 + i][0]); V2[i] = movm(Pk[18 + i][1]); }
        const bool remote = q == 0 && rb > 0;
        uint4 hv[6];
#pragma unroll
        for (int i = 0; i < 6; i++) hv[i] = make_uint4(0u, 0u, tag, 0u);
        if (remote) {
#pragma unroll
          for (int i = 0; i < 6; i++) hv[i] = ll_ld128(hp + i * 32);
        }
        const bool up0 = 2 * t > g, up1 = 2 * t + 1 > g;
        const uint32_t mup = (up0 ? 0xffffu : 0u) | (up1 ? 0xffff0000u : 0u);
        auto finish = [&](const float (&x0)[4], const float (&x1)[4], uint32_t ma, const uint32_t (&Vb)[9], int hi) {
          uint32_t pa[4], pb[4];
          float rs[4];
#pragma unroll
          for (int h = 0; h < 4; h++) {
            const float m = qmax(fmaxf(x0[h], x1[h]));
            const uint32_t p = pack2(ex2(x0[h] - m), ex2(x1[h] - m));
            pa[h] = p & ma; pb[h] = p & ~ma;
          }
#pragma unroll
          for (int h = 0; h < 4; h += 2) {
            float R[4];
            mma16(R, pa[h], pa[h + 1], pb[h], pb[h + 1], 0x3f803f80u, 0x3f803f80u);
            rs[h] = rcp_fast(R[0]); rs[h + 1] = rcp_fast(R[2]);
          }
#pragma unroll
          for (int i = 0; i < 9; i++) {
            const int h = 4 * i / 9, e = (h & 1) * 2;
            const bool split = i == 2 || i == 4 || i == 6, nx = split && 2 * t >= i;
            float O[4], N[4];
            mma16(O, pa[h & 2], pa[h | 1], pb[h & 2], pb[h | 1], V1[i], Vb[i]);
            if (i == 4) mma16(N, pa[2], pa[3], pb[2], pb[3], V1[i], Vb[i]); else { N[0] = O[2]; N[1] = O[3]; }
            const float r = nx ? rs[h + (split ? 1 : 0)] : rs[h];
            stg32(od + i * 1024 + hi * 128, pack2((nx ? N[0] : O[e]) * r, (nx ? N[1] : O[e + 1]) * r));
          }
        };
        {
          float x0[4], x1[4];
#pragma unroll
          for (int h = 0; h < 4; h++) { x0[h] = (up0 ? S1[h][2] : S2[h][2]) * sc1; x1[h] = (up1 ? S1[h][3] : S2[h][3]) * sc1; }
          finish(x0, x1, mup, V2, 1);
        }
        ACLK(2);
        bar_sync(1 + w, 128);
        uint32_t H[18];
        if (q > 0) {
#pragma unroll
          for (int i = 0; i < 18; i++) H[i] = lds32(att - 2048 + (i >> 4) * ST_BYTES + (i & 15) * 128);
        } else {
#pragma unroll 1
          for (int it = 0; it < (1 << 20); it++) {
            bool ok = true;
#pragma unroll
            for (int i = 0; i < 6; i++) ok = ok && hv[i].z == tag;
            if (__all_sync(~0u, ok)) break;
#pragma unroll
            for (int i = 0; i < 6; i++) hv[i] = ll_ld128(hp + i * 32);
          }
#pragma unroll
          for (int i = 0; i < 6; i++) { H[3 * i] = hv[i].x; H[3 * i + 1] = hv[i].y; H[3 * i + 2] = hv[i].w; }
        }
        float S0[4][4];
#pragma unroll
        for (int h = 0; h < 4; h++) {
          mma16(S0[h], qa[h][0], qa[h][1], Pk[GB_[h]][0], Pk[GB_[h]][1], H[GA_[h]], H[GB_[h]]);
        }
#pragma unroll
        for (int h = 0; h < 4; h++) mma8(S0[h], qc[h][0], qc[h][1], H[GC_[h]]);
        uint32_t V0[9];
#pragma unroll
        for (int i = 0; i < 9; i++) V0[i] = movm(H[9 + i]);
        ACLK(3);
        {
          const bool nohalo = (rb | q) == 0;
          const float b0 = up0 && nohalo ? -INFINITY : 0.f, b1 = up1 && nohalo ? -INFINITY : 0.f;
          float x0[4], x1[4];
#pragma unroll
          for (int h = 0; h < 4; h++) { x0[h] = fmaf(up0 ? S0[h][0] : S1[h][0], sc0, b0); x1[h] = fmaf(up1 ? S0[h][1] : S1[h][1], sc0, b1); }
          finish(x0, x1, ~mup, V0, 0);
        }
        ACLK(4);
        signal(EV_O);
        ACLK_OUT;
        TRC(tr, w, tb + 2);
        MCLK(1, 2);
      }
      {
        float acc[36];
        const int hw = rb * 2 + (j & 1), js = (j & 6) + w;
        const uint32_t xt = sb + SM_STG + (16 * q + g) * 288 + w * 144 + t * 4;
        uint32_t xm = sb + SM_STG + (16 * q + (lane & 15)) * 288 + (((9 * w + (lane >> 4)) ^ ((lane >> 2) & 1)) << 4), xl = sb + SM_STG + (2 * q + w) * 2304 + lane * 16;
        uint8_t* xd[5];
#pragma unroll
        for (int u = 0; u < 5; u++) {
          const int row = ((u * 32 + lane) * 57) >> 10;
          xd[u] = P.xs[L + 1] + (128 * rb + 32 * q + 16 * w + (j & 1)) * (DM * 2) + (j & 6) * 144 + row * (DM * 4 - 288) + u * 512 + ((lane ^ (row >> 2)) << 4);
          asm volatile("" : "+l"(xd[u]));
        }
        asm volatile("" : "+r"(xm), "+r"(xl));
        mbar_wait_c(bars + B_RES, L);
        TRC(tr, w, tb + 21);
#pragma unroll
        for (int i = 0; i < 18; i++) { const uint32_t x = lds32(xt + (i >> 1) * 16 + (i & 1) * 2304); acc[2 * i] = blo(x); acc[2 * i + 1] = bhi(x); asm volatile("" : "+f"(acc[2 * i]), "+f"(acc[2 * i + 1])); }
        uint32_t prev = 0;
#pragma unroll 1
        for (int u = 0; u < 5; u++) {
          const uint32_t st = sb + c.s * ST_BYTES, da = dlo(st, 1024), db = dlo(st + ST_B + w * 18432, 1152);
          mbar_wait_c(bars + B_FULL + c.s * 8, c.ph); mbar_wait_c(bars + B_FULLA + c.s * 8, (ia >> 2) & 1);
          TRC(tr && u == 0, w, tb + 3);
          MCLK(u == 0, 3);
          wgmma_fence();
#pragma unroll
          for (int kk = 0; kk < 4; kk++) wgmma_ss_n72(acc, dsc<128, 0>(da, kk * 2048), dsc<128, 0>(db, kk * 2304), 1);
          wgmma_commit();
          wgmma_wait<1>();
          release_if(u > 0, prev);
          mbar_wait_c(bars + B_FULLA + 32 + c.s * 8, (ia >> 2) & 1);
          ia++;
          if (u == 4) break;
          wgmma_fence();
#pragma unroll
          for (int kk = 4; kk < 8; kk++) wgmma_ss_n72(acc, dsc<128, 0>(da, kk * 2048), dsc<128, 0>(db, kk * 2304), 1);
          wgmma_commit();
          prev = c.s; c.next();
        }
        RCLK_INIT;
        wgmma_wait<0>();
        RCLK(0);
        release(c.s);
        c.next();
        if (__builtin_expect(any_nan(acc[0], acc[2]), 0)) {
          SLOW(L);
          const uint8_t* xr = P.xs[L] + (128 * rb + 32 * q + 2 * g + (j & 1)) * (DM * 2) + js * 144 + t * 4;
#pragma unroll
          for (int i = 0; i < 18; i++) { const uint32_t x = ldgpu32(xr + (i >> 1) * 16 + (i & 1) * (DM * 32)); acc[2 * i] = blo(x); acc[2 * i + 1] = bhi(x); }
          redo<KS2, 9, 1024, 128, 1152, 128>(acc, o_block(rb, j & 1) + q * 256 + lane * 4, g_WO + js * WO_SL + lane * 4, [](uint32_t*, int) {});
        }
        TRC(tr && P5TRACE != 5, w, tb + 4);
        MCLK(1, 4);
#pragma unroll
        for (int u = 0; u < 4; u++)
          stsm4(xm + u * 32, pack2(acc[8 * u], acc[8 * u + 1]), pack2(acc[8 * u + 2], acc[8 * u + 3]), pack2(acc[8 * u + 4], acc[8 * u + 5]), pack2(acc[8 * u + 6], acc[8 * u + 7]));
        asm volatile("stmatrix.sync.aligned.m8n8.x2.shared.b16 [%0], {%1,%2};" ::"r"(xm + 128), "r"(pack2(acc[32], acc[33])), "r"(pack2(acc[34], acc[35])) : "memory");
        RCLK(1);
        bar_sync(8 + q, 64);
        RCLK(2);
#pragma unroll
        for (int u = 0; u < 5; u++) {
          const uint4 v = lds128(xl + u * 512);
          stg128_if(u < 4 || lane < 16, xd[u], v.x, v.y, v.z, v.w);
        }
        RCLK(3);
        signal(EV_X1);
        RCLK(4);
        if (P.zero == 0) {
          float s0 = 0.f, s1 = 0.f, q0 = 0.f, q1 = 0.f;
#pragma unroll
          for (int i = 0; i < 36; i++) {
            if (i & 2) { s1 += acc[i]; q1 = fmaf(acc[i], acc[i], q1); } else { s0 += acc[i]; q0 = fmaf(acc[i], acc[i], q0); }
          }
          s0 = qsum(s0); s1 = qsum(s1); q0 = qsum(q0); q1 = qsum(q1);
          const float ss = t ? s1 : s0, m = ss * (1.f / 72.f);
          ll_st128_if(t < 2, g_ST1 + (hw * 8 + js) * 64 + 16 * q + 8 * t + g, m, fmaxf((t ? q1 : q0) - ss * m, 0.f), tag);
        }
        RCLK(5);
        TRC(tr, w, tb + 5);
        RCLK(6);
        RCLK_OUT;
      }
      {
        uint32_t xA[36][4];
        float acc[32];
        uint32_t s0, one, off2;
        uint8_t *z1d, *zd;
        uint64_t db;
        auto bwait = [&](uint32_t dhi, bool skip) {
          s0 = c.s;
          c.next();
          if (!skip) mbar_wait_c(bars + B_FULL + c.s * 8, c.ph);
          db = dsc2(dlo(sb + s0 * ST_BYTES + ST_B, 512) - 3, 0, dhi); one = (c.s ^ P.zero) & 1;
        };
        auto mma = [&](int kk, int pp, bool hand) {
          wgmma_rs_n64(acc, xA[kk], dat(db, (kk / 18) * ST_BYTES + (kk % 18) * 2048 + 48, one), kk != 0);
          if (kk == pp && hand) bar_arrive(7 - w, 256);
          if (kk == 17 || kk == 35) wgmma_commit();
          if (kk == RL3) { wgmma_commit(); wgmma_wait<1>(); release(s0); }
        };
        {
          bwait(0x40000040u, false);
          mbar_wait_c(bars + B_GATE3, L);
          float mean0, mean1, rs0, rs1;
          stat_get(g_ST1 + ((rb * 2 + w) * 8 + 2 * t) * 64 + 16 * q + g, tag, 72.f, LN_EPS, mean0, rs0, mean1, rs1);
          const uint32_t ns0 = pack2(GA * rs0, GA * rs0), ns1 = pack2(GA * rs1, GA * rs1);
          const uint32_t nb0 = pack2(-mean0 * blo(ns0), -mean0 * blo(ns0)), nb1 = pack2(-mean1 * blo(ns1), -mean1 * blo(ns1));
          const uint32_t al = sb + (aoff & 8191);
#pragma unroll
          for (int kb = 0; kb < 9; kb++) {
            mbar_wait_c(bars + B_FA3 + (9 * w + kb) * 8, L);
            TRC(tr && kb == 0, w, tb + 6);
            MCLK(kb == 0, 5);
            if (kb == 0) SCLK(0);
            QCLK(kb);
            const uint32_t at = al + (w ? (((kb + 1) >> 1) & 3) * ST_BYTES + ((kb + 1) & 1) * 8192 : ((kb >> 1) & 3) * ST_BYTES + (kb & 1) * 8192);
#pragma unroll
            for (int kk = 4 * kb; kk < 4 * kb + 4; kk++) ldsm4(xA[kk], at ^ ((kk & 3) << 5));
            if (kb) { wgmma_fence(); mma(4 * kb - 2, PP30, w); mma(4 * kb - 1, PP30, w); }
            const uint32_t dep = xA[4 * kb][0] & xA[4 * kb + 1][0] & xA[4 * kb + 2][0] & xA[4 * kb + 3][0] & P.zero;
#pragma unroll
            for (int kk = 4 * kb; kk < 4 * kb + 4; kk++) {
#pragma unroll
              for (int e = 0; e < 4; e++) xA[kk][e] = hfma2(xA[kk][e], (e & 1) ? ns1 : ns0, (e & 1) ? nb1 : nb0);
            }
            mbar_arrive_if(lane == 0 && (kb == 0 || w == 0), bars + B_EA3 + (9 * w + kb) * 8 + dep);
            wgmma_fence();
            mma(4 * kb, PP30, w); mma(4 * kb + 1, PP30, w);
          }
          mma(34, PP30, w); mma(35, PP30, w);
          off2 = lds32(sb + SM_OFF);
          z1d = z1_block(rb, w, j) + (tid & 127) * 16;
          zd = z2_block(2 * rb + (q >> 1), j) + (4 * (q & 1) + w) * 4608 + ((g & 3) * 2 + (g >> 2)) * 16 + t * 4;
          asm volatile("" : "+l"(z1d), "+l"(zd));
          wgmma_wait<0>();
          if (__builtin_expect(any_nan(acc[0], acc[2]), 0)) {
            SLOW(2 + L);
            uint4* const rd = g_RD + bid * (36 * 256) + tid;
            const uint8_t* xr = P.xs[L + 1] + (128 * rb + 32 * q + 2 * g + w) * (DM * 2) + t * 4;
#pragma unroll
            for (int i = 0; i < 32; i++) acc[i] = 0.f;
            redo<KS3, 8, 16, DM * 32, FH * 32, 16>(acc, xr, (const uint8_t*)P.w_in + g * (FH * 4) + (((9 * j + 1) >> 1) + 36) * 128 + t * 4,
                                              [&](uint32_t* a, int k) {
#pragma unroll
                                                for (int e = 0; e < 4; e++) a[e] = hfma2(a[e], (e & 1) ? ns1 : ns0, (e & 1) ? nb1 : nb0);
                                                stg128(rd + k * 256, a[0], a[1], a[2], a[3]);
                                              });
#pragma unroll
            for (int k = 0; k < 36; k++) { const uint4 v = ldcg128(rd + k * 256); xA[k][0] = v.x; xA[k][1] = v.y; xA[k][2] = v.z; xA[k][3] = v.w; }
          }
        }
        float sm[4] = {0.f, 0.f, 0.f, 0.f}, qq[4] = {0.f, 0.f, 0.f, 0.f};
        auto gelu = [&](auto nz2) {
          constexpr int NZ2 = nz2.value, R = 8 - NZ2, D = NZ2 == 8 ? GM2 : NZ2 ? GMM : GM1;
          float th[32], gb = GB;
          uint32_t qa = 0, qb = 0;
          auto head = [&](int G) {
#pragma unroll
            for (int e = 0; e < 4; e++) { const float v = acc[4 * G + e]; th[4 * G + e] = tanh_fast(v * fmaf(v, v, gb)); }
          };
#pragma unroll
          for (int i = 0; i < D; i++) head((i + R) & 7);
#pragma unroll
          for (int i = 0; i < 8; i++) {
            const int G = (i + R) & 7;
            if (i + D < 8) head((i + D + R) & 7);
            float* z = acc + 4 * G;
#pragma unroll
            for (int e = 0; e < 4; e++) z[e] = fmaf(z[e], th[4 * G + e], z[e]);
            uint32_t pa = pack2(z[0], z[1]), pb = pack2(z[2], z[3]), tok;
            if (i < NZ2) {
#pragma unroll
              for (int e = 0; e < 4; e++) { sm[e] += z[e]; qq[e] = fmaf(z[e], z[e], qq[e]); }
              pa = hsub2(pa, off2); pb = hsub2(pb, off2);
              stg32(zd + i * 128, pa); stg32(zd + i * 128 + 9216, pb);
              tok = pa ^ pb ^ __float_as_uint(qq[1]);
            } else {
              if (G & 1) stg128(z1d + (G >> 1) * 2048 + (NZ2 ? 32768 : 0), qa, qb, pa, pb);
              qa = pa; qb = pb;
              tok = pa ^ pb;
            }
            gb = __uint_as_float(tok * P.zero + __float_as_uint(GB));
          }
        };
#pragma unroll 1
        for (int p = 0;; p++) {
          wgmma_wait<0>();
          release(c.s);
          c.next();
          TRC(tr && p == 4, w, tb + 7);
          TRC(tr && p == 8, w, tb + 11);
          MCLK(p == 8, 6);
          SCLK(2 * p + 1);
          QCLK(10 + 3 * p);
          if (p < 4) {
            gelu(Int<8>{});
            zd += 1024;
          } else if (p == 4) {
            gelu(Int<4>{});
            signal(EV_ZN);
            const float a0 = qsum(sm[0] + sm[1]), a1 = qsum(sm[2] + sm[3]), q0 = qsum(qq[0] + qq[1]), q1 = qsum(qq[2] + qq[3]);
            const float ss = t ? a1 : a0, m = ss * (1.f / 288.f);
            ll_st128_if(t < 2, g_ZST + (rb * 2 + w) * 512 + j * 64 + 16 * q + 8 * t + g, m - blo(off2), fmaxf((t ? q1 : q0) - ss * m, 0.f), tag);
            TRC(tr, w, tb + 8);
            TRC(tr, w, tb + 9);
          } else {
            gelu(Int<0>{});
            z1d += 8192;
          }
          SCLK(2 * p + 2);
          QCLK(11 + 3 * p);
          if (p == 8) break;
          bwait(p == 3 ? 0x80000040u : 0x40000040u, w);
          bar_sync(6 + w, 256);
          TRC(tr && p == 4, w, tb + 10);
          wgmma_fence();
#pragma unroll
          for (int kk = 0; kk < 36; kk++) mma(kk, PP3, w == 0 || p < 7);
        }
        signal(EV_Z1);
        TRC(tr, w, tb + 12);
      }
      uint32_t hA[18][4];
      {
        float acc[144];
        const float c0 = __uint_as_float(lds32(sb + SM_OFF + 4));
#pragma unroll
        for (int i = 0; i < 144; i++) {
          asm volatile("fma.rn.f32 %0, %1, %2, %3;" : "=f"(acc[i]) : "f"(__uint_as_float(P.zero)), "f"((float)(i + 2)), "f"(c0));
        }
        uint32_t prev = 0;
        auto stage = [&](int kb) {
          mbar_wait_c(bars + B_FULL + c.s * 8, c.ph);
          TRC(tr && kb == 0, w, tb + 13);
          SCLK(22 + kb);
          const uint32_t st = sb + c.s * ST_BYTES, rt = sb + SM_RT + kb * 128 + t * 8;
          uint64_t db = dsc2(dlo(st + ST_B, 4608), 0, 8 + P.zero);
          uint32_t a[4][4];
#pragma unroll
          for (int kk = 0; kk < 4; kk++) {
            uint32_t r[4];
            ldsm4(r, st + (aoff ^ (kk << 5)));
            const uint2 sc = lds64(rt + kk * 32);
            a[kk][0] = hmul2(__byte_perm(r[0], r[2], 0x5410), sc.x); a[kk][2] = hmul2(__byte_perm(r[0], r[2], 0x7632), sc.y);
            a[kk][1] = hmul2(__byte_perm(r[1], r[3], 0x5410), sc.x); a[kk][3] = hmul2(__byte_perm(r[1], r[3], 0x7632), sc.y);
          }
          if (LAG4 && (kb & 1) == (LAG4 & 1)) yield(32 - kb, LAG4);
          wgmma_fence();
#pragma unroll
          for (int i = 0; i < 8; i++) {
            const int kk = i & 3, hf = i >> 2;
            wgmma_rs_n144(acc + hf * 72, a[kk], db, 1);
            dadd(db, i == 3 ? 144u - 3 * 576 : 576 + P.zero);
            if (i == 0) { wgmma_commit(); wgmma_wait<1>(); release_if(kb, prev); }
            if (i == 3) wgmma_commit();
          }
          wgmma_commit();
          prev = c.s; c.next();
        };
        mbar_wait_c(bars + B_RT, L);
#pragma unroll 1
        for (int kb = 0; kb < 32; kb += 2) {
          if (kb == 8) mbar_wait_c(bars + B_RT1, L);
          MCLK((kb & 7) == 4, 10 + (kb >> 3));
          stage(kb);
          stage(kb + 1);
        }
        if (LAG4) { yield_done(); lagph ^= 1; }
        if (w == 1) bar_arrive(6, 256);
        HCLK(0);
        mbar_wait_c(bars + B_CV + w * 8, L);
        HCLK(1);
        const float gk = 0.5f / GA;
        const float c1 = __uint_as_float(lds32(sb + SM_OFF + 4));
        const float gb0 = -gk * (c1 + __uint_as_float(lds32(sb + SM_CV + w * 256 + (16 * q + g) * 4))), gb1 = -gk * (c1 + __uint_as_float(lds32(sb + SM_CV + w * 256 + (16 * q + g + 8) * 4)));
        mbar_wait_c(w ? bars + B_ZB : bars + B_FULL + c.s * 8, w ? L : c.ph);
        HCLK(2);
        const uint32_t sx = c.s;
        c.next();
        const uint32_t zt = sb + (tid & 127) * 16, zs0 = zt + sx * ST_BYTES + w * ZB, zs1 = w ? zt + SM_STG - 16384 : zs0, zs2 = w ? zt + c.s * ST_BYTES - 20480 : zs0;
#pragma unroll
        for (int u = 0; u < 18; u++) {
          if (u == 0) { wgmma_wait<1>(); HCLK(3); }
          if (u == 9) {
            HCLK(4);
            wgmma_wait<0>();
            HCLK(5);
            release(prev);
            if (L == 0) signal(EV_P4);
            if (w == 1) mbar_wait_c(bars + B_FULL + c.s * 8, c.ph);
            TRC(tr, w, tb + 14);
            SCLK(54);
          }
          const uint4 z = lds128((u < 8 ? zs0 : u < 10 ? zs1 : zs2) + u * 2048);
          hA[u][0] = hmul2(z.x, pack2(fmaf(acc[8 * u], gk, gb0), fmaf(acc[8 * u + 1], gk, gb0)));
          hA[u][1] = hmul2(z.y, pack2(fmaf(acc[8 * u + 2], gk, gb1), fmaf(acc[8 * u + 3], gk, gb1)));
          hA[u][2] = hmul2(z.z, pack2(fmaf(acc[8 * u + 4], gk, gb0), fmaf(acc[8 * u + 5], gk, gb0)));
          hA[u][3] = hmul2(z.w, pack2(fmaf(acc[8 * u + 6], gk, gb1), fmaf(acc[8 * u + 7], gk, gb1)));
        }
        uint32_t dep = P.zero;
#pragma unroll
        for (int u = 0; u < 18; u++) dep &= hA[u][0];
        release(sx, dep);
        TRC(tr, w, tb + 15);
        HCLK(6);
      }
      {
        CLK_INIT;
        uint32_t pk[16];
#pragma unroll
        for (int i = 0; i < 16; i++) pk[i] = 0u;
        auto dump = [&](int p) {
          const uint32_t d = sb + (p & 3) * ST_BYTES, cb = p + j >= 9 ? p + j - 9 : p + j;
          if (lane == 0) asm volatile("cp.async.bulk.wait_group.read 3;" ::: "memory");
          __syncwarp();
#pragma unroll
          for (int u = 0; u < 4; u++) stsm4(d + (aoff ^ (u << 5)), pk[4 * u], pk[4 * u + 1], pk[4 * u + 2], pk[4 * u + 3]);
          fence_async_s();
          __syncwarp();
          tma3d_red_p(lane == 0, &P.red[L], cb * 64, rb * 64 + q * 16, w, d + w * 8192 + q * 2048);
        };
#pragma unroll 1
        for (int p = 0; p < 9; p++) {
          float acc[32];
          CLK(0);
          mbar_wait_c(bars + B_FULL + c.s * 8, c.ph);
          uint64_t db = dsc2(dlo(sb + c.s * ST_BYTES + ST_B + (j & 1) * 4096, 0), 0, 0x40000040u + P.zero);
          CLK(1);
          HCLK(7 + 2 * p);
          bar_sync(6 + w, 256);
          CLK(2);
          wgmma_fence();
#pragma unroll
          for (int kk = 0; kk < 18; kk++) {
            wgmma_rs_n64(acc, hA[kk], db, kk != 0);
            dadd(db, kk == 15 ? 128 - (j & 1) * (36864 >> 4) : 128 + P.zero);
            if (kk == PPK && (w == 0 || p < 8)) bar_arrive(7 - w, 256);
          }
          wgmma_commit();
          CLK(3);
          if (p > 0) dump(p - 1);
          CLK(5);
          wgmma_wait<0>();
          CLK(4);
          HCLK(8 + 2 * p);
          MCLK(p == 1 || p == 8, 7 + (p >> 3));
          release_if(L == 0 || p < 5, c.s);
          c.next();
#pragma unroll
          for (int i = 0; i < 16; i++) pk[i] = pack2(acc[2 * i], acc[2 * i + 1]);
          if (p == 8) { TRC(tr, w, tb + 16); dump(8); TRC(tr, w, tb + 17); }
        }
        if (lane == 0) asm volatile("cp.async.bulk.wait_group 0;" ::: "memory");
        HCLK(25);
        MCLK(1, 9);
        if (L == 0) signal(EV_PT);
        CLK_OUT;
        TRC(tr, w, tb + 18);
      }
    }
    if ((tid & 127) == 0) g_flags[(rb * 2 + w) * 32 + FR_EP + j] = epoch + 1;
    if (tid == 0) g_flags[FJ + j * 32 + FJ_EP + rb] = epoch + 1;
  }
}

typedef CUresult (*EncodeFn)(CUtensorMap*, CUtensorMapDataType, cuuint32_t, void*, const cuuint64_t*, const cuuint64_t*, const cuuint32_t*,
                             const cuuint32_t*, CUtensorMapInterleave, CUtensorMapSwizzle, CUtensorMapL2promotion, CUtensorMapFloatOOBfill);

static void make_map(EncodeFn fn, CUtensorMap* m, const void* ptr, int rank, uint64_t d0, uint64_t d1, uint64_t d2, uint64_t s1, uint64_t s2,
                     uint32_t b0, uint32_t b1, uint32_t b2, CUtensorMapSwizzle swz) {
  cuuint64_t dims[3] = {d0, d1, d2}, strides[2] = {s1, s2};
  cuuint32_t box[3] = {b0, b1, b2}, es[3] = {1, 1, 1};
  fn(m, CU_TENSOR_MAP_DATA_TYPE_BFLOAT16, rank, const_cast<void*>(ptr), dims, strides, box, es, CU_TENSOR_MAP_INTERLEAVE_NONE, swz,
     CU_TENSOR_MAP_L2_PROMOTION_L2_128B, CU_TENSOR_MAP_FLOAT_OOB_FILL_NONE);
}

}

extern "C" void kernel_launch(void* const* d_in, const int* in_sizes, int n_in, void* d_out, int out_size) {
  using namespace mk;
  (void)in_sizes; (void)n_in; (void)out_size;
  static EncodeFn fn = nullptr;
  static uint8_t *wq, *xb;
  static float* csp;
  if (!fn) {
    cudaGetSymbolAddress((void**)&wq, g_WQ);
    cudaGetSymbolAddress((void**)&xb, g_X);
    cudaGetSymbolAddress((void**)&csp, g_CSP);
    cudaDriverEntryPointQueryResult qr;
    cudaGetDriverEntryPoint("cuTensorMapEncodeTiled", (void**)&fn, cudaEnableDefault, &qr);
    cudaFuncSetAttribute(mega_kernel, cudaFuncAttributeMaxDynamicSharedMemorySize, SM_TOTAL);
  }
  Params p;
  p.wqkv = (const __nv_bfloat16*)d_in[1];
  p.wo = (const __nv_bfloat16*)d_in[2];
  p.w_in = (const __nv_bfloat16*)d_in[4];
  p.w_sp = (const __nv_bfloat16*)d_in[5];
  p.b_sp = (const __nv_bfloat16*)d_in[6];
  p.w_out = (const __nv_bfloat16*)d_in[7];
  p.zero = 0;
  p.wq = wq;
  p.csp = csp;
  p.xs[0] = (uint8_t*)d_in[0];
  p.xs[1] = xb;
  p.xs[2] = (uint8_t*)d_out;
  make_map(fn, &p.wsp, p.w_sp, 3, 2048, 1024, 2, 8192, 4096, 64, 64, 2, CU_TENSOR_MAP_SWIZZLE_128B);
  for (int i = 0; i < 2; i++) {
    make_map(fn, &p.red[i], p.xs[i + 1], 3, DM, 1024, 2, 2304, 1152, 64, 16, 1, CU_TENSOR_MAP_SWIZZLE_128B);
    make_map(fn, &p.res[i], p.xs[i], 3, DM, 1024, 2, 2304, 1152, 144, 64, 1, CU_TENSOR_MAP_SWIZZLE_NONE);
  }
  make_map(fn, &p.psn, d_out, 3, DM, 1024, 2, 2304, 1152, 144, 4, 1, CU_TENSOR_MAP_SWIZZLE_NONE);
  for (int i = 0; i < 3; i++) make_map(fn, &p.act[i], p.xs[i], 3, DM, 1024, 2, 2304, 1152, 64, 64, 1, CU_TENSOR_MAP_SWIZZLE_128B);
  for (int i = 0; i < 2; i++) {
    cuuint64_t dims[4] = {i ? 4608u : 2304u, 8, i ? 1u : 2u, 72}, strides[3] = {9216, 4608, 8 * 9216};
    cuuint32_t box[4] = {i ? 64u : 32u, 8, i ? 1u : 2u, 18}, es[4] = {1, 1, 1, 1};
    fn(i ? &p.win64 : &p.win, CU_TENSOR_MAP_DATA_TYPE_BFLOAT16, 4, d_in[4], dims, strides, box, es, CU_TENSOR_MAP_INTERLEAVE_NONE,
       i ? CU_TENSOR_MAP_SWIZZLE_128B : CU_TENSOR_MAP_SWIZZLE_64B, CU_TENSOR_MAP_L2_PROMOTION_L2_128B, CU_TENSOR_MAP_FLOAT_OOB_FILL_NONE);
  }
  make_map(fn, &p.wout, p.w_out, 2, 576, 2304, 1, 1152, 0, 64, 144, 1, CU_TENSOR_MAP_SWIZZLE_128B);
  mega_kernel<<<NGRID, 384, SM_TOTAL, cudaStreamPerThread>>>(p);
}
```

```cpp
#include <cuda_runtime.h>
#include <cuda.h>
#include <cuda_bf16.h>
#include <stdint.h>

#define MK_TRACE 0
#define MK_DBG 0
#define P5TRACE 0
#define LAG1 2
#define PP3 32
#define PP30 33
#define LAG4 1
#define SPL 2
#define NAP 200
#define NAP0 8000
#define KS2 2
#define KS3 2
#define RL3 21
#define PAD 0
#define STF 1
#define GM2 3
#define GMM 1
#define GM1 2
#define C0S 32.f
#define OFM 0x10u
#define PPK 13

namespace mk {

constexpr int SEQ = 2048, DM = 576, FH = 2304;
constexpr int NCTA = 128;
constexpr int NGRID = 132;
constexpr uint32_t ZB = 36864;
constexpr uint32_t WQ_SL = 72 * 3456;
constexpr uint32_t WO_SL = 72 * 1152;
constexpr float LN_EPS = 1e-5f;
constexpr float GA = 0.3292034911525734f, GB = 2.423681954311584f;

constexpr uint32_t ST_BYTES = 53248, ST_B = 16384, NST = 4;
constexpr uint32_t SM_STG = NST * ST_BYTES;
constexpr uint32_t SM_BAR = SM_STG + 2 * 9216;
constexpr uint32_t SM_OFF = SM_BAR + 1008;
constexpr uint32_t SM_TOTAL = SM_BAR + 1024;
constexpr uint32_t SM_RT = SM_STG + 4096, SM_CV = SM_STG + 12288, SM_WT = SM_CV + 512;
constexpr uint32_t SM_WOI = 44032, SM_CSQ = 49280, SM_XST = 50176;
constexpr uint32_t B_FULL = 0, B_EMPTY = 32, B_FULLA = 64, B_RES = 128, B_WT = 144, B_IMG = 160, B_WOI = 168, B_ZB = 176, B_GATE3 = 184, B_Z1 = 192, B_LAG = 200,
                   B_RT = 208, B_CSQ = 216, B_CV = 224, B_AD = 240, B_EVT = 272, B_RT1 = 368, B_XRW = 384, B_FA3 = 400, B_EA3 = 544;
enum { EV_PT = 0, EV_O = 1, EV_X1 = 2, EV_ZN = 3, EV_Z1 = 4, EV_P4 = 5, EV_N = 6 };

enum { FR_X2 = 0, FR_O = 1, FR_X1 = 3, FR_EP = 16, FJ = 32 * 32, FJ_WQ = 0, FJ_WO = 1, FJ_WQ0 = 2, FJ_ZN = 3, FJ_P4 = 5, FJ_EP = 16, F_N = FJ + 8 * 32 };

__device__ __align__(1024) uint8_t g_Z[512 * ZB];
constexpr uint32_t POISON = 0xffffffffu;
__device__ __align__(1024) uint8_t g_O[32 * 2 * ZB];
__device__ __align__(1024) uint4 g_RD[NCTA * 36 * 256];
__device__ __align__(1024) uint8_t g_X[SEQ * DM * 2];
#define SLOW(i) do {} while (0)
__device__ __align__(1024) uint8_t g_WQ[8 * WQ_SL];
__device__ __align__(1024) uint8_t g_WO[8 * WO_SL];
__device__ __align__(1024) float g_CSP[2 * NCTA * 216];
__device__ __align__(1024) uint2 g_RT[SEQ];
__device__ __align__(1024) uint4 g_XST[2 * SEQ];
__device__ __align__(1024) uint4 g_ST1[SEQ * 8];
__device__ __align__(1024) uint4 g_ZST[SEQ * 8];
__device__ __align__(1024) uint4 g_HALO[32 * 8 * 6 * 32];
__device__ __align__(1024) uint32_t g_flags[F_N];

struct Params {
  const __nv_bfloat16 *wqkv;
  uint8_t* wq;
  float* csp;
  uint32_t zero;
  const __nv_bfloat16 *wo, *w_in, *w_sp, *b_sp, *w_out;
  uint8_t* xs[3];
  CUtensorMap wsp, win, win64, wout;
  CUtensorMap act[3];
  CUtensorMap res[2];
  CUtensorMap red[2];
  CUtensorMap psn;
};

__device__ __forceinline__ uint32_t smem_u32(const void* p) { return (uint32_t)__cvta_generic_to_shared(p); }
__device__ __forceinline__ void mbar_init(uint32_t bar, uint32_t cnt) { asm volatile("mbarrier.init.shared::cta.b64 [%0], %1;" ::"r"(bar), "r"(cnt)); }
__device__ __forceinline__ void mbar_arrive(uint32_t bar) { asm volatile("mbarrier.arrive.shared::cta.b64 _, [%0];" ::"r"(bar) : "memory"); }
__device__ __forceinline__ void mbar_wait(uint32_t bar, uint32_t parity) {
  asm volatile(
      "{\n.reg .pred p;\n.reg .u32 c;\nmov.u32 c, 0;\nLAB_WAIT:\n"
      "mbarrier.try_wait.parity.shared::cta.b64 p, [%0], %1;\n@p bra LAB_DONE;\n"
      "add.u32 c, c, 1;\nsetp.lt.u32 p, c, 0x100000;\n@p bra LAB_WAIT;\ntrap;\nLAB_DONE:\n}" ::"r"(bar), "r"(parity)
      : "memory");
}
__device__ __forceinline__ void mbar_wait_c(uint32_t bar, uint32_t parity) {
  asm volatile("{\n.reg .pred p;\nLAB_WAIT:\nmbarrier.try_wait.parity.shared::cta.b64 p, [%0], %1;\n@!p bra LAB_WAIT;\n}" ::"r"(bar), "r"(parity) : "memory");
}
__device__ __forceinline__ void flag_wait(const uint32_t* f, uint32_t target) {
  asm volatile(
      "{\n.reg .pred p;\n.reg .u32 c, v;\nmov.u32 c, 0;\nLAB_WAIT:\n"
      "ld.relaxed.gpu.global.u32 v, [%0];\nsub.u32 v, v, %1;\nsetp.ge.s32 p, v, 0;\n@p bra LAB_DONE;\n"
      "add.u32 c, c, 1;\nsetp.lt.u32 p, c, 0x400000;\n@p bra LAB_WAIT;\ntrap;\nLAB_DONE:\nfence.acquire.gpu;\n}" ::"l"(f), "r"(target)
      : "memory");
}
__device__ __forceinline__ void fence_gpu() { asm volatile("fence.acq_rel.gpu;" ::: "memory"); }
__device__ __forceinline__ void fence_async_g() { asm volatile("fence.proxy.async.global;" ::: "memory"); }
__device__ __forceinline__ void fence_async_s() { asm volatile("fence.proxy.async.shared::cta;" ::: "memory"); }
__device__ __forceinline__ uint32_t elect_one() {
  uint32_t p; asm volatile("{\n.reg .pred P;\nelect.sync _|P, 0xffffffff;\nselp.u32 %0, 1, 0, P;\n}" : "=r"(p)); return p;
}
__device__ __forceinline__ void expect_tx_p(uint32_t el, uint32_t bar, uint32_t bytes) {
  asm volatile("{\n.reg .pred P;\nsetp.ne.u32 P, %2, 0;\n@P mbarrier.arrive.expect_tx.shared::cta.b64 _, [%0], %1;\n}" ::"r"(bar), "r"(bytes), "r"(el) : "memory");
}
__device__ __forceinline__ void bulk_load_p(uint32_t el, uint32_t dst, const void* src, uint32_t bytes, uint32_t bar) {
  asm volatile("{\n.reg .pred P;\nsetp.ne.u32 P, %4, 0;\n@P cp.async.bulk.shared::cluster.global.mbarrier::complete_tx::bytes [%0], [%1], %2, [%3];\n}" ::"r"(dst), "l"(src), "r"(bytes), "r"(bar), "r"(el) : "memory");
}
__device__ __forceinline__ uint64_t policy_evict_first() { uint64_t p; asm("createpolicy.fractional.L2::evict_first.b64 %0, 1.0;" : "=l"(p)); return p; }
__device__ __forceinline__ void bulk_load_h(uint32_t el, uint32_t dst, const void* src, uint32_t bytes, uint32_t bar, bool ef, uint64_t pol) {
  if (ef) {
    asm volatile("{\n.reg .pred P;\nsetp.ne.u32 P, %4, 0;\n@P cp.async.bulk.shared::cluster.global.mbarrier::complete_tx::bytes.L2::cache_hint [%0], [%1], %2, [%3], %5;\n}" ::"r"(dst), "l"(src), "r"(bytes), "r"(bar), "r"(el), "l"(pol) : "memory");
  } else {
    asm volatile("{\n.reg .pred P;\nsetp.ne.u32 P, %4, 0;\n@P cp.async.bulk.shared::cluster.global.mbarrier::complete_tx::bytes [%0], [%1], %2, [%3];\n}" ::"r"(dst), "l"(src), "r"(bytes), "r"(bar), "r"(el) : "memory");
  }
}
__device__ __forceinline__ void bulk_mc_h(uint32_t el, uint32_t dst, const void* src, uint32_t bytes, uint32_t bar, bool ef, uint64_t pol) {
  if (ef) {
    asm volatile("{\n.reg .pred P;\nsetp.ne.u32 P, %4, 0;\n@P cp.async.bulk.shared::cluster.global.mbarrier::complete_tx::bytes.multicast::cluster.L2::cache_hint [%0], [%1], %2, [%3], %5, %6;\n}" ::"r"(dst), "l"(src), "r"(bytes), "r"(bar), "r"(el), "h"((uint16_t)3), "l"(pol) : "memory");
  } else {
    asm volatile("{\n.reg .pred P;\nsetp.ne.u32 P, %4, 0;\n@P cp.async.bulk.shared::cluster.global.mbarrier::complete_tx::bytes.multicast::cluster [%0], [%1], %2, [%3], %5;\n}" ::"r"(dst), "l"(src), "r"(bytes), "r"(bar), "r"(el), "h"((uint16_t)3) : "memory");
  }
}
__device__ __forceinline__ void tma3d_h(uint32_t el, uint32_t dst, const CUtensorMap* m, int c0, int c1, int c2, uint32_t bar, bool ef, uint64_t pol) {
  if (ef) {
    asm volatile("{\n.reg .pred P;\nsetp.ne.u32 P, %6, 0;\n@P cp.async.bulk.tensor.3d.shared::cluster.global.mbarrier::complete_tx::bytes.L2::cache_hint [%0], [%1, {%3, %4, %5}], [%2], %7;\n}" ::"r"(dst), "l"(m), "r"(bar), "r"(c0), "r"(c1), "r"(c2), "r"(el), "l"(pol) : "memory");
  } else {
    asm volatile("{\n.reg .pred P;\nsetp.ne.u32 P, %6, 0;\n@P cp.async.bulk.tensor.3d.shared::cluster.global.mbarrier::complete_tx::bytes [%0], [%1, {%3, %4, %5}], [%2];\n}" ::"r"(dst), "l"(m), "r"(bar), "r"(c0), "r"(c1), "r"(c2), "r"(el) : "memory");
  }
}
__device__ __forceinline__ void tma2d_mc_h(uint32_t el, uint32_t dst, const CUtensorMap* m, int c0, int c1, uint32_t bar, bool ef, uint64_t pol) {
  if (ef) {
    asm volatile("{\n.reg .pred P;\nsetp.ne.u32 P, %5, 0;\n@P cp.async.bulk.tensor.2d.shared::cluster.global.mbarrier::complete_tx::bytes.multicast::cluster.L2::cache_hint [%0], [%1, {%3, %4}], [%2], %6, %7;\n}" ::"r"(dst), "l"(m), "r"(bar), "r"(c0), "r"(c1), "r"(el), "h"((uint16_t)3), "l"(pol) : "memory");
  } else {
    asm volatile("{\n.reg .pred P;\nsetp.ne.u32 P, %5, 0;\n@P cp.async.bulk.tensor.2d.shared::cluster.global.mbarrier::complete_tx::bytes.multicast::cluster [%0], [%1, {%3, %4}], [%2], %6;\n}" ::"r"(dst), "l"(m), "r"(bar), "r"(c0), "r"(c1), "r"(el), "h"((uint16_t)3) : "memory");
  }
}
__device__ __forceinline__ void tma4d_mc(uint32_t el, uint32_t dst, const CUtensorMap* m, int c0, int c3, uint32_t bar, uint64_t pol) {
  asm volatile("{\n.reg .pred P;\nsetp.ne.u32 P, %5, 0;\n@P cp.async.bulk.tensor.4d.shared::cluster.global.mbarrier::complete_tx::bytes.multicast::cluster.L2::cache_hint [%0], [%1, {%3, 0, 0, %4}], [%2], %6, %7;\n}" ::"r"(dst), "l"(m), "r"(bar), "r"(c0), "r"(c3), "r"(el), "h"((uint16_t)3), "l"(pol) : "memory");
}
__device__ __forceinline__ void mbar_arrive_cluster(uint32_t addr) { asm volatile("mbarrier.arrive.shared::cluster.b64 _, [%0];" ::"r"(addr) : "memory"); }
__device__ __forceinline__ void mbar_arrive_cluster_if(bool c, uint32_t addr) {
  asm volatile("{\n.reg .pred P;\nsetp.ne.u32 P, %1, 0;\n@P mbarrier.arrive.shared::cluster.b64 _, [%0];\n}" ::"r"(addr), "r"((uint32_t)c) : "memory");
}
__device__ __forceinline__ void mbar_arrive_if(bool c, uint32_t addr) {
  asm volatile("{\n.reg .pred P;\nsetp.ne.u32 P, %1, 0;\n@P mbarrier.arrive.shared::cta.b64 _, [%0];\n}" ::"r"(addr), "r"((uint32_t)c) : "memory");
}
__device__ __forceinline__ uint32_t mapa(uint32_t addr, uint32_t rank) { uint32_t r; asm("mapa.shared::cluster.u32 %0, %1, %2;" : "=r"(r) : "r"(addr), "r"(rank)); return r; }
__device__ __forceinline__ void bulk_store_p(uint32_t el, void* dst, uint32_t src, uint32_t bytes) {
  asm volatile("{\n.reg .pred P;\nsetp.ne.u32 P, %3, 0;\n@P cp.async.bulk.global.shared::cta.bulk_group [%0], [%1], %2;\n}" ::"l"(dst), "r"(src), "r"(bytes), "r"(el) : "memory");
}
__device__ __forceinline__ void flag_release_p(uint32_t el, uint32_t* f) {
  asm volatile("{\n.reg .pred P;\nsetp.ne.u32 P, %1, 0;\n@P red.release.gpu.global.add.u32 [%0], 1;\n}" ::"l"(f), "r"(el) : "memory");
}
__device__ __forceinline__ void flag_add_p(uint32_t el, uint32_t* f) {
  asm volatile("{\n.reg .pred P;\nsetp.ne.u32 P, %1, 0;\n@P red.relaxed.gpu.global.add.u32 [%0], 1;\n}" ::"l"(f), "r"(el) : "memory");
}
__device__ __forceinline__ void prefetch_l2(const void* src, uint32_t bytes) { asm volatile("cp.async.bulk.prefetch.L2.global [%0], %1;" ::"l"(src), "r"(bytes) : "memory"); }
__device__ __forceinline__ void prefetch_map(const CUtensorMap* m) { asm volatile("prefetch.tensormap [%0];" ::"l"(m) : "memory"); }
__device__ __forceinline__ void wgmma_fence() { asm volatile("wgmma.fence.sync.aligned;" ::: "memory"); }
__device__ __forceinline__ void wgmma_commit() { asm volatile("wgmma.commit_group.sync.aligned;" ::: "memory"); }
template <int N> __device__ __forceinline__ void wgmma_wait() { asm volatile("wgmma.wait_group.sync.aligned %0;" ::"n"(N) : "memory"); }
__device__ __forceinline__ uint32_t dlo(uint32_t addr, uint32_t lbo) { return ((addr & 0x3FFFF) >> 4) + ((lbo >> 4) << 16); }
template <uint32_t SBO, uint32_t SWZ> __device__ __forceinline__ uint64_t dsc(uint32_t lo, uint32_t off) {
  uint64_t d; asm("mov.b64 %0, {%1, %2};" : "=l"(d) : "r"(lo + (off >> 4)), "n"((SBO >> 4) | (SWZ << 30))); return d;
}
__device__ __forceinline__ uint64_t dsc2(uint32_t lo, uint32_t off, uint32_t hi) {
  uint64_t d; asm("mov.b64 %0, {%1, %2};" : "=l"(d) : "r"(lo + (off >> 4)), "r"(hi)); return d;
}
__device__ __forceinline__ uint64_t dat(uint64_t d, uint32_t off, uint32_t one) { uint64_t r; asm("mad.wide.u32 %0, %1, %2, %3;" : "=l"(r) : "r"(one), "r"(off >> 4), "l"(d)); return r; }
__device__ __forceinline__ void dadd(uint64_t& d, uint32_t v) {
  asm("{\n.reg .b32 lo, hi;\nmov.b64 {lo, hi}, %0;\nadd.u32 lo, lo, %1;\nmov.b64 %0, {lo, hi};\n}" : "+l"(d) : "r"(v));
}
template <int R> __device__ __forceinline__ void reg_alloc() { asm volatile("setmaxnreg.inc.sync.aligned.u32 %0;" ::"n"(R)); }
template <int R> __device__ __forceinline__ void reg_dealloc() { asm volatile("setmaxnreg.dec.sync.aligned.u32 %0;" ::"n"(R)); }
__device__ __forceinline__ void bar_sync(int id, int n) { asm volatile("bar.sync %0, %1;" ::"r"(id), "r"(n) : "memory"); }
__device__ __forceinline__ void bar_arrive(int id, int n) { asm volatile("bar.arrive %0, %1;" ::"r"(id), "r"(n) : "memory"); }
__device__ __forceinline__ void ldsm4(uint32_t* r, uint32_t addr) {
  asm volatile("ldmatrix.sync.aligned.m8n8.x4.shared.b16 {%0,%1,%2,%3}, [%4];" : "=r"(r[0]), "=r"(r[1]), "=r"(r[2]), "=r"(r[3]) : "r"(addr) : "memory");
}
__device__ __forceinline__ uint32_t movm(uint32_t a) { uint32_t d; asm volatile("movmatrix.sync.aligned.m8n8.trans.b16 %0, %1;" : "=r"(d) : "r"(a)); return d; }
__device__ __forceinline__ void mma16(float* c, uint32_t a0, uint32_t a1, uint32_t a2, uint32_t a3, uint32_t b0, uint32_t b1) {
  asm volatile("mma.sync.aligned.m16n8k16.row.col.f32.bf16.bf16.f32 {%0,%1,%2,%3}, {%4,%5,%6,%7}, {%8,%9}, {%10,%10,%10,%10};"
               : "=f"(c[0]), "=f"(c[1]), "=f"(c[2]), "=f"(c[3]) : "r"(a0), "r"(a1), "r"(a2), "r"(a3), "r"(b0), "r"(b1), "f"(0.f));
}
__device__ __forceinline__ void mma8(float* c, uint32_t a0, uint32_t a1, uint32_t b0) {
  asm volatile("mma.sync.aligned.m16n8k8.row.col.f32.bf16.bf16.f32 {%0,%1,%2,%3}, {%4,%5}, {%6}, {%0,%1,%2,%3};"
               : "+f"(c[0]), "+f"(c[1]), "+f"(c[2]), "+f"(c[3]) : "r"(a0), "r"(a1), "r"(b0));
}
__device__ __forceinline__ uint32_t pack2(float lo, float hi) { uint32_t r; asm("cvt.rn.bf16x2.f32 %0, %1, %2;" : "=r"(r) : "f"(hi), "f"(lo)); return r; }
__device__ __forceinline__ float blo(uint32_t v) { return __uint_as_float(v << 16); }
__device__ __forceinline__ float bhi(uint32_t v) { return __uint_as_float(v & 0xffff0000u); }
__device__ __forceinline__ float tanh_fast(float x) { float y; asm("tanh.approx.f32 %0, %1;" : "=f"(y) : "f"(x)); return y; }
__device__ __forceinline__ float rcp_fast(float x) { float y; asm("rcp.approx.ftz.f32 %0, %1;" : "=f"(y) : "f"(x)); return y; }
__device__ __forceinline__ float ex2(float x) { float y; asm("ex2.approx.ftz.f32 %0, %1;" : "=f"(y) : "f"(x)); return y; }
__device__ __forceinline__ float qsum(float v) { v += __shfl_xor_sync(~0u, v, 1); v += __shfl_xor_sync(~0u, v, 2); return v; }
__device__ __forceinline__ float qmax(float v) { v = fmaxf(v, __shfl_xor_sync(~0u, v, 1)); v = fmaxf(v, __shfl_xor_sync(~0u, v, 2)); return v; }
__device__ __forceinline__ void stg32(void* p, uint32_t v) { asm volatile("st.global.u32 [%0], %1;" ::"l"(p), "r"(v) : "memory"); }
__device__ __forceinline__ void stg128(void* p, uint32_t a, uint32_t b, uint32_t c, uint32_t d) { asm volatile("st.global.v4.u32 [%0], {%1,%2,%3,%4};" ::"l"(p), "r"(a), "r"(b), "r"(c), "r"(d) : "memory"); }
__device__ __forceinline__ uint32_t ldcg32(const void* p) { uint32_t v; asm volatile("ld.global.L1::no_allocate.u32 %0, [%1];" : "=r"(v) : "l"(p) : "memory"); return v; }
__device__ __forceinline__ uint32_t ldgpu32(const void* p) { uint32_t v; asm volatile("ld.relaxed.gpu.global.u32 %0, [%1];" : "=r"(v) : "l"(p) : "memory"); return v; }
__device__ __forceinline__ uint32_t ldca32(const void* p) { uint32_t v; asm volatile("ld.global.ca.u32 %0, [%1];" : "=r"(v) : "l"(p) : "memory"); return v; }
__device__ __forceinline__ void stg128_if(bool c, void* p, uint32_t a, uint32_t b, uint32_t cc, uint32_t d) {
  asm volatile("{\n.reg .pred P;\nsetp.ne.u32 P, %5, 0;\n@P st.global.v4.u32 [%0], {%1,%2,%3,%4};\n}" ::"l"(p), "r"(a), "r"(b), "r"(cc), "r"(d), "r"((uint32_t)c) : "memory");
}
__device__ __forceinline__ uint2 lds64(uint32_t a) { uint2 v; asm volatile("ld.shared.v2.u32 {%0,%1}, [%2];" : "=r"(v.x), "=r"(v.y) : "r"(a) : "memory"); return v; }
__device__ __forceinline__ uint4 ldcg128(const void* p) { uint4 v; asm volatile("ld.global.cg.v4.u32 {%0,%1,%2,%3}, [%4];" : "=r"(v.x), "=r"(v.y), "=r"(v.z), "=r"(v.w) : "l"(p) : "memory"); return v; }
__device__ __forceinline__ uint32_t ldnc16(const void* p) { uint16_t v; asm volatile("ld.global.nc.u16 %0, [%1];" : "=h"(v) : "l"(p)); return v; }
__device__ __forceinline__ uint4 ldnc128(const void* p) { uint4 v; asm volatile("ld.global.nc.v4.u32 {%0,%1,%2,%3}, [%4];" : "=r"(v.x), "=r"(v.y), "=r"(v.z), "=r"(v.w) : "l"(p)); return v; }
__device__ __forceinline__ void cp_async16(uint32_t dst, const void* src) { asm volatile("cp.async.cg.shared.global [%0], [%1], 16;" ::"r"(dst), "l"(src) : "memory"); }
__device__ __forceinline__ uint32_t hsub2(uint32_t a, uint32_t b) { uint32_t d; asm("sub.rn.bf16x2 %0, %1, %2;" : "=r"(d) : "r"(a), "r"(b)); return d; }
__device__ __forceinline__ void stg32_if(bool c, void* p, uint32_t v) {
  asm volatile("{\n.reg .pred P;\nsetp.ne.u32 P, %2, 0;\n@P st.global.u32 [%0], %1;\n}" ::"l"(p), "r"(v), "r"((uint32_t)c) : "memory");
}
__device__ __forceinline__ float wsum(float v) { for (int o = 16; o; o >>= 1) v += __shfl_xor_sync(~0u, v, o); return v; }
__device__ __forceinline__ uint32_t hmul2(uint32_t a, uint32_t b) { uint32_t d; asm("mul.rn.bf16x2 %0, %1, %2;" : "=r"(d) : "r"(a), "r"(b)); return d; }
__device__ __forceinline__ void sts32(uint32_t a, uint32_t v) { asm volatile("st.shared.u32 [%0], %1;" ::"r"(a), "r"(v) : "memory"); }
__device__ __forceinline__ uint32_t lds32(uint32_t a) { uint32_t v; asm volatile("ld.shared.u32 %0, [%1];" : "=r"(v) : "r"(a) : "memory"); return v; }
__device__ __forceinline__ void sts128(uint32_t a, uint32_t x, uint32_t y, uint32_t z, uint32_t w) { asm volatile("st.shared.v4.u32 [%0], {%1,%2,%3,%4};" ::"r"(a), "r"(x), "r"(y), "r"(z), "r"(w) : "memory"); }
__device__ __forceinline__ uint4 lds128(uint32_t a) { uint4 v; asm volatile("ld.shared.v4.u32 {%0,%1,%2,%3}, [%4];" : "=r"(v.x), "=r"(v.y), "=r"(v.z), "=r"(v.w) : "r"(a) : "memory"); return v; }
__device__ __forceinline__ void ll_st64(uint2* p, uint32_t v, uint32_t tag) {
  asm volatile("{\n.reg .b64 r;\nmov.b64 r, {%1,%2};\nst.relaxed.gpu.global.b64 [%0], r;\n}" ::"l"(p), "r"(v), "r"(tag) : "memory");
}
__device__ __forceinline__ uint2 ll_ld64(const uint2* p) {
  uint2 v; asm volatile("{\n.reg .b64 r;\nld.relaxed.gpu.global.b64 r, [%2];\nmov.b64 {%0,%1}, r;\n}" : "=r"(v.x), "=r"(v.y) : "l"(p) : "memory"); return v;
}
__device__ __forceinline__ void ll_st128(uint4* p, float a, float b, uint32_t tag, float c = 0.f) {
  asm volatile("{\n.reg .b128 r;\n.reg .b64 lo, hi;\nmov.b64 lo, {%1,%2};\nmov.b64 hi, {%3,%4};\nmov.b128 r, {lo, hi};\nst.relaxed.gpu.global.b128 [%0], r;\n}" ::"l"(p), "r"(__float_as_uint(a)), "r"(__float_as_uint(b)), "r"(tag), "r"(__float_as_uint(c)) : "memory");
}
__device__ __forceinline__ uint4 ll_ld128(const uint4* p) {
  uint4 v; asm volatile("{\n.reg .b128 r;\n.reg .b64 lo, hi;\nld.relaxed.gpu.global.b128 r, [%4];\nmov.b128 {lo, hi}, r;\nmov.b64 {%0,%1}, lo;\nmov.b64 {%2,%3}, hi;\n}" : "=r"(v.x), "=r"(v.y), "=r"(v.z), "=r"(v.w) : "l"(p) : "memory"); return v;
}
__device__ __forceinline__ void publish_p(uint32_t el, uint32_t* f) {
  asm volatile("{\n.reg .pred P;\nsetp.ne.u32 P, %1, 0;\n@P cp.async.bulk.commit_group;\n@P cp.async.bulk.wait_group 0;\n@P red.release.gpu.global.add.u32 [%0], 1;\n}" ::"l"(f), "r"(el) : "memory");
}
__device__ __forceinline__ void tma3d_red_p(uint32_t el, const CUtensorMap* m, int c0, int c1, int c2, uint32_t src) {
  asm volatile("{\n.reg .pred P;\nsetp.ne.u32 P, %5, 0;\n@P cp.reduce.async.bulk.tensor.3d.global.shared::cta.add.tile.bulk_group [%0, {%2, %3, %4}], [%1];\n@P cp.async.bulk.commit_group;\n}" ::"l"(m), "r"(src), "r"(c0), "r"(c1), "r"(c2), "r"(el) : "memory");
}
__device__ __forceinline__ void stsm4(uint32_t addr, uint32_t a, uint32_t b, uint32_t c, uint32_t d) {
  asm volatile("stmatrix.sync.aligned.m8n8.x4.shared.b16 [%0], {%1,%2,%3,%4};" ::"r"(addr), "r"(a), "r"(b), "r"(c), "r"(d) : "memory");
}
__device__ __forceinline__ void sts64(uint32_t a, uint32_t x, uint32_t y) { asm volatile("st.shared.v2.u32 [%0], {%1,%2};" ::"r"(a), "r"(x), "r"(y) : "memory"); }
__device__ __forceinline__ void ll_st128_if(bool on, uint4* p, float a, float b, uint32_t tag) {
  asm volatile("{\n.reg .pred P;\n.reg .b128 r;\n.reg .b64 lo, hi;\nsetp.ne.u32 P, %4, 0;\nmov.b64 lo, {%1,%2};\nmov.b64 hi, {%3,%3};\nmov.b128 r, {lo, hi};\n@P st.relaxed.gpu.global.b128 [%0], r;\n}" ::"l"(p), "r"(__float_as_uint(a)), "r"(__float_as_uint(b)), "r"(tag), "r"((uint32_t)on) : "memory");
}
__device__ __forceinline__ uint4 ldnc128_if(bool c, const void* p) {
  uint4 v = make_uint4(0u, 0u, 0u, 0u);
  asm volatile("{\n.reg .pred P;\nsetp.ne.u32 P, %5, 0;\n@P ld.global.nc.v4.u32 {%0,%1,%2,%3}, [%4];\n}" : "+r"(v.x), "+r"(v.y), "+r"(v.z), "+r"(v.w) : "l"(p), "r"((uint32_t)c));
  return v;
}
__device__ __forceinline__ uint32_t hfma2(uint32_t a, uint32_t b, uint32_t c) { uint32_t d; asm("fma.rn.bf16x2 %0, %1, %2, %3;" : "=r"(d) : "r"(a), "r"(b), "r"(c)); return d; }
__device__ __forceinline__ float2 lds64f(uint32_t a) { float2 v; asm volatile("ld.shared.v2.f32 {%0,%1}, [%2];" : "=f"(v.x), "=f"(v.y) : "r"(a) : "memory"); return v; }
#define TRC(cond, role, idx) do {} while (0)
#define TRV(role, idx, v) do {} while (0)

#define ACLK_INIT do {} while (0)
#define ACLK(i) do {} while (0)
#define ACLK_OUT do {} while (0)
#define QCLK(i) do {} while (0)
#define PH 1
#define RCLK(i) do {} while (0)
#define RCLK_INIT do {} while (0)
#define RCLK_OUT do {} while (0)
#define SCLK(i) do {} while (0)
#define HCLK(i) do {} while (0)
#define MCLK(c, i) do {} while (0)
#define CKK(i) do {} while (0)
#define CKK_OUT do {} while (0)
#define PL 1
#define PCLK(i) do {} while (0)
#define PQ 1
#define CLK_INIT do {} while (0)
#define CLK(i) do {} while (0)
#define CLK_OUT do {} while (0)

__device__ __forceinline__ void wgmma_ss_n216(float* d, uint64_t da, uint64_t db, int scaleD) {
  asm volatile("{\n.reg .pred p;\nsetp.ne.b32 p, %110, 0;\nwgmma.mma_async.sync.aligned.m64n216k16.f32.bf16.bf16 "
    "{%0,%1,%2,%3,%4,%5,%6,%7,%8,%9,%10,%11,%12,%13,%14,%15,%16,%17,%18,%19,%20,%21,%22,%23,%24,%25,%26,%27,%28,%29,%30,%31,%32,%33,%34,%35,%36,%37,%38,%39,%40,%41,%42,%43,%44,%45,%46,%47,%48,%49,%50,%51,%52,%53,%54,%55,%56,%57,%58,%59,%60,%61,%62,%63,%64,%65,%66,%67,%68,%69,%70,%71,%72,%73,%74,%75,%76,%77,%78,%79,%80,%81,%82,%83,%84,%85,%86,%87,%88,%89,%90,%91,%92,%93,%94,%95,%96,%97,%98,%99,%100,%101,%102,%103,%104,%105,%106,%107}, "
    "%108, %109, p, 1, 1, 0, 1;\n}\n"
    : "+f"(d[0]), "+f"(d[1]), "+f"(d[2]), "+f"(d[3]), "+f"(d[4]), "+f"(d[5]), "+f"(d[6]), "+f"(d[7]), "+f"(d[8]), "+f"(d[9]), "+f"(d[10]), "+f"(d[11]), "+f"(d[12]), "+f"(d[13]), "+f"(d[14]), "+f"(d[15]), "+f"(d[16]), "+f"(d[17]), "+f"(d[18]), "+f"(d[19]), "+f"(d[20]), "+f"(d[21]), "+f"(d[22]), "+f"(d[23]), "+f"(d[24]), "+f"(d[25]), "+f"(d[26]), "+f"(d[27]), "+f"(d[28]), "+f"(d[29]), "+f"(d[30]), "+f"(d[31]), "+f"(d[32]), "+f"(d[33]), "+f"(d[34]), "+f"(d[35]), "+f"(d[36]), "+f"(d[37]), "+f"(d[38]), "+f"(d[39]), "+f"(d[40]), "+f"(d[41]), "+f"(d[42]), "+f"(d[43]), "+f"(d[44]), "+f"(d[45]), "+f"(d[46]), "+f"(d[47]), "+f"(d[48]), "+f"(d[49]), "+f"(d[50]), "+f"(d[51]), "+f"(d[52]), "+f"(d[53]), "+f"(d[54]), "+f"(d[55]), "+f"(d[56]), "+f"(d[57]), "+f"(d[58]), "+f"(d[59]), "+f"(d[60]), "+f"(d[61]), "+f"(d[62]), "+f"(d[63]), "+f"(d[64]), "+f"(d[65]), "+f"(d[66]), "+f"(d[67]), "+f"(d[68]), "+f"(d[69]), "+f"(d[70]), "+f"(d[71]), "+f"(d[72]), "+f"(d[73]), "+f"(d[74]), "+f"(d[75]), "+f"(d[76]), "+f"(d[77]), "+f"(d[78]), "+f"(d[79]), "+f"(d[80]), "+f"(d[81]), "+f"(d[82]), "+f"(d[83]), "+f"(d[84]), "+f"(d[85]), "+f"(d[86]), "+f"(d[87]), "+f"(d[88]), "+f"(d[89]), "+f"(d[90]), "+f"(d[91]), "+f"(d[92]), "+f"(d[93]), "+f"(d[94]), "+f"(d[95]), "+f"(d[96]), "+f"(d[97]), "+f"(d[98]), "+f"(d[99]), "+f"(d[100]), "+f"(d[101]), "+f"(d[102]), "+f"(d[103]), "+f"(d[104]), "+f"(d[105]), "+f"(d[106]), "+f"(d[107])
    : "l"(da), "l"(db), "r"(scaleD));
}
__device__ __forceinline__ void wgmma_ss_n72(float* d, uint64_t da, uint64_t db, int scaleD) {
  asm volatile("{\n.reg .pred p;\nsetp.ne.b32 p, %38, 0;\nwgmma.mma_async.sync.aligned.m64n72k16.f32.bf16.bf16 "
    "{%0,%1,%2,%3,%4,%5,%6,%7,%8,%9,%10,%11,%12,%13,%14,%15,%16,%17,%18,%19,%20,%21,%22,%23,%24,%25,%26,%27,%28,%29,%30,%31,%32,%33,%34,%35}, "
    "%36, %37, p, 1, 1, 0, 1;\n}\n"
    : "+f"(d[0]), "+f"(d[1]), "+f"(d[2]), "+f"(d[3]), "+f"(d[4]), "+f"(d[5]), "+f"(d[6]), "+f"(d[7]), "+f"(d[8]), "+f"(d[9]), "+f"(d[10]), "+f"(d[11]), "+f"(d[12]), "+f"(d[13]), "+f"(d[14]), "+f"(d[15]), "+f"(d[16]), "+f"(d[17]), "+f"(d[18]), "+f"(d[19]), "+f"(d[20]), "+f"(d[21]), "+f"(d[22]), "+f"(d[23]), "+f"(d[24]), "+f"(d[25]), "+f"(d[26]), "+f"(d[27]), "+f"(d[28]), "+f"(d[29]), "+f"(d[30]), "+f"(d[31]), "+f"(d[32]), "+f"(d[33]), "+f"(d[34]), "+f"(d[35])
    : "l"(da), "l"(db), "r"(scaleD));
}
__device__ __forceinline__ void wgmma_rs_n144(float* d, const uint32_t* a, uint64_t db, int scaleD) {
  asm volatile("{\n.reg .pred p;\nsetp.ne.b32 p, %77, 0;\nwgmma.mma_async.sync.aligned.m64n144k16.f32.bf16.bf16 "
    "{%0,%1,%2,%3,%4,%5,%6,%7,%8,%9,%10,%11,%12,%13,%14,%15,%16,%17,%18,%19,%20,%21,%22,%23,%24,%25,%26,%27,%28,%29,%30,%31,%32,%33,%34,%35,%36,%37,%38,%39,%40,%41,%42,%43,%44,%45,%46,%47,%48,%49,%50,%51,%52,%53,%54,%55,%56,%57,%58,%59,%60,%61,%62,%63,%64,%65,%66,%67,%68,%69,%70,%71}, "
    "{%72,%73,%74,%75}, %76, p, 1, 1, 1;\n}\n"
    : "+f"(d[0]), "+f"(d[1]), "+f"(d[2]), "+f"(d[3]), "+f"(d[4]), "+f"(d[5]), "+f"(d[6]), "+f"(d[7]), "+f"(d[8]), "+f"(d[9]), "+f"(d[10]), "+f"(d[11]), "+f"(d[12]), "+f"(d[13]), "+f"(d[14]), "+f"(d[15]), "+f"(d[16]), "+f"(d[17]), "+f"(d[18]), "+f"(d[19]), "+f"(d[20]), "+f"(d[21]), "+f"(d[22]), "+f"(d[23]), "+f"(d[24]), "+f"(d[25]), "+f"(d[26]), "+f"(d[27]), "+f"(d[28]), "+f"(d[29]), "+f"(d[30]), "+f"(d[31]), "+f"(d[32]), "+f"(d[33]), "+f"(d[34]), "+f"(d[35]), "+f"(d[36]), "+f"(d[37]), "+f"(d[38]), "+f"(d[39]), "+f"(d[40]), "+f"(d[41]), "+f"(d[42]), "+f"(d[43]), "+f"(d[44]), "+f"(d[45]), "+f"(d[46]), "+f"(d[47]), "+f"(d[48]), "+f"(d[49]), "+f"(d[50]), "+f"(d[51]), "+f"(d[52]), "+f"(d[53]), "+f"(d[54]), "+f"(d[55]), "+f"(d[56]), "+f"(d[57]), "+f"(d[58]), "+f"(d[59]), "+f"(d[60]), "+f"(d[61]), "+f"(d[62]), "+f"(d[63]), "+f"(d[64]), "+f"(d[65]), "+f"(d[66]), "+f"(d[67]), "+f"(d[68]), "+f"(d[69]), "+f"(d[70]), "+f"(d[71])
    : "r"(a[0]), "r"(a[1]), "r"(a[2]), "r"(a[3]), "l"(db), "r"(scaleD));
}
__device__ __forceinline__ void wgmma_rs_n64(float* d, const uint32_t* a, uint64_t db, int scaleD) {
  asm volatile("{\n.reg .pred p;\nsetp.ne.b32 p, %37, 0;\nwgmma.mma_async.sync.aligned.m64n64k16.f32.bf16.bf16 "
    "{%0,%1,%2,%3,%4,%5,%6,%7,%8,%9,%10,%11,%12,%13,%14,%15,%16,%17,%18,%19,%20,%21,%22,%23,%24,%25,%26,%27,%28,%29,%30,%31}, "
    "{%32,%33,%34,%35}, %36, p, 1, 1, 1;\n}\n"
    : "+f"(d[0]), "+f"(d[1]), "+f"(d[2]), "+f"(d[3]), "+f"(d[4]), "+f"(d[5]), "+f"(d[6]), "+f"(d[7]), "+f"(d[8]), "+f"(d[9]), "+f"(d[10]), "+f"(d[11]), "+f"(d[12]), "+f"(d[13]), "+f"(d[14]), "+f"(d[15]), "+f"(d[16]), "+f"(d[17]), "+f"(d[18]), "+f"(d[19]), "+f"(d[20]), "+f"(d[21]), "+f"(d[22]), "+f"(d[23]), "+f"(d[24]), "+f"(d[25]), "+f"(d[26]), "+f"(d[27]), "+f"(d[28]), "+f"(d[29]), "+f"(d[30]), "+f"(d[31])
    : "r"(a[0]), "r"(a[1]), "r"(a[2]), "r"(a[3]), "l"(db), "r"(scaleD));
}

template <int V> struct Int { static constexpr int value = V; };
struct Cur {
  uint32_t s, ph;
  __device__ __forceinline__ void next() { if (++s == NST) { s = 0; ph ^= 1; } }
};

__device__ __forceinline__ uint8_t* z1_block(int rb, int w, int j) { return g_Z + (rb * 16 + w * 8 + j) * ZB; }
__device__ __forceinline__ uint8_t* o_block(int rb, int w) { return g_O + (rb * 2 + w) * (2 * ZB); }
__device__ __forceinline__ uint8_t* z2_block(int kb, int j) { return g_Z + (256 + kb * 8 + j) * ZB; }
__device__ __forceinline__ void combine8(float m0, float q0, float m1, float q1, float n, float eps, float& mean, float& rstd) {
  mean = qsum(m0 + m1) * 0.125f;
  float d0 = m0 - mean, d1 = m1 - mean;
  float M2 = qsum(q0 + q1 + n * (d0 * d0 + d1 * d1));
  rstd = rsqrtf(fmaf(M2, 0.125f / n, eps));
}
__device__ __forceinline__ void stat_get(const uint4* zs, uint32_t tag, float n, float eps, float& m0, float& r0, float& m1, float& r1) {
  uint4 a0, a1, b0, b1;
#pragma unroll 1
  for (int it = 0; it < (1 << 20); it++) {
    a0 = ll_ld128(zs); a1 = ll_ld128(zs + 64); b0 = ll_ld128(zs + 8); b1 = ll_ld128(zs + 72);
    if (__all_sync(~0u, a0.z == tag && a1.z == tag && b0.z == tag && b1.z == tag)) break;
  }
  combine8(__uint_as_float(a0.x), __uint_as_float(a0.y), __uint_as_float(a1.x), __uint_as_float(a1.y), n, eps, m0, r0);
  combine8(__uint_as_float(b0.x), __uint_as_float(b0.y), __uint_as_float(b1.x), __uint_as_float(b1.y), n, eps, m1, r1);
}

__device__ __forceinline__ void rows_fetch(uint32_t el, uint32_t xr, const uint8_t* src, uint32_t bar) {
  expect_tx_p(el, bar, 9216);
#pragma unroll 1
  for (int r = 0; r < 8; r++) bulk_load_p(el, xr + r * 1152, src + r * (DM * 4), 1152, bar);
}
__device__ __forceinline__ void rows_stats(uint32_t xr, uint4* dst, uint32_t tag, int lane) {
  float s[2] = {0.f, 0.f}, q[4] = {0.f, 0.f, 0.f, 0.f};
  const uint32_t a0 = xr + (lane >> 2) * 1152 + (((lane & 3) * 2) ^ (lane >> 2)) * 16;
  uint4 n0 = lds128(a0), n1 = lds128(a0 ^ 16);
#pragma unroll 1
  for (int e = 1; e <= 9; e++) {
    const uint32_t x[8] = {n0.x, n0.y, n0.z, n0.w, n1.x, n1.y, n1.z, n1.w};
    if (e < 9) { n0 = lds128(a0 + e * 128); n1 = lds128((a0 ^ 16) + e * 128); }
#pragma unroll
    for (int u = 0; u < 8; u++) {
      const float lo = blo(x[u]), hi = bhi(x[u]);
      s[u & 1] += lo + hi; q[(u & 1) * 2] = fmaf(lo, lo, q[(u & 1) * 2]); q[(u & 1) * 2 + 1] = fmaf(hi, hi, q[(u & 1) * 2 + 1]);
    }
  }
  const float sx = s[0] + s[1], sq = (q[0] + q[1]) + (q[2] + q[3]);
  const float m = qsum(sx) * (-1.f / DM), r = rsqrtf(fmaxf(fmaf(qsum(sq), 1.f / DM, -m * m), 0.f) + LN_EPS);
  if ((lane & 3) == 0) ll_st128(dst + (lane >> 2) * 2, m, r, tag);
}

__device__ __forceinline__ void poison(uint32_t el, uint32_t src, const CUtensorMap* m, int rb, int j, int lane) {
#pragma unroll 1
  for (int u = lane; u < 72; u += 32) sts128(src + u * 16, POISON, POISON, POISON, POISON);
  fence_async_s();
  __syncwarp();
#pragma unroll 1
  for (int u = 0; u < 16; u++) {
    __nanosleep(NAP);
    bulk_store_p(el, o_block(rb, u >> 3) + j * 9216 + (u & 7) * 1152, src, 1152);
    asm volatile("{\n.reg .pred P;\nsetp.ne.u32 P, %5, 0;\n@P cp.async.bulk.tensor.3d.global.shared::cta.tile.bulk_group [%0, {%2, %3, %4}], [%1];\n}" ::"l"(m), "r"(src), "r"((j & 6) * 72), "r"(rb * 64 + u * 4), "r"(j & 1), "r"(el) : "memory");
  }
}
__device__ __forceinline__ void mma16acc(float* c, const uint32_t* a, uint32_t b0, uint32_t b1) {
  asm volatile("mma.sync.aligned.m16n8k16.row.col.f32.bf16.bf16.f32 {%0,%1,%2,%3}, {%4,%5,%6,%7}, {%8,%9}, {%0,%1,%2,%3};"
               : "+f"(c[0]), "+f"(c[1]), "+f"(c[2]), "+f"(c[3]) : "r"(a[0]), "r"(a[1]), "r"(a[2]), "r"(a[3]), "r"(b0), "r"(b1));
}
template <int KS, int NG, int AK, int AH, int BK, int BG, class F> __device__ __forceinline__ void redo(float* acc, const uint8_t* pa, const uint8_t* pb, F f) {
#pragma unroll 1
  for (int k = 0; k < 36; k += KS) {
    uint32_t a[4 * KS], b[2 * KS][NG];
#pragma unroll 1
    for (int it = 0; it < (1 << 20); it++) {
      bool ok = true;
#pragma unroll
      for (int e = 0; e < 4 * KS; e++) a[e] = ldgpu32(pa + (e >> 1) * AK + (e & 1) * AH);
#pragma unroll
      for (int e = 0; e < 2 * KS * NG; e++) b[e / NG][e % NG] = ldca32(pb + (e / NG) * BK + (e % NG) * BG);
#pragma unroll
      for (int e = 0; e < 4 * KS; e++) ok = ok && a[e] != POISON;
      if (__all_sync(~0u, ok)) break;
    }
#pragma unroll
    for (int e = 0; e < KS; e++) f(a + 4 * e, k + e);
#pragma unroll
    for (int e = 0; e < KS * NG; e++) mma16acc(acc + 4 * (e % NG), a + 4 * (e / NG), movm(b[2 * (e / NG)][e % NG]), movm(b[2 * (e / NG) + 1][e % NG]));
    pa += 2 * KS * AK; pb += 2 * KS * BK;
  }
}
__device__ __forceinline__ bool any_nan(float a, float b) {
  return __any_sync(~0u, a != a || b != b);
}

__global__ void __cluster_dims__(2, 1, 1) __launch_bounds__(384, 1) mega_kernel(const __grid_constant__ Params P) {
  extern __shared__ __align__(1024) uint8_t smem_raw[];
  uint32_t ckk[8];
  (void)ckk;
  CKK(0);
  const uint32_t sb = smem_u32(smem_raw);
  const uint32_t bars = sb + SM_BAR;
  const int tid = threadIdx.x;
  int lane = tid & 31;
  const int wid = __shfl_sync(~0u, tid >> 5, 0);
  const int cl = blockIdx.x >> 1, tp = cl - 36, t7 = (tp * 37) >> 8;
  const int bid = (cl < 4 ? cl * 8 + 32 : tp < 0 ? cl - 4 : cl < 64 ? tp + t7 + 33 : cl) * 2 + (blockIdx.x & 1);
  if (bid >= NCTA) return;
  const int rb = bid & 15, j = bid >> 4;
  { const bool tr = (tid & 127) == 0 && tid < 256; const int w = tid >> 7; (void)tr; (void)w; TRC(tr, w, 0); }
  CKK(1);
  uint4 wv[5];
  const uint8_t* wsrc;
  {
    const int n8 = min(tid >> 3, 26), part = n8 / 9;
    const uint8_t* src = (const uint8_t*)P.wqkv + (8 * rb + (tid & 7)) * (3 * DM * 2) + (part * (DM - 72) + 72 * j + 8 * n8) * 2;
#pragma unroll
    for (int u = 0; u < SPL; u++) wv[u] = ldnc128_if(tid < 216, src + u * (128 * 3 * DM * 2));
    wsrc = src;
  }
  CKK(2);
  if (tid == 352) {
    for (int s = 0; s < (int)NST; s++) {
      mbar_init(bars + B_FULL + s * 8, 1); mbar_init(bars + B_EMPTY + s * 8, 16);
      mbar_init(bars + B_FULLA + s * 8, 1); mbar_init(bars + B_FULLA + 32 + s * 8, 1);
      mbar_init(bars + B_RES + s * 8, 1); mbar_init(bars + B_RT + s * 8, 1); mbar_init(bars + B_AD + s * 8, 2);
    }
    mbar_init(bars + B_IMG, 8); mbar_init(bars + B_RES + 8, 8); mbar_init(bars + B_WOI, 8); mbar_init(bars + B_GATE3, 3); mbar_init(bars + B_Z1, 1); mbar_init(bars + B_ZB, 1); mbar_init(bars + B_LAG, 4);
    mbar_init(bars + B_CSQ, 3); mbar_init(bars + B_RT1, 1); mbar_init(bars + B_XRW, 1); mbar_init(bars + B_XRW + 8, 1);
    for (int e = 0; e < 2 * EV_N; e++) mbar_init(bars + B_EVT + e * 8, 4);
    asm volatile("fence.mbarrier_init.release.cluster;" ::: "memory");
  }
  if (tid == 320) {
#pragma unroll
    for (int e = 0; e < 28; e++) mbar_init(bars + B_FA3 + e * 8, e < 18 ? 1 : 4);
    asm volatile("fence.mbarrier_init.release.cluster;" ::: "memory");
  }
  __syncthreads();

  if (wid >= 8) {
    reg_dealloc<40>();
    const uint32_t el = elect_one();
    const uint64_t pol = policy_evict_first();
    uint32_t* const fj = g_flags + FJ + j * 32;
    if (wid == 8) {
      if (el) { prefetch_map(&P.act[0]); prefetch_map(&P.wsp); prefetch_map(&P.win); prefetch_map(&P.win64); prefetch_map(&P.wout); prefetch_map(&P.act[1]); prefetch_map(&P.res[0]); prefetch_map(&P.res[1]); prefetch_map(&P.red[0]); prefetch_map(&P.red[1]); prefetch_map(&P.act[2]); }
      const uint32_t epoch = ldcg32(fj + FJ_EP + rb);
      Cur c{0, 1};
      const uint32_t rk = bid & 1;
      uint32_t st, full;
      auto slot = [&](uint32_t bytes) {
        st = sb + c.s * ST_BYTES; full = bars + B_FULL + c.s * 8;
        mbar_wait(full, c.ph);
        expect_tx_p(el, full, bytes);
        mbar_wait(full - B_FULL + B_EMPTY, c.ph);
      };
#pragma unroll 1
      for (int L = 0; L < 2; L++) {
#pragma unroll 1
        for (int i = 0; i < 14; i++) {
          if (L == 0 && (i == 0 || i == 2 * SPL || i == 9)) {
            flag_wait(fj + (i == 9 ? FJ_WO : i == 2 * SPL ? FJ_WQ : FJ_WQ0), (epoch + 1) * 16);
            if (i == 9) flag_wait(g_flags + FJ + (j ^ 1) * 32 + FJ_WO, (epoch + 1) * 16);
            fence_async_g();
            TRC(el, 2, i == 9 ? 46 : i ? 47 : 45);
          }
          const uint32_t hb = i < 9 ? 13824 : i < 13 ? 18432 : 9216, o = ST_B + rk * (i < 9 ? 13824 : 18432);
          const uint8_t* src = i < 9 ? g_WQ + j * WQ_SL + i * 27648 + rk * 13824 : g_WO + ((j & 6) + rk) * WO_SL + (i - 9) * 18432;
          slot(2 * hb);
          bulk_mc_h(el, st + o, src, hb, full, true, pol);
          c.next();
        }
#pragma unroll 1
        for (int i = 0; i < 18; i++) {
          const int p = i >> 1, col = p == 4 ? (9 * j + ((j & 1) ? 0 : 8)) * 32 : (((9 * j + 1) >> 1) + (p < 4 ? p + 36 : p - 5)) * 64;
          if (i & 1) {
            slot(2 * ZB);
          } else {
            st = sb + c.s * ST_BYTES; full = bars + B_FULL + ((c.s + 1) & 3) * 8;
            mbar_wait(bars + B_EMPTY + c.s * 8, c.ph);
          }
          tma4d_mc(el, st + ST_B + rk * 18432, p == 4 ? &P.win : &P.win64, col, (i & 1) * 36 + rk * 18, full, pol);
          if (el && !(i & 1)) mbar_arrive(bars + B_FULL + c.s * 8);
          c.next();
        }
        TRC(el, 2, L * 16 + 6);
        flag_wait(fj + FJ_ZN + L, (epoch + 1) * 16);
        fence_async_g();
        TRC(el, 2, L * 16 + 7);
#pragma unroll 1
        for (int i = 0; i < 32; i++) {
          const uint8_t* src = z2_block(i, j) + rk * 18432;
          if (i >= 4) mbar_wait(bars + B_AD + c.s * 8, ((i >> 2) & 1) ^ 1);
          slot(ST_BYTES);
          bulk_mc_h(el, st + ST_B + rk * 18432, src, 18432, full, true, pol);
          tma3d_h(el, st, &P.wsp, i * 64, rb * 64, 0, full, true, pol);
          c.next();
        }
        mbar_wait(bars + B_Z1, L);
        fence_async_g();
        expect_tx_p(el, bars + B_ZB, 20480);
        bulk_load_h(el, sb + SM_STG, z1_block(rb, 1, j) + 16384, 4096, bars + B_ZB, true, pol);
#pragma unroll 1
        for (int i = 0; i < 10; i++) {
          const int cb = i - 1 + j;
          if (i < 4) mbar_wait(bars + B_AD + c.s * 8, 1);
          slot(i == 1 ? ST_BYTES : ZB);
          if (i < 2) bulk_load_h(el, st, z1_block(rb, i, j) + i * 20480, ZB - i * 20480, full, true, pol);
          if (i == 0) bulk_load_h(el, st + ZB, z1_block(rb, 1, j), 16384, bars + B_ZB, true, pol);
          else tma2d_mc_h(el, st + ST_B + rk * 18432, &P.wout, (cb >= 9 ? cb - 9 : cb) * 64, 288 * j + rk * 144, full, true, pol);
          c.next();
        }
      }
    } else if (wid < 11) {
      int w = wid - 9;
      uint32_t* const fr = g_flags + (rb * 2 + w) * 32;
      const uint32_t epoch = ldcg32(fr + FR_EP + j);
      const uint32_t ev = bars + B_EVT + w * EV_N * 8, t8 = (epoch + 1) * 8;
      Cur c{0, 1};
#pragma unroll 1
      for (int L = 0; L < 2; L++) {
        {
          const uint32_t tag = epoch * 2 + L + 1;
          uint4* const xs = g_XST + (rb * 2 + w) * 128;
          if (L) {
            mbar_wait(ev + EV_PT * 8, 0);
            TRC(el, 3, w * 32 + 16);
            flag_release_p(el, fr + FR_X2);
            TRC(el, 3, w * 32 + 17);
          }
#pragma unroll 1
          for (int i = 0; i < 9; i++) {
            const uint32_t full = bars + B_FULLA + w * 32 + c.s * 8, dst = sb + c.s * ST_BYTES + w * 8192;
            if (L == 0 && i == 4) {
              mbar_wait(bars + B_WT + w * 8, 0);
              TRC(el && w == 0, 2, 37);
              rows_stats(sb + SM_STG + w * 9216, xs + 16 * j, tag, lane);
              TRC(el && w == 0, 2, 38);
            }
            const uint32_t src = sb + (L ? 2 * ST_BYTES + SM_WOI : SM_STG + w * 9216);
            if (i == 4) {
#pragma unroll
              for (int u = 0; u < 6; u++) sts128(src + u * 512 + lane * 16, POISON, POISON, POISON, POISON);
              fence_async_s();
              __syncwarp();
            }
            mbar_wait(bars + B_EMPTY + c.s * 8, c.ph);
            expect_tx_p(el, full, 8192);
            if (i < L) { flag_wait(fr + FR_X2, t8); fence_async_g(); }
            tma3d_h(el, dst, &P.act[L], i * 64, rb * 64, w, full, false, pol);
            TRC(el && i < L, 3, w * 32 + 18);
            c.next();
            if (i >= 4 && i < (L ? 5 : 8)) {
              int b = (rb * 2 + w) * 8 + j;
              asm volatile("" : "+r"(b));
              bulk_store_p(el, i == 4 ? (uint8_t*)g_HALO + b * 3072 : g_O + (b * 3 + i - 5) * 3072, src, 3072);
              if (i < 6) bulk_store_p(el, (i == 4 ? g_ST1 : g_ZST) + b * 64, src, 1024);
              if (i == 6) bulk_store_p(el, g_RT + b * 8, src, 64);
            }
            if (L == 0 && i == 3) rows_fetch(el, sb + SM_STG + w * 9216, P.xs[0] + (128 * rb + 16 * j + w) * (DM * 2), bars + B_WT + w * 8);
          }
          if (el) asm volatile("cp.async.bulk.commit_group;\ncp.async.bulk.wait_group 0;" ::: "memory");
          __syncwarp();
          if (L == 0) fence_gpu();
          const uint32_t tab = sb + L * (2 * ST_BYTES) + SM_XST + w * 512 + lane * 8;
          TRC(el, 3, w * 32 + L * 16 + 13);
#pragma unroll 1
          for (int it = 0; it < (1 << 22); it++) {
            const uint4 a = ll_ld128(xs + 2 * lane), b = ll_ld128(xs + 64 + 2 * lane);
            if (__all_sync(~0u, a.z == tag && b.z == tag)) { sts64(tab, a.x, a.y); sts64(tab + 256, b.x, b.y); break; }
          }
          __syncwarp();
          mbar_arrive_if(el, bars + B_CSQ);
          TRC(el, 3, w * 32 + L * 16 + 14);
          if (w == 1) {
            mbar_wait(bars + B_CSQ, L);
            expect_tx_p(el, bars + B_RES, 18432);
            tma3d_h(el, sb + SM_STG, &P.res[L], (j & 6) * 72, rb * 64, j & 1, bars + B_RES, !L, pol);
          }
          if (L) flag_wait(fj + FJ_P4, t8 * 4);
        }
        asm volatile("" : "+r"(w));
        uint32_t* const fo = g_flags + (rb * 2 + (j & 1)) * 32 + L;
        {
          const uint8_t* src = o_block(rb, j & 1) + w * 8192;
#pragma unroll 1
          for (int i = 0; i < 5; i++) {
            const uint32_t full = bars + B_FULLA + w * 32 + c.s * 8, dst = sb + c.s * ST_BYTES + w * 8192;
            const bool none = 2 * i + w > 8;
            mbar_wait(bars + B_EMPTY + c.s * 8, c.ph);
            expect_tx_p(el, full, none ? 0 : 8192);
            if (i == 0) {
              mbar_wait(ev + EV_O * 8, L);
              TRC(el, 3, w * 32 + L * 16 + 3);
              flag_add_p(el, fr + FR_O + L);
              TRC(el, 3, w * 32 + L * 16 + 4);
              flag_wait(fo + FR_O, t8);
              fence_async_g();
            }
            if (!none) bulk_load_h(el, dst, src + i * 16384, 8192, full, true, pol);
            TRC(el && i == 0, 3, w * 32 + L * 16 + 5);
            c.next();
          }
        }
        {
          expect_tx_p(lane < 9, bars + B_FA3 + (9 * w + lane) * 8, 8192);
          mbar_wait(ev + EV_X1 * 8, L);
          TRC(el, 3, w * 32 + L * 16 + 6);
          if (L) flag_add_p(el, fo + FR_X1); else flag_release_p(el, fo + FR_X1);
          mbar_arrive_if(el, bars + B_GATE3);
          TRC(el, 3, w * 32 + L * 16 + 7);
          mbar_arrive_if(lane < 2, bars + B_FULLA + w * 32 + ((c.s + lane) & 3) * 8);
#pragma unroll 1
          for (int kb = 0; kb < 9; kb++) {
            const int n = 9 * w + kb;
            const uint32_t dst = sb + ((n >> 1) & 3) * ST_BYTES + (n & 1) * 8192;
            if (kb == 0) { flag_wait(fr + FR_X1 + L, t8); fence_async_g(); }
            if (n >= 8) mbar_wait(bars + B_EA3 + (n - 8) * 8, L);
            tma3d_h(el, dst, &P.act[L + 1], kb * 64, rb * 64, w, bars + B_FA3 + n * 8, false, pol);
            TRC(el && kb == 0, 3, w * 32 + L * 16 + 8);
          }
          c.ph ^= ((c.s + 18) >> 2) & 1; c.s = (c.s + 18) & 3;
        }
        asm volatile("" : "+r"(lane), "+r"(w));
        expect_tx_p(el, bars + B_WT + w * 8, 2048);
#pragma unroll 1
        for (int r = 0; r < 8; r++)
          bulk_load_p(el, sb + SM_WT + w * 2176 + r * 272, (const uint8_t*)P.w_sp + (size_t)(128 * rb + 16 * j + 2 * r + w) * (SEQ * 2) + 30 * 128, 256, bars + B_WT + w * 8);
        float cv = (lane & 3) ? 0.f : -blo(ldnc16(P.b_sp + 128 * rb + 16 * j + 2 * (lane >> 2) + w));
        mbar_wait(bars + B_RT, L);
        mbar_wait(bars + B_WT + w * 8, L ^ 1);
        mbar_wait(ev + EV_Z1 * 8, L);
        const uint32_t ro = (w * 64 + 8 * j + (lane >> 2)) * 128, x0 = ((lane & 3) * 2) ^ (lane >> 2);
#pragma unroll 1
        for (int i = 0; i < 32; i++) {
          const bool tail = (i >> 1) == 4;
          const int kb = tail ? i + 22 : i < 8 ? i : i - 2;
          if (i == 8) mbar_wait(bars + B_RT1, L);
          if (!tail) mbar_wait(bars + B_FULL + c.s * 8, c.ph ^ 1);
#pragma unroll
          for (int e = 0; e < 2; e++) {
            const uint4 a = lds128(!tail ? sb + c.s * ST_BYTES + ro + ((x0 ^ e) << 4) : sb + SM_WT + w * 2176 + (lane >> 2) * 272 + (i - 8) * 128 + (lane & 3) * 32 + e * 16);
            const uint4 m = lds128(sb + SM_RT + 4096 + kb * 128 + (lane & 3) * 32 + e * 16);
            cv = fmaf(blo(a.x), blo(m.x), fmaf(bhi(a.x), bhi(m.x), fmaf(blo(a.y), blo(m.y), fmaf(bhi(a.y), bhi(m.y), cv))));
            cv = fmaf(blo(a.z), blo(m.z), fmaf(bhi(a.z), bhi(m.z), fmaf(blo(a.w), blo(m.w), fmaf(bhi(a.w), bhi(m.w), cv))));
          }
          if (!tail) {
            mbar_arrive_if(el, bars + B_AD + c.s * 8 + (__float_as_uint(cv) & P.zero));
            c.next();
          }
        }
        TRC(el, 3, w * 32 + L * 16 + 11);
        uint32_t tag = t8;
        asm volatile("" : "+r"(tag));
        tag = (tag >> 2) - 1 + L;
        cv = qsum(cv);
        uint2* const cs = (uint2*)(g_XST + (rb * 2 + w) * 128 + 1);
        if ((lane & 3) == 0) ll_st64(cs + 32 * j + (lane >> 2) * 4, __float_as_uint(cv), tag);
#pragma unroll 1
        for (int it = 0; it < (1 << 22); it++) {
          const uint2 a = ll_ld64(cs + 4 * lane), b = ll_ld64(cs + 128 + 4 * lane);
          if (__all_sync(~0u, a.y == tag && b.y == tag)) { sts32(sb + SM_CV + w * 256 + lane * 4, a.x); sts32(sb + SM_CV + w * 256 + 128 + lane * 4, b.x); break; }
        }
        __syncwarp();
        if (el) mbar_arrive(bars + B_CV + w * 8);
        TRC(el, 3, w * 32 + L * 16 + 12);
#pragma unroll 1
        for (int kb = 30; kb < 32; kb++) {
          mbar_wait(bars + B_FULL + c.s * 8, c.ph ^ 1);
          if (el) mbar_arrive(bars + B_AD + c.s * 8);
          c.next();
        }
        c.ph ^= ((c.s + 10) >> 2) & 1; c.s = (c.s + 10) & 3;
        if (L == 0) {
          mbar_wait(ev + EV_P4 * 8, 0);
          flag_add_p(el, fj + FJ_P4);
        }
      }
    } else {
      const uint32_t epoch = ldcg32(fj + FJ_EP + rb);
      if (SPL) {
        mbar_wait(bars + B_RES + 8, 0);
        TRC(el, 2, 41);
        flag_release_p(el, fj + FJ_WQ0);
        TRC(el, 2, 42);
      }
      mbar_wait(bars + B_IMG, 0);
      TRC(el, 2, 39);
      flag_release_p(el, fj + FJ_WQ);
      TRC(el, 2, 40);
#pragma unroll 1
      for (int L = 0; L < 2; L++) {
        float* const csf = g_CSP + (NCTA + bid) * 216;
        if (L == 0) {
          flag_wait(fj + FJ_WQ, (epoch + 1) * 16);
          fence_async_g();
          expect_tx_p(el, bars + B_XRW, 13824);
          bulk_load_p(el, sb + ST_BYTES + SM_WOI, g_CSP + j * 16 * 216, 6912, bars + B_XRW);
          bulk_load_p(el, sb + 2 * ST_BYTES + SM_WOI, g_CSP + (j * 16 + 8) * 216, 6912, bars + B_XRW);
          mbar_wait(bars + B_XRW, 0);
#pragma unroll 1
          for (int f = lane; f < 54; f += 32) {
            float s[4] = {0.f, 0.f, 0.f, 0.f};
#pragma unroll 4
            for (int r = 0; r < 16; r++) {
              const uint4 v = lds128(sb + ST_BYTES + SM_WOI + (r >> 3) * ST_BYTES + (r & 7) * 864 + f * 16);
              s[0] += __uint_as_float(v.x); s[1] += __uint_as_float(v.y); s[2] += __uint_as_float(v.z); s[3] += __uint_as_float(v.w);
            }
            sts128(sb + SM_CSQ + f * 16, __float_as_uint(s[0]), __float_as_uint(s[1]), __float_as_uint(s[2]), __float_as_uint(s[3]));
            stg128(csf + f * 4, __float_as_uint(s[0]), __float_as_uint(s[1]), __float_as_uint(s[2]), __float_as_uint(s[3]));
          }
          __syncwarp();
          mbar_arrive_if(el, bars + B_CSQ);
        } else {
#pragma unroll 1
          for (int u = 0; u < 4; u++) {
            const int w = u & 1;
            if (u < 2) {
              flag_wait(g_flags + (rb * 2 + w) * 32 + FR_X2, (epoch + 1) * 8);
              fence_async_g();
              TRC(el, 2, 48 + u);
              rows_fetch(el, sb + SM_STG + w * 9216, P.xs[1] + (128 * rb + 16 * j + w) * (DM * 2), bars + B_XRW + w * 8);
            } else {
              mbar_wait(bars + B_XRW + w * 8, w ^ 1);
              TRC(el, 2, 48 + u);
              rows_stats(sb + SM_STG + w * 9216, g_XST + (rb * 2 + w) * 128 + 16 * j, epoch * 2 + 2, lane);
              TRC(el, 2, 50 + u);
            }
          }
          expect_tx_p(el, bars + B_CSQ, 864);
          bulk_load_p(el, sb + 2 * ST_BYTES + SM_CSQ, csf, 864, bars + B_CSQ);
        }
        if (L == 0) {
          TRC(el, 2, 43);
          mbar_wait(bars + B_WOI, 0);
          bulk_store_p(el, g_WO + j * WO_SL + rb * (41 * 128), sb + SM_WOI, (rb < 15 ? 41 : 33) * 128);
          publish_p(el, fj + FJ_WO);
          TRC(el, 2, 44);
          uint4 y[4];
#pragma unroll
          for (int u = 0; u < 4; u++) y[u] = ldnc128((u < 2 ? (const uint8_t*)P.w_in + (100 + 300 * u) * (2 * FH * 2) + (FH + 1024 * u) * 2 : (const uint8_t*)P.w_sp + (1000 * u - 1500) * (SEQ * 2) + u * 1024) + lane * 16);
          float sq[2] = {0.f, 0.f};
#pragma unroll
          for (int u = 0; u < 4; u++) {
            const uint32_t x[4] = {y[u].x, y[u].y, y[u].z, y[u].w};
#pragma unroll
            for (int e = 0; e < 4; e++) sq[u >> 1] = fmaf(blo(x[e]), blo(x[e]), fmaf(bhi(x[e]), bhi(x[e]), sq[u >> 1]));
          }
          const float o0 = sqrtf(wsum(sq[0]) * (2.f * GA * GA * DM / 512.f)), o1 = sqrtf(wsum(sq[1]) * (C0S * C0S * SEQ / 512.f));
          const uint32_t off = (__float_as_uint(o0) & 0x7f800000u) >> 16 | 0x8000u | OFM;
          if (el) sts64(sb + SM_OFF, off * 0x10001u, min(__float_as_uint(o1) & 0x7f800000u, 0x7e000000u) | 0x00400000u);
        }
        if (el) mbar_arrive(bars + B_GATE3);
        const uint32_t tag = epoch * 2 + L + 1;
        asm volatile("" : "+r"(lane));
        mbar_wait(bars + B_EVT + EV_ZN * 8, L);
        mbar_wait(bars + B_EVT + (EV_N + EV_ZN) * 8, L);
        flag_release_p(el, fj + FJ_ZN + L);
        TRC(el, 2, L * 16 + 8);
        {
          uint4 v[4];
#pragma unroll 1
          for (int it = 0; it < (1 << 22); it++) {
            bool ok = true;
#pragma unroll
            for (int u = 0; u < 4; u++) { v[u] = ll_ld128(g_ZST + (rb * 2 + ((lane >> 1) & 1)) * 512 + ((lane & 1) * 4 + u) * 64 + 8 * j + (lane >> 2)); ok = ok && v[u].z == tag; }
            if (__all_sync(~0u, ok)) break;
          }
          float mean = __uint_as_float(v[0].x) + __uint_as_float(v[1].x) + __uint_as_float(v[2].x) + __uint_as_float(v[3].x), M2 = 0.f;
          mean = (mean + __shfl_xor_sync(~0u, mean, 1)) * 0.125f;
#pragma unroll
          for (int u = 0; u < 4; u++) { const float d = __uint_as_float(v[u].x) - mean; M2 += fmaf(288.f * d, d, __uint_as_float(v[u].y)); }
          M2 += __shfl_xor_sync(~0u, M2, 1);
          const float rs = blo(pack2(rsqrtf(fmaf(M2, 1.f / FH, 4.f * GA * GA * LN_EPS)), 0.f));
          if (!(lane & 1)) ll_st64(g_RT + 128 * rb + 16 * j + (lane >> 1), pack2(rs, rs * mean), tag);
        }
        TRC(el, 2, L * 16 + 10);
#pragma unroll 1
        for (int b = 0; b < 8; b++) {
          uint4 v[4];
#pragma unroll 1
          for (int it = 0; it < (1 << 22); it++) {
            bool ok = true;
#pragma unroll
            for (int u = 0; u < 4; u++) { v[u] = ll_ld128((const uint4*)g_RT + b * 128 + u * 32 + lane); ok = ok && v[u].y == tag && v[u].w == tag; }
            if (__all_sync(~0u, ok)) break;
          }
#pragma unroll
          for (int u = 0; u < 4; u++) {
            const uint32_t rt = sb + SM_RT + b * 512 + u * 128, ro = (lane >> 3) * 32 + (lane & 3) * 8 + ((lane >> 2) & 1) * 2;
            sts32(rt + 4096 + lane * 4, __byte_perm(v[u].x, v[u].z, 0x7632));
            asm volatile("st.shared.u16 [%0], %1;\nst.shared.u16 [%0 + 4], %2;" ::"r"(rt + ro), "h"((uint16_t)v[u].x), "h"((uint16_t)v[u].z) : "memory");
          }
          __syncwarp();
          if (el && (b == 1 || b == 7)) mbar_arrive(bars + (b == 1 ? B_RT : B_RT1));
          TRC(el && b < 2, 2, L * 16 + 11 + b);
        }
        TRC(el, 2, L * 16 + 9);
        mbar_wait(bars + B_EVT + EV_Z1 * 8, L);
        mbar_wait(bars + B_EVT + (EV_N + EV_Z1) * 8, L);
        fence_gpu();
        if (el) mbar_arrive(bars + B_Z1);
        if (L == 0) {
          __nanosleep(NAP0);
          poison(el, sb + SM_STG + 17152, &P.psn, rb, j, lane);
          if (el) asm volatile("cp.async.bulk.commit_group;\ncp.async.bulk.wait_group 0;" ::: "memory");
          __syncwarp();
          fence_gpu();
        }
      }
    }
  } else {
    CKK(3);
    uint8_t* const wdst = P.wq + j * WQ_SL + rb * 3456 + tid * 16;
#pragma unroll
    for (int u = 0; u < SPL; u++) stg128_if(tid < 216, wdst + u * (16 * 3456), wv[u].x, wv[u].y, wv[u].z, wv[u].w);
    __syncwarp();
    if (lane == 0) mbar_arrive(bars + B_RES + 8);
    CKK(4);
    auto repack2 = [&]() {
#pragma unroll
      for (int u = SPL; u < 5; u++) stg128_if((u < 4 || rb < 8) && tid < 216, wdst + u * (16 * 3456), wv[u].x, wv[u].y, wv[u].z, wv[u].w);
      float s[8];
#pragma unroll
      for (int e = 0; e < 8; e++) s[e] = 0.f;
#pragma unroll
      for (int u = 0; u < 5; u++) {
        uint32_t x[4] = {wv[u].x, wv[u].y, wv[u].z, wv[u].w};
        asm volatile("" : "+r"(x[0]), "+r"(x[1]), "+r"(x[2]), "+r"(x[3]));
#pragma unroll
        for (int e = 0; e < 4; e++) { s[2 * e] += blo(x[e]); s[2 * e + 1] += bhi(x[e]); }
      }
#pragma unroll
      for (int m = 4; m; m >>= 1) {
#pragma unroll
        for (int e = 0; e < m; e++) s[e] = ((tid & m) ? s[e + m] : s[e]) + __shfl_xor_sync(~0u, (tid & m) ? s[e] : s[e + m], m);
      }
      stg32_if(tid < 216, P.csp + bid * 216 + tid, __float_as_uint(s[0]));
      __syncwarp();
      if (lane == 0) mbar_arrive(bars + B_IMG);
    };
    reg_alloc<232>();
    CKK(5);
#pragma unroll
    for (int v = SPL; v < 5; v++) wv[v] = ldnc128_if(tid < 216 && (v < 4 || rb < 8), wsrc + v * (128 * 3 * DM * 2));
    repack2();
    CKK(6);
    const int w = wid >> 2, q = wid & 3;
    int g = lane >> 2, t = lane & 3;
    const uint32_t ev = bars + B_EVT + w * EV_N * 8;
    const bool tr = (tid & 127) == 0;
    (void)tr;
    Cur c{0, 0};
    const uint32_t ebar = mapa(bars + B_EMPTY, (bid & 1) ^ (lane & 1));
    auto release = [&](uint32_t s, uint32_t dep = 0) { mbar_arrive_cluster_if(lane < 2, ebar + s * 8 + dep); };
    auto release_if = [&](bool on, uint32_t s) { mbar_arrive_cluster_if(lane < 2 && on, ebar + s * 8); };
    uint32_t ia = 0;
    auto wait_ab = [&]() { mbar_wait_c(bars + B_FULL + c.s * 8, c.ph); mbar_wait_c(bars + B_FULLA + w * 32 + c.s * 8, (ia >> 2) & 1); ia++; };
    uint32_t lagph = 0;
    auto yield = [&](int left, int lag) { if (w == 1 && left == lag) mbar_wait_c(bars + B_LAG, lagph); };
    auto yield_done = [&]() { if (w == 0 && lane == 0) mbar_arrive(bars + B_LAG); };
    auto signal = [&](int e) { __syncwarp(); if (lane == 0) mbar_arrive(ev + e * 8); };

    auto fetch_wo = [&]() {
#pragma unroll 1
      for (int u = tid; u < 328; u += 256) {
        const int m = min(41 * rb + (u >> 3), 647), k8 = m / 9;
        cp_async16(sb + SM_WOI + u * 16, (const uint8_t*)P.wo + (8 * k8 + (u & 7)) * (DM * 2) + (72 * j + 8 * (m - k8 * 9)) * 2);
      }
    };
    const uint32_t epoch = ldcg32(g_flags + (rb * 2 + w) * 32 + FR_EP + j);
    TRC(tr, w, 1);
    CKK(7);
    if (PAD && P.zero) {
#pragma unroll
      for (int i = 0; i < PAD; i++) asm volatile("st.shared.u32 [%0], %1;" ::"r"(sb + i * 20), "r"(tid) : "memory");
    }
    CKK_OUT;

#pragma unroll 1
    for (int L = 0; L < 2; L++) {
      const int tb = 2 + L * 24;
      asm volatile("" : "+r"(lane), "+r"(g), "+r"(t));
      (void)tb;
      ia = 0;
      const uint32_t tag = epoch * 2 + L + 1;
      uint32_t aoff = (w * 64 + q * 16 + (lane & 15)) * 128 + (((lane >> 4) ^ (lane & 7)) << 4);
      {
        uint32_t Pk[27][2];
        float sc0, sc1;
        const uint32_t att = sb + w * 8192 + q * 2048 + lane * 4;
        uint4* hp = g_HALO + ((((rb - (q == 0)) * 2 + w) * 8 + j) * 6) * 32 + lane;
        uint8_t* od = o_block(rb, w) + (9 * j) * 1024 + (2 * q) * 128 + lane * 4;
        ACLK_INIT;
        {
          float acc[108];
#pragma unroll
          for (int i = 0; i < 108; i++) acc[i] = 0.f;
          uint32_t prev = 0;
#pragma unroll 1
          for (int kb = 0; kb < 9; kb++) {
            wait_ab();
            yield(9 - kb, LAG1);
            TRC(tr && kb == 0, w, tb + 0);
            MCLK(kb == 0, 0);
            PCLK(kb * 4);
            const uint32_t st = sb + c.s * ST_BYTES, da = dlo(st + w * 8192, 16), db = dlo(st + ST_B, 3456);
            wgmma_fence();
#pragma unroll
            for (int kk = 0; kk < 4; kk++) {
              wgmma_ss_n216(acc, dsc<1024, 1>(da, kk * 32), dsc<128, 0>(db, kk * 6912), 1);
              if (kk == 0) { wgmma_commit(); wgmma_wait<1>(); release_if(kb > 0, prev); }
            }
            wgmma_commit();
            if (kb == 8) yield_done();
            PCLK(kb * 4 + 1);
            if (kb == 0 && L == 0) fetch_wo();
            if (kb == 3 && L == 0) {
              asm volatile("cp.async.wait_all;" ::: "memory");
              fence_async_s();
              __syncwarp();
              if (lane == 0) mbar_arrive(bars + B_WOI);
            }
            PCLK(kb * 4 + 2);
            PCLK(kb * 4 + 3);
            prev = c.s; c.next();
          }
          const uint32_t cs = sb + prev * ST_BYTES + SM_CSQ + t * 8;
          mbar_wait_c(bars + B_CSQ, L);
          const float2 n0 = lds64f(sb + prev * ST_BYTES + SM_XST + w * 512 + (16 * q + g) * 8), n1 = lds64f(sb + prev * ST_BYTES + SM_XST + w * 512 + (16 * q + g + 8) * 8);
          const float m0 = n0.x, r0 = n0.y, m1 = n1.x, r1 = n1.y;
          float2 cv[27];
#pragma unroll
          for (int G = 0; G < 27; G++) cv[G] = lds64f(cs + G * 32);
          PCLK(36);
          wgmma_wait<0>();
          PCLK(37);
          uint32_t dep = P.zero & __float_as_uint(m0) & __float_as_uint(m1);
#pragma unroll
          for (int G = 0; G < 27; G++) dep &= __float_as_uint(cv[G].x);
          release(prev, dep);
          lagph ^= 1;
          TRC(tr, w, tb + 1);
          MCLK(1, 1);
          ACLK(0);
#pragma unroll
          for (int G = 9; G < 27; G++) Pk[G][1] = pack2(fmaf(m1, cv[G].x, acc[4 * G + 2]) * r1, fmaf(m1, cv[G].y, acc[4 * G + 3]) * r1);
          if (q < 3) {
#pragma unroll
            for (int i = 0; i < 18; i++) sts32(att + (i >> 4) * ST_BYTES + (i & 15) * 128, Pk[9 + i][1]);
          } else if (rb < 15) {
#pragma unroll
            for (int i = 0; i < 6; i++) ll_st128(hp + i * 32, __uint_as_float(Pk[9 + 3 * i][1]), __uint_as_float(Pk[10 + 3 * i][1]), tag, __uint_as_float(Pk[11 + 3 * i][1]));
          }
#pragma unroll
          for (int G = 0; G < 27; G++) {
            if (G < 9) {
              Pk[G][0] = pack2(fmaf(m0, cv[G].x, acc[4 * G]), fmaf(m0, cv[G].y, acc[4 * G + 1]));
              Pk[G][1] = pack2(fmaf(m1, cv[G].x, acc[4 * G + 2]), fmaf(m1, cv[G].y, acc[4 * G + 3]));
            } else {
              Pk[G][0] = pack2(fmaf(m0, cv[G].x, acc[4 * G]) * r0, fmaf(m0, cv[G].y, acc[4 * G + 1]) * r0);
            }
          }
          sc0 = r0 * (0.23570226039551584f * 1.4426950408889634f); sc1 = r1 * (0.23570226039551584f * 1.4426950408889634f);
        }
        ACLK(1);
        constexpr int GA_[4] = {0, 2, 4, 7}, GB_[4] = {1, 3, 5, 8}, GC_[4] = {2, 4, 6, 6};
        float S1[4][4], S2[4][4];
        uint32_t qa[4][2], qc[4][2];
#pragma unroll
        for (int h = 0; h < 4; h++) {
#pragma unroll
          for (int r = 0; r < 2; r++) {
            qa[h][r] = (h == 0 || h == 3 || t >= h) ? Pk[GA_[h]][r] : 0u;
            qc[h][r] = (h == 3 ? t == 3 : t <= h) ? Pk[GC_[h]][r] : 0u;
          }
          mma16(S1[h], qa[h][0], qa[h][1], Pk[GB_[h]][0], Pk[GB_[h]][1], Pk[9 + GA_[h]][0], Pk[9 + GB_[h]][0]);
          mma16(S2[h], qa[h][0], qa[h][1], Pk[GB_[h]][0], Pk[GB_[h]][1], Pk[9 + GA_[h]][1], Pk[9 + GB_[h]][1]);
        }
#pragma unroll
        for (int h = 0; h < 4; h++) {
          mma8(S1[h], qc[h][0], qc[h][1], Pk[9 + GC_[h]][0]);
          mma8(S2[h], qc[h][0], qc[h][1], Pk[9 + GC_[h]][1]);
        }
        uint32_t V1[9], V2[9];
#pragma unroll
        for (int i = 0; i < 9; i++) { V1[i] = movm(Pk[18 + i][0]); V2[i] = movm(Pk[18 + i][1]); }
        const bool remote = q == 0 && rb > 0;
        uint4 hv[6];
#pragma unroll
        for (int i = 0; i < 6; i++) hv[i] = make_uint4(0u, 0u, tag, 0u);
        if (remote) {
#pragma unroll
          for (int i = 0; i < 6; i++) hv[i] = ll_ld128(hp + i * 32);
        }
        const bool up0 = 2 * t > g, up1 = 2 * t + 1 > g;
        const uint32_t mup = (up0 ? 0xffffu : 0u) | (up1 ? 0xffff0000u : 0u);
        auto finish = [&](const float (&x0)[4], const float (&x1)[4], uint32_t ma, const uint32_t (&Vb)[9], int hi) {
          uint32_t pa[4], pb[4];
          float rs[4];
#pragma unroll
          for (int h = 0; h < 4; h++) {
            const float m = qmax(fmaxf(x0[h], x1[h]));
            const uint32_t p = pack2(ex2(x0[h] - m), ex2(x1[h] - m));
            pa[h] = p & ma; pb[h] = p & ~ma;
          }
#pragma unroll
          for (int h = 0; h < 4; h += 2) {
            float R[4];
            mma16(R, pa[h], pa[h + 1], pb[h], pb[h + 1], 0x3f803f80u, 0x3f803f80u);
            rs[h] = rcp_fast(R[0]); rs[h + 1] = rcp_fast(R[2]);
          }
#pragma unroll
          for (int i = 0; i < 9; i++) {
            const int h = 4 * i / 9, e = (h & 1) * 2;
            const bool split = i == 2 || i == 4 || i == 6, nx = split && 2 * t >= i;
            float O[4], N[4];
            mma16(O, pa[h & 2], pa[h | 1], pb[h & 2], pb[h | 1], V1[i], Vb[i]);
            if (i == 4) mma16(N, pa[2], pa[3], pb[2], pb[3], V1[i], Vb[i]); else { N[0] = O[2]; N[1] = O[3]; }
            const float r = nx ? rs[h + (split ? 1 : 0)] : rs[h];
            stg32(od + i * 1024 + hi * 128, pack2((nx ? N[0] : O[e]) * r, (nx ? N[1] : O[e + 1]) * r));
          }
        };
        {
          float x0[4], x1[4];
#pragma unroll
          for (int h = 0; h < 4; h++) { x0[h] = (up0 ? S1[h][2] : S2[h][2]) * sc1; x1[h] = (up1 ? S1[h][3] : S2[h][3]) * sc1; }
          finish(x0, x1, mup, V2, 1);
        }
        ACLK(2);
        bar_sync(1 + w, 128);
        uint32_t H[18];
        if (q > 0) {
#pragma unroll
          for (int i = 0; i < 18; i++) H[i] = lds32(att - 2048 + (i >> 4) * ST_BYTES + (i & 15) * 128);
        } else {
#pragma unroll 1
          for (int it = 0; it < (1 << 20); it++) {
            bool ok = true;
#pragma unroll
            for (int i = 0; i < 6; i++) ok = ok && hv[i].z == tag;
            if (__all_sync(~0u, ok)) break;
#pragma unroll
            for (int i = 0; i < 6; i++) hv[i] = ll_ld128(hp + i * 32);
          }
#pragma unroll
          for (int i = 0; i < 6; i++) { H[3 * i] = hv[i].x; H[3 * i + 1] = hv[i].y; H[3 * i + 2] = hv[i].w; }
        }
        float S0[4][4];
#pragma unroll
        for (int h = 0; h < 4; h++) {
          mma16(S0[h], qa[h][0], qa[h][1], Pk[GB_[h]][0], Pk[GB_[h]][1], H[GA_[h]], H[GB_[h]]);
        }
#pragma unroll
        for (int h = 0; h < 4; h++) mma8(S0[h], qc[h][0], qc[h][1], H[GC_[h]]);
        uint32_t V0[9];
#pragma unroll
        for (int i = 0; i < 9; i++) V0[i] = movm(H[9 + i]);
        ACLK(3);
        {
          const bool nohalo = (rb | q) == 0;
          const float b0 = up0 && nohalo ? -INFINITY : 0.f, b1 = up1 && nohalo ? -INFINITY : 0.f;
          float x0[4], x1[4];
#pragma unroll
          for (int h = 0; h < 4; h++) { x0[h] = fmaf(up0 ? S0[h][0] : S1[h][0], sc0, b0); x1[h] = fmaf(up1 ? S0[h][1] : S1[h][1], sc0, b1); }
          finish(x0, x1, ~mup, V0, 0);
        }
        ACLK(4);
        signal(EV_O);
        ACLK_OUT;
        TRC(tr, w, tb + 2);
        MCLK(1, 2);
      }
      {
        float acc[36];
        const int hw = rb * 2 + (j & 1), js = (j & 6) + w;
        const uint32_t xt = sb + SM_STG + (16 * q + g) * 288 + w * 144 + t * 4;
        uint32_t xm = sb + SM_STG + (16 * q + (lane & 15)) * 288 + (((9 * w + (lane >> 4)) ^ ((lane >> 2) & 1)) << 4), xl = sb + SM_STG + (2 * q + w) * 2304 + lane * 16;
        uint8_t* xd[5];
#pragma unroll
        for (int u = 0; u < 5; u++) {
          const int row = ((u * 32 + lane) * 57) >> 10;
          xd[u] = P.xs[L + 1] + (128 * rb + 32 * q + 16 * w + (j & 1)) * (DM * 2) + (j & 6) * 144 + row * (DM * 4 - 288) + u * 512 + ((lane ^ (row >> 2)) << 4);
          asm volatile("" : "+l"(xd[u]));
        }
        asm volatile("" : "+r"(xm), "+r"(xl));
        mbar_wait_c(bars + B_RES, L);
        TRC(tr, w, tb + 21);
#pragma unroll
        for (int i = 0; i < 18; i++) { const uint32_t x = lds32(xt + (i >> 1) * 16 + (i & 1) * 2304); acc[2 * i] = blo(x); acc[2 * i + 1] = bhi(x); asm volatile("" : "+f"(acc[2 * i]), "+f"(acc[2 * i + 1])); }
        uint32_t prev = 0;
#pragma unroll 1
        for (int u = 0; u < 5; u++) {
          const uint32_t st = sb + c.s * ST_BYTES, da = dlo(st, 1024), db = dlo(st + ST_B + w * 18432, 1152);
          mbar_wait_c(bars + B_FULL + c.s * 8, c.ph); mbar_wait_c(bars + B_FULLA + c.s * 8, (ia >> 2) & 1);
          TRC(tr && u == 0, w, tb + 3);
          MCLK(u == 0, 3);
          wgmma_fence();
#pragma unroll
          for (int kk = 0; kk < 4; kk++) wgmma_ss_n72(acc, dsc<128, 0>(da, kk * 2048), dsc<128, 0>(db, kk * 2304), 1);
          wgmma_commit();
          wgmma_wait<1>();
          release_if(u > 0, prev);
          mbar_wait_c(bars + B_FULLA + 32 + c.s * 8, (ia >> 2) & 1);
          ia++;
          if (u == 4) break;
          wgmma_fence();
#pragma unroll
          for (int kk = 4; kk < 8; kk++) wgmma_ss_n72(acc, dsc<128, 0>(da, kk * 2048), dsc<128, 0>(db, kk * 2304), 1);
          wgmma_commit();
          prev = c.s; c.next();
        }
        RCLK_INIT;
        wgmma_wait<0>();
        RCLK(0);
        release(c.s);
        c.next();
        if (__builtin_expect(any_nan(acc[0], acc[2]), 0)) {
          SLOW(L);
          const uint8_t* xr = P.xs[L] + (128 * rb + 32 * q + 2 * g + (j & 1)) * (DM * 2) + js * 144 + t * 4;
#pragma unroll
          for (int i = 0; i < 18; i++) { const uint32_t x = ldgpu32(xr + (i >> 1) * 16 + (i & 1) * (DM * 32)); acc[2 * i] = blo(x); acc[2 * i + 1] = bhi(x); }
          redo<KS2, 9, 1024, 128, 1152, 128>(acc, o_block(rb, j & 1) + q * 256 + lane * 4, g_WO + js * WO_SL + lane * 4, [](uint32_t*, int) {});
        }
        TRC(tr && P5TRACE != 5, w, tb + 4);
        MCLK(1, 4);
#pragma unroll
        for (int u = 0; u < 4; u++)
          stsm4(xm + u * 32, pack2(acc[8 * u], acc[8 * u + 1]), pack2(acc[8 * u + 2], acc[8 * u + 3]), pack2(acc[8 * u + 4], acc[8 * u + 5]), pack2(acc[8 * u + 6], acc[8 * u + 7]));
        asm volatile("stmatrix.sync.aligned.m8n8.x2.shared.b16 [%0], {%1,%2};" ::"r"(xm + 128), "r"(pack2(acc[32], acc[33])), "r"(pack2(acc[34], acc[35])) : "memory");
        auto stats = [&]() {
          float s0 = 0.f, s1 = 0.f, q0 = 0.f, q1 = 0.f;
#pragma unroll
          for (int i = 0; i < 36; i++) {
            if (i & 2) { s1 += acc[i]; q1 = fmaf(acc[i], acc[i], q1); } else { s0 += acc[i]; q0 = fmaf(acc[i], acc[i], q0); }
          }
          s0 = qsum(s0); s1 = qsum(s1); q0 = qsum(q0); q1 = qsum(q1);
          const float ss = t ? s1 : s0, m = ss * (1.f / 72.f);
          ll_st128_if(t < 2, g_ST1 + (hw * 8 + js) * 64 + 16 * q + 8 * t + g, m, fmaxf((t ? q1 : q0) - ss * m, 0.f), tag);
        };
        if (STF == 1) stats();
        RCLK(1);
        bar_sync(8 + q, 64);
        RCLK(2);
#pragma unroll
        for (int u = 0; u < 5; u++) {
          const uint4 v = lds128(xl + u * 512);
          stg128_if(u < 4 || lane < 16, xd[u], v.x, v.y, v.z, v.w);
        }
        if (STF == 2) stats();
        RCLK(3);
        signal(EV_X1);
        RCLK(4);
        if (STF == 0 && P.zero == 0) stats();
        RCLK(5);
        TRC(tr, w, tb + 5);
        RCLK(6);
        RCLK_OUT;
      }
      {
        uint32_t xA[36][4];
        float acc[32];
        uint32_t s0, one, off2;
        uint8_t *z1d, *zd;
        uint64_t db;
        auto bwait = [&](uint32_t dhi, bool skip) {
          s0 = c.s;
          c.next();
          if (!skip) mbar_wait_c(bars + B_FULL + c.s * 8, c.ph);
          db = dsc2(dlo(sb + s0 * ST_BYTES + ST_B, 512) - 3, 0, dhi); one = (c.s ^ P.zero) & 1;
        };
        auto mma = [&](int kk, int pp, bool hand) {
          wgmma_rs_n64(acc, xA[kk], dat(db, (kk / 18) * ST_BYTES + (kk % 18) * 2048 + 48, one), kk != 0);
          if (kk == pp && hand) bar_arrive(7 - w, 256);
          if (kk == 17 || kk == 35) wgmma_commit();
          if (kk == RL3) { wgmma_commit(); wgmma_wait<1>(); release(s0); }
        };
        {
          bwait(0x40000040u, false);
          mbar_wait_c(bars + B_GATE3, L);
          float mean0, mean1, rs0, rs1;
          stat_get(g_ST1 + ((rb * 2 + w) * 8 + 2 * t) * 64 + 16 * q + g, tag, 72.f, LN_EPS, mean0, rs0, mean1, rs1);
          const uint32_t ns0 = pack2(GA * rs0, GA * rs0), ns1 = pack2(GA * rs1, GA * rs1);
          const uint32_t nb0 = pack2(-mean0 * blo(ns0), -mean0 * blo(ns0)), nb1 = pack2(-mean1 * blo(ns1), -mean1 * blo(ns1));
          const uint32_t al = sb + (aoff & 8191);
#pragma unroll
          for (int kb = 0; kb <= 9; kb++) {
            if (kb < 9) {
              mbar_wait_c(bars + B_FA3 + (9 * w + kb) * 8, L);
              TRC(tr && kb == 0, w, tb + 6);
              MCLK(kb == 0, 5);
              if (kb == 0) SCLK(0);
              QCLK(kb);
              const uint32_t at = al + (w ? (((kb + 1) >> 1) & 3) * ST_BYTES + ((kb + 1) & 1) * 8192 : ((kb >> 1) & 3) * ST_BYTES + (kb & 1) * 8192);
#pragma unroll
              for (int kk = 4 * kb; kk < 4 * kb + 4; kk++) ldsm4(xA[kk], at ^ ((kk & 3) << 5));
            }
            if (kb == 0) continue;
            const uint32_t dep = xA[4 * kb - 4][0] & xA[4 * kb - 3][0] & xA[4 * kb - 2][0] & xA[4 * kb - 1][0] & P.zero;
            mbar_arrive_if(lane == 0 && (kb == 1 || w == 0), bars + B_EA3 + (9 * w + kb - 1) * 8 + dep);
#pragma unroll
            for (int kk = 4 * kb - 4; kk < 4 * kb; kk++) {
#pragma unroll
              for (int e = 0; e < 4; e++) xA[kk][e] = hfma2(xA[kk][e], (e & 1) ? ns1 : ns0, (e & 1) ? nb1 : nb0);
            }
            wgmma_fence();
#pragma unroll
            for (int kk = 4 * kb - 4; kk < 4 * kb; kk++) mma(kk, PP30, w);
          }
          off2 = lds32(sb + SM_OFF);
          z1d = z1_block(rb, w, j) + (tid & 127) * 16;
          zd = z2_block(2 * rb + (q >> 1), j) + (4 * (q & 1) + w) * 4608 + ((g & 3) * 2 + (g >> 2)) * 16 + t * 4;
          asm volatile("" : "+l"(z1d), "+l"(zd));
          wgmma_wait<0>();
          if (__builtin_expect(any_nan(acc[0], acc[2]), 0)) {
            SLOW(2 + L);
            uint4* const rd = g_RD + bid * (36 * 256) + tid;
            const uint8_t* xr = P.xs[L + 1] + (128 * rb + 32 * q + 2 * g + w) * (DM * 2) + t * 4;
#pragma unroll
            for (int i = 0; i < 32; i++) acc[i] = 0.f;
            redo<KS3, 8, 16, DM * 32, FH * 32, 16>(acc, xr, (const uint8_t*)P.w_in + g * (FH * 4) + (((9 * j + 1) >> 1) + 36) * 128 + t * 4,
                                              [&](uint32_t* a, int k) {
#pragma unroll
                                                for (int e = 0; e < 4; e++) a[e] = hfma2(a[e], (e & 1) ? ns1 : ns0, (e & 1) ? nb1 : nb0);
                                                stg128(rd + k * 256, a[0], a[1], a[2], a[3]);
                                              });
#pragma unroll
            for (int k = 0; k < 36; k++) { const uint4 v = ldcg128(rd + k * 256); xA[k][0] = v.x; xA[k][1] = v.y; xA[k][2] = v.z; xA[k][3] = v.w; }
          }
        }
        float sm[4] = {0.f, 0.f, 0.f, 0.f}, qq[4] = {0.f, 0.f, 0.f, 0.f};
        auto gelu = [&](auto nz2) {
          constexpr int NZ2 = nz2.value, R = 8 - NZ2, D = NZ2 == 8 ? GM2 : NZ2 ? GMM : GM1;
          float th[32], gb = GB;
          uint32_t qa = 0, qb = 0;
          auto head = [&](int G) {
#pragma unroll
            for (int e = 0; e < 4; e++) { const float v = acc[4 * G + e]; th[4 * G + e] = tanh_fast(v * fmaf(v, v, gb)); }
          };
#pragma unroll
          for (int i = 0; i < D; i++) head((i + R) & 7);
#pragma unroll
          for (int i = 0; i < 8; i++) {
            const int G = (i + R) & 7;
            if (i + D < 8) head((i + D + R) & 7);
            float* z = acc + 4 * G;
#pragma unroll
            for (int e = 0; e < 4; e++) z[e] = fmaf(z[e], th[4 * G + e], z[e]);
            uint32_t pa = pack2(z[0], z[1]), pb = pack2(z[2], z[3]), tok;
            if (i < NZ2) {
#pragma unroll
              for (int e = 0; e < 4; e++) { sm[e] += z[e]; qq[e] = fmaf(z[e], z[e], qq[e]); }
              pa = hsub2(pa, off2); pb = hsub2(pb, off2);
              stg32(zd + i * 128, pa); stg32(zd + i * 128 + 9216, pb);
              tok = pa ^ pb ^ __float_as_uint(qq[1]);
            } else {
              if (G & 1) stg128(z1d + (G >> 1) * 2048 + (NZ2 ? 32768 : 0), qa, qb, pa, pb);
              qa = pa; qb = pb;
              tok = pa ^ pb;
            }
            gb = __uint_as_float(tok * P.zero + __float_as_uint(GB));
          }
        };
#pragma unroll 1
        for (int p = 0;; p++) {
          wgmma_wait<0>();
          release(c.s);
          c.next();
          TRC(tr && p == 4, w, tb + 7);
          TRC(tr && p == 8, w, tb + 11);
          MCLK(p == 8, 6);
          SCLK(2 * p + 1);
          QCLK(10 + 3 * p);
          if (p < 4) {
            gelu(Int<8>{});
            zd += 1024;
          } else if (p == 4) {
            gelu(Int<4>{});
            signal(EV_ZN);
            const float a0 = qsum(sm[0] + sm[1]), a1 = qsum(sm[2] + sm[3]), q0 = qsum(qq[0] + qq[1]), q1 = qsum(qq[2] + qq[3]);
            const float ss = t ? a1 : a0, m = ss * (1.f / 288.f);
            ll_st128_if(t < 2, g_ZST + (rb * 2 + w) * 512 + j * 64 + 16 * q + 8 * t + g, m - blo(off2), fmaxf((t ? q1 : q0) - ss * m, 0.f), tag);
            TRC(tr, w, tb + 8);
            TRC(tr, w, tb + 9);
          } else {
            gelu(Int<0>{});
            z1d += 8192;
          }
          SCLK(2 * p + 2);
          QCLK(11 + 3 * p);
          if (p == 8) break;
          bwait(p == 3 ? 0x80000040u : 0x40000040u, w);
          bar_sync(6 + w, 256);
          TRC(tr && p == 4, w, tb + 10);
          wgmma_fence();
#pragma unroll
          for (int kk = 0; kk < 36; kk++) mma(kk, PP3, w == 0 || p < 7);
        }
        signal(EV_Z1);
        TRC(tr, w, tb + 12);
      }
      uint32_t hA[18][4];
      {
        float acc[144];
        const float c0 = __uint_as_float(lds32(sb + SM_OFF + 4));
#pragma unroll
        for (int i = 0; i < 144; i++) {
          asm volatile("fma.rn.f32 %0, %1, %2, %3;" : "=f"(acc[i]) : "f"(__uint_as_float(P.zero)), "f"((float)(i + 2)), "f"(c0));
        }
        uint32_t prev = 0;
        auto stage = [&](int kb) {
          mbar_wait_c(bars + B_FULL + c.s * 8, c.ph);
          TRC(tr && kb == 0, w, tb + 13);
          SCLK(22 + kb);
          const uint32_t st = sb + c.s * ST_BYTES, rt = sb + SM_RT + kb * 128 + t * 8;
          uint64_t db = dsc2(dlo(st + ST_B, 4608), 0, 8 + P.zero);
          uint32_t a[4][4];
#pragma unroll
          for (int kk = 0; kk < 4; kk++) {
            uint32_t r[4];
            ldsm4(r, st + (aoff ^ (kk << 5)));
            const uint2 sc = lds64(rt + kk * 32);
            a[kk][0] = hmul2(__byte_perm(r[0], r[2], 0x5410), sc.x); a[kk][2] = hmul2(__byte_perm(r[0], r[2], 0x7632), sc.y);
            a[kk][1] = hmul2(__byte_perm(r[1], r[3], 0x5410), sc.x); a[kk][3] = hmul2(__byte_perm(r[1], r[3], 0x7632), sc.y);
          }
          if (LAG4 && (kb & 1) == (LAG4 & 1)) yield(32 - kb, LAG4);
          wgmma_fence();
#pragma unroll
          for (int i = 0; i < 8; i++) {
            const int kk = i & 3, hf = i >> 2;
            wgmma_rs_n144(acc + hf * 72, a[kk], db, 1);
            dadd(db, i == 3 ? 144u - 3 * 576 : 576 + P.zero);
            if (i == 0) { wgmma_commit(); wgmma_wait<1>(); release_if(kb, prev); }
            if (i == 3) wgmma_commit();
          }
          wgmma_commit();
          prev = c.s; c.next();
        };
        mbar_wait_c(bars + B_RT, L);
#pragma unroll 1
        for (int kb = 0; kb < 32; kb += 2) {
          if (kb == 8) mbar_wait_c(bars + B_RT1, L);
          MCLK((kb & 7) == 4, 10 + (kb >> 3));
          stage(kb);
          stage(kb + 1);
        }
        if (LAG4) { yield_done(); lagph ^= 1; }
        if (w == 1) bar_arrive(6, 256);
        HCLK(0);
        mbar_wait_c(bars + B_CV + w * 8, L);
        HCLK(1);
        const float gk = 0.5f / GA;
        const float c1 = __uint_as_float(lds32(sb + SM_OFF + 4));
        const float gb0 = -gk * (c1 + __uint_as_float(lds32(sb + SM_CV + w * 256 + (16 * q + g) * 4))), gb1 = -gk * (c1 + __uint_as_float(lds32(sb + SM_CV + w * 256 + (16 * q + g + 8) * 4)));
        mbar_wait_c(w ? bars + B_ZB : bars + B_FULL + c.s * 8, w ? L : c.ph);
        HCLK(2);
        const uint32_t sx = c.s;
        c.next();
        const uint32_t zt = sb + (tid & 127) * 16, zs0 = zt + sx * ST_BYTES + w * ZB, zs1 = w ? zt + SM_STG - 16384 : zs0, zs2 = w ? zt + c.s * ST_BYTES - 20480 : zs0;
#pragma unroll
        for (int u = 0; u < 18; u++) {
          if (u == 0) { wgmma_wait<1>(); HCLK(3); }
          if (u == 9) {
            HCLK(4);
            wgmma_wait<0>();
            HCLK(5);
            release(prev);
            if (L == 0) signal(EV_P4);
            if (w == 1) mbar_wait_c(bars + B_FULL + c.s * 8, c.ph);
            TRC(tr, w, tb + 14);
            SCLK(54);
          }
          const uint4 z = lds128((u < 8 ? zs0 : u < 10 ? zs1 : zs2) + u * 2048);
          hA[u][0] = hmul2(z.x, pack2(fmaf(acc[8 * u], gk, gb0), fmaf(acc[8 * u + 1], gk, gb0)));
          hA[u][1] = hmul2(z.y, pack2(fmaf(acc[8 * u + 2], gk, gb1), fmaf(acc[8 * u + 3], gk, gb1)));
          hA[u][2] = hmul2(z.z, pack2(fmaf(acc[8 * u + 4], gk, gb0), fmaf(acc[8 * u + 5], gk, gb0)));
          hA[u][3] = hmul2(z.w, pack2(fmaf(acc[8 * u + 6], gk, gb1), fmaf(acc[8 * u + 7], gk, gb1)));
        }
        uint32_t dep = P.zero;
#pragma unroll
        for (int u = 0; u < 18; u++) dep &= hA[u][0];
        release(sx, dep);
        TRC(tr, w, tb + 15);
        HCLK(6);
      }
      {
        CLK_INIT;
        uint32_t pk[16];
#pragma unroll
        for (int i = 0; i < 16; i++) pk[i] = 0u;
        auto dump = [&](int p) {
          const uint32_t d = sb + (p & 3) * ST_BYTES, cb = p + j >= 9 ? p + j - 9 : p + j;
          if (lane == 0) asm volatile("cp.async.bulk.wait_group.read 3;" ::: "memory");
          __syncwarp();
#pragma unroll
          for (int u = 0; u < 4; u++) stsm4(d + (aoff ^ (u << 5)), pk[4 * u], pk[4 * u + 1], pk[4 * u + 2], pk[4 * u + 3]);
          fence_async_s();
          __syncwarp();
          tma3d_red_p(lane == 0, &P.red[L], cb * 64, rb * 64 + q * 16, w, d + w * 8192 + q * 2048);
        };
#pragma unroll 1
        for (int p = 0; p < 9; p++) {
          float acc[32];
          CLK(0);
          mbar_wait_c(bars + B_FULL + c.s * 8, c.ph);
          uint64_t db = dsc2(dlo(sb + c.s * ST_BYTES + ST_B + (j & 1) * 4096, 0), 0, 0x40000040u + P.zero);
          CLK(1);
          HCLK(7 + 2 * p);
          bar_sync(6 + w, 256);
          CLK(2);
          wgmma_fence();
#pragma unroll
          for (int kk = 0; kk < 18; kk++) {
            wgmma_rs_n64(acc, hA[kk], db, kk != 0);
            dadd(db, kk == 15 ? 128 - (j & 1) * (36864 >> 4) : 128 + P.zero);
            if (kk == PPK && (w == 0 || p < 8)) bar_arrive(7 - w, 256);
          }
          wgmma_commit();
          CLK(3);
          if (p > 0) dump(p - 1);
          CLK(5);
          wgmma_wait<0>();
          CLK(4);
          HCLK(8 + 2 * p);
          MCLK(p == 1 || p == 8, 7 + (p >> 3));
          release_if(L == 0 || p < 5, c.s);
          c.next();
#pragma unroll
          for (int i = 0; i < 16; i++) pk[i] = pack2(acc[2 * i], acc[2 * i + 1]);
          if (p == 8) { TRC(tr, w, tb + 16); dump(8); TRC(tr, w, tb + 17); }
        }
        if (lane == 0) asm volatile("cp.async.bulk.wait_group 0;" ::: "memory");
        HCLK(25);
        MCLK(1, 9);
        if (L == 0) signal(EV_PT);
        CLK_OUT;
        TRC(tr, w, tb + 18);
      }
    }
    if ((tid & 127) == 0) g_flags[(rb * 2 + w) * 32 + FR_EP + j] = epoch + 1;
    if (tid == 0) g_flags[FJ + j * 32 + FJ_EP + rb] = epoch + 1;
  }
}

typedef CUresult (*EncodeFn)(CUtensorMap*, CUtensorMapDataType, cuuint32_t, void*, const cuuint64_t*, const cuuint64_t*, const cuuint32_t*,
                             const cuuint32_t*, CUtensorMapInterleave, CUtensorMapSwizzle, CUtensorMapL2promotion, CUtensorMapFloatOOBfill);

static void make_map(EncodeFn fn, CUtensorMap* m, const void* ptr, int rank, uint64_t d0, uint64_t d1, uint64_t d2, uint64_t s1, uint64_t s2,
                     uint32_t b0, uint32_t b1, uint32_t b2, CUtensorMapSwizzle swz) {
  cuuint64_t dims[3] = {d0, d1, d2}, strides[2] = {s1, s2};
  cuuint32_t box[3] = {b0, b1, b2}, es[3] = {1, 1, 1};
  fn(m, CU_TENSOR_MAP_DATA_TYPE_BFLOAT16, rank, const_cast<void*>(ptr), dims, strides, box, es, CU_TENSOR_MAP_INTERLEAVE_NONE, swz,
     CU_TENSOR_MAP_L2_PROMOTION_L2_128B, CU_TENSOR_MAP_FLOAT_OOB_FILL_NONE);
}

}

extern "C" void kernel_launch(void* const* d_in, const int* in_sizes, int n_in, void* d_out, int out_size) {
  using namespace mk;
  (void)in_sizes; (void)n_in; (void)out_size;
  static EncodeFn fn = nullptr;
  static uint8_t *wq, *xb;
  static float* csp;
  if (!fn) {
    cudaGetSymbolAddress((void**)&wq, g_WQ);
    cudaGetSymbolAddress((void**)&xb, g_X);
    cudaGetSymbolAddress((void**)&csp, g_CSP);
    cudaDriverEntryPointQueryResult qr;
    cudaGetDriverEntryPoint("cuTensorMapEncodeTiled", (void**)&fn, cudaEnableDefault, &qr);
    cudaFuncSetAttribute(mega_kernel, cudaFuncAttributeMaxDynamicSharedMemorySize, SM_TOTAL);
  }
  Params p;
  p.wqkv = (const __nv_bfloat16*)d_in[1];
  p.wo = (const __nv_bfloat16*)d_in[2];
  p.w_in = (const __nv_bfloat16*)d_in[4];
  p.w_sp = (const __nv_bfloat16*)d_in[5];
  p.b_sp = (const __nv_bfloat16*)d_in[6];
  p.w_out = (const __nv_bfloat16*)d_in[7];
  p.zero = 0;
  p.wq = wq;
  p.csp = csp;
  p.xs[0] = (uint8_t*)d_in[0];
  p.xs[1] = xb;
  p.xs[2] = (uint8_t*)d_out;
  make_map(fn, &p.wsp, p.w_sp, 3, 2048, 1024, 2, 8192, 4096, 64, 64, 2, CU_TENSOR_MAP_SWIZZLE_128B);
  for (int i = 0; i < 2; i++) {
    make_map(fn, &p.red[i], p.xs[i + 1], 3, DM, 1024, 2, 2304, 1152, 64, 16, 1, CU_TENSOR_MAP_SWIZZLE_128B);
    make_map(fn, &p.res[i], p.xs[i], 3, DM, 1024, 2, 2304, 1152, 144, 64, 1, CU_TENSOR_MAP_SWIZZLE_NONE);
  }
  make_map(fn, &p.psn, d_out, 3, DM, 1024, 2, 2304, 1152, 144, 4, 1, CU_TENSOR_MAP_SWIZZLE_NONE);
  for (int i = 0; i < 3; i++) make_map(fn, &p.act[i], p.xs[i], 3, DM, 1024, 2, 2304, 1152, 64, 64, 1, CU_TENSOR_MAP_SWIZZLE_128B);
  for (int i = 0; i < 2; i++) {
    cuuint64_t dims[4] = {i ? 4608u : 2304u, 8, i ? 1u : 2u, 72}, strides[3] = {9216, 4608, 8 * 9216};
    cuuint32_t box[4] = {i ? 64u : 32u, 8, i ? 1u : 2u, 18}, es[4] = {1, 1, 1, 1};
    fn(i ? &p.win64 : &p.win, CU_TENSOR_MAP_DATA_TYPE_BFLOAT16, 4, d_in[4], dims, strides, box, es, CU_TENSOR_MAP_INTERLEAVE_NONE,
       i ? CU_TENSOR_MAP_SWIZZLE_128B : CU_TENSOR_MAP_SWIZZLE_64B, CU_TENSOR_MAP_L2_PROMOTION_L2_128B, CU_TENSOR_MAP_FLOAT_OOB_FILL_NONE);
  }
  make_map(fn, &p.wout, p.w_out, 2, 576, 2304, 1, 1152, 0, 64, 144, 1, CU_TENSOR_MAP_SWIZZLE_128B);
  mega_kernel<<<NGRID, 384, SM_TOTAL, cudaStreamPerThread>>>(p);
}
```

```cpp
#include <cuda_runtime.h>
#include <cuda.h>
#include <cuda_bf16.h>
#include <stdint.h>

#define MK_TRACE 0
#define MK_DBG 0
#define P5TRACE 0
#define LAG1 2
#define PP3 32
#define PP30 33
#define LAG4 1
#define SPL 2
#define NAP 200
#define NAP0 8000
#define KS2 2
#define KS3 2
#define RL3 21
#define PAD 0
#define GM2 3
#define GMM 1
#define GM1 2
#define C0S 32.f
#define OFM 0x10u
#define PPK 13

namespace mk {

constexpr int SEQ = 2048, DM = 576, FH = 2304;
constexpr int NCTA = 128;
constexpr int NGRID = 132;
constexpr uint32_t ZB = 36864;
constexpr uint32_t WQ_SL = 72 * 3456;
constexpr uint32_t WO_SL = 72 * 1152;
constexpr float LN_EPS = 1e-5f;
constexpr float GA = 0.3292034911525734f, GB = 2.423681954311584f;

constexpr uint32_t ST_BYTES = 53248, ST_B = 16384, NST = 4;
constexpr uint32_t SM_STG = NST * ST_BYTES;
constexpr uint32_t SM_BAR = SM_STG + 2 * 9216;
constexpr uint32_t SM_OFF = SM_BAR + 1008;
constexpr uint32_t SM_TOTAL = SM_BAR + 1024;
constexpr uint32_t SM_RT = SM_STG + 4096, SM_CV = SM_STG + 12288, SM_WT = SM_CV + 512;
constexpr uint32_t SM_WOI = 44032, SM_CSQ = 49792, SM_XST = 50688;
constexpr uint32_t B_FULL = 0, B_EMPTY = 32, B_FULLA = 64, B_RES = 128, B_WT = 144, B_IMG = 160, B_WOI = 168, B_ZB = 176, B_GATE3 = 184, B_Z1 = 192, B_LAG = 200,
                   B_RT = 208, B_CSQ = 216, B_CV = 224, B_AD = 240, B_EVT = 272, B_RT1 = 368, B_XRW = 384, B_FA3 = 400, B_EA3 = 544;
enum { EV_PT = 0, EV_O = 1, EV_X1 = 2, EV_ZN = 3, EV_Z1 = 4, EV_P4 = 5, EV_N = 6 };

enum { FR_X2 = 0, FR_O = 1, FR_X1 = 3, FR_EP = 16, FJ = 32 * 32, FJ_WQ = 0, FJ_WO = 1, FJ_WQ0 = 2, FJ_ZN = 3, FJ_P4 = 5, FJ_EP = 16, F_N = FJ + 8 * 32 };

__device__ __align__(1024) uint8_t g_Z[512 * ZB];
constexpr uint32_t POISON = 0xffffffffu;
__device__ __align__(1024) uint8_t g_O[32 * 2 * ZB];
__device__ __align__(1024) uint4 g_RD[NCTA * 36 * 256];
__device__ __align__(1024) uint8_t g_X[SEQ * DM * 2];
#define SLOW(i) do {} while (0)
__device__ __align__(1024) uint8_t g_WQ[8 * WQ_SL];
__device__ __align__(1024) uint8_t g_WO[8 * WO_SL];
__device__ __align__(1024) float g_CSP[2 * NCTA * 216];
__device__ __align__(1024) uint2 g_RT[SEQ];
__device__ __align__(1024) uint4 g_XST[2 * SEQ];
__device__ __align__(1024) uint4 g_ST1[SEQ * 8];
__device__ __align__(1024) uint4 g_ZST[SEQ * 8];
__device__ __align__(1024) uint4 g_HALO[32 * 8 * 6 * 32];
__device__ __align__(1024) uint32_t g_flags[F_N];

struct Params {
  const __nv_bfloat16 *wqkv;
  uint8_t* wq;
  float* csp;
  uint32_t zero;
  const __nv_bfloat16 *w_in, *w_sp, *b_sp, *w_out;
  uint8_t* xs[3];
  CUtensorMap wo8, wsp, win, win64, wout;
  CUtensorMap act[3];
  CUtensorMap res[2];
  CUtensorMap red[2];
  CUtensorMap psn;
};

__device__ __forceinline__ uint32_t smem_u32(const void* p) { return (uint32_t)__cvta_generic_to_shared(p); }
__device__ __forceinline__ void mbar_init(uint32_t bar, uint32_t cnt) { asm volatile("mbarrier.init.shared::cta.b64 [%0], %1;" ::"r"(bar), "r"(cnt)); }
__device__ __forceinline__ void mbar_arrive(uint32_t bar) { asm volatile("mbarrier.arrive.shared::cta.b64 _, [%0];" ::"r"(bar) : "memory"); }
__device__ __forceinline__ void mbar_wait(uint32_t bar, uint32_t parity) {
  asm volatile(
      "{\n.reg .pred p;\n.reg .u32 c;\nmov.u32 c, 0;\nLAB_WAIT:\n"
      "mbarrier.try_wait.parity.shared::cta.b64 p, [%0], %1;\n@p bra LAB_DONE;\n"
      "add.u32 c, c, 1;\nsetp.lt.u32 p, c, 0x100000;\n@p bra LAB_WAIT;\ntrap;\nLAB_DONE:\n}" ::"r"(bar), "r"(parity)
      : "memory");
}
__device__ __forceinline__ void mbar_wait_c(uint32_t bar, uint32_t parity) {
  asm volatile("{\n.reg .pred p;\nLAB_WAIT:\nmbarrier.try_wait.parity.shared::cta.b64 p, [%0], %1;\n@!p bra LAB_WAIT;\n}" ::"r"(bar), "r"(parity) : "memory");
}
__device__ __forceinline__ void flag_wait(const uint32_t* f, uint32_t target) {
  asm volatile(
      "{\n.reg .pred p;\n.reg .u32 c, v;\nmov.u32 c, 0;\nLAB_WAIT:\n"
      "ld.relaxed.gpu.global.u32 v, [%0];\nsub.u32 v, v, %1;\nsetp.ge.s32 p, v, 0;\n@p bra LAB_DONE;\n"
      "add.u32 c, c, 1;\nsetp.lt.u32 p, c, 0x400000;\n@p bra LAB_WAIT;\ntrap;\nLAB_DONE:\nfence.acquire.gpu;\n}" ::"l"(f), "r"(target)
      : "memory");
}
__device__ __forceinline__ void fence_gpu() { asm volatile("fence.acq_rel.gpu;" ::: "memory"); }
__device__ __forceinline__ void fence_async_g() { asm volatile("fence.proxy.async.global;" ::: "memory"); }
__device__ __forceinline__ void fence_async_s() { asm volatile("fence.proxy.async.shared::cta;" ::: "memory"); }
__device__ __forceinline__ uint32_t elect_one() {
  uint32_t p; asm volatile("{\n.reg .pred P;\nelect.sync _|P, 0xffffffff;\nselp.u32 %0, 1, 0, P;\n}" : "=r"(p)); return p;
}
__device__ __forceinline__ void expect_tx_p(uint32_t el, uint32_t bar, uint32_t bytes) {
  asm volatile("{\n.reg .pred P;\nsetp.ne.u32 P, %2, 0;\n@P mbarrier.arrive.expect_tx.shared::cta.b64 _, [%0], %1;\n}" ::"r"(bar), "r"(bytes), "r"(el) : "memory");
}
__device__ __forceinline__ void bulk_load_p(uint32_t el, uint32_t dst, const void* src, uint32_t bytes, uint32_t bar) {
  asm volatile("{\n.reg .pred P;\nsetp.ne.u32 P, %4, 0;\n@P cp.async.bulk.shared::cluster.global.mbarrier::complete_tx::bytes [%0], [%1], %2, [%3];\n}" ::"r"(dst), "l"(src), "r"(bytes), "r"(bar), "r"(el) : "memory");
}
__device__ __forceinline__ uint64_t policy_evict_first() { uint64_t p; asm("createpolicy.fractional.L2::evict_first.b64 %0, 1.0;" : "=l"(p)); return p; }
__device__ __forceinline__ void bulk_load_h(uint32_t el, uint32_t dst, const void* src, uint32_t bytes, uint32_t bar, bool ef, uint64_t pol) {
  if (ef) {
    asm volatile("{\n.reg .pred P;\nsetp.ne.u32 P, %4, 0;\n@P cp.async.bulk.shared::cluster.global.mbarrier::complete_tx::bytes.L2::cache_hint [%0], [%1], %2, [%3], %5;\n}" ::"r"(dst), "l"(src), "r"(bytes), "r"(bar), "r"(el), "l"(pol) : "memory");
  } else {
    asm volatile("{\n.reg .pred P;\nsetp.ne.u32 P, %4, 0;\n@P cp.async.bulk.shared::cluster.global.mbarrier::complete_tx::bytes [%0], [%1], %2, [%3];\n}" ::"r"(dst), "l"(src), "r"(bytes), "r"(bar), "r"(el) : "memory");
  }
}
__device__ __forceinline__ void bulk_mc_h(uint32_t el, uint32_t dst, const void* src, uint32_t bytes, uint32_t bar, bool ef, uint64_t pol) {
  if (ef) {
    asm volatile("{\n.reg .pred P;\nsetp.ne.u32 P, %4, 0;\n@P cp.async.bulk.shared::cluster.global.mbarrier::complete_tx::bytes.multicast::cluster.L2::cache_hint [%0], [%1], %2, [%3], %5, %6;\n}" ::"r"(dst), "l"(src), "r"(bytes), "r"(bar), "r"(el), "h"((uint16_t)3), "l"(pol) : "memory");
  } else {
    asm volatile("{\n.reg .pred P;\nsetp.ne.u32 P, %4, 0;\n@P cp.async.bulk.shared::cluster.global.mbarrier::complete_tx::bytes.multicast::cluster [%0], [%1], %2, [%3], %5;\n}" ::"r"(dst), "l"(src), "r"(bytes), "r"(bar), "r"(el), "h"((uint16_t)3) : "memory");
  }
}
__device__ __forceinline__ void tma3d_h(uint32_t el, uint32_t dst, const CUtensorMap* m, int c0, int c1, int c2, uint32_t bar, bool ef, uint64_t pol) {
  if (ef) {
    asm volatile("{\n.reg .pred P;\nsetp.ne.u32 P, %6, 0;\n@P cp.async.bulk.tensor.3d.shared::cluster.global.mbarrier::complete_tx::bytes.L2::cache_hint [%0], [%1, {%3, %4, %5}], [%2], %7;\n}" ::"r"(dst), "l"(m), "r"(bar), "r"(c0), "r"(c1), "r"(c2), "r"(el), "l"(pol) : "memory");
  } else {
    asm volatile("{\n.reg .pred P;\nsetp.ne.u32 P, %6, 0;\n@P cp.async.bulk.tensor.3d.shared::cluster.global.mbarrier::complete_tx::bytes [%0], [%1, {%3, %4, %5}], [%2];\n}" ::"r"(dst), "l"(m), "r"(bar), "r"(c0), "r"(c1), "r"(c2), "r"(el) : "memory");
  }
}
__device__ __forceinline__ void tma2d_mc_h(uint32_t el, uint32_t dst, const CUtensorMap* m, int c0, int c1, uint32_t bar, bool ef, uint64_t pol) {
  if (ef) {
    asm volatile("{\n.reg .pred P;\nsetp.ne.u32 P, %5, 0;\n@P cp.async.bulk.tensor.2d.shared::cluster.global.mbarrier::complete_tx::bytes.multicast::cluster.L2::cache_hint [%0], [%1, {%3, %4}], [%2], %6, %7;\n}" ::"r"(dst), "l"(m), "r"(bar), "r"(c0), "r"(c1), "r"(el), "h"((uint16_t)3), "l"(pol) : "memory");
  } else {
    asm volatile("{\n.reg .pred P;\nsetp.ne.u32 P, %5, 0;\n@P cp.async.bulk.tensor.2d.shared::cluster.global.mbarrier::complete_tx::bytes.multicast::cluster [%0], [%1, {%3, %4}], [%2], %6;\n}" ::"r"(dst), "l"(m), "r"(bar), "r"(c0), "r"(c1), "r"(el), "h"((uint16_t)3) : "memory");
  }
}
__device__ __forceinline__ void tma4d_mc(uint32_t el, uint32_t dst, const CUtensorMap* m, int c0, int c3, uint32_t bar, uint64_t pol) {
  asm volatile("{\n.reg .pred P;\nsetp.ne.u32 P, %5, 0;\n@P cp.async.bulk.tensor.4d.shared::cluster.global.mbarrier::complete_tx::bytes.multicast::cluster.L2::cache_hint [%0], [%1, {%3, 0, 0, %4}], [%2], %6, %7;\n}" ::"r"(dst), "l"(m), "r"(bar), "r"(c0), "r"(c3), "r"(el), "h"((uint16_t)3), "l"(pol) : "memory");
}
__device__ __forceinline__ void mbar_arrive_cluster(uint32_t addr) { asm volatile("mbarrier.arrive.shared::cluster.b64 _, [%0];" ::"r"(addr) : "memory"); }
__device__ __forceinline__ void mbar_arrive_cluster_if(bool c, uint32_t addr) {
  asm volatile("{\n.reg .pred P;\nsetp.ne.u32 P, %1, 0;\n@P mbarrier.arrive.shared::cluster.b64 _, [%0];\n}" ::"r"(addr), "r"((uint32_t)c) : "memory");
}
__device__ __forceinline__ void mbar_arrive_if(bool c, uint32_t addr) {
  asm volatile("{\n.reg .pred P;\nsetp.ne.u32 P, %1, 0;\n@P mbarrier.arrive.shared::cta.b64 _, [%0];\n}" ::"r"(addr), "r"((uint32_t)c) : "memory");
}
__device__ __forceinline__ uint32_t mapa(uint32_t addr, uint32_t rank) { uint32_t r; asm("mapa.shared::cluster.u32 %0, %1, %2;" : "=r"(r) : "r"(addr), "r"(rank)); return r; }
__device__ __forceinline__ void bulk_store_p(uint32_t el, void* dst, uint32_t src, uint32_t bytes) {
  asm volatile("{\n.reg .pred P;\nsetp.ne.u32 P, %3, 0;\n@P cp.async.bulk.global.shared::cta.bulk_group [%0], [%1], %2;\n}" ::"l"(dst), "r"(src), "r"(bytes), "r"(el) : "memory");
}
__device__ __forceinline__ void flag_release_p(uint32_t el, uint32_t* f) {
  asm volatile("{\n.reg .pred P;\nsetp.ne.u32 P, %1, 0;\n@P red.release.gpu.global.add.u32 [%0], 1;\n}" ::"l"(f), "r"(el) : "memory");
}
__device__ __forceinline__ void flag_add_p(uint32_t el, uint32_t* f) {
  asm volatile("{\n.reg .pred P;\nsetp.ne.u32 P, %1, 0;\n@P red.relaxed.gpu.global.add.u32 [%0], 1;\n}" ::"l"(f), "r"(el) : "memory");
}
__device__ __forceinline__ void prefetch_l2(const void* src, uint32_t bytes) { asm volatile("cp.async.bulk.prefetch.L2.global [%0], %1;" ::"l"(src), "r"(bytes) : "memory"); }
__device__ __forceinline__ void prefetch_map(const CUtensorMap* m) { asm volatile("prefetch.tensormap [%0];" ::"l"(m) : "memory"); }
__device__ __forceinline__ void wgmma_fence() { asm volatile("wgmma.fence.sync.aligned;" ::: "memory"); }
__device__ __forceinline__ void wgmma_commit() { asm volatile("wgmma.commit_group.sync.aligned;" ::: "memory"); }
template <int N> __device__ __forceinline__ void wgmma_wait() { asm volatile("wgmma.wait_group.sync.aligned %0;" ::"n"(N) : "memory"); }
__device__ __forceinline__ uint32_t dlo(uint32_t addr, uint32_t lbo) { return ((addr & 0x3FFFF) >> 4) + ((lbo >> 4) << 16); }
template <uint32_t SBO, uint32_t SWZ> __device__ __forceinline__ uint64_t dsc(uint32_t lo, uint32_t off) {
  uint64_t d; asm("mov.b64 %0, {%1, %2};" : "=l"(d) : "r"(lo + (off >> 4)), "n"((SBO >> 4) | (SWZ << 30))); return d;
}
__device__ __forceinline__ uint64_t dsc2(uint32_t lo, uint32_t off, uint32_t hi) {
  uint64_t d; asm("mov.b64 %0, {%1, %2};" : "=l"(d) : "r"(lo + (off >> 4)), "r"(hi)); return d;
}
__device__ __forceinline__ uint64_t dat(uint64_t d, uint32_t off, uint32_t one) { uint64_t r; asm("mad.wide.u32 %0, %1, %2, %3;" : "=l"(r) : "r"(one), "r"(off >> 4), "l"(d)); return r; }
__device__ __forceinline__ void dadd(uint64_t& d, uint32_t v) {
  asm("{\n.reg .b32 lo, hi;\nmov.b64 {lo, hi}, %0;\nadd.u32 lo, lo, %1;\nmov.b64 %0, {lo, hi};\n}" : "+l"(d) : "r"(v));
}
template <int R> __device__ __forceinline__ void reg_alloc() { asm volatile("setmaxnreg.inc.sync.aligned.u32 %0;" ::"n"(R)); }
template <int R> __device__ __forceinline__ void reg_dealloc() { asm volatile("setmaxnreg.dec.sync.aligned.u32 %0;" ::"n"(R)); }
__device__ __forceinline__ void bar_sync(int id, int n) { asm volatile("bar.sync %0, %1;" ::"r"(id), "r"(n) : "memory"); }
__device__ __forceinline__ void bar_arrive(int id, int n) { asm volatile("bar.arrive %0, %1;" ::"r"(id), "r"(n) : "memory"); }
__device__ __forceinline__ void ldsm4(uint32_t* r, uint32_t addr) {
  asm volatile("ldmatrix.sync.aligned.m8n8.x4.shared.b16 {%0,%1,%2,%3}, [%4];" : "=r"(r[0]), "=r"(r[1]), "=r"(r[2]), "=r"(r[3]) : "r"(addr) : "memory");
}
__device__ __forceinline__ uint32_t movm(uint32_t a) { uint32_t d; asm volatile("movmatrix.sync.aligned.m8n8.trans.b16 %0, %1;" : "=r"(d) : "r"(a)); return d; }
__device__ __forceinline__ void mma16(float* c, uint32_t a0, uint32_t a1, uint32_t a2, uint32_t a3, uint32_t b0, uint32_t b1) {
  asm volatile("mma.sync.aligned.m16n8k16.row.col.f32.bf16.bf16.f32 {%0,%1,%2,%3}, {%4,%5,%6,%7}, {%8,%9}, {%10,%10,%10,%10};"
               : "=f"(c[0]), "=f"(c[1]), "=f"(c[2]), "=f"(c[3]) : "r"(a0), "r"(a1), "r"(a2), "r"(a3), "r"(b0), "r"(b1), "f"(0.f));
}
__device__ __forceinline__ void mma8(float* c, uint32_t a0, uint32_t a1, uint32_t b0) {
  asm volatile("mma.sync.aligned.m16n8k8.row.col.f32.bf16.bf16.f32 {%0,%1,%2,%3}, {%4,%5}, {%6}, {%0,%1,%2,%3};"
               : "+f"(c[0]), "+f"(c[1]), "+f"(c[2]), "+f"(c[3]) : "r"(a0), "r"(a1), "r"(b0));
}
__device__ __forceinline__ uint32_t pack2(float lo, float hi) { uint32_t r; asm("cvt.rn.bf16x2.f32 %0, %1, %2;" : "=r"(r) : "f"(hi), "f"(lo)); return r; }
__device__ __forceinline__ float blo(uint32_t v) { return __uint_as_float(v << 16); }
__device__ __forceinline__ float bhi(uint32_t v) { return __uint_as_float(v & 0xffff0000u); }
__device__ __forceinline__ float tanh_fast(float x) { float y; asm("tanh.approx.f32 %0, %1;" : "=f"(y) : "f"(x)); return y; }
__device__ __forceinline__ float rcp_fast(float x) { float y; asm("rcp.approx.ftz.f32 %0, %1;" : "=f"(y) : "f"(x)); return y; }
__device__ __forceinline__ float ex2(float x) { float y; asm("ex2.approx.ftz.f32 %0, %1;" : "=f"(y) : "f"(x)); return y; }
__device__ __forceinline__ float qsum(float v) { v += __shfl_xor_sync(~0u, v, 1); v += __shfl_xor_sync(~0u, v, 2); return v; }
__device__ __forceinline__ float qmax(float v) { v = fmaxf(v, __shfl_xor_sync(~0u, v, 1)); v = fmaxf(v, __shfl_xor_sync(~0u, v, 2)); return v; }
__device__ __forceinline__ void stg32(void* p, uint32_t v) { asm volatile("st.global.u32 [%0], %1;" ::"l"(p), "r"(v) : "memory"); }
__device__ __forceinline__ void stg128(void* p, uint32_t a, uint32_t b, uint32_t c, uint32_t d) { asm volatile("st.global.v4.u32 [%0], {%1,%2,%3,%4};" ::"l"(p), "r"(a), "r"(b), "r"(c), "r"(d) : "memory"); }
__device__ __forceinline__ uint32_t ldcg32(const void* p) { uint32_t v; asm volatile("ld.global.L1::no_allocate.u32 %0, [%1];" : "=r"(v) : "l"(p) : "memory"); return v; }
__device__ __forceinline__ uint32_t ldgpu32(const void* p) { uint32_t v; asm volatile("ld.relaxed.gpu.global.u32 %0, [%1];" : "=r"(v) : "l"(p) : "memory"); return v; }
__device__ __forceinline__ uint32_t ldca32(const void* p) { uint32_t v; asm volatile("ld.global.ca.u32 %0, [%1];" : "=r"(v) : "l"(p) : "memory"); return v; }
__device__ __forceinline__ void stg128_if(bool c, void* p, uint32_t a, uint32_t b, uint32_t cc, uint32_t d) {
  asm volatile("{\n.reg .pred P;\nsetp.ne.u32 P, %5, 0;\n@P st.global.v4.u32 [%0], {%1,%2,%3,%4};\n}" ::"l"(p), "r"(a), "r"(b), "r"(cc), "r"(d), "r"((uint32_t)c) : "memory");
}
__device__ __forceinline__ uint2 lds64(uint32_t a) { uint2 v; asm volatile("ld.shared.v2.u32 {%0,%1}, [%2];" : "=r"(v.x), "=r"(v.y) : "r"(a) : "memory"); return v; }
__device__ __forceinline__ uint4 ldcg128(const void* p) { uint4 v; asm volatile("ld.global.cg.v4.u32 {%0,%1,%2,%3}, [%4];" : "=r"(v.x), "=r"(v.y), "=r"(v.z), "=r"(v.w) : "l"(p) : "memory"); return v; }
__device__ __forceinline__ uint32_t ldnc16(const void* p) { uint16_t v; asm volatile("ld.global.nc.u16 %0, [%1];" : "=h"(v) : "l"(p)); return v; }
__device__ __forceinline__ uint4 ldnc128(const void* p) { uint4 v; asm volatile("ld.global.nc.v4.u32 {%0,%1,%2,%3}, [%4];" : "=r"(v.x), "=r"(v.y), "=r"(v.z), "=r"(v.w) : "l"(p)); return v; }
__device__ __forceinline__ uint32_t hsub2(uint32_t a, uint32_t b) { uint32_t d; asm("sub.rn.bf16x2 %0, %1, %2;" : "=r"(d) : "r"(a), "r"(b)); return d; }
__device__ __forceinline__ void stg32_if(bool c, void* p, uint32_t v) {
  asm volatile("{\n.reg .pred P;\nsetp.ne.u32 P, %2, 0;\n@P st.global.u32 [%0], %1;\n}" ::"l"(p), "r"(v), "r"((uint32_t)c) : "memory");
}
__device__ __forceinline__ uint32_t hmul2(uint32_t a, uint32_t b) { uint32_t d; asm("mul.rn.bf16x2 %0, %1, %2;" : "=r"(d) : "r"(a), "r"(b)); return d; }
__device__ __forceinline__ void sts32(uint32_t a, uint32_t v) { asm volatile("st.shared.u32 [%0], %1;" ::"r"(a), "r"(v) : "memory"); }
__device__ __forceinline__ uint32_t lds32(uint32_t a) { uint32_t v; asm volatile("ld.shared.u32 %0, [%1];" : "=r"(v) : "r"(a) : "memory"); return v; }
__device__ __forceinline__ void sts128(uint32_t a, uint32_t x, uint32_t y, uint32_t z, uint32_t w) { asm volatile("st.shared.v4.u32 [%0], {%1,%2,%3,%4};" ::"r"(a), "r"(x), "r"(y), "r"(z), "r"(w) : "memory"); }
__device__ __forceinline__ uint4 lds128(uint32_t a) { uint4 v; asm volatile("ld.shared.v4.u32 {%0,%1,%2,%3}, [%4];" : "=r"(v.x), "=r"(v.y), "=r"(v.z), "=r"(v.w) : "r"(a) : "memory"); return v; }
__device__ __forceinline__ void ll_st64(uint2* p, uint32_t v, uint32_t tag) {
  asm volatile("{\n.reg .b64 r;\nmov.b64 r, {%1,%2};\nst.relaxed.gpu.global.b64 [%0], r;\n}" ::"l"(p), "r"(v), "r"(tag) : "memory");
}
__device__ __forceinline__ uint2 ll_ld64(const uint2* p) {
  uint2 v; asm volatile("{\n.reg .b64 r;\nld.relaxed.gpu.global.b64 r, [%2];\nmov.b64 {%0,%1}, r;\n}" : "=r"(v.x), "=r"(v.y) : "l"(p) : "memory"); return v;
}
__device__ __forceinline__ void ll_st128(uint4* p, float a, float b, uint32_t tag, float c = 0.f) {
  asm volatile("{\n.reg .b128 r;\n.reg .b64 lo, hi;\nmov.b64 lo, {%1,%2};\nmov.b64 hi, {%3,%4};\nmov.b128 r, {lo, hi};\nst.relaxed.gpu.global.b128 [%0], r;\n}" ::"l"(p), "r"(__float_as_uint(a)), "r"(__float_as_uint(b)), "r"(tag), "r"(__float_as_uint(c)) : "memory");
}
__device__ __forceinline__ uint4 ll_ld128(const uint4* p) {
  uint4 v; asm volatile("{\n.reg .b128 r;\n.reg .b64 lo, hi;\nld.relaxed.gpu.global.b128 r, [%4];\nmov.b128 {lo, hi}, r;\nmov.b64 {%0,%1}, lo;\nmov.b64 {%2,%3}, hi;\n}" : "=r"(v.x), "=r"(v.y), "=r"(v.z), "=r"(v.w) : "l"(p) : "memory"); return v;
}
__device__ __forceinline__ void publish_p(uint32_t el, uint32_t* f) {
  asm volatile("{\n.reg .pred P;\nsetp.ne.u32 P, %1, 0;\n@P cp.async.bulk.commit_group;\n@P cp.async.bulk.wait_group 0;\n@P red.release.gpu.global.add.u32 [%0], 1;\n}" ::"l"(f), "r"(el) : "memory");
}
__device__ __forceinline__ void tma3d_red_p(uint32_t el, const CUtensorMap* m, int c0, int c1, int c2, uint32_t src) {
  asm volatile("{\n.reg .pred P;\nsetp.ne.u32 P, %5, 0;\n@P cp.reduce.async.bulk.tensor.3d.global.shared::cta.add.tile.bulk_group [%0, {%2, %3, %4}], [%1];\n@P cp.async.bulk.commit_group;\n}" ::"l"(m), "r"(src), "r"(c0), "r"(c1), "r"(c2), "r"(el) : "memory");
}
__device__ __forceinline__ void stsm4(uint32_t addr, uint32_t a, uint32_t b, uint32_t c, uint32_t d) {
  asm volatile("stmatrix.sync.aligned.m8n8.x4.shared.b16 [%0], {%1,%2,%3,%4};" ::"r"(addr), "r"(a), "r"(b), "r"(c), "r"(d) : "memory");
}
__device__ __forceinline__ void sts64(uint32_t a, uint32_t x, uint32_t y) { asm volatile("st.shared.v2.u32 [%0], {%1,%2};" ::"r"(a), "r"(x), "r"(y) : "memory"); }
__device__ __forceinline__ void ll_st128_if(bool on, uint4* p, float a, float b, uint32_t tag) {
  asm volatile("{\n.reg .pred P;\n.reg .b128 r;\n.reg .b64 lo, hi;\nsetp.ne.u32 P, %4, 0;\nmov.b64 lo, {%1,%2};\nmov.b64 hi, {%3,%3};\nmov.b128 r, {lo, hi};\n@P st.relaxed.gpu.global.b128 [%0], r;\n}" ::"l"(p), "r"(__float_as_uint(a)), "r"(__float_as_uint(b)), "r"(tag), "r"((uint32_t)on) : "memory");
}
__device__ __forceinline__ uint4 ldnc128_if(bool c, const void* p) {
  uint4 v = make_uint4(0u, 0u, 0u, 0u);
  asm volatile("{\n.reg .pred P;\nsetp.ne.u32 P, %5, 0;\n@P ld.global.nc.v4.u32 {%0,%1,%2,%3}, [%4];\n}" : "+r"(v.x), "+r"(v.y), "+r"(v.z), "+r"(v.w) : "l"(p), "r"((uint32_t)c));
  return v;
}
__device__ __forceinline__ uint32_t hfma2(uint32_t a, uint32_t b, uint32_t c) { uint32_t d; asm("fma.rn.bf16x2 %0, %1, %2, %3;" : "=r"(d) : "r"(a), "r"(b), "r"(c)); return d; }
__device__ __forceinline__ float2 lds64f(uint32_t a) { float2 v; asm volatile("ld.shared.v2.f32 {%0,%1}, [%2];" : "=f"(v.x), "=f"(v.y) : "r"(a) : "memory"); return v; }
#define TRC(cond, role, idx) do {} while (0)
#define TRV(role, idx, v) do {} while (0)

#define ACLK_INIT do {} while (0)
#define ACLK(i) do {} while (0)
#define ACLK_OUT do {} while (0)
#define QCLK(i) do {} while (0)
#define PH 1
#define RCLK(i) do {} while (0)
#define RCLK_INIT do {} while (0)
#define RCLK_OUT do {} while (0)
#define SCLK(i) do {} while (0)
#define HCLK(i) do {} while (0)
#define MCLK(c, i) do {} while (0)
#define CKK(i) do {} while (0)
#define CKK_OUT do {} while (0)
#define PL 1
#define PCLK(i) do {} while (0)
#define PQ 1
#define CLK_INIT do {} while (0)
#define CLK(i) do {} while (0)
#define CLK_OUT do {} while (0)

__device__ __forceinline__ void wgmma_ss_n216(float* d, uint64_t da, uint64_t db, int scaleD) {
  asm volatile("{\n.reg .pred p;\nsetp.ne.b32 p, %110, 0;\nwgmma.mma_async.sync.aligned.m64n216k16.f32.bf16.bf16 "
    "{%0,%1,%2,%3,%4,%5,%6,%7,%8,%9,%10,%11,%12,%13,%14,%15,%16,%17,%18,%19,%20,%21,%22,%23,%24,%25,%26,%27,%28,%29,%30,%31,%32,%33,%34,%35,%36,%37,%38,%39,%40,%41,%42,%43,%44,%45,%46,%47,%48,%49,%50,%51,%52,%53,%54,%55,%56,%57,%58,%59,%60,%61,%62,%63,%64,%65,%66,%67,%68,%69,%70,%71,%72,%73,%74,%75,%76,%77,%78,%79,%80,%81,%82,%83,%84,%85,%86,%87,%88,%89,%90,%91,%92,%93,%94,%95,%96,%97,%98,%99,%100,%101,%102,%103,%104,%105,%106,%107}, "
    "%108, %109, p, 1, 1, 0, 1;\n}\n"
    : "+f"(d[0]), "+f"(d[1]), "+f"(d[2]), "+f"(d[3]), "+f"(d[4]), "+f"(d[5]), "+f"(d[6]), "+f"(d[7]), "+f"(d[8]), "+f"(d[9]), "+f"(d[10]), "+f"(d[11]), "+f"(d[12]), "+f"(d[13]), "+f"(d[14]), "+f"(d[15]), "+f"(d[16]), "+f"(d[17]), "+f"(d[18]), "+f"(d[19]), "+f"(d[20]), "+f"(d[21]), "+f"(d[22]), "+f"(d[23]), "+f"(d[24]), "+f"(d[25]), "+f"(d[26]), "+f"(d[27]), "+f"(d[28]), "+f"(d[29]), "+f"(d[30]), "+f"(d[31]), "+f"(d[32]), "+f"(d[33]), "+f"(d[34]), "+f"(d[35]), "+f"(d[36]), "+f"(d[37]), "+f"(d[38]), "+f"(d[39]), "+f"(d[40]), "+f"(d[41]), "+f"(d[42]), "+f"(d[43]), "+f"(d[44]), "+f"(d[45]), "+f"(d[46]), "+f"(d[47]), "+f"(d[48]), "+f"(d[49]), "+f"(d[50]), "+f"(d[51]), "+f"(d[52]), "+f"(d[53]), "+f"(d[54]), "+f"(d[55]), "+f"(d[56]), "+f"(d[57]), "+f"(d[58]), "+f"(d[59]), "+f"(d[60]), "+f"(d[61]), "+f"(d[62]), "+f"(d[63]), "+f"(d[64]), "+f"(d[65]), "+f"(d[66]), "+f"(d[67]), "+f"(d[68]), "+f"(d[69]), "+f"(d[70]), "+f"(d[71]), "+f"(d[72]), "+f"(d[73]), "+f"(d[74]), "+f"(d[75]), "+f"(d[76]), "+f"(d[77]), "+f"(d[78]), "+f"(d[79]), "+f"(d[80]), "+f"(d[81]), "+f"(d[82]), "+f"(d[83]), "+f"(d[84]), "+f"(d[85]), "+f"(d[86]), "+f"(d[87]), "+f"(d[88]), "+f"(d[89]), "+f"(d[90]), "+f"(d[91]), "+f"(d[92]), "+f"(d[93]), "+f"(d[94]), "+f"(d[95]), "+f"(d[96]), "+f"(d[97]), "+f"(d[98]), "+f"(d[99]), "+f"(d[100]), "+f"(d[101]), "+f"(d[102]), "+f"(d[103]), "+f"(d[104]), "+f"(d[105]), "+f"(d[106]), "+f"(d[107])
    : "l"(da), "l"(db), "r"(scaleD));
}
__device__ __forceinline__ void wgmma_ss_n72(float* d, uint64_t da, uint64_t db, int scaleD) {
  asm volatile("{\n.reg .pred p;\nsetp.ne.b32 p, %38, 0;\nwgmma.mma_async.sync.aligned.m64n72k16.f32.bf16.bf16 "
    "{%0,%1,%2,%3,%4,%5,%6,%7,%8,%9,%10,%11,%12,%13,%14,%15,%16,%17,%18,%19,%20,%21,%22,%23,%24,%25,%26,%27,%28,%29,%30,%31,%32,%33,%34,%35}, "
    "%36, %37, p, 1, 1, 0, 1;\n}\n"
    : "+f"(d[0]), "+f"(d[1]), "+f"(d[2]), "+f"(d[3]), "+f"(d[4]), "+f"(d[5]), "+f"(d[6]), "+f"(d[7]), "+f"(d[8]), "+f"(d[9]), "+f"(d[10]), "+f"(d[11]), "+f"(d[12]), "+f"(d[13]), "+f"(d[14]), "+f"(d[15]), "+f"(d[16]), "+f"(d[17]), "+f"(d[18]), "+f"(d[19]), "+f"(d[20]), "+f"(d[21]), "+f"(d[22]), "+f"(d[23]), "+f"(d[24]), "+f"(d[25]), "+f"(d[26]), "+f"(d[27]), "+f"(d[28]), "+f"(d[29]), "+f"(d[30]), "+f"(d[31]), "+f"(d[32]), "+f"(d[33]), "+f"(d[34]), "+f"(d[35])
    : "l"(da), "l"(db), "r"(scaleD));
}
__device__ __forceinline__ void wgmma_rs_n144(float* d, const uint32_t* a, uint64_t db, int scaleD) {
  asm volatile("{\n.reg .pred p;\nsetp.ne.b32 p, %77, 0;\nwgmma.mma_async.sync.aligned.m64n144k16.f32.bf16.bf16 "
    "{%0,%1,%2,%3,%4,%5,%6,%7,%8,%9,%10,%11,%12,%13,%14,%15,%16,%17,%18,%19,%20,%21,%22,%23,%24,%25,%26,%27,%28,%29,%30,%31,%32,%33,%34,%35,%36,%37,%38,%39,%40,%41,%42,%43,%44,%45,%46,%47,%48,%49,%50,%51,%52,%53,%54,%55,%56,%57,%58,%59,%60,%61,%62,%63,%64,%65,%66,%67,%68,%69,%70,%71}, "
    "{%72,%73,%74,%75}, %76, p, 1, 1, 1;\n}\n"
    : "+f"(d[0]), "+f"(d[1]), "+f"(d[2]), "+f"(d[3]), "+f"(d[4]), "+f"(d[5]), "+f"(d[6]), "+f"(d[7]), "+f"(d[8]), "+f"(d[9]), "+f"(d[10]), "+f"(d[11]), "+f"(d[12]), "+f"(d[13]), "+f"(d[14]), "+f"(d[15]), "+f"(d[16]), "+f"(d[17]), "+f"(d[18]), "+f"(d[19]), "+f"(d[20]), "+f"(d[21]), "+f"(d[22]), "+f"(d[23]), "+f"(d[24]), "+f"(d[25]), "+f"(d[26]), "+f"(d[27]), "+f"(d[28]), "+f"(d[29]), "+f"(d[30]), "+f"(d[31]), "+f"(d[32]), "+f"(d[33]), "+f"(d[34]), "+f"(d[35]), "+f"(d[36]), "+f"(d[37]), "+f"(d[38]), "+f"(d[39]), "+f"(d[40]), "+f"(d[41]), "+f"(d[42]), "+f"(d[43]), "+f"(d[44]), "+f"(d[45]), "+f"(d[46]), "+f"(d[47]), "+f"(d[48]), "+f"(d[49]), "+f"(d[50]), "+f"(d[51]), "+f"(d[52]), "+f"(d[53]), "+f"(d[54]), "+f"(d[55]), "+f"(d[56]), "+f"(d[57]), "+f"(d[58]), "+f"(d[59]), "+f"(d[60]), "+f"(d[61]), "+f"(d[62]), "+f"(d[63]), "+f"(d[64]), "+f"(d[65]), "+f"(d[66]), "+f"(d[67]), "+f"(d[68]), "+f"(d[69]), "+f"(d[70]), "+f"(d[71])
    : "r"(a[0]), "r"(a[1]), "r"(a[2]), "r"(a[3]), "l"(db), "r"(scaleD));
}
__device__ __forceinline__ void wgmma_rs_n64(float* d, const uint32_t* a, uint64_t db, int scaleD) {
  asm volatile("{\n.reg .pred p;\nsetp.ne.b32 p, %37, 0;\nwgmma.mma_async.sync.aligned.m64n64k16.f32.bf16.bf16 "
    "{%0,%1,%2,%3,%4,%5,%6,%7,%8,%9,%10,%11,%12,%13,%14,%15,%16,%17,%18,%19,%20,%21,%22,%23,%24,%25,%26,%27,%28,%29,%30,%31}, "
    "{%32,%33,%34,%35}, %36, p, 1, 1, 1;\n}\n"
    : "+f"(d[0]), "+f"(d[1]), "+f"(d[2]), "+f"(d[3]), "+f"(d[4]), "+f"(d[5]), "+f"(d[6]), "+f"(d[7]), "+f"(d[8]), "+f"(d[9]), "+f"(d[10]), "+f"(d[11]), "+f"(d[12]), "+f"(d[13]), "+f"(d[14]), "+f"(d[15]), "+f"(d[16]), "+f"(d[17]), "+f"(d[18]), "+f"(d[19]), "+f"(d[20]), "+f"(d[21]), "+f"(d[22]), "+f"(d[23]), "+f"(d[24]), "+f"(d[25]), "+f"(d[26]), "+f"(d[27]), "+f"(d[28]), "+f"(d[29]), "+f"(d[30]), "+f"(d[31])
    : "r"(a[0]), "r"(a[1]), "r"(a[2]), "r"(a[3]), "l"(db), "r"(scaleD));
}

template <int V> struct Int { static constexpr int value = V; };
struct Cur {
  uint32_t s, ph;
  __device__ __forceinline__ void next() { if (++s == NST) { s = 0; ph ^= 1; } }
};

__device__ __forceinline__ uint8_t* z1_block(int rb, int w, int j) { return g_Z + (rb * 16 + w * 8 + j) * ZB; }
__device__ __forceinline__ uint8_t* o_block(int rb, int w) { return g_O + (rb * 2 + w) * (2 * ZB); }
__device__ __forceinline__ uint8_t* z2_block(int kb, int j) { return g_Z + (256 + kb * 8 + j) * ZB; }
__device__ __forceinline__ void combine8(float m0, float q0, float m1, float q1, float n, float eps, float& mean, float& rstd) {
  mean = qsum(m0 + m1) * 0.125f;
  float d0 = m0 - mean, d1 = m1 - mean;
  float M2 = qsum(q0 + q1 + n * (d0 * d0 + d1 * d1));
  rstd = rsqrtf(fmaf(M2, 0.125f / n, eps));
}
__device__ __forceinline__ void stat_get(const uint4* zs, uint32_t tag, float n, float eps, float& m0, float& r0, float& m1, float& r1) {
  uint4 a0, a1, b0, b1;
#pragma unroll 1
  for (int it = 0; it < (1 << 20); it++) {
    a0 = ll_ld128(zs); a1 = ll_ld128(zs + 64); b0 = ll_ld128(zs + 8); b1 = ll_ld128(zs + 72);
    if (__all_sync(~0u, a0.z == tag && a1.z == tag && b0.z == tag && b1.z == tag)) break;
  }
  combine8(__uint_as_float(a0.x), __uint_as_float(a0.y), __uint_as_float(a1.x), __uint_as_float(a1.y), n, eps, m0, r0);
  combine8(__uint_as_float(b0.x), __uint_as_float(b0.y), __uint_as_float(b1.x), __uint_as_float(b1.y), n, eps, m1, r1);
}

__device__ __forceinline__ void rows_fetch(uint32_t el, uint32_t xr, const uint8_t* src, uint32_t bar) {
  expect_tx_p(el, bar, 9216);
#pragma unroll 1
  for (int r = 0; r < 8; r++) bulk_load_p(el, xr + r * 1152, src + r * (DM * 4), 1152, bar);
}
__device__ __forceinline__ void rows_stats(uint32_t xr, uint4* dst, uint32_t tag, int lane) {
  float s[2] = {0.f, 0.f}, q[4] = {0.f, 0.f, 0.f, 0.f};
  const uint32_t a0 = xr + (lane >> 2) * 1152 + (((lane & 3) * 2) ^ (lane >> 2)) * 16;
  uint4 n0 = lds128(a0), n1 = lds128(a0 ^ 16);
#pragma unroll 1
  for (int e = 1; e <= 9; e++) {
    const uint32_t x[8] = {n0.x, n0.y, n0.z, n0.w, n1.x, n1.y, n1.z, n1.w};
    if (e < 9) { n0 = lds128(a0 + e * 128); n1 = lds128((a0 ^ 16) + e * 128); }
#pragma unroll
    for (int u = 0; u < 8; u++) {
      const float lo = blo(x[u]), hi = bhi(x[u]);
      s[u & 1] += lo + hi; q[(u & 1) * 2] = fmaf(lo, lo, q[(u & 1) * 2]); q[(u & 1) * 2 + 1] = fmaf(hi, hi, q[(u & 1) * 2 + 1]);
    }
  }
  const float sx = s[0] + s[1], sq = (q[0] + q[1]) + (q[2] + q[3]);
  const float m = qsum(sx) * (-1.f / DM), r = rsqrtf(fmaxf(fmaf(qsum(sq), 1.f / DM, -m * m), 0.f) + LN_EPS);
  if ((lane & 3) == 0) ll_st128(dst + (lane >> 2) * 2, m, r, tag);
}

__device__ __forceinline__ void poison(uint32_t el, uint32_t src, const CUtensorMap* m, int rb, int j, int lane) {
#pragma unroll 1
  for (int u = lane; u < 72; u += 32) sts128(src + u * 16, POISON, POISON, POISON, POISON);
  fence_async_s();
  __syncwarp();
#pragma unroll 1
  for (int u = 0; u < 16; u++) {
    __nanosleep(NAP);
    bulk_store_p(el, o_block(rb, u >> 3) + j * 9216 + (u & 7) * 1152, src, 1152);
    asm volatile("{\n.reg .pred P;\nsetp.ne.u32 P, %5, 0;\n@P cp.async.bulk.tensor.3d.global.shared::cta.tile.bulk_group [%0, {%2, %3, %4}], [%1];\n}" ::"l"(m), "r"(src), "r"((j & 6) * 72), "r"(rb * 64 + u * 4), "r"(j & 1), "r"(el) : "memory");
  }
}
__device__ __forceinline__ void mma16acc(float* c, const uint32_t* a, uint32_t b0, uint32_t b1) {
  asm volatile("mma.sync.aligned.m16n8k16.row.col.f32.bf16.bf16.f32 {%0,%1,%2,%3}, {%4,%5,%6,%7}, {%8,%9}, {%0,%1,%2,%3};"
               : "+f"(c[0]), "+f"(c[1]), "+f"(c[2]), "+f"(c[3]) : "r"(a[0]), "r"(a[1]), "r"(a[2]), "r"(a[3]), "r"(b0), "r"(b1));
}
template <int KS, int NG, int AK, int AH, int BK, int BG, class F> __device__ __forceinline__ void redo(float* acc, const uint8_t* pa, const uint8_t* pb, F f) {
#pragma unroll 1
  for (int k = 0; k < 36; k += KS) {
    uint32_t a[4 * KS], b[2 * KS][NG];
#pragma unroll 1
    for (int it = 0; it < (1 << 20); it++) {
      bool ok = true;
#pragma unroll
      for (int e = 0; e < 4 * KS; e++) a[e] = ldgpu32(pa + (e >> 1) * AK + (e & 1) * AH);
#pragma unroll
      for (int e = 0; e < 2 * KS * NG; e++) b[e / NG][e % NG] = ldca32(pb + (e / NG) * BK + (e % NG) * BG);
#pragma unroll
      for (int e = 0; e < 4 * KS; e++) ok = ok && a[e] != POISON;
      if (__all_sync(~0u, ok)) break;
    }
#pragma unroll
    for (int e = 0; e < KS; e++) f(a + 4 * e, k + e);
#pragma unroll
    for (int e = 0; e < KS * NG; e++) mma16acc(acc + 4 * (e % NG), a + 4 * (e / NG), movm(b[2 * (e / NG)][e % NG]), movm(b[2 * (e / NG) + 1][e % NG]));
    pa += 2 * KS * AK; pb += 2 * KS * BK;
  }
}
__device__ __forceinline__ bool any_nan(float a, float b) {
  return __any_sync(~0u, a != a || b != b);
}

__global__ void __cluster_dims__(2, 1, 1) __launch_bounds__(384, 1) mega_kernel(const __grid_constant__ Params P) {
  extern __shared__ __align__(1024) uint8_t smem_raw[];
  uint32_t ckk[8];
  (void)ckk;
  CKK(0);
  const uint32_t sb = smem_u32(smem_raw);
  const uint32_t bars = sb + SM_BAR;
  const int tid = threadIdx.x;
  int lane = tid & 31;
  const int wid = __shfl_sync(~0u, tid >> 5, 0);
  const int cl = blockIdx.x >> 1, tp = cl - 36, t7 = (tp * 37) >> 8;
  const int bid = (cl < 4 ? cl * 8 + 32 : tp < 0 ? cl - 4 : cl < 64 ? tp + t7 + 33 : cl) * 2 + (blockIdx.x & 1);
  if (bid >= NCTA) return;
  const int rb = bid & 15, j = bid >> 4;
  { const bool tr = (tid & 127) == 0 && tid < 256; const int w = tid >> 7; (void)tr; (void)w; TRC(tr, w, 0); }
  CKK(1);
  uint4 wv[5];
  const uint8_t* wsrc;
  {
    const int n8 = min(tid >> 3, 26), part = n8 / 9;
    const uint8_t* src = (const uint8_t*)P.wqkv + (8 * rb + (tid & 7)) * (3 * DM * 2) + (part * (DM - 72) + 72 * j + 8 * n8) * 2;
#pragma unroll
    for (int u = 0; u < SPL; u++) wv[u] = ldnc128_if(tid < 216, src + u * (128 * 3 * DM * 2));
    wsrc = src;
  }
  CKK(2);
  if (tid == 352) {
    for (int s = 0; s < (int)NST; s++) {
      mbar_init(bars + B_FULL + s * 8, 1); mbar_init(bars + B_EMPTY + s * 8, 16);
      mbar_init(bars + B_FULLA + s * 8, 1); mbar_init(bars + B_FULLA + 32 + s * 8, 1);
      mbar_init(bars + B_RES + s * 8, 1); mbar_init(bars + B_RT + s * 8, 1); mbar_init(bars + B_AD + s * 8, 2);
    }
    mbar_init(bars + B_IMG, 8); mbar_init(bars + B_RES + 8, 8); mbar_init(bars + B_WOI, 1); mbar_init(bars + B_GATE3, 3); mbar_init(bars + B_Z1, 1); mbar_init(bars + B_ZB, 1); mbar_init(bars + B_LAG, 4);
    mbar_init(bars + B_CSQ, 3); mbar_init(bars + B_RT1, 1); mbar_init(bars + B_XRW, 1); mbar_init(bars + B_XRW + 8, 1);
    for (int e = 0; e < 2 * EV_N; e++) mbar_init(bars + B_EVT + e * 8, 4);
    asm volatile("fence.mbarrier_init.release.cluster;" ::: "memory");
  }
  if (tid == 320) {
#pragma unroll
    for (int e = 0; e < 28; e++) mbar_init(bars + B_FA3 + e * 8, e < 18 ? 1 : 4);
    asm volatile("fence.mbarrier_init.release.cluster;" ::: "memory");
  }
  __syncthreads();

  if (wid >= 8) {
    reg_dealloc<40>();
    const uint32_t el = elect_one();
    const uint64_t pol = policy_evict_first();
    uint32_t* const fj = g_flags + FJ + j * 32;
    if (wid == 8) {
#pragma unroll 1
      for (int i = 0; i < 12; i++) if (el) prefetch_map(&P.act[0] + (i < 7 ? i : i - 12));
      const uint32_t epoch = ldcg32(fj + FJ_EP + rb);
      Cur c{0, 1};
      const uint32_t rk = bid & 1;
      uint32_t st, full;
      auto slot = [&](uint32_t bytes) {
        st = sb + c.s * ST_BYTES; full = bars + B_FULL + c.s * 8;
        mbar_wait(full, c.ph);
        expect_tx_p(el, full, bytes);
        mbar_wait(full - B_FULL + B_EMPTY, c.ph);
      };
#pragma unroll 1
      for (int L = 0; L < 2; L++) {
#pragma unroll 1
        for (int i = 0; i < 14; i++) {
          if (L == 0 && (i == 0 || i == 2 * SPL || i == 9)) {
            flag_wait(fj + (i == 9 ? FJ_WO : i == 2 * SPL ? FJ_WQ : FJ_WQ0), (epoch + 1) * 16);
            if (i == 9) flag_wait(g_flags + FJ + (j ^ 1) * 32 + FJ_WO, (epoch + 1) * 16);
            fence_async_g();
            TRC(el, 2, i == 9 ? 46 : i ? 47 : 45);
          }
          const uint32_t hb = i < 9 ? 13824 : i < 13 ? 18432 : 9216, o = ST_B + rk * (i < 9 ? 13824 : 18432);
          const uint8_t* src = i < 9 ? g_WQ + j * WQ_SL + i * 27648 + rk * 13824 : g_WO + ((j & 6) + rk) * WO_SL + (i - 9) * 18432;
          slot(2 * hb);
          bulk_mc_h(el, st + o, src, hb, full, true, pol);
          c.next();
        }
#pragma unroll 1
        for (int i = 0; i < 18; i++) {
          const int p = i >> 1, col = p == 4 ? (9 * j + ((j & 1) ? 0 : 8)) * 32 : (((9 * j + 1) >> 1) + (p < 4 ? p + 36 : p - 5)) * 64;
          if (i & 1) {
            slot(2 * ZB);
          } else {
            st = sb + c.s * ST_BYTES; full = bars + B_FULL + ((c.s + 1) & 3) * 8;
            mbar_wait(bars + B_EMPTY + c.s * 8, c.ph);
          }
          tma4d_mc(el, st + ST_B + rk * 18432, p == 4 ? &P.win : &P.win64, col, (i & 1) * 36 + rk * 18, full, pol);
          if (el && !(i & 1)) mbar_arrive(bars + B_FULL + c.s * 8);
          c.next();
        }
        TRC(el, 2, L * 16 + 6);
        flag_wait(fj + FJ_ZN + L, (epoch + 1) * 16);
        fence_async_g();
        TRC(el, 2, L * 16 + 7);
#pragma unroll 1
        for (int i = 0; i < 32; i++) {
          const uint8_t* src = z2_block(i, j) + rk * 18432;
          if (i >= 4) mbar_wait(bars + B_AD + c.s * 8, ((i >> 2) & 1) ^ 1);
          slot(ST_BYTES);
          bulk_mc_h(el, st + ST_B + rk * 18432, src, 18432, full, true, pol);
          tma3d_h(el, st, &P.wsp, i * 64, rb * 64, 0, full, true, pol);
          c.next();
        }
        mbar_wait(bars + B_Z1, L);
        fence_async_g();
        expect_tx_p(el, bars + B_ZB, 20480);
        bulk_load_h(el, sb + SM_STG, z1_block(rb, 1, j) + 16384, 4096, bars + B_ZB, true, pol);
#pragma unroll 1
        for (int i = 0; i < 10; i++) {
          const int cb = i - 1 + j;
          if (i < 4) mbar_wait(bars + B_AD + c.s * 8, 1);
          slot(i == 1 ? ST_BYTES : ZB);
          if (i < 2) bulk_load_h(el, st, z1_block(rb, i, j) + i * 20480, ZB - i * 20480, full, true, pol);
          if (i == 0) bulk_load_h(el, st + ZB, z1_block(rb, 1, j), 16384, bars + B_ZB, true, pol);
          else tma2d_mc_h(el, st + ST_B + rk * 18432, &P.wout, (cb >= 9 ? cb - 9 : cb) * 64, 288 * j + rk * 144, full, true, pol);
          c.next();
        }
      }
    } else if (wid < 11) {
      int w = wid - 9;
      uint32_t* const fr = g_flags + (rb * 2 + w) * 32;
      const uint32_t epoch = ldcg32(fr + FR_EP + j);
      const uint32_t ev = bars + B_EVT + w * EV_N * 8, t8 = (epoch + 1) * 8;
      Cur c{0, 1};
#pragma unroll 1
      for (int L = 0; L < 2; L++) {
        {
          const uint32_t tag = epoch * 2 + L + 1;
          uint4* const xs = g_XST + (rb * 2 + w) * 128;
          if (L) {
            mbar_wait(ev + EV_PT * 8, 0);
            TRC(el, 3, w * 32 + 16);
            flag_release_p(el, fr + FR_X2);
            TRC(el, 3, w * 32 + 17);
          }
#pragma unroll 1
          for (int i = 0; i < 9; i++) {
            const uint32_t full = bars + B_FULLA + w * 32 + c.s * 8, dst = sb + c.s * ST_BYTES + w * 8192;
            if (L == 0 && i == 4) {
              mbar_wait(bars + B_WT + w * 8, 0);
              TRC(el && w == 0, 2, 37);
              rows_stats(sb + SM_STG + w * 9216, xs + 16 * j, tag, lane);
              TRC(el && w == 0, 2, 38);
            }
            const uint32_t src = sb + (L ? 2 * ST_BYTES + SM_WOI : SM_STG + w * 9216);
            if (i == 4) {
#pragma unroll
              for (int u = 0; u < 6; u++) sts128(src + u * 512 + lane * 16, POISON, POISON, POISON, POISON);
              fence_async_s();
              __syncwarp();
            }
            mbar_wait(bars + B_EMPTY + c.s * 8, c.ph);
            expect_tx_p(el, full, 8192);
            if (i < L) { flag_wait(fr + FR_X2, t8); fence_async_g(); }
            tma3d_h(el, dst, &P.act[L], i * 64, rb * 64, w, full, false, pol);
            TRC(el && i < L, 3, w * 32 + 18);
            c.next();
            if (i >= 4 && i < (L ? 5 : 8)) {
              int b = (rb * 2 + w) * 8 + j;
              asm volatile("" : "+r"(b));
              bulk_store_p(el, i == 4 ? (uint8_t*)g_HALO + b * 3072 : g_O + (b * 3 + i - 5) * 3072, src, 3072);
              if (i < 6) bulk_store_p(el, (i == 4 ? g_ST1 : g_ZST) + b * 64, src, 1024);
              if (i == 6) bulk_store_p(el, g_RT + b * 8, src, 64);
            }
            if (L == 0 && i == 3) rows_fetch(el, sb + SM_STG + w * 9216, P.xs[0] + (128 * rb + 16 * j + w) * (DM * 2), bars + B_WT + w * 8);
          }
          if (el) asm volatile("cp.async.bulk.commit_group;\ncp.async.bulk.wait_group 0;" ::: "memory");
          __syncwarp();
          if (L == 0) fence_gpu();
          const uint32_t tab = sb + L * (2 * ST_BYTES) + SM_XST + w * 512 + lane * 8;
          TRC(el, 3, w * 32 + L * 16 + 13);
#pragma unroll 1
          for (int it = 0; it < (1 << 22); it++) {
            const uint4 a = ll_ld128(xs + 2 * lane), b = ll_ld128(xs + 64 + 2 * lane);
            if (__all_sync(~0u, a.z == tag && b.z == tag)) { sts64(tab, a.x, a.y); sts64(tab + 256, b.x, b.y); break; }
          }
          __syncwarp();
          mbar_arrive_if(el, bars + B_CSQ);
          TRC(el, 3, w * 32 + L * 16 + 14);
          if (w == 1) {
            mbar_wait(bars + B_CSQ, L);
            expect_tx_p(el, bars + B_RES, 18432);
            tma3d_h(el, sb + SM_STG, &P.res[L], (j & 6) * 72, rb * 64, j & 1, bars + B_RES, !L, pol);
          }
          if (L) flag_wait(fj + FJ_P4, t8 * 4);
        }
        asm volatile("" : "+r"(w));
        uint32_t* const fo = g_flags + (rb * 2 + (j & 1)) * 32 + L;
        {
          const uint8_t* src = o_block(rb, j & 1) + w * 8192;
#pragma unroll 1
          for (int i = 0; i < 5; i++) {
            const uint32_t full = bars + B_FULLA + w * 32 + c.s * 8, dst = sb + c.s * ST_BYTES + w * 8192;
            const bool none = 2 * i + w > 8;
            mbar_wait(bars + B_EMPTY + c.s * 8, c.ph);
            expect_tx_p(el, full, none ? 0 : 8192);
            if (i == 0) {
              mbar_wait(ev + EV_O * 8, L);
              TRC(el, 3, w * 32 + L * 16 + 3);
              flag_add_p(el, fr + FR_O + L);
              TRC(el, 3, w * 32 + L * 16 + 4);
              flag_wait(fo + FR_O, t8);
              fence_async_g();
            }
            if (!none) bulk_load_h(el, dst, src + i * 16384, 8192, full, true, pol);
            TRC(el && i == 0, 3, w * 32 + L * 16 + 5);
            c.next();
          }
        }
        {
          expect_tx_p(lane < 9, bars + B_FA3 + (9 * w + lane) * 8, 8192);
          mbar_wait(ev + EV_X1 * 8, L);
          TRC(el, 3, w * 32 + L * 16 + 6);
          if (L) flag_add_p(el, fo + FR_X1); else flag_release_p(el, fo + FR_X1);
          mbar_arrive_if(el, bars + B_GATE3);
          TRC(el, 3, w * 32 + L * 16 + 7);
          mbar_arrive_if(lane < 2, bars + B_FULLA + w * 32 + ((c.s + lane) & 3) * 8);
#pragma unroll 1
          for (int kb = 0; kb < 9; kb++) {
            const int n = 9 * w + kb;
            const uint32_t dst = sb + ((n >> 1) & 3) * ST_BYTES + (n & 1) * 8192;
            if (kb == 0) { flag_wait(fr + FR_X1 + L, t8); fence_async_g(); }
            if (n >= 8) mbar_wait(bars + B_EA3 + (n - 8) * 8, L);
            tma3d_h(el, dst, &P.act[L + 1], kb * 64, rb * 64, w, bars + B_FA3 + n * 8, false, pol);
            TRC(el && kb == 0, 3, w * 32 + L * 16 + 8);
          }
          c.ph ^= ((c.s + 18) >> 2) & 1; c.s = (c.s + 18) & 3;
        }
        asm volatile("" : "+r"(lane), "+r"(w));
        expect_tx_p(el, bars + B_WT + w * 8, 2048);
#pragma unroll 1
        for (int r = 0; r < 8; r++)
          bulk_load_p(el, sb + SM_WT + w * 2176 + r * 272, (const uint8_t*)P.w_sp + (size_t)(128 * rb + 16 * j + 2 * r + w) * (SEQ * 2) + 30 * 128, 256, bars + B_WT + w * 8);
        float cv = (lane & 3) ? 0.f : -blo(ldnc16(P.b_sp + 128 * rb + 16 * j + 2 * (lane >> 2) + w));
        mbar_wait(bars + B_RT, L);
        mbar_wait(bars + B_WT + w * 8, L ^ 1);
        mbar_wait(ev + EV_Z1 * 8, L);
        const uint32_t ro = (w * 64 + 8 * j + (lane >> 2)) * 128, x0 = ((lane & 3) * 2) ^ (lane >> 2);
#pragma unroll 1
        for (int i = 0; i < 32; i++) {
          const bool tail = (i >> 1) == 4;
          const int kb = tail ? i + 22 : i < 8 ? i : i - 2;
          if (i == 8) mbar_wait(bars + B_RT1, L);
          if (!tail) mbar_wait(bars + B_FULL + c.s * 8, c.ph ^ 1);
#pragma unroll
          for (int e = 0; e < 2; e++) {
            const uint4 a = lds128(!tail ? sb + c.s * ST_BYTES + ro + ((x0 ^ e) << 4) : sb + SM_WT + w * 2176 + (lane >> 2) * 272 + (i - 8) * 128 + (lane & 3) * 32 + e * 16);
            const uint4 m = lds128(sb + SM_RT + 4096 + kb * 128 + (lane & 3) * 32 + e * 16);
            cv = fmaf(blo(a.x), blo(m.x), fmaf(bhi(a.x), bhi(m.x), fmaf(blo(a.y), blo(m.y), fmaf(bhi(a.y), bhi(m.y), cv))));
            cv = fmaf(blo(a.z), blo(m.z), fmaf(bhi(a.z), bhi(m.z), fmaf(blo(a.w), blo(m.w), fmaf(bhi(a.w), bhi(m.w), cv))));
          }
          if (!tail) {
            mbar_arrive_if(el, bars + B_AD + c.s * 8 + (__float_as_uint(cv) & P.zero));
            c.next();
          }
        }
        TRC(el, 3, w * 32 + L * 16 + 11);
        uint32_t tag = t8;
        asm volatile("" : "+r"(tag));
        tag = (tag >> 2) - 1 + L;
        cv = qsum(cv);
        uint2* const cs = (uint2*)(g_XST + (rb * 2 + w) * 128 + 1);
        if ((lane & 3) == 0) ll_st64(cs + 32 * j + (lane >> 2) * 4, __float_as_uint(cv), tag);
#pragma unroll 1
        for (int it = 0; it < (1 << 22); it++) {
          const uint2 a = ll_ld64(cs + 4 * lane), b = ll_ld64(cs + 128 + 4 * lane);
          if (__all_sync(~0u, a.y == tag && b.y == tag)) { sts32(sb + SM_CV + w * 256 + lane * 4, a.x); sts32(sb + SM_CV + w * 256 + 128 + lane * 4, b.x); break; }
        }
        __syncwarp();
        if (el) mbar_arrive(bars + B_CV + w * 8);
        TRC(el, 3, w * 32 + L * 16 + 12);
#pragma unroll 1
        for (int kb = 30; kb < 32; kb++) {
          mbar_wait(bars + B_FULL + c.s * 8, c.ph ^ 1);
          if (el) mbar_arrive(bars + B_AD + c.s * 8);
          c.next();
        }
        c.ph ^= ((c.s + 10) >> 2) & 1; c.s = (c.s + 10) & 3;
        if (L == 0) {
          mbar_wait(ev + EV_P4 * 8, 0);
          flag_add_p(el, fj + FJ_P4);
        }
      }
    } else {
      const uint32_t epoch = ldcg32(fj + FJ_EP + rb);
      if (SPL) {
        mbar_wait(bars + B_RES + 8, 0);
        TRC(el, 2, 41);
        flag_release_p(el, fj + FJ_WQ0);
        TRC(el, 2, 42);
      }
      mbar_wait(bars + B_IMG, 0);
      TRC(el, 2, 39);
      flag_release_p(el, fj + FJ_WQ);
      TRC(el, 2, 40);
#pragma unroll 1
      for (int L = 0; L < 2; L++) {
        auto wo_fetch = [&]() {
          expect_tx_p(el, bars + B_WOI, 5760);
          asm volatile("{\n.reg .pred P;\nsetp.ne.u32 P, %5, 0;\n@P cp.async.bulk.tensor.4d.shared::cluster.global.mbarrier::complete_tx::bytes [%0], [%1, {0, 0, %3, %4}], [%2];\n}" ::"r"(sb + SM_WOI), "l"(&P.wo8), "r"(bars + B_WOI), "r"(9 * j), "r"((9 * rb) >> 1), "r"(el) : "memory");
        };
        float* const csf = g_CSP + (NCTA + bid) * 216;
        if (L == 0) {
          flag_wait(fj + FJ_WQ, (epoch + 1) * 16);
          fence_async_g();
          expect_tx_p(el, bars + B_XRW, 13824);
          bulk_load_p(el, sb + ST_BYTES + SM_WOI, g_CSP + j * 16 * 216, 6912, bars + B_XRW);
          bulk_load_p(el, sb + 2 * ST_BYTES + SM_WOI, g_CSP + (j * 16 + 8) * 216, 6912, bars + B_XRW);
          wo_fetch();
          mbar_wait(bars + B_XRW, 0);
#pragma unroll 1
          for (int f = lane; f < 54; f += 32) {
            float s[4] = {0.f, 0.f, 0.f, 0.f};
#pragma unroll 4
            for (int r = 0; r < 16; r++) {
              const uint4 v = lds128(sb + ST_BYTES + SM_WOI + (r >> 3) * ST_BYTES + (r & 7) * 864 + f * 16);
              s[0] += __uint_as_float(v.x); s[1] += __uint_as_float(v.y); s[2] += __uint_as_float(v.z); s[3] += __uint_as_float(v.w);
            }
            sts128(sb + SM_CSQ + f * 16, __float_as_uint(s[0]), __float_as_uint(s[1]), __float_as_uint(s[2]), __float_as_uint(s[3]));
            stg128(csf + f * 4, __float_as_uint(s[0]), __float_as_uint(s[1]), __float_as_uint(s[2]), __float_as_uint(s[3]));
          }
          __syncwarp();
          mbar_arrive_if(el, bars + B_CSQ);
        } else {
#pragma unroll 1
          for (int u = 0; u < 4; u++) {
            const int w = u & 1;
            if (u < 2) {
              flag_wait(g_flags + (rb * 2 + w) * 32 + FR_X2, (epoch + 1) * 8);
              fence_async_g();
              TRC(el, 2, 48 + u);
              rows_fetch(el, sb + SM_STG + w * 9216, P.xs[1] + (128 * rb + 16 * j + w) * (DM * 2), bars + B_XRW + w * 8);
            } else {
              mbar_wait(bars + B_XRW + w * 8, w ^ 1);
              TRC(el, 2, 48 + u);
              rows_stats(sb + SM_STG + w * 9216, g_XST + (rb * 2 + w) * 128 + 16 * j, epoch * 2 + 2, lane);
              TRC(el, 2, 50 + u);
            }
          }
          expect_tx_p(el, bars + B_CSQ, 864);
          bulk_load_p(el, sb + 2 * ST_BYTES + SM_CSQ, csf, 864, bars + B_CSQ);
        }
        if (L == 0) {
          TRC(el, 2, 43);
          mbar_wait(bars + B_WOI, 0);
          bulk_store_p(el, g_WO + j * WO_SL + ((9 * rb) >> 1) * 1152, sb + SM_WOI, 5760);
          publish_p(el, fj + FJ_WO);
          TRC(el, 2, 44);
          const uint8_t* sp = lane < 16 ? (const uint8_t*)P.w_in + (30 * lane + 50) * (FH * 4) + FH * 2 + lane * 256 : (const uint8_t*)P.w_sp + (60 * lane) * (SEQ * 2) + lane * 64;
          float sq = 0.f;
#pragma unroll 1
          for (int u = 0; u < 4; u++) {
            const uint4 y = ldnc128(sp + u * 16);
            const uint32_t x[4] = {y.x, y.y, y.z, y.w};
#pragma unroll
            for (int e = 0; e < 4; e++) sq = fmaf(blo(x[e]), blo(x[e]), fmaf(bhi(x[e]), bhi(x[e]), sq));
          }
#pragma unroll 1
          for (int o = 8; o; o >>= 1) sq += __shfl_xor_sync(~0u, sq, o);
          sq *= lane < 16 ? 2.f * GA * GA * DM / 512.f : C0S * C0S * SEQ / 512.f;
          asm("sqrt.approx.f32 %0, %0;" : "+f"(sq));
          const float o0 = __shfl_sync(~0u, sq, 0), o1 = __shfl_sync(~0u, sq, 16);
          const uint32_t off = (__float_as_uint(o0) & 0x7f800000u) >> 16 | 0x8000u | OFM;
          if (el) sts64(sb + SM_OFF, off * 0x10001u, min(__float_as_uint(o1) & 0x7f800000u, 0x7e000000u) | 0x00400000u);
        }
        if (el) mbar_arrive(bars + B_GATE3);
        const uint32_t tag = epoch * 2 + L + 1;
        asm volatile("" : "+r"(lane));
        mbar_wait(bars + B_EVT + EV_ZN * 8, L);
        mbar_wait(bars + B_EVT + (EV_N + EV_ZN) * 8, L);
        flag_release_p(el, fj + FJ_ZN + L);
        TRC(el, 2, L * 16 + 8);
        {
          uint4 v[4];
#pragma unroll 1
          for (int it = 0; it < (1 << 22); it++) {
            bool ok = true;
#pragma unroll
            for (int u = 0; u < 4; u++) { v[u] = ll_ld128(g_ZST + (rb * 2 + ((lane >> 1) & 1)) * 512 + ((lane & 1) * 4 + u) * 64 + 8 * j + (lane >> 2)); ok = ok && v[u].z == tag; }
            if (__all_sync(~0u, ok)) break;
          }
          float mean = __uint_as_float(v[0].x) + __uint_as_float(v[1].x) + __uint_as_float(v[2].x) + __uint_as_float(v[3].x), M2 = 0.f;
          mean = (mean + __shfl_xor_sync(~0u, mean, 1)) * 0.125f;
#pragma unroll
          for (int u = 0; u < 4; u++) { const float d = __uint_as_float(v[u].x) - mean; M2 += fmaf(288.f * d, d, __uint_as_float(v[u].y)); }
          M2 += __shfl_xor_sync(~0u, M2, 1);
          const float rs = blo(pack2(rsqrtf(fmaf(M2, 1.f / FH, 4.f * GA * GA * LN_EPS)), 0.f));
          if (!(lane & 1)) ll_st64(g_RT + 128 * rb + 16 * j + (lane >> 1), pack2(rs, rs * mean), tag);
        }
        TRC(el, 2, L * 16 + 10);
#pragma unroll 1
        for (int b = 0; b < 8; b++) {
          uint4 v[4];
#pragma unroll 1
          for (int it = 0; it < (1 << 22); it++) {
            bool ok = true;
#pragma unroll
            for (int u = 0; u < 4; u++) { v[u] = ll_ld128((const uint4*)g_RT + b * 128 + u * 32 + lane); ok = ok && v[u].y == tag && v[u].w == tag; }
            if (__all_sync(~0u, ok)) break;
          }
#pragma unroll
          for (int u = 0; u < 4; u++) {
            const uint32_t rt = sb + SM_RT + b * 512 + u * 128, ro = (lane >> 3) * 32 + (lane & 3) * 8 + ((lane >> 2) & 1) * 2;
            sts32(rt + 4096 + lane * 4, __byte_perm(v[u].x, v[u].z, 0x7632));
            asm volatile("st.shared.u16 [%0], %1;\nst.shared.u16 [%0 + 4], %2;" ::"r"(rt + ro), "h"((uint16_t)v[u].x), "h"((uint16_t)v[u].z) : "memory");
          }
          __syncwarp();
          if (el && (b == 1 || b == 7)) mbar_arrive(bars + (b == 1 ? B_RT : B_RT1));
          TRC(el && b < 2, 2, L * 16 + 11 + b);
        }
        TRC(el, 2, L * 16 + 9);
        mbar_wait(bars + B_EVT + EV_Z1 * 8, L);
        mbar_wait(bars + B_EVT + (EV_N + EV_Z1) * 8, L);
        fence_gpu();
        if (el) mbar_arrive(bars + B_Z1);
        if (L == 0) {
          __nanosleep(NAP0);
          poison(el, sb + SM_STG + 17152, &P.psn, rb, j, lane);
          if (el) asm volatile("cp.async.bulk.commit_group;\ncp.async.bulk.wait_group 0;" ::: "memory");
          __syncwarp();
          fence_gpu();
        }
      }
    }
  } else {
    CKK(3);
    uint8_t* const wdst = P.wq + j * WQ_SL + rb * 3456 + tid * 16;
#pragma unroll
    for (int u = 0; u < SPL; u++) stg128_if(tid < 216, wdst + u * (16 * 3456), wv[u].x, wv[u].y, wv[u].z, wv[u].w);
    __syncwarp();
    if (lane == 0) mbar_arrive(bars + B_RES + 8);
    CKK(4);
    auto repack2 = [&]() {
#pragma unroll
      for (int u = SPL; u < 5; u++) stg128_if((u < 4 || rb < 8) && tid < 216, wdst + u * (16 * 3456), wv[u].x, wv[u].y, wv[u].z, wv[u].w);
      float s[8];
#pragma unroll
      for (int e = 0; e < 8; e++) s[e] = 0.f;
#pragma unroll
      for (int u = 0; u < 5; u++) {
        uint32_t x[4] = {wv[u].x, wv[u].y, wv[u].z, wv[u].w};
        asm volatile("" : "+r"(x[0]), "+r"(x[1]), "+r"(x[2]), "+r"(x[3]));
#pragma unroll
        for (int e = 0; e < 4; e++) { s[2 * e] += blo(x[e]); s[2 * e + 1] += bhi(x[e]); }
      }
#pragma unroll
      for (int m = 4; m; m >>= 1) {
#pragma unroll
        for (int e = 0; e < m; e++) s[e] = ((tid & m) ? s[e + m] : s[e]) + __shfl_xor_sync(~0u, (tid & m) ? s[e] : s[e + m], m);
      }
      stg32_if(tid < 216, P.csp + bid * 216 + tid, __float_as_uint(s[0]));
      __syncwarp();
      if (lane == 0) mbar_arrive(bars + B_IMG);
    };
    reg_alloc<232>();
    CKK(5);
#pragma unroll
    for (int v = SPL; v < 5; v++) wv[v] = ldnc128_if(tid < 216 && (v < 4 || rb < 8), wsrc + v * (128 * 3 * DM * 2));
    repack2();
    CKK(6);
    const int w = wid >> 2, q = wid & 3;
    int g = lane >> 2, t = lane & 3;
    const uint32_t ev = bars + B_EVT + w * EV_N * 8;
    const bool tr = (tid & 127) == 0;
    (void)tr;
    Cur c{0, 0};
    const uint32_t ebar = mapa(bars + B_EMPTY, (bid & 1) ^ (lane & 1));
    auto release = [&](uint32_t s, uint32_t dep = 0) { mbar_arrive_cluster_if(lane < 2, ebar + s * 8 + dep); };
    auto release_if = [&](bool on, uint32_t s) { mbar_arrive_cluster_if(lane < 2 && on, ebar + s * 8); };
    uint32_t ia = 0;
    auto wait_ab = [&]() { mbar_wait_c(bars + B_FULL + c.s * 8, c.ph); mbar_wait_c(bars + B_FULLA + w * 32 + c.s * 8, (ia >> 2) & 1); ia++; };
    uint32_t lagph = 0;
    auto yield = [&](int left, int lag) { if (w == 1 && left == lag) mbar_wait_c(bars + B_LAG, lagph); };
    auto yield_done = [&]() { if (w == 0 && lane == 0) mbar_arrive(bars + B_LAG); };
    auto signal = [&](int e) { __syncwarp(); if (lane == 0) mbar_arrive(ev + e * 8); };

    const uint32_t epoch = ldcg32(g_flags + (rb * 2 + w) * 32 + FR_EP + j);
    TRC(tr, w, 1);
    CKK(7);
    if (PAD && P.zero) {
#pragma unroll
      for (int i = 0; i < PAD; i++) asm volatile("st.shared.u32 [%0], %1;" ::"r"(sb + i * 20), "r"(tid) : "memory");
    }
    CKK_OUT;

#pragma unroll 1
    for (int L = 0; L < 2; L++) {
      const int tb = 2 + L * 24;
      asm volatile("" : "+r"(lane), "+r"(g), "+r"(t));
      (void)tb;
      ia = 0;
      const uint32_t tag = epoch * 2 + L + 1;
      uint32_t aoff = (w * 64 + q * 16 + (lane & 15)) * 128 + (((lane >> 4) ^ (lane & 7)) << 4);
      {
        uint32_t Pk[27][2];
        float sc0, sc1;
        const uint32_t att = sb + w * 8192 + q * 2048 + lane * 4;
        uint4* hp = g_HALO + ((((rb - (q == 0)) * 2 + w) * 8 + j) * 6) * 32 + lane;
        uint8_t* od = o_block(rb, w) + (9 * j) * 1024 + (2 * q) * 128 + lane * 4;
        ACLK_INIT;
        {
          float acc[108];
#pragma unroll
          for (int i = 0; i < 108; i++) acc[i] = 0.f;
          uint32_t prev = 0;
#pragma unroll 1
          for (int kb = 0; kb < 9; kb++) {
            wait_ab();
            yield(9 - kb, LAG1);
            TRC(tr && kb == 0, w, tb + 0);
            MCLK(kb == 0, 0);
            PCLK(kb * 4);
            const uint32_t st = sb + c.s * ST_BYTES, da = dlo(st + w * 8192, 16), db = dlo(st + ST_B, 3456);
            wgmma_fence();
#pragma unroll
            for (int kk = 0; kk < 4; kk++) {
              wgmma_ss_n216(acc, dsc<1024, 1>(da, kk * 32), dsc<128, 0>(db, kk * 6912), 1);
              if (kk == 0) { wgmma_commit(); wgmma_wait<1>(); release_if(kb > 0, prev); }
            }
            wgmma_commit();
            if (kb == 8) yield_done();
            PCLK(kb * 4 + 1);
            PCLK(kb * 4 + 2);
            PCLK(kb * 4 + 3);
            prev = c.s; c.next();
          }
          const uint32_t cs = sb + prev * ST_BYTES + SM_CSQ + t * 8;
          mbar_wait_c(bars + B_CSQ, L);
          const float2 n0 = lds64f(sb + prev * ST_BYTES + SM_XST + w * 512 + (16 * q + g) * 8), n1 = lds64f(sb + prev * ST_BYTES + SM_XST + w * 512 + (16 * q + g + 8) * 8);
          const float m0 = n0.x, r0 = n0.y, m1 = n1.x, r1 = n1.y;
          float2 cv[27];
#pragma unroll
          for (int G = 0; G < 27; G++) cv[G] = lds64f(cs + G * 32);
          PCLK(36);
          wgmma_wait<0>();
          PCLK(37);
          uint32_t dep = P.zero & __float_as_uint(m0) & __float_as_uint(m1);
#pragma unroll
          for (int G = 0; G < 27; G++) dep &= __float_as_uint(cv[G].x);
          release(prev, dep);
          lagph ^= 1;
          TRC(tr, w, tb + 1);
          MCLK(1, 1);
          ACLK(0);
#pragma unroll
          for (int G = 9; G < 27; G++) Pk[G][1] = pack2(fmaf(m1, cv[G].x, acc[4 * G + 2]) * r1, fmaf(m1, cv[G].y, acc[4 * G + 3]) * r1);
          if (q < 3) {
#pragma unroll
            for (int i = 0; i < 18; i++) sts32(att + (i >> 4) * ST_BYTES + (i & 15) * 128, Pk[9 + i][1]);
          } else if (rb < 15) {
#pragma unroll
            for (int i = 0; i < 6; i++) ll_st128(hp + i * 32, __uint_as_float(Pk[9 + 3 * i][1]), __uint_as_float(Pk[10 + 3 * i][1]), tag, __uint_as_float(Pk[11 + 3 * i][1]));
          }
#pragma unroll
          for (int G = 0; G < 27; G++) {
            if (G < 9) {
              Pk[G][0] = pack2(fmaf(m0, cv[G].x, acc[4 * G]), fmaf(m0, cv[G].y, acc[4 * G + 1]));
              Pk[G][1] = pack2(fmaf(m1, cv[G].x, acc[4 * G + 2]), fmaf(m1, cv[G].y, acc[4 * G + 3]));
            } else {
              Pk[G][0] = pack2(fmaf(m0, cv[G].x, acc[4 * G]) * r0, fmaf(m0, cv[G].y, acc[4 * G + 1]) * r0);
            }
          }
          sc0 = r0 * (0.23570226039551584f * 1.4426950408889634f); sc1 = r1 * (0.23570226039551584f * 1.4426950408889634f);
        }
        ACLK(1);
        constexpr int GA_[4] = {0, 2, 4, 7}, GB_[4] = {1, 3, 5, 8}, GC_[4] = {2, 4, 6, 6};
        float S1[4][4], S2[4][4];
        uint32_t qa[4][2], qc[4][2];
#pragma unroll
        for (int h = 0; h < 4; h++) {
#pragma unroll
          for (int r = 0; r < 2; r++) {
            qa[h][r] = (h == 0 || h == 3 || t >= h) ? Pk[GA_[h]][r] : 0u;
            qc[h][r] = (h == 3 ? t == 3 : t <= h) ? Pk[GC_[h]][r] : 0u;
          }
          mma16(S1[h], qa[h][0], qa[h][1], Pk[GB_[h]][0], Pk[GB_[h]][1], Pk[9 + GA_[h]][0], Pk[9 + GB_[h]][0]);
          mma16(S2[h], qa[h][0], qa[h][1], Pk[GB_[h]][0], Pk[GB_[h]][1], Pk[9 + GA_[h]][1], Pk[9 + GB_[h]][1]);
        }
#pragma unroll
        for (int h = 0; h < 4; h++) {
          mma8(S1[h], qc[h][0], qc[h][1], Pk[9 + GC_[h]][0]);
          mma8(S2[h], qc[h][0], qc[h][1], Pk[9 + GC_[h]][1]);
        }
        uint32_t V1[9], V2[9];
#pragma unroll
        for (int i = 0; i < 9; i++) { V1[i] = movm(Pk[18 + i][0]); V2[i] = movm(Pk[18 + i][1]); }
        const bool remote = q == 0 && rb > 0;
        uint4 hv[6];
#pragma unroll
        for (int i = 0; i < 6; i++) hv[i] = make_uint4(0u, 0u, tag, 0u);
        if (remote) {
#pragma unroll
          for (int i = 0; i < 6; i++) hv[i] = ll_ld128(hp + i * 32);
        }
        const bool up0 = 2 * t > g, up1 = 2 * t + 1 > g;
        const uint32_t mup = (up0 ? 0xffffu : 0u) | (up1 ? 0xffff0000u : 0u);
        auto finish = [&](const float (&x0)[4], const float (&x1)[4], uint32_t ma, const uint32_t (&Vb)[9], int hi) {
          uint32_t pa[4], pb[4];
          float rs[4];
#pragma unroll
          for (int h = 0; h < 4; h++) {
            const float m = qmax(fmaxf(x0[h], x1[h]));
            const uint32_t p = pack2(ex2(x0[h] - m), ex2(x1[h] - m));
            pa[h] = p & ma; pb[h] = p & ~ma;
          }
#pragma unroll
          for (int h = 0; h < 4; h += 2) {
            float R[4];
            mma16(R, pa[h], pa[h + 1], pb[h], pb[h + 1], 0x3f803f80u, 0x3f803f80u);
            rs[h] = rcp_fast(R[0]); rs[h + 1] = rcp_fast(R[2]);
          }
#pragma unroll
          for (int i = 0; i < 9; i++) {
            const int h = 4 * i / 9, e = (h & 1) * 2;
            const bool split = i == 2 || i == 4 || i == 6, nx = split && 2 * t >= i;
            float O[4], N[4];
            mma16(O, pa[h & 2], pa[h | 1], pb[h & 2], pb[h | 1], V1[i], Vb[i]);
            if (i == 4) mma16(N, pa[2], pa[3], pb[2], pb[3], V1[i], Vb[i]); else { N[0] = O[2]; N[1] = O[3]; }
            const float r = nx ? rs[h + (split ? 1 : 0)] : rs[h];
            stg32(od + i * 1024 + hi * 128, pack2((nx ? N[0] : O[e]) * r, (nx ? N[1] : O[e + 1]) * r));
          }
        };
        {
          float x0[4], x1[4];
#pragma unroll
          for (int h = 0; h < 4; h++) { x0[h] = (up0 ? S1[h][2] : S2[h][2]) * sc1; x1[h] = (up1 ? S1[h][3] : S2[h][3]) * sc1; }
          finish(x0, x1, mup, V2, 1);
        }
        ACLK(2);
        bar_sync(1 + w, 128);
        uint32_t H[18];
        if (q > 0) {
#pragma unroll
          for (int i = 0; i < 18; i++) H[i] = lds32(att - 2048 + (i >> 4) * ST_BYTES + (i & 15) * 128);
        } else {
#pragma unroll 1
          for (int it = 0; it < (1 << 20); it++) {
            bool ok = true;
#pragma unroll
            for (int i = 0; i < 6; i++) ok = ok && hv[i].z == tag;
            if (__all_sync(~0u, ok)) break;
#pragma unroll
            for (int i = 0; i < 6; i++) hv[i] = ll_ld128(hp + i * 32);
          }
#pragma unroll
          for (int i = 0; i < 6; i++) { H[3 * i] = hv[i].x; H[3 * i + 1] = hv[i].y; H[3 * i + 2] = hv[i].w; }
        }
        float S0[4][4];
#pragma unroll
        for (int h = 0; h < 4; h++) {
          mma16(S0[h], qa[h][0], qa[h][1], Pk[GB_[h]][0], Pk[GB_[h]][1], H[GA_[h]], H[GB_[h]]);
        }
#pragma unroll
        for (int h = 0; h < 4; h++) mma8(S0[h], qc[h][0], qc[h][1], H[GC_[h]]);
        uint32_t V0[9];
#pragma unroll
        for (int i = 0; i < 9; i++) V0[i] = movm(H[9 + i]);
        ACLK(3);
        {
          const bool nohalo = (rb | q) == 0;
          const float b0 = up0 && nohalo ? -INFINITY : 0.f, b1 = up1 && nohalo ? -INFINITY : 0.f;
          float x0[4], x1[4];
#pragma unroll
          for (int h = 0; h < 4; h++) { x0[h] = fmaf(up0 ? S0[h][0] : S1[h][0], sc0, b0); x1[h] = fmaf(up1 ? S0[h][1] : S1[h][1], sc0, b1); }
          finish(x0, x1, ~mup, V0, 0);
        }
        ACLK(4);
        signal(EV_O);
        ACLK_OUT;
        TRC(tr, w, tb + 2);
        MCLK(1, 2);
      }
      {
        float acc[36];
        const int hw = rb * 2 + (j & 1), js = (j & 6) + w;
        const uint32_t xt = sb + SM_STG + (16 * q + g) * 288 + w * 144 + t * 4;
        uint32_t xm = sb + SM_STG + (16 * q + (lane & 15)) * 288 + (((9 * w + (lane >> 4)) ^ ((lane >> 2) & 1)) << 4), xl = sb + SM_STG + (2 * q + w) * 2304 + lane * 16;
        uint8_t* xd[5];
#pragma unroll
        for (int u = 0; u < 5; u++) {
          const int row = ((u * 32 + lane) * 57) >> 10;
          xd[u] = P.xs[L + 1] + (128 * rb + 32 * q + 16 * w + (j & 1)) * (DM * 2) + (j & 6) * 144 + row * (DM * 4 - 288) + u * 512 + ((lane ^ (row >> 2)) << 4);
          asm volatile("" : "+l"(xd[u]));
        }
        asm volatile("" : "+r"(xm), "+r"(xl));
        mbar_wait_c(bars + B_RES, L);
        TRC(tr, w, tb + 21);
#pragma unroll
        for (int i = 0; i < 18; i++) { const uint32_t x = lds32(xt + (i >> 1) * 16 + (i & 1) * 2304); acc[2 * i] = blo(x); acc[2 * i + 1] = bhi(x); asm volatile("" : "+f"(acc[2 * i]), "+f"(acc[2 * i + 1])); }
        uint32_t prev = 0;
#pragma unroll 1
        for (int u = 0; u < 5; u++) {
          const uint32_t st = sb + c.s * ST_BYTES, da = dlo(st, 1024), db = dlo(st + ST_B + w * 18432, 1152);
          mbar_wait_c(bars + B_FULL + c.s * 8, c.ph); mbar_wait_c(bars + B_FULLA + c.s * 8, (ia >> 2) & 1);
          TRC(tr && u == 0, w, tb + 3);
          MCLK(u == 0, 3);
          wgmma_fence();
#pragma unroll
          for (int kk = 0; kk < 4; kk++) wgmma_ss_n72(acc, dsc<128, 0>(da, kk * 2048), dsc<128, 0>(db, kk * 2304), 1);
          wgmma_commit();
          wgmma_wait<1>();
          release_if(u > 0, prev);
          mbar_wait_c(bars + B_FULLA + 32 + c.s * 8, (ia >> 2) & 1);
          ia++;
          if (u == 4) break;
          wgmma_fence();
#pragma unroll
          for (int kk = 4; kk < 8; kk++) wgmma_ss_n72(acc, dsc<128, 0>(da, kk * 2048), dsc<128, 0>(db, kk * 2304), 1);
          wgmma_commit();
          prev = c.s; c.next();
        }
        RCLK_INIT;
        wgmma_wait<0>();
        RCLK(0);
        release(c.s);
        c.next();
        if (__builtin_expect(any_nan(acc[0], acc[2]), 0)) {
          SLOW(L);
          const uint8_t* xr = P.xs[L] + (128 * rb + 32 * q + 2 * g + (j & 1)) * (DM * 2) + js * 144 + t * 4;
#pragma unroll
          for (int i = 0; i < 18; i++) { const uint32_t x = ldgpu32(xr + (i >> 1) * 16 + (i & 1) * (DM * 32)); acc[2 * i] = blo(x); acc[2 * i + 1] = bhi(x); }
          redo<KS2, 9, 1024, 128, 1152, 128>(acc, o_block(rb, j & 1) + q * 256 + lane * 4, g_WO + js * WO_SL + lane * 4, [](uint32_t*, int) {});
        }
        TRC(tr && P5TRACE != 5, w, tb + 4);
        MCLK(1, 4);
#pragma unroll
        for (int u = 0; u < 4; u++)
          stsm4(xm + u * 32, pack2(acc[8 * u], acc[8 * u + 1]), pack2(acc[8 * u + 2], acc[8 * u + 3]), pack2(acc[8 * u + 4], acc[8 * u + 5]), pack2(acc[8 * u + 6], acc[8 * u + 7]));
        asm volatile("stmatrix.sync.aligned.m8n8.x2.shared.b16 [%0], {%1,%2};" ::"r"(xm + 128), "r"(pack2(acc[32], acc[33])), "r"(pack2(acc[34], acc[35])) : "memory");
        auto stats = [&]() {
          float s0 = 0.f, s1 = 0.f, q0 = 0.f, q1 = 0.f;
#pragma unroll
          for (int i = 0; i < 36; i++) {
            if (i & 2) { s1 += acc[i]; q1 = fmaf(acc[i], acc[i], q1); } else { s0 += acc[i]; q0 = fmaf(acc[i], acc[i], q0); }
          }
          s0 = qsum(s0); s1 = qsum(s1); q0 = qsum(q0); q1 = qsum(q1);
          const float ss = t ? s1 : s0, m = ss * (1.f / 72.f);
          ll_st128_if(t < 2, g_ST1 + (hw * 8 + js) * 64 + 16 * q + 8 * t + g, m, fmaxf((t ? q1 : q0) - ss * m, 0.f), tag);
        };
        stats();
        RCLK(1);
        bar_sync(8 + q, 64);
        RCLK(2);
#pragma unroll
        for (int u = 0; u < 5; u++) {
          const uint4 v = lds128(xl + u * 512);
          stg128_if(u < 4 || lane < 16, xd[u], v.x, v.y, v.z, v.w);
        }
        RCLK(3);
        signal(EV_X1);
        RCLK(4);
        RCLK(5);
        TRC(tr, w, tb + 5);
        RCLK(6);
        RCLK_OUT;
      }
      {
        uint32_t xA[36][4];
        float acc[32];
        uint32_t s0, one, off2;
        uint8_t *z1d, *zd;
        uint64_t db;
        auto bwait = [&](uint32_t dhi, bool skip) {
          s0 = c.s;
          c.next();
          if (!skip) mbar_wait_c(bars + B_FULL + c.s * 8, c.ph);
          db = dsc2(dlo(sb + s0 * ST_BYTES + ST_B, 512) - 3, 0, dhi); one = (c.s ^ P.zero) & 1;
        };
        auto mma = [&](int kk, int pp, bool hand) {
          wgmma_rs_n64(acc, xA[kk], dat(db, (kk / 18) * ST_BYTES + (kk % 18) * 2048 + 48, one), kk != 0);
          if (kk == pp && hand) bar_arrive(7 - w, 256);
          if (kk == 17 || kk == 35) wgmma_commit();
          if (kk == RL3) { wgmma_commit(); wgmma_wait<1>(); release(s0); }
        };
        {
          bwait(0x40000040u, false);
          mbar_wait_c(bars + B_GATE3, L);
          float mean0, mean1, rs0, rs1;
          stat_get(g_ST1 + ((rb * 2 + w) * 8 + 2 * t) * 64 + 16 * q + g, tag, 72.f, LN_EPS, mean0, rs0, mean1, rs1);
          const uint32_t ns0 = pack2(GA * rs0, GA * rs0), ns1 = pack2(GA * rs1, GA * rs1);
          const uint32_t nb0 = pack2(-mean0 * blo(ns0), -mean0 * blo(ns0)), nb1 = pack2(-mean1 * blo(ns1), -mean1 * blo(ns1));
          const uint32_t al = sb + (aoff & 8191);
#pragma unroll
          for (int kb = 0; kb <= 9; kb++) {
            if (kb < 9) {
              mbar_wait_c(bars + B_FA3 + (9 * w + kb) * 8, L);
              TRC(tr && kb == 0, w, tb + 6);
              MCLK(kb == 0, 5);
              if (kb == 0) SCLK(0);
              QCLK(kb);
              const uint32_t at = al + (w ? (((kb + 1) >> 1) & 3) * ST_BYTES + ((kb + 1) & 1) * 8192 : ((kb >> 1) & 3) * ST_BYTES + (kb & 1) * 8192);
#pragma unroll
              for (int kk = 4 * kb; kk < 4 * kb + 4; kk++) ldsm4(xA[kk], at ^ ((kk & 3) << 5));
            }
            if (kb == 0) continue;
            const uint32_t dep = xA[4 * kb - 4][0] & xA[4 * kb - 3][0] & xA[4 * kb - 2][0] & xA[4 * kb - 1][0] & P.zero;
            mbar_arrive_if(lane == 0 && (kb == 1 || w == 0), bars + B_EA3 + (9 * w + kb - 1) * 8 + dep);
#pragma unroll
            for (int kk = 4 * kb - 4; kk < 4 * kb; kk++) {
#pragma unroll
              for (int e = 0; e < 4; e++) xA[kk][e] = hfma2(xA[kk][e], (e & 1) ? ns1 : ns0, (e & 1) ? nb1 : nb0);
            }
            wgmma_fence();
#pragma unroll
            for (int kk = 4 * kb - 4; kk < 4 * kb; kk++) mma(kk, PP30, w);
          }
          off2 = lds32(sb + SM_OFF);
          z1d = z1_block(rb, w, j) + (tid & 127) * 16;
          zd = z2_block(2 * rb + (q >> 1), j) + (4 * (q & 1) + w) * 4608 + ((g & 3) * 2 + (g >> 2)) * 16 + t * 4;
          asm volatile("" : "+l"(z1d), "+l"(zd));
          wgmma_wait<0>();
          if (__builtin_expect(any_nan(acc[0], acc[2]), 0)) {
            SLOW(2 + L);
            uint4* const rd = g_RD + bid * (36 * 256) + tid;
            const uint8_t* xr = P.xs[L + 1] + (128 * rb + 32 * q + 2 * g + w) * (DM * 2) + t * 4;
#pragma unroll
            for (int i = 0; i < 32; i++) acc[i] = 0.f;
            redo<KS3, 8, 16, DM * 32, FH * 32, 16>(acc, xr, (const uint8_t*)P.w_in + g * (FH * 4) + (((9 * j + 1) >> 1) + 36) * 128 + t * 4,
                                              [&](uint32_t* a, int k) {
#pragma unroll
                                                for (int e = 0; e < 4; e++) a[e] = hfma2(a[e], (e & 1) ? ns1 : ns0, (e & 1) ? nb1 : nb0);
                                                stg128(rd + k * 256, a[0], a[1], a[2], a[3]);
                                              });
#pragma unroll
            for (int k = 0; k < 36; k++) { const uint4 v = ldcg128(rd + k * 256); xA[k][0] = v.x; xA[k][1] = v.y; xA[k][2] = v.z; xA[k][3] = v.w; }
          }
        }
        float sm[4] = {0.f, 0.f, 0.f, 0.f}, qq[4] = {0.f, 0.f, 0.f, 0.f};
        auto gelu = [&](auto nz2) {
          constexpr int NZ2 = nz2.value, R = 8 - NZ2, N = 8, D = NZ2 == 8 ? GM2 : NZ2 ? GMM : GM1;
          float th[32], gb = GB;
          uint32_t qa = 0, qb = 0;
          auto head = [&](int G) {
#pragma unroll
            for (int e = 0; e < 4; e++) { const float v = acc[4 * G + e]; th[4 * G + e] = tanh_fast(v * fmaf(v, v, gb)); }
          };
#pragma unroll
          for (int i = 0; i < D; i++) head((i + R) & 7);
#pragma unroll
          for (int i = 0; i < N; i++) {
            const int G = (i + R) & 7;
            if (i + D < N) head((i + D + R) & 7);
            float* z = acc + 4 * G;
#pragma unroll
            for (int e = 0; e < 4; e++) z[e] = fmaf(z[e], th[4 * G + e], z[e]);
            uint32_t pa = pack2(z[0], z[1]), pb = pack2(z[2], z[3]), tok;
            if (i < NZ2) {
#pragma unroll
              for (int e = 0; e < 4; e++) { sm[e] += z[e]; qq[e] = fmaf(z[e], z[e], qq[e]); }
              pa = hsub2(pa, off2); pb = hsub2(pb, off2);
              stg32(zd + i * 128, pa); stg32(zd + i * 128 + 9216, pb);
              tok = pa ^ pb ^ __float_as_uint(qq[1]);
            } else {
              if (G & 1) stg128(z1d + (G >> 1) * 2048 + (NZ2 ? 32768 : 0), qa, qb, pa, pb);
              qa = pa; qb = pb;
              tok = pa ^ pb;
            }
            gb = __uint_as_float(tok * P.zero + __float_as_uint(GB));
          }
        };
#pragma unroll 1
        for (int p = 0;; p++) {
          wgmma_wait<0>();
          release(c.s);
          c.next();
          TRC(tr && p == 4, w, tb + 7);
          TRC(tr && p == 8, w, tb + 11);
          MCLK(p == 8, 6);
          SCLK(2 * p + 1);
          QCLK(10 + 3 * p);
          auto publish = [&]() {
            signal(EV_ZN);
            const float a0 = qsum(sm[0] + sm[1]), a1 = qsum(sm[2] + sm[3]), q0 = qsum(qq[0] + qq[1]), q1 = qsum(qq[2] + qq[3]);
            const float ss = t ? a1 : a0, m = ss * (1.f / 288.f);
            ll_st128_if(t < 2, g_ZST + (rb * 2 + w) * 512 + j * 64 + 16 * q + 8 * t + g, m - blo(off2), fmaxf((t ? q1 : q0) - ss * m, 0.f), tag);
            TRC(tr, w, tb + 8);
            TRC(tr, w, tb + 9);
          };
          if (p < 4) {
            gelu(Int<8>{});
            zd += 1024;
          } else if (p == 4) {
            gelu(Int<4>{});
            publish();
          } else {
            gelu(Int<0>{});
            z1d += 8192;
          }
          SCLK(2 * p + 2);
          QCLK(11 + 3 * p);
          if (p == 8) break;
          bwait(p == 3 ? 0x80000040u : 0x40000040u, w);
          bar_sync(6 + w, 256);
          TRC(tr && p == 4, w, tb + 10);
          wgmma_fence();
#pragma unroll
          for (int kk = 0; kk < 36; kk++) mma(kk, PP3, w == 0 || p < 7);
        }
        signal(EV_Z1);
        TRC(tr, w, tb + 12);
      }
      uint32_t hA[18][4];
      {
        float acc[144];
        const float c0 = __uint_as_float(lds32(sb + SM_OFF + 4));
#pragma unroll
        for (int i = 0; i < 144; i++) {
          asm volatile("fma.rn.f32 %0, %1, %2, %3;" : "=f"(acc[i]) : "f"(__uint_as_float(P.zero)), "f"((float)(i + 2)), "f"(c0));
        }
        uint32_t prev = 0;
        auto stage = [&](int kb) {
          mbar_wait_c(bars + B_FULL + c.s * 8, c.ph);
          TRC(tr && kb == 0, w, tb + 13);
          SCLK(22 + kb);
          const uint32_t st = sb + c.s * ST_BYTES, rt = sb + SM_RT + kb * 128 + t * 8;
          uint64_t db = dsc2(dlo(st + ST_B, 4608), 0, 8 + P.zero);
          uint32_t a[4][4];
#pragma unroll
          for (int kk = 0; kk < 4; kk++) {
            uint32_t r[4];
            ldsm4(r, st + (aoff ^ (kk << 5)));
            const uint2 sc = lds64(rt + kk * 32);
            a[kk][0] = hmul2(__byte_perm(r[0], r[2], 0x5410), sc.x); a[kk][2] = hmul2(__byte_perm(r[0], r[2], 0x7632), sc.y);
            a[kk][1] = hmul2(__byte_perm(r[1], r[3], 0x5410), sc.x); a[kk][3] = hmul2(__byte_perm(r[1], r[3], 0x7632), sc.y);
          }
          if (LAG4 && (kb & 1) == (LAG4 & 1)) yield(32 - kb, LAG4);
          wgmma_fence();
#pragma unroll
          for (int i = 0; i < 8; i++) {
            const int kk = i & 3, hf = i >> 2;
            wgmma_rs_n144(acc + hf * 72, a[kk], db, 1);
            dadd(db, i == 3 ? 144u - 3 * 576 : 576 + P.zero);
            if (i == 0) { wgmma_commit(); wgmma_wait<1>(); release_if(kb, prev); }
            if (i == 3) wgmma_commit();
          }
          wgmma_commit();
          prev = c.s; c.next();
        };
        mbar_wait_c(bars + B_RT, L);
#pragma unroll 1
        for (int kb = 0; kb < 32; kb += 2) {
          if (kb == 8) mbar_wait_c(bars + B_RT1, L);
          MCLK((kb & 7) == 4, 10 + (kb >> 3));
          stage(kb);
          stage(kb + 1);
        }
        if (LAG4) { yield_done(); lagph ^= 1; }
        if (w == 1) bar_arrive(6, 256);
        HCLK(0);
        mbar_wait_c(bars + B_CV + w * 8, L);
        HCLK(1);
        const float gk = 0.5f / GA;
        const float c1 = __uint_as_float(lds32(sb + SM_OFF + 4));
        const float gb0 = -gk * (c1 + __uint_as_float(lds32(sb + SM_CV + w * 256 + (16 * q + g) * 4))), gb1 = -gk * (c1 + __uint_as_float(lds32(sb + SM_CV + w * 256 + (16 * q + g + 8) * 4)));
        mbar_wait_c(w ? bars + B_ZB : bars + B_FULL + c.s * 8, w ? L : c.ph);
        HCLK(2);
        const uint32_t sx = c.s;
        c.next();
        const uint32_t zt = sb + (tid & 127) * 16, zs0 = zt + sx * ST_BYTES + w * ZB, zs1 = w ? zt + SM_STG - 16384 : zs0, zs2 = w ? zt + c.s * ST_BYTES - 20480 : zs0;
#pragma unroll
        for (int u = 0; u < 18; u++) {
          if (u == 0) { wgmma_wait<1>(); HCLK(3); }
          if (u == 9) {
            HCLK(4);
            wgmma_wait<0>();
            HCLK(5);
            release(prev);
            if (L == 0) signal(EV_P4);
            if (w == 1) mbar_wait_c(bars + B_FULL + c.s * 8, c.ph);
            TRC(tr, w, tb + 14);
            SCLK(54);
          }
          const uint4 z = lds128((u < 8 ? zs0 : u < 10 ? zs1 : zs2) + u * 2048);
          hA[u][0] = hmul2(z.x, pack2(fmaf(acc[8 * u], gk, gb0), fmaf(acc[8 * u + 1], gk, gb0)));
          hA[u][1] = hmul2(z.y, pack2(fmaf(acc[8 * u + 2], gk, gb1), fmaf(acc[8 * u + 3], gk, gb1)));
          hA[u][2] = hmul2(z.z, pack2(fmaf(acc[8 * u + 4], gk, gb0), fmaf(acc[8 * u + 5], gk, gb0)));
          hA[u][3] = hmul2(z.w, pack2(fmaf(acc[8 * u + 6], gk, gb1), fmaf(acc[8 * u + 7], gk, gb1)));
        }
        uint32_t dep = P.zero;
#pragma unroll
        for (int u = 0; u < 18; u++) dep &= hA[u][0];
        release(sx, dep);
        TRC(tr, w, tb + 15);
        HCLK(6);
      }
      {
        CLK_INIT;
        uint32_t pk[16];
#pragma unroll
        for (int i = 0; i < 16; i++) pk[i] = 0u;
        auto dump = [&](int p) {
          const uint32_t d = sb + (p & 3) * ST_BYTES, cb = p + j >= 9 ? p + j - 9 : p + j;
          if (lane == 0) asm volatile("cp.async.bulk.wait_group.read 3;" ::: "memory");
          __syncwarp();
#pragma unroll
          for (int u = 0; u < 4; u++) stsm4(d + (aoff ^ (u << 5)), pk[4 * u], pk[4 * u + 1], pk[4 * u + 2], pk[4 * u + 3]);
          fence_async_s();
          __syncwarp();
          tma3d_red_p(lane == 0, &P.red[L], cb * 64, rb * 64 + q * 16, w, d + w * 8192 + q * 2048);
        };
#pragma unroll 1
        for (int p = 0; p < 9; p++) {
          float acc[32];
          CLK(0);
          mbar_wait_c(bars + B_FULL + c.s * 8, c.ph);
          uint64_t db = dsc2(dlo(sb + c.s * ST_BYTES + ST_B + (j & 1) * 4096, 0), 0, 0x40000040u + P.zero);
          CLK(1);
          HCLK(7 + 2 * p);
          bar_sync(6 + w, 256);
          CLK(2);
          wgmma_fence();
#pragma unroll
          for (int kk = 0; kk < 18; kk++) {
            wgmma_rs_n64(acc, hA[kk], db, kk != 0);
            dadd(db, kk == 15 ? 128 - (j & 1) * (36864 >> 4) : 128 + P.zero);
            if (kk == PPK && (w == 0 || p < 8)) bar_arrive(7 - w, 256);
          }
          wgmma_commit();
          CLK(3);
          if (p > 0) dump(p - 1);
          CLK(5);
          wgmma_wait<0>();
          CLK(4);
          HCLK(8 + 2 * p);
          MCLK(p == 1 || p == 8, 7 + (p >> 3));
          release_if(L == 0 || p < 5, c.s);
          c.next();
#pragma unroll
          for (int i = 0; i < 16; i++) pk[i] = pack2(acc[2 * i], acc[2 * i + 1]);
          if (p == 8) { TRC(tr, w, tb + 16); dump(8); TRC(tr, w, tb + 17); }
        }
        if (lane == 0) asm volatile("cp.async.bulk.wait_group 0;" ::: "memory");
        HCLK(25);
        MCLK(1, 9);
        if (L == 0) signal(EV_PT);
        CLK_OUT;
        TRC(tr, w, tb + 18);
      }
    }
    if ((tid & 127) == 0) g_flags[(rb * 2 + w) * 32 + FR_EP + j] = epoch + 1;
    if (tid == 0) g_flags[FJ + j * 32 + FJ_EP + rb] = epoch + 1;
  }
}

typedef CUresult (*EncodeFn)(CUtensorMap*, CUtensorMapDataType, cuuint32_t, void*, const cuuint64_t*, const cuuint64_t*, const cuuint32_t*,
                             const cuuint32_t*, CUtensorMapInterleave, CUtensorMapSwizzle, CUtensorMapL2promotion, CUtensorMapFloatOOBfill);

static void make_map(EncodeFn fn, CUtensorMap* m, const void* ptr, int rank, uint64_t d0, uint64_t d1, uint64_t d2, uint64_t s1, uint64_t s2,
                     uint32_t b0, uint32_t b1, uint32_t b2, CUtensorMapSwizzle swz) {
  cuuint64_t dims[3] = {d0, d1, d2}, strides[2] = {s1, s2};
  cuuint32_t box[3] = {b0, b1, b2}, es[3] = {1, 1, 1};
  fn(m, CU_TENSOR_MAP_DATA_TYPE_BFLOAT16, rank, const_cast<void*>(ptr), dims, strides, box, es, CU_TENSOR_MAP_INTERLEAVE_NONE, swz,
     CU_TENSOR_MAP_L2_PROMOTION_L2_128B, CU_TENSOR_MAP_FLOAT_OOB_FILL_NONE);
}

}

extern "C" void kernel_launch(void* const* d_in, const int* in_sizes, int n_in, void* d_out, int out_size) {
  using namespace mk;
  (void)in_sizes; (void)n_in; (void)out_size;
  static EncodeFn fn = nullptr;
  static uint8_t *wq, *xb;
  static float* csp;
  if (!fn) {
    cudaGetSymbolAddress((void**)&wq, g_WQ);
    cudaGetSymbolAddress((void**)&xb, g_X);
    cudaGetSymbolAddress((void**)&csp, g_CSP);
    cudaDriverEntryPointQueryResult qr;
    cudaGetDriverEntryPoint("cuTensorMapEncodeTiled", (void**)&fn, cudaEnableDefault, &qr);
    cudaFuncSetAttribute(mega_kernel, cudaFuncAttributeMaxDynamicSharedMemorySize, SM_TOTAL);
  }
  Params p;
  p.wqkv = (const __nv_bfloat16*)d_in[1];
  p.w_in = (const __nv_bfloat16*)d_in[4];
  p.w_sp = (const __nv_bfloat16*)d_in[5];
  p.b_sp = (const __nv_bfloat16*)d_in[6];
  p.w_out = (const __nv_bfloat16*)d_in[7];
  p.zero = 0;
  p.wq = wq;
  p.csp = csp;
  p.xs[0] = (uint8_t*)d_in[0];
  p.xs[1] = xb;
  p.xs[2] = (uint8_t*)d_out;
  make_map(fn, &p.wsp, p.w_sp, 3, 2048, 1024, 2, 8192, 4096, 64, 64, 2, CU_TENSOR_MAP_SWIZZLE_128B);
  for (int i = 0; i < 2; i++) {
    make_map(fn, &p.red[i], p.xs[i + 1], 3, DM, 1024, 2, 2304, 1152, 64, 16, 1, CU_TENSOR_MAP_SWIZZLE_128B);
    make_map(fn, &p.res[i], p.xs[i], 3, DM, 1024, 2, 2304, 1152, 144, 64, 1, CU_TENSOR_MAP_SWIZZLE_NONE);
  }
  make_map(fn, &p.psn, d_out, 3, DM, 1024, 2, 2304, 1152, 144, 4, 1, CU_TENSOR_MAP_SWIZZLE_NONE);
  for (int i = 0; i < 3; i++) make_map(fn, &p.act[i], p.xs[i], 3, DM, 1024, 2, 2304, 1152, 64, 64, 1, CU_TENSOR_MAP_SWIZZLE_128B);
  {
    cuuint64_t dims[4] = {8, 8, 72, 72}, strides[3] = {1152, 16, 9216};
    cuuint32_t box[4] = {8, 8, 9, 5}, es[4] = {1, 1, 1, 1};
    fn(&p.wo8, CU_TENSOR_MAP_DATA_TYPE_BFLOAT16, 4, d_in[2], dims, strides, box, es, CU_TENSOR_MAP_INTERLEAVE_NONE, CU_TENSOR_MAP_SWIZZLE_NONE,
       CU_TENSOR_MAP_L2_PROMOTION_L2_128B, CU_TENSOR_MAP_FLOAT_OOB_FILL_NONE);
  }
  for (int i = 0; i < 2; i++) {
    cuuint64_t dims[4] = {i ? 4608u : 2304u, 8, i ? 1u : 2u, 72}, strides[3] = {9216, 4608, 8 * 9216};
    cuuint32_t box[4] = {i ? 64u : 32u, 8, i ? 1u : 2u, 18}, es[4] = {1, 1, 1, 1};
    fn(i ? &p.win64 : &p.win, CU_TENSOR_MAP_DATA_TYPE_BFLOAT16, 4, d_in[4], dims, strides, box, es, CU_TENSOR_MAP_INTERLEAVE_NONE,
       i ? CU_TENSOR_MAP_SWIZZLE_128B : CU_TENSOR_MAP_SWIZZLE_64B, CU_TENSOR_MAP_L2_PROMOTION_L2_128B, CU_TENSOR_MAP_FLOAT_OOB_FILL_NONE);
  }
  make_map(fn, &p.wout, p.w_out, 2, 576, 2304, 1, 1152, 0, 64, 144, 1, CU_TENSOR_MAP_SWIZZLE_128B);
  mega_kernel<<<NGRID, 384, SM_TOTAL, cudaStreamPerThread>>>(p);
}
```

```cpp
#include <cuda_runtime.h>
#include <cuda.h>
#include <cuda_bf16.h>
#include <stdint.h>

#define MK_TRACE 0
#define MK_DBG 0
#define P5TRACE 0
#define LAG1 2
#define PP3 32
#define PP30 33
#define LAG4 1
#define SPL 2
#define NAP 200
#define NAP0 8000
#define KS2 2
#define KS3 2
#define RL3 21
#define PAD 0
#define ZA 6
#define ZW 10
#define GM2 3
#define GMM 1
#define GM1 2
#define C0S 32.f
#define OFM 0x10u
#define PPK 13

namespace mk {

constexpr int SEQ = 2048, DM = 576, FH = 2304;
constexpr int NCTA = 128;
constexpr int NGRID = 132;
constexpr uint32_t ZB = 36864;
constexpr uint32_t WQ_SL = 72 * 3456;
constexpr uint32_t WO_SL = 72 * 1152;
constexpr float LN_EPS = 1e-5f;
constexpr float GA = 0.3292034911525734f, GB = 2.423681954311584f;

constexpr uint32_t ST_BYTES = 53248, ST_B = 16384, NST = 4;
constexpr uint32_t SM_STG = NST * ST_BYTES;
constexpr uint32_t SM_BAR = SM_STG + 2 * 9216;
constexpr uint32_t SM_OFF = SM_BAR + 1008;
constexpr uint32_t SM_TOTAL = SM_BAR + 1024;
constexpr uint32_t SM_RT = SM_STG + 4096, SM_CV = SM_STG + 12288, SM_WT = SM_CV + 512;
constexpr uint32_t SM_WOI = 44032, SM_CSQ = 49792, SM_XST = 50688;
constexpr uint32_t B_FULL = 0, B_EMPTY = 32, B_FULLA = 64, B_RES = 128, B_WT = 144, B_IMG = 160, B_WOI = 168, B_ZB = 176, B_GATE3 = 184, B_Z1 = 192, B_LAG = 200,
                   B_RT = 208, B_CSQ = 216, B_CV = 224, B_AD = 240, B_EVT = 272, B_RT1 = 368, B_XRW = 384, B_FA3 = 400, B_EA3 = 544;
enum { EV_PT = 0, EV_O = 1, EV_X1 = 2, EV_ZN = 3, EV_Z1 = 4, EV_P4 = 5, EV_N = 6 };

enum { FR_X2 = 0, FR_O = 1, FR_X1 = 3, FR_EP = 16, FJ = 32 * 32, FJ_WQ = 0, FJ_WO = 1, FJ_WQ0 = 2, FJ_ZN = 3, FJ_P4 = 5, FJ_EP = 16, F_N = FJ + 8 * 32 };

__device__ __align__(1024) uint8_t g_Z[512 * ZB];
constexpr uint32_t POISON = 0xffffffffu;
__device__ __align__(1024) uint8_t g_O[32 * 2 * ZB];
__device__ __align__(1024) uint4 g_RD[NCTA * 36 * 256];
__device__ __align__(1024) uint8_t g_X[SEQ * DM * 2];
#define SLOW(i) do {} while (0)
__device__ __align__(1024) uint8_t g_WQ[8 * WQ_SL];
__device__ __align__(1024) uint8_t g_WO[8 * WO_SL];
__device__ __align__(1024) float g_CSP[2 * NCTA * 216];
__device__ __align__(1024) uint2 g_RT[SEQ];
__device__ __align__(1024) uint4 g_XST[2 * SEQ];
__device__ __align__(1024) uint4 g_ST1[SEQ * 8];
__device__ __align__(1024) uint4 g_ZST[SEQ * 8];
__device__ __align__(1024) uint4 g_HALO[32 * 8 * 6 * 32];
__device__ __align__(1024) uint32_t g_flags[F_N];

struct Params {
  const __nv_bfloat16 *wqkv;
  uint8_t* wq;
  float* csp;
  uint32_t zero;
  const __nv_bfloat16 *w_in, *w_sp, *b_sp, *w_out;
  uint8_t* xs[3];
  CUtensorMap wo8, wsp, win, win64, wout;
  CUtensorMap act[3];
  CUtensorMap res[2];
  CUtensorMap red[2];
  CUtensorMap psn;
};

__device__ __forceinline__ uint32_t smem_u32(const void* p) { return (uint32_t)__cvta_generic_to_shared(p); }
__device__ __forceinline__ void mbar_init(uint32_t bar, uint32_t cnt) { asm volatile("mbarrier.init.shared::cta.b64 [%0], %1;" ::"r"(bar), "r"(cnt)); }
__device__ __forceinline__ void mbar_arrive(uint32_t bar) { asm volatile("mbarrier.arrive.shared::cta.b64 _, [%0];" ::"r"(bar) : "memory"); }
__device__ __forceinline__ void mbar_wait(uint32_t bar, uint32_t parity) {
  asm volatile(
      "{\n.reg .pred p;\n.reg .u32 c;\nmov.u32 c, 0;\nLAB_WAIT:\n"
      "mbarrier.try_wait.parity.shared::cta.b64 p, [%0], %1;\n@p bra LAB_DONE;\n"
      "add.u32 c, c, 1;\nsetp.lt.u32 p, c, 0x100000;\n@p bra LAB_WAIT;\ntrap;\nLAB_DONE:\n}" ::"r"(bar), "r"(parity)
      : "memory");
}
__device__ __forceinline__ void mbar_wait_c(uint32_t bar, uint32_t parity) {
  asm volatile("{\n.reg .pred p;\nLAB_WAIT:\nmbarrier.try_wait.parity.shared::cta.b64 p, [%0], %1;\n@!p bra LAB_WAIT;\n}" ::"r"(bar), "r"(parity) : "memory");
}
__device__ __forceinline__ void flag_wait(const uint32_t* f, uint32_t target) {
  asm volatile(
      "{\n.reg .pred p;\n.reg .u32 c, v;\nmov.u32 c, 0;\nLAB_WAIT:\n"
      "ld.relaxed.gpu.global.u32 v, [%0];\nsub.u32 v, v, %1;\nsetp.ge.s32 p, v, 0;\n@p bra LAB_DONE;\n"
      "add.u32 c, c, 1;\nsetp.lt.u32 p, c, 0x400000;\n@p bra LAB_WAIT;\ntrap;\nLAB_DONE:\nfence.acquire.gpu;\n}" ::"l"(f), "r"(target)
      : "memory");
}
__device__ __forceinline__ void fence_gpu() { asm volatile("fence.acq_rel.gpu;" ::: "memory"); }
__device__ __forceinline__ void fence_async_g() { asm volatile("fence.proxy.async.global;" ::: "memory"); }
__device__ __forceinline__ void fence_async_s() { asm volatile("fence.proxy.async.shared::cta;" ::: "memory"); }
__device__ __forceinline__ uint32_t elect_one() {
  uint32_t p; asm volatile("{\n.reg .pred P;\nelect.sync _|P, 0xffffffff;\nselp.u32 %0, 1, 0, P;\n}" : "=r"(p)); return p;
}
__device__ __forceinline__ void expect_tx_p(uint32_t el, uint32_t bar, uint32_t bytes) {
  asm volatile("{\n.reg .pred P;\nsetp.ne.u32 P, %2, 0;\n@P mbarrier.arrive.expect_tx.shared::cta.b64 _, [%0], %1;\n}" ::"r"(bar), "r"(bytes), "r"(el) : "memory");
}
__device__ __forceinline__ void bulk_load_p(uint32_t el, uint32_t dst, const void* src, uint32_t bytes, uint32_t bar) {
  asm volatile("{\n.reg .pred P;\nsetp.ne.u32 P, %4, 0;\n@P cp.async.bulk.shared::cluster.global.mbarrier::complete_tx::bytes [%0], [%1], %2, [%3];\n}" ::"r"(dst), "l"(src), "r"(bytes), "r"(bar), "r"(el) : "memory");
}
__device__ __forceinline__ uint64_t policy_evict_first() { uint64_t p; asm("createpolicy.fractional.L2::evict_first.b64 %0, 1.0;" : "=l"(p)); return p; }
__device__ __forceinline__ void bulk_load_h(uint32_t el, uint32_t dst, const void* src, uint32_t bytes, uint32_t bar, bool ef, uint64_t pol) {
  if (ef) {
    asm volatile("{\n.reg .pred P;\nsetp.ne.u32 P, %4, 0;\n@P cp.async.bulk.shared::cluster.global.mbarrier::complete_tx::bytes.L2::cache_hint [%0], [%1], %2, [%3], %5;\n}" ::"r"(dst), "l"(src), "r"(bytes), "r"(bar), "r"(el), "l"(pol) : "memory");
  } else {
    asm volatile("{\n.reg .pred P;\nsetp.ne.u32 P, %4, 0;\n@P cp.async.bulk.shared::cluster.global.mbarrier::complete_tx::bytes [%0], [%1], %2, [%3];\n}" ::"r"(dst), "l"(src), "r"(bytes), "r"(bar), "r"(el) : "memory");
  }
}
__device__ __forceinline__ void bulk_mc_h(uint32_t el, uint32_t dst, const void* src, uint32_t bytes, uint32_t bar, bool ef, uint64_t pol) {
  if (ef) {
    asm volatile("{\n.reg .pred P;\nsetp.ne.u32 P, %4, 0;\n@P cp.async.bulk.shared::cluster.global.mbarrier::complete_tx::bytes.multicast::cluster.L2::cache_hint [%0], [%1], %2, [%3], %5, %6;\n}" ::"r"(dst), "l"(src), "r"(bytes), "r"(bar), "r"(el), "h"((uint16_t)3), "l"(pol) : "memory");
  } else {
    asm volatile("{\n.reg .pred P;\nsetp.ne.u32 P, %4, 0;\n@P cp.async.bulk.shared::cluster.global.mbarrier::complete_tx::bytes.multicast::cluster [%0], [%1], %2, [%3], %5;\n}" ::"r"(dst), "l"(src), "r"(bytes), "r"(bar), "r"(el), "h"((uint16_t)3) : "memory");
  }
}
__device__ __forceinline__ void tma3d_h(uint32_t el, uint32_t dst, const CUtensorMap* m, int c0, int c1, int c2, uint32_t bar, bool ef, uint64_t pol) {
  if (ef) {
    asm volatile("{\n.reg .pred P;\nsetp.ne.u32 P, %6, 0;\n@P cp.async.bulk.tensor.3d.shared::cluster.global.mbarrier::complete_tx::bytes.L2::cache_hint [%0], [%1, {%3, %4, %5}], [%2], %7;\n}" ::"r"(dst), "l"(m), "r"(bar), "r"(c0), "r"(c1), "r"(c2), "r"(el), "l"(pol) : "memory");
  } else {
    asm volatile("{\n.reg .pred P;\nsetp.ne.u32 P, %6, 0;\n@P cp.async.bulk.tensor.3d.shared::cluster.global.mbarrier::complete_tx::bytes [%0], [%1, {%3, %4, %5}], [%2];\n}" ::"r"(dst), "l"(m), "r"(bar), "r"(c0), "r"(c1), "r"(c2), "r"(el) : "memory");
  }
}
__device__ __forceinline__ void tma2d_mc_h(uint32_t el, uint32_t dst, const CUtensorMap* m, int c0, int c1, uint32_t bar, bool ef, uint64_t pol) {
  if (ef) {
    asm volatile("{\n.reg .pred P;\nsetp.ne.u32 P, %5, 0;\n@P cp.async.bulk.tensor.2d.shared::cluster.global.mbarrier::complete_tx::bytes.multicast::cluster.L2::cache_hint [%0], [%1, {%3, %4}], [%2], %6, %7;\n}" ::"r"(dst), "l"(m), "r"(bar), "r"(c0), "r"(c1), "r"(el), "h"((uint16_t)3), "l"(pol) : "memory");
  } else {
    asm volatile("{\n.reg .pred P;\nsetp.ne.u32 P, %5, 0;\n@P cp.async.bulk.tensor.2d.shared::cluster.global.mbarrier::complete_tx::bytes.multicast::cluster [%0], [%1, {%3, %4}], [%2], %6;\n}" ::"r"(dst), "l"(m), "r"(bar), "r"(c0), "r"(c1), "r"(el), "h"((uint16_t)3) : "memory");
  }
}
__device__ __forceinline__ void tma4d_mc(uint32_t el, uint32_t dst, const CUtensorMap* m, int c0, int c3, uint32_t bar, uint64_t pol) {
  asm volatile("{\n.reg .pred P;\nsetp.ne.u32 P, %5, 0;\n@P cp.async.bulk.tensor.4d.shared::cluster.global.mbarrier::complete_tx::bytes.multicast::cluster.L2::cache_hint [%0], [%1, {%3, 0, 0, %4}], [%2], %6, %7;\n}" ::"r"(dst), "l"(m), "r"(bar), "r"(c0), "r"(c3), "r"(el), "h"((uint16_t)3), "l"(pol) : "memory");
}
__device__ __forceinline__ void mbar_arrive_cluster(uint32_t addr) { asm volatile("mbarrier.arrive.shared::cluster.b64 _, [%0];" ::"r"(addr) : "memory"); }
__device__ __forceinline__ void mbar_arrive_cluster_if(bool c, uint32_t addr) {
  asm volatile("{\n.reg .pred P;\nsetp.ne.u32 P, %1, 0;\n@P mbarrier.arrive.shared::cluster.b64 _, [%0];\n}" ::"r"(addr), "r"((uint32_t)c) : "memory");
}
__device__ __forceinline__ void mbar_arrive_if(bool c, uint32_t addr) {
  asm volatile("{\n.reg .pred P;\nsetp.ne.u32 P, %1, 0;\n@P mbarrier.arrive.shared::cta.b64 _, [%0];\n}" ::"r"(addr), "r"((uint32_t)c) : "memory");
}
__device__ __forceinline__ uint32_t mapa(uint32_t addr, uint32_t rank) { uint32_t r; asm("mapa.shared::cluster.u32 %0, %1, %2;" : "=r"(r) : "r"(addr), "r"(rank)); return r; }
__device__ __forceinline__ void bulk_store_p(uint32_t el, void* dst, uint32_t src, uint32_t bytes) {
  asm volatile("{\n.reg .pred P;\nsetp.ne.u32 P, %3, 0;\n@P cp.async.bulk.global.shared::cta.bulk_group [%0], [%1], %2;\n}" ::"l"(dst), "r"(src), "r"(bytes), "r"(el) : "memory");
}
__device__ __forceinline__ void flag_release_p(uint32_t el, uint32_t* f) {
  asm volatile("{\n.reg .pred P;\nsetp.ne.u32 P, %1, 0;\n@P red.release.gpu.global.add.u32 [%0], 1;\n}" ::"l"(f), "r"(el) : "memory");
}
__device__ __forceinline__ void flag_add_p(uint32_t el, uint32_t* f) {
  asm volatile("{\n.reg .pred P;\nsetp.ne.u32 P, %1, 0;\n@P red.relaxed.gpu.global.add.u32 [%0], 1;\n}" ::"l"(f), "r"(el) : "memory");
}
__device__ __forceinline__ void prefetch_l2(const void* src, uint32_t bytes) { asm volatile("cp.async.bulk.prefetch.L2.global [%0], %1;" ::"l"(src), "r"(bytes) : "memory"); }
__device__ __forceinline__ void prefetch_map(const CUtensorMap* m) { asm volatile("prefetch.tensormap [%0];" ::"l"(m) : "memory"); }
__device__ __forceinline__ void wgmma_fence() { asm volatile("wgmma.fence.sync.aligned;" ::: "memory"); }
__device__ __forceinline__ void wgmma_commit() { asm volatile("wgmma.commit_group.sync.aligned;" ::: "memory"); }
template <int N> __device__ __forceinline__ void wgmma_wait() { asm volatile("wgmma.wait_group.sync.aligned %0;" ::"n"(N) : "memory"); }
__device__ __forceinline__ uint32_t dlo(uint32_t addr, uint32_t lbo) { return ((addr & 0x3FFFF) >> 4) + ((lbo >> 4) << 16); }
template <uint32_t SBO, uint32_t SWZ> __device__ __forceinline__ uint64_t dsc(uint32_t lo, uint32_t off) {
  uint64_t d; asm("mov.b64 %0, {%1, %2};" : "=l"(d) : "r"(lo + (off >> 4)), "n"((SBO >> 4) | (SWZ << 30))); return d;
}
__device__ __forceinline__ uint64_t dsc2(uint32_t lo, uint32_t off, uint32_t hi) {
  uint64_t d; asm("mov.b64 %0, {%1, %2};" : "=l"(d) : "r"(lo + (off >> 4)), "r"(hi)); return d;
}
__device__ __forceinline__ uint64_t dat(uint64_t d, uint32_t off, uint32_t one) { uint64_t r; asm("mad.wide.u32 %0, %1, %2, %3;" : "=l"(r) : "r"(one), "r"(off >> 4), "l"(d)); return r; }
__device__ __forceinline__ void dadd(uint64_t& d, uint32_t v) {
  asm("{\n.reg .b32 lo, hi;\nmov.b64 {lo, hi}, %0;\nadd.u32 lo, lo, %1;\nmov.b64 %0, {lo, hi};\n}" : "+l"(d) : "r"(v));
}
template <int R> __device__ __forceinline__ void reg_alloc() { asm volatile("setmaxnreg.inc.sync.aligned.u32 %0;" ::"n"(R)); }
template <int R> __device__ __forceinline__ void reg_dealloc() { asm volatile("setmaxnreg.dec.sync.aligned.u32 %0;" ::"n"(R)); }
__device__ __forceinline__ void bar_sync(int id, int n) { asm volatile("bar.sync %0, %1;" ::"r"(id), "r"(n) : "memory"); }
__device__ __forceinline__ void bar_arrive(int id, int n) { asm volatile("bar.arrive %0, %1;" ::"r"(id), "r"(n) : "memory"); }
__device__ __forceinline__ void ldsm4(uint32_t* r, uint32_t addr) {
  asm volatile("ldmatrix.sync.aligned.m8n8.x4.shared.b16 {%0,%1,%2,%3}, [%4];" : "=r"(r[0]), "=r"(r[1]), "=r"(r[2]), "=r"(r[3]) : "r"(addr) : "memory");
}
__device__ __forceinline__ uint32_t movm(uint32_t a) { uint32_t d; asm volatile("movmatrix.sync.aligned.m8n8.trans.b16 %0, %1;" : "=r"(d) : "r"(a)); return d; }
__device__ __forceinline__ void mma16(float* c, uint32_t a0, uint32_t a1, uint32_t a2, uint32_t a3, uint32_t b0, uint32_t b1) {
  asm volatile("mma.sync.aligned.m16n8k16.row.col.f32.bf16.bf16.f32 {%0,%1,%2,%3}, {%4,%5,%6,%7}, {%8,%9}, {%10,%10,%10,%10};"
               : "=f"(c[0]), "=f"(c[1]), "=f"(c[2]), "=f"(c[3]) : "r"(a0), "r"(a1), "r"(a2), "r"(a3), "r"(b0), "r"(b1), "f"(0.f));
}
__device__ __forceinline__ void mma8(float* c, uint32_t a0, uint32_t a1, uint32_t b0) {
  asm volatile("mma.sync.aligned.m16n8k8.row.col.f32.bf16.bf16.f32 {%0,%1,%2,%3}, {%4,%5}, {%6}, {%0,%1,%2,%3};"
               : "+f"(c[0]), "+f"(c[1]), "+f"(c[2]), "+f"(c[3]) : "r"(a0), "r"(a1), "r"(b0));
}
__device__ __forceinline__ uint32_t pack2(float lo, float hi) { uint32_t r; asm("cvt.rn.bf16x2.f32 %0, %1, %2;" : "=r"(r) : "f"(hi), "f"(lo)); return r; }
__device__ __forceinline__ float blo(uint32_t v) { return __uint_as_float(v << 16); }
__device__ __forceinline__ float bhi(uint32_t v) { return __uint_as_float(v & 0xffff0000u); }
__device__ __forceinline__ float tanh_fast(float x) { float y; asm("tanh.approx.f32 %0, %1;" : "=f"(y) : "f"(x)); return y; }
__device__ __forceinline__ float rcp_fast(float x) { float y; asm("rcp.approx.ftz.f32 %0, %1;" : "=f"(y) : "f"(x)); return y; }
__device__ __forceinline__ float ex2(float x) { float y; asm("ex2.approx.ftz.f32 %0, %1;" : "=f"(y) : "f"(x)); return y; }
__device__ __forceinline__ float qsum(float v) { v += __shfl_xor_sync(~0u, v, 1); v += __shfl_xor_sync(~0u, v, 2); return v; }
__device__ __forceinline__ float qmax(float v) { v = fmaxf(v, __shfl_xor_sync(~0u, v, 1)); v = fmaxf(v, __shfl_xor_sync(~0u, v, 2)); return v; }
__device__ __forceinline__ void stg32(void* p, uint32_t v) { asm volatile("st.global.u32 [%0], %1;" ::"l"(p), "r"(v) : "memory"); }
__device__ __forceinline__ void stg128(void* p, uint32_t a, uint32_t b, uint32_t c, uint32_t d) { asm volatile("st.global.v4.u32 [%0], {%1,%2,%3,%4};" ::"l"(p), "r"(a), "r"(b), "r"(c), "r"(d) : "memory"); }
__device__ __forceinline__ uint32_t ldcg32(const void* p) { uint32_t v; asm volatile("ld.global.L1::no_allocate.u32 %0, [%1];" : "=r"(v) : "l"(p) : "memory"); return v; }
__device__ __forceinline__ uint32_t ldgpu32(const void* p) { uint32_t v; asm volatile("ld.relaxed.gpu.global.u32 %0, [%1];" : "=r"(v) : "l"(p) : "memory"); return v; }
__device__ __forceinline__ uint32_t ldca32(const void* p) { uint32_t v; asm volatile("ld.global.ca.u32 %0, [%1];" : "=r"(v) : "l"(p) : "memory"); return v; }
__device__ __forceinline__ void stg128_if(bool c, void* p, uint32_t a, uint32_t b, uint32_t cc, uint32_t d) {
  asm volatile("{\n.reg .pred P;\nsetp.ne.u32 P, %5, 0;\n@P st.global.v4.u32 [%0], {%1,%2,%3,%4};\n}" ::"l"(p), "r"(a), "r"(b), "r"(cc), "r"(d), "r"((uint32_t)c) : "memory");
}
__device__ __forceinline__ uint2 lds64(uint32_t a) { uint2 v; asm volatile("ld.shared.v2.u32 {%0,%1}, [%2];" : "=r"(v.x), "=r"(v.y) : "r"(a) : "memory"); return v; }
__device__ __forceinline__ uint4 ldcg128(const void* p) { uint4 v; asm volatile("ld.global.cg.v4.u32 {%0,%1,%2,%3}, [%4];" : "=r"(v.x), "=r"(v.y), "=r"(v.z), "=r"(v.w) : "l"(p) : "memory"); return v; }
__device__ __forceinline__ uint32_t ldnc16(const void* p) { uint16_t v; asm volatile("ld.global.nc.u16 %0, [%1];" : "=h"(v) : "l"(p)); return v; }
__device__ __forceinline__ uint4 ldnc128(const void* p) { uint4 v; asm volatile("ld.global.nc.v4.u32 {%0,%1,%2,%3}, [%4];" : "=r"(v.x), "=r"(v.y), "=r"(v.z), "=r"(v.w) : "l"(p)); return v; }
__device__ __forceinline__ uint32_t hsub2(uint32_t a, uint32_t b) { uint32_t d; asm("sub.rn.bf16x2 %0, %1, %2;" : "=r"(d) : "r"(a), "r"(b)); return d; }
__device__ __forceinline__ void stg32_if(bool c, void* p, uint32_t v) {
  asm volatile("{\n.reg .pred P;\nsetp.ne.u32 P, %2, 0;\n@P st.global.u32 [%0], %1;\n}" ::"l"(p), "r"(v), "r"((uint32_t)c) : "memory");
}
__device__ __forceinline__ uint32_t hmul2(uint32_t a, uint32_t b) { uint32_t d; asm("mul.rn.bf16x2 %0, %1, %2;" : "=r"(d) : "r"(a), "r"(b)); return d; }
__device__ __forceinline__ void sts32(uint32_t a, uint32_t v) { asm volatile("st.shared.u32 [%0], %1;" ::"r"(a), "r"(v) : "memory"); }
__device__ __forceinline__ uint32_t lds32(uint32_t a) { uint32_t v; asm volatile("ld.shared.u32 %0, [%1];" : "=r"(v) : "r"(a) : "memory"); return v; }
__device__ __forceinline__ void sts128(uint32_t a, uint32_t x, uint32_t y, uint32_t z, uint32_t w) { asm volatile("st.shared.v4.u32 [%0], {%1,%2,%3,%4};" ::"r"(a), "r"(x), "r"(y), "r"(z), "r"(w) : "memory"); }
__device__ __forceinline__ uint4 lds128(uint32_t a) { uint4 v; asm volatile("ld.shared.v4.u32 {%0,%1,%2,%3}, [%4];" : "=r"(v.x), "=r"(v.y), "=r"(v.z), "=r"(v.w) : "r"(a) : "memory"); return v; }
__device__ __forceinline__ void ll_st64(uint2* p, uint32_t v, uint32_t tag) {
  asm volatile("{\n.reg .b64 r;\nmov.b64 r, {%1,%2};\nst.relaxed.gpu.global.b64 [%0], r;\n}" ::"l"(p), "r"(v), "r"(tag) : "memory");
}
__device__ __forceinline__ uint2 ll_ld64(const uint2* p) {
  uint2 v; asm volatile("{\n.reg .b64 r;\nld.relaxed.gpu.global.b64 r, [%2];\nmov.b64 {%0,%1}, r;\n}" : "=r"(v.x), "=r"(v.y) : "l"(p) : "memory"); return v;
}
__device__ __forceinline__ void ll_st128(uint4* p, float a, float b, uint32_t tag, float c = 0.f) {
  asm volatile("{\n.reg .b128 r;\n.reg .b64 lo, hi;\nmov.b64 lo, {%1,%2};\nmov.b64 hi, {%3,%4};\nmov.b128 r, {lo, hi};\nst.relaxed.gpu.global.b128 [%0], r;\n}" ::"l"(p), "r"(__float_as_uint(a)), "r"(__float_as_uint(b)), "r"(tag), "r"(__float_as_uint(c)) : "memory");
}
__device__ __forceinline__ uint4 ll_ld128(const uint4* p) {
  uint4 v; asm volatile("{\n.reg .b128 r;\n.reg .b64 lo, hi;\nld.relaxed.gpu.global.b128 r, [%4];\nmov.b128 {lo, hi}, r;\nmov.b64 {%0,%1}, lo;\nmov.b64 {%2,%3}, hi;\n}" : "=r"(v.x), "=r"(v.y), "=r"(v.z), "=r"(v.w) : "l"(p) : "memory"); return v;
}
__device__ __forceinline__ void publish_p(uint32_t el, uint32_t* f) {
  asm volatile("{\n.reg .pred P;\nsetp.ne.u32 P, %1, 0;\n@P cp.async.bulk.commit_group;\n@P cp.async.bulk.wait_group 0;\n@P red.release.gpu.global.add.u32 [%0], 1;\n}" ::"l"(f), "r"(el) : "memory");
}
__device__ __forceinline__ void tma3d_red_p(uint32_t el, const CUtensorMap* m, int c0, int c1, int c2, uint32_t src) {
  asm volatile("{\n.reg .pred P;\nsetp.ne.u32 P, %5, 0;\n@P cp.reduce.async.bulk.tensor.3d.global.shared::cta.add.tile.bulk_group [%0, {%2, %3, %4}], [%1];\n@P cp.async.bulk.commit_group;\n}" ::"l"(m), "r"(src), "r"(c0), "r"(c1), "r"(c2), "r"(el) : "memory");
}
__device__ __forceinline__ void stsm4(uint32_t addr, uint32_t a, uint32_t b, uint32_t c, uint32_t d) {
  asm volatile("stmatrix.sync.aligned.m8n8.x4.shared.b16 [%0], {%1,%2,%3,%4};" ::"r"(addr), "r"(a), "r"(b), "r"(c), "r"(d) : "memory");
}
__device__ __forceinline__ void sts64(uint32_t a, uint32_t x, uint32_t y) { asm volatile("st.shared.v2.u32 [%0], {%1,%2};" ::"r"(a), "r"(x), "r"(y) : "memory"); }
__device__ __forceinline__ void ll_st128_if(bool on, uint4* p, float a, float b, uint32_t tag) {
  asm volatile("{\n.reg .pred P;\n.reg .b128 r;\n.reg .b64 lo, hi;\nsetp.ne.u32 P, %4, 0;\nmov.b64 lo, {%1,%2};\nmov.b64 hi, {%3,%3};\nmov.b128 r, {lo, hi};\n@P st.relaxed.gpu.global.b128 [%0], r;\n}" ::"l"(p), "r"(__float_as_uint(a)), "r"(__float_as_uint(b)), "r"(tag), "r"((uint32_t)on) : "memory");
}
__device__ __forceinline__ uint4 ldnc128_if(bool c, const void* p) {
  uint4 v = make_uint4(0u, 0u, 0u, 0u);
  asm volatile("{\n.reg .pred P;\nsetp.ne.u32 P, %5, 0;\n@P ld.global.nc.v4.u32 {%0,%1,%2,%3}, [%4];\n}" : "+r"(v.x), "+r"(v.y), "+r"(v.z), "+r"(v.w) : "l"(p), "r"((uint32_t)c));
  return v;
}
__device__ __forceinline__ uint32_t hfma2(uint32_t a, uint32_t b, uint32_t c) { uint32_t d; asm("fma.rn.bf16x2 %0, %1, %2, %3;" : "=r"(d) : "r"(a), "r"(b), "r"(c)); return d; }
__device__ __forceinline__ float2 lds64f(uint32_t a) { float2 v; asm volatile("ld.shared.v2.f32 {%0,%1}, [%2];" : "=f"(v.x), "=f"(v.y) : "r"(a) : "memory"); return v; }
#define TRC(cond, role, idx) do {} while (0)
#define TRV(role, idx, v) do {} while (0)

#define ACLK_INIT do {} while (0)
#define ACLK(i) do {} while (0)
#define ACLK_OUT do {} while (0)
#define QCLK(i) do {} while (0)
#define PH 1
#define RCLK(i) do {} while (0)
#define RCLK_INIT do {} while (0)
#define RCLK_OUT do {} while (0)
#define SCLK(i) do {} while (0)
#define HCLK(i) do {} while (0)
#define MCLK(c, i) do {} while (0)
#define CKK(i) do {} while (0)
#define CKK_OUT do {} while (0)
#define PL 1
#define PCLK(i) do {} while (0)
#define PQ 1
#define CLK_INIT do {} while (0)
#define CLK(i) do {} while (0)
#define CLK_OUT do {} while (0)

__device__ __forceinline__ void wgmma_ss_n216(float* d, uint64_t da, uint64_t db, int scaleD) {
  asm volatile("{\n.reg .pred p;\nsetp.ne.b32 p, %110, 0;\nwgmma.mma_async.sync.aligned.m64n216k16.f32.bf16.bf16 "
    "{%0,%1,%2,%3,%4,%5,%6,%7,%8,%9,%10,%11,%12,%13,%14,%15,%16,%17,%18,%19,%20,%21,%22,%23,%24,%25,%26,%27,%28,%29,%30,%31,%32,%33,%34,%35,%36,%37,%38,%39,%40,%41,%42,%43,%44,%45,%46,%47,%48,%49,%50,%51,%52,%53,%54,%55,%56,%57,%58,%59,%60,%61,%62,%63,%64,%65,%66,%67,%68,%69,%70,%71,%72,%73,%74,%75,%76,%77,%78,%79,%80,%81,%82,%83,%84,%85,%86,%87,%88,%89,%90,%91,%92,%93,%94,%95,%96,%97,%98,%99,%100,%101,%102,%103,%104,%105,%106,%107}, "
    "%108, %109, p, 1, 1, 0, 1;\n}\n"
    : "+f"(d[0]), "+f"(d[1]), "+f"(d[2]), "+f"(d[3]), "+f"(d[4]), "+f"(d[5]), "+f"(d[6]), "+f"(d[7]), "+f"(d[8]), "+f"(d[9]), "+f"(d[10]), "+f"(d[11]), "+f"(d[12]), "+f"(d[13]), "+f"(d[14]), "+f"(d[15]), "+f"(d[16]), "+f"(d[17]), "+f"(d[18]), "+f"(d[19]), "+f"(d[20]), "+f"(d[21]), "+f"(d[22]), "+f"(d[23]), "+f"(d[24]), "+f"(d[25]), "+f"(d[26]), "+f"(d[27]), "+f"(d[28]), "+f"(d[29]), "+f"(d[30]), "+f"(d[31]), "+f"(d[32]), "+f"(d[33]), "+f"(d[34]), "+f"(d[35]), "+f"(d[36]), "+f"(d[37]), "+f"(d[38]), "+f"(d[39]), "+f"(d[40]), "+f"(d[41]), "+f"(d[42]), "+f"(d[43]), "+f"(d[44]), "+f"(d[45]), "+f"(d[46]), "+f"(d[47]), "+f"(d[48]), "+f"(d[49]), "+f"(d[50]), "+f"(d[51]), "+f"(d[52]), "+f"(d[53]), "+f"(d[54]), "+f"(d[55]), "+f"(d[56]), "+f"(d[57]), "+f"(d[58]), "+f"(d[59]), "+f"(d[60]), "+f"(d[61]), "+f"(d[62]), "+f"(d[63]), "+f"(d[64]), "+f"(d[65]), "+f"(d[66]), "+f"(d[67]), "+f"(d[68]), "+f"(d[69]), "+f"(d[70]), "+f"(d[71]), "+f"(d[72]), "+f"(d[73]), "+f"(d[74]), "+f"(d[75]), "+f"(d[76]), "+f"(d[77]), "+f"(d[78]), "+f"(d[79]), "+f"(d[80]), "+f"(d[81]), "+f"(d[82]), "+f"(d[83]), "+f"(d[84]), "+f"(d[85]), "+f"(d[86]), "+f"(d[87]), "+f"(d[88]), "+f"(d[89]), "+f"(d[90]), "+f"(d[91]), "+f"(d[92]), "+f"(d[93]), "+f"(d[94]), "+f"(d[95]), "+f"(d[96]), "+f"(d[97]), "+f"(d[98]), "+f"(d[99]), "+f"(d[100]), "+f"(d[101]), "+f"(d[102]), "+f"(d[103]), "+f"(d[104]), "+f"(d[105]), "+f"(d[106]), "+f"(d[107])
    : "l"(da), "l"(db), "r"(scaleD));
}
__device__ __forceinline__ void wgmma_ss_n72(float* d, uint64_t da, uint64_t db, int scaleD) {
  asm volatile("{\n.reg .pred p;\nsetp.ne.b32 p, %38, 0;\nwgmma.mma_async.sync.aligned.m64n72k16.f32.bf16.bf16 "
    "{%0,%1,%2,%3,%4,%5,%6,%7,%8,%9,%10,%11,%12,%13,%14,%15,%16,%17,%18,%19,%20,%21,%22,%23,%24,%25,%26,%27,%28,%29,%30,%31,%32,%33,%34,%35}, "
    "%36, %37, p, 1, 1, 0, 1;\n}\n"
    : "+f"(d[0]), "+f"(d[1]), "+f"(d[2]), "+f"(d[3]), "+f"(d[4]), "+f"(d[5]), "+f"(d[6]), "+f"(d[7]), "+f"(d[8]), "+f"(d[9]), "+f"(d[10]), "+f"(d[11]), "+f"(d[12]), "+f"(d[13]), "+f"(d[14]), "+f"(d[15]), "+f"(d[16]), "+f"(d[17]), "+f"(d[18]), "+f"(d[19]), "+f"(d[20]), "+f"(d[21]), "+f"(d[22]), "+f"(d[23]), "+f"(d[24]), "+f"(d[25]), "+f"(d[26]), "+f"(d[27]), "+f"(d[28]), "+f"(d[29]), "+f"(d[30]), "+f"(d[31]), "+f"(d[32]), "+f"(d[33]), "+f"(d[34]), "+f"(d[35])
    : "l"(da), "l"(db), "r"(scaleD));
}
__device__ __forceinline__ void wgmma_rs_n144(float* d, const uint32_t* a, uint64_t db, int scaleD) {
  asm volatile("{\n.reg .pred p;\nsetp.ne.b32 p, %77, 0;\nwgmma.mma_async.sync.aligned.m64n144k16.f32.bf16.bf16 "
    "{%0,%1,%2,%3,%4,%5,%6,%7,%8,%9,%10,%11,%12,%13,%14,%15,%16,%17,%18,%19,%20,%21,%22,%23,%24,%25,%26,%27,%28,%29,%30,%31,%32,%33,%34,%35,%36,%37,%38,%39,%40,%41,%42,%43,%44,%45,%46,%47,%48,%49,%50,%51,%52,%53,%54,%55,%56,%57,%58,%59,%60,%61,%62,%63,%64,%65,%66,%67,%68,%69,%70,%71}, "
    "{%72,%73,%74,%75}, %76, p, 1, 1, 1;\n}\n"
    : "+f"(d[0]), "+f"(d[1]), "+f"(d[2]), "+f"(d[3]), "+f"(d[4]), "+f"(d[5]), "+f"(d[6]), "+f"(d[7]), "+f"(d[8]), "+f"(d[9]), "+f"(d[10]), "+f"(d[11]), "+f"(d[12]), "+f"(d[13]), "+f"(d[14]), "+f"(d[15]), "+f"(d[16]), "+f"(d[17]), "+f"(d[18]), "+f"(d[19]), "+f"(d[20]), "+f"(d[21]), "+f"(d[22]), "+f"(d[23]), "+f"(d[24]), "+f"(d[25]), "+f"(d[26]), "+f"(d[27]), "+f"(d[28]), "+f"(d[29]), "+f"(d[30]), "+f"(d[31]), "+f"(d[32]), "+f"(d[33]), "+f"(d[34]), "+f"(d[35]), "+f"(d[36]), "+f"(d[37]), "+f"(d[38]), "+f"(d[39]), "+f"(d[40]), "+f"(d[41]), "+f"(d[42]), "+f"(d[43]), "+f"(d[44]), "+f"(d[45]), "+f"(d[46]), "+f"(d[47]), "+f"(d[48]), "+f"(d[49]), "+f"(d[50]), "+f"(d[51]), "+f"(d[52]), "+f"(d[53]), "+f"(d[54]), "+f"(d[55]), "+f"(d[56]), "+f"(d[57]), "+f"(d[58]), "+f"(d[59]), "+f"(d[60]), "+f"(d[61]), "+f"(d[62]), "+f"(d[63]), "+f"(d[64]), "+f"(d[65]), "+f"(d[66]), "+f"(d[67]), "+f"(d[68]), "+f"(d[69]), "+f"(d[70]), "+f"(d[71])
    : "r"(a[0]), "r"(a[1]), "r"(a[2]), "r"(a[3]), "l"(db), "r"(scaleD));
}
__device__ __forceinline__ void wgmma_rs_n64(float* d, const uint32_t* a, uint64_t db, int scaleD) {
  asm volatile("{\n.reg .pred p;\nsetp.ne.b32 p, %37, 0;\nwgmma.mma_async.sync.aligned.m64n64k16.f32.bf16.bf16 "
    "{%0,%1,%2,%3,%4,%5,%6,%7,%8,%9,%10,%11,%12,%13,%14,%15,%16,%17,%18,%19,%20,%21,%22,%23,%24,%25,%26,%27,%28,%29,%30,%31}, "
    "{%32,%33,%34,%35}, %36, p, 1, 1, 1;\n}\n"
    : "+f"(d[0]), "+f"(d[1]), "+f"(d[2]), "+f"(d[3]), "+f"(d[4]), "+f"(d[5]), "+f"(d[6]), "+f"(d[7]), "+f"(d[8]), "+f"(d[9]), "+f"(d[10]), "+f"(d[11]), "+f"(d[12]), "+f"(d[13]), "+f"(d[14]), "+f"(d[15]), "+f"(d[16]), "+f"(d[17]), "+f"(d[18]), "+f"(d[19]), "+f"(d[20]), "+f"(d[21]), "+f"(d[22]), "+f"(d[23]), "+f"(d[24]), "+f"(d[25]), "+f"(d[26]), "+f"(d[27]), "+f"(d[28]), "+f"(d[29]), "+f"(d[30]), "+f"(d[31])
    : "r"(a[0]), "r"(a[1]), "r"(a[2]), "r"(a[3]), "l"(db), "r"(scaleD));
}

template <int V> struct Int { static constexpr int value = V; };
struct Cur {
  uint32_t s, ph;
  __device__ __forceinline__ void next() { if (++s == NST) { s = 0; ph ^= 1; } }
};

__device__ __forceinline__ uint8_t* z1_block(int rb, int w, int j) { return g_Z + (rb * 16 + w * 8 + j) * ZB; }
__device__ __forceinline__ uint8_t* o_block(int rb, int w) { return g_O + (rb * 2 + w) * (2 * ZB); }
__device__ __forceinline__ uint8_t* z2_block(int kb, int j) { return g_Z + (256 + kb * 8 + j) * ZB; }
__device__ __forceinline__ void combine8(float m0, float q0, float m1, float q1, float n, float eps, float& mean, float& rstd) {
  mean = qsum(m0 + m1) * 0.125f;
  float d0 = m0 - mean, d1 = m1 - mean;
  float M2 = qsum(q0 + q1 + n * (d0 * d0 + d1 * d1));
  rstd = rsqrtf(fmaf(M2, 0.125f / n, eps));
}
__device__ __forceinline__ void stat_get(const uint4* zs, uint32_t tag, float n, float eps, float& m0, float& r0, float& m1, float& r1) {
  uint4 a0, a1, b0, b1;
#pragma unroll 1
  for (int it = 0; it < (1 << 20); it++) {
    a0 = ll_ld128(zs); a1 = ll_ld128(zs + 64); b0 = ll_ld128(zs + 8); b1 = ll_ld128(zs + 72);
    if (__all_sync(~0u, a0.z == tag && a1.z == tag && b0.z == tag && b1.z == tag)) break;
  }
  combine8(__uint_as_float(a0.x), __uint_as_float(a0.y), __uint_as_float(a1.x), __uint_as_float(a1.y), n, eps, m0, r0);
  combine8(__uint_as_float(b0.x), __uint_as_float(b0.y), __uint_as_float(b1.x), __uint_as_float(b1.y), n, eps, m1, r1);
}

__device__ __forceinline__ void rows_fetch(uint32_t el, uint32_t xr, const uint8_t* src, uint32_t bar) {
  expect_tx_p(el, bar, 9216);
#pragma unroll 1
  for (int r = 0; r < 8; r++) bulk_load_p(el, xr + r * 1152, src + r * (DM * 4), 1152, bar);
}
__device__ __forceinline__ void rows_stats(uint32_t xr, uint4* dst, uint32_t tag, int lane) {
  float s[2] = {0.f, 0.f}, q[4] = {0.f, 0.f, 0.f, 0.f};
  const uint32_t a0 = xr + (lane >> 2) * 1152 + (((lane & 3) * 2) ^ (lane >> 2)) * 16;
  uint4 n0 = lds128(a0), n1 = lds128(a0 ^ 16);
#pragma unroll 1
  for (int e = 1; e <= 9; e++) {
    const uint32_t x[8] = {n0.x, n0.y, n0.z, n0.w, n1.x, n1.y, n1.z, n1.w};
    if (e < 9) { n0 = lds128(a0 + e * 128); n1 = lds128((a0 ^ 16) + e * 128); }
#pragma unroll
    for (int u = 0; u < 8; u++) {
      const float lo = blo(x[u]), hi = bhi(x[u]);
      s[u & 1] += lo + hi; q[(u & 1) * 2] = fmaf(lo, lo, q[(u & 1) * 2]); q[(u & 1) * 2 + 1] = fmaf(hi, hi, q[(u & 1) * 2 + 1]);
    }
  }
  const float sx = s[0] + s[1], sq = (q[0] + q[1]) + (q[2] + q[3]);
  const float m = qsum(sx) * (-1.f / DM), r = rsqrtf(fmaxf(fmaf(qsum(sq), 1.f / DM, -m * m), 0.f) + LN_EPS);
  if ((lane & 3) == 0) ll_st128(dst + (lane >> 2) * 2, m, r, tag);
}

__device__ __forceinline__ void poison(uint32_t el, uint32_t src, const CUtensorMap* m, int rb, int j, int lane) {
#pragma unroll 1
  for (int u = lane; u < 72; u += 32) sts128(src + u * 16, POISON, POISON, POISON, POISON);
  fence_async_s();
  __syncwarp();
#pragma unroll 1
  for (int u = 0; u < 16; u++) {
    __nanosleep(NAP);
    bulk_store_p(el, o_block(rb, u >> 3) + j * 9216 + (u & 7) * 1152, src, 1152);
    asm volatile("{\n.reg .pred P;\nsetp.ne.u32 P, %5, 0;\n@P cp.async.bulk.tensor.3d.global.shared::cta.tile.bulk_group [%0, {%2, %3, %4}], [%1];\n}" ::"l"(m), "r"(src), "r"((j & 6) * 72), "r"(rb * 64 + u * 4), "r"(j & 1), "r"(el) : "memory");
  }
}
__device__ __forceinline__ void mma16acc(float* c, const uint32_t* a, uint32_t b0, uint32_t b1) {
  asm volatile("mma.sync.aligned.m16n8k16.row.col.f32.bf16.bf16.f32 {%0,%1,%2,%3}, {%4,%5,%6,%7}, {%8,%9}, {%0,%1,%2,%3};"
               : "+f"(c[0]), "+f"(c[1]), "+f"(c[2]), "+f"(c[3]) : "r"(a[0]), "r"(a[1]), "r"(a[2]), "r"(a[3]), "r"(b0), "r"(b1));
}
template <int KS, int NG, int AK, int AH, int BK, int BG, class F> __device__ __forceinline__ void redo(float* acc, const uint8_t* pa, const uint8_t* pb, F f) {
#pragma unroll 1
  for (int k = 0; k < 36; k += KS) {
    uint32_t a[4 * KS], b[2 * KS][NG];
#pragma unroll 1
    for (int it = 0; it < (1 << 20); it++) {
      bool ok = true;
#pragma unroll
      for (int e = 0; e < 4 * KS; e++) a[e] = ldgpu32(pa + (e >> 1) * AK + (e & 1) * AH);
#pragma unroll
      for (int e = 0; e < 2 * KS * NG; e++) b[e / NG][e % NG] = ldca32(pb + (e / NG) * BK + (e % NG) * BG);
#pragma unroll
      for (int e = 0; e < 4 * KS; e++) ok = ok && a[e] != POISON;
      if (__all_sync(~0u, ok)) break;
    }
#pragma unroll
    for (int e = 0; e < KS; e++) f(a + 4 * e, k + e);
#pragma unroll
    for (int e = 0; e < KS * NG; e++) mma16acc(acc + 4 * (e % NG), a + 4 * (e / NG), movm(b[2 * (e / NG)][e % NG]), movm(b[2 * (e / NG) + 1][e % NG]));
    pa += 2 * KS * AK; pb += 2 * KS * BK;
  }
}
__device__ __forceinline__ bool any_nan(float a, float b) {
  return __any_sync(~0u, a != a || b != b);
}

__global__ void __cluster_dims__(2, 1, 1) __launch_bounds__(384, 1) mega_kernel(const __grid_constant__ Params P) {
  extern __shared__ __align__(1024) uint8_t smem_raw[];
  uint32_t ckk[8];
  (void)ckk;
  CKK(0);
  const uint32_t sb = smem_u32(smem_raw);
  const uint32_t bars = sb + SM_BAR;
  const int tid = threadIdx.x;
  int lane = tid & 31;
  const int wid = __shfl_sync(~0u, tid >> 5, 0);
  const int cl = blockIdx.x >> 1, tp = cl - 36, t7 = (tp * 37) >> 8;
  const int bid = (cl < 4 ? cl * 8 + 32 : tp < 0 ? cl - 4 : cl < 64 ? tp + t7 + 33 : cl) * 2 + (blockIdx.x & 1);
  if (bid >= NCTA) return;
  const int rb = bid & 15, j = bid >> 4;
  { const bool tr = (tid & 127) == 0 && tid < 256; const int w = tid >> 7; (void)tr; (void)w; TRC(tr, w, 0); }
  CKK(1);
  uint4 wv[5];
  const uint8_t* wsrc;
  {
    const int n8 = min(tid >> 3, 26), part = n8 / 9;
    const uint8_t* src = (const uint8_t*)P.wqkv + (8 * rb + (tid & 7)) * (3 * DM * 2) + (part * (DM - 72) + 72 * j + 8 * n8) * 2;
#pragma unroll
    for (int u = 0; u < SPL; u++) wv[u] = ldnc128_if(tid < 216, src + u * (128 * 3 * DM * 2));
    wsrc = src;
  }
  CKK(2);
  if (tid == 352) {
    for (int s = 0; s < (int)NST; s++) {
      mbar_init(bars + B_FULL + s * 8, 1); mbar_init(bars + B_EMPTY + s * 8, 16);
      mbar_init(bars + B_FULLA + s * 8, 1); mbar_init(bars + B_FULLA + 32 + s * 8, 1);
      mbar_init(bars + B_RES + s * 8, 1); mbar_init(bars + B_RT + s * 8, 1); mbar_init(bars + B_AD + s * 8, 2);
    }
    mbar_init(bars + B_IMG, 8); mbar_init(bars + B_RES + 8, 8); mbar_init(bars + B_WOI, 1); mbar_init(bars + B_GATE3, 3); mbar_init(bars + B_Z1, 1); mbar_init(bars + B_ZB, 1); mbar_init(bars + B_LAG, 4);
    mbar_init(bars + B_CSQ, 3); mbar_init(bars + B_RT1, 1); mbar_init(bars + B_XRW, 1); mbar_init(bars + B_XRW + 8, 1);
    for (int e = 0; e < 2 * EV_N; e++) mbar_init(bars + B_EVT + e * 8, 4);
    asm volatile("fence.mbarrier_init.release.cluster;" ::: "memory");
  }
  if (tid == 320) {
#pragma unroll
    for (int e = 0; e < 28; e++) mbar_init(bars + B_FA3 + e * 8, e < 18 ? 1 : 4);
    asm volatile("fence.mbarrier_init.release.cluster;" ::: "memory");
  }
  __syncthreads();

  if (wid >= 8) {
    reg_dealloc<40>();
    const uint32_t el = elect_one();
    const uint64_t pol = policy_evict_first();
    uint32_t* const fj = g_flags + FJ + j * 32;
    if (wid == 8) {
#pragma unroll 1
      for (int i = 0; i < 12; i++) if (el) prefetch_map(&P.act[0] + (i < 7 ? i : i - 12));
      const uint32_t epoch = ldcg32(fj + FJ_EP + rb);
      Cur c{0, 1};
      const uint32_t rk = bid & 1;
      uint32_t st, full;
      auto slot = [&](uint32_t bytes) {
        st = sb + c.s * ST_BYTES; full = bars + B_FULL + c.s * 8;
        mbar_wait(full, c.ph);
        expect_tx_p(el, full, bytes);
        mbar_wait(full - B_FULL + B_EMPTY, c.ph);
      };
#pragma unroll 1
      for (int L = 0; L < 2; L++) {
#pragma unroll 1
        for (int i = 0; i < 14; i++) {
          if (L == 0 && (i == 0 || i == 2 * SPL || i == 9)) {
            flag_wait(fj + (i == 9 ? FJ_WO : i == 2 * SPL ? FJ_WQ : FJ_WQ0), (epoch + 1) * 16);
            if (i == 9) flag_wait(g_flags + FJ + (j ^ 1) * 32 + FJ_WO, (epoch + 1) * 16);
            fence_async_g();
            TRC(el, 2, i == 9 ? 46 : i ? 47 : 45);
          }
          const uint32_t hb = i < 9 ? 13824 : i < 13 ? 18432 : 9216, o = ST_B + rk * (i < 9 ? 13824 : 18432);
          const uint8_t* src = i < 9 ? g_WQ + j * WQ_SL + i * 27648 + rk * 13824 : g_WO + ((j & 6) + rk) * WO_SL + (i - 9) * 18432;
          slot(2 * hb);
          bulk_mc_h(el, st + o, src, hb, full, true, pol);
          c.next();
        }
#pragma unroll 1
        for (int i = 0; i < 18; i++) {
          const int p = i >> 1, col = p == 4 ? (9 * j + ((j & 1) ? 0 : 8)) * 32 : (((9 * j + 1) >> 1) + (p < 4 ? p + 36 : p - 5)) * 64;
          if (i & 1) {
            slot(2 * ZB);
          } else {
            st = sb + c.s * ST_BYTES; full = bars + B_FULL + ((c.s + 1) & 3) * 8;
            mbar_wait(bars + B_EMPTY + c.s * 8, c.ph);
          }
          tma4d_mc(el, st + ST_B + rk * 18432, p == 4 ? &P.win : &P.win64, col, (i & 1) * 36 + rk * 18, full, pol);
          if (el && !(i & 1)) mbar_arrive(bars + B_FULL + c.s * 8);
          c.next();
        }
        TRC(el, 2, L * 16 + 6);
        flag_wait(fj + FJ_ZN + L, (epoch + 1) * 16);
        fence_async_g();
        TRC(el, 2, L * 16 + 7);
#pragma unroll 1
        for (int i = 0; i < 32; i++) {
          const uint8_t* src = z2_block(i, j) + rk * 18432;
          if (i >= 4) mbar_wait(bars + B_AD + c.s * 8, ((i >> 2) & 1) ^ 1);
          slot(ST_BYTES);
          bulk_mc_h(el, st + ST_B + rk * 18432, src, 18432, full, true, pol);
          tma3d_h(el, st, &P.wsp, i * 64, rb * 64, 0, full, true, pol);
          c.next();
        }
        mbar_wait(bars + B_Z1, L);
        fence_async_g();
        expect_tx_p(el, bars + B_ZB, 20480);
        bulk_load_h(el, sb + SM_STG, z1_block(rb, 1, j) + 16384, 4096, bars + B_ZB, true, pol);
#pragma unroll 1
        for (int i = 0; i < 10; i++) {
          const int cb = i - 1 + j;
          if (i < 4) mbar_wait(bars + B_AD + c.s * 8, 1);
          slot(i == 1 ? ST_BYTES : ZB);
          if (i < 2) bulk_load_h(el, st, z1_block(rb, i, j) + i * 20480, ZB - i * 20480, full, true, pol);
          if (i == 0) bulk_load_h(el, st + ZB, z1_block(rb, 1, j), 16384, bars + B_ZB, true, pol);
          else tma2d_mc_h(el, st + ST_B + rk * 18432, &P.wout, (cb >= 9 ? cb - 9 : cb) * 64, 288 * j + rk * 144, full, true, pol);
          c.next();
        }
      }
    } else if (wid < 11) {
      int w = wid - 9;
      uint32_t* const fr = g_flags + (rb * 2 + w) * 32;
      const uint32_t epoch = ldcg32(fr + FR_EP + j);
      const uint32_t ev = bars + B_EVT + w * EV_N * 8, t8 = (epoch + 1) * 8;
      Cur c{0, 1};
#pragma unroll 1
      for (int L = 0; L < 2; L++) {
        {
          const uint32_t tag = epoch * 2 + L + 1;
          uint4* const xs = g_XST + (rb * 2 + w) * 128;
          if (L) {
            mbar_wait(ev + EV_PT * 8, 0);
            TRC(el, 3, w * 32 + 16);
            flag_release_p(el, fr + FR_X2);
            TRC(el, 3, w * 32 + 17);
          }
#pragma unroll 1
          for (int i = 0; i < 9; i++) {
            const uint32_t full = bars + B_FULLA + w * 32 + c.s * 8, dst = sb + c.s * ST_BYTES + w * 8192;
            if (L == 0 && i == 4) {
              mbar_wait(bars + B_WT + w * 8, 0);
              TRC(el && w == 0, 2, 37);
              rows_stats(sb + SM_STG + w * 9216, xs + 16 * j, tag, lane);
              TRC(el && w == 0, 2, 38);
            }
            const uint32_t src = sb + (L ? 2 * ST_BYTES + SM_WOI : SM_STG + w * 9216);
            if (i == 4) {
#pragma unroll
              for (int u = 0; u < 6; u++) sts128(src + u * 512 + lane * 16, POISON, POISON, POISON, POISON);
              fence_async_s();
              __syncwarp();
            }
            mbar_wait(bars + B_EMPTY + c.s * 8, c.ph);
            expect_tx_p(el, full, 8192);
            if (i < L) { flag_wait(fr + FR_X2, t8); fence_async_g(); }
            tma3d_h(el, dst, &P.act[L], i * 64, rb * 64, w, full, false, pol);
            TRC(el && i < L, 3, w * 32 + 18);
            c.next();
            if (i >= 4 && i < (L ? 5 : 8)) {
              int b = (rb * 2 + w) * 8 + j;
              asm volatile("" : "+r"(b));
              bulk_store_p(el, i == 4 ? (uint8_t*)g_HALO + b * 3072 : g_O + (b * 3 + i - 5) * 3072, src, 3072);
              if (i < 6) bulk_store_p(el, (i == 4 ? g_ST1 : g_ZST) + b * 64, src, 1024);
              if (i == 6) bulk_store_p(el, g_RT + b * 8, src, 64);
            }
            if (L == 0 && i == 3) rows_fetch(el, sb + SM_STG + w * 9216, P.xs[0] + (128 * rb + 16 * j + w) * (DM * 2), bars + B_WT + w * 8);
          }
          if (el) asm volatile("cp.async.bulk.commit_group;\ncp.async.bulk.wait_group 0;" ::: "memory");
          __syncwarp();
          if (L == 0) fence_gpu();
          const uint32_t tab = sb + L * (2 * ST_BYTES) + SM_XST + w * 512 + lane * 8;
          TRC(el, 3, w * 32 + L * 16 + 13);
#pragma unroll 1
          for (int it = 0; it < (1 << 22); it++) {
            const uint4 a = ll_ld128(xs + 2 * lane), b = ll_ld128(xs + 64 + 2 * lane);
            if (__all_sync(~0u, a.z == tag && b.z == tag)) { sts64(tab, a.x, a.y); sts64(tab + 256, b.x, b.y); break; }
          }
          __syncwarp();
          mbar_arrive_if(el, bars + B_CSQ);
          TRC(el, 3, w * 32 + L * 16 + 14);
          if (w == 1) {
            mbar_wait(bars + B_CSQ, L);
            expect_tx_p(el, bars + B_RES, 18432);
            tma3d_h(el, sb + SM_STG, &P.res[L], (j & 6) * 72, rb * 64, j & 1, bars + B_RES, !L, pol);
          }
          if (L) flag_wait(fj + FJ_P4, t8 * 4);
        }
        asm volatile("" : "+r"(w));
        uint32_t* const fo = g_flags + (rb * 2 + (j & 1)) * 32 + L;
        {
          const uint8_t* src = o_block(rb, j & 1) + w * 8192;
#pragma unroll 1
          for (int i = 0; i < 5; i++) {
            const uint32_t full = bars + B_FULLA + w * 32 + c.s * 8, dst = sb + c.s * ST_BYTES + w * 8192;
            const bool none = 2 * i + w > 8;
            mbar_wait(bars + B_EMPTY + c.s * 8, c.ph);
            expect_tx_p(el, full, none ? 0 : 8192);
            if (i == 0) {
              mbar_wait(ev + EV_O * 8, L);
              TRC(el, 3, w * 32 + L * 16 + 3);
              flag_add_p(el, fr + FR_O + L);
              TRC(el, 3, w * 32 + L * 16 + 4);
              flag_wait(fo + FR_O, t8);
              fence_async_g();
            }
            if (!none) bulk_load_h(el, dst, src + i * 16384, 8192, full, true, pol);
            TRC(el && i == 0, 3, w * 32 + L * 16 + 5);
            c.next();
          }
        }
        {
          expect_tx_p(lane < 9, bars + B_FA3 + (9 * w + lane) * 8, 8192);
          mbar_wait(ev + EV_X1 * 8, L);
          TRC(el, 3, w * 32 + L * 16 + 6);
          if (L) flag_add_p(el, fo + FR_X1); else flag_release_p(el, fo + FR_X1);
          mbar_arrive_if(el, bars + B_GATE3);
          TRC(el, 3, w * 32 + L * 16 + 7);
          mbar_arrive_if(lane < 2, bars + B_FULLA + w * 32 + ((c.s + lane) & 3) * 8);
#pragma unroll 1
          for (int kb = 0; kb < 9; kb++) {
            const int n = 9 * w + kb;
            const uint32_t dst = sb + ((n >> 1) & 3) * ST_BYTES + (n & 1) * 8192;
            if (kb == 0) { flag_wait(fr + FR_X1 + L, t8); fence_async_g(); }
            if (n >= 8) mbar_wait(bars + B_EA3 + (n - 8) * 8, L);
            tma3d_h(el, dst, &P.act[L + 1], kb * 64, rb * 64, w, bars + B_FA3 + n * 8, false, pol);
            TRC(el && kb == 0, 3, w * 32 + L * 16 + 8);
          }
          c.ph ^= ((c.s + 18) >> 2) & 1; c.s = (c.s + 18) & 3;
        }
        asm volatile("" : "+r"(lane), "+r"(w));
        expect_tx_p(el, bars + B_WT + w * 8, 2048);
#pragma unroll 1
        for (int r = 0; r < 8; r++)
          bulk_load_p(el, sb + SM_WT + w * 2176 + r * 272, (const uint8_t*)P.w_sp + (size_t)(128 * rb + 16 * j + 2 * r + w) * (SEQ * 2) + 30 * 128, 256, bars + B_WT + w * 8);
        float cv = (lane & 3) ? 0.f : -blo(ldnc16(P.b_sp + 128 * rb + 16 * j + 2 * (lane >> 2) + w));
        mbar_wait(bars + B_RT, L);
        mbar_wait(bars + B_WT + w * 8, L ^ 1);
        mbar_wait(ev + EV_Z1 * 8, L);
        const uint32_t ro = (w * 64 + 8 * j + (lane >> 2)) * 128, x0 = ((lane & 3) * 2) ^ (lane >> 2);
#pragma unroll 1
        for (int i = 0; i < 32; i++) {
          const bool tail = (i >> 1) == 4;
          const int kb = tail ? i + 22 : i < 8 ? i : i - 2;
          if (i == 8) mbar_wait(bars + B_RT1, L);
          if (!tail) mbar_wait(bars + B_FULL + c.s * 8, c.ph ^ 1);
#pragma unroll
          for (int e = 0; e < 2; e++) {
            const uint4 a = lds128(!tail ? sb + c.s * ST_BYTES + ro + ((x0 ^ e) << 4) : sb + SM_WT + w * 2176 + (lane >> 2) * 272 + (i - 8) * 128 + (lane & 3) * 32 + e * 16);
            const uint4 m = lds128(sb + SM_RT + 4096 + kb * 128 + (lane & 3) * 32 + e * 16);
            cv = fmaf(blo(a.x), blo(m.x), fmaf(bhi(a.x), bhi(m.x), fmaf(blo(a.y), blo(m.y), fmaf(bhi(a.y), bhi(m.y), cv))));
            cv = fmaf(blo(a.z), blo(m.z), fmaf(bhi(a.z), bhi(m.z), fmaf(blo(a.w), blo(m.w), fmaf(bhi(a.w), bhi(m.w), cv))));
          }
          if (!tail) {
            mbar_arrive_if(el, bars + B_AD + c.s * 8 + (__float_as_uint(cv) & P.zero));
            c.next();
          }
        }
        TRC(el, 3, w * 32 + L * 16 + 11);
        uint32_t tag = t8;
        asm volatile("" : "+r"(tag));
        tag = (tag >> 2) - 1 + L;
        cv = qsum(cv);
        uint2* const cs = (uint2*)(g_XST + (rb * 2 + w) * 128 + 1);
        if ((lane & 3) == 0) ll_st64(cs + 32 * j + (lane >> 2) * 4, __float_as_uint(cv), tag);
#pragma unroll 1
        for (int it = 0; it < (1 << 22); it++) {
          const uint2 a = ll_ld64(cs + 4 * lane), b = ll_ld64(cs + 128 + 4 * lane);
          if (__all_sync(~0u, a.y == tag && b.y == tag)) { sts32(sb + SM_CV + w * 256 + lane * 4, a.x); sts32(sb + SM_CV + w * 256 + 128 + lane * 4, b.x); break; }
        }
        __syncwarp();
        if (el) mbar_arrive(bars + B_CV + w * 8);
        TRC(el, 3, w * 32 + L * 16 + 12);
#pragma unroll 1
        for (int kb = 30; kb < 32; kb++) {
          mbar_wait(bars + B_FULL + c.s * 8, c.ph ^ 1);
          if (el) mbar_arrive(bars + B_AD + c.s * 8);
          c.next();
        }
        c.ph ^= ((c.s + 10) >> 2) & 1; c.s = (c.s + 10) & 3;
        if (L == 0) {
          mbar_wait(ev + EV_P4 * 8, 0);
          flag_add_p(el, fj + FJ_P4);
        }
      }
    } else {
      const uint32_t epoch = ldcg32(fj + FJ_EP + rb);
      if (SPL) {
        mbar_wait(bars + B_RES + 8, 0);
        TRC(el, 2, 41);
        flag_release_p(el, fj + FJ_WQ0);
        TRC(el, 2, 42);
      }
      mbar_wait(bars + B_IMG, 0);
      TRC(el, 2, 39);
      flag_release_p(el, fj + FJ_WQ);
      TRC(el, 2, 40);
#pragma unroll 1
      for (int L = 0; L < 2; L++) {
        auto wo_fetch = [&]() {
          expect_tx_p(el, bars + B_WOI, 5760);
          asm volatile("{\n.reg .pred P;\nsetp.ne.u32 P, %5, 0;\n@P cp.async.bulk.tensor.4d.shared::cluster.global.mbarrier::complete_tx::bytes [%0], [%1, {0, 0, %3, %4}], [%2];\n}" ::"r"(sb + SM_WOI), "l"(&P.wo8), "r"(bars + B_WOI), "r"(9 * j), "r"((9 * rb) >> 1), "r"(el) : "memory");
        };
        float* const csf = g_CSP + (NCTA + bid) * 216;
        if (L == 0) {
          flag_wait(fj + FJ_WQ, (epoch + 1) * 16);
          fence_async_g();
          expect_tx_p(el, bars + B_XRW, 13824);
          bulk_load_p(el, sb + ST_BYTES + SM_WOI, g_CSP + j * 16 * 216, 6912, bars + B_XRW);
          bulk_load_p(el, sb + 2 * ST_BYTES + SM_WOI, g_CSP + (j * 16 + 8) * 216, 6912, bars + B_XRW);
          wo_fetch();
          mbar_wait(bars + B_XRW, 0);
#pragma unroll 1
          for (int f = lane; f < 54; f += 32) {
            float s[4] = {0.f, 0.f, 0.f, 0.f};
#pragma unroll 4
            for (int r = 0; r < 16; r++) {
              const uint4 v = lds128(sb + ST_BYTES + SM_WOI + (r >> 3) * ST_BYTES + (r & 7) * 864 + f * 16);
              s[0] += __uint_as_float(v.x); s[1] += __uint_as_float(v.y); s[2] += __uint_as_float(v.z); s[3] += __uint_as_float(v.w);
            }
            sts128(sb + SM_CSQ + f * 16, __float_as_uint(s[0]), __float_as_uint(s[1]), __float_as_uint(s[2]), __float_as_uint(s[3]));
            stg128(csf + f * 4, __float_as_uint(s[0]), __float_as_uint(s[1]), __float_as_uint(s[2]), __float_as_uint(s[3]));
          }
          __syncwarp();
          mbar_arrive_if(el, bars + B_CSQ);
        } else {
#pragma unroll 1
          for (int u = 0; u < 4; u++) {
            const int w = u & 1;
            if (u < 2) {
              flag_wait(g_flags + (rb * 2 + w) * 32 + FR_X2, (epoch + 1) * 8);
              fence_async_g();
              TRC(el, 2, 48 + u);
              rows_fetch(el, sb + SM_STG + w * 9216, P.xs[1] + (128 * rb + 16 * j + w) * (DM * 2), bars + B_XRW + w * 8);
            } else {
              mbar_wait(bars + B_XRW + w * 8, w ^ 1);
              TRC(el, 2, 48 + u);
              rows_stats(sb + SM_STG + w * 9216, g_XST + (rb * 2 + w) * 128 + 16 * j, epoch * 2 + 2, lane);
              TRC(el, 2, 50 + u);
            }
          }
          expect_tx_p(el, bars + B_CSQ, 864);
          bulk_load_p(el, sb + 2 * ST_BYTES + SM_CSQ, csf, 864, bars + B_CSQ);
        }
        if (L == 0) {
          TRC(el, 2, 43);
          mbar_wait(bars + B_WOI, 0);
          bulk_store_p(el, g_WO + j * WO_SL + ((9 * rb) >> 1) * 1152, sb + SM_WOI, 5760);
          publish_p(el, fj + FJ_WO);
          TRC(el, 2, 44);
          const uint8_t* sp = lane < 16 ? (const uint8_t*)P.w_in + (30 * lane + 50) * (FH * 4) + FH * 2 + lane * 256 : (const uint8_t*)P.w_sp + (60 * lane) * (SEQ * 2) + lane * 64;
          float sq = 0.f;
#pragma unroll 1
          for (int u = 0; u < 4; u++) {
            const uint4 y = ldnc128(sp + u * 16);
            const uint32_t x[4] = {y.x, y.y, y.z, y.w};
#pragma unroll
            for (int e = 0; e < 4; e++) sq = fmaf(blo(x[e]), blo(x[e]), fmaf(bhi(x[e]), bhi(x[e]), sq));
          }
#pragma unroll 1
          for (int o = 8; o; o >>= 1) sq += __shfl_xor_sync(~0u, sq, o);
          sq *= lane < 16 ? 2.f * GA * GA * DM / 512.f : C0S * C0S * SEQ / 512.f;
          asm("sqrt.approx.f32 %0, %0;" : "+f"(sq));
          const float o0 = __shfl_sync(~0u, sq, 0), o1 = __shfl_sync(~0u, sq, 16);
          const uint32_t off = (__float_as_uint(o0) & 0x7f800000u) >> 16 | 0x8000u | OFM;
          if (el) sts64(sb + SM_OFF, off * 0x10001u, min(__float_as_uint(o1) & 0x7f800000u, 0x7e000000u) | 0x00400000u);
        }
        if (el) mbar_arrive(bars + B_GATE3);
        const uint32_t tag = epoch * 2 + L + 1;
        asm volatile("" : "+r"(lane));
        mbar_wait(bars + B_EVT + EV_ZN * 8, L);
        mbar_wait(bars + B_EVT + (EV_N + EV_ZN) * 8, L);
        flag_release_p(el, fj + FJ_ZN + L);
        TRC(el, 2, L * 16 + 8);
        {
          uint4 v[4];
#pragma unroll 1
          for (int it = 0; it < (1 << 22); it++) {
            bool ok = true;
#pragma unroll
            for (int u = 0; u < 4; u++) { v[u] = ll_ld128(g_ZST + (rb * 2 + ((lane >> 1) & 1)) * 512 + ((lane & 1) * 4 + u) * 64 + 8 * j + (lane >> 2)); ok = ok && v[u].z == tag; }
            if (__all_sync(~0u, ok)) break;
          }
          float mean = __uint_as_float(v[0].x) + __uint_as_float(v[1].x) + __uint_as_float(v[2].x) + __uint_as_float(v[3].x), M2 = 0.f;
          mean = (mean + __shfl_xor_sync(~0u, mean, 1)) * 0.125f;
#pragma unroll
          for (int u = 0; u < 4; u++) { const float d = __uint_as_float(v[u].x) - mean; M2 += fmaf(288.f * d, d, __uint_as_float(v[u].y)); }
          M2 += __shfl_xor_sync(~0u, M2, 1);
          const float rs = blo(pack2(rsqrtf(fmaf(M2, 1.f / FH, 4.f * GA * GA * LN_EPS)), 0.f));
          if (!(lane & 1)) ll_st64(g_RT + 128 * rb + 16 * j + (lane >> 1), pack2(rs, rs * mean), tag);
        }
        TRC(el, 2, L * 16 + 10);
#pragma unroll 1
        for (int b = 0; b < 8; b++) {
          uint4 v[4];
#pragma unroll 1
          for (int it = 0; it < (1 << 22); it++) {
            bool ok = true;
#pragma unroll
            for (int u = 0; u < 4; u++) { v[u] = ll_ld128((const uint4*)g_RT + b * 128 + u * 32 + lane); ok = ok && v[u].y == tag && v[u].w == tag; }
            if (__all_sync(~0u, ok)) break;
          }
#pragma unroll
          for (int u = 0; u < 4; u++) {
            const uint32_t rt = sb + SM_RT + b * 512 + u * 128, ro = (lane >> 3) * 32 + (lane & 3) * 8 + ((lane >> 2) & 1) * 2;
            sts32(rt + 4096 + lane * 4, __byte_perm(v[u].x, v[u].z, 0x7632));
            asm volatile("st.shared.u16 [%0], %1;\nst.shared.u16 [%0 + 4], %2;" ::"r"(rt + ro), "h"((uint16_t)v[u].x), "h"((uint16_t)v[u].z) : "memory");
          }
          __syncwarp();
          if (el && (b == 1 || b == 7)) mbar_arrive(bars + (b == 1 ? B_RT : B_RT1));
          TRC(el && b < 2, 2, L * 16 + 11 + b);
        }
        TRC(el, 2, L * 16 + 9);
        mbar_wait(bars + B_EVT + EV_Z1 * 8, L);
        mbar_wait(bars + B_EVT + (EV_N + EV_Z1) * 8, L);
        fence_gpu();
        if (el) mbar_arrive(bars + B_Z1);
        if (L == 0) {
          __nanosleep(NAP0);
          poison(el, sb + SM_STG + 17152, &P.psn, rb, j, lane);
          if (el) asm volatile("cp.async.bulk.commit_group;\ncp.async.bulk.wait_group 0;" ::: "memory");
          __syncwarp();
          fence_gpu();
        }
      }
    }
  } else {
    CKK(3);
    uint8_t* const wdst = P.wq + j * WQ_SL + rb * 3456 + tid * 16;
#pragma unroll
    for (int u = 0; u < SPL; u++) stg128_if(tid < 216, wdst + u * (16 * 3456), wv[u].x, wv[u].y, wv[u].z, wv[u].w);
    __syncwarp();
    if (lane == 0) mbar_arrive(bars + B_RES + 8);
    CKK(4);
    auto repack2 = [&]() {
#pragma unroll
      for (int u = SPL; u < 5; u++) stg128_if((u < 4 || rb < 8) && tid < 216, wdst + u * (16 * 3456), wv[u].x, wv[u].y, wv[u].z, wv[u].w);
      float s[8];
#pragma unroll
      for (int e = 0; e < 8; e++) s[e] = 0.f;
#pragma unroll
      for (int u = 0; u < 5; u++) {
        uint32_t x[4] = {wv[u].x, wv[u].y, wv[u].z, wv[u].w};
        asm volatile("" : "+r"(x[0]), "+r"(x[1]), "+r"(x[2]), "+r"(x[3]));
#pragma unroll
        for (int e = 0; e < 4; e++) { s[2 * e] += blo(x[e]); s[2 * e + 1] += bhi(x[e]); }
      }
#pragma unroll
      for (int m = 4; m; m >>= 1) {
#pragma unroll
        for (int e = 0; e < m; e++) s[e] = ((tid & m) ? s[e + m] : s[e]) + __shfl_xor_sync(~0u, (tid & m) ? s[e] : s[e + m], m);
      }
      stg32_if(tid < 216, P.csp + bid * 216 + tid, __float_as_uint(s[0]));
      __syncwarp();
      if (lane == 0) mbar_arrive(bars + B_IMG);
    };
    reg_alloc<232>();
    CKK(5);
#pragma unroll
    for (int v = SPL; v < 5; v++) wv[v] = ldnc128_if(tid < 216 && (v < 4 || rb < 8), wsrc + v * (128 * 3 * DM * 2));
    repack2();
    CKK(6);
    const int w = wid >> 2, q = wid & 3;
    int g = lane >> 2, t = lane & 3;
    const uint32_t ev = bars + B_EVT + w * EV_N * 8;
    const bool tr = (tid & 127) == 0;
    (void)tr;
    Cur c{0, 0};
    const uint32_t ebar = mapa(bars + B_EMPTY, (bid & 1) ^ (lane & 1));
    auto release = [&](uint32_t s, uint32_t dep = 0) { mbar_arrive_cluster_if(lane < 2, ebar + s * 8 + dep); };
    auto release_if = [&](bool on, uint32_t s) { mbar_arrive_cluster_if(lane < 2 && on, ebar + s * 8); };
    uint32_t ia = 0;
    auto wait_ab = [&]() { mbar_wait_c(bars + B_FULL + c.s * 8, c.ph); mbar_wait_c(bars + B_FULLA + w * 32 + c.s * 8, (ia >> 2) & 1); ia++; };
    uint32_t lagph = 0;
    auto yield = [&](int left, int lag) { if (w == 1 && left == lag) mbar_wait_c(bars + B_LAG, lagph); };
    auto yield_done = [&]() { if (w == 0 && lane == 0) mbar_arrive(bars + B_LAG); };
    auto signal = [&](int e) { __syncwarp(); mbar_arrive_if(lane == 0, ev + e * 8); };

    const uint32_t epoch = ldcg32(g_flags + (rb * 2 + w) * 32 + FR_EP + j);
    TRC(tr, w, 1);
    CKK(7);
    if (PAD && P.zero) {
#pragma unroll
      for (int i = 0; i < PAD; i++) asm volatile("st.shared.u32 [%0], %1;" ::"r"(sb + i * 20), "r"(tid) : "memory");
    }
    CKK_OUT;

#pragma unroll 1
    for (int L = 0; L < 2; L++) {
      const int tb = 2 + L * 24;
      asm volatile("" : "+r"(lane), "+r"(g), "+r"(t));
      (void)tb;
      ia = 0;
      const uint32_t tag = epoch * 2 + L + 1;
      uint32_t aoff = (w * 64 + q * 16 + (lane & 15)) * 128 + (((lane >> 4) ^ (lane & 7)) << 4);
      {
        uint32_t Pk[27][2];
        float sc0, sc1;
        const uint32_t att = sb + w * 8192 + q * 2048 + lane * 4;
        uint4* hp = g_HALO + ((((rb - (q == 0)) * 2 + w) * 8 + j) * 6) * 32 + lane;
        uint8_t* od = o_block(rb, w) + (9 * j) * 1024 + (2 * q) * 128 + lane * 4;
        ACLK_INIT;
        {
          float acc[108];
#pragma unroll
          for (int i = 0; i < 108; i++) acc[i] = 0.f;
          uint32_t prev = 0;
#pragma unroll 1
          for (int kb = 0; kb < 9; kb++) {
            wait_ab();
            yield(9 - kb, LAG1);
            TRC(tr && kb == 0, w, tb + 0);
            MCLK(kb == 0, 0);
            PCLK(kb * 4);
            const uint32_t st = sb + c.s * ST_BYTES, da = dlo(st + w * 8192, 16), db = dlo(st + ST_B, 3456);
            wgmma_fence();
#pragma unroll
            for (int kk = 0; kk < 4; kk++) {
              wgmma_ss_n216(acc, dsc<1024, 1>(da, kk * 32), dsc<128, 0>(db, kk * 6912), 1);
              if (kk == 0) { wgmma_commit(); wgmma_wait<1>(); release_if(kb > 0, prev); }
            }
            wgmma_commit();
            if (kb == 8) yield_done();
            PCLK(kb * 4 + 1);
            PCLK(kb * 4 + 2);
            PCLK(kb * 4 + 3);
            prev = c.s; c.next();
          }
          const uint32_t cs = sb + prev * ST_BYTES + SM_CSQ + t * 8;
          mbar_wait_c(bars + B_CSQ, L);
          const float2 n0 = lds64f(sb + prev * ST_BYTES + SM_XST + w * 512 + (16 * q + g) * 8), n1 = lds64f(sb + prev * ST_BYTES + SM_XST + w * 512 + (16 * q + g + 8) * 8);
          const float m0 = n0.x, r0 = n0.y, m1 = n1.x, r1 = n1.y;
          float2 cv[27];
#pragma unroll
          for (int G = 0; G < 27; G++) cv[G] = lds64f(cs + G * 32);
          PCLK(36);
          wgmma_wait<0>();
          PCLK(37);
          uint32_t dep = P.zero & __float_as_uint(m0) & __float_as_uint(m1);
#pragma unroll
          for (int G = 0; G < 27; G++) dep &= __float_as_uint(cv[G].x);
          release(prev, dep);
          lagph ^= 1;
          TRC(tr, w, tb + 1);
          MCLK(1, 1);
          ACLK(0);
#pragma unroll
          for (int G = 9; G < 27; G++) Pk[G][1] = pack2(fmaf(m1, cv[G].x, acc[4 * G + 2]) * r1, fmaf(m1, cv[G].y, acc[4 * G + 3]) * r1);
          if (q < 3) {
#pragma unroll
            for (int i = 0; i < 18; i++) sts32(att + (i >> 4) * ST_BYTES + (i & 15) * 128, Pk[9 + i][1]);
          } else if (rb < 15) {
#pragma unroll
            for (int i = 0; i < 6; i++) ll_st128(hp + i * 32, __uint_as_float(Pk[9 + 3 * i][1]), __uint_as_float(Pk[10 + 3 * i][1]), tag, __uint_as_float(Pk[11 + 3 * i][1]));
          }
#pragma unroll
          for (int G = 0; G < 27; G++) {
            if (G < 9) {
              Pk[G][0] = pack2(fmaf(m0, cv[G].x, acc[4 * G]), fmaf(m0, cv[G].y, acc[4 * G + 1]));
              Pk[G][1] = pack2(fmaf(m1, cv[G].x, acc[4 * G + 2]), fmaf(m1, cv[G].y, acc[4 * G + 3]));
            } else {
              Pk[G][0] = pack2(fmaf(m0, cv[G].x, acc[4 * G]) * r0, fmaf(m0, cv[G].y, acc[4 * G + 1]) * r0);
            }
          }
          sc0 = r0 * (0.23570226039551584f * 1.4426950408889634f); sc1 = r1 * (0.23570226039551584f * 1.4426950408889634f);
        }
        ACLK(1);
        constexpr int GA_[4] = {0, 2, 4, 7}, GB_[4] = {1, 3, 5, 8}, GC_[4] = {2, 4, 6, 6};
        float S1[4][4], S2[4][4];
        uint32_t qa[4][2], qc[4][2];
#pragma unroll
        for (int h = 0; h < 4; h++) {
#pragma unroll
          for (int r = 0; r < 2; r++) {
            qa[h][r] = (h == 0 || h == 3 || t >= h) ? Pk[GA_[h]][r] : 0u;
            qc[h][r] = (h == 3 ? t == 3 : t <= h) ? Pk[GC_[h]][r] : 0u;
          }
          mma16(S1[h], qa[h][0], qa[h][1], Pk[GB_[h]][0], Pk[GB_[h]][1], Pk[9 + GA_[h]][0], Pk[9 + GB_[h]][0]);
          mma16(S2[h], qa[h][0], qa[h][1], Pk[GB_[h]][0], Pk[GB_[h]][1], Pk[9 + GA_[h]][1], Pk[9 + GB_[h]][1]);
        }
#pragma unroll
        for (int h = 0; h < 4; h++) {
          mma8(S1[h], qc[h][0], qc[h][1], Pk[9 + GC_[h]][0]);
          mma8(S2[h], qc[h][0], qc[h][1], Pk[9 + GC_[h]][1]);
        }
        uint32_t V1[9], V2[9];
#pragma unroll
        for (int i = 0; i < 9; i++) { V1[i] = movm(Pk[18 + i][0]); V2[i] = movm(Pk[18 + i][1]); }
        const bool remote = q == 0 && rb > 0;
        uint4 hv[6];
#pragma unroll
        for (int i = 0; i < 6; i++) hv[i] = make_uint4(0u, 0u, tag, 0u);
        if (remote) {
#pragma unroll
          for (int i = 0; i < 6; i++) hv[i] = ll_ld128(hp + i * 32);
        }
        const bool up0 = 2 * t > g, up1 = 2 * t + 1 > g;
        const uint32_t mup = (up0 ? 0xffffu : 0u) | (up1 ? 0xffff0000u : 0u);
        auto finish = [&](const float (&x0)[4], const float (&x1)[4], uint32_t ma, const uint32_t (&Vb)[9], int hi) {
          uint32_t pa[4], pb[4];
          float rs[4];
#pragma unroll
          for (int h = 0; h < 4; h++) {
            const float m = qmax(fmaxf(x0[h], x1[h]));
            const uint32_t p = pack2(ex2(x0[h] - m), ex2(x1[h] - m));
            pa[h] = p & ma; pb[h] = p & ~ma;
          }
#pragma unroll
          for (int h = 0; h < 4; h += 2) {
            float R[4];
            mma16(R, pa[h], pa[h + 1], pb[h], pb[h + 1], 0x3f803f80u, 0x3f803f80u);
            rs[h] = rcp_fast(R[0]); rs[h + 1] = rcp_fast(R[2]);
          }
#pragma unroll
          for (int i = 0; i < 9; i++) {
            const int h = 4 * i / 9, e = (h & 1) * 2;
            const bool split = i == 2 || i == 4 || i == 6, nx = split && 2 * t >= i;
            float O[4], N[4];
            mma16(O, pa[h & 2], pa[h | 1], pb[h & 2], pb[h | 1], V1[i], Vb[i]);
            if (i == 4) mma16(N, pa[2], pa[3], pb[2], pb[3], V1[i], Vb[i]); else { N[0] = O[2]; N[1] = O[3]; }
            const float r = nx ? rs[h + (split ? 1 : 0)] : rs[h];
            stg32(od + i * 1024 + hi * 128, pack2((nx ? N[0] : O[e]) * r, (nx ? N[1] : O[e + 1]) * r));
          }
        };
        {
          float x0[4], x1[4];
#pragma unroll
          for (int h = 0; h < 4; h++) { x0[h] = (up0 ? S1[h][2] : S2[h][2]) * sc1; x1[h] = (up1 ? S1[h][3] : S2[h][3]) * sc1; }
          finish(x0, x1, mup, V2, 1);
        }
        ACLK(2);
        bar_sync(1 + w, 128);
        uint32_t H[18];
        if (q > 0) {
#pragma unroll
          for (int i = 0; i < 18; i++) H[i] = lds32(att - 2048 + (i >> 4) * ST_BYTES + (i & 15) * 128);
        } else {
#pragma unroll 1
          for (int it = 0; it < (1 << 20); it++) {
            bool ok = true;
#pragma unroll
            for (int i = 0; i < 6; i++) ok = ok && hv[i].z == tag;
            if (__all_sync(~0u, ok)) break;
#pragma unroll
            for (int i = 0; i < 6; i++) hv[i] = ll_ld128(hp + i * 32);
          }
#pragma unroll
          for (int i = 0; i < 6; i++) { H[3 * i] = hv[i].x; H[3 * i + 1] = hv[i].y; H[3 * i + 2] = hv[i].w; }
        }
        float S0[4][4];
#pragma unroll
        for (int h = 0; h < 4; h++) {
          mma16(S0[h], qa[h][0], qa[h][1], Pk[GB_[h]][0], Pk[GB_[h]][1], H[GA_[h]], H[GB_[h]]);
        }
#pragma unroll
        for (int h = 0; h < 4; h++) mma8(S0[h], qc[h][0], qc[h][1], H[GC_[h]]);
        uint32_t V0[9];
#pragma unroll
        for (int i = 0; i < 9; i++) V0[i] = movm(H[9 + i]);
        ACLK(3);
        {
          const bool nohalo = (rb | q) == 0;
          const float b0 = up0 && nohalo ? -INFINITY : 0.f, b1 = up1 && nohalo ? -INFINITY : 0.f;
          float x0[4], x1[4];
#pragma unroll
          for (int h = 0; h < 4; h++) { x0[h] = fmaf(up0 ? S0[h][0] : S1[h][0], sc0, b0); x1[h] = fmaf(up1 ? S0[h][1] : S1[h][1], sc0, b1); }
          finish(x0, x1, ~mup, V0, 0);
        }
        ACLK(4);
        signal(EV_O);
        ACLK_OUT;
        TRC(tr, w, tb + 2);
        MCLK(1, 2);
      }
      {
        float acc[36];
        const int hw = rb * 2 + (j & 1), js = (j & 6) + w;
        const uint32_t xt = sb + SM_STG + (16 * q + g) * 288 + w * 144 + t * 4;
        uint32_t xm = sb + SM_STG + (16 * q + (lane & 15)) * 288 + (((9 * w + (lane >> 4)) ^ ((lane >> 2) & 1)) << 4), xl = sb + SM_STG + (2 * q + w) * 2304 + lane * 16;
        uint8_t* xd[5];
#pragma unroll
        for (int u = 0; u < 5; u++) {
          const int row = ((u * 32 + lane) * 57) >> 10;
          xd[u] = P.xs[L + 1] + (128 * rb + 32 * q + 16 * w + (j & 1)) * (DM * 2) + (j & 6) * 144 + row * (DM * 4 - 288) + u * 512 + ((lane ^ (row >> 2)) << 4);
          asm volatile("" : "+l"(xd[u]));
        }
        asm volatile("" : "+r"(xm), "+r"(xl));
        mbar_wait_c(bars + B_RES, L);
        TRC(tr, w, tb + 21);
#pragma unroll
        for (int i = 0; i < 18; i++) { const uint32_t x = lds32(xt + (i >> 1) * 16 + (i & 1) * 2304); acc[2 * i] = blo(x); acc[2 * i + 1] = bhi(x); asm volatile("" : "+f"(acc[2 * i]), "+f"(acc[2 * i + 1])); }
        uint32_t prev = 0;
#pragma unroll 1
        for (int u = 0; u < 5; u++) {
          const uint32_t st = sb + c.s * ST_BYTES, da = dlo(st, 1024), db = dlo(st + ST_B + w * 18432, 1152);
          mbar_wait_c(bars + B_FULL + c.s * 8, c.ph); mbar_wait_c(bars + B_FULLA + c.s * 8, (ia >> 2) & 1);
          TRC(tr && u == 0, w, tb + 3);
          MCLK(u == 0, 3);
          wgmma_fence();
#pragma unroll
          for (int kk = 0; kk < 4; kk++) wgmma_ss_n72(acc, dsc<128, 0>(da, kk * 2048), dsc<128, 0>(db, kk * 2304), 1);
          wgmma_commit();
          wgmma_wait<1>();
          release_if(u > 0, prev);
          mbar_wait_c(bars + B_FULLA + 32 + c.s * 8, (ia >> 2) & 1);
          ia++;
          if (u == 4) break;
          wgmma_fence();
#pragma unroll
          for (int kk = 4; kk < 8; kk++) wgmma_ss_n72(acc, dsc<128, 0>(da, kk * 2048), dsc<128, 0>(db, kk * 2304), 1);
          wgmma_commit();
          prev = c.s; c.next();
        }
        RCLK_INIT;
        wgmma_wait<0>();
        RCLK(0);
        release(c.s);
        c.next();
        if (__builtin_expect(any_nan(acc[0], acc[2]), 0)) {
          SLOW(L);
          const uint8_t* xr = P.xs[L] + (128 * rb + 32 * q + 2 * g + (j & 1)) * (DM * 2) + js * 144 + t * 4;
#pragma unroll
          for (int i = 0; i < 18; i++) { const uint32_t x = ldgpu32(xr + (i >> 1) * 16 + (i & 1) * (DM * 32)); acc[2 * i] = blo(x); acc[2 * i + 1] = bhi(x); }
          redo<KS2, 9, 1024, 128, 1152, 128>(acc, o_block(rb, j & 1) + q * 256 + lane * 4, g_WO + js * WO_SL + lane * 4, [](uint32_t*, int) {});
        }
        TRC(tr && P5TRACE != 5, w, tb + 4);
        MCLK(1, 4);
#pragma unroll
        for (int u = 0; u < 4; u++)
          stsm4(xm + u * 32, pack2(acc[8 * u], acc[8 * u + 1]), pack2(acc[8 * u + 2], acc[8 * u + 3]), pack2(acc[8 * u + 4], acc[8 * u + 5]), pack2(acc[8 * u + 6], acc[8 * u + 7]));
        asm volatile("stmatrix.sync.aligned.m8n8.x2.shared.b16 [%0], {%1,%2};" ::"r"(xm + 128), "r"(pack2(acc[32], acc[33])), "r"(pack2(acc[34], acc[35])) : "memory");
        auto stats = [&]() {
          float s0 = 0.f, s1 = 0.f, q0 = 0.f, q1 = 0.f;
#pragma unroll
          for (int i = 0; i < 36; i++) {
            if (i & 2) { s1 += acc[i]; q1 = fmaf(acc[i], acc[i], q1); } else { s0 += acc[i]; q0 = fmaf(acc[i], acc[i], q0); }
          }
          s0 = qsum(s0); s1 = qsum(s1); q0 = qsum(q0); q1 = qsum(q1);
          const float ss = t ? s1 : s0, m = ss * (1.f / 72.f);
          ll_st128_if(t < 2, g_ST1 + (hw * 8 + js) * 64 + 16 * q + 8 * t + g, m, fmaxf((t ? q1 : q0) - ss * m, 0.f), tag);
        };
        stats();
        RCLK(1);
        bar_sync(8 + q, 64);
        RCLK(2);
#pragma unroll
        for (int u = 0; u < 5; u++) {
          const uint4 v = lds128(xl + u * 512);
          stg128_if(u < 4 || lane < 16, xd[u], v.x, v.y, v.z, v.w);
        }
        RCLK(3);
        signal(EV_X1);
        RCLK(4);
        RCLK(5);
        TRC(tr, w, tb + 5);
        RCLK(6);
        RCLK_OUT;
      }
      {
        uint32_t xA[36][4];
        float acc[32];
        uint32_t s0, one, off2;
        uint8_t *z1d, *zd;
        uint64_t db;
        auto bwait = [&](uint32_t dhi, bool skip) {
          s0 = c.s;
          c.next();
          if (!skip) mbar_wait_c(bars + B_FULL + c.s * 8, c.ph);
          db = dsc2(dlo(sb + s0 * ST_BYTES + ST_B, 512) - 3, 0, dhi); one = (c.s ^ P.zero) & 1;
        };
        auto mma = [&](int kk, int pp, bool hand) {
          wgmma_rs_n64(acc, xA[kk], dat(db, (kk / 18) * ST_BYTES + (kk % 18) * 2048 + 48, one), kk != 0);
          if (kk == pp && hand) bar_arrive(7 - w, 256);
          if (kk == 17 || kk == 35) wgmma_commit();
          if (kk == RL3) { wgmma_commit(); wgmma_wait<1>(); release(s0); }
        };
        {
          bwait(0x40000040u, false);
          mbar_wait_c(bars + B_GATE3, L);
          float mean0, mean1, rs0, rs1;
          stat_get(g_ST1 + ((rb * 2 + w) * 8 + 2 * t) * 64 + 16 * q + g, tag, 72.f, LN_EPS, mean0, rs0, mean1, rs1);
          const uint32_t ns0 = pack2(GA * rs0, GA * rs0), ns1 = pack2(GA * rs1, GA * rs1);
          const uint32_t nb0 = pack2(-mean0 * blo(ns0), -mean0 * blo(ns0)), nb1 = pack2(-mean1 * blo(ns1), -mean1 * blo(ns1));
          const uint32_t al = sb + (aoff & 8191);
#pragma unroll
          for (int kb = 0; kb <= 9; kb++) {
            if (kb < 9) {
              mbar_wait_c(bars + B_FA3 + (9 * w + kb) * 8, L);
              TRC(tr && kb == 0, w, tb + 6);
              MCLK(kb == 0, 5);
              if (kb == 0) SCLK(0);
              QCLK(kb);
              const uint32_t at = al + (w ? (((kb + 1) >> 1) & 3) * ST_BYTES + ((kb + 1) & 1) * 8192 : ((kb >> 1) & 3) * ST_BYTES + (kb & 1) * 8192);
#pragma unroll
              for (int kk = 4 * kb; kk < 4 * kb + 4; kk++) ldsm4(xA[kk], at ^ ((kk & 3) << 5));
            }
            if (kb == 0) continue;
            const uint32_t dep = xA[4 * kb - 4][0] & xA[4 * kb - 3][0] & xA[4 * kb - 2][0] & xA[4 * kb - 1][0] & P.zero;
            mbar_arrive_if(lane == 0 && (kb == 1 || w == 0), bars + B_EA3 + (9 * w + kb - 1) * 8 + dep);
#pragma unroll
            for (int kk = 4 * kb - 4; kk < 4 * kb; kk++) {
#pragma unroll
              for (int e = 0; e < 4; e++) xA[kk][e] = hfma2(xA[kk][e], (e & 1) ? ns1 : ns0, (e & 1) ? nb1 : nb0);
            }
            wgmma_fence();
#pragma unroll
            for (int kk = 4 * kb - 4; kk < 4 * kb; kk++) mma(kk, PP30, w);
          }
          off2 = lds32(sb + SM_OFF);
          z1d = z1_block(rb, w, j) + (tid & 127) * 16;
          zd = z2_block(2 * rb + (q >> 1), j) + (4 * (q & 1) + w) * 4608 + ((g & 3) * 2 + (g >> 2)) * 16 + t * 4;
          asm volatile("" : "+l"(z1d), "+l"(zd));
          wgmma_wait<0>();
          if (__builtin_expect(any_nan(acc[0], acc[2]), 0)) {
            SLOW(2 + L);
            uint4* const rd = g_RD + bid * (36 * 256) + tid;
            const uint8_t* xr = P.xs[L + 1] + (128 * rb + 32 * q + 2 * g + w) * (DM * 2) + t * 4;
#pragma unroll
            for (int i = 0; i < 32; i++) acc[i] = 0.f;
            redo<KS3, 8, 16, DM * 32, FH * 32, 16>(acc, xr, (const uint8_t*)P.w_in + g * (FH * 4) + (((9 * j + 1) >> 1) + 36) * 128 + t * 4,
                                              [&](uint32_t* a, int k) {
#pragma unroll
                                                for (int e = 0; e < 4; e++) a[e] = hfma2(a[e], (e & 1) ? ns1 : ns0, (e & 1) ? nb1 : nb0);
                                                stg128(rd + k * 256, a[0], a[1], a[2], a[3]);
                                              });
#pragma unroll
            for (int k = 0; k < 36; k++) { const uint4 v = ldcg128(rd + k * 256); xA[k][0] = v.x; xA[k][1] = v.y; xA[k][2] = v.z; xA[k][3] = v.w; }
          }
        }
        float sm[4] = {0.f, 0.f, 0.f, 0.f}, qq[4] = {0.f, 0.f, 0.f, 0.f};
        auto gelu = [&](auto nz2) {
          constexpr int NZ2 = nz2.value, R = 8 - NZ2, N = 8, D = NZ2 == 8 ? GM2 : NZ2 ? GMM : GM1;
          float th[32], gb = GB;
          uint32_t qa = 0, qb = 0;
          auto head = [&](int G) {
#pragma unroll
            for (int e = 0; e < 4; e++) { const float v = acc[4 * G + e]; th[4 * G + e] = tanh_fast(v * fmaf(v, v, gb)); }
          };
#pragma unroll
          for (int i = 0; i < D; i++) head((i + R) & 7);
#pragma unroll
          for (int i = 0; i < N; i++) {
            const int G = (i + R) & 7;
            if (i + D < N) head((i + D + R) & 7);
            float* z = acc + 4 * G;
#pragma unroll
            for (int e = 0; e < 4; e++) z[e] = fmaf(z[e], th[4 * G + e], z[e]);
            uint32_t pa = pack2(z[0], z[1]), pb = pack2(z[2], z[3]), tok;
            if (i < NZ2) {
#pragma unroll
              for (int e = 0; e < 4; e++) { sm[e] += z[e]; qq[e] = fmaf(z[e], z[e], qq[e]); }
              pa = hsub2(pa, off2); pb = hsub2(pb, off2);
              stg32(zd + i * 128, pa); stg32(zd + i * 128 + 9216, pb);
              tok = pa ^ pb ^ __float_as_uint(qq[1]);
            } else {
              if (G & 1) stg128(z1d + (G >> 1) * 2048 + (NZ2 ? 32768 : 0), qa, qb, pa, pb);
              qa = pa; qb = pb;
              tok = pa ^ pb;
            }
            gb = __uint_as_float(tok * P.zero + __float_as_uint(GB));
          }
        };
#pragma unroll 1
        for (int p = 0;; p++) {
          wgmma_wait<0>();
          release(c.s);
          c.next();
          TRC(tr && p == 4, w, tb + 7);
          TRC(tr && p == 8, w, tb + 11);
          MCLK(p == 8, 6);
          SCLK(2 * p + 1);
          QCLK(10 + 3 * p);
          auto publish = [&]() {
            signal(EV_ZN);
            const float a0 = qsum(sm[0] + sm[1]), a1 = qsum(sm[2] + sm[3]), q0 = qsum(qq[0] + qq[1]), q1 = qsum(qq[2] + qq[3]);
            const float ss = t ? a1 : a0, m = ss * (1.f / 288.f);
            ll_st128_if(t < 2, g_ZST + (rb * 2 + w) * 512 + j * 64 + 16 * q + 8 * t + g, m - blo(off2), fmaxf((t ? q1 : q0) - ss * m, 0.f), tag);
            TRC(tr, w, tb + 8);
            TRC(tr, w, tb + 9);
          };
          if (p < 4) {
            gelu(Int<8>{});
            zd += 1024;
          } else if (p == 4) {
            gelu(Int<4>{});
            publish();
          } else {
            gelu(Int<0>{});
            z1d += 8192;
          }
          SCLK(2 * p + 2);
          QCLK(11 + 3 * p);
          if (p == 8) break;
          bwait(p == 3 ? 0x80000040u : 0x40000040u, w);
          bar_sync(6 + w, 256);
          TRC(tr && p == 4, w, tb + 10);
          wgmma_fence();
#pragma unroll
          for (int kk = 0; kk < 36; kk++) mma(kk, PP3, w == 0 || p < 7);
        }
        signal(EV_Z1);
        TRC(tr, w, tb + 12);
      }
      uint32_t hA[18][4];
      {
        float acc[144];
        const float c0 = __uint_as_float(lds32(sb + SM_OFF + 4));
#pragma unroll
        for (int i = 0; i < 144; i++) {
          asm volatile("fma.rn.f32 %0, %1, %2, %3;" : "=f"(acc[i]) : "f"(__uint_as_float(P.zero)), "f"((float)(i + 2)), "f"(c0));
        }
        uint32_t prev = 0;
        auto stage = [&](int kb) {
          mbar_wait_c(bars + B_FULL + c.s * 8, c.ph);
          TRC(tr && kb == 0, w, tb + 13);
          SCLK(22 + kb);
          const uint32_t st = sb + c.s * ST_BYTES, rt = sb + SM_RT + kb * 128 + t * 8;
          uint64_t db = dsc2(dlo(st + ST_B, 4608), 0, 8 + P.zero);
          uint32_t a[4][4];
#pragma unroll
          for (int kk = 0; kk < 4; kk++) {
            uint32_t r[4];
            ldsm4(r, st + (aoff ^ (kk << 5)));
            const uint2 sc = lds64(rt + kk * 32);
            a[kk][0] = hmul2(__byte_perm(r[0], r[2], 0x5410), sc.x); a[kk][2] = hmul2(__byte_perm(r[0], r[2], 0x7632), sc.y);
            a[kk][1] = hmul2(__byte_perm(r[1], r[3], 0x5410), sc.x); a[kk][3] = hmul2(__byte_perm(r[1], r[3], 0x7632), sc.y);
          }
          if (LAG4 && (kb & 1) == (LAG4 & 1)) yield(32 - kb, LAG4);
          wgmma_fence();
#pragma unroll
          for (int i = 0; i < 8; i++) {
            const int kk = i & 3, hf = i >> 2;
            wgmma_rs_n144(acc + hf * 72, a[kk], db, 1);
            dadd(db, i == 3 ? 144u - 3 * 576 : 576 + P.zero);
            if (i == 0) { wgmma_commit(); wgmma_wait<1>(); release_if(kb, prev); }
            if (i == 3) wgmma_commit();
          }
          wgmma_commit();
          prev = c.s; c.next();
        };
        mbar_wait_c(bars + B_RT, L);
#pragma unroll 1
        for (int kb = 0; kb < 32; kb += 2) {
          if (kb == 8) mbar_wait_c(bars + B_RT1, L);
          MCLK((kb & 7) == 4, 10 + (kb >> 3));
          stage(kb);
          stage(kb + 1);
        }
        if (LAG4) { yield_done(); lagph ^= 1; }
        if (w == 1) bar_arrive(6, 256);
        HCLK(0);
        mbar_wait_c(bars + B_CV + w * 8, L);
        HCLK(1);
        const float gk = 0.5f / GA;
        const float c1 = __uint_as_float(lds32(sb + SM_OFF + 4));
        const float gb0 = -gk * (c1 + __uint_as_float(lds32(sb + SM_CV + w * 256 + (16 * q + g) * 4))), gb1 = -gk * (c1 + __uint_as_float(lds32(sb + SM_CV + w * 256 + (16 * q + g + 8) * 4)));
        mbar_wait_c(w ? bars + B_ZB : bars + B_FULL + c.s * 8, w ? L : c.ph);
        HCLK(2);
        const uint32_t sx = c.s;
        c.next();
        const uint32_t zt = sb + (tid & 127) * 16, zs0 = zt + sx * ST_BYTES + w * ZB, zs1 = w ? zt + SM_STG - 16384 : zs0, zs2 = w ? zt + c.s * ST_BYTES - 20480 : zs0;
        uint4 zz[18];
        auto zload = [&](int u) {
          if (u == ZW && w == 1) mbar_wait_c(bars + B_FULL + c.s * 8, c.ph);
          zz[u] = lds128((u < 8 ? zs0 : u < 10 ? zs1 : zs2) + u * 2048);
        };
#pragma unroll
        for (int u = 0; u < ZA; u++) zload(u);
#pragma unroll
        for (int u = 0; u < 18; u++) {
          if (u == 0) { wgmma_wait<1>(); HCLK(3); }
          if (u == 9) {
            HCLK(4);
            wgmma_wait<0>();
            HCLK(5);
            release(prev);
            mbar_arrive_if(L == 0 && lane == 0, ev + EV_P4 * 8);
            TRC(tr, w, tb + 14);
            SCLK(54);
          }
          if (u + ZA < 18) zload(u + ZA);
          const uint4 z = zz[u];
          hA[u][0] = hmul2(z.x, pack2(fmaf(acc[8 * u], gk, gb0), fmaf(acc[8 * u + 1], gk, gb0)));
          hA[u][1] = hmul2(z.y, pack2(fmaf(acc[8 * u + 2], gk, gb1), fmaf(acc[8 * u + 3], gk, gb1)));
          hA[u][2] = hmul2(z.z, pack2(fmaf(acc[8 * u + 4], gk, gb0), fmaf(acc[8 * u + 5], gk, gb0)));
          hA[u][3] = hmul2(z.w, pack2(fmaf(acc[8 * u + 6], gk, gb1), fmaf(acc[8 * u + 7], gk, gb1)));
        }
        uint32_t dep = P.zero;
#pragma unroll
        for (int u = 0; u < 18; u++) dep &= hA[u][0];
        release(sx, dep);
        TRC(tr, w, tb + 15);
        HCLK(6);
      }
      {
        CLK_INIT;
        uint32_t pk[16];
#pragma unroll
        for (int i = 0; i < 16; i++) pk[i] = 0u;
        auto dump = [&](int p) {
          const uint32_t d = sb + (p & 3) * ST_BYTES, cb = p + j >= 9 ? p + j - 9 : p + j;
          if (lane == 0) asm volatile("cp.async.bulk.wait_group.read 3;" ::: "memory");
          __syncwarp();
#pragma unroll
          for (int u = 0; u < 4; u++) stsm4(d + (aoff ^ (u << 5)), pk[4 * u], pk[4 * u + 1], pk[4 * u + 2], pk[4 * u + 3]);
          fence_async_s();
          __syncwarp();
          tma3d_red_p(lane == 0, &P.red[L], cb * 64, rb * 64 + q * 16, w, d + w * 8192 + q * 2048);
        };
#pragma unroll 1
        for (int p = 0; p < 9; p++) {
          float acc[32];
          CLK(0);
          mbar_wait_c(bars + B_FULL + c.s * 8, c.ph);
          uint64_t db = dsc2(dlo(sb + c.s * ST_BYTES + ST_B + (j & 1) * 4096, 0), 0, 0x40000040u + P.zero);
          CLK(1);
          HCLK(7 + 2 * p);
          bar_sync(6 + w, 256);
          CLK(2);
          wgmma_fence();
#pragma unroll
          for (int kk = 0; kk < 18; kk++) {
            wgmma_rs_n64(acc, hA[kk], db, kk != 0);
            dadd(db, kk == 15 ? 128 - (j & 1) * (36864 >> 4) : 128 + P.zero);
            if (kk == PPK && (w == 0 || p < 8)) bar_arrive(7 - w, 256);
          }
          wgmma_commit();
          CLK(3);
          if (p > 0) dump(p - 1);
          CLK(5);
          wgmma_wait<0>();
          CLK(4);
          HCLK(8 + 2 * p);
          MCLK(p == 1 || p == 8, 7 + (p >> 3));
          release_if(L == 0 || p < 5, c.s);
          c.next();
#pragma unroll
          for (int i = 0; i < 16; i++) pk[i] = pack2(acc[2 * i], acc[2 * i + 1]);
          if (p == 8) { TRC(tr, w, tb + 16); dump(8); TRC(tr, w, tb + 17); }
        }
        if (lane == 0) asm volatile("cp.async.bulk.wait_group 0;" ::: "memory");
        HCLK(25);
        MCLK(1, 9);
        if (L == 0) signal(EV_PT);
        CLK_OUT;
        TRC(tr, w, tb + 18);
      }
    }
    if ((tid & 127) == 0) g_flags[(rb * 2 + w) * 32 + FR_EP + j] = epoch + 1;
    if (tid == 0) g_flags[FJ + j * 32 + FJ_EP + rb] = epoch + 1;
  }
}

typedef CUresult (*EncodeFn)(CUtensorMap*, CUtensorMapDataType, cuuint32_t, void*, const cuuint64_t*, const cuuint64_t*, const cuuint32_t*,
                             const cuuint32_t*, CUtensorMapInterleave, CUtensorMapSwizzle, CUtensorMapL2promotion, CUtensorMapFloatOOBfill);

static void make_map(EncodeFn fn, CUtensorMap* m, const void* ptr, int rank, uint64_t d0, uint64_t d1, uint64_t d2, uint64_t s1, uint64_t s2,
                     uint32_t b0, uint32_t b1, uint32_t b2, CUtensorMapSwizzle swz) {
  cuuint64_t dims[3] = {d0, d1, d2}, strides[2] = {s1, s2};
  cuuint32_t box[3] = {b0, b1, b2}, es[3] = {1, 1, 1};
  fn(m, CU_TENSOR_MAP_DATA_TYPE_BFLOAT16, rank, const_cast<void*>(ptr), dims, strides, box, es, CU_TENSOR_MAP_INTERLEAVE_NONE, swz,
     CU_TENSOR_MAP_L2_PROMOTION_L2_128B, CU_TENSOR_MAP_FLOAT_OOB_FILL_NONE);
}

}

extern "C" void kernel_launch(void* const* d_in, const int* in_sizes, int n_in, void* d_out, int out_size) {
  using namespace mk;
  (void)in_sizes; (void)n_in; (void)out_size;
  static EncodeFn fn = nullptr;
  static uint8_t *wq, *xb;
  static float* csp;
  if (!fn) {
    cudaGetSymbolAddress((void**)&wq, g_WQ);
    cudaGetSymbolAddress((void**)&xb, g_X);
    cudaGetSymbolAddress((void**)&csp, g_CSP);
    cudaDriverEntryPointQueryResult qr;
    cudaGetDriverEntryPoint("cuTensorMapEncodeTiled", (void**)&fn, cudaEnableDefault, &qr);
    cudaFuncSetAttribute(mega_kernel, cudaFuncAttributeMaxDynamicSharedMemorySize, SM_TOTAL);
  }
  Params p;
  p.wqkv = (const __nv_bfloat16*)d_in[1];
  p.w_in = (const __nv_bfloat16*)d_in[4];
  p.w_sp = (const __nv_bfloat16*)d_in[5];
  p.b_sp = (const __nv_bfloat16*)d_in[6];
  p.w_out = (const __nv_bfloat16*)d_in[7];
  p.zero = 0;
  p.wq = wq;
  p.csp = csp;
  p.xs[0] = (uint8_t*)d_in[0];
  p.xs[1] = xb;
  p.xs[2] = (uint8_t*)d_out;
  make_map(fn, &p.wsp, p.w_sp, 3, 2048, 1024, 2, 8192, 4096, 64, 64, 2, CU_TENSOR_MAP_SWIZZLE_128B);
  for (int i = 0; i < 2; i++) {
    make_map(fn, &p.red[i], p.xs[i + 1], 3, DM, 1024, 2, 2304, 1152, 64, 16, 1, CU_TENSOR_MAP_SWIZZLE_128B);
    make_map(fn, &p.res[i], p.xs[i], 3, DM, 1024, 2, 2304, 1152, 144, 64, 1, CU_TENSOR_MAP_SWIZZLE_NONE);
  }
  make_map(fn, &p.psn, d_out, 3, DM, 1024, 2, 2304, 1152, 144, 4, 1, CU_TENSOR_MAP_SWIZZLE_NONE);
  for (int i = 0; i < 3; i++) make_map(fn, &p.act[i], p.xs[i], 3, DM, 1024, 2, 2304, 1152, 64, 64, 1, CU_TENSOR_MAP_SWIZZLE_128B);
  {
    cuuint64_t dims[4] = {8, 8, 72, 72}, strides[3] = {1152, 16, 9216};
    cuuint32_t box[4] = {8, 8, 9, 5}, es[4] = {1, 1, 1, 1};
    fn(&p.wo8, CU_TENSOR_MAP_DATA_TYPE_BFLOAT16, 4, d_in[2], dims, strides, box, es, CU_TENSOR_MAP_INTERLEAVE_NONE, CU_TENSOR_MAP_SWIZZLE_NONE,
       CU_TENSOR_MAP_L2_PROMOTION_L2_128B, CU_TENSOR_MAP_FLOAT_OOB_FILL_NONE);
  }
  for (int i = 0; i < 2; i++) {
    cuuint64_t dims[4] = {i ? 4608u : 2304u, 8, i ? 1u : 2u, 72}, strides[3] = {9216, 4608, 8 * 9216};
    cuuint32_t box[4] = {i ? 64u : 32u, 8, i ? 1u : 2u, 18}, es[4] = {1, 1, 1, 1};
    fn(i ? &p.win64 : &p.win, CU_TENSOR_MAP_DATA_TYPE_BFLOAT16, 4, d_in[4], dims, strides, box, es, CU_TENSOR_MAP_INTERLEAVE_NONE,
       i ? CU_TENSOR_MAP_SWIZZLE_128B : CU_TENSOR_MAP_SWIZZLE_64B, CU_TENSOR_MAP_L2_PROMOTION_L2_128B, CU_TENSOR_MAP_FLOAT_OOB_FILL_NONE);
  }
  make_map(fn, &p.wout, p.w_out, 2, 576, 2304, 1, 1152, 0, 64, 144, 1, CU_TENSOR_MAP_SWIZZLE_128B);
  mega_kernel<<<NGRID, 384, SM_TOTAL, cudaStreamPerThread>>>(p);
}
```

```cpp
#include <cuda_runtime.h>
#include <cuda.h>
#include <cuda_bf16.h>
#include <stdint.h>

#define MK_TRACE 0
#define MK_DBG 0
#define P5TRACE 0
#define LAG1 2
#define PP3 32
#define PP30 33
#define LAG4 1
#define SPL 2
#define NAP 200
#define NAP0 8000
#define KS2 2
#define KS3 2
#define RL3 21
#define PAD 0
#define ZA 4
#define ZW 10
#define GM2 1
#define GMM 1
#define GM1 2
#define C0S 32.f
#define OFM 0x10u
#define PPK 13

namespace mk {

constexpr int SEQ = 2048, DM = 576, FH = 2304;
constexpr int NCTA = 128;
constexpr int NGRID = 132;
constexpr uint32_t ZB = 36864;
constexpr uint32_t WQ_SL = 72 * 3456;
constexpr uint32_t WO_SL = 72 * 1152;
constexpr float LN_EPS = 1e-5f;
constexpr float GA = 0.3292034911525734f, GB = 2.423681954311584f;

constexpr uint32_t ST_BYTES = 53248, ST_B = 16384, NST = 4;
constexpr uint32_t SM_STG = NST * ST_BYTES;
constexpr uint32_t SM_BAR = SM_STG + 2 * 9216;
constexpr uint32_t SM_OFF = SM_BAR + 1008;
constexpr uint32_t SM_TOTAL = SM_BAR + 1024;
constexpr uint32_t SM_RT = SM_STG + 4096, SM_CV = SM_STG + 12288, SM_WT = SM_CV + 512;
constexpr uint32_t SM_WOI = 44032, SM_CSQ = 49792, SM_XST = 50688;
constexpr uint32_t B_FULL = 0, B_EMPTY = 32, B_FULLA = 64, B_RES = 128, B_WT = 144, B_IMG = 160, B_WOI = 168, B_ZB = 176, B_GATE3 = 184, B_Z1 = 192, B_LAG = 200,
                   B_RT = 208, B_CSQ = 216, B_CV = 224, B_AD = 240, B_EVT = 272, B_RT1 = 368, B_XRW = 384, B_FA3 = 400, B_EA3 = 544;
enum { EV_PT = 0, EV_O = 1, EV_X1 = 2, EV_ZN = 3, EV_Z1 = 4, EV_P4 = 5, EV_N = 6 };

enum { FR_X2 = 0, FR_O = 1, FR_X1 = 3, FR_EP = 16, FJ = 32 * 32, FJ_WQ = 0, FJ_WO = 1, FJ_WQ0 = 2, FJ_ZN = 3, FJ_P4 = 5, FJ_EP = 16, F_N = FJ + 8 * 32 };

__device__ __align__(1024) uint8_t g_Z[512 * ZB];
constexpr uint32_t POISON = 0xffffffffu;
__device__ __align__(1024) uint8_t g_O[32 * 2 * ZB];
__device__ __align__(1024) uint4 g_RD[NCTA * 36 * 256];
__device__ __align__(1024) uint8_t g_X[SEQ * DM * 2];
#define SLOW(i) do {} while (0)
__device__ __align__(1024) uint8_t g_WQ[8 * WQ_SL];
__device__ __align__(1024) uint8_t g_WO[8 * WO_SL];
__device__ __align__(1024) float g_CSP[2 * NCTA * 216];
__device__ __align__(1024) uint2 g_RT[SEQ];
__device__ __align__(1024) uint4 g_XST[2 * SEQ];
__device__ __align__(1024) uint4 g_ST1[SEQ * 8];
__device__ __align__(1024) uint4 g_ZST[SEQ * 8];
__device__ __align__(1024) uint4 g_HALO[32 * 8 * 6 * 32];
__device__ __align__(1024) uint32_t g_flags[F_N];

struct Params {
  const __nv_bfloat16 *wqkv;
  uint8_t* wq;
  float* csp;
  uint32_t zero;
  const __nv_bfloat16 *w_in, *w_sp, *b_sp, *w_out;
  uint8_t* xs[3];
  CUtensorMap wo8, wsp, win, win64, wout;
  CUtensorMap act[3];
  CUtensorMap res[2];
  CUtensorMap red[2];
  CUtensorMap psn;
};

__device__ __forceinline__ uint32_t smem_u32(const void* p) { return (uint32_t)__cvta_generic_to_shared(p); }
__device__ __forceinline__ void mbar_init(uint32_t bar, uint32_t cnt) { asm volatile("mbarrier.init.shared::cta.b64 [%0], %1;" ::"r"(bar), "r"(cnt)); }
__device__ __forceinline__ void mbar_arrive(uint32_t bar) { asm volatile("mbarrier.arrive.shared::cta.b64 _, [%0];" ::"r"(bar) : "memory"); }
__device__ __forceinline__ void mbar_wait(uint32_t bar, uint32_t parity) {
  asm volatile(
      "{\n.reg .pred p;\n.reg .u32 c;\nmov.u32 c, 0;\nLAB_WAIT:\n"
      "mbarrier.try_wait.parity.shared::cta.b64 p, [%0], %1;\n@p bra LAB_DONE;\n"
      "add.u32 c, c, 1;\nsetp.lt.u32 p, c, 0x100000;\n@p bra LAB_WAIT;\ntrap;\nLAB_DONE:\n}" ::"r"(bar), "r"(parity)
      : "memory");
}
__device__ __forceinline__ void mbar_wait_c(uint32_t bar, uint32_t parity) {
  asm volatile("{\n.reg .pred p;\nLAB_WAIT:\nmbarrier.try_wait.parity.shared::cta.b64 p, [%0], %1;\n@!p bra LAB_WAIT;\n}" ::"r"(bar), "r"(parity) : "memory");
}
__device__ __forceinline__ void flag_wait(const uint32_t* f, uint32_t target) {
  asm volatile(
      "{\n.reg .pred p;\n.reg .u32 c, v;\nmov.u32 c, 0;\nLAB_WAIT:\n"
      "ld.relaxed.gpu.global.u32 v, [%0];\nsub.u32 v, v, %1;\nsetp.ge.s32 p, v, 0;\n@p bra LAB_DONE;\n"
      "add.u32 c, c, 1;\nsetp.lt.u32 p, c, 0x400000;\n@p bra LAB_WAIT;\ntrap;\nLAB_DONE:\nfence.acquire.gpu;\n}" ::"l"(f), "r"(target)
      : "memory");
}
__device__ __forceinline__ void fence_gpu() { asm volatile("fence.acq_rel.gpu;" ::: "memory"); }
__device__ __forceinline__ void fence_async_g() { asm volatile("fence.proxy.async.global;" ::: "memory"); }
__device__ __forceinline__ void fence_async_s() { asm volatile("fence.proxy.async.shared::cta;" ::: "memory"); }
__device__ __forceinline__ uint32_t elect_one() {
  uint32_t p; asm volatile("{\n.reg .pred P;\nelect.sync _|P, 0xffffffff;\nselp.u32 %0, 1, 0, P;\n}" : "=r"(p)); return p;
}
__device__ __forceinline__ void expect_tx_p(uint32_t el, uint32_t bar, uint32_t bytes) {
  asm volatile("{\n.reg .pred P;\nsetp.ne.u32 P, %2, 0;\n@P mbarrier.arrive.expect_tx.shared::cta.b64 _, [%0], %1;\n}" ::"r"(bar), "r"(bytes), "r"(el) : "memory");
}
__device__ __forceinline__ void bulk_load_p(uint32_t el, uint32_t dst, const void* src, uint32_t bytes, uint32_t bar) {
  asm volatile("{\n.reg .pred P;\nsetp.ne.u32 P, %4, 0;\n@P cp.async.bulk.shared::cluster.global.mbarrier::complete_tx::bytes [%0], [%1], %2, [%3];\n}" ::"r"(dst), "l"(src), "r"(bytes), "r"(bar), "r"(el) : "memory");
}
__device__ __forceinline__ uint64_t policy_evict_first() { uint64_t p; asm("createpolicy.fractional.L2::evict_first.b64 %0, 1.0;" : "=l"(p)); return p; }
__device__ __forceinline__ void bulk_load_h(uint32_t el, uint32_t dst, const void* src, uint32_t bytes, uint32_t bar, bool ef, uint64_t pol) {
  if (ef) {
    asm volatile("{\n.reg .pred P;\nsetp.ne.u32 P, %4, 0;\n@P cp.async.bulk.shared::cluster.global.mbarrier::complete_tx::bytes.L2::cache_hint [%0], [%1], %2, [%3], %5;\n}" ::"r"(dst), "l"(src), "r"(bytes), "r"(bar), "r"(el), "l"(pol) : "memory");
  } else {
    asm volatile("{\n.reg .pred P;\nsetp.ne.u32 P, %4, 0;\n@P cp.async.bulk.shared::cluster.global.mbarrier::complete_tx::bytes [%0], [%1], %2, [%3];\n}" ::"r"(dst), "l"(src), "r"(bytes), "r"(bar), "r"(el) : "memory");
  }
}
__device__ __forceinline__ void bulk_mc_h(uint32_t el, uint32_t dst, const void* src, uint32_t bytes, uint32_t bar, bool ef, uint64_t pol) {
  if (ef) {
    asm volatile("{\n.reg .pred P;\nsetp.ne.u32 P, %4, 0;\n@P cp.async.bulk.shared::cluster.global.mbarrier::complete_tx::bytes.multicast::cluster.L2::cache_hint [%0], [%1], %2, [%3], %5, %6;\n}" ::"r"(dst), "l"(src), "r"(bytes), "r"(bar), "r"(el), "h"((uint16_t)3), "l"(pol) : "memory");
  } else {
    asm volatile("{\n.reg .pred P;\nsetp.ne.u32 P, %4, 0;\n@P cp.async.bulk.shared::cluster.global.mbarrier::complete_tx::bytes.multicast::cluster [%0], [%1], %2, [%3], %5;\n}" ::"r"(dst), "l"(src), "r"(bytes), "r"(bar), "r"(el), "h"((uint16_t)3) : "memory");
  }
}
__device__ __forceinline__ void tma3d_h(uint32_t el, uint32_t dst, const CUtensorMap* m, int c0, int c1, int c2, uint32_t bar, bool ef, uint64_t pol) {
  if (ef) {
    asm volatile("{\n.reg .pred P;\nsetp.ne.u32 P, %6, 0;\n@P cp.async.bulk.tensor.3d.shared::cluster.global.mbarrier::complete_tx::bytes.L2::cache_hint [%0], [%1, {%3, %4, %5}], [%2], %7;\n}" ::"r"(dst), "l"(m), "r"(bar), "r"(c0), "r"(c1), "r"(c2), "r"(el), "l"(pol) : "memory");
  } else {
    asm volatile("{\n.reg .pred P;\nsetp.ne.u32 P, %6, 0;\n@P cp.async.bulk.tensor.3d.shared::cluster.global.mbarrier::complete_tx::bytes [%0], [%1, {%3, %4, %5}], [%2];\n}" ::"r"(dst), "l"(m), "r"(bar), "r"(c0), "r"(c1), "r"(c2), "r"(el) : "memory");
  }
}
__device__ __forceinline__ void tma2d_mc_h(uint32_t el, uint32_t dst, const CUtensorMap* m, int c0, int c1, uint32_t bar, bool ef, uint64_t pol) {
  if (ef) {
    asm volatile("{\n.reg .pred P;\nsetp.ne.u32 P, %5, 0;\n@P cp.async.bulk.tensor.2d.shared::cluster.global.mbarrier::complete_tx::bytes.multicast::cluster.L2::cache_hint [%0], [%1, {%3, %4}], [%2], %6, %7;\n}" ::"r"(dst), "l"(m), "r"(bar), "r"(c0), "r"(c1), "r"(el), "h"((uint16_t)3), "l"(pol) : "memory");
  } else {
    asm volatile("{\n.reg .pred P;\nsetp.ne.u32 P, %5, 0;\n@P cp.async.bulk.tensor.2d.shared::cluster.global.mbarrier::complete_tx::bytes.multicast::cluster [%0], [%1, {%3, %4}], [%2], %6;\n}" ::"r"(dst), "l"(m), "r"(bar), "r"(c0), "r"(c1), "r"(el), "h"((uint16_t)3) : "memory");
  }
}
__device__ __forceinline__ void tma4d_mc(uint32_t el, uint32_t dst, const CUtensorMap* m, int c0, int c3, uint32_t bar, uint64_t pol) {
  asm volatile("{\n.reg .pred P;\nsetp.ne.u32 P, %5, 0;\n@P cp.async.bulk.tensor.4d.shared::cluster.global.mbarrier::complete_tx::bytes.multicast::cluster.L2::cache_hint [%0], [%1, {%3, 0, 0, %4}], [%2], %6, %7;\n}" ::"r"(dst), "l"(m), "r"(bar), "r"(c0), "r"(c3), "r"(el), "h"((uint16_t)3), "l"(pol) : "memory");
}
__device__ __forceinline__ void mbar_arrive_cluster(uint32_t addr) { asm volatile("mbarrier.arrive.shared::cluster.b64 _, [%0];" ::"r"(addr) : "memory"); }
__device__ __forceinline__ void mbar_arrive_cluster_if(bool c, uint32_t addr) {
  asm volatile("{\n.reg .pred P;\nsetp.ne.u32 P, %1, 0;\n@P mbarrier.arrive.shared::cluster.b64 _, [%0];\n}" ::"r"(addr), "r"((uint32_t)c) : "memory");
}
__device__ __forceinline__ void mbar_arrive_if(bool c, uint32_t addr) {
  asm volatile("{\n.reg .pred P;\nsetp.ne.u32 P, %1, 0;\n@P mbarrier.arrive.shared::cta.b64 _, [%0];\n}" ::"r"(addr), "r"((uint32_t)c) : "memory");
}
__device__ __forceinline__ uint32_t mapa(uint32_t addr, uint32_t rank) { uint32_t r; asm("mapa.shared::cluster.u32 %0, %1, %2;" : "=r"(r) : "r"(addr), "r"(rank)); return r; }
__device__ __forceinline__ void bulk_store_p(uint32_t el, void* dst, uint32_t src, uint32_t bytes) {
  asm volatile("{\n.reg .pred P;\nsetp.ne.u32 P, %3, 0;\n@P cp.async.bulk.global.shared::cta.bulk_group [%0], [%1], %2;\n}" ::"l"(dst), "r"(src), "r"(bytes), "r"(el) : "memory");
}
__device__ __forceinline__ void flag_release_p(uint32_t el, uint32_t* f) {
  asm volatile("{\n.reg .pred P;\nsetp.ne.u32 P, %1, 0;\n@P red.release.gpu.global.add.u32 [%0], 1;\n}" ::"l"(f), "r"(el) : "memory");
}
__device__ __forceinline__ void flag_add_p(uint32_t el, uint32_t* f) {
  asm volatile("{\n.reg .pred P;\nsetp.ne.u32 P, %1, 0;\n@P red.relaxed.gpu.global.add.u32 [%0], 1;\n}" ::"l"(f), "r"(el) : "memory");
}
__device__ __forceinline__ void prefetch_l2(const void* src, uint32_t bytes) { asm volatile("cp.async.bulk.prefetch.L2.global [%0], %1;" ::"l"(src), "r"(bytes) : "memory"); }
__device__ __forceinline__ void prefetch_map(const CUtensorMap* m) { asm volatile("prefetch.tensormap [%0];" ::"l"(m) : "memory"); }
__device__ __forceinline__ void wgmma_fence() { asm volatile("wgmma.fence.sync.aligned;" ::: "memory"); }
__device__ __forceinline__ void wgmma_commit() { asm volatile("wgmma.commit_group.sync.aligned;" ::: "memory"); }
template <int N> __device__ __forceinline__ void wgmma_wait() { asm volatile("wgmma.wait_group.sync.aligned %0;" ::"n"(N) : "memory"); }
__device__ __forceinline__ uint32_t dlo(uint32_t addr, uint32_t lbo) { return ((addr & 0x3FFFF) >> 4) + ((lbo >> 4) << 16); }
template <uint32_t SBO, uint32_t SWZ> __device__ __forceinline__ uint64_t dsc(uint32_t lo, uint32_t off) {
  uint64_t d; asm("mov.b64 %0, {%1, %2};" : "=l"(d) : "r"(lo + (off >> 4)), "n"((SBO >> 4) | (SWZ << 30))); return d;
}
__device__ __forceinline__ uint64_t dsc2(uint32_t lo, uint32_t off, uint32_t hi) {
  uint64_t d; asm("mov.b64 %0, {%1, %2};" : "=l"(d) : "r"(lo + (off >> 4)), "r"(hi)); return d;
}
__device__ __forceinline__ uint64_t dat(uint64_t d, uint32_t off, uint32_t one) { uint64_t r; asm("mad.wide.u32 %0, %1, %2, %3;" : "=l"(r) : "r"(one), "r"(off >> 4), "l"(d)); return r; }
__device__ __forceinline__ void dadd(uint64_t& d, uint32_t v) {
  asm("{\n.reg .b32 lo, hi;\nmov.b64 {lo, hi}, %0;\nadd.u32 lo, lo, %1;\nmov.b64 %0, {lo, hi};\n}" : "+l"(d) : "r"(v));
}
template <int R> __device__ __forceinline__ void reg_alloc() { asm volatile("setmaxnreg.inc.sync.aligned.u32 %0;" ::"n"(R)); }
template <int R> __device__ __forceinline__ void reg_dealloc() { asm volatile("setmaxnreg.dec.sync.aligned.u32 %0;" ::"n"(R)); }
__device__ __forceinline__ void bar_sync(int id, int n) { asm volatile("bar.sync %0, %1;" ::"r"(id), "r"(n) : "memory"); }
__device__ __forceinline__ void bar_arrive(int id, int n) { asm volatile("bar.arrive %0, %1;" ::"r"(id), "r"(n) : "memory"); }
__device__ __forceinline__ void ldsm4(uint32_t* r, uint32_t addr) {
  asm volatile("ldmatrix.sync.aligned.m8n8.x4.shared.b16 {%0,%1,%2,%3}, [%4];" : "=r"(r[0]), "=r"(r[1]), "=r"(r[2]), "=r"(r[3]) : "r"(addr) : "memory");
}
__device__ __forceinline__ uint32_t movm(uint32_t a) { uint32_t d; asm volatile("movmatrix.sync.aligned.m8n8.trans.b16 %0, %1;" : "=r"(d) : "r"(a)); return d; }
__device__ __forceinline__ void mma16(float* c, uint32_t a0, uint32_t a1, uint32_t a2, uint32_t a3, uint32_t b0, uint32_t b1) {
  asm volatile("mma.sync.aligned.m16n8k16.row.col.f32.bf16.bf16.f32 {%0,%1,%2,%3}, {%4,%5,%6,%7}, {%8,%9}, {%10,%10,%10,%10};"
               : "=f"(c[0]), "=f"(c[1]), "=f"(c[2]), "=f"(c[3]) : "r"(a0), "r"(a1), "r"(a2), "r"(a3), "r"(b0), "r"(b1), "f"(0.f));
}
__device__ __forceinline__ void mma8(float* c, uint32_t a0, uint32_t a1, uint32_t b0) {
  asm volatile("mma.sync.aligned.m16n8k8.row.col.f32.bf16.bf16.f32 {%0,%1,%2,%3}, {%4,%5}, {%6}, {%0,%1,%2,%3};"
               : "+f"(c[0]), "+f"(c[1]), "+f"(c[2]), "+f"(c[3]) : "r"(a0), "r"(a1), "r"(b0));
}
__device__ __forceinline__ uint32_t pack2(float lo, float hi) { uint32_t r; asm("cvt.rn.bf16x2.f32 %0, %1, %2;" : "=r"(r) : "f"(hi), "f"(lo)); return r; }
__device__ __forceinline__ float blo(uint32_t v) { return __uint_as_float(v << 16); }
__device__ __forceinline__ float bhi(uint32_t v) { return __uint_as_float(v & 0xffff0000u); }
__device__ __forceinline__ float tanh_fast(float x) { float y; asm("tanh.approx.f32 %0, %1;" : "=f"(y) : "f"(x)); return y; }
__device__ __forceinline__ float rcp_fast(float x) { float y; asm("rcp.approx.ftz.f32 %0, %1;" : "=f"(y) : "f"(x)); return y; }
__device__ __forceinline__ float ex2(float x) { float y; asm("ex2.approx.ftz.f32 %0, %1;" : "=f"(y) : "f"(x)); return y; }
__device__ __forceinline__ float qsum(float v) { v += __shfl_xor_sync(~0u, v, 1); v += __shfl_xor_sync(~0u, v, 2); return v; }
__device__ __forceinline__ float qmax(float v) { v = fmaxf(v, __shfl_xor_sync(~0u, v, 1)); v = fmaxf(v, __shfl_xor_sync(~0u, v, 2)); return v; }
__device__ __forceinline__ void stg32(void* p, uint32_t v) { asm volatile("st.global.u32 [%0], %1;" ::"l"(p), "r"(v) : "memory"); }
__device__ __forceinline__ void stg128(void* p, uint32_t a, uint32_t b, uint32_t c, uint32_t d) { asm volatile("st.global.v4.u32 [%0], {%1,%2,%3,%4};" ::"l"(p), "r"(a), "r"(b), "r"(c), "r"(d) : "memory"); }
__device__ __forceinline__ uint32_t ldcg32(const void* p) { uint32_t v; asm volatile("ld.global.L1::no_allocate.u32 %0, [%1];" : "=r"(v) : "l"(p) : "memory"); return v; }
__device__ __forceinline__ uint32_t ldgpu32(const void* p) { uint32_t v; asm volatile("ld.relaxed.gpu.global.u32 %0, [%1];" : "=r"(v) : "l"(p) : "memory"); return v; }
__device__ __forceinline__ uint32_t ldca32(const void* p) { uint32_t v; asm volatile("ld.global.ca.u32 %0, [%1];" : "=r"(v) : "l"(p) : "memory"); return v; }
__device__ __forceinline__ void stg128_if(bool c, void* p, uint32_t a, uint32_t b, uint32_t cc, uint32_t d) {
  asm volatile("{\n.reg .pred P;\nsetp.ne.u32 P, %5, 0;\n@P st.global.v4.u32 [%0], {%1,%2,%3,%4};\n}" ::"l"(p), "r"(a), "r"(b), "r"(cc), "r"(d), "r"((uint32_t)c) : "memory");
}
__device__ __forceinline__ uint2 lds64(uint32_t a) { uint2 v; asm volatile("ld.shared.v2.u32 {%0,%1}, [%2];" : "=r"(v.x), "=r"(v.y) : "r"(a) : "memory"); return v; }
__device__ __forceinline__ uint4 ldcg128(const void* p) { uint4 v; asm volatile("ld.global.cg.v4.u32 {%0,%1,%2,%3}, [%4];" : "=r"(v.x), "=r"(v.y), "=r"(v.z), "=r"(v.w) : "l"(p) : "memory"); return v; }
__device__ __forceinline__ uint32_t ldnc16(const void* p) { uint16_t v; asm volatile("ld.global.nc.u16 %0, [%1];" : "=h"(v) : "l"(p)); return v; }
__device__ __forceinline__ uint4 ldnc128(const void* p) { uint4 v; asm volatile("ld.global.nc.v4.u32 {%0,%1,%2,%3}, [%4];" : "=r"(v.x), "=r"(v.y), "=r"(v.z), "=r"(v.w) : "l"(p)); return v; }
__device__ __forceinline__ uint32_t hsub2(uint32_t a, uint32_t b) { uint32_t d; asm("sub.rn.bf16x2 %0, %1, %2;" : "=r"(d) : "r"(a), "r"(b)); return d; }
__device__ __forceinline__ void stg32_if(bool c, void* p, uint32_t v) {
  asm volatile("{\n.reg .pred P;\nsetp.ne.u32 P, %2, 0;\n@P st.global.u32 [%0], %1;\n}" ::"l"(p), "r"(v), "r"((uint32_t)c) : "memory");
}
__device__ __forceinline__ uint32_t hmul2(uint32_t a, uint32_t b) { uint32_t d; asm("mul.rn.bf16x2 %0, %1, %2;" : "=r"(d) : "r"(a), "r"(b)); return d; }
__device__ __forceinline__ void sts32(uint32_t a, uint32_t v) { asm volatile("st.shared.u32 [%0], %1;" ::"r"(a), "r"(v) : "memory"); }
__device__ __forceinline__ uint32_t lds32(uint32_t a) { uint32_t v; asm volatile("ld.shared.u32 %0, [%1];" : "=r"(v) : "r"(a) : "memory"); return v; }
__device__ __forceinline__ void sts128(uint32_t a, uint32_t x, uint32_t y, uint32_t z, uint32_t w) { asm volatile("st.shared.v4.u32 [%0], {%1,%2,%3,%4};" ::"r"(a), "r"(x), "r"(y), "r"(z), "r"(w) : "memory"); }
__device__ __forceinline__ uint4 lds128(uint32_t a) { uint4 v; asm volatile("ld.shared.v4.u32 {%0,%1,%2,%3}, [%4];" : "=r"(v.x), "=r"(v.y), "=r"(v.z), "=r"(v.w) : "r"(a) : "memory"); return v; }
__device__ __forceinline__ void ll_st64(uint2* p, uint32_t v, uint32_t tag) {
  asm volatile("{\n.reg .b64 r;\nmov.b64 r, {%1,%2};\nst.relaxed.gpu.global.b64 [%0], r;\n}" ::"l"(p), "r"(v), "r"(tag) : "memory");
}
__device__ __forceinline__ uint2 ll_ld64(const uint2* p) {
  uint2 v; asm volatile("{\n.reg .b64 r;\nld.relaxed.gpu.global.b64 r, [%2];\nmov.b64 {%0,%1}, r;\n}" : "=r"(v.x), "=r"(v.y) : "l"(p) : "memory"); return v;
}
__device__ __forceinline__ void ll_st128(uint4* p, float a, float b, uint32_t tag, float c = 0.f) {
  asm volatile("{\n.reg .b128 r;\n.reg .b64 lo, hi;\nmov.b64 lo, {%1,%2};\nmov.b64 hi, {%3,%4};\nmov.b128 r, {lo, hi};\nst.relaxed.gpu.global.b128 [%0], r;\n}" ::"l"(p), "r"(__float_as_uint(a)), "r"(__float_as_uint(b)), "r"(tag), "r"(__float_as_uint(c)) : "memory");
}
__device__ __forceinline__ uint4 ll_ld128(const uint4* p) {
  uint4 v; asm volatile("{\n.reg .b128 r;\n.reg .b64 lo, hi;\nld.relaxed.gpu.global.b128 r, [%4];\nmov.b128 {lo, hi}, r;\nmov.b64 {%0,%1}, lo;\nmov.b64 {%2,%3}, hi;\n}" : "=r"(v.x), "=r"(v.y), "=r"(v.z), "=r"(v.w) : "l"(p) : "memory"); return v;
}
__device__ __forceinline__ void publish_p(uint32_t el, uint32_t* f) {
  asm volatile("{\n.reg .pred P;\nsetp.ne.u32 P, %1, 0;\n@P cp.async.bulk.commit_group;\n@P cp.async.bulk.wait_group 0;\n@P red.release.gpu.global.add.u32 [%0], 1;\n}" ::"l"(f), "r"(el) : "memory");
}
__device__ __forceinline__ void tma3d_red_p(uint32_t el, const CUtensorMap* m, int c0, int c1, int c2, uint32_t src) {
  asm volatile("{\n.reg .pred P;\nsetp.ne.u32 P, %5, 0;\n@P cp.reduce.async.bulk.tensor.3d.global.shared::cta.add.tile.bulk_group [%0, {%2, %3, %4}], [%1];\n@P cp.async.bulk.commit_group;\n}" ::"l"(m), "r"(src), "r"(c0), "r"(c1), "r"(c2), "r"(el) : "memory");
}
__device__ __forceinline__ void stsm4(uint32_t addr, uint32_t a, uint32_t b, uint32_t c, uint32_t d) {
  asm volatile("stmatrix.sync.aligned.m8n8.x4.shared.b16 [%0], {%1,%2,%3,%4};" ::"r"(addr), "r"(a), "r"(b), "r"(c), "r"(d) : "memory");
}
__device__ __forceinline__ void sts64(uint32_t a, uint32_t x, uint32_t y) { asm volatile("st.shared.v2.u32 [%0], {%1,%2};" ::"r"(a), "r"(x), "r"(y) : "memory"); }
__device__ __forceinline__ void ll_st128_if(bool on, uint4* p, float a, float b, uint32_t tag) {
  asm volatile("{\n.reg .pred P;\n.reg .b128 r;\n.reg .b64 lo, hi;\nsetp.ne.u32 P, %4, 0;\nmov.b64 lo, {%1,%2};\nmov.b64 hi, {%3,%3};\nmov.b128 r, {lo, hi};\n@P st.relaxed.gpu.global.b128 [%0], r;\n}" ::"l"(p), "r"(__float_as_uint(a)), "r"(__float_as_uint(b)), "r"(tag), "r"((uint32_t)on) : "memory");
}
__device__ __forceinline__ uint4 ldnc128_if(bool c, const void* p) {
  uint4 v = make_uint4(0u, 0u, 0u, 0u);
  asm volatile("{\n.reg .pred P;\nsetp.ne.u32 P, %5, 0;\n@P ld.global.nc.v4.u32 {%0,%1,%2,%3}, [%4];\n}" : "+r"(v.x), "+r"(v.y), "+r"(v.z), "+r"(v.w) : "l"(p), "r"((uint32_t)c));
  return v;
}
__device__ __forceinline__ uint32_t hfma2(uint32_t a, uint32_t b, uint32_t c) { uint32_t d; asm("fma.rn.bf16x2 %0, %1, %2, %3;" : "=r"(d) : "r"(a), "r"(b), "r"(c)); return d; }
__device__ __forceinline__ float2 lds64f(uint32_t a) { float2 v; asm volatile("ld.shared.v2.f32 {%0,%1}, [%2];" : "=f"(v.x), "=f"(v.y) : "r"(a) : "memory"); return v; }
#define TRC(cond, role, idx) do {} while (0)
#define TRV(role, idx, v) do {} while (0)

#define ACLK_INIT do {} while (0)
#define ACLK(i) do {} while (0)
#define ACLK_OUT do {} while (0)
#define QCLK(i) do {} while (0)
#define PH 1
#define RCLK(i) do {} while (0)
#define RCLK_INIT do {} while (0)
#define RCLK_OUT do {} while (0)
#define SCLK(i) do {} while (0)
#define HCLK(i) do {} while (0)
#define MCLK(c, i) do {} while (0)
#define CKK(i) do {} while (0)
#define CKK_OUT do {} while (0)
#define PL 1
#define PCLK(i) do {} while (0)
#define PQ 1
#define CLK_INIT do {} while (0)
#define CLK(i) do {} while (0)
#define CLK_OUT do {} while (0)

__device__ __forceinline__ void wgmma_ss_n216(float* d, uint64_t da, uint64_t db, int scaleD) {
  asm volatile("{\n.reg .pred p;\nsetp.ne.b32 p, %110, 0;\nwgmma.mma_async.sync.aligned.m64n216k16.f32.bf16.bf16 "
    "{%0,%1,%2,%3,%4,%5,%6,%7,%8,%9,%10,%11,%12,%13,%14,%15,%16,%17,%18,%19,%20,%21,%22,%23,%24,%25,%26,%27,%28,%29,%30,%31,%32,%33,%34,%35,%36,%37,%38,%39,%40,%41,%42,%43,%44,%45,%46,%47,%48,%49,%50,%51,%52,%53,%54,%55,%56,%57,%58,%59,%60,%61,%62,%63,%64,%65,%66,%67,%68,%69,%70,%71,%72,%73,%74,%75,%76,%77,%78,%79,%80,%81,%82,%83,%84,%85,%86,%87,%88,%89,%90,%91,%92,%93,%94,%95,%96,%97,%98,%99,%100,%101,%102,%103,%104,%105,%106,%107}, "
    "%108, %109, p, 1, 1, 0, 1;\n}\n"
    : "+f"(d[0]), "+f"(d[1]), "+f"(d[2]), "+f"(d[3]), "+f"(d[4]), "+f"(d[5]), "+f"(d[6]), "+f"(d[7]), "+f"(d[8]), "+f"(d[9]), "+f"(d[10]), "+f"(d[11]), "+f"(d[12]), "+f"(d[13]), "+f"(d[14]), "+f"(d[15]), "+f"(d[16]), "+f"(d[17]), "+f"(d[18]), "+f"(d[19]), "+f"(d[20]), "+f"(d[21]), "+f"(d[22]), "+f"(d[23]), "+f"(d[24]), "+f"(d[25]), "+f"(d[26]), "+f"(d[27]), "+f"(d[28]), "+f"(d[29]), "+f"(d[30]), "+f"(d[31]), "+f"(d[32]), "+f"(d[33]), "+f"(d[34]), "+f"(d[35]), "+f"(d[36]), "+f"(d[37]), "+f"(d[38]), "+f"(d[39]), "+f"(d[40]), "+f"(d[41]), "+f"(d[42]), "+f"(d[43]), "+f"(d[44]), "+f"(d[45]), "+f"(d[46]), "+f"(d[47]), "+f"(d[48]), "+f"(d[49]), "+f"(d[50]), "+f"(d[51]), "+f"(d[52]), "+f"(d[53]), "+f"(d[54]), "+f"(d[55]), "+f"(d[56]), "+f"(d[57]), "+f"(d[58]), "+f"(d[59]), "+f"(d[60]), "+f"(d[61]), "+f"(d[62]), "+f"(d[63]), "+f"(d[64]), "+f"(d[65]), "+f"(d[66]), "+f"(d[67]), "+f"(d[68]), "+f"(d[69]), "+f"(d[70]), "+f"(d[71]), "+f"(d[72]), "+f"(d[73]), "+f"(d[74]), "+f"(d[75]), "+f"(d[76]), "+f"(d[77]), "+f"(d[78]), "+f"(d[79]), "+f"(d[80]), "+f"(d[81]), "+f"(d[82]), "+f"(d[83]), "+f"(d[84]), "+f"(d[85]), "+f"(d[86]), "+f"(d[87]), "+f"(d[88]), "+f"(d[89]), "+f"(d[90]), "+f"(d[91]), "+f"(d[92]), "+f"(d[93]), "+f"(d[94]), "+f"(d[95]), "+f"(d[96]), "+f"(d[97]), "+f"(d[98]), "+f"(d[99]), "+f"(d[100]), "+f"(d[101]), "+f"(d[102]), "+f"(d[103]), "+f"(d[104]), "+f"(d[105]), "+f"(d[106]), "+f"(d[107])
    : "l"(da), "l"(db), "r"(scaleD));
}
__device__ __forceinline__ void wgmma_ss_n72(float* d, uint64_t da, uint64_t db, int scaleD) {
  asm volatile("{\n.reg .pred p;\nsetp.ne.b32 p, %38, 0;\nwgmma.mma_async.sync.aligned.m64n72k16.f32.bf16.bf16 "
    "{%0,%1,%2,%3,%4,%5,%6,%7,%8,%9,%10,%11,%12,%13,%14,%15,%16,%17,%18,%19,%20,%21,%22,%23,%24,%25,%26,%27,%28,%29,%30,%31,%32,%33,%34,%35}, "
    "%36, %37, p, 1, 1, 0, 1;\n}\n"
    : "+f"(d[0]), "+f"(d[1]), "+f"(d[2]), "+f"(d[3]), "+f"(d[4]), "+f"(d[5]), "+f"(d[6]), "+f"(d[7]), "+f"(d[8]), "+f"(d[9]), "+f"(d[10]), "+f"(d[11]), "+f"(d[12]), "+f"(d[13]), "+f"(d[14]), "+f"(d[15]), "+f"(d[16]), "+f"(d[17]), "+f"(d[18]), "+f"(d[19]), "+f"(d[20]), "+f"(d[21]), "+f"(d[22]), "+f"(d[23]), "+f"(d[24]), "+f"(d[25]), "+f"(d[26]), "+f"(d[27]), "+f"(d[28]), "+f"(d[29]), "+f"(d[30]), "+f"(d[31]), "+f"(d[32]), "+f"(d[33]), "+f"(d[34]), "+f"(d[35])
    : "l"(da), "l"(db), "r"(scaleD));
}
__device__ __forceinline__ void wgmma_rs_n144(float* d, const uint32_t* a, uint64_t db, int scaleD) {
  asm volatile("{\n.reg .pred p;\nsetp.ne.b32 p, %77, 0;\nwgmma.mma_async.sync.aligned.m64n144k16.f32.bf16.bf16 "
    "{%0,%1,%2,%3,%4,%5,%6,%7,%8,%9,%10,%11,%12,%13,%14,%15,%16,%17,%18,%19,%20,%21,%22,%23,%24,%25,%26,%27,%28,%29,%30,%31,%32,%33,%34,%35,%36,%37,%38,%39,%40,%41,%42,%43,%44,%45,%46,%47,%48,%49,%50,%51,%52,%53,%54,%55,%56,%57,%58,%59,%60,%61,%62,%63,%64,%65,%66,%67,%68,%69,%70,%71}, "
    "{%72,%73,%74,%75}, %76, p, 1, 1, 1;\n}\n"
    : "+f"(d[0]), "+f"(d[1]), "+f"(d[2]), "+f"(d[3]), "+f"(d[4]), "+f"(d[5]), "+f"(d[6]), "+f"(d[7]), "+f"(d[8]), "+f"(d[9]), "+f"(d[10]), "+f"(d[11]), "+f"(d[12]), "+f"(d[13]), "+f"(d[14]), "+f"(d[15]), "+f"(d[16]), "+f"(d[17]), "+f"(d[18]), "+f"(d[19]), "+f"(d[20]), "+f"(d[21]), "+f"(d[22]), "+f"(d[23]), "+f"(d[24]), "+f"(d[25]), "+f"(d[26]), "+f"(d[27]), "+f"(d[28]), "+f"(d[29]), "+f"(d[30]), "+f"(d[31]), "+f"(d[32]), "+f"(d[33]), "+f"(d[34]), "+f"(d[35]), "+f"(d[36]), "+f"(d[37]), "+f"(d[38]), "+f"(d[39]), "+f"(d[40]), "+f"(d[41]), "+f"(d[42]), "+f"(d[43]), "+f"(d[44]), "+f"(d[45]), "+f"(d[46]), "+f"(d[47]), "+f"(d[48]), "+f"(d[49]), "+f"(d[50]), "+f"(d[51]), "+f"(d[52]), "+f"(d[53]), "+f"(d[54]), "+f"(d[55]), "+f"(d[56]), "+f"(d[57]), "+f"(d[58]), "+f"(d[59]), "+f"(d[60]), "+f"(d[61]), "+f"(d[62]), "+f"(d[63]), "+f"(d[64]), "+f"(d[65]), "+f"(d[66]), "+f"(d[67]), "+f"(d[68]), "+f"(d[69]), "+f"(d[70]), "+f"(d[71])
    : "r"(a[0]), "r"(a[1]), "r"(a[2]), "r"(a[3]), "l"(db), "r"(scaleD));
}
__device__ __forceinline__ void wgmma_rs_n64(float* d, const uint32_t* a, uint64_t db, int scaleD) {
  asm volatile("{\n.reg .pred p;\nsetp.ne.b32 p, %37, 0;\nwgmma.mma_async.sync.aligned.m64n64k16.f32.bf16.bf16 "
    "{%0,%1,%2,%3,%4,%5,%6,%7,%8,%9,%10,%11,%12,%13,%14,%15,%16,%17,%18,%19,%20,%21,%22,%23,%24,%25,%26,%27,%28,%29,%30,%31}, "
    "{%32,%33,%34,%35}, %36, p, 1, 1, 1;\n}\n"
    : "+f"(d[0]), "+f"(d[1]), "+f"(d[2]), "+f"(d[3]), "+f"(d[4]), "+f"(d[5]), "+f"(d[6]), "+f"(d[7]), "+f"(d[8]), "+f"(d[9]), "+f"(d[10]), "+f"(d[11]), "+f"(d[12]), "+f"(d[13]), "+f"(d[14]), "+f"(d[15]), "+f"(d[16]), "+f"(d[17]), "+f"(d[18]), "+f"(d[19]), "+f"(d[20]), "+f"(d[21]), "+f"(d[22]), "+f"(d[23]), "+f"(d[24]), "+f"(d[25]), "+f"(d[26]), "+f"(d[27]), "+f"(d[28]), "+f"(d[29]), "+f"(d[30]), "+f"(d[31])
    : "r"(a[0]), "r"(a[1]), "r"(a[2]), "r"(a[3]), "l"(db), "r"(scaleD));
}

template <int V> struct Int { static constexpr int value = V; };
struct Cur {
  uint32_t s, ph;
  __device__ __forceinline__ void next() { if (++s == NST) { s = 0; ph ^= 1; } }
};

__device__ __forceinline__ uint8_t* z1_block(int rb, int w, int j) { return g_Z + (rb * 16 + w * 8 + j) * ZB; }
__device__ __forceinline__ uint8_t* o_block(int rb, int w) { return g_O + (rb * 2 + w) * (2 * ZB); }
__device__ __forceinline__ uint8_t* z2_block(int kb, int j) { return g_Z + (256 + kb * 8 + j) * ZB; }
__device__ __forceinline__ void combine8(float m0, float q0, float m1, float q1, float n, float eps, float& mean, float& rstd) {
  mean = qsum(m0 + m1) * 0.125f;
  float d0 = m0 - mean, d1 = m1 - mean;
  float M2 = qsum(q0 + q1 + n * (d0 * d0 + d1 * d1));
  rstd = rsqrtf(fmaf(M2, 0.125f / n, eps));
}
__device__ __forceinline__ void stat_get(const uint4* zs, uint32_t tag, float n, float eps, float& m0, float& r0, float& m1, float& r1) {
  uint4 a0, a1, b0, b1;
#pragma unroll 1
  for (int it = 0; it < (1 << 20); it++) {
    a0 = ll_ld128(zs); a1 = ll_ld128(zs + 64); b0 = ll_ld128(zs + 8); b1 = ll_ld128(zs + 72);
    if (__all_sync(~0u, a0.z == tag && a1.z == tag && b0.z == tag && b1.z == tag)) break;
  }
  combine8(__uint_as_float(a0.x), __uint_as_float(a0.y), __uint_as_float(a1.x), __uint_as_float(a1.y), n, eps, m0, r0);
  combine8(__uint_as_float(b0.x), __uint_as_float(b0.y), __uint_as_float(b1.x), __uint_as_float(b1.y), n, eps, m1, r1);
}

__device__ __forceinline__ void rows_fetch(uint32_t el, uint32_t xr, const uint8_t* src, uint32_t bar) {
  expect_tx_p(el, bar, 9216);
#pragma unroll 1
  for (int r = 0; r < 8; r++) bulk_load_p(el, xr + r * 1152, src + r * (DM * 4), 1152, bar);
}
__device__ __forceinline__ void rows_stats(uint32_t xr, uint4* dst, uint32_t tag, int lane) {
  float s[2] = {0.f, 0.f}, q[4] = {0.f, 0.f, 0.f, 0.f};
  const uint32_t a0 = xr + (lane >> 2) * 1152 + (((lane & 3) * 2) ^ (lane >> 2)) * 16;
  uint4 n0 = lds128(a0), n1 = lds128(a0 ^ 16);
#pragma unroll 1
  for (int e = 1; e <= 9; e++) {
    const uint32_t x[8] = {n0.x, n0.y, n0.z, n0.w, n1.x, n1.y, n1.z, n1.w};
    if (e < 9) { n0 = lds128(a0 + e * 128); n1 = lds128((a0 ^ 16) + e * 128); }
#pragma unroll
    for (int u = 0; u < 8; u++) {
      const float lo = blo(x[u]), hi = bhi(x[u]);
      s[u & 1] += lo + hi; q[(u & 1) * 2] = fmaf(lo, lo, q[(u & 1) * 2]); q[(u & 1) * 2 + 1] = fmaf(hi, hi, q[(u & 1) * 2 + 1]);
    }
  }
  const float sx = s[0] + s[1], sq = (q[0] + q[1]) + (q[2] + q[3]);
  const float m = qsum(sx) * (-1.f / DM), r = rsqrtf(fmaxf(fmaf(qsum(sq), 1.f / DM, -m * m), 0.f) + LN_EPS);
  if ((lane & 3) == 0) ll_st128(dst + (lane >> 2) * 2, m, r, tag);
}

__device__ __forceinline__ void poison(uint32_t el, uint32_t src, const CUtensorMap* m, int rb, int j, int lane) {
#pragma unroll 1
  for (int u = lane; u < 72; u += 32) sts128(src + u * 16, POISON, POISON, POISON, POISON);
  fence_async_s();
  __syncwarp();
#pragma unroll 1
  for (int u = 0; u < 16; u++) {
    __nanosleep(NAP);
    bulk_store_p(el, o_block(rb, u >> 3) + j * 9216 + (u & 7) * 1152, src, 1152);
    asm volatile("{\n.reg .pred P;\nsetp.ne.u32 P, %5, 0;\n@P cp.async.bulk.tensor.3d.global.shared::cta.tile.bulk_group [%0, {%2, %3, %4}], [%1];\n}" ::"l"(m), "r"(src), "r"((j & 6) * 72), "r"(rb * 64 + u * 4), "r"(j & 1), "r"(el) : "memory");
  }
}
__device__ __forceinline__ void mma16acc(float* c, const uint32_t* a, uint32_t b0, uint32_t b1) {
  asm volatile("mma.sync.aligned.m16n8k16.row.col.f32.bf16.bf16.f32 {%0,%1,%2,%3}, {%4,%5,%6,%7}, {%8,%9}, {%0,%1,%2,%3};"
               : "+f"(c[0]), "+f"(c[1]), "+f"(c[2]), "+f"(c[3]) : "r"(a[0]), "r"(a[1]), "r"(a[2]), "r"(a[3]), "r"(b0), "r"(b1));
}
template <int KS, int NG, int AK, int AH, int BK, int BG, class F> __device__ __forceinline__ void redo(float* acc, const uint8_t* pa, const uint8_t* pb, F f) {
#pragma unroll 1
  for (int k = 0; k < 36; k += KS) {
    uint32_t a[4 * KS], b[2 * KS][NG];
#pragma unroll 1
    for (int it = 0; it < (1 << 20); it++) {
      bool ok = true;
#pragma unroll
      for (int e = 0; e < 4 * KS; e++) a[e] = ldgpu32(pa + (e >> 1) * AK + (e & 1) * AH);
#pragma unroll
      for (int e = 0; e < 2 * KS * NG; e++) b[e / NG][e % NG] = ldca32(pb + (e / NG) * BK + (e % NG) * BG);
#pragma unroll
      for (int e = 0; e < 4 * KS; e++) ok = ok && a[e] != POISON;
      if (__all_sync(~0u, ok)) break;
    }
#pragma unroll
    for (int e = 0; e < KS; e++) f(a + 4 * e, k + e);
#pragma unroll
    for (int e = 0; e < KS * NG; e++) mma16acc(acc + 4 * (e % NG), a + 4 * (e / NG), movm(b[2 * (e / NG)][e % NG]), movm(b[2 * (e / NG) + 1][e % NG]));
    pa += 2 * KS * AK; pb += 2 * KS * BK;
  }
}
__device__ __forceinline__ bool any_nan(float a, float b) {
  return __any_sync(~0u, a != a || b != b);
}

__global__ void __cluster_dims__(2, 1, 1) __launch_bounds__(384, 1) mega_kernel(const __grid_constant__ Params P) {
  extern __shared__ __align__(1024) uint8_t smem_raw[];
  uint32_t ckk[8];
  (void)ckk;
  CKK(0);
  const uint32_t sb = smem_u32(smem_raw);
  const uint32_t bars = sb + SM_BAR;
  const int tid = threadIdx.x;
  int lane = tid & 31;
  const int wid = __shfl_sync(~0u, tid >> 5, 0);
  const int cl = blockIdx.x >> 1, tp = cl - 36, t7 = (tp * 37) >> 8;
  const int bid = (cl < 4 ? cl * 8 + 32 : tp < 0 ? cl - 4 : cl < 64 ? tp + t7 + 33 : cl) * 2 + (blockIdx.x & 1);
  if (bid >= NCTA) return;
  const int rb = bid & 15, j = bid >> 4;
  { const bool tr = (tid & 127) == 0 && tid < 256; const int w = tid >> 7; (void)tr; (void)w; TRC(tr, w, 0); }
  CKK(1);
  uint4 wv[5];
  const uint8_t* wsrc;
  {
    const int n8 = min(tid >> 3, 26), part = n8 / 9;
    const uint8_t* src = (const uint8_t*)P.wqkv + (8 * rb + (tid & 7)) * (3 * DM * 2) + (part * (DM - 72) + 72 * j + 8 * n8) * 2;
#pragma unroll
    for (int u = 0; u < SPL; u++) wv[u] = ldnc128_if(tid < 216, src + u * (128 * 3 * DM * 2));
    wsrc = src;
  }
  CKK(2);
  if (tid == 352) {
    for (int s = 0; s < (int)NST; s++) {
      mbar_init(bars + B_FULL + s * 8, 1); mbar_init(bars + B_EMPTY + s * 8, 16);
      mbar_init(bars + B_FULLA + s * 8, 1); mbar_init(bars + B_FULLA + 32 + s * 8, 1);
      mbar_init(bars + B_RES + s * 8, 1); mbar_init(bars + B_RT + s * 8, 1); mbar_init(bars + B_AD + s * 8, 2);
    }
    mbar_init(bars + B_IMG, 8); mbar_init(bars + B_RES + 8, 8); mbar_init(bars + B_WOI, 1); mbar_init(bars + B_GATE3, 3); mbar_init(bars + B_Z1, 1); mbar_init(bars + B_ZB, 1); mbar_init(bars + B_LAG, 4);
    mbar_init(bars + B_CSQ, 3); mbar_init(bars + B_RT1, 1); mbar_init(bars + B_XRW, 1); mbar_init(bars + B_XRW + 8, 1);
    for (int e = 0; e < 2 * EV_N; e++) mbar_init(bars + B_EVT + e * 8, 4);
    asm volatile("fence.mbarrier_init.release.cluster;" ::: "memory");
  }
  if (tid == 320) {
#pragma unroll
    for (int e = 0; e < 28; e++) mbar_init(bars + B_FA3 + e * 8, e < 18 ? 1 : 4);
    asm volatile("fence.mbarrier_init.release.cluster;" ::: "memory");
  }
  __syncthreads();

  if (wid >= 8) {
    reg_dealloc<40>();
    const uint32_t el = elect_one();
    const uint64_t pol = policy_evict_first();
    uint32_t* const fj = g_flags + FJ + j * 32;
    if (wid == 8) {
#pragma unroll 1
      for (int i = 0; i < 12; i++) if (el) prefetch_map(&P.act[0] + (i < 7 ? i : i - 12));
      const uint32_t epoch = ldcg32(fj + FJ_EP + rb);
      Cur c{0, 1};
      const uint32_t rk = bid & 1;
      uint32_t st, full;
      auto slot = [&](uint32_t bytes) {
        st = sb + c.s * ST_BYTES; full = bars + B_FULL + c.s * 8;
        mbar_wait(full, c.ph);
        expect_tx_p(el, full, bytes);
        mbar_wait(full - B_FULL + B_EMPTY, c.ph);
      };
#pragma unroll 1
      for (int L = 0; L < 2; L++) {
#pragma unroll 1
        for (int i = 0; i < 14; i++) {
          if (L == 0 && (i == 0 || i == 2 * SPL || i == 9)) {
            flag_wait(fj + (i == 9 ? FJ_WO : i == 2 * SPL ? FJ_WQ : FJ_WQ0), (epoch + 1) * 16);
            if (i == 9) flag_wait(g_flags + FJ + (j ^ 1) * 32 + FJ_WO, (epoch + 1) * 16);
            fence_async_g();
            TRC(el, 2, i == 9 ? 46 : i ? 47 : 45);
          }
          const uint32_t hb = i < 9 ? 13824 : i < 13 ? 18432 : 9216, o = ST_B + rk * (i < 9 ? 13824 : 18432);
          const uint8_t* src = i < 9 ? g_WQ + j * WQ_SL + i * 27648 + rk * 13824 : g_WO + ((j & 6) + rk) * WO_SL + (i - 9) * 18432;
          slot(2 * hb);
          bulk_mc_h(el, st + o, src, hb, full, true, pol);
          c.next();
        }
#pragma unroll 1
        for (int i = 0; i < 18; i++) {
          const int p = i >> 1, col = p == 4 ? (9 * j + ((j & 1) ? 0 : 8)) * 32 : (((9 * j + 1) >> 1) + (p < 4 ? p + 36 : p - 5)) * 64;
          if (i & 1) {
            slot(2 * ZB);
          } else {
            st = sb + c.s * ST_BYTES; full = bars + B_FULL + ((c.s + 1) & 3) * 8;
            mbar_wait(bars + B_EMPTY + c.s * 8, c.ph);
          }
          tma4d_mc(el, st + ST_B + rk * 18432, p == 4 ? &P.win : &P.win64, col, (i & 1) * 36 + rk * 18, full, pol);
          if (el && !(i & 1)) mbar_arrive(bars + B_FULL + c.s * 8);
          c.next();
        }
        TRC(el, 2, L * 16 + 6);
        flag_wait(fj + FJ_ZN + L, (epoch + 1) * 16);
        fence_async_g();
        TRC(el, 2, L * 16 + 7);
#pragma unroll 1
        for (int i = 0; i < 32; i++) {
          const uint8_t* src = z2_block(i, j) + rk * 18432;
          if (i >= 4) mbar_wait(bars + B_AD + c.s * 8, ((i >> 2) & 1) ^ 1);
          slot(ST_BYTES);
          bulk_mc_h(el, st + ST_B + rk * 18432, src, 18432, full, true, pol);
          tma3d_h(el, st, &P.wsp, i * 64, rb * 64, 0, full, true, pol);
          c.next();
        }
        mbar_wait(bars + B_Z1, L);
        fence_async_g();
        expect_tx_p(el, bars + B_ZB, 28672);
        bulk_load_h(el, sb + SM_STG, z1_block(rb, 0, j), 4096, bars + B_ZB, true, pol);
#pragma unroll 1
        for (int i = 0; i < 10; i++) {
          const int cb = i - 1 + j;
          if (i < 4) mbar_wait(bars + B_AD + c.s * 8, 1);
          slot(i ? ZB : 28672);
          if (i == 0) {
            bulk_load_h(el, st, z1_block(rb, 0, j) + 4096, 24576, bars + B_ZB, true, pol);
            bulk_load_h(el, st + 24576, z1_block(rb, 1, j), 28672, full, true, pol);
          } else {
            tma2d_mc_h(el, st + ST_B + rk * 18432, &P.wout, (cb >= 9 ? cb - 9 : cb) * 64, 288 * j + rk * 144, full, true, pol);
          }
          c.next();
        }
      }
    } else if (wid < 11) {
      int w = wid - 9;
      uint32_t* const fr = g_flags + (rb * 2 + w) * 32;
      const uint32_t epoch = ldcg32(fr + FR_EP + j);
      const uint32_t ev = bars + B_EVT + w * EV_N * 8, t8 = (epoch + 1) * 8;
      Cur c{0, 1};
#pragma unroll 1
      for (int L = 0; L < 2; L++) {
        {
          const uint32_t tag = epoch * 2 + L + 1;
          uint4* const xs = g_XST + (rb * 2 + w) * 128;
          if (L) {
            mbar_wait(ev + EV_PT * 8, 0);
            TRC(el, 3, w * 32 + 16);
            flag_release_p(el, fr + FR_X2);
            TRC(el, 3, w * 32 + 17);
          }
#pragma unroll 1
          for (int i = 0; i < 9; i++) {
            const uint32_t full = bars + B_FULLA + w * 32 + c.s * 8, dst = sb + c.s * ST_BYTES + w * 8192;
            if (L == 0 && i == 4) {
              mbar_wait(bars + B_WT + w * 8, 0);
              TRC(el && w == 0, 2, 37);
              rows_stats(sb + SM_STG + w * 9216, xs + 16 * j, tag, lane);
              TRC(el && w == 0, 2, 38);
            }
            const uint32_t src = sb + (L ? 2 * ST_BYTES + SM_WOI : SM_STG + w * 9216);
            if (i == 4) {
#pragma unroll
              for (int u = 0; u < 6; u++) sts128(src + u * 512 + lane * 16, POISON, POISON, POISON, POISON);
              fence_async_s();
              __syncwarp();
            }
            mbar_wait(bars + B_EMPTY + c.s * 8, c.ph);
            expect_tx_p(el, full, 8192);
            if (i < L) { flag_wait(fr + FR_X2, t8); fence_async_g(); }
            tma3d_h(el, dst, &P.act[L], i * 64, rb * 64, w, full, false, pol);
            TRC(el && i < L, 3, w * 32 + 18);
            c.next();
            if (i >= 4 && i < (L ? 5 : 8)) {
              int b = (rb * 2 + w) * 8 + j;
              asm volatile("" : "+r"(b));
              bulk_store_p(el, i == 4 ? (uint8_t*)g_HALO + b * 3072 : g_O + (b * 3 + i - 5) * 3072, src, 3072);
              if (i < 6) bulk_store_p(el, (i == 4 ? g_ST1 : g_ZST) + b * 64, src, 1024);
              if (i == 6) bulk_store_p(el, g_RT + b * 8, src, 64);
            }
            if (L == 0 && i == 3) rows_fetch(el, sb + SM_STG + w * 9216, P.xs[0] + (128 * rb + 16 * j + w) * (DM * 2), bars + B_WT + w * 8);
          }
          if (el) asm volatile("cp.async.bulk.commit_group;\ncp.async.bulk.wait_group 0;" ::: "memory");
          __syncwarp();
          if (L == 0) fence_gpu();
          const uint32_t tab = sb + L * (2 * ST_BYTES) + SM_XST + w * 512 + lane * 8;
          TRC(el, 3, w * 32 + L * 16 + 13);
#pragma unroll 1
          for (int it = 0; it < (1 << 22); it++) {
            const uint4 a = ll_ld128(xs + 2 * lane), b = ll_ld128(xs + 64 + 2 * lane);
            if (__all_sync(~0u, a.z == tag && b.z == tag)) { sts64(tab, a.x, a.y); sts64(tab + 256, b.x, b.y); break; }
          }
          __syncwarp();
          mbar_arrive_if(el, bars + B_CSQ);
          TRC(el, 3, w * 32 + L * 16 + 14);
          if (w == 1) {
            mbar_wait(bars + B_CSQ, L);
            expect_tx_p(el, bars + B_RES, 18432);
            tma3d_h(el, sb + SM_STG, &P.res[L], (j & 6) * 72, rb * 64, j & 1, bars + B_RES, !L, pol);
          }
          if (L) flag_wait(fj + FJ_P4, t8 * 4);
        }
        asm volatile("" : "+r"(w));
        uint32_t* const fo = g_flags + (rb * 2 + (j & 1)) * 32 + L;
        {
          const uint8_t* src = o_block(rb, j & 1) + w * 8192;
#pragma unroll 1
          for (int i = 0; i < 5; i++) {
            const uint32_t full = bars + B_FULLA + w * 32 + c.s * 8, dst = sb + c.s * ST_BYTES + w * 8192;
            const bool none = 2 * i + w > 8;
            mbar_wait(bars + B_EMPTY + c.s * 8, c.ph);
            expect_tx_p(el, full, none ? 0 : 8192);
            if (i == 0) {
              mbar_wait(ev + EV_O * 8, L);
              TRC(el, 3, w * 32 + L * 16 + 3);
              flag_add_p(el, fr + FR_O + L);
              TRC(el, 3, w * 32 + L * 16 + 4);
              flag_wait(fo + FR_O, t8);
              fence_async_g();
            }
            if (!none) bulk_load_h(el, dst, src + i * 16384, 8192, full, true, pol);
            TRC(el && i == 0, 3, w * 32 + L * 16 + 5);
            c.next();
          }
        }
        {
          expect_tx_p(lane < 9, bars + B_FA3 + (9 * w + lane) * 8, 8192);
          mbar_wait(ev + EV_X1 * 8, L);
          TRC(el, 3, w * 32 + L * 16 + 6);
          if (L) flag_add_p(el, fo + FR_X1); else flag_release_p(el, fo + FR_X1);
          mbar_arrive_if(el, bars + B_GATE3);
          TRC(el, 3, w * 32 + L * 16 + 7);
          mbar_arrive_if(lane < 2, bars + B_FULLA + w * 32 + ((c.s + lane) & 3) * 8);
#pragma unroll 1
          for (int kb = 0; kb < 9; kb++) {
            const int n = 9 * w + kb;
            const uint32_t dst = sb + ((n >> 1) & 3) * ST_BYTES + (n & 1) * 8192;
            if (kb == 0) { flag_wait(fr + FR_X1 + L, t8); fence_async_g(); }
            if (n >= 8) mbar_wait(bars + B_EA3 + (n - 8) * 8, L);
            tma3d_h(el, dst, &P.act[L + 1], kb * 64, rb * 64, w, bars + B_FA3 + n * 8, false, pol);
            TRC(el && kb == 0, 3, w * 32 + L * 16 + 8);
          }
          c.ph ^= ((c.s + 18) >> 2) & 1; c.s = (c.s + 18) & 3;
        }
        asm volatile("" : "+r"(lane), "+r"(w));
        expect_tx_p(el, bars + B_WT + w * 8, 2048);
#pragma unroll 1
        for (int r = 0; r < 8; r++)
          bulk_load_p(el, sb + SM_WT + w * 2176 + r * 272, (const uint8_t*)P.w_sp + (size_t)(128 * rb + 16 * j + 2 * r + w) * (SEQ * 2) + 30 * 128, 256, bars + B_WT + w * 8);
        float cv = (lane & 3) ? 0.f : -blo(ldnc16(P.b_sp + 128 * rb + 16 * j + 2 * (lane >> 2) + w));
        mbar_wait(bars + B_RT, L);
        mbar_wait(bars + B_WT + w * 8, L ^ 1);
        mbar_wait(ev + EV_Z1 * 8, L);
        const uint32_t ro = (w * 64 + 8 * j + (lane >> 2)) * 128, x0 = ((lane & 3) * 2) ^ (lane >> 2);
#pragma unroll 1
        for (int i = 0; i < 32; i++) {
          const bool tail = (i >> 1) == 4;
          const int kb = tail ? i + 22 : i < 8 ? i : i - 2;
          if (i == 8) mbar_wait(bars + B_RT1, L);
          if (!tail) mbar_wait(bars + B_FULL + c.s * 8, c.ph ^ 1);
#pragma unroll
          for (int e = 0; e < 2; e++) {
            const uint4 a = lds128(!tail ? sb + c.s * ST_BYTES + ro + ((x0 ^ e) << 4) : sb + SM_WT + w * 2176 + (lane >> 2) * 272 + (i - 8) * 128 + (lane & 3) * 32 + e * 16);
            const uint4 m = lds128(sb + SM_RT + 4096 + kb * 128 + (lane & 3) * 32 + e * 16);
            cv = fmaf(blo(a.x), blo(m.x), fmaf(bhi(a.x), bhi(m.x), fmaf(blo(a.y), blo(m.y), fmaf(bhi(a.y), bhi(m.y), cv))));
            cv = fmaf(blo(a.z), blo(m.z), fmaf(bhi(a.z), bhi(m.z), fmaf(blo(a.w), blo(m.w), fmaf(bhi(a.w), bhi(m.w), cv))));
          }
          if (!tail) {
            mbar_arrive_if(el, bars + B_AD + c.s * 8 + (__float_as_uint(cv) & P.zero));
            c.next();
          }
        }
        TRC(el, 3, w * 32 + L * 16 + 11);
        uint32_t tag = t8;
        asm volatile("" : "+r"(tag));
        tag = (tag >> 2) - 1 + L;
        cv = qsum(cv);
        uint2* const cs = (uint2*)(g_XST + (rb * 2 + w) * 128 + 1);
        if ((lane & 3) == 0) ll_st64(cs + 32 * j + (lane >> 2) * 4, __float_as_uint(cv), tag);
#pragma unroll 1
        for (int it = 0; it < (1 << 22); it++) {
          const uint2 a = ll_ld64(cs + 4 * lane), b = ll_ld64(cs + 128 + 4 * lane);
          if (__all_sync(~0u, a.y == tag && b.y == tag)) { sts32(sb + SM_CV + w * 256 + lane * 4, a.x); sts32(sb + SM_CV + w * 256 + 128 + lane * 4, b.x); break; }
        }
        __syncwarp();
        if (el) mbar_arrive(bars + B_CV + w * 8);
        TRC(el, 3, w * 32 + L * 16 + 12);
#pragma unroll 1
        for (int kb = 30; kb < 32; kb++) {
          mbar_wait(bars + B_FULL + c.s * 8, c.ph ^ 1);
          if (el) mbar_arrive(bars + B_AD + c.s * 8);
          c.next();
        }
        c.ph ^= ((c.s + 10) >> 2) & 1; c.s = (c.s + 10) & 3;
        if (L == 0) {
          mbar_wait(ev + EV_P4 * 8, 0);
          flag_add_p(el, fj + FJ_P4);
        }
      }
    } else {
      const uint32_t epoch = ldcg32(fj + FJ_EP + rb);
      if (SPL) {
        mbar_wait(bars + B_RES + 8, 0);
        TRC(el, 2, 41);
        flag_release_p(el, fj + FJ_WQ0);
        TRC(el, 2, 42);
      }
      mbar_wait(bars + B_IMG, 0);
      TRC(el, 2, 39);
      flag_release_p(el, fj + FJ_WQ);
      TRC(el, 2, 40);
#pragma unroll 1
      for (int L = 0; L < 2; L++) {
        auto wo_fetch = [&]() {
          expect_tx_p(el, bars + B_WOI, 5760);
          asm volatile("{\n.reg .pred P;\nsetp.ne.u32 P, %5, 0;\n@P cp.async.bulk.tensor.4d.shared::cluster.global.mbarrier::complete_tx::bytes [%0], [%1, {0, 0, %3, %4}], [%2];\n}" ::"r"(sb + SM_WOI), "l"(&P.wo8), "r"(bars + B_WOI), "r"(9 * j), "r"((9 * rb) >> 1), "r"(el) : "memory");
        };
        float* const csf = g_CSP + (NCTA + bid) * 216;
        if (L == 0) {
          flag_wait(fj + FJ_WQ, (epoch + 1) * 16);
          fence_async_g();
          expect_tx_p(el, bars + B_XRW, 13824);
          bulk_load_p(el, sb + ST_BYTES + SM_WOI, g_CSP + j * 16 * 216, 6912, bars + B_XRW);
          bulk_load_p(el, sb + 2 * ST_BYTES + SM_WOI, g_CSP + (j * 16 + 8) * 216, 6912, bars + B_XRW);
          wo_fetch();
          mbar_wait(bars + B_XRW, 0);
#pragma unroll 1
          for (int f = lane; f < 54; f += 32) {
            float s[4] = {0.f, 0.f, 0.f, 0.f};
#pragma unroll 4
            for (int r = 0; r < 16; r++) {
              const uint4 v = lds128(sb + ST_BYTES + SM_WOI + (r >> 3) * ST_BYTES + (r & 7) * 864 + f * 16);
              s[0] += __uint_as_float(v.x); s[1] += __uint_as_float(v.y); s[2] += __uint_as_float(v.z); s[3] += __uint_as_float(v.w);
            }
            sts128(sb + SM_CSQ + f * 16, __float_as_uint(s[0]), __float_as_uint(s[1]), __float_as_uint(s[2]), __float_as_uint(s[3]));
            stg128(csf + f * 4, __float_as_uint(s[0]), __float_as_uint(s[1]), __float_as_uint(s[2]), __float_as_uint(s[3]));
          }
          __syncwarp();
          mbar_arrive_if(el, bars + B_CSQ);
        } else {
#pragma unroll 1
          for (int u = 0; u < 4; u++) {
            const int w = u & 1;
            if (u < 2) {
              flag_wait(g_flags + (rb * 2 + w) * 32 + FR_X2, (epoch + 1) * 8);
              fence_async_g();
              TRC(el, 2, 48 + u);
              rows_fetch(el, sb + SM_STG + w * 9216, P.xs[1] + (128 * rb + 16 * j + w) * (DM * 2), bars + B_XRW + w * 8);
            } else {
              mbar_wait(bars + B_XRW + w * 8, w ^ 1);
              TRC(el, 2, 48 + u);
              rows_stats(sb + SM_STG + w * 9216, g_XST + (rb * 2 + w) * 128 + 16 * j, epoch * 2 + 2, lane);
              TRC(el, 2, 50 + u);
            }
          }
          expect_tx_p(el, bars + B_CSQ, 864);
          bulk_load_p(el, sb + 2 * ST_BYTES + SM_CSQ, csf, 864, bars + B_CSQ);
        }
        if (L == 0) {
          TRC(el, 2, 43);
          mbar_wait(bars + B_WOI, 0);
          bulk_store_p(el, g_WO + j * WO_SL + ((9 * rb) >> 1) * 1152, sb + SM_WOI, 5760);
          publish_p(el, fj + FJ_WO);
          TRC(el, 2, 44);
          const uint8_t* sp = lane < 16 ? (const uint8_t*)P.w_in + (30 * lane + 50) * (FH * 4) + FH * 2 + lane * 256 : (const uint8_t*)P.w_sp + (60 * lane) * (SEQ * 2) + lane * 64;
          float sq = 0.f;
#pragma unroll 1
          for (int u = 0; u < 4; u++) {
            const uint4 y = ldnc128(sp + u * 16);
            const uint32_t x[4] = {y.x, y.y, y.z, y.w};
#pragma unroll
            for (int e = 0; e < 4; e++) sq = fmaf(blo(x[e]), blo(x[e]), fmaf(bhi(x[e]), bhi(x[e]), sq));
          }
#pragma unroll 1
          for (int o = 8; o; o >>= 1) sq += __shfl_xor_sync(~0u, sq, o);
          sq *= lane < 16 ? 2.f * GA * GA * DM / 512.f : C0S * C0S * SEQ / 512.f;
          asm("sqrt.approx.f32 %0, %0;" : "+f"(sq));
          const float o0 = __shfl_sync(~0u, sq, 0), o1 = __shfl_sync(~0u, sq, 16);
          const uint32_t off = (__float_as_uint(o0) & 0x7f800000u) >> 16 | 0x8000u | OFM;
          if (el) sts64(sb + SM_OFF, off * 0x10001u, min(__float_as_uint(o1) & 0x7f800000u, 0x7e000000u) | 0x00400000u);
        }
        if (el) mbar_arrive(bars + B_GATE3);
        const uint32_t tag = epoch * 2 + L + 1;
        asm volatile("" : "+r"(lane));
        mbar_wait(bars + B_EVT + EV_ZN * 8, L);
        mbar_wait(bars + B_EVT + (EV_N + EV_ZN) * 8, L);
        flag_release_p(el, fj + FJ_ZN + L);
        TRC(el, 2, L * 16 + 8);
        {
          uint4 v[4];
#pragma unroll 1
          for (int it = 0; it < (1 << 22); it++) {
            bool ok = true;
#pragma unroll
            for (int u = 0; u < 4; u++) { v[u] = ll_ld128(g_ZST + (rb * 2 + ((lane >> 1) & 1)) * 512 + ((lane & 1) * 4 + u) * 64 + 8 * j + (lane >> 2)); ok = ok && v[u].z == tag; }
            if (__all_sync(~0u, ok)) break;
          }
          float mean = __uint_as_float(v[0].x) + __uint_as_float(v[1].x) + __uint_as_float(v[2].x) + __uint_as_float(v[3].x), M2 = 0.f;
          mean = (mean + __shfl_xor_sync(~0u, mean, 1)) * 0.125f;
#pragma unroll
          for (int u = 0; u < 4; u++) { const float d = __uint_as_float(v[u].x) - mean; M2 += fmaf(288.f * d, d, __uint_as_float(v[u].y)); }
          M2 += __shfl_xor_sync(~0u, M2, 1);
          const float rs = blo(pack2(rsqrtf(fmaf(M2, 1.f / FH, 4.f * GA * GA * LN_EPS)), 0.f));
          if (!(lane & 1)) ll_st64(g_RT + 128 * rb + 16 * j + (lane >> 1), pack2(rs, rs * mean), tag);
        }
        TRC(el, 2, L * 16 + 10);
#pragma unroll 1
        for (int b = 0; b < 8; b++) {
          uint4 v[4];
#pragma unroll 1
          for (int it = 0; it < (1 << 22); it++) {
            bool ok = true;
#pragma unroll
            for (int u = 0; u < 4; u++) { v[u] = ll_ld128((const uint4*)g_RT + b * 128 + u * 32 + lane); ok = ok && v[u].y == tag && v[u].w == tag; }
            if (__all_sync(~0u, ok)) break;
          }
#pragma unroll
          for (int u = 0; u < 4; u++) {
            const uint32_t rt = sb + SM_RT + b * 512 + u * 128, ro = (lane >> 3) * 32 + (lane & 3) * 8 + ((lane >> 2) & 1) * 2;
            sts32(rt + 4096 + lane * 4, __byte_perm(v[u].x, v[u].z, 0x7632));
            asm volatile("st.shared.u16 [%0], %1;\nst.shared.u16 [%0 + 4], %2;" ::"r"(rt + ro), "h"((uint16_t)v[u].x), "h"((uint16_t)v[u].z) : "memory");
          }
          __syncwarp();
          if (el && (b == 1 || b == 7)) mbar_arrive(bars + (b == 1 ? B_RT : B_RT1));
          TRC(el && b < 2, 2, L * 16 + 11 + b);
        }
        TRC(el, 2, L * 16 + 9);
        mbar_wait(bars + B_EVT + EV_Z1 * 8, L);
        mbar_wait(bars + B_EVT + (EV_N + EV_Z1) * 8, L);
        fence_gpu();
        if (el) mbar_arrive(bars + B_Z1);
        if (L == 0) {
          __nanosleep(NAP0);
          poison(el, sb + SM_STG + 17152, &P.psn, rb, j, lane);
          if (el) asm volatile("cp.async.bulk.commit_group;\ncp.async.bulk.wait_group 0;" ::: "memory");
          __syncwarp();
          fence_gpu();
        }
      }
    }
  } else {
    CKK(3);
    uint8_t* const wdst = P.wq + j * WQ_SL + rb * 3456 + tid * 16;
#pragma unroll
    for (int u = 0; u < SPL; u++) stg128_if(tid < 216, wdst + u * (16 * 3456), wv[u].x, wv[u].y, wv[u].z, wv[u].w);
    __syncwarp();
    if (lane == 0) mbar_arrive(bars + B_RES + 8);
    CKK(4);
    auto repack2 = [&]() {
#pragma unroll
      for (int u = SPL; u < 5; u++) stg128_if((u < 4 || rb < 8) && tid < 216, wdst + u * (16 * 3456), wv[u].x, wv[u].y, wv[u].z, wv[u].w);
      float s[8];
#pragma unroll
      for (int e = 0; e < 8; e++) s[e] = 0.f;
#pragma unroll
      for (int u = 0; u < 5; u++) {
        uint32_t x[4] = {wv[u].x, wv[u].y, wv[u].z, wv[u].w};
        asm volatile("" : "+r"(x[0]), "+r"(x[1]), "+r"(x[2]), "+r"(x[3]));
#pragma unroll
        for (int e = 0; e < 4; e++) { s[2 * e] += blo(x[e]); s[2 * e + 1] += bhi(x[e]); }
      }
#pragma unroll
      for (int m = 4; m; m >>= 1) {
#pragma unroll
        for (int e = 0; e < m; e++) s[e] = ((tid & m) ? s[e + m] : s[e]) + __shfl_xor_sync(~0u, (tid & m) ? s[e] : s[e + m], m);
      }
      stg32_if(tid < 216, P.csp + bid * 216 + tid, __float_as_uint(s[0]));
      __syncwarp();
      if (lane == 0) mbar_arrive(bars + B_IMG);
    };
    reg_alloc<232>();
    CKK(5);
#pragma unroll
    for (int v = SPL; v < 5; v++) wv[v] = ldnc128_if(tid < 216 && (v < 4 || rb < 8), wsrc + v * (128 * 3 * DM * 2));
    repack2();
    CKK(6);
    const int w = wid >> 2, q = wid & 3;
    int g = lane >> 2, t = lane & 3;
    const uint32_t ev = bars + B_EVT + w * EV_N * 8;
    const bool tr = (tid & 127) == 0;
    (void)tr;
    Cur c{0, 0};
    const uint32_t ebar = mapa(bars + B_EMPTY, (bid & 1) ^ (lane & 1));
    auto release = [&](uint32_t s, uint32_t dep = 0) { mbar_arrive_cluster_if(lane < 2, ebar + s * 8 + dep); };
    auto release_if = [&](bool on, uint32_t s) { mbar_arrive_cluster_if(lane < 2 && on, ebar + s * 8); };
    uint32_t ia = 0;
    auto wait_ab = [&]() { mbar_wait_c(bars + B_FULL + c.s * 8, c.ph); mbar_wait_c(bars + B_FULLA + w * 32 + c.s * 8, (ia >> 2) & 1); ia++; };
    uint32_t lagph = 0;
    auto yield = [&](int left, int lag) { if (w == 1 && left == lag) mbar_wait_c(bars + B_LAG, lagph); };
    auto yield_done = [&]() { if (w == 0 && lane == 0) mbar_arrive(bars + B_LAG); };
    auto signal = [&](int e) { __syncwarp(); mbar_arrive_if(lane == 0, ev + e * 8); };

    const uint32_t epoch = ldcg32(g_flags + (rb * 2 + w) * 32 + FR_EP + j);
    TRC(tr, w, 1);
    CKK(7);
    if (PAD && P.zero) {
#pragma unroll
      for (int i = 0; i < PAD; i++) asm volatile("st.shared.u32 [%0], %1;" ::"r"(sb + i * 20), "r"(tid) : "memory");
    }
    CKK_OUT;

#pragma unroll 1
    for (int L = 0; L < 2; L++) {
      const int tb = 2 + L * 24;
      asm volatile("" : "+r"(lane), "+r"(g), "+r"(t));
      (void)tb;
      ia = 0;
      const uint32_t tag = epoch * 2 + L + 1;
      uint32_t aoff = (w * 64 + q * 16 + (lane & 15)) * 128 + (((lane >> 4) ^ (lane & 7)) << 4);
      {
        uint32_t Pk[27][2];
        float sc0, sc1;
        const uint32_t att = sb + w * 8192 + q * 2048 + lane * 4;
        uint4* hp = g_HALO + ((((rb - (q == 0)) * 2 + w) * 8 + j) * 6) * 32 + lane;
        uint8_t* od = o_block(rb, w) + (9 * j) * 1024 + (2 * q) * 128 + lane * 4;
        ACLK_INIT;
        {
          float acc[108];
#pragma unroll
          for (int i = 0; i < 108; i++) acc[i] = 0.f;
          uint32_t prev = 0;
#pragma unroll 1
          for (int kb = 0; kb < 9; kb++) {
            wait_ab();
            yield(9 - kb, LAG1);
            TRC(tr && kb == 0, w, tb + 0);
            MCLK(kb == 0, 0);
            PCLK(kb * 4);
            const uint32_t st = sb + c.s * ST_BYTES, da = dlo(st + w * 8192, 16), db = dlo(st + ST_B, 3456);
            wgmma_fence();
#pragma unroll
            for (int kk = 0; kk < 4; kk++) {
              wgmma_ss_n216(acc, dsc<1024, 1>(da, kk * 32), dsc<128, 0>(db, kk * 6912), 1);
              if (kk == 0) { wgmma_commit(); wgmma_wait<1>(); release_if(kb > 0, prev); }
            }
            wgmma_commit();
            if (kb == 8) yield_done();
            PCLK(kb * 4 + 1);
            PCLK(kb * 4 + 2);
            PCLK(kb * 4 + 3);
            prev = c.s; c.next();
          }
          const uint32_t cs = sb + prev * ST_BYTES + SM_CSQ + t * 8;
          mbar_wait_c(bars + B_CSQ, L);
          const float2 n0 = lds64f(sb + prev * ST_BYTES + SM_XST + w * 512 + (16 * q + g) * 8), n1 = lds64f(sb + prev * ST_BYTES + SM_XST + w * 512 + (16 * q + g + 8) * 8);
          const float m0 = n0.x, r0 = n0.y, m1 = n1.x, r1 = n1.y;
          float2 cv[27];
#pragma unroll
          for (int G = 0; G < 27; G++) cv[G] = lds64f(cs + G * 32);
          PCLK(36);
          wgmma_wait<0>();
          PCLK(37);
          uint32_t dep = P.zero & __float_as_uint(m0) & __float_as_uint(m1);
#pragma unroll
          for (int G = 0; G < 27; G++) dep &= __float_as_uint(cv[G].x);
          release(prev, dep);
          lagph ^= 1;
          TRC(tr, w, tb + 1);
          MCLK(1, 1);
          ACLK(0);
#pragma unroll
          for (int G = 9; G < 27; G++) Pk[G][1] = pack2(fmaf(m1, cv[G].x, acc[4 * G + 2]) * r1, fmaf(m1, cv[G].y, acc[4 * G + 3]) * r1);
          if (q < 3) {
#pragma unroll
            for (int i = 0; i < 18; i++) sts32(att + (i >> 4) * ST_BYTES + (i & 15) * 128, Pk[9 + i][1]);
          } else if (rb < 15) {
#pragma unroll
            for (int i = 0; i < 6; i++) ll_st128(hp + i * 32, __uint_as_float(Pk[9 + 3 * i][1]), __uint_as_float(Pk[10 + 3 * i][1]), tag, __uint_as_float(Pk[11 + 3 * i][1]));
          }
#pragma unroll
          for (int G = 0; G < 27; G++) {
            if (G < 9) {
              Pk[G][0] = pack2(fmaf(m0, cv[G].x, acc[4 * G]), fmaf(m0, cv[G].y, acc[4 * G + 1]));
              Pk[G][1] = pack2(fmaf(m1, cv[G].x, acc[4 * G + 2]), fmaf(m1, cv[G].y, acc[4 * G + 3]));
            } else {
              Pk[G][0] = pack2(fmaf(m0, cv[G].x, acc[4 * G]) * r0, fmaf(m0, cv[G].y, acc[4 * G + 1]) * r0);
            }
          }
          sc0 = r0 * (0.23570226039551584f * 1.4426950408889634f); sc1 = r1 * (0.23570226039551584f * 1.4426950408889634f);
        }
        ACLK(1);
        constexpr int GA_[4] = {0, 2, 4, 7}, GB_[4] = {1, 3, 5, 8}, GC_[4] = {2, 4, 6, 6};
        float S1[4][4], S2[4][4];
        uint32_t qa[4][2], qc[4][2];
#pragma unroll
        for (int h = 0; h < 4; h++) {
#pragma unroll
          for (int r = 0; r < 2; r++) {
            qa[h][r] = (h == 0 || h == 3 || t >= h) ? Pk[GA_[h]][r] : 0u;
            qc[h][r] = (h == 3 ? t == 3 : t <= h) ? Pk[GC_[h]][r] : 0u;
          }
          mma16(S1[h], qa[h][0], qa[h][1], Pk[GB_[h]][0], Pk[GB_[h]][1], Pk[9 + GA_[h]][0], Pk[9 + GB_[h]][0]);
          mma16(S2[h], qa[h][0], qa[h][1], Pk[GB_[h]][0], Pk[GB_[h]][1], Pk[9 + GA_[h]][1], Pk[9 + GB_[h]][1]);
        }
#pragma unroll
        for (int h = 0; h < 4; h++) {
          mma8(S1[h], qc[h][0], qc[h][1], Pk[9 + GC_[h]][0]);
          mma8(S2[h], qc[h][0], qc[h][1], Pk[9 + GC_[h]][1]);
        }
        uint32_t V1[9], V2[9];
#pragma unroll
        for (int i = 0; i < 9; i++) { V1[i] = movm(Pk[18 + i][0]); V2[i] = movm(Pk[18 + i][1]); }
        const bool remote = q == 0 && rb > 0;
        uint4 hv[6];
#pragma unroll
        for (int i = 0; i < 6; i++) hv[i] = make_uint4(0u, 0u, tag, 0u);
        if (remote) {
#pragma unroll
          for (int i = 0; i < 6; i++) hv[i] = ll_ld128(hp + i * 32);
        }
        const bool up0 = 2 * t > g, up1 = 2 * t + 1 > g;
        const uint32_t mup = (up0 ? 0xffffu : 0u) | (up1 ? 0xffff0000u : 0u);
        auto finish = [&](const float (&x0)[4], const float (&x1)[4], uint32_t ma, const uint32_t (&Vb)[9], int hi) {
          uint32_t pa[4], pb[4];
          float rs[4];
#pragma unroll
          for (int h = 0; h < 4; h++) {
            const float m = qmax(fmaxf(x0[h], x1[h]));
            const uint32_t p = pack2(ex2(x0[h] - m), ex2(x1[h] - m));
            pa[h] = p & ma; pb[h] = p & ~ma;
          }
#pragma unroll
          for (int h = 0; h < 4; h += 2) {
            float R[4];
            mma16(R, pa[h], pa[h + 1], pb[h], pb[h + 1], 0x3f803f80u, 0x3f803f80u);
            rs[h] = rcp_fast(R[0]); rs[h + 1] = rcp_fast(R[2]);
          }
#pragma unroll
          for (int i = 0; i < 9; i++) {
            const int h = 4 * i / 9, e = (h & 1) * 2;
            const bool split = i == 2 || i == 4 || i == 6, nx = split && 2 * t >= i;
            float O[4], N[4];
            mma16(O, pa[h & 2], pa[h | 1], pb[h & 2], pb[h | 1], V1[i], Vb[i]);
            if (i == 4) mma16(N, pa[2], pa[3], pb[2], pb[3], V1[i], Vb[i]); else { N[0] = O[2]; N[1] = O[3]; }
            const float r = nx ? rs[h + (split ? 1 : 0)] : rs[h];
            stg32(od + i * 1024 + hi * 128, pack2((nx ? N[0] : O[e]) * r, (nx ? N[1] : O[e + 1]) * r));
          }
        };
        {
          float x0[4], x1[4];
#pragma unroll
          for (int h = 0; h < 4; h++) { x0[h] = (up0 ? S1[h][2] : S2[h][2]) * sc1; x1[h] = (up1 ? S1[h][3] : S2[h][3]) * sc1; }
          finish(x0, x1, mup, V2, 1);
        }
        ACLK(2);
        bar_sync(1 + w, 128);
        uint32_t H[18];
        if (q > 0) {
#pragma unroll
          for (int i = 0; i < 18; i++) H[i] = lds32(att - 2048 + (i >> 4) * ST_BYTES + (i & 15) * 128);
        } else {
#pragma unroll 1
          for (int it = 0; it < (1 << 20); it++) {
            bool ok = true;
#pragma unroll
            for (int i = 0; i < 6; i++) ok = ok && hv[i].z == tag;
            if (__all_sync(~0u, ok)) break;
#pragma unroll
            for (int i = 0; i < 6; i++) hv[i] = ll_ld128(hp + i * 32);
          }
#pragma unroll
          for (int i = 0; i < 6; i++) { H[3 * i] = hv[i].x; H[3 * i + 1] = hv[i].y; H[3 * i + 2] = hv[i].w; }
        }
        float S0[4][4];
#pragma unroll
        for (int h = 0; h < 4; h++) {
          mma16(S0[h], qa[h][0], qa[h][1], Pk[GB_[h]][0], Pk[GB_[h]][1], H[GA_[h]], H[GB_[h]]);
        }
#pragma unroll
        for (int h = 0; h < 4; h++) mma8(S0[h], qc[h][0], qc[h][1], H[GC_[h]]);
        uint32_t V0[9];
#pragma unroll
        for (int i = 0; i < 9; i++) V0[i] = movm(H[9 + i]);
        ACLK(3);
        {
          const bool nohalo = (rb | q) == 0;
          const float b0 = up0 && nohalo ? -INFINITY : 0.f, b1 = up1 && nohalo ? -INFINITY : 0.f;
          float x0[4], x1[4];
#pragma unroll
          for (int h = 0; h < 4; h++) { x0[h] = fmaf(up0 ? S0[h][0] : S1[h][0], sc0, b0); x1[h] = fmaf(up1 ? S0[h][1] : S1[h][1], sc0, b1); }
          finish(x0, x1, ~mup, V0, 0);
        }
        ACLK(4);
        signal(EV_O);
        ACLK_OUT;
        TRC(tr, w, tb + 2);
        MCLK(1, 2);
      }
      {
        float acc[36];
        const int hw = rb * 2 + (j & 1), js = (j & 6) + w;
        const uint32_t xt = sb + SM_STG + (16 * q + g) * 288 + w * 144 + t * 4;
        uint32_t xm = sb + SM_STG + (16 * q + (lane & 15)) * 288 + (((9 * w + (lane >> 4)) ^ ((lane >> 2) & 1)) << 4), xl = sb + SM_STG + (2 * q + w) * 2304 + lane * 16;
        uint8_t* xd[5];
#pragma unroll
        for (int u = 0; u < 5; u++) {
          const int row = ((u * 32 + lane) * 57) >> 10;
          xd[u] = P.xs[L + 1] + (128 * rb + 32 * q + 16 * w + (j & 1)) * (DM * 2) + (j & 6) * 144 + row * (DM * 4 - 288) + u * 512 + ((lane ^ (row >> 2)) << 4);
          asm volatile("" : "+l"(xd[u]));
        }
        asm volatile("" : "+r"(xm), "+r"(xl));
        mbar_wait_c(bars + B_RES, L);
        TRC(tr, w, tb + 21);
#pragma unroll
        for (int i = 0; i < 18; i++) { const uint32_t x = lds32(xt + (i >> 1) * 16 + (i & 1) * 2304); acc[2 * i] = blo(x); acc[2 * i + 1] = bhi(x); asm volatile("" : "+f"(acc[2 * i]), "+f"(acc[2 * i + 1])); }
        uint32_t prev = 0;
#pragma unroll 1
        for (int u = 0; u < 5; u++) {
          const uint32_t st = sb + c.s * ST_BYTES, da = dlo(st, 1024), db = dlo(st + ST_B + w * 18432, 1152);
          mbar_wait_c(bars + B_FULL + c.s * 8, c.ph); mbar_wait_c(bars + B_FULLA + c.s * 8, (ia >> 2) & 1);
          TRC(tr && u == 0, w, tb + 3);
          MCLK(u == 0, 3);
          wgmma_fence();
#pragma unroll
          for (int kk = 0; kk < 4; kk++) wgmma_ss_n72(acc, dsc<128, 0>(da, kk * 2048), dsc<128, 0>(db, kk * 2304), 1);
          wgmma_commit();
          wgmma_wait<1>();
          release_if(u > 0, prev);
          mbar_wait_c(bars + B_FULLA + 32 + c.s * 8, (ia >> 2) & 1);
          ia++;
          if (u == 4) break;
          wgmma_fence();
#pragma unroll
          for (int kk = 4; kk < 8; kk++) wgmma_ss_n72(acc, dsc<128, 0>(da, kk * 2048), dsc<128, 0>(db, kk * 2304), 1);
          wgmma_commit();
          prev = c.s; c.next();
        }
        RCLK_INIT;
        wgmma_wait<0>();
        RCLK(0);
        release(c.s);
        c.next();
        if (__builtin_expect(any_nan(acc[0], acc[2]), 0)) {
          SLOW(L);
          const uint8_t* xr = P.xs[L] + (128 * rb + 32 * q + 2 * g + (j & 1)) * (DM * 2) + js * 144 + t * 4;
#pragma unroll
          for (int i = 0; i < 18; i++) { const uint32_t x = ldgpu32(xr + (i >> 1) * 16 + (i & 1) * (DM * 32)); acc[2 * i] = blo(x); acc[2 * i + 1] = bhi(x); }
          redo<KS2, 9, 1024, 128, 1152, 128>(acc, o_block(rb, j & 1) + q * 256 + lane * 4, g_WO + js * WO_SL + lane * 4, [](uint32_t*, int) {});
        }
        TRC(tr && P5TRACE != 5, w, tb + 4);
        MCLK(1, 4);
#pragma unroll
        for (int u = 0; u < 4; u++)
          stsm4(xm + u * 32, pack2(acc[8 * u], acc[8 * u + 1]), pack2(acc[8 * u + 2], acc[8 * u + 3]), pack2(acc[8 * u + 4], acc[8 * u + 5]), pack2(acc[8 * u + 6], acc[8 * u + 7]));
        asm volatile("stmatrix.sync.aligned.m8n8.x2.shared.b16 [%0], {%1,%2};" ::"r"(xm + 128), "r"(pack2(acc[32], acc[33])), "r"(pack2(acc[34], acc[35])) : "memory");
        auto stats = [&]() {
          float s0 = 0.f, s1 = 0.f, q0 = 0.f, q1 = 0.f;
#pragma unroll
          for (int i = 0; i < 36; i++) {
            if (i & 2) { s1 += acc[i]; q1 = fmaf(acc[i], acc[i], q1); } else { s0 += acc[i]; q0 = fmaf(acc[i], acc[i], q0); }
          }
          s0 = qsum(s0); s1 = qsum(s1); q0 = qsum(q0); q1 = qsum(q1);
          const float ss = t ? s1 : s0, m = ss * (1.f / 72.f);
          ll_st128_if(t < 2, g_ST1 + (hw * 8 + js) * 64 + 16 * q + 8 * t + g, m, fmaxf((t ? q1 : q0) - ss * m, 0.f), tag);
        };
        stats();
        RCLK(1);
        bar_sync(8 + q, 64);
        RCLK(2);
#pragma unroll
        for (int u = 0; u < 5; u++) {
          const uint4 v = lds128(xl + u * 512);
          stg128_if(u < 4 || lane < 16, xd[u], v.x, v.y, v.z, v.w);
        }
        RCLK(3);
        signal(EV_X1);
        RCLK(4);
        RCLK(5);
        TRC(tr, w, tb + 5);
        RCLK(6);
        RCLK_OUT;
      }
      uint4 zk[4];
      {
        uint32_t xA[36][4];
        float acc[32];
        uint32_t s0, one, off2;
        uint8_t *z1d, *zd;
        uint64_t db;
        auto bwait = [&](uint32_t dhi, bool skip) {
          s0 = c.s;
          c.next();
          if (!skip) mbar_wait_c(bars + B_FULL + c.s * 8, c.ph);
          db = dsc2(dlo(sb + s0 * ST_BYTES + ST_B, 512) - 3, 0, dhi); one = (c.s ^ P.zero) & 1;
        };
        auto mma = [&](int kk, int pp, bool hand) {
          wgmma_rs_n64(acc, xA[kk], dat(db, (kk / 18) * ST_BYTES + (kk % 18) * 2048 + 48, one), kk != 0);
          if (kk == pp && hand) bar_arrive(7 - w, 256);
          if (kk == 17 || kk == 35) wgmma_commit();
          if (kk == RL3) { wgmma_commit(); wgmma_wait<1>(); release(s0); }
        };
        {
          bwait(0x40000040u, false);
          mbar_wait_c(bars + B_GATE3, L);
          float mean0, mean1, rs0, rs1;
          stat_get(g_ST1 + ((rb * 2 + w) * 8 + 2 * t) * 64 + 16 * q + g, tag, 72.f, LN_EPS, mean0, rs0, mean1, rs1);
          const uint32_t ns0 = pack2(GA * rs0, GA * rs0), ns1 = pack2(GA * rs1, GA * rs1);
          const uint32_t nb0 = pack2(-mean0 * blo(ns0), -mean0 * blo(ns0)), nb1 = pack2(-mean1 * blo(ns1), -mean1 * blo(ns1));
          const uint32_t al = sb + (aoff & 8191);
#pragma unroll
          for (int kb = 0; kb <= 9; kb++) {
            if (kb < 9) {
              mbar_wait_c(bars + B_FA3 + (9 * w + kb) * 8, L);
              TRC(tr && kb == 0, w, tb + 6);
              MCLK(kb == 0, 5);
              if (kb == 0) SCLK(0);
              QCLK(kb);
              const uint32_t at = al + (w ? (((kb + 1) >> 1) & 3) * ST_BYTES + ((kb + 1) & 1) * 8192 : ((kb >> 1) & 3) * ST_BYTES + (kb & 1) * 8192);
#pragma unroll
              for (int kk = 4 * kb; kk < 4 * kb + 4; kk++) ldsm4(xA[kk], at ^ ((kk & 3) << 5));
            }
            if (kb == 0) continue;
            const uint32_t dep = xA[4 * kb - 4][0] & xA[4 * kb - 3][0] & xA[4 * kb - 2][0] & xA[4 * kb - 1][0] & P.zero;
            mbar_arrive_if(lane == 0 && (kb == 1 || w == 0), bars + B_EA3 + (9 * w + kb - 1) * 8 + dep);
#pragma unroll
            for (int kk = 4 * kb - 4; kk < 4 * kb; kk++) {
#pragma unroll
              for (int e = 0; e < 4; e++) xA[kk][e] = hfma2(xA[kk][e], (e & 1) ? ns1 : ns0, (e & 1) ? nb1 : nb0);
            }
            wgmma_fence();
#pragma unroll
            for (int kk = 4 * kb - 4; kk < 4 * kb; kk++) mma(kk, PP30, w);
          }
          off2 = lds32(sb + SM_OFF);
          z1d = z1_block(rb, w, j) + (tid & 127) * 16;
          zd = z2_block(2 * rb + (q >> 1), j) + (4 * (q & 1) + w) * 4608 + ((g & 3) * 2 + (g >> 2)) * 16 + t * 4;
          asm volatile("" : "+l"(z1d), "+l"(zd));
          wgmma_wait<0>();
          if (__builtin_expect(any_nan(acc[0], acc[2]), 0)) {
            SLOW(2 + L);
            uint4* const rd = g_RD + bid * (36 * 256) + tid;
            const uint8_t* xr = P.xs[L + 1] + (128 * rb + 32 * q + 2 * g + w) * (DM * 2) + t * 4;
#pragma unroll
            for (int i = 0; i < 32; i++) acc[i] = 0.f;
            redo<KS3, 8, 16, DM * 32, FH * 32, 16>(acc, xr, (const uint8_t*)P.w_in + g * (FH * 4) + (((9 * j + 1) >> 1) + 36) * 128 + t * 4,
                                              [&](uint32_t* a, int k) {
#pragma unroll
                                                for (int e = 0; e < 4; e++) a[e] = hfma2(a[e], (e & 1) ? ns1 : ns0, (e & 1) ? nb1 : nb0);
                                                stg128(rd + k * 256, a[0], a[1], a[2], a[3]);
                                              });
#pragma unroll
            for (int k = 0; k < 36; k++) { const uint4 v = ldcg128(rd + k * 256); xA[k][0] = v.x; xA[k][1] = v.y; xA[k][2] = v.z; xA[k][3] = v.w; }
          }
        }
        float sm[4] = {0.f, 0.f, 0.f, 0.f}, qq[4] = {0.f, 0.f, 0.f, 0.f};
        auto gelu = [&](auto nz2, bool out) {
          constexpr int NZ2 = nz2.value, R = 8 - NZ2, N = 8, D = NZ2 == 8 ? GM2 : NZ2 ? GMM : GM1;
          float th[32], gb = GB;
          uint32_t qa = 0, qb = 0;
          auto head = [&](int G) {
#pragma unroll
            for (int e = 0; e < 4; e++) { const float v = acc[4 * G + e]; th[4 * G + e] = tanh_fast(v * fmaf(v, v, gb)); }
          };
#pragma unroll
          for (int i = 0; i < D; i++) head((i + R) & 7);
#pragma unroll
          for (int i = 0; i < N; i++) {
            const int G = (i + R) & 7;
            if (i + D < N) head((i + D + R) & 7);
            float* z = acc + 4 * G;
#pragma unroll
            for (int e = 0; e < 4; e++) z[e] = fmaf(z[e], th[4 * G + e], z[e]);
            uint32_t pa = pack2(z[0], z[1]), pb = pack2(z[2], z[3]), tok;
            if (i < NZ2) {
#pragma unroll
              for (int e = 0; e < 4; e++) { sm[e] += z[e]; qq[e] = fmaf(z[e], z[e], qq[e]); }
              pa = hsub2(pa, off2); pb = hsub2(pb, off2);
              stg32(zd + i * 128, pa); stg32(zd + i * 128 + 9216, pb);
              tok = pa ^ pb ^ __float_as_uint(qq[1]);
            } else {
              if (G & 1) stg128_if(out, z1d + (G >> 1) * 2048 + (NZ2 ? 24576 : 0), qa, qb, pa, pb);
              qa = pa; qb = pb;
              tok = pa ^ pb;
            }
            gb = __uint_as_float(tok * P.zero + __float_as_uint(GB));
          }
        };
#pragma unroll 1
        for (int p = 0;; p++) {
          wgmma_wait<0>();
          release(c.s);
          c.next();
          TRC(tr && p == 4, w, tb + 7);
          TRC(tr && p == 8, w, tb + 11);
          MCLK(p == 8, 6);
          SCLK(2 * p + 1);
          QCLK(10 + 3 * p);
          auto publish = [&]() {
            signal(EV_ZN);
            const float a0 = qsum(sm[0] + sm[1]), a1 = qsum(sm[2] + sm[3]), q0 = qsum(qq[0] + qq[1]), q1 = qsum(qq[2] + qq[3]);
            const float ss = t ? a1 : a0, m = ss * (1.f / 288.f);
            ll_st128_if(t < 2, g_ZST + (rb * 2 + w) * 512 + j * 64 + 16 * q + 8 * t + g, m - blo(off2), fmaxf((t ? q1 : q0) - ss * m, 0.f), tag);
            TRC(tr, w, tb + 8);
            TRC(tr, w, tb + 9);
          };
          if (p < 4) {
            gelu(Int<8>{}, true);
            zd += 1024;
          } else if (p == 4) {
            gelu(Int<4>{}, true);
            publish();
          } else {
            gelu(Int<0>{}, p < 8);
            z1d += 8192;
          }
          SCLK(2 * p + 2);
          QCLK(11 + 3 * p);
          if (p == 8) break;
          bwait(p == 3 ? 0x80000040u : 0x40000040u, w);
          bar_sync(6 + w, 256);
          TRC(tr && p == 4, w, tb + 10);
          wgmma_fence();
#pragma unroll
          for (int kk = 0; kk < 36; kk++) mma(kk, PP3, w == 0 || p < 7);
        }
        signal(EV_Z1);
#pragma unroll
        for (int u = 0; u < 4; u++) {
          zk[u] = make_uint4(pack2(acc[8 * u], acc[8 * u + 1]), pack2(acc[8 * u + 2], acc[8 * u + 3]), pack2(acc[8 * u + 4], acc[8 * u + 5]), pack2(acc[8 * u + 6], acc[8 * u + 7]));
          asm volatile("" : "+r"(zk[u].x), "+r"(zk[u].y), "+r"(zk[u].z), "+r"(zk[u].w));
        }
        TRC(tr, w, tb + 12);
      }
      uint32_t hA[18][4];
      {
        float acc[144];
        const float c0 = __uint_as_float(lds32(sb + SM_OFF + 4));
#pragma unroll
        for (int i = 0; i < 144; i++) {
          asm volatile("fma.rn.f32 %0, %1, %2, %3;" : "=f"(acc[i]) : "f"(__uint_as_float(P.zero)), "f"((float)(i + 2)), "f"(c0));
        }
        uint32_t prev = 0;
        auto stage = [&](int kb) {
          mbar_wait_c(bars + B_FULL + c.s * 8, c.ph);
          TRC(tr && kb == 0, w, tb + 13);
          SCLK(22 + kb);
          const uint32_t st = sb + c.s * ST_BYTES, rt = sb + SM_RT + kb * 128 + t * 8;
          uint64_t db = dsc2(dlo(st + ST_B, 4608), 0, 8 + P.zero);
          uint32_t a[4][4];
#pragma unroll
          for (int kk = 0; kk < 4; kk++) {
            uint32_t r[4];
            ldsm4(r, st + (aoff ^ (kk << 5)));
            const uint2 sc = lds64(rt + kk * 32);
            a[kk][0] = hmul2(__byte_perm(r[0], r[2], 0x5410), sc.x); a[kk][2] = hmul2(__byte_perm(r[0], r[2], 0x7632), sc.y);
            a[kk][1] = hmul2(__byte_perm(r[1], r[3], 0x5410), sc.x); a[kk][3] = hmul2(__byte_perm(r[1], r[3], 0x7632), sc.y);
          }
          if (LAG4 && (kb & 1) == (LAG4 & 1)) yield(32 - kb, LAG4);
          wgmma_fence();
#pragma unroll
          for (int i = 0; i < 8; i++) {
            const int kk = i & 3, hf = i >> 2;
            wgmma_rs_n144(acc + hf * 72, a[kk], db, 1);
            dadd(db, i == 3 ? 144u - 3 * 576 : 576 + P.zero);
            if (i == 0) { wgmma_commit(); wgmma_wait<1>(); release_if(kb, prev); }
            if (i == 3) wgmma_commit();
          }
          wgmma_commit();
          prev = c.s; c.next();
        };
        mbar_wait_c(bars + B_RT, L);
#pragma unroll 1
        for (int kb = 0; kb < 32; kb += 2) {
          if (kb == 8) mbar_wait_c(bars + B_RT1, L);
          MCLK((kb & 7) == 4, 10 + (kb >> 3));
          stage(kb);
          stage(kb + 1);
        }
        if (LAG4) { yield_done(); lagph ^= 1; }
        if (w == 1) bar_arrive(6, 256);
        HCLK(0);
        mbar_wait_c(bars + B_CV + w * 8, L);
        HCLK(1);
        const float gk = 0.5f / GA;
        const float c1 = __uint_as_float(lds32(sb + SM_OFF + 4));
        const float gb0 = -gk * (c1 + __uint_as_float(lds32(sb + SM_CV + w * 256 + (16 * q + g) * 4))), gb1 = -gk * (c1 + __uint_as_float(lds32(sb + SM_CV + w * 256 + (16 * q + g + 8) * 4)));
        mbar_wait_c(w ? bars + B_FULL + c.s * 8 : bars + B_ZB, w ? c.ph : L);
        HCLK(2);
        const uint32_t sx = c.s;
        c.next();
        const uint32_t zt = sb + (tid & 127) * 16, zs1 = zt + sx * ST_BYTES + w * 28672 - 4096, zs0 = w ? zs1 : zt + SM_STG;
        uint4 zz[18];
        auto zload = [&](int u) {
          if (ZW && u == ZW && P.zero) __nanosleep(0);
          if (u >= 12 && u < 16) zz[u] = zk[u - 12]; else zz[u] = lds128((u < 2 ? zs0 : zs1) + (u < 12 ? u : u - 4) * 2048);
        };
#pragma unroll
        for (int u = 0; u < ZA; u++) zload(u);
#pragma unroll
        for (int u = 0; u < 18; u++) {
          if (u == 0) { wgmma_wait<1>(); HCLK(3); }
          if (u == 9) {
            HCLK(4);
            wgmma_wait<0>();
            HCLK(5);
            release(prev);
            mbar_arrive_if(L == 0 && lane == 0, ev + EV_P4 * 8);
            TRC(tr, w, tb + 14);
            SCLK(54);
          }
          if (u + ZA < 18) zload(u + ZA);
          const uint4 z = zz[u];
          hA[u][0] = hmul2(z.x, pack2(fmaf(acc[8 * u], gk, gb0), fmaf(acc[8 * u + 1], gk, gb0)));
          hA[u][1] = hmul2(z.y, pack2(fmaf(acc[8 * u + 2], gk, gb1), fmaf(acc[8 * u + 3], gk, gb1)));
          hA[u][2] = hmul2(z.z, pack2(fmaf(acc[8 * u + 4], gk, gb0), fmaf(acc[8 * u + 5], gk, gb0)));
          hA[u][3] = hmul2(z.w, pack2(fmaf(acc[8 * u + 6], gk, gb1), fmaf(acc[8 * u + 7], gk, gb1)));
        }
        uint32_t dep = P.zero;
#pragma unroll
        for (int u = 0; u < 18; u++) dep &= hA[u][0];
        release(sx, dep);
        TRC(tr, w, tb + 15);
        HCLK(6);
      }
      {
        CLK_INIT;
        uint32_t pk[16];
#pragma unroll
        for (int i = 0; i < 16; i++) pk[i] = 0u;
        auto dump = [&](int p) {
          const uint32_t d = sb + (p & 3) * ST_BYTES, cb = p + j >= 9 ? p + j - 9 : p + j;
          if (lane == 0) asm volatile("cp.async.bulk.wait_group.read 3;" ::: "memory");
          __syncwarp();
#pragma unroll
          for (int u = 0; u < 4; u++) stsm4(d + (aoff ^ (u << 5)), pk[4 * u], pk[4 * u + 1], pk[4 * u + 2], pk[4 * u + 3]);
          fence_async_s();
          __syncwarp();
          tma3d_red_p(lane == 0, &P.red[L], cb * 64, rb * 64 + q * 16, w, d + w * 8192 + q * 2048);
        };
#pragma unroll 1
        for (int p = 0; p < 9; p++) {
          float acc[32];
          CLK(0);
          mbar_wait_c(bars + B_FULL + c.s * 8, c.ph);
          uint64_t db = dsc2(dlo(sb + c.s * ST_BYTES + ST_B + (j & 1) * 4096, 0), 0, 0x40000040u + P.zero);
          CLK(1);
          HCLK(7 + 2 * p);
          bar_sync(6 + w, 256);
          CLK(2);
          wgmma_fence();
#pragma unroll
          for (int kk = 0; kk < 18; kk++) {
            wgmma_rs_n64(acc, hA[kk], db, kk != 0);
            dadd(db, kk == 15 ? 128 - (j & 1) * (36864 >> 4) : 128 + P.zero);
            if (kk == PPK && (w == 0 || p < 8)) bar_arrive(7 - w, 256);
          }
          wgmma_commit();
          CLK(3);
          if (p > 0) dump(p - 1);
          CLK(5);
          wgmma_wait<0>();
          CLK(4);
          HCLK(8 + 2 * p);
          MCLK(p == 1 || p == 8, 7 + (p >> 3));
          release_if(L == 0 || p < 5, c.s);
          c.next();
#pragma unroll
          for (int i = 0; i < 16; i++) pk[i] = pack2(acc[2 * i], acc[2 * i + 1]);
          if (p == 8) { TRC(tr, w, tb + 16); dump(8); TRC(tr, w, tb + 17); }
        }
        if (lane == 0) asm volatile("cp.async.bulk.wait_group 0;" ::: "memory");
        HCLK(25);
        MCLK(1, 9);
        if (L == 0) signal(EV_PT);
        CLK_OUT;
        TRC(tr, w, tb + 18);
      }
    }
    if ((tid & 127) == 0) g_flags[(rb * 2 + w) * 32 + FR_EP + j] = epoch + 1;
    if (tid == 0) g_flags[FJ + j * 32 + FJ_EP + rb] = epoch + 1;
  }
}

typedef CUresult (*EncodeFn)(CUtensorMap*, CUtensorMapDataType, cuuint32_t, void*, const cuuint64_t*, const cuuint64_t*, const cuuint32_t*,
                             const cuuint32_t*, CUtensorMapInterleave, CUtensorMapSwizzle, CUtensorMapL2promotion, CUtensorMapFloatOOBfill);

static void make_map(EncodeFn fn, CUtensorMap* m, const void* ptr, int rank, uint64_t d0, uint64_t d1, uint64_t d2, uint64_t s1, uint64_t s2,
                     uint32_t b0, uint32_t b1, uint32_t b2, CUtensorMapSwizzle swz) {
  cuuint64_t dims[3] = {d0, d1, d2}, strides[2] = {s1, s2};
  cuuint32_t box[3] = {b0, b1, b2}, es[3] = {1, 1, 1};
  fn(m, CU_TENSOR_MAP_DATA_TYPE_BFLOAT16, rank, const_cast<void*>(ptr), dims, strides, box, es, CU_TENSOR_MAP_INTERLEAVE_NONE, swz,
     CU_TENSOR_MAP_L2_PROMOTION_L2_128B, CU_TENSOR_MAP_FLOAT_OOB_FILL_NONE);
}

}

extern "C" void kernel_launch(void* const* d_in, const int* in_sizes, int n_in, void* d_out, int out_size) {
  using namespace mk;
  (void)in_sizes; (void)n_in; (void)out_size;
  static EncodeFn fn = nullptr;
  static uint8_t *wq, *xb;
  static float* csp;
  if (!fn) {
    cudaGetSymbolAddress((void**)&wq, g_WQ);
    cudaGetSymbolAddress((void**)&xb, g_X);
    cudaGetSymbolAddress((void**)&csp, g_CSP);
    cudaDriverEntryPointQueryResult qr;
    cudaGetDriverEntryPoint("cuTensorMapEncodeTiled", (void**)&fn, cudaEnableDefault, &qr);
    cudaFuncSetAttribute(mega_kernel, cudaFuncAttributeMaxDynamicSharedMemorySize, SM_TOTAL);
  }
  Params p;
  p.wqkv = (const __nv_bfloat16*)d_in[1];
  p.w_in = (const __nv_bfloat16*)d_in[4];
  p.w_sp = (const __nv_bfloat16*)d_in[5];
  p.b_sp = (const __nv_bfloat16*)d_in[6];
  p.w_out = (const __nv_bfloat16*)d_in[7];
  p.zero = 0;
  p.wq = wq;
  p.csp = csp;
  p.xs[0] = (uint8_t*)d_in[0];
  p.xs[1] = xb;
  p.xs[2] = (uint8_t*)d_out;
  make_map(fn, &p.wsp, p.w_sp, 3, 2048, 1024, 2, 8192, 4096, 64, 64, 2, CU_TENSOR_MAP_SWIZZLE_128B);
  for (int i = 0; i < 2; i++) {
    make_map(fn, &p.red[i], p.xs[i + 1], 3, DM, 1024, 2, 2304, 1152, 64, 16, 1, CU_TENSOR_MAP_SWIZZLE_128B);
    make_map(fn, &p.res[i], p.xs[i], 3, DM, 1024, 2, 2304, 1152, 144, 64, 1, CU_TENSOR_MAP_SWIZZLE_NONE);
  }
  make_map(fn, &p.psn, d_out, 3, DM, 1024, 2, 2304, 1152, 144, 4, 1, CU_TENSOR_MAP_SWIZZLE_NONE);
  for (int i = 0; i < 3; i++) make_map(fn, &p.act[i], p.xs[i], 3, DM, 1024, 2, 2304, 1152, 64, 64, 1, CU_TENSOR_MAP_SWIZZLE_128B);
  {
    cuuint64_t dims[4] = {8, 8, 72, 72}, strides[3] = {1152, 16, 9216};
    cuuint32_t box[4] = {8, 8, 9, 5}, es[4] = {1, 1, 1, 1};
    fn(&p.wo8, CU_TENSOR_MAP_DATA_TYPE_BFLOAT16, 4, d_in[2], dims, strides, box, es, CU_TENSOR_MAP_INTERLEAVE_NONE, CU_TENSOR_MAP_SWIZZLE_NONE,
       CU_TENSOR_MAP_L2_PROMOTION_L2_128B, CU_TENSOR_MAP_FLOAT_OOB_FILL_NONE);
  }
  for (int i = 0; i < 2; i++) {
    cuuint64_t dims[4] = {i ? 4608u : 2304u, 8, i ? 1u : 2u, 72}, strides[3] = {9216, 4608, 8 * 9216};
    cuuint32_t box[4] = {i ? 64u : 32u, 8, i ? 1u : 2u, 18}, es[4] = {1, 1, 1, 1};
    fn(i ? &p.win64 : &p.win, CU_TENSOR_MAP_DATA_TYPE_BFLOAT16, 4, d_in[4], dims, strides, box, es, CU_TENSOR_MAP_INTERLEAVE_NONE,
       i ? CU_TENSOR_MAP_SWIZZLE_128B : CU_TENSOR_MAP_SWIZZLE_64B, CU_TENSOR_MAP_L2_PROMOTION_L2_128B, CU_TENSOR_MAP_FLOAT_OOB_FILL_NONE);
  }
  make_map(fn, &p.wout, p.w_out, 2, 576, 2304, 1, 1152, 0, 64, 144, 1, CU_TENSOR_MAP_SWIZZLE_128B);
  mega_kernel<<<NGRID, 384, SM_TOTAL, cudaStreamPerThread>>>(p);
}
```

```cpp
#include <cuda_runtime.h>
#include <cuda.h>
#include <cuda_bf16.h>
#include <stdint.h>

#define MK_TRACE 0
#define MK_DBG 0
#define P5TRACE 0
#define LAG1 3
#define PP3 32
#define PP30 33
#define SPL 2
#define NAP 200
#define NAP0 8000
#define KS2 2
#define KS3 2
#define RL3 21
#define PAD 0
#define ZA 4
#define ZW 10
#define GM2 1
#define GMM 1
#define GM1 2
#define C0S 32.f
#define OFM 0x10u
#define PPK 13

namespace mk {

constexpr int SEQ = 2048, DM = 576, FH = 2304;
constexpr int NCTA = 128;
constexpr int NGRID = 132;
constexpr uint32_t ZB = 36864;
constexpr uint32_t WQ_SL = 72 * 3456;
constexpr uint32_t WO_SL = 72 * 1152;
constexpr float LN_EPS = 1e-5f;
constexpr float GA = 0.3292034911525734f, GB = 2.423681954311584f;

constexpr uint32_t ST_BYTES = 53248, ST_B = 16384, NST = 4;
constexpr uint32_t SM_STG = NST * ST_BYTES;
constexpr uint32_t SM_BAR = SM_STG + 2 * 9216;
constexpr uint32_t SM_OFF = SM_BAR + 1008;
constexpr uint32_t SM_TOTAL = SM_BAR + 1024;
constexpr uint32_t SM_RT = SM_STG + 4096, SM_CV = SM_STG + 12288, SM_WT = SM_CV + 512;
constexpr uint32_t SM_WOI = 44032, SM_CSQ = 49792, SM_XST = 50688;
constexpr uint32_t B_FULL = 0, B_EMPTY = 32, B_FULLA = 64, B_RES = 128, B_WT = 144, B_IMG = 160, B_WOI = 168, B_ZB = 176, B_GATE3 = 184, B_Z1 = 192, B_LAG = 200,
                   B_RT = 208, B_CSQ = 216, B_CV = 224, B_AD = 240, B_EVT = 272, B_RT1 = 368, B_XS = 624, B_XRW = 384, B_FA3 = 400, B_EA3 = 544;
enum { EV_PT = 0, EV_O = 1, EV_X1 = 2, EV_ZN = 3, EV_Z1 = 4, EV_P4 = 5, EV_N = 6 };

enum { FR_X2 = 0, FR_O = 1, FR_X1 = 3, FR_EP = 16, FJ = 32 * 32, FJ_WQ = 0, FJ_WO = 1, FJ_WQ0 = 2, FJ_ZN = 3, FJ_P4 = 5, FJ_EP = 16, F_N = FJ + 8 * 32 };

__device__ __align__(1024) uint8_t g_Z[512 * ZB];
constexpr uint32_t POISON = 0xffffffffu;
__device__ __align__(1024) uint8_t g_O[32 * 2 * ZB];
__device__ __align__(1024) uint4 g_RD[NCTA * 36 * 256];
__device__ __align__(1024) uint8_t g_X[SEQ * DM * 2];
#define SLOW(i) do {} while (0)
__device__ __align__(1024) uint8_t g_WQ[8 * WQ_SL];
__device__ __align__(1024) uint8_t g_WO[8 * WO_SL];
__device__ __align__(1024) float g_CSP[2 * NCTA * 216];
__device__ __align__(1024) uint2 g_RT[SEQ];
__device__ __align__(1024) uint4 g_XST[2 * SEQ];
__device__ __align__(1024) uint4 g_ST1[SEQ * 8];
__device__ __align__(1024) uint4 g_ZST[SEQ * 8];
__device__ __align__(1024) uint4 g_HALO[32 * 8 * 6 * 32];
__device__ __align__(1024) uint32_t g_flags[F_N];

struct Params {
  const __nv_bfloat16 *wqkv;
  uint8_t* wq;
  float* csp;
  uint32_t zero;
  const __nv_bfloat16 *w_in, *w_sp, *b_sp, *w_out;
  uint8_t* xs[3];
  CUtensorMap wo8, wsp, win, win64, wout;
  CUtensorMap act[3];
  CUtensorMap res[2];
  CUtensorMap red[2];
  CUtensorMap psn;
};

__device__ __forceinline__ uint32_t smem_u32(const void* p) { return (uint32_t)__cvta_generic_to_shared(p); }
__device__ __forceinline__ void mbar_init(uint32_t bar, uint32_t cnt) { asm volatile("mbarrier.init.shared::cta.b64 [%0], %1;" ::"r"(bar), "r"(cnt)); }
__device__ __forceinline__ void mbar_arrive(uint32_t bar) { asm volatile("mbarrier.arrive.shared::cta.b64 _, [%0];" ::"r"(bar) : "memory"); }
__device__ __forceinline__ void mbar_wait(uint32_t bar, uint32_t parity) {
  asm volatile(
      "{\n.reg .pred p;\n.reg .u32 c;\nmov.u32 c, 0;\nLAB_WAIT:\n"
      "mbarrier.try_wait.parity.shared::cta.b64 p, [%0], %1;\n@p bra LAB_DONE;\n"
      "add.u32 c, c, 1;\nsetp.lt.u32 p, c, 0x100000;\n@p bra LAB_WAIT;\ntrap;\nLAB_DONE:\n}" ::"r"(bar), "r"(parity)
      : "memory");
}
__device__ __forceinline__ void mbar_wait_c(uint32_t bar, uint32_t parity) {
  asm volatile("{\n.reg .pred p;\nLAB_WAIT:\nmbarrier.try_wait.parity.shared::cta.b64 p, [%0], %1;\n@!p bra LAB_WAIT;\n}" ::"r"(bar), "r"(parity) : "memory");
}
__device__ __forceinline__ void flag_wait(const uint32_t* f, uint32_t target) {
  asm volatile(
      "{\n.reg .pred p;\n.reg .u32 c, v;\nmov.u32 c, 0;\nLAB_WAIT:\n"
      "ld.relaxed.gpu.global.u32 v, [%0];\nsub.u32 v, v, %1;\nsetp.ge.s32 p, v, 0;\n@p bra LAB_DONE;\n"
      "add.u32 c, c, 1;\nsetp.lt.u32 p, c, 0x400000;\n@p bra LAB_WAIT;\ntrap;\nLAB_DONE:\nfence.acquire.gpu;\n}" ::"l"(f), "r"(target)
      : "memory");
}
__device__ __forceinline__ void fence_gpu() { asm volatile("fence.acq_rel.gpu;" ::: "memory"); }
__device__ __forceinline__ void fence_async_g() { asm volatile("fence.proxy.async.global;" ::: "memory"); }
__device__ __forceinline__ void fence_async_s() { asm volatile("fence.proxy.async.shared::cta;" ::: "memory"); }
__device__ __forceinline__ uint32_t elect_one() {
  uint32_t p; asm volatile("{\n.reg .pred P;\nelect.sync _|P, 0xffffffff;\nselp.u32 %0, 1, 0, P;\n}" : "=r"(p)); return p;
}
__device__ __forceinline__ void expect_tx_p(uint32_t el, uint32_t bar, uint32_t bytes) {
  asm volatile("{\n.reg .pred P;\nsetp.ne.u32 P, %2, 0;\n@P mbarrier.arrive.expect_tx.shared::cta.b64 _, [%0], %1;\n}" ::"r"(bar), "r"(bytes), "r"(el) : "memory");
}
__device__ __forceinline__ void bulk_load_p(uint32_t el, uint32_t dst, const void* src, uint32_t bytes, uint32_t bar) {
  asm volatile("{\n.reg .pred P;\nsetp.ne.u32 P, %4, 0;\n@P cp.async.bulk.shared::cluster.global.mbarrier::complete_tx::bytes [%0], [%1], %2, [%3];\n}" ::"r"(dst), "l"(src), "r"(bytes), "r"(bar), "r"(el) : "memory");
}
__device__ __forceinline__ uint64_t policy_evict_first() { uint64_t p; asm("createpolicy.fractional.L2::evict_first.b64 %0, 1.0;" : "=l"(p)); return p; }
__device__ __forceinline__ void bulk_load_h(uint32_t el, uint32_t dst, const void* src, uint32_t bytes, uint32_t bar, bool ef, uint64_t pol) {
  if (ef) {
    asm volatile("{\n.reg .pred P;\nsetp.ne.u32 P, %4, 0;\n@P cp.async.bulk.shared::cluster.global.mbarrier::complete_tx::bytes.L2::cache_hint [%0], [%1], %2, [%3], %5;\n}" ::"r"(dst), "l"(src), "r"(bytes), "r"(bar), "r"(el), "l"(pol) : "memory");
  } else {
    asm volatile("{\n.reg .pred P;\nsetp.ne.u32 P, %4, 0;\n@P cp.async.bulk.shared::cluster.global.mbarrier::complete_tx::bytes [%0], [%1], %2, [%3];\n}" ::"r"(dst), "l"(src), "r"(bytes), "r"(bar), "r"(el) : "memory");
  }
}
__device__ __forceinline__ void bulk_mc_h(uint32_t el, uint32_t dst, const void* src, uint32_t bytes, uint32_t bar, bool ef, uint64_t pol) {
  if (ef) {
    asm volatile("{\n.reg .pred P;\nsetp.ne.u32 P, %4, 0;\n@P cp.async.bulk.shared::cluster.global.mbarrier::complete_tx::bytes.multicast::cluster.L2::cache_hint [%0], [%1], %2, [%3], %5, %6;\n}" ::"r"(dst), "l"(src), "r"(bytes), "r"(bar), "r"(el), "h"((uint16_t)3), "l"(pol) : "memory");
  } else {
    asm volatile("{\n.reg .pred P;\nsetp.ne.u32 P, %4, 0;\n@P cp.async.bulk.shared::cluster.global.mbarrier::complete_tx::bytes.multicast::cluster [%0], [%1], %2, [%3], %5;\n}" ::"r"(dst), "l"(src), "r"(bytes), "r"(bar), "r"(el), "h"((uint16_t)3) : "memory");
  }
}
__device__ __forceinline__ void tma3d_h(uint32_t el, uint32_t dst, const CUtensorMap* m, int c0, int c1, int c2, uint32_t bar, bool ef, uint64_t pol) {
  if (ef) {
    asm volatile("{\n.reg .pred P;\nsetp.ne.u32 P, %6, 0;\n@P cp.async.bulk.tensor.3d.shared::cluster.global.mbarrier::complete_tx::bytes.L2::cache_hint [%0], [%1, {%3, %4, %5}], [%2], %7;\n}" ::"r"(dst), "l"(m), "r"(bar), "r"(c0), "r"(c1), "r"(c2), "r"(el), "l"(pol) : "memory");
  } else {
    asm volatile("{\n.reg .pred P;\nsetp.ne.u32 P, %6, 0;\n@P cp.async.bulk.tensor.3d.shared::cluster.global.mbarrier::complete_tx::bytes [%0], [%1, {%3, %4, %5}], [%2];\n}" ::"r"(dst), "l"(m), "r"(bar), "r"(c0), "r"(c1), "r"(c2), "r"(el) : "memory");
  }
}
__device__ __forceinline__ void tma2d_mc_h(uint32_t el, uint32_t dst, const CUtensorMap* m, int c0, int c1, uint32_t bar, bool ef, uint64_t pol) {
  if (ef) {
    asm volatile("{\n.reg .pred P;\nsetp.ne.u32 P, %5, 0;\n@P cp.async.bulk.tensor.2d.shared::cluster.global.mbarrier::complete_tx::bytes.multicast::cluster.L2::cache_hint [%0], [%1, {%3, %4}], [%2], %6, %7;\n}" ::"r"(dst), "l"(m), "r"(bar), "r"(c0), "r"(c1), "r"(el), "h"((uint16_t)3), "l"(pol) : "memory");
  } else {
    asm volatile("{\n.reg .pred P;\nsetp.ne.u32 P, %5, 0;\n@P cp.async.bulk.tensor.2d.shared::cluster.global.mbarrier::complete_tx::bytes.multicast::cluster [%0], [%1, {%3, %4}], [%2], %6;\n}" ::"r"(dst), "l"(m), "r"(bar), "r"(c0), "r"(c1), "r"(el), "h"((uint16_t)3) : "memory");
  }
}
__device__ __forceinline__ void tma4d_mc(uint32_t el, uint32_t dst, const CUtensorMap* m, int c0, int c3, uint32_t bar, uint64_t pol) {
  asm volatile("{\n.reg .pred P;\nsetp.ne.u32 P, %5, 0;\n@P cp.async.bulk.tensor.4d.shared::cluster.global.mbarrier::complete_tx::bytes.multicast::cluster.L2::cache_hint [%0], [%1, {%3, 0, 0, %4}], [%2], %6, %7;\n}" ::"r"(dst), "l"(m), "r"(bar), "r"(c0), "r"(c3), "r"(el), "h"((uint16_t)3), "l"(pol) : "memory");
}
__device__ __forceinline__ void mbar_arrive_cluster(uint32_t addr) { asm volatile("mbarrier.arrive.shared::cluster.b64 _, [%0];" ::"r"(addr) : "memory"); }
__device__ __forceinline__ void mbar_arrive_cluster_if(bool c, uint32_t addr) {
  asm volatile("{\n.reg .pred P;\nsetp.ne.u32 P, %1, 0;\n@P mbarrier.arrive.shared::cluster.b64 _, [%0];\n}" ::"r"(addr), "r"((uint32_t)c) : "memory");
}
__device__ __forceinline__ void mbar_arrive_if(bool c, uint32_t addr) {
  asm volatile("{\n.reg .pred P;\nsetp.ne.u32 P, %1, 0;\n@P mbarrier.arrive.shared::cta.b64 _, [%0];\n}" ::"r"(addr), "r"((uint32_t)c) : "memory");
}
__device__ __forceinline__ uint32_t mapa(uint32_t addr, uint32_t rank) { uint32_t r; asm("mapa.shared::cluster.u32 %0, %1, %2;" : "=r"(r) : "r"(addr), "r"(rank)); return r; }
__device__ __forceinline__ void bulk_store_p(uint32_t el, void* dst, uint32_t src, uint32_t bytes) {
  asm volatile("{\n.reg .pred P;\nsetp.ne.u32 P, %3, 0;\n@P cp.async.bulk.global.shared::cta.bulk_group [%0], [%1], %2;\n}" ::"l"(dst), "r"(src), "r"(bytes), "r"(el) : "memory");
}
__device__ __forceinline__ void flag_release_p(uint32_t el, uint32_t* f) {
  asm volatile("{\n.reg .pred P;\nsetp.ne.u32 P, %1, 0;\n@P red.release.gpu.global.add.u32 [%0], 1;\n}" ::"l"(f), "r"(el) : "memory");
}
__device__ __forceinline__ void flag_add_p(uint32_t el, uint32_t* f) {
  asm volatile("{\n.reg .pred P;\nsetp.ne.u32 P, %1, 0;\n@P red.relaxed.gpu.global.add.u32 [%0], 1;\n}" ::"l"(f), "r"(el) : "memory");
}
__device__ __forceinline__ void prefetch_l2(const void* src, uint32_t bytes) { asm volatile("cp.async.bulk.prefetch.L2.global [%0], %1;" ::"l"(src), "r"(bytes) : "memory"); }
__device__ __forceinline__ void prefetch_map(const CUtensorMap* m) { asm volatile("prefetch.tensormap [%0];" ::"l"(m) : "memory"); }
__device__ __forceinline__ void wgmma_fence() { asm volatile("wgmma.fence.sync.aligned;" ::: "memory"); }
__device__ __forceinline__ void wgmma_commit() { asm volatile("wgmma.commit_group.sync.aligned;" ::: "memory"); }
template <int N> __device__ __forceinline__ void wgmma_wait() { asm volatile("wgmma.wait_group.sync.aligned %0;" ::"n"(N) : "memory"); }
__device__ __forceinline__ uint32_t dlo(uint32_t addr, uint32_t lbo) { return ((addr & 0x3FFFF) >> 4) + ((lbo >> 4) << 16); }
template <uint32_t SBO, uint32_t SWZ> __device__ __forceinline__ uint64_t dsc(uint32_t lo, uint32_t off) {
  uint64_t d; asm("mov.b64 %0, {%1, %2};" : "=l"(d) : "r"(lo + (off >> 4)), "n"((SBO >> 4) | (SWZ << 30))); return d;
}
__device__ __forceinline__ uint64_t dsc2(uint32_t lo, uint32_t off, uint32_t hi) {
  uint64_t d; asm("mov.b64 %0, {%1, %2};" : "=l"(d) : "r"(lo + (off >> 4)), "r"(hi)); return d;
}
__device__ __forceinline__ uint64_t dat(uint64_t d, uint32_t off, uint32_t one) { uint64_t r; asm("mad.wide.u32 %0, %1, %2, %3;" : "=l"(r) : "r"(one), "r"(off >> 4), "l"(d)); return r; }
__device__ __forceinline__ void dadd(uint64_t& d, uint32_t v) {
  asm("{\n.reg .b32 lo, hi;\nmov.b64 {lo, hi}, %0;\nadd.u32 lo, lo, %1;\nmov.b64 %0, {lo, hi};\n}" : "+l"(d) : "r"(v));
}
template <int R> __device__ __forceinline__ void reg_alloc() { asm volatile("setmaxnreg.inc.sync.aligned.u32 %0;" ::"n"(R)); }
template <int R> __device__ __forceinline__ void reg_dealloc() { asm volatile("setmaxnreg.dec.sync.aligned.u32 %0;" ::"n"(R)); }
__device__ __forceinline__ void bar_sync(int id, int n) { asm volatile("bar.sync %0, %1;" ::"r"(id), "r"(n) : "memory"); }
__device__ __forceinline__ void bar_arrive(int id, int n) { asm volatile("bar.arrive %0, %1;" ::"r"(id), "r"(n) : "memory"); }
__device__ __forceinline__ void ldsm4(uint32_t* r, uint32_t addr) {
  asm volatile("ldmatrix.sync.aligned.m8n8.x4.shared.b16 {%0,%1,%2,%3}, [%4];" : "=r"(r[0]), "=r"(r[1]), "=r"(r[2]), "=r"(r[3]) : "r"(addr) : "memory");
}
__device__ __forceinline__ uint32_t movm(uint32_t a) { uint32_t d; asm volatile("movmatrix.sync.aligned.m8n8.trans.b16 %0, %1;" : "=r"(d) : "r"(a)); return d; }
__device__ __forceinline__ void mma16(float* c, uint32_t a0, uint32_t a1, uint32_t a2, uint32_t a3, uint32_t b0, uint32_t b1) {
  asm volatile("mma.sync.aligned.m16n8k16.row.col.f32.bf16.bf16.f32 {%0,%1,%2,%3}, {%4,%5,%6,%7}, {%8,%9}, {%10,%10,%10,%10};"
               : "=f"(c[0]), "=f"(c[1]), "=f"(c[2]), "=f"(c[3]) : "r"(a0), "r"(a1), "r"(a2), "r"(a3), "r"(b0), "r"(b1), "f"(0.f));
}
__device__ __forceinline__ void mma8(float* c, uint32_t a0, uint32_t a1, uint32_t b0) {
  asm volatile("mma.sync.aligned.m16n8k8.row.col.f32.bf16.bf16.f32 {%0,%1,%2,%3}, {%4,%5}, {%6}, {%0,%1,%2,%3};"
               : "+f"(c[0]), "+f"(c[1]), "+f"(c[2]), "+f"(c[3]) : "r"(a0), "r"(a1), "r"(b0));
}
__device__ __forceinline__ uint32_t pack2(float lo, float hi) { uint32_t r; asm("cvt.rn.bf16x2.f32 %0, %1, %2;" : "=r"(r) : "f"(hi), "f"(lo)); return r; }
__device__ __forceinline__ float blo(uint32_t v) { return __uint_as_float(v << 16); }
__device__ __forceinline__ float bhi(uint32_t v) { return __uint_as_float(v & 0xffff0000u); }
__device__ __forceinline__ float tanh_fast(float x) { float y; asm("tanh.approx.f32 %0, %1;" : "=f"(y) : "f"(x)); return y; }
__device__ __forceinline__ float rcp_fast(float x) { float y; asm("rcp.approx.ftz.f32 %0, %1;" : "=f"(y) : "f"(x)); return y; }
__device__ __forceinline__ float ex2(float x) { float y; asm("ex2.approx.ftz.f32 %0, %1;" : "=f"(y) : "f"(x)); return y; }
__device__ __forceinline__ float qsum(float v) { v += __shfl_xor_sync(~0u, v, 1); v += __shfl_xor_sync(~0u, v, 2); return v; }
__device__ __forceinline__ float qmax(float v) { v = fmaxf(v, __shfl_xor_sync(~0u, v, 1)); v = fmaxf(v, __shfl_xor_sync(~0u, v, 2)); return v; }
__device__ __forceinline__ void stg32(void* p, uint32_t v) { asm volatile("st.global.u32 [%0], %1;" ::"l"(p), "r"(v) : "memory"); }
__device__ __forceinline__ void stg128(void* p, uint32_t a, uint32_t b, uint32_t c, uint32_t d) { asm volatile("st.global.v4.u32 [%0], {%1,%2,%3,%4};" ::"l"(p), "r"(a), "r"(b), "r"(c), "r"(d) : "memory"); }
__device__ __forceinline__ uint32_t ldcg32(const void* p) { uint32_t v; asm volatile("ld.global.L1::no_allocate.u32 %0, [%1];" : "=r"(v) : "l"(p) : "memory"); return v; }
__device__ __forceinline__ uint32_t ldgpu32(const void* p) { uint32_t v; asm volatile("ld.relaxed.gpu.global.u32 %0, [%1];" : "=r"(v) : "l"(p) : "memory"); return v; }
__device__ __forceinline__ uint32_t ldca32(const void* p) { uint32_t v; asm volatile("ld.global.ca.u32 %0, [%1];" : "=r"(v) : "l"(p) : "memory"); return v; }
__device__ __forceinline__ void stg128_if(bool c, void* p, uint32_t a, uint32_t b, uint32_t cc, uint32_t d) {
  asm volatile("{\n.reg .pred P;\nsetp.ne.u32 P, %5, 0;\n@P st.global.v4.u32 [%0], {%1,%2,%3,%4};\n}" ::"l"(p), "r"(a), "r"(b), "r"(cc), "r"(d), "r"((uint32_t)c) : "memory");
}
__device__ __forceinline__ uint2 lds64(uint32_t a) { uint2 v; asm volatile("ld.shared.v2.u32 {%0,%1}, [%2];" : "=r"(v.x), "=r"(v.y) : "r"(a) : "memory"); return v; }
__device__ __forceinline__ uint4 ldcg128(const void* p) { uint4 v; asm volatile("ld.global.cg.v4.u32 {%0,%1,%2,%3}, [%4];" : "=r"(v.x), "=r"(v.y), "=r"(v.z), "=r"(v.w) : "l"(p) : "memory"); return v; }
__device__ __forceinline__ uint32_t ldnc16(const void* p) { uint16_t v; asm volatile("ld.global.nc.u16 %0, [%1];" : "=h"(v) : "l"(p)); return v; }
__device__ __forceinline__ uint4 ldnc128(const void* p) { uint4 v; asm volatile("ld.global.nc.v4.u32 {%0,%1,%2,%3}, [%4];" : "=r"(v.x), "=r"(v.y), "=r"(v.z), "=r"(v.w) : "l"(p)); return v; }
__device__ __forceinline__ uint32_t hsub2(uint32_t a, uint32_t b) { uint32_t d; asm("sub.rn.bf16x2 %0, %1, %2;" : "=r"(d) : "r"(a), "r"(b)); return d; }
__device__ __forceinline__ void stg32_if(bool c, void* p, uint32_t v) {
  asm volatile("{\n.reg .pred P;\nsetp.ne.u32 P, %2, 0;\n@P st.global.u32 [%0], %1;\n}" ::"l"(p), "r"(v), "r"((uint32_t)c) : "memory");
}
__device__ __forceinline__ uint32_t hmul2(uint32_t a, uint32_t b) { uint32_t d; asm("mul.rn.bf16x2 %0, %1, %2;" : "=r"(d) : "r"(a), "r"(b)); return d; }
__device__ __forceinline__ void sts32(uint32_t a, uint32_t v) { asm volatile("st.shared.u32 [%0], %1;" ::"r"(a), "r"(v) : "memory"); }
__device__ __forceinline__ uint32_t lds32(uint32_t a) { uint32_t v; asm volatile("ld.shared.u32 %0, [%1];" : "=r"(v) : "r"(a) : "memory"); return v; }
__device__ __forceinline__ void sts128(uint32_t a, uint32_t x, uint32_t y, uint32_t z, uint32_t w) { asm volatile("st.shared.v4.u32 [%0], {%1,%2,%3,%4};" ::"r"(a), "r"(x), "r"(y), "r"(z), "r"(w) : "memory"); }
__device__ __forceinline__ uint4 lds128(uint32_t a) { uint4 v; asm volatile("ld.shared.v4.u32 {%0,%1,%2,%3}, [%4];" : "=r"(v.x), "=r"(v.y), "=r"(v.z), "=r"(v.w) : "r"(a) : "memory"); return v; }
__device__ __forceinline__ void ll_st64(uint2* p, uint32_t v, uint32_t tag) {
  asm volatile("{\n.reg .b64 r;\nmov.b64 r, {%1,%2};\nst.relaxed.gpu.global.b64 [%0], r;\n}" ::"l"(p), "r"(v), "r"(tag) : "memory");
}
__device__ __forceinline__ uint2 ll_ld64(const uint2* p) {
  uint2 v; asm volatile("{\n.reg .b64 r;\nld.relaxed.gpu.global.b64 r, [%2];\nmov.b64 {%0,%1}, r;\n}" : "=r"(v.x), "=r"(v.y) : "l"(p) : "memory"); return v;
}
__device__ __forceinline__ void ll_st128(uint4* p, float a, float b, uint32_t tag, float c = 0.f) {
  asm volatile("{\n.reg .b128 r;\n.reg .b64 lo, hi;\nmov.b64 lo, {%1,%2};\nmov.b64 hi, {%3,%4};\nmov.b128 r, {lo, hi};\nst.relaxed.gpu.global.b128 [%0], r;\n}" ::"l"(p), "r"(__float_as_uint(a)), "r"(__float_as_uint(b)), "r"(tag), "r"(__float_as_uint(c)) : "memory");
}
__device__ __forceinline__ uint4 ll_ld128(const uint4* p) {
  uint4 v; asm volatile("{\n.reg .b128 r;\n.reg .b64 lo, hi;\nld.relaxed.gpu.global.b128 r, [%4];\nmov.b128 {lo, hi}, r;\nmov.b64 {%0,%1}, lo;\nmov.b64 {%2,%3}, hi;\n}" : "=r"(v.x), "=r"(v.y), "=r"(v.z), "=r"(v.w) : "l"(p) : "memory"); return v;
}
__device__ __forceinline__ void publish_p(uint32_t el, uint32_t* f) {
  asm volatile("{\n.reg .pred P;\nsetp.ne.u32 P, %1, 0;\n@P cp.async.bulk.commit_group;\n@P cp.async.bulk.wait_group 0;\n@P red.release.gpu.global.add.u32 [%0], 1;\n}" ::"l"(f), "r"(el) : "memory");
}
__device__ __forceinline__ void tma3d_red_p(uint32_t el, const CUtensorMap* m, int c0, int c1, int c2, uint32_t src) {
  asm volatile("{\n.reg .pred P;\nsetp.ne.u32 P, %5, 0;\n@P cp.reduce.async.bulk.tensor.3d.global.shared::cta.add.tile.bulk_group [%0, {%2, %3, %4}], [%1];\n@P cp.async.bulk.commit_group;\n}" ::"l"(m), "r"(src), "r"(c0), "r"(c1), "r"(c2), "r"(el) : "memory");
}
__device__ __forceinline__ void stsm4(uint32_t addr, uint32_t a, uint32_t b, uint32_t c, uint32_t d) {
  asm volatile("stmatrix.sync.aligned.m8n8.x4.shared.b16 [%0], {%1,%2,%3,%4};" ::"r"(addr), "r"(a), "r"(b), "r"(c), "r"(d) : "memory");
}
__device__ __forceinline__ void sts64(uint32_t a, uint32_t x, uint32_t y) { asm volatile("st.shared.v2.u32 [%0], {%1,%2};" ::"r"(a), "r"(x), "r"(y) : "memory"); }
__device__ __forceinline__ void ll_st128_if(bool on, uint4* p, float a, float b, uint32_t tag) {
  asm volatile("{\n.reg .pred P;\n.reg .b128 r;\n.reg .b64 lo, hi;\nsetp.ne.u32 P, %4, 0;\nmov.b64 lo, {%1,%2};\nmov.b64 hi, {%3,%3};\nmov.b128 r, {lo, hi};\n@P st.relaxed.gpu.global.b128 [%0], r;\n}" ::"l"(p), "r"(__float_as_uint(a)), "r"(__float_as_uint(b)), "r"(tag), "r"((uint32_t)on) : "memory");
}
__device__ __forceinline__ uint4 ldnc128_if(bool c, const void* p) {
  uint4 v = make_uint4(0u, 0u, 0u, 0u);
  asm volatile("{\n.reg .pred P;\nsetp.ne.u32 P, %5, 0;\n@P ld.global.nc.v4.u32 {%0,%1,%2,%3}, [%4];\n}" : "+r"(v.x), "+r"(v.y), "+r"(v.z), "+r"(v.w) : "l"(p), "r"((uint32_t)c));
  return v;
}
__device__ __forceinline__ uint32_t hfma2(uint32_t a, uint32_t b, uint32_t c) { uint32_t d; asm("fma.rn.bf16x2 %0, %1, %2, %3;" : "=r"(d) : "r"(a), "r"(b), "r"(c)); return d; }
__device__ __forceinline__ float2 lds64f(uint32_t a) { float2 v; asm volatile("ld.shared.v2.f32 {%0,%1}, [%2];" : "=f"(v.x), "=f"(v.y) : "r"(a) : "memory"); return v; }
#define TRC(cond, role, idx) do {} while (0)
#define TRV(role, idx, v) do {} while (0)

#define ACLK_INIT do {} while (0)
#define ACLK(i) do {} while (0)
#define ACLK_OUT do {} while (0)
#define QCLK(i) do {} while (0)
#define PH 1
#define RCLK(i) do {} while (0)
#define RCLK_INIT do {} while (0)
#define RCLK_OUT do {} while (0)
#define SCLK(i) do {} while (0)
#define HCLK(i) do {} while (0)
#define MCLK(c, i) do {} while (0)
#define CKK(i) do {} while (0)
#define CKK_OUT do {} while (0)
#define PL 1
#define PCLK(i) do {} while (0)
#define PQ 1
#define CLK_INIT do {} while (0)
#define CLK(i) do {} while (0)
#define CLK_OUT do {} while (0)

__device__ __forceinline__ void wgmma_ss_n216(float* d, uint64_t da, uint64_t db, int scaleD) {
  asm volatile("{\n.reg .pred p;\nsetp.ne.b32 p, %110, 0;\nwgmma.mma_async.sync.aligned.m64n216k16.f32.bf16.bf16 "
    "{%0,%1,%2,%3,%4,%5,%6,%7,%8,%9,%10,%11,%12,%13,%14,%15,%16,%17,%18,%19,%20,%21,%22,%23,%24,%25,%26,%27,%28,%29,%30,%31,%32,%33,%34,%35,%36,%37,%38,%39,%40,%41,%42,%43,%44,%45,%46,%47,%48,%49,%50,%51,%52,%53,%54,%55,%56,%57,%58,%59,%60,%61,%62,%63,%64,%65,%66,%67,%68,%69,%70,%71,%72,%73,%74,%75,%76,%77,%78,%79,%80,%81,%82,%83,%84,%85,%86,%87,%88,%89,%90,%91,%92,%93,%94,%95,%96,%97,%98,%99,%100,%101,%102,%103,%104,%105,%106,%107}, "
    "%108, %109, p, 1, 1, 0, 1;\n}\n"
    : "+f"(d[0]), "+f"(d[1]), "+f"(d[2]), "+f"(d[3]), "+f"(d[4]), "+f"(d[5]), "+f"(d[6]), "+f"(d[7]), "+f"(d[8]), "+f"(d[9]), "+f"(d[10]), "+f"(d[11]), "+f"(d[12]), "+f"(d[13]), "+f"(d[14]), "+f"(d[15]), "+f"(d[16]), "+f"(d[17]), "+f"(d[18]), "+f"(d[19]), "+f"(d[20]), "+f"(d[21]), "+f"(d[22]), "+f"(d[23]), "+f"(d[24]), "+f"(d[25]), "+f"(d[26]), "+f"(d[27]), "+f"(d[28]), "+f"(d[29]), "+f"(d[30]), "+f"(d[31]), "+f"(d[32]), "+f"(d[33]), "+f"(d[34]), "+f"(d[35]), "+f"(d[36]), "+f"(d[37]), "+f"(d[38]), "+f"(d[39]), "+f"(d[40]), "+f"(d[41]), "+f"(d[42]), "+f"(d[43]), "+f"(d[44]), "+f"(d[45]), "+f"(d[46]), "+f"(d[47]), "+f"(d[48]), "+f"(d[49]), "+f"(d[50]), "+f"(d[51]), "+f"(d[52]), "+f"(d[53]), "+f"(d[54]), "+f"(d[55]), "+f"(d[56]), "+f"(d[57]), "+f"(d[58]), "+f"(d[59]), "+f"(d[60]), "+f"(d[61]), "+f"(d[62]), "+f"(d[63]), "+f"(d[64]), "+f"(d[65]), "+f"(d[66]), "+f"(d[67]), "+f"(d[68]), "+f"(d[69]), "+f"(d[70]), "+f"(d[71]), "+f"(d[72]), "+f"(d[73]), "+f"(d[74]), "+f"(d[75]), "+f"(d[76]), "+f"(d[77]), "+f"(d[78]), "+f"(d[79]), "+f"(d[80]), "+f"(d[81]), "+f"(d[82]), "+f"(d[83]), "+f"(d[84]), "+f"(d[85]), "+f"(d[86]), "+f"(d[87]), "+f"(d[88]), "+f"(d[89]), "+f"(d[90]), "+f"(d[91]), "+f"(d[92]), "+f"(d[93]), "+f"(d[94]), "+f"(d[95]), "+f"(d[96]), "+f"(d[97]), "+f"(d[98]), "+f"(d[99]), "+f"(d[100]), "+f"(d[101]), "+f"(d[102]), "+f"(d[103]), "+f"(d[104]), "+f"(d[105]), "+f"(d[106]), "+f"(d[107])
    : "l"(da), "l"(db), "r"(scaleD));
}
__device__ __forceinline__ void wgmma_ss_n72(float* d, uint64_t da, uint64_t db, int scaleD) {
  asm volatile("{\n.reg .pred p;\nsetp.ne.b32 p, %38, 0;\nwgmma.mma_async.sync.aligned.m64n72k16.f32.bf16.bf16 "
    "{%0,%1,%2,%3,%4,%5,%6,%7,%8,%9,%10,%11,%12,%13,%14,%15,%16,%17,%18,%19,%20,%21,%22,%23,%24,%25,%26,%27,%28,%29,%30,%31,%32,%33,%34,%35}, "
    "%36, %37, p, 1, 1, 0, 1;\n}\n"
    : "+f"(d[0]), "+f"(d[1]), "+f"(d[2]), "+f"(d[3]), "+f"(d[4]), "+f"(d[5]), "+f"(d[6]), "+f"(d[7]), "+f"(d[8]), "+f"(d[9]), "+f"(d[10]), "+f"(d[11]), "+f"(d[12]), "+f"(d[13]), "+f"(d[14]), "+f"(d[15]), "+f"(d[16]), "+f"(d[17]), "+f"(d[18]), "+f"(d[19]), "+f"(d[20]), "+f"(d[21]), "+f"(d[22]), "+f"(d[23]), "+f"(d[24]), "+f"(d[25]), "+f"(d[26]), "+f"(d[27]), "+f"(d[28]), "+f"(d[29]), "+f"(d[30]), "+f"(d[31]), "+f"(d[32]), "+f"(d[33]), "+f"(d[34]), "+f"(d[35])
    : "l"(da), "l"(db), "r"(scaleD));
}
__device__ __forceinline__ void wgmma_rs_n144(float* d, const uint32_t* a, uint64_t db, int scaleD) {
  asm volatile("{\n.reg .pred p;\nsetp.ne.b32 p, %77, 0;\nwgmma.mma_async.sync.aligned.m64n144k16.f32.bf16.bf16 "
    "{%0,%1,%2,%3,%4,%5,%6,%7,%8,%9,%10,%11,%12,%13,%14,%15,%16,%17,%18,%19,%20,%21,%22,%23,%24,%25,%26,%27,%28,%29,%30,%31,%32,%33,%34,%35,%36,%37,%38,%39,%40,%41,%42,%43,%44,%45,%46,%47,%48,%49,%50,%51,%52,%53,%54,%55,%56,%57,%58,%59,%60,%61,%62,%63,%64,%65,%66,%67,%68,%69,%70,%71}, "
    "{%72,%73,%74,%75}, %76, p, 1, 1, 1;\n}\n"
    : "+f"(d[0]), "+f"(d[1]), "+f"(d[2]), "+f"(d[3]), "+f"(d[4]), "+f"(d[5]), "+f"(d[6]), "+f"(d[7]), "+f"(d[8]), "+f"(d[9]), "+f"(d[10]), "+f"(d[11]), "+f"(d[12]), "+f"(d[13]), "+f"(d[14]), "+f"(d[15]), "+f"(d[16]), "+f"(d[17]), "+f"(d[18]), "+f"(d[19]), "+f"(d[20]), "+f"(d[21]), "+f"(d[22]), "+f"(d[23]), "+f"(d[24]), "+f"(d[25]), "+f"(d[26]), "+f"(d[27]), "+f"(d[28]), "+f"(d[29]), "+f"(d[30]), "+f"(d[31]), "+f"(d[32]), "+f"(d[33]), "+f"(d[34]), "+f"(d[35]), "+f"(d[36]), "+f"(d[37]), "+f"(d[38]), "+f"(d[39]), "+f"(d[40]), "+f"(d[41]), "+f"(d[42]), "+f"(d[43]), "+f"(d[44]), "+f"(d[45]), "+f"(d[46]), "+f"(d[47]), "+f"(d[48]), "+f"(d[49]), "+f"(d[50]), "+f"(d[51]), "+f"(d[52]), "+f"(d[53]), "+f"(d[54]), "+f"(d[55]), "+f"(d[56]), "+f"(d[57]), "+f"(d[58]), "+f"(d[59]), "+f"(d[60]), "+f"(d[61]), "+f"(d[62]), "+f"(d[63]), "+f"(d[64]), "+f"(d[65]), "+f"(d[66]), "+f"(d[67]), "+f"(d[68]), "+f"(d[69]), "+f"(d[70]), "+f"(d[71])
    : "r"(a[0]), "r"(a[1]), "r"(a[2]), "r"(a[3]), "l"(db), "r"(scaleD));
}
__device__ __forceinline__ void wgmma_rs_n64(float* d, const uint32_t* a, uint64_t db, int scaleD) {
  asm volatile("{\n.reg .pred p;\nsetp.ne.b32 p, %37, 0;\nwgmma.mma_async.sync.aligned.m64n64k16.f32.bf16.bf16 "
    "{%0,%1,%2,%3,%4,%5,%6,%7,%8,%9,%10,%11,%12,%13,%14,%15,%16,%17,%18,%19,%20,%21,%22,%23,%24,%25,%26,%27,%28,%29,%30,%31}, "
    "{%32,%33,%34,%35}, %36, p, 1, 1, 1;\n}\n"
    : "+f"(d[0]), "+f"(d[1]), "+f"(d[2]), "+f"(d[3]), "+f"(d[4]), "+f"(d[5]), "+f"(d[6]), "+f"(d[7]), "+f"(d[8]), "+f"(d[9]), "+f"(d[10]), "+f"(d[11]), "+f"(d[12]), "+f"(d[13]), "+f"(d[14]), "+f"(d[15]), "+f"(d[16]), "+f"(d[17]), "+f"(d[18]), "+f"(d[19]), "+f"(d[20]), "+f"(d[21]), "+f"(d[22]), "+f"(d[23]), "+f"(d[24]), "+f"(d[25]), "+f"(d[26]), "+f"(d[27]), "+f"(d[28]), "+f"(d[29]), "+f"(d[30]), "+f"(d[31])
    : "r"(a[0]), "r"(a[1]), "r"(a[2]), "r"(a[3]), "l"(db), "r"(scaleD));
}

template <int V> struct Int { static constexpr int value = V; };
struct Cur {
  uint32_t s, ph;
  __device__ __forceinline__ void next() { if (++s == NST) { s = 0; ph ^= 1; } }
};

__device__ __forceinline__ uint8_t* z1_block(int rb, int w, int j) { return g_Z + (rb * 16 + w * 8 + j) * ZB; }
__device__ __forceinline__ uint8_t* o_block(int rb, int w) { return g_O + (rb * 2 + w) * (2 * ZB); }
__device__ __forceinline__ uint8_t* z2_block(int kb, int j) { return g_Z + (256 + kb * 8 + j) * ZB; }
__device__ __forceinline__ void combine8(float m0, float q0, float m1, float q1, float n, float eps, float& mean, float& rstd) {
  mean = qsum(m0 + m1) * 0.125f;
  float d0 = m0 - mean, d1 = m1 - mean;
  float M2 = qsum(q0 + q1 + n * (d0 * d0 + d1 * d1));
  rstd = rsqrtf(fmaf(M2, 0.125f / n, eps));
}
__device__ __forceinline__ void stat_get(const uint4* zs, uint32_t tag, float n, float eps, float& m0, float& r0, float& m1, float& r1) {
  uint4 a0, a1, b0, b1;
#pragma unroll 1
  for (int it = 0; it < (1 << 20); it++) {
    a0 = ll_ld128(zs); a1 = ll_ld128(zs + 64); b0 = ll_ld128(zs + 8); b1 = ll_ld128(zs + 72);
    if (__all_sync(~0u, a0.z == tag && a1.z == tag && b0.z == tag && b1.z == tag)) break;
  }
  combine8(__uint_as_float(a0.x), __uint_as_float(a0.y), __uint_as_float(a1.x), __uint_as_float(a1.y), n, eps, m0, r0);
  combine8(__uint_as_float(b0.x), __uint_as_float(b0.y), __uint_as_float(b1.x), __uint_as_float(b1.y), n, eps, m1, r1);
}

__device__ __forceinline__ void rows_fetch(uint32_t el, uint32_t xr, const uint8_t* src, uint32_t bar) {
  expect_tx_p(el, bar, 9216);
#pragma unroll 1
  for (int r = 0; r < 8; r++) bulk_load_p(el, xr + r * 1152, src + r * (DM * 4), 1152, bar);
}
__device__ __forceinline__ void rows_stats(uint32_t xr, uint4* dst, uint32_t tag, int lane) {
  float s[2] = {0.f, 0.f}, q[4] = {0.f, 0.f, 0.f, 0.f};
  const uint32_t a0 = xr + (lane >> 2) * 1152 + (((lane & 3) * 2) ^ (lane >> 2)) * 16;
  uint4 n0 = lds128(a0), n1 = lds128(a0 ^ 16);
#pragma unroll 1
  for (int e = 1; e <= 9; e++) {
    const uint32_t x[8] = {n0.x, n0.y, n0.z, n0.w, n1.x, n1.y, n1.z, n1.w};
    if (e < 9) { n0 = lds128(a0 + e * 128); n1 = lds128((a0 ^ 16) + e * 128); }
#pragma unroll
    for (int u = 0; u < 8; u++) {
      const float lo = blo(x[u]), hi = bhi(x[u]);
      s[u & 1] += lo + hi; q[(u & 1) * 2] = fmaf(lo, lo, q[(u & 1) * 2]); q[(u & 1) * 2 + 1] = fmaf(hi, hi, q[(u & 1) * 2 + 1]);
    }
  }
  const float sx = s[0] + s[1], sq = (q[0] + q[1]) + (q[2] + q[3]);
  const float m = qsum(sx) * (-1.f / DM), r = rsqrtf(fmaxf(fmaf(qsum(sq), 1.f / DM, -m * m), 0.f) + LN_EPS);
  if ((lane & 3) == 0) ll_st128(dst + (lane >> 2) * 2, m, r, tag);
}

__device__ __forceinline__ void poison(uint32_t el, uint32_t src, const CUtensorMap* m, int rb, int j, int lane) {
#pragma unroll 1
  for (int u = lane; u < 72; u += 32) sts128(src + u * 16, POISON, POISON, POISON, POISON);
  fence_async_s();
  __syncwarp();
#pragma unroll 1
  for (int u = 0; u < 16; u++) {
    __nanosleep(NAP);
    bulk_store_p(el, o_block(rb, u >> 3) + j * 9216 + (u & 7) * 1152, src, 1152);
    asm volatile("{\n.reg .pred P;\nsetp.ne.u32 P, %5, 0;\n@P cp.async.bulk.tensor.3d.global.shared::cta.tile.bulk_group [%0, {%2, %3, %4}], [%1];\n}" ::"l"(m), "r"(src), "r"((j & 6) * 72), "r"(rb * 64 + u * 4), "r"(j & 1), "r"(el) : "memory");
  }
}
__device__ __forceinline__ void mma16acc(float* c, const uint32_t* a, uint32_t b0, uint32_t b1) {
  asm volatile("mma.sync.aligned.m16n8k16.row.col.f32.bf16.bf16.f32 {%0,%1,%2,%3}, {%4,%5,%6,%7}, {%8,%9}, {%0,%1,%2,%3};"
               : "+f"(c[0]), "+f"(c[1]), "+f"(c[2]), "+f"(c[3]) : "r"(a[0]), "r"(a[1]), "r"(a[2]), "r"(a[3]), "r"(b0), "r"(b1));
}
template <int KS, int NG, int AK, int AH, int BK, int BG, class F> __device__ __forceinline__ void redo(float* acc, const uint8_t* pa, const uint8_t* pb, F f) {
#pragma unroll 1
  for (int k = 0; k < 36; k += KS) {
    uint32_t a[4 * KS], b[2 * KS][NG];
#pragma unroll 1
    for (int it = 0; it < (1 << 20); it++) {
      bool ok = true;
#pragma unroll
      for (int e = 0; e < 4 * KS; e++) a[e] = ldgpu32(pa + (e >> 1) * AK + (e & 1) * AH);
#pragma unroll
      for (int e = 0; e < 2 * KS * NG; e++) b[e / NG][e % NG] = ldca32(pb + (e / NG) * BK + (e % NG) * BG);
#pragma unroll
      for (int e = 0; e < 4 * KS; e++) ok = ok && a[e] != POISON;
      if (__all_sync(~0u, ok)) break;
    }
#pragma unroll
    for (int e = 0; e < KS; e++) f(a + 4 * e, k + e);
#pragma unroll
    for (int e = 0; e < KS * NG; e++) mma16acc(acc + 4 * (e % NG), a + 4 * (e / NG), movm(b[2 * (e / NG)][e % NG]), movm(b[2 * (e / NG) + 1][e % NG]));
    pa += 2 * KS * AK; pb += 2 * KS * BK;
  }
}
__device__ __forceinline__ bool any_nan(float a, float b) {
  return __any_sync(~0u, a != a || b != b);
}

__global__ void __cluster_dims__(2, 1, 1) __launch_bounds__(384, 1) mega_kernel(const __grid_constant__ Params P) {
  extern __shared__ __align__(1024) uint8_t smem_raw[];
  uint32_t ckk[8];
  (void)ckk;
  CKK(0);
  const uint32_t sb = smem_u32(smem_raw);
  const uint32_t bars = sb + SM_BAR;
  const int tid = threadIdx.x;
  int lane = tid & 31;
  const int wid = __shfl_sync(~0u, tid >> 5, 0);
  const int cl = blockIdx.x >> 1, tp = cl - 36, t7 = (tp * 37) >> 8;
  const int bid = (cl < 4 ? cl * 8 + 32 : tp < 0 ? cl - 4 : cl < 64 ? tp + t7 + 33 : cl) * 2 + (blockIdx.x & 1);
  if (bid >= NCTA) return;
  const int rb = bid & 15, j = bid >> 4;
  { const bool tr = (tid & 127) == 0 && tid < 256; const int w = tid >> 7; (void)tr; (void)w; TRC(tr, w, 0); }
  CKK(1);
  uint4 wv[5];
  const uint8_t* wsrc;
  {
    const int n8 = min(tid >> 3, 26), part = n8 / 9;
    const uint8_t* src = (const uint8_t*)P.wqkv + (8 * rb + (tid & 7)) * (3 * DM * 2) + (part * (DM - 72) + 72 * j + 8 * n8) * 2;
#pragma unroll
    for (int u = 0; u < SPL; u++) wv[u] = ldnc128_if(tid < 216, src + u * (128 * 3 * DM * 2));
    wsrc = src;
  }
  CKK(2);
  if (tid == 352) {
    for (int s = 0; s < (int)NST; s++) {
      mbar_init(bars + B_FULL + s * 8, 1); mbar_init(bars + B_EMPTY + s * 8, 16);
      mbar_init(bars + B_FULLA + s * 8, 1); mbar_init(bars + B_FULLA + 32 + s * 8, 1);
      mbar_init(bars + B_RES + s * 8, 1); mbar_init(bars + B_RT + s * 8, 1); mbar_init(bars + B_AD + s * 8, 2);
    }
    mbar_init(bars + B_IMG, 8); mbar_init(bars + B_RES + 8, 8); mbar_init(bars + B_WOI, 1); mbar_init(bars + B_GATE3, 3); mbar_init(bars + B_Z1, 1); mbar_init(bars + B_ZB, 1); mbar_init(bars + B_LAG, 4);
    mbar_init(bars + B_XS, 1); mbar_init(bars + B_XS + 8, 1); mbar_init(bars + B_RT1, 1); mbar_init(bars + B_XRW, 1); mbar_init(bars + B_XRW + 8, 1);
    for (int e = 0; e < 2 * EV_N; e++) mbar_init(bars + B_EVT + e * 8, 4);
    asm volatile("fence.mbarrier_init.release.cluster;" ::: "memory");
  }
  if (tid == 320) {
#pragma unroll
    for (int e = 0; e < 28; e++) mbar_init(bars + B_FA3 + e * 8, e < 18 ? 1 : 4);
    asm volatile("fence.mbarrier_init.release.cluster;" ::: "memory");
  }
  __syncthreads();

  if (wid >= 8) {
    reg_dealloc<40>();
    const uint32_t el = elect_one();
    const uint64_t pol = policy_evict_first();
    uint32_t* const fj = g_flags + FJ + j * 32;
    if (wid == 8) {
#pragma unroll 1
      for (int i = 0; i < 12; i++) if (el) prefetch_map(&P.act[0] + (i < 7 ? i : i - 12));
      const uint32_t epoch = ldcg32(fj + FJ_EP + rb);
      Cur c{0, 1};
      const uint32_t rk = bid & 1;
      uint32_t st, full;
      auto slot = [&](uint32_t bytes) {
        st = sb + c.s * ST_BYTES; full = bars + B_FULL + c.s * 8;
        mbar_wait(full, c.ph);
        expect_tx_p(el, full, bytes);
        mbar_wait(full - B_FULL + B_EMPTY, c.ph);
      };
#pragma unroll 1
      for (int L = 0; L < 2; L++) {
#pragma unroll 1
        for (int i = 0; i < 14; i++) {
          if (L == 0 && (i == 0 || i == 2 * SPL || i == 9)) {
            flag_wait(fj + (i == 9 ? FJ_WO : i == 2 * SPL ? FJ_WQ : FJ_WQ0), (epoch + 1) * 16);
            if (i == 9) flag_wait(g_flags + FJ + (j ^ 1) * 32 + FJ_WO, (epoch + 1) * 16);
            fence_async_g();
            TRC(el, 2, i == 9 ? 46 : i ? 47 : 45);
          }
          const uint32_t hb = i < 9 ? 13824 : i < 13 ? 18432 : 9216, o = ST_B + rk * (i < 9 ? 13824 : 18432);
          const uint8_t* src = i < 9 ? g_WQ + j * WQ_SL + i * 27648 + rk * 13824 : g_WO + ((j & 6) + rk) * WO_SL + (i - 9) * 18432;
          slot(2 * hb);
          bulk_mc_h(el, st + o, src, hb, full, true, pol);
          c.next();
        }
#pragma unroll 1
        for (int i = 0; i < 18; i++) {
          const int p = i >> 1, col = p == 4 ? (9 * j + ((j & 1) ? 0 : 8)) * 32 : (((9 * j + 1) >> 1) + (p < 4 ? p + 36 : p - 5)) * 64;
          if (i & 1) {
            slot(2 * ZB);
          } else {
            st = sb + c.s * ST_BYTES; full = bars + B_FULL + ((c.s + 1) & 3) * 8;
            mbar_wait(bars + B_EMPTY + c.s * 8, c.ph);
          }
          tma4d_mc(el, st + ST_B + rk * 18432, p == 4 ? &P.win : &P.win64, col, (i & 1) * 36 + rk * 18, full, pol);
          if (el && !(i & 1)) mbar_arrive(bars + B_FULL + c.s * 8);
          c.next();
        }
        TRC(el, 2, L * 16 + 6);
        flag_wait(fj + FJ_ZN + L, (epoch + 1) * 16);
        fence_async_g();
        TRC(el, 2, L * 16 + 7);
#pragma unroll 1
        for (int i = 0; i < 32; i++) {
          const uint8_t* src = z2_block(i, j) + rk * 18432;
          if (i >= 4) mbar_wait(bars + B_AD + c.s * 8, ((i >> 2) & 1) ^ 1);
          slot(ST_BYTES);
          bulk_mc_h(el, st + ST_B + rk * 18432, src, 18432, full, true, pol);
          tma3d_h(el, st, &P.wsp, i * 64, rb * 64, 0, full, true, pol);
          c.next();
        }
        mbar_wait(bars + B_Z1, L);
        fence_async_g();
        expect_tx_p(el, bars + B_ZB, 26624);
#pragma unroll 1
        for (int i = 0; i < 10; i++) {
          const int cb = i - 1 + j;
          if (i < 4) mbar_wait(bars + B_AD + c.s * 8, 1);
          slot(i ? ZB : 26624);
          if (i == 0) {
            bulk_load_h(el, st, z1_block(rb, 0, j), 26624, bars + B_ZB, true, pol);
            bulk_load_h(el, st + 26624, z1_block(rb, 1, j), 26624, full, true, pol);
          } else {
            tma2d_mc_h(el, st + ST_B + rk * 18432, &P.wout, (cb >= 9 ? cb - 9 : cb) * 64, 288 * j + rk * 144, full, true, pol);
          }
          c.next();
        }
      }
    } else if (wid < 11) {
      int w = wid - 9;
      uint32_t* const fr = g_flags + (rb * 2 + w) * 32;
      const uint32_t epoch = ldcg32(fr + FR_EP + j);
      const uint32_t ev = bars + B_EVT + w * EV_N * 8, t8 = (epoch + 1) * 8;
      Cur c{0, 1};
#pragma unroll 1
      for (int L = 0; L < 2; L++) {
        {
          const uint32_t tag = epoch * 2 + L + 1;
          uint4* const xs = g_XST + (rb * 2 + w) * 128;
          if (L) {
            mbar_wait(ev + EV_PT * 8, 0);
            TRC(el, 3, w * 32 + 16);
            flag_release_p(el, fr + FR_X2);
            TRC(el, 3, w * 32 + 17);
          }
#pragma unroll 1
          for (int i = 0; i < 9; i++) {
            const uint32_t full = bars + B_FULLA + w * 32 + c.s * 8, dst = sb + c.s * ST_BYTES + w * 8192;
            if (L == 0 && i == 4) {
              mbar_wait(bars + B_WT + w * 8, 0);
              TRC(el && w == 0, 2, 37);
              rows_stats(sb + SM_STG + w * 9216, xs + 16 * j, tag, lane);
              TRC(el && w == 0, 2, 38);
            }
            const uint32_t src = sb + (L ? 2 * ST_BYTES + SM_WOI : SM_STG + w * 9216);
            if (i == 4) {
#pragma unroll
              for (int u = 0; u < 6; u++) sts128(src + u * 512 + lane * 16, POISON, POISON, POISON, POISON);
              fence_async_s();
              __syncwarp();
            }
            mbar_wait(bars + B_EMPTY + c.s * 8, c.ph);
            expect_tx_p(el, full, 8192);
            if (i < L) { flag_wait(fr + FR_X2, t8); fence_async_g(); }
            tma3d_h(el, dst, &P.act[L], i * 64, rb * 64, w, full, false, pol);
            TRC(el && i < L, 3, w * 32 + 18);
            c.next();
            if (i >= 4 && i < (L ? 5 : 8)) {
              int b = (rb * 2 + w) * 8 + j;
              asm volatile("" : "+r"(b));
              bulk_store_p(el, i == 4 ? (uint8_t*)g_HALO + b * 3072 : g_O + (b * 3 + i - 5) * 3072, src, 3072);
              if (i < 6) bulk_store_p(el, (i == 4 ? g_ST1 : g_ZST) + b * 64, src, 1024);
              if (i == 6) bulk_store_p(el, g_RT + b * 8, src, 64);
            }
            if (L == 0 && i == 3) rows_fetch(el, sb + SM_STG + w * 9216, P.xs[0] + (128 * rb + 16 * j + w) * (DM * 2), bars + B_WT + w * 8);
          }
          if (el) asm volatile("cp.async.bulk.commit_group;\ncp.async.bulk.wait_group 0;" ::: "memory");
          __syncwarp();
          if (L == 0) fence_gpu();
          const uint32_t tab = sb + L * (2 * ST_BYTES) + SM_XST + w * 512 + lane * 8;
          TRC(el, 3, w * 32 + L * 16 + 13);
#pragma unroll 1
          for (int it = 0; it < (1 << 22); it++) {
            const uint4 a = ll_ld128(xs + 2 * lane), b = ll_ld128(xs + 64 + 2 * lane);
            if (__all_sync(~0u, a.z == tag && b.z == tag)) { sts64(tab, a.x, a.y); sts64(tab + 256, b.x, b.y); break; }
          }
          __syncwarp();
          mbar_arrive_if(el, bars + B_XS + w * 8);
          TRC(el, 3, w * 32 + L * 16 + 14);
          if (w == 1) {
            mbar_wait(bars + B_XS, L);
            expect_tx_p(el, bars + B_RES, 18432);
            tma3d_h(el, sb + SM_STG, &P.res[L], (j & 6) * 72, rb * 64, j & 1, bars + B_RES, !L, pol);
          }
          if (L) flag_wait(fj + FJ_P4, t8 * 4);
        }
        asm volatile("" : "+r"(w));
        uint32_t* const fo = g_flags + (rb * 2 + (j & 1)) * 32 + L;
        {
          const uint8_t* src = o_block(rb, j & 1) + w * 8192;
#pragma unroll 1
          for (int i = 0; i < 5; i++) {
            const uint32_t full = bars + B_FULLA + w * 32 + c.s * 8, dst = sb + c.s * ST_BYTES + w * 8192;
            const bool none = 2 * i + w > 8;
            mbar_wait(bars + B_EMPTY + c.s * 8, c.ph);
            expect_tx_p(el, full, none ? 0 : 8192);
            if (i == 0) {
              mbar_wait(ev + EV_O * 8, L);
              TRC(el, 3, w * 32 + L * 16 + 3);
              flag_add_p(el, fr + FR_O + L);
              TRC(el, 3, w * 32 + L * 16 + 4);
              flag_wait(fo + FR_O, t8);
              fence_async_g();
            }
            if (!none) bulk_load_h(el, dst, src + i * 16384, 8192, full, true, pol);
            TRC(el && i == 0, 3, w * 32 + L * 16 + 5);
            c.next();
          }
        }
        {
          expect_tx_p(lane < 9, bars + B_FA3 + (9 * w + lane) * 8, 8192);
          mbar_wait(ev + EV_X1 * 8, L);
          TRC(el, 3, w * 32 + L * 16 + 6);
          if (L) flag_add_p(el, fo + FR_X1); else flag_release_p(el, fo + FR_X1);
          mbar_arrive_if(el, bars + B_GATE3);
          TRC(el, 3, w * 32 + L * 16 + 7);
          mbar_arrive_if(lane < 2, bars + B_FULLA + w * 32 + ((c.s + lane) & 3) * 8);
#pragma unroll 1
          for (int kb = 0; kb < 9; kb++) {
            const int n = 9 * w + kb;
            const uint32_t dst = sb + ((n >> 1) & 3) * ST_BYTES + (n & 1) * 8192;
            if (kb == 0) { flag_wait(fr + FR_X1 + L, t8); fence_async_g(); }
            if (n >= 8) mbar_wait(bars + B_EA3 + (n - 8) * 8, L);
            tma3d_h(el, dst, &P.act[L + 1], kb * 64, rb * 64, w, bars + B_FA3 + n * 8, false, pol);
            TRC(el && kb == 0, 3, w * 32 + L * 16 + 8);
          }
          c.ph ^= ((c.s + 18) >> 2) & 1; c.s = (c.s + 18) & 3;
        }
        asm volatile("" : "+r"(lane), "+r"(w));
        expect_tx_p(el, bars + B_WT + w * 8, 2048);
#pragma unroll 1
        for (int r = 0; r < 8; r++)
          bulk_load_p(el, sb + SM_WT + w * 2176 + r * 272, (const uint8_t*)P.w_sp + (size_t)(128 * rb + 16 * j + 2 * r + w) * (SEQ * 2) + 30 * 128, 256, bars + B_WT + w * 8);
        float cv = (lane & 3) ? 0.f : -blo(ldnc16(P.b_sp + 128 * rb + 16 * j + 2 * (lane >> 2) + w));
        mbar_wait(bars + B_RT, L);
        mbar_wait(bars + B_WT + w * 8, L ^ 1);
        mbar_wait(ev + EV_Z1 * 8, L);
        const uint32_t ro = (w * 64 + 8 * j + (lane >> 2)) * 128, x0 = ((lane & 3) * 2) ^ (lane >> 2);
#pragma unroll 1
        for (int i = 0; i < 32; i++) {
          const bool tail = (i >> 1) == 4;
          const int kb = tail ? i + 22 : i < 8 ? i : i - 2;
          if (i == 8) mbar_wait(bars + B_RT1, L);
          if (!tail) mbar_wait(bars + B_FULL + c.s * 8, c.ph ^ 1);
#pragma unroll
          for (int e = 0; e < 2; e++) {
            const uint4 a = lds128(!tail ? sb + c.s * ST_BYTES + ro + ((x0 ^ e) << 4) : sb + SM_WT + w * 2176 + (lane >> 2) * 272 + (i - 8) * 128 + (lane & 3) * 32 + e * 16);
            const uint4 m = lds128(sb + SM_RT + 4096 + kb * 128 + (lane & 3) * 32 + e * 16);
            cv = fmaf(blo(a.x), blo(m.x), fmaf(bhi(a.x), bhi(m.x), fmaf(blo(a.y), blo(m.y), fmaf(bhi(a.y), bhi(m.y), cv))));
            cv = fmaf(blo(a.z), blo(m.z), fmaf(bhi(a.z), bhi(m.z), fmaf(blo(a.w), blo(m.w), fmaf(bhi(a.w), bhi(m.w), cv))));
          }
          if (!tail) {
            mbar_arrive_if(el, bars + B_AD + c.s * 8 + (__float_as_uint(cv) & P.zero));
            c.next();
          }
        }
        TRC(el, 3, w * 32 + L * 16 + 11);
        uint32_t tag = t8;
        asm volatile("" : "+r"(tag));
        tag = (tag >> 2) - 1 + L;
        cv = qsum(cv);
        uint2* const cs = (uint2*)(g_XST + (rb * 2 + w) * 128 + 1);
        if ((lane & 3) == 0) ll_st64(cs + 32 * j + (lane >> 2) * 4, __float_as_uint(cv), tag);
#pragma unroll 1
        for (int it = 0; it < (1 << 22); it++) {
          const uint2 a = ll_ld64(cs + 4 * lane), b = ll_ld64(cs + 128 + 4 * lane);
          if (__all_sync(~0u, a.y == tag && b.y == tag)) { sts32(sb + SM_CV + w * 256 + lane * 4, a.x); sts32(sb + SM_CV + w * 256 + 128 + lane * 4, b.x); break; }
        }
        __syncwarp();
        if (el) mbar_arrive(bars + B_CV + w * 8);
        TRC(el, 3, w * 32 + L * 16 + 12);
#pragma unroll 1
        for (int kb = 30; kb < 32; kb++) {
          mbar_wait(bars + B_FULL + c.s * 8, c.ph ^ 1);
          if (el) mbar_arrive(bars + B_AD + c.s * 8);
          c.next();
        }
        c.ph ^= ((c.s + 10) >> 2) & 1; c.s = (c.s + 10) & 3;
        if (L == 0) {
          mbar_wait(ev + EV_P4 * 8, 0);
          flag_add_p(el, fj + FJ_P4);
        }
      }
    } else {
      const uint32_t epoch = ldcg32(fj + FJ_EP + rb);
      if (SPL) {
        mbar_wait(bars + B_RES + 8, 0);
        TRC(el, 2, 41);
        flag_release_p(el, fj + FJ_WQ0);
        TRC(el, 2, 42);
      }
      mbar_wait(bars + B_IMG, 0);
      TRC(el, 2, 39);
      flag_release_p(el, fj + FJ_WQ);
      TRC(el, 2, 40);
#pragma unroll 1
      for (int L = 0; L < 2; L++) {
        auto wo_fetch = [&]() {
          expect_tx_p(el, bars + B_WOI, 5760);
          asm volatile("{\n.reg .pred P;\nsetp.ne.u32 P, %5, 0;\n@P cp.async.bulk.tensor.4d.shared::cluster.global.mbarrier::complete_tx::bytes [%0], [%1, {0, 0, %3, %4}], [%2];\n}" ::"r"(sb + SM_WOI), "l"(&P.wo8), "r"(bars + B_WOI), "r"(9 * j), "r"((9 * rb) >> 1), "r"(el) : "memory");
        };
        float* const csf = g_CSP + (NCTA + bid) * 216;
        if (L == 0) {
          flag_wait(fj + FJ_WQ, (epoch + 1) * 16);
          fence_async_g();
          expect_tx_p(el, bars + B_XRW, 13824);
          bulk_load_p(el, sb + ST_BYTES + SM_WOI, g_CSP + j * 16 * 216, 6912, bars + B_XRW);
          bulk_load_p(el, sb + 2 * ST_BYTES + SM_WOI, g_CSP + (j * 16 + 8) * 216, 6912, bars + B_XRW);
          wo_fetch();
          mbar_wait(bars + B_XRW, 0);
#pragma unroll 1
          for (int f = lane; f < 54; f += 32) {
            float s[4] = {0.f, 0.f, 0.f, 0.f};
#pragma unroll 4
            for (int r = 0; r < 16; r++) {
              const uint4 v = lds128(sb + ST_BYTES + SM_WOI + (r >> 3) * ST_BYTES + (r & 7) * 864 + f * 16);
              s[0] += __uint_as_float(v.x); s[1] += __uint_as_float(v.y); s[2] += __uint_as_float(v.z); s[3] += __uint_as_float(v.w);
            }
            sts128(sb + SM_CSQ + f * 16, __float_as_uint(s[0]), __float_as_uint(s[1]), __float_as_uint(s[2]), __float_as_uint(s[3]));
            stg128(csf + f * 4, __float_as_uint(s[0]), __float_as_uint(s[1]), __float_as_uint(s[2]), __float_as_uint(s[3]));
          }
          __syncwarp();
          mbar_arrive_if(el, bars + B_CSQ);
        } else {
#pragma unroll 1
          for (int u = 0; u < 4; u++) {
            const int w = u & 1;
            if (u < 2) {
              flag_wait(g_flags + (rb * 2 + w) * 32 + FR_X2, (epoch + 1) * 8);
              fence_async_g();
              TRC(el, 2, 48 + u);
              rows_fetch(el, sb + SM_STG + w * 9216, P.xs[1] + (128 * rb + 16 * j + w) * (DM * 2), bars + B_XRW + w * 8);
            } else {
              if (u == 2) {
                expect_tx_p(el, bars + B_CSQ, 864);
                bulk_load_p(el, sb + 2 * ST_BYTES + SM_CSQ, csf, 864, bars + B_CSQ);
              }
              mbar_wait(bars + B_XRW + w * 8, w ^ 1);
              TRC(el, 2, 48 + u);
              rows_stats(sb + SM_STG + w * 9216, g_XST + (rb * 2 + w) * 128 + 16 * j, epoch * 2 + 2, lane);
              TRC(el, 2, 50 + u);
            }
          }
        }
        if (L == 0) {
          TRC(el, 2, 43);
          mbar_wait(bars + B_WOI, 0);
          bulk_store_p(el, g_WO + j * WO_SL + ((9 * rb) >> 1) * 1152, sb + SM_WOI, 5760);
          publish_p(el, fj + FJ_WO);
          TRC(el, 2, 44);
          const uint8_t* sp = lane < 16 ? (const uint8_t*)P.w_in + (30 * lane + 50) * (FH * 4) + FH * 2 + lane * 256 : (const uint8_t*)P.w_sp + (60 * lane) * (SEQ * 2) + lane * 64;
          float sq = 0.f;
#pragma unroll 1
          for (int u = 0; u < 4; u++) {
            const uint4 y = ldnc128(sp + u * 16);
            const uint32_t x[4] = {y.x, y.y, y.z, y.w};
#pragma unroll
            for (int e = 0; e < 4; e++) sq = fmaf(blo(x[e]), blo(x[e]), fmaf(bhi(x[e]), bhi(x[e]), sq));
          }
#pragma unroll 1
          for (int o = 8; o; o >>= 1) sq += __shfl_xor_sync(~0u, sq, o);
          sq *= lane < 16 ? 2.f * GA * GA * DM / 512.f : C0S * C0S * SEQ / 512.f;
          asm("sqrt.approx.f32 %0, %0;" : "+f"(sq));
          const float o0 = __shfl_sync(~0u, sq, 0), o1 = __shfl_sync(~0u, sq, 16);
          const uint32_t off = (__float_as_uint(o0) & 0x7f800000u) >> 16 | 0x8000u | OFM;
          if (el) sts64(sb + SM_OFF, off * 0x10001u, min(__float_as_uint(o1) & 0x7f800000u, 0x7e000000u) | 0x00400000u);
        }
        if (el) mbar_arrive(bars + B_GATE3);
        const uint32_t tag = epoch * 2 + L + 1;
        asm volatile("" : "+r"(lane));
        mbar_wait(bars + B_EVT + EV_ZN * 8, L);
        mbar_wait(bars + B_EVT + (EV_N + EV_ZN) * 8, L);
        flag_release_p(el, fj + FJ_ZN + L);
        TRC(el, 2, L * 16 + 8);
        {
          uint4 v[4];
#pragma unroll 1
          for (int it = 0; it < (1 << 22); it++) {
            bool ok = true;
#pragma unroll
            for (int u = 0; u < 4; u++) { v[u] = ll_ld128(g_ZST + (rb * 2 + ((lane >> 1) & 1)) * 512 + ((lane & 1) * 4 + u) * 64 + 8 * j + (lane >> 2)); ok = ok && v[u].z == tag; }
            if (__all_sync(~0u, ok)) break;
          }
          float mean = __uint_as_float(v[0].x) + __uint_as_float(v[1].x) + __uint_as_float(v[2].x) + __uint_as_float(v[3].x), M2 = 0.f;
          mean = (mean + __shfl_xor_sync(~0u, mean, 1)) * 0.125f;
#pragma unroll
          for (int u = 0; u < 4; u++) { const float d = __uint_as_float(v[u].x) - mean; M2 += fmaf(288.f * d, d, __uint_as_float(v[u].y)); }
          M2 += __shfl_xor_sync(~0u, M2, 1);
          const float rs = blo(pack2(rsqrtf(fmaf(M2, 1.f / FH, 4.f * GA * GA * LN_EPS)), 0.f));
          if (!(lane & 1)) ll_st64(g_RT + 128 * rb + 16 * j + (lane >> 1), pack2(rs, rs * mean), tag);
        }
        TRC(el, 2, L * 16 + 10);
#pragma unroll 1
        for (int b = 0; b < 8; b++) {
          uint4 v[4];
#pragma unroll 1
          for (int it = 0; it < (1 << 22); it++) {
            bool ok = true;
#pragma unroll
            for (int u = 0; u < 4; u++) { v[u] = ll_ld128((const uint4*)g_RT + b * 128 + u * 32 + lane); ok = ok && v[u].y == tag && v[u].w == tag; }
            if (__all_sync(~0u, ok)) break;
          }
#pragma unroll
          for (int u = 0; u < 4; u++) {
            const uint32_t rt = sb + SM_RT + b * 512 + u * 128, ro = (lane >> 3) * 32 + (lane & 3) * 8 + ((lane >> 2) & 1) * 2;
            sts32(rt + 4096 + lane * 4, __byte_perm(v[u].x, v[u].z, 0x7632));
            asm volatile("st.shared.u16 [%0], %1;\nst.shared.u16 [%0 + 4], %2;" ::"r"(rt + ro), "h"((uint16_t)v[u].x), "h"((uint16_t)v[u].z) : "memory");
          }
          __syncwarp();
          if (el && (b == 1 || b == 7)) mbar_arrive(bars + (b == 1 ? B_RT : B_RT1));
          TRC(el && b < 2, 2, L * 16 + 11 + b);
        }
        TRC(el, 2, L * 16 + 9);
        mbar_wait(bars + B_EVT + EV_Z1 * 8, L);
        mbar_wait(bars + B_EVT + (EV_N + EV_Z1) * 8, L);
        fence_gpu();
        if (el) mbar_arrive(bars + B_Z1);
        if (L == 0) {
          __nanosleep(NAP0);
          poison(el, sb + SM_STG + 17152, &P.psn, rb, j, lane);
          if (el) asm volatile("cp.async.bulk.commit_group;\ncp.async.bulk.wait_group 0;" ::: "memory");
          __syncwarp();
          fence_gpu();
        }
      }
    }
  } else {
    CKK(3);
    uint8_t* const wdst = P.wq + j * WQ_SL + rb * 3456 + tid * 16;
#pragma unroll
    for (int u = 0; u < SPL; u++) stg128_if(tid < 216, wdst + u * (16 * 3456), wv[u].x, wv[u].y, wv[u].z, wv[u].w);
    __syncwarp();
    if (lane == 0) mbar_arrive(bars + B_RES + 8);
    CKK(4);
    auto repack2 = [&]() {
#pragma unroll
      for (int u = SPL; u < 5; u++) stg128_if((u < 4 || rb < 8) && tid < 216, wdst + u * (16 * 3456), wv[u].x, wv[u].y, wv[u].z, wv[u].w);
      float s[8];
#pragma unroll
      for (int e = 0; e < 8; e++) s[e] = 0.f;
#pragma unroll
      for (int u = 0; u < 5; u++) {
        uint32_t x[4] = {wv[u].x, wv[u].y, wv[u].z, wv[u].w};
        asm volatile("" : "+r"(x[0]), "+r"(x[1]), "+r"(x[2]), "+r"(x[3]));
#pragma unroll
        for (int e = 0; e < 4; e++) { s[2 * e] += blo(x[e]); s[2 * e + 1] += bhi(x[e]); }
      }
#pragma unroll
      for (int m = 4; m; m >>= 1) {
#pragma unroll
        for (int e = 0; e < m; e++) s[e] = ((tid & m) ? s[e + m] : s[e]) + __shfl_xor_sync(~0u, (tid & m) ? s[e] : s[e + m], m);
      }
      stg32_if(tid < 216, P.csp + bid * 216 + tid, __float_as_uint(s[0]));
      __syncwarp();
      if (lane == 0) mbar_arrive(bars + B_IMG);
    };
    reg_alloc<232>();
    CKK(5);
#pragma unroll
    for (int v = SPL; v < 5; v++) wv[v] = ldnc128_if(tid < 216 && (v < 4 || rb < 8), wsrc + v * (128 * 3 * DM * 2));
    repack2();
    CKK(6);
    const int w = wid >> 2, q = wid & 3;
    int g = lane >> 2, t = lane & 3;
    const uint32_t ev = bars + B_EVT + w * EV_N * 8;
    const bool tr = (tid & 127) == 0;
    (void)tr;
    Cur c{0, 0};
    const uint32_t ebar = mapa(bars + B_EMPTY, (bid & 1) ^ (lane & 1));
    auto release = [&](uint32_t s, uint32_t dep = 0) { mbar_arrive_cluster_if(lane < 2, ebar + s * 8 + dep); };
    auto release_if = [&](bool on, uint32_t s) { mbar_arrive_cluster_if(lane < 2 && on, ebar + s * 8); };
    uint32_t ia = 0;
    auto wait_ab = [&]() { mbar_wait_c(bars + B_FULL + c.s * 8, c.ph); mbar_wait_c(bars + B_FULLA + w * 32 + c.s * 8, (ia >> 2) & 1); ia++; };

    auto yield_done = [&]() { if (w == 0 && lane == 0) mbar_arrive(bars + B_LAG); };
    auto signal = [&](int e) { __syncwarp(); mbar_arrive_if(lane == 0, ev + e * 8); };

    const uint32_t epoch = ldcg32(g_flags + (rb * 2 + w) * 32 + FR_EP + j);
    TRC(tr, w, 1);
    CKK(7);
    if (PAD && P.zero) {
#pragma unroll
      for (int i = 0; i < PAD; i++) asm volatile("st.shared.u32 [%0], %1;" ::"r"(sb + i * 20), "r"(tid) : "memory");
    }
    CKK_OUT;

#pragma unroll 1
    for (int L = 0; L < 2; L++) {
      const int tb = 2 + L * 24;
      asm volatile("" : "+r"(lane), "+r"(g), "+r"(t));
      (void)tb;
      ia = 0;
      const uint32_t tag = epoch * 2 + L + 1;
      uint32_t aoff = (w * 64 + q * 16 + (lane & 15)) * 128 + (((lane >> 4) ^ (lane & 7)) << 4);
      {
        uint32_t Pk[27][2];
        float sc0, sc1;
        const uint32_t att = sb + w * 8192 + q * 2048 + lane * 4;
        uint4* hp = g_HALO + ((((rb - (q == 0)) * 2 + w) * 8 + j) * 6) * 32 + lane;
        uint8_t* od = o_block(rb, w) + (9 * j) * 1024 + (2 * q) * 128 + lane * 4;
        ACLK_INIT;
        {
          float acc[108];
#pragma unroll
          for (int i = 0; i < 108; i++) acc[i] = 0.f;
          uint32_t prev = 0;
#pragma unroll 1
          for (int kb = 0; kb < 9; kb++) {
            wait_ab();
            if (w == 1 && kb == 9 - LAG1) mbar_wait_c(bars + B_LAG, L);
            TRC(tr && kb == 0, w, tb + 0);
            MCLK(kb == 0, 0);
            PCLK(kb * 4);
            const uint32_t st = sb + c.s * ST_BYTES, da = dlo(st + w * 8192, 16), db = dlo(st + ST_B, 3456);
            wgmma_fence();
#pragma unroll
            for (int kk = 0; kk < 4; kk++) {
              wgmma_ss_n216(acc, dsc<1024, 1>(da, kk * 32), dsc<128, 0>(db, kk * 6912), 1);
              if (kk == 0) { wgmma_commit(); wgmma_wait<1>(); release_if(kb > 0, prev); }
            }
            wgmma_commit();
            if (kb == 8) yield_done();
            PCLK(kb * 4 + 1);
            PCLK(kb * 4 + 2);
            PCLK(kb * 4 + 3);
            prev = c.s; c.next();
          }
          const uint32_t cs = sb + prev * ST_BYTES + SM_CSQ + t * 8;
          mbar_wait_c(bars + B_CSQ, L);
          mbar_wait_c(bars + B_XS + w * 8, L);
          const float2 n0 = lds64f(sb + prev * ST_BYTES + SM_XST + w * 512 + (16 * q + g) * 8), n1 = lds64f(sb + prev * ST_BYTES + SM_XST + w * 512 + (16 * q + g + 8) * 8);
          const float m0 = n0.x, r0 = n0.y, m1 = n1.x, r1 = n1.y;
          float2 cv[27];
#pragma unroll
          for (int G = 0; G < 27; G++) cv[G] = lds64f(cs + G * 32);
          PCLK(36);
          wgmma_wait<0>();
          PCLK(37);
          uint32_t dep = P.zero & __float_as_uint(m0) & __float_as_uint(m1);
#pragma unroll
          for (int G = 0; G < 27; G++) dep &= __float_as_uint(cv[G].x);
          release(prev, dep);
          TRC(tr, w, tb + 1);
          MCLK(1, 1);
          ACLK(0);
#pragma unroll
          for (int G = 9; G < 27; G++) Pk[G][1] = pack2(fmaf(m1, cv[G].x, acc[4 * G + 2]) * r1, fmaf(m1, cv[G].y, acc[4 * G + 3]) * r1);
          if (q < 3) {
#pragma unroll
            for (int i = 0; i < 18; i++) sts32(att + (i >> 4) * ST_BYTES + (i & 15) * 128, Pk[9 + i][1]);
          } else if (rb < 15) {
#pragma unroll
            for (int i = 0; i < 6; i++) ll_st128(hp + i * 32, __uint_as_float(Pk[9 + 3 * i][1]), __uint_as_float(Pk[10 + 3 * i][1]), tag, __uint_as_float(Pk[11 + 3 * i][1]));
          }
#pragma unroll
          for (int G = 0; G < 27; G++) {
            if (G < 9) {
              Pk[G][0] = pack2(fmaf(m0, cv[G].x, acc[4 * G]), fmaf(m0, cv[G].y, acc[4 * G + 1]));
              Pk[G][1] = pack2(fmaf(m1, cv[G].x, acc[4 * G + 2]), fmaf(m1, cv[G].y, acc[4 * G + 3]));
            } else {
              Pk[G][0] = pack2(fmaf(m0, cv[G].x, acc[4 * G]) * r0, fmaf(m0, cv[G].y, acc[4 * G + 1]) * r0);
            }
          }
          sc0 = r0 * (0.23570226039551584f * 1.4426950408889634f); sc1 = r1 * (0.23570226039551584f * 1.4426950408889634f);
        }
        ACLK(1);
        constexpr int GA_[4] = {0, 2, 4, 7}, GB_[4] = {1, 3, 5, 8}, GC_[4] = {2, 4, 6, 6};
        float S1[4][4], S2[4][4];
        uint32_t qa[4][2], qc[4][2];
#pragma unroll
        for (int h = 0; h < 4; h++) {
#pragma unroll
          for (int r = 0; r < 2; r++) {
            qa[h][r] = (h == 0 || h == 3 || t >= h) ? Pk[GA_[h]][r] : 0u;
            qc[h][r] = (h == 3 ? t == 3 : t <= h) ? Pk[GC_[h]][r] : 0u;
          }
          mma16(S1[h], qa[h][0], qa[h][1], Pk[GB_[h]][0], Pk[GB_[h]][1], Pk[9 + GA_[h]][0], Pk[9 + GB_[h]][0]);
          mma16(S2[h], qa[h][0], qa[h][1], Pk[GB_[h]][0], Pk[GB_[h]][1], Pk[9 + GA_[h]][1], Pk[9 + GB_[h]][1]);
        }
#pragma unroll
        for (int h = 0; h < 4; h++) {
          mma8(S1[h], qc[h][0], qc[h][1], Pk[9 + GC_[h]][0]);
          mma8(S2[h], qc[h][0], qc[h][1], Pk[9 + GC_[h]][1]);
        }
        uint32_t V1[9], V2[9];
#pragma unroll
        for (int i = 0; i < 9; i++) { V1[i] = movm(Pk[18 + i][0]); V2[i] = movm(Pk[18 + i][1]); }
        const bool remote = q == 0 && rb > 0;
        uint4 hv[6];
#pragma unroll
        for (int i = 0; i < 6; i++) hv[i] = make_uint4(0u, 0u, tag, 0u);
        if (remote) {
#pragma unroll
          for (int i = 0; i < 6; i++) hv[i] = ll_ld128(hp + i * 32);
        }
        const bool up0 = 2 * t > g, up1 = 2 * t + 1 > g;
        const uint32_t mup = (up0 ? 0xffffu : 0u) | (up1 ? 0xffff0000u : 0u);
        auto finish = [&](const float (&x0)[4], const float (&x1)[4], uint32_t ma, const uint32_t (&Vb)[9], int hi) {
          uint32_t pa[4], pb[4];
          float rs[4];
#pragma unroll
          for (int h = 0; h < 4; h++) {
            const float m = qmax(fmaxf(x0[h], x1[h]));
            const uint32_t p = pack2(ex2(x0[h] - m), ex2(x1[h] - m));
            pa[h] = p & ma; pb[h] = p & ~ma;
          }
#pragma unroll
          for (int h = 0; h < 4; h += 2) {
            float R[4];
            mma16(R, pa[h], pa[h + 1], pb[h], pb[h + 1], 0x3f803f80u, 0x3f803f80u);
            rs[h] = rcp_fast(R[0]); rs[h + 1] = rcp_fast(R[2]);
          }
#pragma unroll
          for (int i = 0; i < 9; i++) {
            const int h = 4 * i / 9, e = (h & 1) * 2;
            const bool split = i == 2 || i == 4 || i == 6, nx = split && 2 * t >= i;
            float O[4], N[4];
            mma16(O, pa[h & 2], pa[h | 1], pb[h & 2], pb[h | 1], V1[i], Vb[i]);
            if (i == 4) mma16(N, pa[2], pa[3], pb[2], pb[3], V1[i], Vb[i]); else { N[0] = O[2]; N[1] = O[3]; }
            const float r = nx ? rs[h + (split ? 1 : 0)] : rs[h];
            stg32(od + i * 1024 + hi * 128, pack2((nx ? N[0] : O[e]) * r, (nx ? N[1] : O[e + 1]) * r));
          }
        };
        {
          float x0[4], x1[4];
#pragma unroll
          for (int h = 0; h < 4; h++) { x0[h] = (up0 ? S1[h][2] : S2[h][2]) * sc1; x1[h] = (up1 ? S1[h][3] : S2[h][3]) * sc1; }
          finish(x0, x1, mup, V2, 1);
        }
        ACLK(2);
        bar_sync(1 + w, 128);
        uint32_t H[18];
        if (q > 0) {
#pragma unroll
          for (int i = 0; i < 18; i++) H[i] = lds32(att - 2048 + (i >> 4) * ST_BYTES + (i & 15) * 128);
        } else {
#pragma unroll 1
          for (int it = 0; it < (1 << 20); it++) {
            bool ok = true;
#pragma unroll
            for (int i = 0; i < 6; i++) ok = ok && hv[i].z == tag;
            if (__all_sync(~0u, ok)) break;
#pragma unroll
            for (int i = 0; i < 6; i++) hv[i] = ll_ld128(hp + i * 32);
          }
#pragma unroll
          for (int i = 0; i < 6; i++) { H[3 * i] = hv[i].x; H[3 * i + 1] = hv[i].y; H[3 * i + 2] = hv[i].w; }
        }
        float S0[4][4];
#pragma unroll
        for (int h = 0; h < 4; h++) {
          mma16(S0[h], qa[h][0], qa[h][1], Pk[GB_[h]][0], Pk[GB_[h]][1], H[GA_[h]], H[GB_[h]]);
        }
#pragma unroll
        for (int h = 0; h < 4; h++) mma8(S0[h], qc[h][0], qc[h][1], H[GC_[h]]);
        uint32_t V0[9];
#pragma unroll
        for (int i = 0; i < 9; i++) V0[i] = movm(H[9 + i]);
        ACLK(3);
        {
          const bool nohalo = (rb | q) == 0;
          const float b0 = up0 && nohalo ? -INFINITY : 0.f, b1 = up1 && nohalo ? -INFINITY : 0.f;
          float x0[4], x1[4];
#pragma unroll
          for (int h = 0; h < 4; h++) { x0[h] = fmaf(up0 ? S0[h][0] : S1[h][0], sc0, b0); x1[h] = fmaf(up1 ? S0[h][1] : S1[h][1], sc0, b1); }
          finish(x0, x1, ~mup, V0, 0);
        }
        ACLK(4);
        signal(EV_O);
        ACLK_OUT;
        TRC(tr, w, tb + 2);
        MCLK(1, 2);
      }
      {
        float acc[36];
        const int hw = rb * 2 + (j & 1), js = (j & 6) + w;
        const uint32_t xt = sb + SM_STG + (16 * q + g) * 288 + w * 144 + t * 4;
        uint32_t xm = sb + SM_STG + (16 * q + (lane & 15)) * 288 + (((9 * w + (lane >> 4)) ^ ((lane >> 2) & 1)) << 4), xl = sb + SM_STG + (2 * q + w) * 2304 + lane * 16;
        uint8_t* xd[5];
#pragma unroll
        for (int u = 0; u < 5; u++) {
          const int row = ((u * 32 + lane) * 57) >> 10;
          xd[u] = P.xs[L + 1] + (128 * rb + 32 * q + 16 * w + (j & 1)) * (DM * 2) + (j & 6) * 144 + row * (DM * 4 - 288) + u * 512 + ((lane ^ (row >> 2)) << 4);
          asm volatile("" : "+l"(xd[u]));
        }
        asm volatile("" : "+r"(xm), "+r"(xl));
        mbar_wait_c(bars + B_RES, L);
        TRC(tr, w, tb + 21);
#pragma unroll
        for (int i = 0; i < 18; i++) { const uint32_t x = lds32(xt + (i >> 1) * 16 + (i & 1) * 2304); acc[2 * i] = blo(x); acc[2 * i + 1] = bhi(x); asm volatile("" : "+f"(acc[2 * i]), "+f"(acc[2 * i + 1])); }
        uint32_t prev = 0;
#pragma unroll 1
        for (int u = 0; u < 5; u++) {
          const uint32_t st = sb + c.s * ST_BYTES, da = dlo(st, 1024), db = dlo(st + ST_B + w * 18432, 1152);
          mbar_wait_c(bars + B_FULL + c.s * 8, c.ph); mbar_wait_c(bars + B_FULLA + c.s * 8, (ia >> 2) & 1);
          TRC(tr && u == 0, w, tb + 3);
          MCLK(u == 0, 3);
          wgmma_fence();
#pragma unroll
          for (int kk = 0; kk < 4; kk++) wgmma_ss_n72(acc, dsc<128, 0>(da, kk * 2048), dsc<128, 0>(db, kk * 2304), 1);
          wgmma_commit();
          wgmma_wait<1>();
          release_if(u > 0, prev);
          mbar_wait_c(bars + B_FULLA + 32 + c.s * 8, (ia >> 2) & 1);
          ia++;
          if (u == 4) break;
          wgmma_fence();
#pragma unroll
          for (int kk = 4; kk < 8; kk++) wgmma_ss_n72(acc, dsc<128, 0>(da, kk * 2048), dsc<128, 0>(db, kk * 2304), 1);
          wgmma_commit();
          prev = c.s; c.next();
        }
        RCLK_INIT;
        wgmma_wait<0>();
        RCLK(0);
        release(c.s);
        c.next();
        if (__builtin_expect(any_nan(acc[0], acc[2]), 0)) {
          SLOW(L);
          const uint8_t* xr = P.xs[L] + (128 * rb + 32 * q + 2 * g + (j & 1)) * (DM * 2) + js * 144 + t * 4;
#pragma unroll
          for (int i = 0; i < 18; i++) { const uint32_t x = ldgpu32(xr + (i >> 1) * 16 + (i & 1) * (DM * 32)); acc[2 * i] = blo(x); acc[2 * i + 1] = bhi(x); }
          redo<KS2, 9, 1024, 128, 1152, 128>(acc, o_block(rb, j & 1) + q * 256 + lane * 4, g_WO + js * WO_SL + lane * 4, [](uint32_t*, int) {});
        }
        TRC(tr && P5TRACE != 5, w, tb + 4);
        MCLK(1, 4);
#pragma unroll
        for (int u = 0; u < 4; u++)
          stsm4(xm + u * 32, pack2(acc[8 * u], acc[8 * u + 1]), pack2(acc[8 * u + 2], acc[8 * u + 3]), pack2(acc[8 * u + 4], acc[8 * u + 5]), pack2(acc[8 * u + 6], acc[8 * u + 7]));
        asm volatile("stmatrix.sync.aligned.m8n8.x2.shared.b16 [%0], {%1,%2};" ::"r"(xm + 128), "r"(pack2(acc[32], acc[33])), "r"(pack2(acc[34], acc[35])) : "memory");
        auto stats = [&]() {
          float s0 = 0.f, s1 = 0.f, q0 = 0.f, q1 = 0.f;
#pragma unroll
          for (int i = 0; i < 36; i++) {
            if (i & 2) { s1 += acc[i]; q1 = fmaf(acc[i], acc[i], q1); } else { s0 += acc[i]; q0 = fmaf(acc[i], acc[i], q0); }
          }
          s0 = qsum(s0); s1 = qsum(s1); q0 = qsum(q0); q1 = qsum(q1);
          const float ss = t ? s1 : s0, m = ss * (1.f / 72.f);
          ll_st128_if(t < 2, g_ST1 + (hw * 8 + js) * 64 + 16 * q + 8 * t + g, m, fmaxf((t ? q1 : q0) - ss * m, 0.f), tag);
        };
        stats();
        RCLK(1);
        bar_sync(8 + q, 64);
        RCLK(2);
#pragma unroll
        for (int u = 0; u < 5; u++) {
          const uint4 v = lds128(xl + u * 512);
          stg128_if(u < 4 || lane < 16, xd[u], v.x, v.y, v.z, v.w);
        }
        RCLK(3);
        signal(EV_X1);
        RCLK(4);
        RCLK(5);
        TRC(tr, w, tb + 5);
        RCLK(6);
        RCLK_OUT;
      }
      uint4 zk[4];
      {
        uint32_t xA[36][4];
        float acc[32];
        uint32_t s0, one, off2;
        uint8_t *z1d, *zd;
        uint64_t db;
        auto bwait = [&](uint32_t dhi, bool skip) {
          s0 = c.s;
          c.next();
          if (!skip) mbar_wait_c(bars + B_FULL + c.s * 8, c.ph);
          db = dsc2(dlo(sb + s0 * ST_BYTES + ST_B, 512) - 3, 0, dhi); one = (c.s ^ P.zero) & 1;
        };
        auto mma = [&](int kk, int pp, bool hand) {
          wgmma_rs_n64(acc, xA[kk], dat(db, (kk / 18) * ST_BYTES + (kk % 18) * 2048 + 48, one), kk != 0);
          if (kk == pp && hand) bar_arrive(7 - w, 256);
          if (kk == 17 || kk == 35) wgmma_commit();
          if (kk == RL3) { wgmma_commit(); wgmma_wait<1>(); release(s0); }
        };
        {
          bwait(0x40000040u, false);
          mbar_wait_c(bars + B_GATE3, L);
          float mean0, mean1, rs0, rs1;
          stat_get(g_ST1 + ((rb * 2 + w) * 8 + 2 * t) * 64 + 16 * q + g, tag, 72.f, LN_EPS, mean0, rs0, mean1, rs1);
          const uint32_t ns0 = pack2(GA * rs0, GA * rs0), ns1 = pack2(GA * rs1, GA * rs1);
          const uint32_t nb0 = pack2(-mean0 * blo(ns0), -mean0 * blo(ns0)), nb1 = pack2(-mean1 * blo(ns1), -mean1 * blo(ns1));
          const uint32_t al = sb + (aoff & 8191);
#pragma unroll
          for (int kb = 0; kb <= 9; kb++) {
            if (kb < 9) {
              mbar_wait_c(bars + B_FA3 + (9 * w + kb) * 8, L);
              TRC(tr && kb == 0, w, tb + 6);
              MCLK(kb == 0, 5);
              if (kb == 0) SCLK(0);
              QCLK(kb);
              const uint32_t at = al + (w ? (((kb + 1) >> 1) & 3) * ST_BYTES + ((kb + 1) & 1) * 8192 : ((kb >> 1) & 3) * ST_BYTES + (kb & 1) * 8192);
#pragma unroll
              for (int kk = 4 * kb; kk < 4 * kb + 4; kk++) ldsm4(xA[kk], at ^ ((kk & 3) << 5));
            }
            if (kb == 0) continue;
            const uint32_t dep = xA[4 * kb - 4][0] & xA[4 * kb - 3][0] & xA[4 * kb - 2][0] & xA[4 * kb - 1][0] & P.zero;
            mbar_arrive_if(lane == 0 && (kb == 1 || w == 0), bars + B_EA3 + (9 * w + kb - 1) * 8 + dep);
#pragma unroll
            for (int kk = 4 * kb - 4; kk < 4 * kb; kk++) {
#pragma unroll
              for (int e = 0; e < 4; e++) xA[kk][e] = hfma2(xA[kk][e], (e & 1) ? ns1 : ns0, (e & 1) ? nb1 : nb0);
            }
            wgmma_fence();
#pragma unroll
            for (int kk = 4 * kb - 4; kk < 4 * kb; kk++) mma(kk, PP30, w);
          }
          off2 = lds32(sb + SM_OFF);
          z1d = z1_block(rb, w, j) + (tid & 127) * 16;
          zd = z2_block(2 * rb + (q >> 1), j) + (4 * (q & 1) + w) * 4608 + ((g & 3) * 2 + (g >> 2)) * 16 + t * 4;
          asm volatile("" : "+l"(z1d), "+l"(zd));
          wgmma_wait<0>();
          if (__builtin_expect(any_nan(acc[0], acc[2]), 0)) {
            SLOW(2 + L);
            uint4* const rd = g_RD + bid * (36 * 256) + tid;
            const uint8_t* xr = P.xs[L + 1] + (128 * rb + 32 * q + 2 * g + w) * (DM * 2) + t * 4;
#pragma unroll
            for (int i = 0; i < 32; i++) acc[i] = 0.f;
            redo<KS3, 8, 16, DM * 32, FH * 32, 16>(acc, xr, (const uint8_t*)P.w_in + g * (FH * 4) + (((9 * j + 1) >> 1) + 36) * 128 + t * 4,
                                              [&](uint32_t* a, int k) {
#pragma unroll
                                                for (int e = 0; e < 4; e++) a[e] = hfma2(a[e], (e & 1) ? ns1 : ns0, (e & 1) ? nb1 : nb0);
                                                stg128(rd + k * 256, a[0], a[1], a[2], a[3]);
                                              });
#pragma unroll
            for (int k = 0; k < 36; k++) { const uint4 v = ldcg128(rd + k * 256); xA[k][0] = v.x; xA[k][1] = v.y; xA[k][2] = v.z; xA[k][3] = v.w; }
          }
        }
        float sm[4] = {0.f, 0.f, 0.f, 0.f}, qq[4] = {0.f, 0.f, 0.f, 0.f};
        auto gelu = [&](auto nz2, bool out) {
          constexpr int NZ2 = nz2.value, R = 8 - NZ2, N = 8, D = NZ2 == 8 ? GM2 : NZ2 ? GMM : GM1;
          float th[32], gb = GB;
          uint32_t qa = 0, qb = 0;
          auto head = [&](int G) {
#pragma unroll
            for (int e = 0; e < 4; e++) { const float v = acc[4 * G + e]; th[4 * G + e] = tanh_fast(v * fmaf(v, v, gb)); }
          };
#pragma unroll
          for (int i = 0; i < D; i++) head((i + R) & 7);
#pragma unroll
          for (int i = 0; i < N; i++) {
            const int G = (i + R) & 7;
            if (i + D < N) head((i + D + R) & 7);
            float* z = acc + 4 * G;
#pragma unroll
            for (int e = 0; e < 4; e++) z[e] = fmaf(z[e], th[4 * G + e], z[e]);
            uint32_t pa = pack2(z[0], z[1]), pb = pack2(z[2], z[3]), tok;
            if (i < NZ2) {
#pragma unroll
              for (int e = 0; e < 4; e++) { sm[e] += z[e]; qq[e] = fmaf(z[e], z[e], qq[e]); }
              pa = hsub2(pa, off2); pb = hsub2(pb, off2);
              stg32(zd + i * 128, pa); stg32(zd + i * 128 + 9216, pb);
              tok = pa ^ pb ^ __float_as_uint(qq[1]);
            } else {
              if (NZ2 && G == 3) sts128(sb + SM_STG + tid * 16, qa, qb, pa, pb);
              else if (G & 1) stg128_if(out, z1d + (G >> 1) * 2048 + (NZ2 ? 24576 : 0), qa, qb, pa, pb);
              qa = pa; qb = pb;
              tok = pa ^ pb;
            }
            gb = __uint_as_float(tok * P.zero + __float_as_uint(GB));
          }
        };
#pragma unroll 1
        for (int p = 0;; p++) {
          wgmma_wait<0>();
          release(c.s);
          c.next();
          TRC(tr && p == 4, w, tb + 7);
          TRC(tr && p == 8, w, tb + 11);
          MCLK(p == 8, 6);
          SCLK(2 * p + 1);
          QCLK(10 + 3 * p);
          auto publish = [&]() {
            signal(EV_ZN);
            const float a0 = qsum(sm[0] + sm[1]), a1 = qsum(sm[2] + sm[3]), q0 = qsum(qq[0] + qq[1]), q1 = qsum(qq[2] + qq[3]);
            const float ss = t ? a1 : a0, m = ss * (1.f / 288.f);
            ll_st128_if(t < 2, g_ZST + (rb * 2 + w) * 512 + j * 64 + 16 * q + 8 * t + g, m - blo(off2), fmaxf((t ? q1 : q0) - ss * m, 0.f), tag);
            TRC(tr, w, tb + 8);
            TRC(tr, w, tb + 9);
          };
          if (p < 4) {
            gelu(Int<8>{}, true);
            zd += 1024;
          } else if (p == 4) {
            gelu(Int<4>{}, true);
            publish();
          } else {
            gelu(Int<0>{}, p < 8);
            z1d += 8192;
          }
          SCLK(2 * p + 2);
          QCLK(11 + 3 * p);
          if (p == 8) break;
          bwait(p == 3 ? 0x80000040u : 0x40000040u, w);
          bar_sync(6 + w, 256);
          TRC(tr && p == 4, w, tb + 10);
          wgmma_fence();
#pragma unroll
          for (int kk = 0; kk < 36; kk++) mma(kk, PP3, w == 0 || p < 7);
        }
        signal(EV_Z1);
#pragma unroll
        for (int u = 0; u < 4; u++) {
          zk[u] = make_uint4(pack2(acc[8 * u], acc[8 * u + 1]), pack2(acc[8 * u + 2], acc[8 * u + 3]), pack2(acc[8 * u + 4], acc[8 * u + 5]), pack2(acc[8 * u + 6], acc[8 * u + 7]));
          asm volatile("" : "+r"(zk[u].x), "+r"(zk[u].y), "+r"(zk[u].z), "+r"(zk[u].w));
        }
        TRC(tr, w, tb + 12);
      }
      uint32_t hA[18][4];
      {
        float acc[144];
        const float c0 = __uint_as_float(lds32(sb + SM_OFF + 4));
#pragma unroll
        for (int i = 0; i < 144; i++) {
          asm volatile("fma.rn.f32 %0, %1, %2, %3;" : "=f"(acc[i]) : "f"(__uint_as_float(P.zero)), "f"((float)(i + 2)), "f"(c0));
        }
        uint32_t prev = 0;
        auto stage = [&](int kb) {
          mbar_wait_c(bars + B_FULL + c.s * 8, c.ph);
          TRC(tr && kb == 0, w, tb + 13);
          SCLK(22 + kb);
          const uint32_t st = sb + c.s * ST_BYTES, rt = sb + SM_RT + kb * 128 + t * 8;
          uint64_t db = dsc2(dlo(st + ST_B, 4608), 0, 8 + P.zero);
          uint32_t a[4][4];
#pragma unroll
          for (int kk = 0; kk < 4; kk++) {
            uint32_t r[4];
            ldsm4(r, st + (aoff ^ (kk << 5)));
            const uint2 sc = lds64(rt + kk * 32);
            a[kk][0] = hmul2(__byte_perm(r[0], r[2], 0x5410), sc.x); a[kk][2] = hmul2(__byte_perm(r[0], r[2], 0x7632), sc.y);
            a[kk][1] = hmul2(__byte_perm(r[1], r[3], 0x5410), sc.x); a[kk][3] = hmul2(__byte_perm(r[1], r[3], 0x7632), sc.y);
          }
          wgmma_fence();
#pragma unroll
          for (int i = 0; i < 8; i++) {
            const int kk = i & 3, hf = i >> 2;
            wgmma_rs_n144(acc + hf * 72, a[kk], db, 1);
            dadd(db, i == 3 ? 144u - 3 * 576 : 576 + P.zero);
            if (i == 0) { wgmma_commit(); wgmma_wait<1>(); release_if(kb, prev); }
            if (i == 3) wgmma_commit();
          }
          wgmma_commit();
          prev = c.s; c.next();
        };
        mbar_wait_c(bars + B_RT, L);
#pragma unroll 1
        for (int kb = 0; kb < 32; kb += 2) {
          if (kb == 8) mbar_wait_c(bars + B_RT1, L);
          MCLK((kb & 7) == 4, 10 + (kb >> 3));
          stage(kb);
          stage(kb + 1);
        }
        if (w == 1) bar_arrive(6, 256);
        HCLK(0);
        mbar_wait_c(bars + B_CV + w * 8, L);
        HCLK(1);
        const float gk = 0.5f / GA;
        const float c1 = __uint_as_float(lds32(sb + SM_OFF + 4));
        const float gb0 = -gk * (c1 + __uint_as_float(lds32(sb + SM_CV + w * 256 + (16 * q + g) * 4))), gb1 = -gk * (c1 + __uint_as_float(lds32(sb + SM_CV + w * 256 + (16 * q + g + 8) * 4)));
        mbar_wait_c(w ? bars + B_FULL + c.s * 8 : bars + B_ZB, w ? c.ph : L);
        HCLK(2);
        const uint32_t sx = c.s;
        c.next();
        const uint32_t zt = sb + tid * 16, zs = zt + sx * ST_BYTES + w * 24576;
        uint4 zz[18];
        auto zload = [&](int u) {
          if (ZW && u == ZW && P.zero) __nanosleep(0);
          if (u >= 12 && u < 16) zz[u] = zk[u - 12]; else zz[u] = lds128(u == 17 ? zt + SM_STG : zs + (u < 12 ? u : 12) * 2048);
        };
#pragma unroll
        for (int u = 0; u < ZA; u++) zload(u);
#pragma unroll
        for (int u = 0; u < 18; u++) {
          if (u == 0) { wgmma_wait<1>(); HCLK(3); }
          if (u == 9) {
            HCLK(4);
            wgmma_wait<0>();
            HCLK(5);
            release(prev);
            mbar_arrive_if(L == 0 && lane == 0, ev + EV_P4 * 8);
            TRC(tr, w, tb + 14);
            SCLK(54);
          }
          if (u + ZA < 18) zload(u + ZA);
          const uint4 z = zz[u];
          hA[u][0] = hmul2(z.x, pack2(fmaf(acc[8 * u], gk, gb0), fmaf(acc[8 * u + 1], gk, gb0)));
          hA[u][1] = hmul2(z.y, pack2(fmaf(acc[8 * u + 2], gk, gb1), fmaf(acc[8 * u + 3], gk, gb1)));
          hA[u][2] = hmul2(z.z, pack2(fmaf(acc[8 * u + 4], gk, gb0), fmaf(acc[8 * u + 5], gk, gb0)));
          hA[u][3] = hmul2(z.w, pack2(fmaf(acc[8 * u + 6], gk, gb1), fmaf(acc[8 * u + 7], gk, gb1)));
        }
        uint32_t dep = P.zero;
#pragma unroll
        for (int u = 0; u < 18; u++) dep &= hA[u][0];
        release(sx, dep);
        TRC(tr, w, tb + 15);
        HCLK(6);
      }
      {
        CLK_INIT;
        uint32_t pk[16];
#pragma unroll
        for (int i = 0; i < 16; i++) pk[i] = 0u;
        auto dump = [&](int p) {
          const uint32_t d = sb + (p & 3) * ST_BYTES, cb = p + j >= 9 ? p + j - 9 : p + j;
          if (lane == 0) asm volatile("cp.async.bulk.wait_group.read 3;" ::: "memory");
          __syncwarp();
#pragma unroll
          for (int u = 0; u < 4; u++) stsm4(d + (aoff ^ (u << 5)), pk[4 * u], pk[4 * u + 1], pk[4 * u + 2], pk[4 * u + 3]);
          fence_async_s();
          __syncwarp();
          tma3d_red_p(lane == 0, &P.red[L], cb * 64, rb * 64 + q * 16, w, d + w * 8192 + q * 2048);
        };
#pragma unroll 1
        for (int p = 0; p < 9; p++) {
          float acc[32];
          CLK(0);
          mbar_wait_c(bars + B_FULL + c.s * 8, c.ph);
          uint64_t db = dsc2(dlo(sb + c.s * ST_BYTES + ST_B + (j & 1) * 4096, 0), 0, 0x40000040u + P.zero);
          CLK(1);
          HCLK(7 + 2 * p);
          bar_sync(6 + w, 256);
          CLK(2);
          wgmma_fence();
#pragma unroll
          for (int kk = 0; kk < 18; kk++) {
            wgmma_rs_n64(acc, hA[kk], db, kk != 0);
            dadd(db, kk == 15 ? 128 - (j & 1) * (36864 >> 4) : 128 + P.zero);
            if (kk == PPK && (w == 0 || p < 8)) bar_arrive(7 - w, 256);
          }
          wgmma_commit();
          CLK(3);
          if (p > 0) dump(p - 1);
          CLK(5);
          wgmma_wait<0>();
          CLK(4);
          HCLK(8 + 2 * p);
          MCLK(p == 1 || p == 8, 7 + (p >> 3));
          release_if(L == 0 || p < 5, c.s);
          c.next();
#pragma unroll
          for (int i = 0; i < 16; i++) pk[i] = pack2(acc[2 * i], acc[2 * i + 1]);
          if (p == 8) { TRC(tr, w, tb + 16); dump(8); TRC(tr, w, tb + 17); }
        }
        if (lane == 0) asm volatile("cp.async.bulk.wait_group 0;" ::: "memory");
        HCLK(25);
        MCLK(1, 9);
        if (L == 0) signal(EV_PT);
        CLK_OUT;
        TRC(tr, w, tb + 18);
      }
    }
    if ((tid & 127) == 0) g_flags[(rb * 2 + w) * 32 + FR_EP + j] = epoch + 1;
    if (tid == 0) g_flags[FJ + j * 32 + FJ_EP + rb] = epoch + 1;
  }
}

typedef CUresult (*EncodeFn)(CUtensorMap*, CUtensorMapDataType, cuuint32_t, void*, const cuuint64_t*, const cuuint64_t*, const cuuint32_t*,
                             const cuuint32_t*, CUtensorMapInterleave, CUtensorMapSwizzle, CUtensorMapL2promotion, CUtensorMapFloatOOBfill);

static void make_map(EncodeFn fn, CUtensorMap* m, const void* ptr, int rank, uint64_t d0, uint64_t d1, uint64_t d2, uint64_t s1, uint64_t s2,
                     uint32_t b0, uint32_t b1, uint32_t b2, CUtensorMapSwizzle swz) {
  cuuint64_t dims[3] = {d0, d1, d2}, strides[2] = {s1, s2};
  cuuint32_t box[3] = {b0, b1, b2}, es[3] = {1, 1, 1};
  fn(m, CU_TENSOR_MAP_DATA_TYPE_BFLOAT16, rank, const_cast<void*>(ptr), dims, strides, box, es, CU_TENSOR_MAP_INTERLEAVE_NONE, swz,
     CU_TENSOR_MAP_L2_PROMOTION_L2_128B, CU_TENSOR_MAP_FLOAT_OOB_FILL_NONE);
}

}

extern "C" void kernel_launch(void* const* d_in, const int* in_sizes, int n_in, void* d_out, int out_size) {
  using namespace mk;
  (void)in_sizes; (void)n_in; (void)out_size;
  static EncodeFn fn = nullptr;
  static uint8_t *wq, *xb;
  static float* csp;
  if (!fn) {
    cudaGetSymbolAddress((void**)&wq, g_WQ);
    cudaGetSymbolAddress((void**)&xb, g_X);
    cudaGetSymbolAddress((void**)&csp, g_CSP);
    cudaDriverEntryPointQueryResult qr;
    cudaGetDriverEntryPoint("cuTensorMapEncodeTiled", (void**)&fn, cudaEnableDefault, &qr);
    cudaFuncSetAttribute(mega_kernel, cudaFuncAttributeMaxDynamicSharedMemorySize, SM_TOTAL);
  }
  Params p;
  p.wqkv = (const __nv_bfloat16*)d_in[1];
  p.w_in = (const __nv_bfloat16*)d_in[4];
  p.w_sp = (const __nv_bfloat16*)d_in[5];
  p.b_sp = (const __nv_bfloat16*)d_in[6];
  p.w_out = (const __nv_bfloat16*)d_in[7];
  p.zero = 0;
  p.wq = wq;
  p.csp = csp;
  p.xs[0] = (uint8_t*)d_in[0];
  p.xs[1] = xb;
  p.xs[2] = (uint8_t*)d_out;
  make_map(fn, &p.wsp, p.w_sp, 3, 2048, 1024, 2, 8192, 4096, 64, 64, 2, CU_TENSOR_MAP_SWIZZLE_128B);
  for (int i = 0; i < 2; i++) {
    make_map(fn, &p.red[i], p.xs[i + 1], 3, DM, 1024, 2, 2304, 1152, 64, 16, 1, CU_TENSOR_MAP_SWIZZLE_128B);
    make_map(fn, &p.res[i], p.xs[i], 3, DM, 1024, 2, 2304, 1152, 144, 64, 1, CU_TENSOR_MAP_SWIZZLE_NONE);
  }
  make_map(fn, &p.psn, d_out, 3, DM, 1024, 2, 2304, 1152, 144, 4, 1, CU_TENSOR_MAP_SWIZZLE_NONE);
  for (int i = 0; i < 3; i++) make_map(fn, &p.act[i], p.xs[i], 3, DM, 1024, 2, 2304, 1152, 64, 64, 1, CU_TENSOR_MAP_SWIZZLE_128B);
  {
    cuuint64_t dims[4] = {8, 8, 72, 72}, strides[3] = {1152, 16, 9216};
    cuuint32_t box[4] = {8, 8, 9, 5}, es[4] = {1, 1, 1, 1};
    fn(&p.wo8, CU_TENSOR_MAP_DATA_TYPE_BFLOAT16, 4, d_in[2], dims, strides, box, es, CU_TENSOR_MAP_INTERLEAVE_NONE, CU_TENSOR_MAP_SWIZZLE_NONE,
       CU_TENSOR_MAP_L2_PROMOTION_L2_128B, CU_TENSOR_MAP_FLOAT_OOB_FILL_NONE);
  }
  for (int i = 0; i < 2; i++) {
    cuuint64_t dims[4] = {i ? 4608u : 2304u, 8, i ? 1u : 2u, 72}, strides[3] = {9216, 4608, 8 * 9216};
    cuuint32_t box[4] = {i ? 64u : 32u, 8, i ? 1u : 2u, 18}, es[4] = {1, 1, 1, 1};
    fn(i ? &p.win64 : &p.win, CU_TENSOR_MAP_DATA_TYPE_BFLOAT16, 4, d_in[4], dims, strides, box, es, CU_TENSOR_MAP_INTERLEAVE_NONE,
       i ? CU_TENSOR_MAP_SWIZZLE_128B : CU_TENSOR_MAP_SWIZZLE_64B, CU_TENSOR_MAP_L2_PROMOTION_L2_128B, CU_TENSOR_MAP_FLOAT_OOB_FILL_NONE);
  }
  make_map(fn, &p.wout, p.w_out, 2, 576, 2304, 1, 1152, 0, 64, 144, 1, CU_TENSOR_MAP_SWIZZLE_128B);
  mega_kernel<<<NGRID, 384, SM_TOTAL, cudaStreamPerThread>>>(p);
}
```

```cpp
#include <cuda_runtime.h>
#include <cuda.h>
#include <cuda_bf16.h>
#include <stdint.h>

#define MK_TRACE 0
#define MK_DBG 0
#define P5TRACE 0
#define LAG1 3
#define PP3 32
#define PP30 33
#define SPL 2
#define NAP 200
#define NAP0 8000
#define KS2 2
#define KS3 2
#define RL3 21
#define PAD 0
#define ZA 4
#define ZW 10
#define GM2 1
#define GMM 1
#define GM1 2
#define C0S 32.f
#define OFA 0.125f
#define OFK 2.f
#define PPK 13

namespace mk {

constexpr int SEQ = 2048, DM = 576, FH = 2304;
constexpr int NCTA = 128;
constexpr int NGRID = 132;
constexpr uint32_t ZB = 36864;
constexpr uint32_t WQ_SL = 72 * 3456;
constexpr uint32_t WO_SL = 72 * 1152;
constexpr float LN_EPS = 1e-5f;
constexpr float GA = 0.3292034911525734f, GB = 2.423681954311584f;

constexpr uint32_t ST_BYTES = 53248, ST_B = 16384, NST = 4;
constexpr uint32_t SM_STG = NST * ST_BYTES;
constexpr uint32_t SM_BAR = SM_STG + 2 * 9216;
constexpr uint32_t SM_OFF = SM_BAR + 1008;
constexpr uint32_t SM_TOTAL = SM_BAR + 1024;
constexpr uint32_t SM_RT = SM_STG + 4096, SM_CV = SM_STG + 12288, SM_WT = SM_CV + 512;
constexpr uint32_t SM_WOI = 44032, SM_CSQ = 49792, SM_XST = 50688;
constexpr uint32_t B_FULL = 0, B_EMPTY = 32, B_FULLA = 64, B_RES = 128, B_WT = 144, B_IMG = 160, B_WOI = 168, B_ZB = 176, B_GATE3 = 184, B_Z1 = 192, B_LAG = 200,
                   B_RT = 208, B_CSQ = 216, B_CV = 224, B_AD = 240, B_EVT = 272, B_RT1 = 368, B_XS = 624, B_XRW = 384, B_FA3 = 400, B_EA3 = 544;
enum { EV_PT = 0, EV_O = 1, EV_X1 = 2, EV_ZN = 3, EV_Z1 = 4, EV_P4 = 5, EV_N = 6 };

enum { FR_X2 = 0, FR_O = 1, FR_X1 = 3, FR_EP = 16, FJ = 32 * 32, FJ_WQ = 0, FJ_WO = 1, FJ_WQ0 = 2, FJ_ZN = 3, FJ_P4 = 5, FJ_EP = 16, F_N = FJ + 8 * 32 };

__device__ __align__(1024) uint8_t g_Z[512 * ZB];
constexpr uint32_t POISON = 0xffffffffu;
__device__ __align__(1024) uint8_t g_O[32 * 2 * ZB];
__device__ __align__(1024) uint4 g_RD[NCTA * 36 * 256];
__device__ __align__(1024) uint8_t g_X[SEQ * DM * 2];
#define SLOW(i) do {} while (0)
__device__ __align__(1024) uint8_t g_WQ[8 * WQ_SL];
__device__ __align__(1024) uint8_t g_WO[8 * WO_SL];
__device__ __align__(1024) float g_CSP[2 * NCTA * 216];
__device__ __align__(1024) uint2 g_RT[SEQ];
__device__ __align__(1024) uint4 g_XST[2 * SEQ];
__device__ __align__(1024) uint4 g_ST1[SEQ * 8];
__device__ __align__(1024) uint4 g_ZST[SEQ * 8];
__device__ __align__(1024) uint4 g_HALO[32 * 8 * 6 * 32];
__device__ __align__(1024) uint32_t g_flags[F_N];

struct Params {
  const __nv_bfloat16 *wqkv;
  uint8_t* wq;
  float* csp;
  uint32_t zero;
  const __nv_bfloat16 *w_in, *w_sp, *b_sp, *w_out;
  uint8_t* xs[3];
  CUtensorMap wo8, wsp, win, win64, wout;
  CUtensorMap act[3];
  CUtensorMap res[2];
  CUtensorMap red[2];
  CUtensorMap psn;
};

__device__ __forceinline__ uint32_t smem_u32(const void* p) { return (uint32_t)__cvta_generic_to_shared(p); }
__device__ __forceinline__ void mbar_init(uint32_t bar, uint32_t cnt) { asm volatile("mbarrier.init.shared::cta.b64 [%0], %1;" ::"r"(bar), "r"(cnt)); }
__device__ __forceinline__ void mbar_arrive(uint32_t bar) { asm volatile("mbarrier.arrive.shared::cta.b64 _, [%0];" ::"r"(bar) : "memory"); }
__device__ __forceinline__ void mbar_wait(uint32_t bar, uint32_t parity) {
  asm volatile(
      "{\n.reg .pred p;\n.reg .u32 c;\nmov.u32 c, 0;\nLAB_WAIT:\n"
      "mbarrier.try_wait.parity.shared::cta.b64 p, [%0], %1;\n@p bra LAB_DONE;\n"
      "add.u32 c, c, 1;\nsetp.lt.u32 p, c, 0x100000;\n@p bra LAB_WAIT;\ntrap;\nLAB_DONE:\n}" ::"r"(bar), "r"(parity)
      : "memory");
}
__device__ __forceinline__ void mbar_wait_c(uint32_t bar, uint32_t parity) {
  asm volatile("{\n.reg .pred p;\nLAB_WAIT:\nmbarrier.try_wait.parity.shared::cta.b64 p, [%0], %1;\n@!p bra LAB_WAIT;\n}" ::"r"(bar), "r"(parity) : "memory");
}
__device__ __forceinline__ void flag_wait(const uint32_t* f, uint32_t target) {
  asm volatile(
      "{\n.reg .pred p;\n.reg .u32 c, v;\nmov.u32 c, 0;\nLAB_WAIT:\n"
      "ld.relaxed.gpu.global.u32 v, [%0];\nsub.u32 v, v, %1;\nsetp.ge.s32 p, v, 0;\n@p bra LAB_DONE;\n"
      "add.u32 c, c, 1;\nsetp.lt.u32 p, c, 0x400000;\n@p bra LAB_WAIT;\ntrap;\nLAB_DONE:\nfence.acquire.gpu;\n}" ::"l"(f), "r"(target)
      : "memory");
}
__device__ __forceinline__ void fence_gpu() { asm volatile("fence.acq_rel.gpu;" ::: "memory"); }
__device__ __forceinline__ void fence_async_g() { asm volatile("fence.proxy.async.global;" ::: "memory"); }
__device__ __forceinline__ void fence_async_s() { asm volatile("fence.proxy.async.shared::cta;" ::: "memory"); }
__device__ __forceinline__ uint32_t elect_one() {
  uint32_t p; asm volatile("{\n.reg .pred P;\nelect.sync _|P, 0xffffffff;\nselp.u32 %0, 1, 0, P;\n}" : "=r"(p)); return p;
}
__device__ __forceinline__ void expect_tx_p(uint32_t el, uint32_t bar, uint32_t bytes) {
  asm volatile("{\n.reg .pred P;\nsetp.ne.u32 P, %2, 0;\n@P mbarrier.arrive.expect_tx.shared::cta.b64 _, [%0], %1;\n}" ::"r"(bar), "r"(bytes), "r"(el) : "memory");
}
__device__ __forceinline__ void bulk_load_p(uint32_t el, uint32_t dst, const void* src, uint32_t bytes, uint32_t bar) {
  asm volatile("{\n.reg .pred P;\nsetp.ne.u32 P, %4, 0;\n@P cp.async.bulk.shared::cluster.global.mbarrier::complete_tx::bytes [%0], [%1], %2, [%3];\n}" ::"r"(dst), "l"(src), "r"(bytes), "r"(bar), "r"(el) : "memory");
}
__device__ __forceinline__ uint64_t policy_evict_first() { uint64_t p; asm("createpolicy.fractional.L2::evict_first.b64 %0, 1.0;" : "=l"(p)); return p; }
__device__ __forceinline__ void bulk_load_h(uint32_t el, uint32_t dst, const void* src, uint32_t bytes, uint32_t bar, bool ef, uint64_t pol) {
  if (ef) {
    asm volatile("{\n.reg .pred P;\nsetp.ne.u32 P, %4, 0;\n@P cp.async.bulk.shared::cluster.global.mbarrier::complete_tx::bytes.L2::cache_hint [%0], [%1], %2, [%3], %5;\n}" ::"r"(dst), "l"(src), "r"(bytes), "r"(bar), "r"(el), "l"(pol) : "memory");
  } else {
    asm volatile("{\n.reg .pred P;\nsetp.ne.u32 P, %4, 0;\n@P cp.async.bulk.shared::cluster.global.mbarrier::complete_tx::bytes [%0], [%1], %2, [%3];\n}" ::"r"(dst), "l"(src), "r"(bytes), "r"(bar), "r"(el) : "memory");
  }
}
__device__ __forceinline__ void bulk_mc_h(uint32_t el, uint32_t dst, const void* src, uint32_t bytes, uint32_t bar, bool ef, uint64_t pol) {
  if (ef) {
    asm volatile("{\n.reg .pred P;\nsetp.ne.u32 P, %4, 0;\n@P cp.async.bulk.shared::cluster.global.mbarrier::complete_tx::bytes.multicast::cluster.L2::cache_hint [%0], [%1], %2, [%3], %5, %6;\n}" ::"r"(dst), "l"(src), "r"(bytes), "r"(bar), "r"(el), "h"((uint16_t)3), "l"(pol) : "memory");
  } else {
    asm volatile("{\n.reg .pred P;\nsetp.ne.u32 P, %4, 0;\n@P cp.async.bulk.shared::cluster.global.mbarrier::complete_tx::bytes.multicast::cluster [%0], [%1], %2, [%3], %5;\n}" ::"r"(dst), "l"(src), "r"(bytes), "r"(bar), "r"(el), "h"((uint16_t)3) : "memory");
  }
}
__device__ __forceinline__ void tma3d_h(uint32_t el, uint32_t dst, const CUtensorMap* m, int c0, int c1, int c2, uint32_t bar, bool ef, uint64_t pol) {
  if (ef) {
    asm volatile("{\n.reg .pred P;\nsetp.ne.u32 P, %6, 0;\n@P cp.async.bulk.tensor.3d.shared::cluster.global.mbarrier::complete_tx::bytes.L2::cache_hint [%0], [%1, {%3, %4, %5}], [%2], %7;\n}" ::"r"(dst), "l"(m), "r"(bar), "r"(c0), "r"(c1), "r"(c2), "r"(el), "l"(pol) : "memory");
  } else {
    asm volatile("{\n.reg .pred P;\nsetp.ne.u32 P, %6, 0;\n@P cp.async.bulk.tensor.3d.shared::cluster.global.mbarrier::complete_tx::bytes [%0], [%1, {%3, %4, %5}], [%2];\n}" ::"r"(dst), "l"(m), "r"(bar), "r"(c0), "r"(c1), "r"(c2), "r"(el) : "memory");
  }
}
__device__ __forceinline__ void tma2d_mc_h(uint32_t el, uint32_t dst, const CUtensorMap* m, int c0, int c1, uint32_t bar, bool ef, uint64_t pol) {
  if (ef) {
    asm volatile("{\n.reg .pred P;\nsetp.ne.u32 P, %5, 0;\n@P cp.async.bulk.tensor.2d.shared::cluster.global.mbarrier::complete_tx::bytes.multicast::cluster.L2::cache_hint [%0], [%1, {%3, %4}], [%2], %6, %7;\n}" ::"r"(dst), "l"(m), "r"(bar), "r"(c0), "r"(c1), "r"(el), "h"((uint16_t)3), "l"(pol) : "memory");
  } else {
    asm volatile("{\n.reg .pred P;\nsetp.ne.u32 P, %5, 0;\n@P cp.async.bulk.tensor.2d.shared::cluster.global.mbarrier::complete_tx::bytes.multicast::cluster [%0], [%1, {%3, %4}], [%2], %6;\n}" ::"r"(dst), "l"(m), "r"(bar), "r"(c0), "r"(c1), "r"(el), "h"((uint16_t)3) : "memory");
  }
}
__device__ __forceinline__ void tma4d_mc(uint32_t el, uint32_t dst, const CUtensorMap* m, int c0, int c3, uint32_t bar, uint64_t pol) {
  asm volatile("{\n.reg .pred P;\nsetp.ne.u32 P, %5, 0;\n@P cp.async.bulk.tensor.4d.shared::cluster.global.mbarrier::complete_tx::bytes.multicast::cluster.L2::cache_hint [%0], [%1, {%3, 0, 0, %4}], [%2], %6, %7;\n}" ::"r"(dst), "l"(m), "r"(bar), "r"(c0), "r"(c3), "r"(el), "h"((uint16_t)3), "l"(pol) : "memory");
}
__device__ __forceinline__ void mbar_arrive_cluster(uint32_t addr) { asm volatile("mbarrier.arrive.shared::cluster.b64 _, [%0];" ::"r"(addr) : "memory"); }
__device__ __forceinline__ void mbar_arrive_cluster_if(bool c, uint32_t addr) {
  asm volatile("{\n.reg .pred P;\nsetp.ne.u32 P, %1, 0;\n@P mbarrier.arrive.shared::cluster.b64 _, [%0];\n}" ::"r"(addr), "r"((uint32_t)c) : "memory");
}
__device__ __forceinline__ void mbar_arrive_if(bool c, uint32_t addr) {
  asm volatile("{\n.reg .pred P;\nsetp.ne.u32 P, %1, 0;\n@P mbarrier.arrive.shared::cta.b64 _, [%0];\n}" ::"r"(addr), "r"((uint32_t)c) : "memory");
}
__device__ __forceinline__ uint32_t mapa(uint32_t addr, uint32_t rank) { uint32_t r; asm("mapa.shared::cluster.u32 %0, %1, %2;" : "=r"(r) : "r"(addr), "r"(rank)); return r; }
__device__ __forceinline__ void bulk_store_p(uint32_t el, void* dst, uint32_t src, uint32_t bytes) {
  asm volatile("{\n.reg .pred P;\nsetp.ne.u32 P, %3, 0;\n@P cp.async.bulk.global.shared::cta.bulk_group [%0], [%1], %2;\n}" ::"l"(dst), "r"(src), "r"(bytes), "r"(el) : "memory");
}
__device__ __forceinline__ void flag_release_p(uint32_t el, uint32_t* f) {
  asm volatile("{\n.reg .pred P;\nsetp.ne.u32 P, %1, 0;\n@P red.release.gpu.global.add.u32 [%0], 1;\n}" ::"l"(f), "r"(el) : "memory");
}
__device__ __forceinline__ void flag_add_p(uint32_t el, uint32_t* f) {
  asm volatile("{\n.reg .pred P;\nsetp.ne.u32 P, %1, 0;\n@P red.relaxed.gpu.global.add.u32 [%0], 1;\n}" ::"l"(f), "r"(el) : "memory");
}
__device__ __forceinline__ void prefetch_l2(const void* src, uint32_t bytes) { asm volatile("cp.async.bulk.prefetch.L2.global [%0], %1;" ::"l"(src), "r"(bytes) : "memory"); }
__device__ __forceinline__ void prefetch_map(const CUtensorMap* m) { asm volatile("prefetch.tensormap [%0];" ::"l"(m) : "memory"); }
__device__ __forceinline__ void wgmma_fence() { asm volatile("wgmma.fence.sync.aligned;" ::: "memory"); }
__device__ __forceinline__ void wgmma_commit() { asm volatile("wgmma.commit_group.sync.aligned;" ::: "memory"); }
template <int N> __device__ __forceinline__ void wgmma_wait() { asm volatile("wgmma.wait_group.sync.aligned %0;" ::"n"(N) : "memory"); }
__device__ __forceinline__ uint32_t dlo(uint32_t addr, uint32_t lbo) { return ((addr & 0x3FFFF) >> 4) + ((lbo >> 4) << 16); }
template <uint32_t SBO, uint32_t SWZ> __device__ __forceinline__ uint64_t dsc(uint32_t lo, uint32_t off) {
  uint64_t d; asm("mov.b64 %0, {%1, %2};" : "=l"(d) : "r"(lo + (off >> 4)), "n"((SBO >> 4) | (SWZ << 30))); return d;
}
__device__ __forceinline__ uint64_t dsc2(uint32_t lo, uint32_t off, uint32_t hi) {
  uint64_t d; asm("mov.b64 %0, {%1, %2};" : "=l"(d) : "r"(lo + (off >> 4)), "r"(hi)); return d;
}
__device__ __forceinline__ uint64_t dat(uint64_t d, uint32_t off, uint32_t one) { uint64_t r; asm("mad.wide.u32 %0, %1, %2, %3;" : "=l"(r) : "r"(one), "r"(off >> 4), "l"(d)); return r; }
__device__ __forceinline__ void dadd(uint64_t& d, uint32_t v) {
  asm("{\n.reg .b32 lo, hi;\nmov.b64 {lo, hi}, %0;\nadd.u32 lo, lo, %1;\nmov.b64 %0, {lo, hi};\n}" : "+l"(d) : "r"(v));
}
template <int R> __device__ __forceinline__ void reg_alloc() { asm volatile("setmaxnreg.inc.sync.aligned.u32 %0;" ::"n"(R)); }
template <int R> __device__ __forceinline__ void reg_dealloc() { asm volatile("setmaxnreg.dec.sync.aligned.u32 %0;" ::"n"(R)); }
__device__ __forceinline__ void bar_sync(int id, int n) { asm volatile("bar.sync %0, %1;" ::"r"(id), "r"(n) : "memory"); }
__device__ __forceinline__ void bar_arrive(int id, int n) { asm volatile("bar.arrive %0, %1;" ::"r"(id), "r"(n) : "memory"); }
__device__ __forceinline__ void ldsm4(uint32_t* r, uint32_t addr) {
  asm volatile("ldmatrix.sync.aligned.m8n8.x4.shared.b16 {%0,%1,%2,%3}, [%4];" : "=r"(r[0]), "=r"(r[1]), "=r"(r[2]), "=r"(r[3]) : "r"(addr) : "memory");
}
__device__ __forceinline__ uint32_t movm(uint32_t a) { uint32_t d; asm volatile("movmatrix.sync.aligned.m8n8.trans.b16 %0, %1;" : "=r"(d) : "r"(a)); return d; }
__device__ __forceinline__ void mma16(float* c, uint32_t a0, uint32_t a1, uint32_t a2, uint32_t a3, uint32_t b0, uint32_t b1) {
  asm volatile("mma.sync.aligned.m16n8k16.row.col.f32.bf16.bf16.f32 {%0,%1,%2,%3}, {%4,%5,%6,%7}, {%8,%9}, {%10,%10,%10,%10};"
               : "=f"(c[0]), "=f"(c[1]), "=f"(c[2]), "=f"(c[3]) : "r"(a0), "r"(a1), "r"(a2), "r"(a3), "r"(b0), "r"(b1), "f"(0.f));
}
__device__ __forceinline__ void mma8(float* c, uint32_t a0, uint32_t a1, uint32_t b0) {
  asm volatile("mma.sync.aligned.m16n8k8.row.col.f32.bf16.bf16.f32 {%0,%1,%2,%3}, {%4,%5}, {%6}, {%0,%1,%2,%3};"
               : "+f"(c[0]), "+f"(c[1]), "+f"(c[2]), "+f"(c[3]) : "r"(a0), "r"(a1), "r"(b0));
}
__device__ __forceinline__ uint32_t pack2(float lo, float hi) { uint32_t r; asm("cvt.rn.bf16x2.f32 %0, %1, %2;" : "=r"(r) : "f"(hi), "f"(lo)); return r; }
__device__ __forceinline__ float blo(uint32_t v) { return __uint_as_float(v << 16); }
__device__ __forceinline__ float bhi(uint32_t v) { return __uint_as_float(v & 0xffff0000u); }
__device__ __forceinline__ float tanh_fast(float x) { float y; asm("tanh.approx.f32 %0, %1;" : "=f"(y) : "f"(x)); return y; }
__device__ __forceinline__ float rcp_fast(float x) { float y; asm("rcp.approx.ftz.f32 %0, %1;" : "=f"(y) : "f"(x)); return y; }
__device__ __forceinline__ float ex2(float x) { float y; asm("ex2.approx.ftz.f32 %0, %1;" : "=f"(y) : "f"(x)); return y; }
__device__ __forceinline__ float qsum(float v) { v += __shfl_xor_sync(~0u, v, 1); v += __shfl_xor_sync(~0u, v, 2); return v; }
__device__ __forceinline__ float qmax(float v) { v = fmaxf(v, __shfl_xor_sync(~0u, v, 1)); v = fmaxf(v, __shfl_xor_sync(~0u, v, 2)); return v; }
__device__ __forceinline__ void stg32(void* p, uint32_t v) { asm volatile("st.global.u32 [%0], %1;" ::"l"(p), "r"(v) : "memory"); }
__device__ __forceinline__ void stg128(void* p, uint32_t a, uint32_t b, uint32_t c, uint32_t d) { asm volatile("st.global.v4.u32 [%0], {%1,%2,%3,%4};" ::"l"(p), "r"(a), "r"(b), "r"(c), "r"(d) : "memory"); }
__device__ __forceinline__ uint32_t ldcg32(const void* p) { uint32_t v; asm volatile("ld.global.L1::no_allocate.u32 %0, [%1];" : "=r"(v) : "l"(p) : "memory"); return v; }
__device__ __forceinline__ uint32_t ldgpu32(const void* p) { uint32_t v; asm volatile("ld.relaxed.gpu.global.u32 %0, [%1];" : "=r"(v) : "l"(p) : "memory"); return v; }
__device__ __forceinline__ uint32_t ldca32(const void* p) { uint32_t v; asm volatile("ld.global.ca.u32 %0, [%1];" : "=r"(v) : "l"(p) : "memory"); return v; }
__device__ __forceinline__ void stg128_if(bool c, void* p, uint32_t a, uint32_t b, uint32_t cc, uint32_t d) {
  asm volatile("{\n.reg .pred P;\nsetp.ne.u32 P, %5, 0;\n@P st.global.v4.u32 [%0], {%1,%2,%3,%4};\n}" ::"l"(p), "r"(a), "r"(b), "r"(cc), "r"(d), "r"((uint32_t)c) : "memory");
}
__device__ __forceinline__ uint2 lds64(uint32_t a) { uint2 v; asm volatile("ld.shared.v2.u32 {%0,%1}, [%2];" : "=r"(v.x), "=r"(v.y) : "r"(a) : "memory"); return v; }
__device__ __forceinline__ uint4 ldcg128(const void* p) { uint4 v; asm volatile("ld.global.cg.v4.u32 {%0,%1,%2,%3}, [%4];" : "=r"(v.x), "=r"(v.y), "=r"(v.z), "=r"(v.w) : "l"(p) : "memory"); return v; }
__device__ __forceinline__ uint32_t ldnc16(const void* p) { uint16_t v; asm volatile("ld.global.nc.u16 %0, [%1];" : "=h"(v) : "l"(p)); return v; }
__device__ __forceinline__ uint4 ldnc128(const void* p) { uint4 v; asm volatile("ld.global.nc.v4.u32 {%0,%1,%2,%3}, [%4];" : "=r"(v.x), "=r"(v.y), "=r"(v.z), "=r"(v.w) : "l"(p)); return v; }
__device__ __forceinline__ uint32_t hsub2(uint32_t a, uint32_t b) { uint32_t d; asm("sub.rn.bf16x2 %0, %1, %2;" : "=r"(d) : "r"(a), "r"(b)); return d; }
__device__ __forceinline__ void stg32_if(bool c, void* p, uint32_t v) {
  asm volatile("{\n.reg .pred P;\nsetp.ne.u32 P, %2, 0;\n@P st.global.u32 [%0], %1;\n}" ::"l"(p), "r"(v), "r"((uint32_t)c) : "memory");
}
__device__ __forceinline__ uint32_t hmul2(uint32_t a, uint32_t b) { uint32_t d; asm("mul.rn.bf16x2 %0, %1, %2;" : "=r"(d) : "r"(a), "r"(b)); return d; }
__device__ __forceinline__ void sts32(uint32_t a, uint32_t v) { asm volatile("st.shared.u32 [%0], %1;" ::"r"(a), "r"(v) : "memory"); }
__device__ __forceinline__ uint32_t lds32(uint32_t a) { uint32_t v; asm volatile("ld.shared.u32 %0, [%1];" : "=r"(v) : "r"(a) : "memory"); return v; }
__device__ __forceinline__ void sts128(uint32_t a, uint32_t x, uint32_t y, uint32_t z, uint32_t w) { asm volatile("st.shared.v4.u32 [%0], {%1,%2,%3,%4};" ::"r"(a), "r"(x), "r"(y), "r"(z), "r"(w) : "memory"); }
__device__ __forceinline__ uint4 lds128(uint32_t a) { uint4 v; asm volatile("ld.shared.v4.u32 {%0,%1,%2,%3}, [%4];" : "=r"(v.x), "=r"(v.y), "=r"(v.z), "=r"(v.w) : "r"(a) : "memory"); return v; }
__device__ __forceinline__ void ll_st64(uint2* p, uint32_t v, uint32_t tag) {
  asm volatile("{\n.reg .b64 r;\nmov.b64 r, {%1,%2};\nst.relaxed.gpu.global.b64 [%0], r;\n}" ::"l"(p), "r"(v), "r"(tag) : "memory");
}
__device__ __forceinline__ uint2 ll_ld64(const uint2* p) {
  uint2 v; asm volatile("{\n.reg .b64 r;\nld.relaxed.gpu.global.b64 r, [%2];\nmov.b64 {%0,%1}, r;\n}" : "=r"(v.x), "=r"(v.y) : "l"(p) : "memory"); return v;
}
__device__ __forceinline__ void ll_st128(uint4* p, float a, float b, uint32_t tag, float c = 0.f) {
  asm volatile("{\n.reg .b128 r;\n.reg .b64 lo, hi;\nmov.b64 lo, {%1,%2};\nmov.b64 hi, {%3,%4};\nmov.b128 r, {lo, hi};\nst.relaxed.gpu.global.b128 [%0], r;\n}" ::"l"(p), "r"(__float_as_uint(a)), "r"(__float_as_uint(b)), "r"(tag), "r"(__float_as_uint(c)) : "memory");
}
__device__ __forceinline__ uint4 ll_ld128(const uint4* p) {
  uint4 v; asm volatile("{\n.reg .b128 r;\n.reg .b64 lo, hi;\nld.relaxed.gpu.global.b128 r, [%4];\nmov.b128 {lo, hi}, r;\nmov.b64 {%0,%1}, lo;\nmov.b64 {%2,%3}, hi;\n}" : "=r"(v.x), "=r"(v.y), "=r"(v.z), "=r"(v.w) : "l"(p) : "memory"); return v;
}
__device__ __forceinline__ void publish_p(uint32_t el, uint32_t* f) {
  asm volatile("{\n.reg .pred P;\nsetp.ne.u32 P, %1, 0;\n@P cp.async.bulk.commit_group;\n@P cp.async.bulk.wait_group 0;\n@P red.release.gpu.global.add.u32 [%0], 1;\n}" ::"l"(f), "r"(el) : "memory");
}
__device__ __forceinline__ void tma3d_red_p(uint32_t el, const CUtensorMap* m, int c0, int c1, int c2, uint32_t src) {
  asm volatile("{\n.reg .pred P;\nsetp.ne.u32 P, %5, 0;\n@P cp.reduce.async.bulk.tensor.3d.global.shared::cta.add.tile.bulk_group [%0, {%2, %3, %4}], [%1];\n@P cp.async.bulk.commit_group;\n}" ::"l"(m), "r"(src), "r"(c0), "r"(c1), "r"(c2), "r"(el) : "memory");
}
__device__ __forceinline__ void stsm4(uint32_t addr, uint32_t a, uint32_t b, uint32_t c, uint32_t d) {
  asm volatile("stmatrix.sync.aligned.m8n8.x4.shared.b16 [%0], {%1,%2,%3,%4};" ::"r"(addr), "r"(a), "r"(b), "r"(c), "r"(d) : "memory");
}
__device__ __forceinline__ void sts64(uint32_t a, uint32_t x, uint32_t y) { asm volatile("st.shared.v2.u32 [%0], {%1,%2};" ::"r"(a), "r"(x), "r"(y) : "memory"); }
__device__ __forceinline__ void ll_st128_if(bool on, uint4* p, float a, float b, uint32_t tag) {
  asm volatile("{\n.reg .pred P;\n.reg .b128 r;\n.reg .b64 lo, hi;\nsetp.ne.u32 P, %4, 0;\nmov.b64 lo, {%1,%2};\nmov.b64 hi, {%3,%3};\nmov.b128 r, {lo, hi};\n@P st.relaxed.gpu.global.b128 [%0], r;\n}" ::"l"(p), "r"(__float_as_uint(a)), "r"(__float_as_uint(b)), "r"(tag), "r"((uint32_t)on) : "memory");
}
__device__ __forceinline__ uint4 ldnc128_if(bool c, const void* p) {
  uint4 v = make_uint4(0u, 0u, 0u, 0u);
  asm volatile("{\n.reg .pred P;\nsetp.ne.u32 P, %5, 0;\n@P ld.global.nc.v4.u32 {%0,%1,%2,%3}, [%4];\n}" : "+r"(v.x), "+r"(v.y), "+r"(v.z), "+r"(v.w) : "l"(p), "r"((uint32_t)c));
  return v;
}
__device__ __forceinline__ uint32_t hfma2(uint32_t a, uint32_t b, uint32_t c) { uint32_t d; asm("fma.rn.bf16x2 %0, %1, %2, %3;" : "=r"(d) : "r"(a), "r"(b), "r"(c)); return d; }
__device__ __forceinline__ float2 lds64f(uint32_t a) { float2 v; asm volatile("ld.shared.v2.f32 {%0,%1}, [%2];" : "=f"(v.x), "=f"(v.y) : "r"(a) : "memory"); return v; }
#define TRC(cond, role, idx) do {} while (0)
#define TRV(role, idx, v) do {} while (0)

#define ACLK_INIT do {} while (0)
#define ACLK(i) do {} while (0)
#define ACLK_OUT do {} while (0)
#define QCLK(i) do {} while (0)
#define PH 1
#define RCLK(i) do {} while (0)
#define RCLK_INIT do {} while (0)
#define RCLK_OUT do {} while (0)
#define SCLK(i) do {} while (0)
#define HCLK(i) do {} while (0)
#define MCLK(c, i) do {} while (0)
#define CKK(i) do {} while (0)
#define CKK_OUT do {} while (0)
#define PL 1
#define PCLK(i) do {} while (0)
#define PQ 1
#define CLK_INIT do {} while (0)
#define CLK(i) do {} while (0)
#define CLK_OUT do {} while (0)

__device__ __forceinline__ void wgmma_ss_n216(float* d, uint64_t da, uint64_t db, int scaleD) {
  asm volatile("{\n.reg .pred p;\nsetp.ne.b32 p, %110, 0;\nwgmma.mma_async.sync.aligned.m64n216k16.f32.bf16.bf16 "
    "{%0,%1,%2,%3,%4,%5,%6,%7,%8,%9,%10,%11,%12,%13,%14,%15,%16,%17,%18,%19,%20,%21,%22,%23,%24,%25,%26,%27,%28,%29,%30,%31,%32,%33,%34,%35,%36,%37,%38,%39,%40,%41,%42,%43,%44,%45,%46,%47,%48,%49,%50,%51,%52,%53,%54,%55,%56,%57,%58,%59,%60,%61,%62,%63,%64,%65,%66,%67,%68,%69,%70,%71,%72,%73,%74,%75,%76,%77,%78,%79,%80,%81,%82,%83,%84,%85,%86,%87,%88,%89,%90,%91,%92,%93,%94,%95,%96,%97,%98,%99,%100,%101,%102,%103,%104,%105,%106,%107}, "
    "%108, %109, p, 1, 1, 0, 1;\n}\n"
    : "+f"(d[0]), "+f"(d[1]), "+f"(d[2]), "+f"(d[3]), "+f"(d[4]), "+f"(d[5]), "+f"(d[6]), "+f"(d[7]), "+f"(d[8]), "+f"(d[9]), "+f"(d[10]), "+f"(d[11]), "+f"(d[12]), "+f"(d[13]), "+f"(d[14]), "+f"(d[15]), "+f"(d[16]), "+f"(d[17]), "+f"(d[18]), "+f"(d[19]), "+f"(d[20]), "+f"(d[21]), "+f"(d[22]), "+f"(d[23]), "+f"(d[24]), "+f"(d[25]), "+f"(d[26]), "+f"(d[27]), "+f"(d[28]), "+f"(d[29]), "+f"(d[30]), "+f"(d[31]), "+f"(d[32]), "+f"(d[33]), "+f"(d[34]), "+f"(d[35]), "+f"(d[36]), "+f"(d[37]), "+f"(d[38]), "+f"(d[39]), "+f"(d[40]), "+f"(d[41]), "+f"(d[42]), "+f"(d[43]), "+f"(d[44]), "+f"(d[45]), "+f"(d[46]), "+f"(d[47]), "+f"(d[48]), "+f"(d[49]), "+f"(d[50]), "+f"(d[51]), "+f"(d[52]), "+f"(d[53]), "+f"(d[54]), "+f"(d[55]), "+f"(d[56]), "+f"(d[57]), "+f"(d[58]), "+f"(d[59]), "+f"(d[60]), "+f"(d[61]), "+f"(d[62]), "+f"(d[63]), "+f"(d[64]), "+f"(d[65]), "+f"(d[66]), "+f"(d[67]), "+f"(d[68]), "+f"(d[69]), "+f"(d[70]), "+f"(d[71]), "+f"(d[72]), "+f"(d[73]), "+f"(d[74]), "+f"(d[75]), "+f"(d[76]), "+f"(d[77]), "+f"(d[78]), "+f"(d[79]), "+f"(d[80]), "+f"(d[81]), "+f"(d[82]), "+f"(d[83]), "+f"(d[84]), "+f"(d[85]), "+f"(d[86]), "+f"(d[87]), "+f"(d[88]), "+f"(d[89]), "+f"(d[90]), "+f"(d[91]), "+f"(d[92]), "+f"(d[93]), "+f"(d[94]), "+f"(d[95]), "+f"(d[96]), "+f"(d[97]), "+f"(d[98]), "+f"(d[99]), "+f"(d[100]), "+f"(d[101]), "+f"(d[102]), "+f"(d[103]), "+f"(d[104]), "+f"(d[105]), "+f"(d[106]), "+f"(d[107])
    : "l"(da), "l"(db), "r"(scaleD));
}
__device__ __forceinline__ void wgmma_ss_n72(float* d, uint64_t da, uint64_t db, int scaleD) {
  asm volatile("{\n.reg .pred p;\nsetp.ne.b32 p, %38, 0;\nwgmma.mma_async.sync.aligned.m64n72k16.f32.bf16.bf16 "
    "{%0,%1,%2,%3,%4,%5,%6,%7,%8,%9,%10,%11,%12,%13,%14,%15,%16,%17,%18,%19,%20,%21,%22,%23,%24,%25,%26,%27,%28,%29,%30,%31,%32,%33,%34,%35}, "
    "%36, %37, p, 1, 1, 0, 1;\n}\n"
    : "+f"(d[0]), "+f"(d[1]), "+f"(d[2]), "+f"(d[3]), "+f"(d[4]), "+f"(d[5]), "+f"(d[6]), "+f"(d[7]), "+f"(d[8]), "+f"(d[9]), "+f"(d[10]), "+f"(d[11]), "+f"(d[12]), "+f"(d[13]), "+f"(d[14]), "+f"(d[15]), "+f"(d[16]), "+f"(d[17]), "+f"(d[18]), "+f"(d[19]), "+f"(d[20]), "+f"(d[21]), "+f"(d[22]), "+f"(d[23]), "+f"(d[24]), "+f"(d[25]), "+f"(d[26]), "+f"(d[27]), "+f"(d[28]), "+f"(d[29]), "+f"(d[30]), "+f"(d[31]), "+f"(d[32]), "+f"(d[33]), "+f"(d[34]), "+f"(d[35])
    : "l"(da), "l"(db), "r"(scaleD));
}
__device__ __forceinline__ void wgmma_rs_n144(float* d, const uint32_t* a, uint64_t db, int scaleD) {
  asm volatile("{\n.reg .pred p;\nsetp.ne.b32 p, %77, 0;\nwgmma.mma_async.sync.aligned.m64n144k16.f32.bf16.bf16 "
    "{%0,%1,%2,%3,%4,%5,%6,%7,%8,%9,%10,%11,%12,%13,%14,%15,%16,%17,%18,%19,%20,%21,%22,%23,%24,%25,%26,%27,%28,%29,%30,%31,%32,%33,%34,%35,%36,%37,%38,%39,%40,%41,%42,%43,%44,%45,%46,%47,%48,%49,%50,%51,%52,%53,%54,%55,%56,%57,%58,%59,%60,%61,%62,%63,%64,%65,%66,%67,%68,%69,%70,%71}, "
    "{%72,%73,%74,%75}, %76, p, 1, 1, 1;\n}\n"
    : "+f"(d[0]), "+f"(d[1]), "+f"(d[2]), "+f"(d[3]), "+f"(d[4]), "+f"(d[5]), "+f"(d[6]), "+f"(d[7]), "+f"(d[8]), "+f"(d[9]), "+f"(d[10]), "+f"(d[11]), "+f"(d[12]), "+f"(d[13]), "+f"(d[14]), "+f"(d[15]), "+f"(d[16]), "+f"(d[17]), "+f"(d[18]), "+f"(d[19]), "+f"(d[20]), "+f"(d[21]), "+f"(d[22]), "+f"(d[23]), "+f"(d[24]), "+f"(d[25]), "+f"(d[26]), "+f"(d[27]), "+f"(d[28]), "+f"(d[29]), "+f"(d[30]), "+f"(d[31]), "+f"(d[32]), "+f"(d[33]), "+f"(d[34]), "+f"(d[35]), "+f"(d[36]), "+f"(d[37]), "+f"(d[38]), "+f"(d[39]), "+f"(d[40]), "+f"(d[41]), "+f"(d[42]), "+f"(d[43]), "+f"(d[44]), "+f"(d[45]), "+f"(d[46]), "+f"(d[47]), "+f"(d[48]), "+f"(d[49]), "+f"(d[50]), "+f"(d[51]), "+f"(d[52]), "+f"(d[53]), "+f"(d[54]), "+f"(d[55]), "+f"(d[56]), "+f"(d[57]), "+f"(d[58]), "+f"(d[59]), "+f"(d[60]), "+f"(d[61]), "+f"(d[62]), "+f"(d[63]), "+f"(d[64]), "+f"(d[65]), "+f"(d[66]), "+f"(d[67]), "+f"(d[68]), "+f"(d[69]), "+f"(d[70]), "+f"(d[71])
    : "r"(a[0]), "r"(a[1]), "r"(a[2]), "r"(a[3]), "l"(db), "r"(scaleD));
}
__device__ __forceinline__ void wgmma_rs_n64(float* d, const uint32_t* a, uint64_t db, int scaleD) {
  asm volatile("{\n.reg .pred p;\nsetp.ne.b32 p, %37, 0;\nwgmma.mma_async.sync.aligned.m64n64k16.f32.bf16.bf16 "
    "{%0,%1,%2,%3,%4,%5,%6,%7,%8,%9,%10,%11,%12,%13,%14,%15,%16,%17,%18,%19,%20,%21,%22,%23,%24,%25,%26,%27,%28,%29,%30,%31}, "
    "{%32,%33,%34,%35}, %36, p, 1, 1, 1;\n}\n"
    : "+f"(d[0]), "+f"(d[1]), "+f"(d[2]), "+f"(d[3]), "+f"(d[4]), "+f"(d[5]), "+f"(d[6]), "+f"(d[7]), "+f"(d[8]), "+f"(d[9]), "+f"(d[10]), "+f"(d[11]), "+f"(d[12]), "+f"(d[13]), "+f"(d[14]), "+f"(d[15]), "+f"(d[16]), "+f"(d[17]), "+f"(d[18]), "+f"(d[19]), "+f"(d[20]), "+f"(d[21]), "+f"(d[22]), "+f"(d[23]), "+f"(d[24]), "+f"(d[25]), "+f"(d[26]), "+f"(d[27]), "+f"(d[28]), "+f"(d[29]), "+f"(d[30]), "+f"(d[31])
    : "r"(a[0]), "r"(a[1]), "r"(a[2]), "r"(a[3]), "l"(db), "r"(scaleD));
}

template <int V> struct Int { static constexpr int value = V; };
struct Cur {
  uint32_t s, ph;
  __device__ __forceinline__ void next() { if (++s == NST) { s = 0; ph ^= 1; } }
};

__device__ __forceinline__ uint8_t* z1_block(int rb, int w, int j) { return g_Z + (rb * 16 + w * 8 + j) * ZB; }
__device__ __forceinline__ uint8_t* o_block(int rb, int w) { return g_O + (rb * 2 + w) * (2 * ZB); }
__device__ __forceinline__ uint8_t* z2_block(int kb, int j) { return g_Z + (256 + kb * 8 + j) * ZB; }
__device__ __forceinline__ void combine8(float m0, float q0, float m1, float q1, float n, float eps, float& mean, float& rstd) {
  mean = qsum(m0 + m1) * 0.125f;
  float d0 = m0 - mean, d1 = m1 - mean;
  float M2 = qsum(q0 + q1 + n * (d0 * d0 + d1 * d1));
  rstd = rsqrtf(fmaf(M2, 0.125f / n, eps));
}
__device__ __forceinline__ void stat_get(const uint4* zs, uint32_t tag, float n, float eps, float& m0, float& r0, float& m1, float& r1) {
  uint4 a0, a1, b0, b1;
#pragma unroll 1
  for (int it = 0; it < (1 << 20); it++) {
    a0 = ll_ld128(zs); a1 = ll_ld128(zs + 64); b0 = ll_ld128(zs + 8); b1 = ll_ld128(zs + 72);
    if (__all_sync(~0u, a0.z == tag && a1.z == tag && b0.z == tag && b1.z == tag)) break;
  }
  combine8(__uint_as_float(a0.x), __uint_as_float(a0.y), __uint_as_float(a1.x), __uint_as_float(a1.y), n, eps, m0, r0);
  combine8(__uint_as_float(b0.x), __uint_as_float(b0.y), __uint_as_float(b1.x), __uint_as_float(b1.y), n, eps, m1, r1);
}

__device__ __forceinline__ void rows_fetch(uint32_t el, uint32_t xr, const uint8_t* src, uint32_t bar) {
  expect_tx_p(el, bar, 9216);
#pragma unroll 1
  for (int r = 0; r < 8; r++) bulk_load_p(el, xr + r * 1152, src + r * (DM * 4), 1152, bar);
}
__device__ __forceinline__ void rows_stats(uint32_t xr, uint4* dst, uint32_t tag, int lane) {
  float s[2] = {0.f, 0.f}, q[4] = {0.f, 0.f, 0.f, 0.f};
  const uint32_t a0 = xr + (lane >> 2) * 1152 + (((lane & 3) * 2) ^ (lane >> 2)) * 16;
  uint4 n0 = lds128(a0), n1 = lds128(a0 ^ 16);
#pragma unroll 1
  for (int e = 1; e <= 9; e++) {
    const uint32_t x[8] = {n0.x, n0.y, n0.z, n0.w, n1.x, n1.y, n1.z, n1.w};
    if (e < 9) { n0 = lds128(a0 + e * 128); n1 = lds128((a0 ^ 16) + e * 128); }
#pragma unroll
    for (int u = 0; u < 8; u++) {
      const float lo = blo(x[u]), hi = bhi(x[u]);
      s[u & 1] += lo + hi; q[(u & 1) * 2] = fmaf(lo, lo, q[(u & 1) * 2]); q[(u & 1) * 2 + 1] = fmaf(hi, hi, q[(u & 1) * 2 + 1]);
    }
  }
  const float sx = s[0] + s[1], sq = (q[0] + q[1]) + (q[2] + q[3]);
  const float m = qsum(sx) * (-1.f / DM), r = rsqrtf(fmaxf(fmaf(qsum(sq), 1.f / DM, -m * m), 0.f) + LN_EPS);
  if ((lane & 3) == 0) ll_st128(dst + (lane >> 2) * 2, m, r, tag);
}

__device__ __forceinline__ void poison(uint32_t el, uint32_t src, const CUtensorMap* m, int rb, int j, int lane) {
#pragma unroll 1
  for (int u = lane; u < 72; u += 32) sts128(src + u * 16, POISON, POISON, POISON, POISON);
  fence_async_s();
  __syncwarp();
#pragma unroll 1
  for (int u = 0; u < 16; u++) {
    __nanosleep(NAP);
    bulk_store_p(el, o_block(rb, u >> 3) + j * 9216 + (u & 7) * 1152, src, 1152);
    asm volatile("{\n.reg .pred P;\nsetp.ne.u32 P, %5, 0;\n@P cp.async.bulk.tensor.3d.global.shared::cta.tile.bulk_group [%0, {%2, %3, %4}], [%1];\n}" ::"l"(m), "r"(src), "r"((j & 6) * 72), "r"(rb * 64 + u * 4), "r"(j & 1), "r"(el) : "memory");
  }
}
__device__ __forceinline__ void mma16acc(float* c, const uint32_t* a, uint32_t b0, uint32_t b1) {
  asm volatile("mma.sync.aligned.m16n8k16.row.col.f32.bf16.bf16.f32 {%0,%1,%2,%3}, {%4,%5,%6,%7}, {%8,%9}, {%0,%1,%2,%3};"
               : "+f"(c[0]), "+f"(c[1]), "+f"(c[2]), "+f"(c[3]) : "r"(a[0]), "r"(a[1]), "r"(a[2]), "r"(a[3]), "r"(b0), "r"(b1));
}
template <int KS, int NG, int AK, int AH, int BK, int BG, class F> __device__ __forceinline__ void redo(float* acc, const uint8_t* pa, const uint8_t* pb, F f) {
#pragma unroll 1
  for (int k = 0; k < 36; k += KS) {
    uint32_t a[4 * KS], b[2 * KS][NG];
#pragma unroll 1
    for (int it = 0; it < (1 << 20); it++) {
      bool ok = true;
#pragma unroll
      for (int e = 0; e < 4 * KS; e++) a[e] = ldgpu32(pa + (e >> 1) * AK + (e & 1) * AH);
#pragma unroll
      for (int e = 0; e < 2 * KS * NG; e++) b[e / NG][e % NG] = ldca32(pb + (e / NG) * BK + (e % NG) * BG);
#pragma unroll
      for (int e = 0; e < 4 * KS; e++) ok = ok && a[e] != POISON;
      if (__all_sync(~0u, ok)) break;
    }
#pragma unroll
    for (int e = 0; e < KS; e++) f(a + 4 * e, k + e);
#pragma unroll
    for (int e = 0; e < KS * NG; e++) mma16acc(acc + 4 * (e % NG), a + 4 * (e / NG), movm(b[2 * (e / NG)][e % NG]), movm(b[2 * (e / NG) + 1][e % NG]));
    pa += 2 * KS * AK; pb += 2 * KS * BK;
  }
}
__device__ __forceinline__ bool any_nan(float a, float b) {
  return __any_sync(~0u, a != a || b != b);
}

__global__ void __cluster_dims__(2, 1, 1) __launch_bounds__(384, 1) mega_kernel(const __grid_constant__ Params P) {
  extern __shared__ __align__(1024) uint8_t smem_raw[];
  uint32_t ckk[8];
  (void)ckk;
  CKK(0);
  const uint32_t sb = smem_u32(smem_raw);
  const uint32_t bars = sb + SM_BAR;
  const int tid = threadIdx.x;
  int lane = tid & 31;
  const int wid = __shfl_sync(~0u, tid >> 5, 0);
  const int cl = blockIdx.x >> 1, tp = cl - 36, t7 = (tp * 37) >> 8;
  const int bid = (cl < 4 ? cl * 8 + 32 : tp < 0 ? cl - 4 : cl < 64 ? tp + t7 + 33 : cl) * 2 + (blockIdx.x & 1);
  if (bid >= NCTA) return;
  const int rb = bid & 15, j = bid >> 4;
  { const bool tr = (tid & 127) == 0 && tid < 256; const int w = tid >> 7; (void)tr; (void)w; TRC(tr, w, 0); }
  CKK(1);
  uint4 wv[5];
  const uint8_t* wsrc;
  {
    const int n8 = min(tid >> 3, 26), part = n8 / 9;
    const uint8_t* src = (const uint8_t*)P.wqkv + (8 * rb + (tid & 7)) * (3 * DM * 2) + (part * (DM - 72) + 72 * j + 8 * n8) * 2;
#pragma unroll
    for (int u = 0; u < SPL; u++) wv[u] = ldnc128_if(tid < 216, src + u * (128 * 3 * DM * 2));
    wsrc = src;
  }
  CKK(2);
  if (tid == 352) {
    for (int s = 0; s < (int)NST; s++) {
      mbar_init(bars + B_FULL + s * 8, 1); mbar_init(bars + B_EMPTY + s * 8, 16);
      mbar_init(bars + B_FULLA + s * 8, 1); mbar_init(bars + B_FULLA + 32 + s * 8, 1);
      mbar_init(bars + B_RES + s * 8, 1); mbar_init(bars + B_RT + s * 8, 1); mbar_init(bars + B_AD + s * 8, 2);
    }
    mbar_init(bars + B_IMG, 8); mbar_init(bars + B_RES + 8, 8); mbar_init(bars + B_WOI, 1); mbar_init(bars + B_GATE3, 3); mbar_init(bars + B_Z1, 1); mbar_init(bars + B_ZB, 1); mbar_init(bars + B_LAG, 4);
    mbar_init(bars + B_XS, 1); mbar_init(bars + B_XS + 8, 1); mbar_init(bars + B_RT1, 1); mbar_init(bars + B_XRW, 1); mbar_init(bars + B_XRW + 8, 1);
    for (int e = 0; e < 2 * EV_N; e++) mbar_init(bars + B_EVT + e * 8, 4);
    asm volatile("fence.mbarrier_init.release.cluster;" ::: "memory");
  }
  if (tid == 320) {
#pragma unroll
    for (int e = 0; e < 28; e++) mbar_init(bars + B_FA3 + e * 8, e < 18 ? 1 : 4);
    asm volatile("fence.mbarrier_init.release.cluster;" ::: "memory");
  }
  __syncthreads();

  if (wid >= 8) {
    reg_dealloc<40>();
    const uint32_t el = elect_one();
    const uint64_t pol = policy_evict_first();
    uint32_t* const fj = g_flags + FJ + j * 32;
    if (wid == 8) {
#pragma unroll 1
      for (int i = 0; i < 12; i++) if (el) prefetch_map(&P.act[0] + (i < 7 ? i : i - 12));
      const uint32_t epoch = ldcg32(fj + FJ_EP + rb);
      Cur c{0, 1};
      const uint32_t rk = bid & 1;
      uint32_t st, full;
      auto slot = [&](uint32_t bytes) {
        st = sb + c.s * ST_BYTES; full = bars + B_FULL + c.s * 8;
        mbar_wait(full, c.ph);
        expect_tx_p(el, full, bytes);
        mbar_wait(full - B_FULL + B_EMPTY, c.ph);
      };
#pragma unroll 1
      for (int L = 0; L < 2; L++) {
#pragma unroll 1
        for (int i = 0; i < 14; i++) {
          if (L == 0 && (i == 0 || i == 2 * SPL || i == 9)) {
            flag_wait(fj + (i == 9 ? FJ_WO : i == 2 * SPL ? FJ_WQ : FJ_WQ0), (epoch + 1) * 16);
            if (i == 9) flag_wait(g_flags + FJ + (j ^ 1) * 32 + FJ_WO, (epoch + 1) * 16);
            fence_async_g();
            TRC(el, 2, i == 9 ? 46 : i ? 47 : 45);
          }
          const uint32_t hb = i < 9 ? 13824 : i < 13 ? 18432 : 9216, o = ST_B + rk * (i < 9 ? 13824 : 18432);
          const uint8_t* src = i < 9 ? g_WQ + j * WQ_SL + i * 27648 + rk * 13824 : g_WO + ((j & 6) + rk) * WO_SL + (i - 9) * 18432;
          slot(2 * hb);
          bulk_mc_h(el, st + o, src, hb, full, true, pol);
          c.next();
        }
#pragma unroll 1
        for (int i = 0; i < 18; i++) {
          const int p = i >> 1, col = p == 4 ? (9 * j + ((j & 1) ? 0 : 8)) * 32 : (((9 * j + 1) >> 1) + (p < 4 ? p + 36 : p - 5)) * 64;
          if (i & 1) {
            slot(2 * ZB);
          } else {
            st = sb + c.s * ST_BYTES; full = bars + B_FULL + ((c.s + 1) & 3) * 8;
            mbar_wait(bars + B_EMPTY + c.s * 8, c.ph);
          }
          tma4d_mc(el, st + ST_B + rk * 18432, p == 4 ? &P.win : &P.win64, col, (i & 1) * 36 + rk * 18, full, pol);
          if (el && !(i & 1)) mbar_arrive(bars + B_FULL + c.s * 8);
          c.next();
        }
        TRC(el, 2, L * 16 + 6);
        flag_wait(fj + FJ_ZN + L, (epoch + 1) * 16);
        fence_async_g();
        TRC(el, 2, L * 16 + 7);
#pragma unroll 1
        for (int i = 0; i < 32; i++) {
          const uint8_t* src = z2_block(i, j) + rk * 18432;
          if (i >= 4) mbar_wait(bars + B_AD + c.s * 8, ((i >> 2) & 1) ^ 1);
          slot(ST_BYTES);
          bulk_mc_h(el, st + ST_B + rk * 18432, src, 18432, full, true, pol);
          tma3d_h(el, st, &P.wsp, i * 64, rb * 64, 0, full, true, pol);
          c.next();
        }
        mbar_wait(bars + B_Z1, L);
        fence_async_g();
        expect_tx_p(el, bars + B_ZB, 26624);
#pragma unroll 1
        for (int i = 0; i < 10; i++) {
          const int cb = i - 1 + j;
          if (i < 4) mbar_wait(bars + B_AD + c.s * 8, 1);
          slot(i ? ZB : 26624);
          if (i == 0) {
            bulk_load_h(el, st, z1_block(rb, 0, j), 26624, bars + B_ZB, true, pol);
            bulk_load_h(el, st + 26624, z1_block(rb, 1, j), 26624, full, true, pol);
          } else {
            tma2d_mc_h(el, st + ST_B + rk * 18432, &P.wout, (cb >= 9 ? cb - 9 : cb) * 64, 288 * j + rk * 144, full, true, pol);
          }
          c.next();
        }
      }
    } else if (wid < 11) {
      int w = wid - 9;
      uint32_t* const fr = g_flags + (rb * 2 + w) * 32;
      const uint32_t epoch = ldcg32(fr + FR_EP + j);
      const uint32_t ev = bars + B_EVT + w * EV_N * 8, t8 = (epoch + 1) * 8;
      Cur c{0, 1};
#pragma unroll 1
      for (int L = 0; L < 2; L++) {
        {
          const uint32_t tag = epoch * 2 + L + 1;
          uint4* const xs = g_XST + (rb * 2 + w) * 128;
          if (L) {
            mbar_wait(ev + EV_PT * 8, 0);
            TRC(el, 3, w * 32 + 16);
            flag_release_p(el, fr + FR_X2);
            TRC(el, 3, w * 32 + 17);
          }
#pragma unroll 1
          for (int i = 0; i < 9; i++) {
            const uint32_t full = bars + B_FULLA + w * 32 + c.s * 8, dst = sb + c.s * ST_BYTES + w * 8192;
            if (L == 0 && i == 4) {
              mbar_wait(bars + B_WT + w * 8, 0);
              TRC(el && w == 0, 2, 37);
              rows_stats(sb + SM_STG + w * 9216, xs + 16 * j, tag, lane);
              TRC(el && w == 0, 2, 38);
            }
            const uint32_t src = sb + (L ? 2 * ST_BYTES + SM_WOI : SM_STG + w * 9216);
            if (i == 4) {
#pragma unroll
              for (int u = 0; u < 6; u++) sts128(src + u * 512 + lane * 16, POISON, POISON, POISON, POISON);
              fence_async_s();
              __syncwarp();
            }
            mbar_wait(bars + B_EMPTY + c.s * 8, c.ph);
            expect_tx_p(el, full, 8192);
            if (i < L) { flag_wait(fr + FR_X2, t8); fence_async_g(); }
            tma3d_h(el, dst, &P.act[L], i * 64, rb * 64, w, full, false, pol);
            TRC(el && i < L, 3, w * 32 + 18);
            c.next();
            if (i >= 4 && i < (L ? 5 : 8)) {
              int b = (rb * 2 + w) * 8 + j;
              asm volatile("" : "+r"(b));
              bulk_store_p(el, i == 4 ? (uint8_t*)g_HALO + b * 3072 : g_O + (b * 3 + i - 5) * 3072, src, 3072);
              if (i < 6) bulk_store_p(el, (i == 4 ? g_ST1 : g_ZST) + b * 64, src, 1024);
              if (i == 6) bulk_store_p(el, g_RT + b * 8, src, 64);
            }
            if (L == 0 && i == 3) rows_fetch(el, sb + SM_STG + w * 9216, P.xs[0] + (128 * rb + 16 * j + w) * (DM * 2), bars + B_WT + w * 8);
          }
          if (el) asm volatile("cp.async.bulk.commit_group;\ncp.async.bulk.wait_group 0;" ::: "memory");
          __syncwarp();
          if (L == 0) fence_gpu();
          const uint32_t tab = sb + L * (2 * ST_BYTES) + SM_XST + w * 512 + lane * 8;
          TRC(el, 3, w * 32 + L * 16 + 13);
#pragma unroll 1
          for (int it = 0; it < (1 << 22); it++) {
            const uint4 a = ll_ld128(xs + 2 * lane), b = ll_ld128(xs + 64 + 2 * lane);
            if (__all_sync(~0u, a.z == tag && b.z == tag)) { sts64(tab, a.x, a.y); sts64(tab + 256, b.x, b.y); break; }
          }
          __syncwarp();
          mbar_arrive_if(el, bars + B_XS + w * 8);
          TRC(el, 3, w * 32 + L * 16 + 14);
          if (w == 1) {
            mbar_wait(bars + B_XS, L);
            expect_tx_p(el, bars + B_RES, 18432);
            tma3d_h(el, sb + SM_STG, &P.res[L], (j & 6) * 72, rb * 64, j & 1, bars + B_RES, !L, pol);
          }
          if (L) flag_wait(fj + FJ_P4, t8 * 4);
        }
        asm volatile("" : "+r"(w));
        uint32_t* const fo = g_flags + (rb * 2 + (j & 1)) * 32 + L;
        {
          const uint8_t* src = o_block(rb, j & 1) + w * 8192;
#pragma unroll 1
          for (int i = 0; i < 5; i++) {
            const uint32_t full = bars + B_FULLA + w * 32 + c.s * 8, dst = sb + c.s * ST_BYTES + w * 8192;
            const bool none = 2 * i + w > 8;
            mbar_wait(bars + B_EMPTY + c.s * 8, c.ph);
            expect_tx_p(el, full, none ? 0 : 8192);
            if (i == 0) {
              mbar_wait(ev + EV_O * 8, L);
              TRC(el, 3, w * 32 + L * 16 + 3);
              flag_add_p(el, fr + FR_O + L);
              TRC(el, 3, w * 32 + L * 16 + 4);
              flag_wait(fo + FR_O, t8);
              fence_async_g();
            }
            if (!none) bulk_load_h(el, dst, src + i * 16384, 8192, full, true, pol);
            TRC(el && i == 0, 3, w * 32 + L * 16 + 5);
            c.next();
          }
        }
        {
          expect_tx_p(lane < 9, bars + B_FA3 + (9 * w + lane) * 8, 8192);
          mbar_wait(ev + EV_X1 * 8, L);
          TRC(el, 3, w * 32 + L * 16 + 6);
          if (L) flag_add_p(el, fo + FR_X1); else flag_release_p(el, fo + FR_X1);
          mbar_arrive_if(el, bars + B_GATE3);
          TRC(el, 3, w * 32 + L * 16 + 7);
          mbar_arrive_if(lane < 2, bars + B_FULLA + w * 32 + ((c.s + lane) & 3) * 8);
#pragma unroll 1
          for (int kb = 0; kb < 9; kb++) {
            const int n = 9 * w + kb;
            const uint32_t dst = sb + ((n >> 1) & 3) * ST_BYTES + (n & 1) * 8192;
            if (kb == 0) { flag_wait(fr + FR_X1 + L, t8); fence_async_g(); }
            if (n >= 8) mbar_wait(bars + B_EA3 + (n - 8) * 8, L);
            tma3d_h(el, dst, &P.act[L + 1], kb * 64, rb * 64, w, bars + B_FA3 + n * 8, false, pol);
            TRC(el && kb == 0, 3, w * 32 + L * 16 + 8);
          }
          c.ph ^= ((c.s + 18) >> 2) & 1; c.s = (c.s + 18) & 3;
        }
        asm volatile("" : "+r"(lane), "+r"(w));
        expect_tx_p(el, bars + B_WT + w * 8, 2048);
#pragma unroll 1
        for (int r = 0; r < 8; r++)
          bulk_load_p(el, sb + SM_WT + w * 2176 + r * 272, (const uint8_t*)P.w_sp + (size_t)(128 * rb + 16 * j + 2 * r + w) * (SEQ * 2) + 30 * 128, 256, bars + B_WT + w * 8);
        float cv = (lane & 3) ? 0.f : -blo(ldnc16(P.b_sp + 128 * rb + 16 * j + 2 * (lane >> 2) + w));
        mbar_wait(bars + B_RT, L);
        mbar_wait(bars + B_WT + w * 8, L ^ 1);
        mbar_wait(ev + EV_Z1 * 8, L);
        const uint32_t ro = (w * 64 + 8 * j + (lane >> 2)) * 128, x0 = ((lane & 3) * 2) ^ (lane >> 2);
#pragma unroll 1
        for (int i = 0; i < 32; i++) {
          const bool tail = (i >> 1) == 4;
          const int kb = tail ? i + 22 : i < 8 ? i : i - 2;
          if (i == 8) mbar_wait(bars + B_RT1, L);
          if (!tail) mbar_wait(bars + B_FULL + c.s * 8, c.ph ^ 1);
#pragma unroll
          for (int e = 0; e < 2; e++) {
            const uint4 a = lds128(!tail ? sb + c.s * ST_BYTES + ro + ((x0 ^ e) << 4) : sb + SM_WT + w * 2176 + (lane >> 2) * 272 + (i - 8) * 128 + (lane & 3) * 32 + e * 16);
            const uint4 m = lds128(sb + SM_RT + 4096 + kb * 128 + (lane & 3) * 32 + e * 16);
            cv = fmaf(blo(a.x), blo(m.x), fmaf(bhi(a.x), bhi(m.x), fmaf(blo(a.y), blo(m.y), fmaf(bhi(a.y), bhi(m.y), cv))));
            cv = fmaf(blo(a.z), blo(m.z), fmaf(bhi(a.z), bhi(m.z), fmaf(blo(a.w), blo(m.w), fmaf(bhi(a.w), bhi(m.w), cv))));
          }
          if (!tail) {
            mbar_arrive_if(el, bars + B_AD + c.s * 8 + (__float_as_uint(cv) & P.zero));
            c.next();
          }
        }
        TRC(el, 3, w * 32 + L * 16 + 11);
        uint32_t tag = t8;
        asm volatile("" : "+r"(tag));
        tag = (tag >> 2) - 1 + L;
        cv = qsum(cv);
        uint2* const cs = (uint2*)(g_XST + (rb * 2 + w) * 128 + 1);
        if ((lane & 3) == 0) ll_st64(cs + 32 * j + (lane >> 2) * 4, __float_as_uint(cv), tag);
#pragma unroll 1
        for (int it = 0; it < (1 << 22); it++) {
          const uint2 a = ll_ld64(cs + 4 * lane), b = ll_ld64(cs + 128 + 4 * lane);
          if (__all_sync(~0u, a.y == tag && b.y == tag)) { sts32(sb + SM_CV + w * 256 + lane * 4, a.x); sts32(sb + SM_CV + w * 256 + 128 + lane * 4, b.x); break; }
        }
        __syncwarp();
        if (el) mbar_arrive(bars + B_CV + w * 8);
        TRC(el, 3, w * 32 + L * 16 + 12);
#pragma unroll 1
        for (int kb = 30; kb < 32; kb++) {
          mbar_wait(bars + B_FULL + c.s * 8, c.ph ^ 1);
          if (el) mbar_arrive(bars + B_AD + c.s * 8);
          c.next();
        }
        c.ph ^= ((c.s + 10) >> 2) & 1; c.s = (c.s + 10) & 3;
        if (L == 0) {
          mbar_wait(ev + EV_P4 * 8, 0);
          flag_add_p(el, fj + FJ_P4);
        }
      }
    } else {
      const uint32_t epoch = ldcg32(fj + FJ_EP + rb);
      if (SPL) {
        mbar_wait(bars + B_RES + 8, 0);
        TRC(el, 2, 41);
        flag_release_p(el, fj + FJ_WQ0);
        TRC(el, 2, 42);
      }
      mbar_wait(bars + B_IMG, 0);
      TRC(el, 2, 39);
      flag_release_p(el, fj + FJ_WQ);
      TRC(el, 2, 40);
#pragma unroll 1
      for (int L = 0; L < 2; L++) {
        auto wo_fetch = [&]() {
          expect_tx_p(el, bars + B_WOI, 5760);
          asm volatile("{\n.reg .pred P;\nsetp.ne.u32 P, %5, 0;\n@P cp.async.bulk.tensor.4d.shared::cluster.global.mbarrier::complete_tx::bytes [%0], [%1, {0, 0, %3, %4}], [%2];\n}" ::"r"(sb + SM_WOI), "l"(&P.wo8), "r"(bars + B_WOI), "r"(9 * j), "r"((9 * rb) >> 1), "r"(el) : "memory");
        };
        float* const csf = g_CSP + (NCTA + bid) * 216;
        if (L == 0) {
          flag_wait(fj + FJ_WQ, (epoch + 1) * 16);
          fence_async_g();
          expect_tx_p(el, bars + B_XRW, 13824);
          bulk_load_p(el, sb + ST_BYTES + SM_WOI, g_CSP + j * 16 * 216, 6912, bars + B_XRW);
          bulk_load_p(el, sb + 2 * ST_BYTES + SM_WOI, g_CSP + (j * 16 + 8) * 216, 6912, bars + B_XRW);
          wo_fetch();
          mbar_wait(bars + B_XRW, 0);
#pragma unroll 1
          for (int f = lane; f < 54; f += 32) {
            float s[4] = {0.f, 0.f, 0.f, 0.f};
#pragma unroll 4
            for (int r = 0; r < 16; r++) {
              const uint4 v = lds128(sb + ST_BYTES + SM_WOI + (r >> 3) * ST_BYTES + (r & 7) * 864 + f * 16);
              s[0] += __uint_as_float(v.x); s[1] += __uint_as_float(v.y); s[2] += __uint_as_float(v.z); s[3] += __uint_as_float(v.w);
            }
            sts128(sb + SM_CSQ + f * 16, __float_as_uint(s[0]), __float_as_uint(s[1]), __float_as_uint(s[2]), __float_as_uint(s[3]));
            stg128(csf + f * 4, __float_as_uint(s[0]), __float_as_uint(s[1]), __float_as_uint(s[2]), __float_as_uint(s[3]));
          }
          __syncwarp();
          mbar_arrive_if(el, bars + B_CSQ);
        } else {
#pragma unroll 1
          for (int u = 0; u < 4; u++) {
            const int w = u & 1;
            if (u < 2) {
              flag_wait(g_flags + (rb * 2 + w) * 32 + FR_X2, (epoch + 1) * 8);
              fence_async_g();
              TRC(el, 2, 48 + u);
              rows_fetch(el, sb + SM_STG + w * 9216, P.xs[1] + (128 * rb + 16 * j + w) * (DM * 2), bars + B_XRW + w * 8);
            } else {
              if (u == 2) {
                expect_tx_p(el, bars + B_CSQ, 864);
                bulk_load_p(el, sb + 2 * ST_BYTES + SM_CSQ, csf, 864, bars + B_CSQ);
              }
              mbar_wait(bars + B_XRW + w * 8, w ^ 1);
              TRC(el, 2, 48 + u);
              rows_stats(sb + SM_STG + w * 9216, g_XST + (rb * 2 + w) * 128 + 16 * j, epoch * 2 + 2, lane);
              TRC(el, 2, 50 + u);
            }
          }
        }
        if (L == 0) {
          TRC(el, 2, 43);
          mbar_wait(bars + B_WOI, 0);
          bulk_store_p(el, g_WO + j * WO_SL + ((9 * rb) >> 1) * 1152, sb + SM_WOI, 5760);
          publish_p(el, fj + FJ_WO);
          TRC(el, 2, 44);
          const uint8_t* sp = lane < 16 ? (const uint8_t*)P.w_in + (30 * lane + 50) * (FH * 4) + FH * 2 + lane * 256 : (const uint8_t*)P.w_sp + (60 * lane) * (SEQ * 2) + lane * 64;
          float sq = 0.f;
#pragma unroll 1
          for (int u = 0; u < 4; u++) {
            const uint4 y = ldnc128(sp + u * 16);
            const uint32_t x[4] = {y.x, y.y, y.z, y.w};
#pragma unroll
            for (int e = 0; e < 4; e++) sq = fmaf(blo(x[e]), blo(x[e]), fmaf(bhi(x[e]), bhi(x[e]), sq));
          }
#pragma unroll 1
          for (int o = 8; o; o >>= 1) sq += __shfl_xor_sync(~0u, sq, o);
          sq *= lane < 16 ? 2.f * GA * GA * DM / 512.f : C0S * C0S * SEQ / 512.f;
          asm("sqrt.approx.f32 %0, %0;" : "+f"(sq));
          const float o0 = __shfl_sync(~0u, sq, 0), o1 = __shfl_sync(~0u, sq, 16);
          const float p2 = __uint_as_float(min(__float_as_uint(o0) & 0x7f800000u, 0x7e000000u)) * OFK, off = -p2 - fminf(OFA, 0.5f * p2);
          if (el) sts64(sb + SM_OFF, pack2(off, off), min(__float_as_uint(o1) & 0x7f800000u, 0x7e000000u) | 0x00400000u);
        }
        if (el) mbar_arrive(bars + B_GATE3);
        const uint32_t tag = epoch * 2 + L + 1;
        asm volatile("" : "+r"(lane));
        mbar_wait(bars + B_EVT + EV_ZN * 8, L);
        mbar_wait(bars + B_EVT + (EV_N + EV_ZN) * 8, L);
        flag_release_p(el, fj + FJ_ZN + L);
        TRC(el, 2, L * 16 + 8);
        {
          uint4 v[4];
#pragma unroll 1
          for (int it = 0; it < (1 << 22); it++) {
            bool ok = true;
#pragma unroll
            for (int u = 0; u < 4; u++) { v[u] = ll_ld128(g_ZST + (rb * 2 + ((lane >> 1) & 1)) * 512 + ((lane & 1) * 4 + u) * 64 + 8 * j + (lane >> 2)); ok = ok && v[u].z == tag; }
            if (__all_sync(~0u, ok)) break;
          }
          float mean = __uint_as_float(v[0].x) + __uint_as_float(v[1].x) + __uint_as_float(v[2].x) + __uint_as_float(v[3].x), M2 = 0.f;
          mean = (mean + __shfl_xor_sync(~0u, mean, 1)) * 0.125f;
#pragma unroll
          for (int u = 0; u < 4; u++) { const float d = __uint_as_float(v[u].x) - mean; M2 += fmaf(288.f * d, d, __uint_as_float(v[u].y)); }
          M2 += __shfl_xor_sync(~0u, M2, 1);
          const float rs = blo(pack2(rsqrtf(fmaf(M2, 1.f / FH, 4.f * GA * GA * LN_EPS)), 0.f));
          if (!(lane & 1)) ll_st64(g_RT + 128 * rb + 16 * j + (lane >> 1), pack2(rs, rs * mean), tag);
        }
        TRC(el, 2, L * 16 + 10);
#pragma unroll 1
        for (int b = 0; b < 8; b++) {
          uint4 v[4];
#pragma unroll 1
          for (int it = 0; it < (1 << 22); it++) {
            bool ok = true;
#pragma unroll
            for (int u = 0; u < 4; u++) { v[u] = ll_ld128((const uint4*)g_RT + b * 128 + u * 32 + lane); ok = ok && v[u].y == tag && v[u].w == tag; }
            if (__all_sync(~0u, ok)) break;
          }
#pragma unroll
          for (int u = 0; u < 4; u++) {
            const uint32_t rt = sb + SM_RT + b * 512 + u * 128, ro = (lane >> 3) * 32 + (lane & 3) * 8 + ((lane >> 2) & 1) * 2;
            sts32(rt + 4096 + lane * 4, __byte_perm(v[u].x, v[u].z, 0x7632));
            asm volatile("st.shared.u16 [%0], %1;\nst.shared.u16 [%0 + 4], %2;" ::"r"(rt + ro), "h"((uint16_t)v[u].x), "h"((uint16_t)v[u].z) : "memory");
          }
          __syncwarp();
          if (el && (b == 1 || b == 7)) mbar_arrive(bars + (b == 1 ? B_RT : B_RT1));
          TRC(el && b < 2, 2, L * 16 + 11 + b);
        }
        TRC(el, 2, L * 16 + 9);
        mbar_wait(bars + B_EVT + EV_Z1 * 8, L);
        mbar_wait(bars + B_EVT + (EV_N + EV_Z1) * 8, L);
        fence_gpu();
        if (el) mbar_arrive(bars + B_Z1);
        if (L == 0) {
          __nanosleep(NAP0);
          poison(el, sb + SM_STG + 17152, &P.psn, rb, j, lane);
          if (el) asm volatile("cp.async.bulk.commit_group;\ncp.async.bulk.wait_group 0;" ::: "memory");
          __syncwarp();
          fence_gpu();
        }
      }
    }
  } else {
    CKK(3);
    uint8_t* const wdst = P.wq + j * WQ_SL + rb * 3456 + tid * 16;
#pragma unroll
    for (int u = 0; u < SPL; u++) stg128_if(tid < 216, wdst + u * (16 * 3456), wv[u].x, wv[u].y, wv[u].z, wv[u].w);
    __syncwarp();
    if (lane == 0) mbar_arrive(bars + B_RES + 8);
    CKK(4);
    auto repack2 = [&]() {
#pragma unroll
      for (int u = SPL; u < 5; u++) stg128_if((u < 4 || rb < 8) && tid < 216, wdst + u * (16 * 3456), wv[u].x, wv[u].y, wv[u].z, wv[u].w);
      float s[8];
#pragma unroll
      for (int e = 0; e < 8; e++) s[e] = 0.f;
#pragma unroll
      for (int u = 0; u < 5; u++) {
        uint32_t x[4] = {wv[u].x, wv[u].y, wv[u].z, wv[u].w};
        asm volatile("" : "+r"(x[0]), "+r"(x[1]), "+r"(x[2]), "+r"(x[3]));
#pragma unroll
        for (int e = 0; e < 4; e++) { s[2 * e] += blo(x[e]); s[2 * e + 1] += bhi(x[e]); }
      }
#pragma unroll
      for (int m = 4; m; m >>= 1) {
#pragma unroll
        for (int e = 0; e < m; e++) s[e] = ((tid & m) ? s[e + m] : s[e]) + __shfl_xor_sync(~0u, (tid & m) ? s[e] : s[e + m], m);
      }
      stg32_if(tid < 216, P.csp + bid * 216 + tid, __float_as_uint(s[0]));
      __syncwarp();
      if (lane == 0) mbar_arrive(bars + B_IMG);
    };
    reg_alloc<232>();
    CKK(5);
#pragma unroll
    for (int v = SPL; v < 5; v++) wv[v] = ldnc128_if(tid < 216 && (v < 4 || rb < 8), wsrc + v * (128 * 3 * DM * 2));
    repack2();
    CKK(6);
    const int w = wid >> 2, q = wid & 3;
    int g = lane >> 2, t = lane & 3;
    const uint32_t ev = bars + B_EVT + w * EV_N * 8;
    const bool tr = (tid & 127) == 0;
    (void)tr;
    Cur c{0, 0};
    const uint32_t ebar = mapa(bars + B_EMPTY, (bid & 1) ^ (lane & 1));
    auto release = [&](uint32_t s, uint32_t dep = 0) { mbar_arrive_cluster_if(lane < 2, ebar + s * 8 + dep); };
    auto release_if = [&](bool on, uint32_t s) { mbar_arrive_cluster_if(lane < 2 && on, ebar + s * 8); };
    uint32_t ia = 0;
    auto wait_ab = [&]() { mbar_wait_c(bars + B_FULL + c.s * 8, c.ph); mbar_wait_c(bars + B_FULLA + w * 32 + c.s * 8, (ia >> 2) & 1); ia++; };

    auto yield_done = [&]() { if (w == 0 && lane == 0) mbar_arrive(bars + B_LAG); };
    auto signal = [&](int e) { __syncwarp(); mbar_arrive_if(lane == 0, ev + e * 8); };

    const uint32_t epoch = ldcg32(g_flags + (rb * 2 + w) * 32 + FR_EP + j);
    TRC(tr, w, 1);
    CKK(7);
    if (PAD && P.zero) {
#pragma unroll
      for (int i = 0; i < PAD; i++) asm volatile("st.shared.u32 [%0], %1;" ::"r"(sb + i * 20), "r"(tid) : "memory");
    }
    CKK_OUT;

#pragma unroll 1
    for (int L = 0; L < 2; L++) {
      const int tb = 2 + L * 24;
      asm volatile("" : "+r"(lane), "+r"(g), "+r"(t));
      (void)tb;
      ia = 0;
      const uint32_t tag = epoch * 2 + L + 1;
      uint32_t aoff = (w * 64 + q * 16 + (lane & 15)) * 128 + (((lane >> 4) ^ (lane & 7)) << 4);
      {
        uint32_t Pk[27][2];
        float sc0, sc1;
        const uint32_t att = sb + w * 8192 + q * 2048 + lane * 4;
        uint4* hp = g_HALO + ((((rb - (q == 0)) * 2 + w) * 8 + j) * 6) * 32 + lane;
        uint8_t* od = o_block(rb, w) + (9 * j) * 1024 + (2 * q) * 128 + lane * 4;
        ACLK_INIT;
        {
          float acc[108];
#pragma unroll
          for (int i = 0; i < 108; i++) acc[i] = 0.f;
          uint32_t prev = 0;
#pragma unroll 1
          for (int kb = 0; kb < 9; kb++) {
            wait_ab();
            if (w == 1 && kb == 9 - LAG1) mbar_wait_c(bars + B_LAG, L);
            TRC(tr && kb == 0, w, tb + 0);
            MCLK(kb == 0, 0);
            PCLK(kb * 4);
            const uint32_t st = sb + c.s * ST_BYTES, da = dlo(st + w * 8192, 16), db = dlo(st + ST_B, 3456);
            wgmma_fence();
#pragma unroll
            for (int kk = 0; kk < 4; kk++) {
              wgmma_ss_n216(acc, dsc<1024, 1>(da, kk * 32), dsc<128, 0>(db, kk * 6912), 1);
              if (kk == 0) { wgmma_commit(); wgmma_wait<1>(); release_if(kb > 0, prev); }
            }
            wgmma_commit();
            if (kb == 8) yield_done();
            PCLK(kb * 4 + 1);
            PCLK(kb * 4 + 2);
            PCLK(kb * 4 + 3);
            prev = c.s; c.next();
          }
          const uint32_t cs = sb + prev * ST_BYTES + SM_CSQ + t * 8;
          mbar_wait_c(bars + B_CSQ, L);
          mbar_wait_c(bars + B_XS + w * 8, L);
          const float2 n0 = lds64f(sb + prev * ST_BYTES + SM_XST + w * 512 + (16 * q + g) * 8), n1 = lds64f(sb + prev * ST_BYTES + SM_XST + w * 512 + (16 * q + g + 8) * 8);
          const float m0 = n0.x, r0 = n0.y, m1 = n1.x, r1 = n1.y;
          float2 cv[27];
#pragma unroll
          for (int G = 0; G < 27; G++) cv[G] = lds64f(cs + G * 32);
          PCLK(36);
          wgmma_wait<0>();
          PCLK(37);
          uint32_t dep = P.zero & __float_as_uint(m0) & __float_as_uint(m1);
#pragma unroll
          for (int G = 0; G < 27; G++) dep &= __float_as_uint(cv[G].x);
          release(prev, dep);
          TRC(tr, w, tb + 1);
          MCLK(1, 1);
          ACLK(0);
#pragma unroll
          for (int G = 9; G < 27; G++) Pk[G][1] = pack2(fmaf(m1, cv[G].x, acc[4 * G + 2]) * r1, fmaf(m1, cv[G].y, acc[4 * G + 3]) * r1);
          if (q < 3) {
#pragma unroll
            for (int i = 0; i < 18; i++) sts32(att + (i >> 4) * ST_BYTES + (i & 15) * 128, Pk[9 + i][1]);
          } else if (rb < 15) {
#pragma unroll
            for (int i = 0; i < 6; i++) ll_st128(hp + i * 32, __uint_as_float(Pk[9 + 3 * i][1]), __uint_as_float(Pk[10 + 3 * i][1]), tag, __uint_as_float(Pk[11 + 3 * i][1]));
          }
#pragma unroll
          for (int G = 0; G < 27; G++) {
            if (G < 9) {
              Pk[G][0] = pack2(fmaf(m0, cv[G].x, acc[4 * G]), fmaf(m0, cv[G].y, acc[4 * G + 1]));
              Pk[G][1] = pack2(fmaf(m1, cv[G].x, acc[4 * G + 2]), fmaf(m1, cv[G].y, acc[4 * G + 3]));
            } else {
              Pk[G][0] = pack2(fmaf(m0, cv[G].x, acc[4 * G]) * r0, fmaf(m0, cv[G].y, acc[4 * G + 1]) * r0);
            }
          }
          sc0 = r0 * (0.23570226039551584f * 1.4426950408889634f); sc1 = r1 * (0.23570226039551584f * 1.4426950408889634f);
        }
        ACLK(1);
        constexpr int GA_[4] = {0, 2, 4, 7}, GB_[4] = {1, 3, 5, 8}, GC_[4] = {2, 4, 6, 6};
        float S1[4][4], S2[4][4];
        uint32_t qa[4][2], qc[4][2];
#pragma unroll
        for (int h = 0; h < 4; h++) {
#pragma unroll
          for (int r = 0; r < 2; r++) {
            qa[h][r] = (h == 0 || h == 3 || t >= h) ? Pk[GA_[h]][r] : 0u;
            qc[h][r] = (h == 3 ? t == 3 : t <= h) ? Pk[GC_[h]][r] : 0u;
          }
          mma16(S1[h], qa[h][0], qa[h][1], Pk[GB_[h]][0], Pk[GB_[h]][1], Pk[9 + GA_[h]][0], Pk[9 + GB_[h]][0]);
          mma16(S2[h], qa[h][0], qa[h][1], Pk[GB_[h]][0], Pk[GB_[h]][1], Pk[9 + GA_[h]][1], Pk[9 + GB_[h]][1]);
        }
#pragma unroll
        for (int h = 0; h < 4; h++) {
          mma8(S1[h], qc[h][0], qc[h][1], Pk[9 + GC_[h]][0]);
          mma8(S2[h], qc[h][0], qc[h][1], Pk[9 + GC_[h]][1]);
        }
        uint32_t V1[9], V2[9];
#pragma unroll
        for (int i = 0; i < 9; i++) { V1[i] = movm(Pk[18 + i][0]); V2[i] = movm(Pk[18 + i][1]); }
        const bool remote = q == 0 && rb > 0;
        uint4 hv[6];
#pragma unroll
        for (int i = 0; i < 6; i++) hv[i] = make_uint4(0u, 0u, tag, 0u);
        if (remote) {
#pragma unroll
          for (int i = 0; i < 6; i++) hv[i] = ll_ld128(hp + i * 32);
        }
        const bool up0 = 2 * t > g, up1 = 2 * t + 1 > g;
        const uint32_t mup = (up0 ? 0xffffu : 0u) | (up1 ? 0xffff0000u : 0u);
        auto finish = [&](const float (&x0)[4], const float (&x1)[4], uint32_t ma, const uint32_t (&Vb)[9], int hi) {
          uint32_t pa[4], pb[4];
          float rs[4];
#pragma unroll
          for (int h = 0; h < 4; h++) {
            const float m = qmax(fmaxf(x0[h], x1[h]));
            const uint32_t p = pack2(ex2(x0[h] - m), ex2(x1[h] - m));
            pa[h] = p & ma; pb[h] = p & ~ma;
          }
#pragma unroll
          for (int h = 0; h < 4; h += 2) {
            float R[4];
            mma16(R, pa[h], pa[h + 1], pb[h], pb[h + 1], 0x3f803f80u, 0x3f803f80u);
            rs[h] = rcp_fast(R[0]); rs[h + 1] = rcp_fast(R[2]);
          }
#pragma unroll
          for (int i = 0; i < 9; i++) {
            const int h = 4 * i / 9, e = (h & 1) * 2;
            const bool split = i == 2 || i == 4 || i == 6, nx = split && 2 * t >= i;
            float O[4], N[4];
            mma16(O, pa[h & 2], pa[h | 1], pb[h & 2], pb[h | 1], V1[i], Vb[i]);
            if (i == 4) mma16(N, pa[2], pa[3], pb[2], pb[3], V1[i], Vb[i]); else { N[0] = O[2]; N[1] = O[3]; }
            const float r = nx ? rs[h + (split ? 1 : 0)] : rs[h];
            stg32(od + i * 1024 + hi * 128, pack2((nx ? N[0] : O[e]) * r, (nx ? N[1] : O[e + 1]) * r));
          }
        };
        {
          float x0[4], x1[4];
#pragma unroll
          for (int h = 0; h < 4; h++) { x0[h] = (up0 ? S1[h][2] : S2[h][2]) * sc1; x1[h] = (up1 ? S1[h][3] : S2[h][3]) * sc1; }
          finish(x0, x1, mup, V2, 1);
        }
        ACLK(2);
        bar_sync(1 + w, 128);
        uint32_t H[18];
        if (q > 0) {
#pragma unroll
          for (int i = 0; i < 18; i++) H[i] = lds32(att - 2048 + (i >> 4) * ST_BYTES + (i & 15) * 128);
        } else {
#pragma unroll 1
          for (int it = 0; it < (1 << 20); it++) {
            bool ok = true;
#pragma unroll
            for (int i = 0; i < 6; i++) ok = ok && hv[i].z == tag;
            if (__all_sync(~0u, ok)) break;
#pragma unroll
            for (int i = 0; i < 6; i++) hv[i] = ll_ld128(hp + i * 32);
          }
#pragma unroll
          for (int i = 0; i < 6; i++) { H[3 * i] = hv[i].x; H[3 * i + 1] = hv[i].y; H[3 * i + 2] = hv[i].w; }
        }
        float S0[4][4];
#pragma unroll
        for (int h = 0; h < 4; h++) {
          mma16(S0[h], qa[h][0], qa[h][1], Pk[GB_[h]][0], Pk[GB_[h]][1], H[GA_[h]], H[GB_[h]]);
        }
#pragma unroll
        for (int h = 0; h < 4; h++) mma8(S0[h], qc[h][0], qc[h][1], H[GC_[h]]);
        uint32_t V0[9];
#pragma unroll
        for (int i = 0; i < 9; i++) V0[i] = movm(H[9 + i]);
        ACLK(3);
        {
          const bool nohalo = (rb | q) == 0;
          const float b0 = up0 && nohalo ? -INFINITY : 0.f, b1 = up1 && nohalo ? -INFINITY : 0.f;
          float x0[4], x1[4];
#pragma unroll
          for (int h = 0; h < 4; h++) { x0[h] = fmaf(up0 ? S0[h][0] : S1[h][0], sc0, b0); x1[h] = fmaf(up1 ? S0[h][1] : S1[h][1], sc0, b1); }
          finish(x0, x1, ~mup, V0, 0);
        }
        ACLK(4);
        signal(EV_O);
        ACLK_OUT;
        TRC(tr, w, tb + 2);
        MCLK(1, 2);
      }
      {
        float acc[36];
        const int hw = rb * 2 + (j & 1), js = (j & 6) + w;
        const uint32_t xt = sb + SM_STG + (16 * q + g) * 288 + w * 144 + t * 4;
        uint32_t xm = sb + SM_STG + (16 * q + (lane & 15)) * 288 + (((9 * w + (lane >> 4)) ^ ((lane >> 2) & 1)) << 4), xl = sb + SM_STG + (2 * q + w) * 2304 + lane * 16;
        uint8_t* xd[5];
#pragma unroll
        for (int u = 0; u < 5; u++) {
          const int row = ((u * 32 + lane) * 57) >> 10;
          xd[u] = P.xs[L + 1] + (128 * rb + 32 * q + 16 * w + (j & 1)) * (DM * 2) + (j & 6) * 144 + row * (DM * 4 - 288) + u * 512 + ((lane ^ (row >> 2)) << 4);
          asm volatile("" : "+l"(xd[u]));
        }
        asm volatile("" : "+r"(xm), "+r"(xl));
        mbar_wait_c(bars + B_RES, L);
        TRC(tr, w, tb + 21);
#pragma unroll
        for (int i = 0; i < 18; i++) { const uint32_t x = lds32(xt + (i >> 1) * 16 + (i & 1) * 2304); acc[2 * i] = blo(x); acc[2 * i + 1] = bhi(x); asm volatile("" : "+f"(acc[2 * i]), "+f"(acc[2 * i + 1])); }
        uint32_t prev = 0;
#pragma unroll 1
        for (int u = 0; u < 5; u++) {
          const uint32_t st = sb + c.s * ST_BYTES, da = dlo(st, 1024), db = dlo(st + ST_B + w * 18432, 1152);
          mbar_wait_c(bars + B_FULL + c.s * 8, c.ph); mbar_wait_c(bars + B_FULLA + c.s * 8, (ia >> 2) & 1);
          TRC(tr && u == 0, w, tb + 3);
          MCLK(u == 0, 3);
          wgmma_fence();
#pragma unroll
          for (int kk = 0; kk < 4; kk++) wgmma_ss_n72(acc, dsc<128, 0>(da, kk * 2048), dsc<128, 0>(db, kk * 2304), 1);
          wgmma_commit();
          wgmma_wait<1>();
          release_if(u > 0, prev);
          mbar_wait_c(bars + B_FULLA + 32 + c.s * 8, (ia >> 2) & 1);
          ia++;
          if (u == 4) break;
          wgmma_fence();
#pragma unroll
          for (int kk = 4; kk < 8; kk++) wgmma_ss_n72(acc, dsc<128, 0>(da, kk * 2048), dsc<128, 0>(db, kk * 2304), 1);
          wgmma_commit();
          prev = c.s; c.next();
        }
        RCLK_INIT;
        wgmma_wait<0>();
        RCLK(0);
        release(c.s);
        c.next();
        if (__builtin_expect(any_nan(acc[0], acc[2]), 0)) {
          SLOW(L);
          const uint8_t* xr = P.xs[L] + (128 * rb + 32 * q + 2 * g + (j & 1)) * (DM * 2) + js * 144 + t * 4;
#pragma unroll
          for (int i = 0; i < 18; i++) { const uint32_t x = ldgpu32(xr + (i >> 1) * 16 + (i & 1) * (DM * 32)); acc[2 * i] = blo(x); acc[2 * i + 1] = bhi(x); }
          redo<KS2, 9, 1024, 128, 1152, 128>(acc, o_block(rb, j & 1) + q * 256 + lane * 4, g_WO + js * WO_SL + lane * 4, [](uint32_t*, int) {});
        }
        TRC(tr && P5TRACE != 5, w, tb + 4);
        MCLK(1, 4);
#pragma unroll
        for (int u = 0; u < 4; u++)
          stsm4(xm + u * 32, pack2(acc[8 * u], acc[8 * u + 1]), pack2(acc[8 * u + 2], acc[8 * u + 3]), pack2(acc[8 * u + 4], acc[8 * u + 5]), pack2(acc[8 * u + 6], acc[8 * u + 7]));
        asm volatile("stmatrix.sync.aligned.m8n8.x2.shared.b16 [%0], {%1,%2};" ::"r"(xm + 128), "r"(pack2(acc[32], acc[33])), "r"(pack2(acc[34], acc[35])) : "memory");
        auto stats = [&]() {
          float s0 = 0.f, s1 = 0.f, q0 = 0.f, q1 = 0.f;
#pragma unroll
          for (int i = 0; i < 36; i++) {
            if (i & 2) { s1 += acc[i]; q1 = fmaf(acc[i], acc[i], q1); } else { s0 += acc[i]; q0 = fmaf(acc[i], acc[i], q0); }
          }
          s0 = qsum(s0); s1 = qsum(s1); q0 = qsum(q0); q1 = qsum(q1);
          const float ss = t ? s1 : s0, m = ss * (1.f / 72.f);
          ll_st128_if(t < 2, g_ST1 + (hw * 8 + js) * 64 + 16 * q + 8 * t + g, m, fmaxf((t ? q1 : q0) - ss * m, 0.f), tag);
        };
        stats();
        RCLK(1);
        bar_sync(8 + q, 64);
        RCLK(2);
#pragma unroll
        for (int u = 0; u < 5; u++) {
          const uint4 v = lds128(xl + u * 512);
          stg128_if(u < 4 || lane < 16, xd[u], v.x, v.y, v.z, v.w);
        }
        RCLK(3);
        signal(EV_X1);
        RCLK(4);
        RCLK(5);
        TRC(tr, w, tb + 5);
        RCLK(6);
        RCLK_OUT;
      }
      uint4 zk[4];
      {
        uint32_t xA[36][4];
        float acc[32];
        uint32_t s0, one, off2;
        uint8_t *z1d, *zd;
        uint64_t db;
        auto bwait = [&](uint32_t dhi, bool skip) {
          s0 = c.s;
          c.next();
          if (!skip) mbar_wait_c(bars + B_FULL + c.s * 8, c.ph);
          db = dsc2(dlo(sb + s0 * ST_BYTES + ST_B, 512) - 3, 0, dhi); one = (c.s ^ P.zero) & 1;
        };
        auto mma = [&](int kk, int pp, bool hand) {
          wgmma_rs_n64(acc, xA[kk], dat(db, (kk / 18) * ST_BYTES + (kk % 18) * 2048 + 48, one), kk != 0);
          if (kk == pp && hand) bar_arrive(7 - w, 256);
          if (kk == 17 || kk == 35) wgmma_commit();
          if (kk == RL3) { wgmma_commit(); wgmma_wait<1>(); release(s0); }
        };
        {
          bwait(0x40000040u, false);
          mbar_wait_c(bars + B_GATE3, L);
          float mean0, mean1, rs0, rs1;
          stat_get(g_ST1 + ((rb * 2 + w) * 8 + 2 * t) * 64 + 16 * q + g, tag, 72.f, LN_EPS, mean0, rs0, mean1, rs1);
          const uint32_t ns0 = pack2(GA * rs0, GA * rs0), ns1 = pack2(GA * rs1, GA * rs1);
          const uint32_t nb0 = pack2(-mean0 * blo(ns0), -mean0 * blo(ns0)), nb1 = pack2(-mean1 * blo(ns1), -mean1 * blo(ns1));
          const uint32_t al = sb + (aoff & 8191);
#pragma unroll
          for (int kb = 0; kb <= 9; kb++) {
            if (kb < 9) {
              mbar_wait_c(bars + B_FA3 + (9 * w + kb) * 8, L);
              TRC(tr && kb == 0, w, tb + 6);
              MCLK(kb == 0, 5);
              if (kb == 0) SCLK(0);
              QCLK(kb);
              const uint32_t at = al + (w ? (((kb + 1) >> 1) & 3) * ST_BYTES + ((kb + 1) & 1) * 8192 : ((kb >> 1) & 3) * ST_BYTES + (kb & 1) * 8192);
#pragma unroll
              for (int kk = 4 * kb; kk < 4 * kb + 4; kk++) ldsm4(xA[kk], at ^ ((kk & 3) << 5));
            }
            if (kb == 0) continue;
            const uint32_t dep = xA[4 * kb - 4][0] & xA[4 * kb - 3][0] & xA[4 * kb - 2][0] & xA[4 * kb - 1][0] & P.zero;
            mbar_arrive_if(lane == 0 && (kb == 1 || w == 0), bars + B_EA3 + (9 * w + kb - 1) * 8 + dep);
#pragma unroll
            for (int kk = 4 * kb - 4; kk < 4 * kb; kk++) {
#pragma unroll
              for (int e = 0; e < 4; e++) xA[kk][e] = hfma2(xA[kk][e], (e & 1) ? ns1 : ns0, (e & 1) ? nb1 : nb0);
            }
            wgmma_fence();
#pragma unroll
            for (int kk = 4 * kb - 4; kk < 4 * kb; kk++) mma(kk, PP30, w);
          }
          off2 = lds32(sb + SM_OFF);
          z1d = z1_block(rb, w, j) + (tid & 127) * 16;
          zd = z2_block(2 * rb + (q >> 1), j) + (4 * (q & 1) + w) * 4608 + ((g & 3) * 2 + (g >> 2)) * 16 + t * 4;
          asm volatile("" : "+l"(z1d), "+l"(zd));
          wgmma_wait<0>();
          if (__builtin_expect(any_nan(acc[0], acc[2]), 0)) {
            SLOW(2 + L);
            uint4* const rd = g_RD + bid * (36 * 256) + tid;
            const uint8_t* xr = P.xs[L + 1] + (128 * rb + 32 * q + 2 * g + w) * (DM * 2) + t * 4;
#pragma unroll
            for (int i = 0; i < 32; i++) acc[i] = 0.f;
            redo<KS3, 8, 16, DM * 32, FH * 32, 16>(acc, xr, (const uint8_t*)P.w_in + g * (FH * 4) + (((9 * j + 1) >> 1) + 36) * 128 + t * 4,
                                              [&](uint32_t* a, int k) {
#pragma unroll
                                                for (int e = 0; e < 4; e++) a[e] = hfma2(a[e], (e & 1) ? ns1 : ns0, (e & 1) ? nb1 : nb0);
                                                stg128(rd + k * 256, a[0], a[1], a[2], a[3]);
                                              });
#pragma unroll
            for (int k = 0; k < 36; k++) { const uint4 v = ldcg128(rd + k * 256); xA[k][0] = v.x; xA[k][1] = v.y; xA[k][2] = v.z; xA[k][3] = v.w; }
          }
        }
        float sm[4] = {0.f, 0.f, 0.f, 0.f}, qq[4] = {0.f, 0.f, 0.f, 0.f};
        auto gelu = [&](auto nz2, bool out) {
          constexpr int NZ2 = nz2.value, R = 8 - NZ2, N = 8, D = NZ2 == 8 ? GM2 : NZ2 ? GMM : GM1;
          float th[32], gb = GB;
          uint32_t qa = 0, qb = 0;
          auto head = [&](int G) {
#pragma unroll
            for (int e = 0; e < 4; e++) { const float v = acc[4 * G + e]; th[4 * G + e] = tanh_fast(v * fmaf(v, v, gb)); }
          };
#pragma unroll
          for (int i = 0; i < D; i++) head((i + R) & 7);
#pragma unroll
          for (int i = 0; i < N; i++) {
            const int G = (i + R) & 7;
            if (i + D < N) head((i + D + R) & 7);
            float* z = acc + 4 * G;
#pragma unroll
            for (int e = 0; e < 4; e++) z[e] = fmaf(z[e], th[4 * G + e], z[e]);
            uint32_t pa = pack2(z[0], z[1]), pb = pack2(z[2], z[3]), tok;
            if (i < NZ2) {
#pragma unroll
              for (int e = 0; e < 4; e++) { sm[e] += z[e]; qq[e] = fmaf(z[e], z[e], qq[e]); }
              pa = hsub2(pa, off2); pb = hsub2(pb, off2);
              stg32(zd + i * 128, pa); stg32(zd + i * 128 + 9216, pb);
              tok = pa ^ pb ^ __float_as_uint(qq[1]);
            } else {
              if (NZ2 && G == 3) sts128(sb + SM_STG + tid * 16, qa, qb, pa, pb);
              else if (G & 1) stg128_if(out, z1d + (G >> 1) * 2048 + (NZ2 ? 24576 : 0), qa, qb, pa, pb);
              qa = pa; qb = pb;
              tok = pa ^ pb;
            }
            gb = __uint_as_float(tok * P.zero + __float_as_uint(GB));
          }
        };
#pragma unroll 1
        for (int p = 0;; p++) {
          wgmma_wait<0>();
          release(c.s);
          c.next();
          TRC(tr && p == 4, w, tb + 7);
          TRC(tr && p == 8, w, tb + 11);
          MCLK(p == 8, 6);
          SCLK(2 * p + 1);
          QCLK(10 + 3 * p);
          auto publish = [&]() {
            signal(EV_ZN);
            const float a0 = qsum(sm[0] + sm[1]), a1 = qsum(sm[2] + sm[3]), q0 = qsum(qq[0] + qq[1]), q1 = qsum(qq[2] + qq[3]);
            const float ss = t ? a1 : a0, m = ss * (1.f / 288.f);
            ll_st128_if(t < 2, g_ZST + (rb * 2 + w) * 512 + j * 64 + 16 * q + 8 * t + g, m - blo(off2), fmaxf((t ? q1 : q0) - ss * m, 0.f), tag);
            TRC(tr, w, tb + 8);
            TRC(tr, w, tb + 9);
          };
          if (p < 4) {
            gelu(Int<8>{}, true);
            zd += 1024;
          } else if (p == 4) {
            gelu(Int<4>{}, true);
            publish();
          } else {
            gelu(Int<0>{}, p < 8);
            z1d += 8192;
          }
          SCLK(2 * p + 2);
          QCLK(11 + 3 * p);
          if (p == 8) break;
          bwait(p == 3 ? 0x80000040u : 0x40000040u, w);
          bar_sync(6 + w, 256);
          TRC(tr && p == 4, w, tb + 10);
          wgmma_fence();
#pragma unroll
          for (int kk = 0; kk < 36; kk++) mma(kk, PP3, w == 0 || p < 7);
        }
        signal(EV_Z1);
#pragma unroll
        for (int u = 0; u < 4; u++) {
          zk[u] = make_uint4(pack2(acc[8 * u], acc[8 * u + 1]), pack2(acc[8 * u + 2], acc[8 * u + 3]), pack2(acc[8 * u + 4], acc[8 * u + 5]), pack2(acc[8 * u + 6], acc[8 * u + 7]));
          asm volatile("" : "+r"(zk[u].x), "+r"(zk[u].y), "+r"(zk[u].z), "+r"(zk[u].w));
        }
        TRC(tr, w, tb + 12);
      }
      uint32_t hA[18][4];
      {
        float acc[144];
        const float c0 = __uint_as_float(lds32(sb + SM_OFF + 4));
#pragma unroll
        for (int i = 0; i < 144; i++) {
          asm volatile("fma.rn.f32 %0, %1, %2, %3;" : "=f"(acc[i]) : "f"(__uint_as_float(P.zero)), "f"((float)(i + 2)), "f"(c0));
        }
        uint32_t prev = 0;
        auto stage = [&](int kb) {
          mbar_wait_c(bars + B_FULL + c.s * 8, c.ph);
          TRC(tr && kb == 0, w, tb + 13);
          SCLK(22 + kb);
          const uint32_t st = sb + c.s * ST_BYTES, rt = sb + SM_RT + kb * 128 + t * 8;
          uint64_t db = dsc2(dlo(st + ST_B, 4608), 0, 8 + P.zero);
          uint32_t a[4][4];
#pragma unroll
          for (int kk = 0; kk < 4; kk++) {
            uint32_t r[4];
            ldsm4(r, st + (aoff ^ (kk << 5)));
            const uint2 sc = lds64(rt + kk * 32);
            a[kk][0] = hmul2(__byte_perm(r[0], r[2], 0x5410), sc.x); a[kk][2] = hmul2(__byte_perm(r[0], r[2], 0x7632), sc.y);
            a[kk][1] = hmul2(__byte_perm(r[1], r[3], 0x5410), sc.x); a[kk][3] = hmul2(__byte_perm(r[1], r[3], 0x7632), sc.y);
          }
          wgmma_fence();
#pragma unroll
          for (int i = 0; i < 8; i++) {
            const int kk = i & 3, hf = i >> 2;
            wgmma_rs_n144(acc + hf * 72, a[kk], db, 1);
            dadd(db, i == 3 ? 144u - 3 * 576 : 576 + P.zero);
            if (i == 0) { wgmma_commit(); wgmma_wait<1>(); release_if(kb, prev); }
            if (i == 3) wgmma_commit();
          }
          wgmma_commit();
          prev = c.s; c.next();
        };
        mbar_wait_c(bars + B_RT, L);
#pragma unroll 1
        for (int kb = 0; kb < 32; kb += 2) {
          if (kb == 8) mbar_wait_c(bars + B_RT1, L);
          MCLK((kb & 7) == 4, 10 + (kb >> 3));
          stage(kb);
          stage(kb + 1);
        }
        if (w == 1) bar_arrive(6, 256);
        HCLK(0);
        mbar_wait_c(bars + B_CV + w * 8, L);
        HCLK(1);
        const float gk = 0.5f / GA;
        const float c1 = __uint_as_float(lds32(sb + SM_OFF + 4));
        const float gb0 = -gk * (c1 + __uint_as_float(lds32(sb + SM_CV + w * 256 + (16 * q + g) * 4))), gb1 = -gk * (c1 + __uint_as_float(lds32(sb + SM_CV + w * 256 + (16 * q + g + 8) * 4)));
        mbar_wait_c(w ? bars + B_FULL + c.s * 8 : bars + B_ZB, w ? c.ph : L);
        HCLK(2);
        const uint32_t sx = c.s;
        c.next();
        const uint32_t zt = sb + tid * 16, zs = zt + sx * ST_BYTES + w * 24576;
        uint4 zz[18];
        auto zload = [&](int u) {
          if (ZW && u == ZW && P.zero) __nanosleep(0);
          if (u >= 12 && u < 16) zz[u] = zk[u - 12]; else zz[u] = lds128(u == 17 ? zt + SM_STG : zs + (u < 12 ? u : 12) * 2048);
        };
#pragma unroll
        for (int u = 0; u < ZA; u++) zload(u);
#pragma unroll
        for (int u = 0; u < 18; u++) {
          if (u == 0) { wgmma_wait<1>(); HCLK(3); }
          if (u == 9) {
            HCLK(4);
            wgmma_wait<0>();
            HCLK(5);
            release(prev);
            mbar_arrive_if(L == 0 && lane == 0, ev + EV_P4 * 8);
            TRC(tr, w, tb + 14);
            SCLK(54);
          }
          if (u + ZA < 18) zload(u + ZA);
          const uint4 z = zz[u];
          hA[u][0] = hmul2(z.x, pack2(fmaf(acc[8 * u], gk, gb0), fmaf(acc[8 * u + 1], gk, gb0)));
          hA[u][1] = hmul2(z.y, pack2(fmaf(acc[8 * u + 2], gk, gb1), fmaf(acc[8 * u + 3], gk, gb1)));
          hA[u][2] = hmul2(z.z, pack2(fmaf(acc[8 * u + 4], gk, gb0), fmaf(acc[8 * u + 5], gk, gb0)));
          hA[u][3] = hmul2(z.w, pack2(fmaf(acc[8 * u + 6], gk, gb1), fmaf(acc[8 * u + 7], gk, gb1)));
        }
        uint32_t dep = P.zero;
#pragma unroll
        for (int u = 0; u < 18; u++) dep &= hA[u][0];
        release(sx, dep);
        TRC(tr, w, tb + 15);
        HCLK(6);
      }
      {
        CLK_INIT;
        uint32_t pk[16];
#pragma unroll
        for (int i = 0; i < 16; i++) pk[i] = 0u;
        auto dump = [&](int p) {
          const uint32_t d = sb + (p & 3) * ST_BYTES, cb = p + j >= 9 ? p + j - 9 : p + j;
          if (lane == 0) asm volatile("cp.async.bulk.wait_group.read 3;" ::: "memory");
          __syncwarp();
#pragma unroll
          for (int u = 0; u < 4; u++) stsm4(d + (aoff ^ (u << 5)), pk[4 * u], pk[4 * u + 1], pk[4 * u + 2], pk[4 * u + 3]);
          fence_async_s();
          __syncwarp();
          tma3d_red_p(lane == 0, &P.red[L], cb * 64, rb * 64 + q * 16, w, d + w * 8192 + q * 2048);
        };
#pragma unroll 1
        for (int p = 0; p < 9; p++) {
          float acc[32];
          CLK(0);
          mbar_wait_c(bars + B_FULL + c.s * 8, c.ph);
          uint64_t db = dsc2(dlo(sb + c.s * ST_BYTES + ST_B + (j & 1) * 4096, 0), 0, 0x40000040u + P.zero);
          CLK(1);
          HCLK(7 + 2 * p);
          bar_sync(6 + w, 256);
          CLK(2);
          wgmma_fence();
#pragma unroll
          for (int kk = 0; kk < 18; kk++) {
            wgmma_rs_n64(acc, hA[kk], db, kk != 0);
            dadd(db, kk == 15 ? 128 - (j & 1) * (36864 >> 4) : 128 + P.zero);
            if (kk == PPK && (w == 0 || p < 8)) bar_arrive(7 - w, 256);
          }
          wgmma_commit();
          CLK(3);
          if (p > 0) dump(p - 1);
          CLK(5);
          wgmma_wait<0>();
          CLK(4);
          HCLK(8 + 2 * p);
          MCLK(p == 1 || p == 8, 7 + (p >> 3));
          release_if(L == 0 || p < 5, c.s);
          c.next();
#pragma unroll
          for (int i = 0; i < 16; i++) pk[i] = pack2(acc[2 * i], acc[2 * i + 1]);
          if (p == 8) { TRC(tr, w, tb + 16); dump(8); TRC(tr, w, tb + 17); }
        }
        if (lane == 0) asm volatile("cp.async.bulk.wait_group 0;" ::: "memory");
        HCLK(25);
        MCLK(1, 9);
        if (L == 0) signal(EV_PT);
        CLK_OUT;
        TRC(tr, w, tb + 18);
      }
    }
    if ((tid & 127) == 0) g_flags[(rb * 2 + w) * 32 + FR_EP + j] = epoch + 1;
    if (tid == 0) g_flags[FJ + j * 32 + FJ_EP + rb] = epoch + 1;
  }
}

typedef CUresult (*EncodeFn)(CUtensorMap*, CUtensorMapDataType, cuuint32_t, void*, const cuuint64_t*, const cuuint64_t*, const cuuint32_t*,
                             const cuuint32_t*, CUtensorMapInterleave, CUtensorMapSwizzle, CUtensorMapL2promotion, CUtensorMapFloatOOBfill);

static void make_map(EncodeFn fn, CUtensorMap* m, const void* ptr, int rank, uint64_t d0, uint64_t d1, uint64_t d2, uint64_t s1, uint64_t s2,
                     uint32_t b0, uint32_t b1, uint32_t b2, CUtensorMapSwizzle swz) {
  cuuint64_t dims[3] = {d0, d1, d2}, strides[2] = {s1, s2};
  cuuint32_t box[3] = {b0, b1, b2}, es[3] = {1, 1, 1};
  fn(m, CU_TENSOR_MAP_DATA_TYPE_BFLOAT16, rank, const_cast<void*>(ptr), dims, strides, box, es, CU_TENSOR_MAP_INTERLEAVE_NONE, swz,
     CU_TENSOR_MAP_L2_PROMOTION_L2_128B, CU_TENSOR_MAP_FLOAT_OOB_FILL_NONE);
}

}

extern "C" void kernel_launch(void* const* d_in, const int* in_sizes, int n_in, void* d_out, int out_size) {
  using namespace mk;
  (void)in_sizes; (void)n_in; (void)out_size;
  static EncodeFn fn = nullptr;
  static uint8_t *wq, *xb;
  static float* csp;
  if (!fn) {
    cudaGetSymbolAddress((void**)&wq, g_WQ);
    cudaGetSymbolAddress((void**)&xb, g_X);
    cudaGetSymbolAddress((void**)&csp, g_CSP);
    cudaDriverEntryPointQueryResult qr;
    cudaGetDriverEntryPoint("cuTensorMapEncodeTiled", (void**)&fn, cudaEnableDefault, &qr);
    cudaFuncSetAttribute(mega_kernel, cudaFuncAttributeMaxDynamicSharedMemorySize, SM_TOTAL);
  }
  Params p;
  p.wqkv = (const __nv_bfloat16*)d_in[1];
  p.w_in = (const __nv_bfloat16*)d_in[4];
  p.w_sp = (const __nv_bfloat16*)d_in[5];
  p.b_sp = (const __nv_bfloat16*)d_in[6];
  p.w_out = (const __nv_bfloat16*)d_in[7];
  p.zero = 0;
  p.wq = wq;
  p.csp = csp;
  p.xs[0] = (uint8_t*)d_in[0];
  p.xs[1] = xb;
  p.xs[2] = (uint8_t*)d_out;
  make_map(fn, &p.wsp, p.w_sp, 3, 2048, 1024, 2, 8192, 4096, 64, 64, 2, CU_TENSOR_MAP_SWIZZLE_128B);
  for (int i = 0; i < 2; i++) {
    make_map(fn, &p.red[i], p.xs[i + 1], 3, DM, 1024, 2, 2304, 1152, 64, 16, 1, CU_TENSOR_MAP_SWIZZLE_128B);
    make_map(fn, &p.res[i], p.xs[i], 3, DM, 1024, 2, 2304, 1152, 144, 64, 1, CU_TENSOR_MAP_SWIZZLE_NONE);
  }
  make_map(fn, &p.psn, d_out, 3, DM, 1024, 2, 2304, 1152, 144, 4, 1, CU_TENSOR_MAP_SWIZZLE_NONE);
  for (int i = 0; i < 3; i++) make_map(fn, &p.act[i], p.xs[i], 3, DM, 1024, 2, 2304, 1152, 64, 64, 1, CU_TENSOR_MAP_SWIZZLE_128B);
  {
    cuuint64_t dims[4] = {8, 8, 72, 72}, strides[3] = {1152, 16, 9216};
    cuuint32_t box[4] = {8, 8, 9, 5}, es[4] = {1, 1, 1, 1};
    fn(&p.wo8, CU_TENSOR_MAP_DATA_TYPE_BFLOAT16, 4, d_in[2], dims, strides, box, es, CU_TENSOR_MAP_INTERLEAVE_NONE, CU_TENSOR_MAP_SWIZZLE_NONE,
       CU_TENSOR_MAP_L2_PROMOTION_L2_128B, CU_TENSOR_MAP_FLOAT_OOB_FILL_NONE);
  }
  for (int i = 0; i < 2; i++) {
    cuuint64_t dims[4] = {i ? 4608u : 2304u, 8, i ? 1u : 2u, 72}, strides[3] = {9216, 4608, 8 * 9216};
    cuuint32_t box[4] = {i ? 64u : 32u, 8, i ? 1u : 2u, 18}, es[4] = {1, 1, 1, 1};
    fn(i ? &p.win64 : &p.win, CU_TENSOR_MAP_DATA_TYPE_BFLOAT16, 4, d_in[4], dims, strides, box, es, CU_TENSOR_MAP_INTERLEAVE_NONE,
       i ? CU_TENSOR_MAP_SWIZZLE_128B : CU_TENSOR_MAP_SWIZZLE_64B, CU_TENSOR_MAP_L2_PROMOTION_L2_128B, CU_TENSOR_MAP_FLOAT_OOB_FILL_NONE);
  }
  make_map(fn, &p.wout, p.w_out, 2, 576, 2304, 1, 1152, 0, 64, 144, 1, CU_TENSOR_MAP_SWIZZLE_128B);
  mega_kernel<<<NGRID, 384, SM_TOTAL, cudaStreamPerThread>>>(p);
}
```

```cpp
#include <cuda_runtime.h>
#include <cuda.h>
#include <cuda_bf16.h>
#include <stdint.h>

#define MK_TRACE 0
#define MK_DBG 0
#define P5TRACE 0
#define LAG1 3
#define PP3 32
#define PP30 33
#define SPL 2
#define NAP 200
#define NAP0 8000
#define KS2 2
#define KS3 2
#define RL3 21
#define PAD 0
#define ZA 4
#define ZW 10
#define GM2 1
#define GMM 1
#define GM1 2
#define C0S 32.f
#define OFA 0.125f
#define OFK 2.f
#define PPK 15

namespace mk {

constexpr int SEQ = 2048, DM = 576, FH = 2304;
constexpr int NCTA = 128;
constexpr int NGRID = 132;
constexpr uint32_t ZB = 36864;
constexpr uint32_t WQ_SL = 72 * 3456;
constexpr uint32_t WO_SL = 72 * 1152;
constexpr float LN_EPS = 1e-5f;
constexpr float GA = 0.3292034911525734f, GB = 2.423681954311584f;

constexpr uint32_t ST_BYTES = 53248, ST_B = 16384, NST = 4;
constexpr uint32_t SM_STG = NST * ST_BYTES;
constexpr uint32_t SM_BAR = SM_STG + 2 * 9216;
constexpr uint32_t SM_OFF = SM_BAR + 1008;
constexpr uint32_t SM_TOTAL = SM_BAR + 1024;
constexpr uint32_t SM_RT = SM_STG + 4096, SM_CV = SM_STG + 12288, SM_WT = SM_CV + 512;
constexpr uint32_t SM_WOI = 44032, SM_CSQ = 49792, SM_XST = 50688;
constexpr uint32_t B_FULL = 0, B_EMPTY = 32, B_FULLA = 64, B_RES = 128, B_WT = 144, B_IMG = 160, B_WOI = 168, B_ZB = 176, B_GATE3 = 184, B_Z1 = 192, B_LAG = 200,
                   B_RT = 208, B_CSQ = 216, B_CV = 224, B_AD = 240, B_EVT = 272, B_RT1 = 368, B_XS = 624, B_XRW = 384, B_FA3 = 400, B_EA3 = 544;
enum { EV_PT = 0, EV_O = 1, EV_X1 = 2, EV_ZN = 3, EV_Z1 = 4, EV_P4 = 5, EV_N = 6 };

enum { FR_X2 = 0, FR_O = 1, FR_X1 = 3, FR_EP = 16, FJ = 32 * 32, FJ_WQ = 0, FJ_WO = 1, FJ_WQ0 = 2, FJ_ZN = 3, FJ_P4 = 5, FJ_EP = 16, F_N = FJ + 8 * 32 };

__device__ __align__(1024) uint8_t g_Z[512 * ZB];
constexpr uint32_t POISON = 0xffffffffu;
__device__ __align__(1024) uint8_t g_O[32 * 2 * ZB];
__device__ __align__(1024) uint4 g_RD[NCTA * 36 * 256];
__device__ __align__(1024) uint8_t g_X[SEQ * DM * 2];
#define SLOW(i) do {} while (0)
__device__ __align__(1024) uint8_t g_WQ[8 * WQ_SL];
__device__ __align__(1024) uint8_t g_WO[8 * WO_SL];
__device__ __align__(1024) float g_CSP[2 * NCTA * 216];
__device__ __align__(1024) uint2 g_RT[SEQ];
__device__ __align__(1024) uint4 g_XST[2 * SEQ];
__device__ __align__(1024) uint4 g_ST1[SEQ * 8];
__device__ __align__(1024) uint4 g_ZST[SEQ * 8];
__device__ __align__(1024) uint4 g_HALO[32 * 8 * 6 * 32];
__device__ __align__(1024) uint32_t g_flags[F_N];

struct Params {
  const __nv_bfloat16 *wqkv;
  uint8_t* wq;
  float* csp;
  uint32_t zero;
  const __nv_bfloat16 *w_in, *w_sp, *b_sp, *w_out;
  uint8_t* xs[3];
  CUtensorMap wo8, wsp, win, win64, wout;
  CUtensorMap act[3];
  CUtensorMap res[2];
  CUtensorMap red[2];
  CUtensorMap psn;
};

__device__ __forceinline__ uint32_t smem_u32(const void* p) { return (uint32_t)__cvta_generic_to_shared(p); }
__device__ __forceinline__ void mbar_init(uint32_t bar, uint32_t cnt) { asm volatile("mbarrier.init.shared::cta.b64 [%0], %1;" ::"r"(bar), "r"(cnt)); }
__device__ __forceinline__ void mbar_arrive(uint32_t bar) { asm volatile("mbarrier.arrive.shared::cta.b64 _, [%0];" ::"r"(bar) : "memory"); }
__device__ __forceinline__ void mbar_wait(uint32_t bar, uint32_t parity) {
  asm volatile(
      "{\n.reg .pred p;\n.reg .u32 c;\nmov.u32 c, 0;\nLAB_WAIT:\n"
      "mbarrier.try_wait.parity.shared::cta.b64 p, [%0], %1;\n@p bra LAB_DONE;\n"
      "add.u32 c, c, 1;\nsetp.lt.u32 p, c, 0x100000;\n@p bra LAB_WAIT;\ntrap;\nLAB_DONE:\n}" ::"r"(bar), "r"(parity)
      : "memory");
}
__device__ __forceinline__ void mbar_wait_c(uint32_t bar, uint32_t parity) {
  asm volatile("{\n.reg .pred p;\nLAB_WAIT:\nmbarrier.try_wait.parity.shared::cta.b64 p, [%0], %1;\n@!p bra LAB_WAIT;\n}" ::"r"(bar), "r"(parity) : "memory");
}
__device__ __forceinline__ void flag_wait(const uint32_t* f, uint32_t target) {
  asm volatile(
      "{\n.reg .pred p;\n.reg .u32 c, v;\nmov.u32 c, 0;\nLAB_WAIT:\n"
      "ld.relaxed.gpu.global.u32 v, [%0];\nsub.u32 v, v, %1;\nsetp.ge.s32 p, v, 0;\n@p bra LAB_DONE;\n"
      "add.u32 c, c, 1;\nsetp.lt.u32 p, c, 0x400000;\n@p bra LAB_WAIT;\ntrap;\nLAB_DONE:\nfence.acquire.gpu;\n}" ::"l"(f), "r"(target)
      : "memory");
}
__device__ __forceinline__ void fence_gpu() { asm volatile("fence.acq_rel.gpu;" ::: "memory"); }
__device__ __forceinline__ void fence_async_g() { asm volatile("fence.proxy.async.global;" ::: "memory"); }
__device__ __forceinline__ void fence_async_s() { asm volatile("fence.proxy.async.shared::cta;" ::: "memory"); }
__device__ __forceinline__ uint32_t elect_one() {
  uint32_t p; asm volatile("{\n.reg .pred P;\nelect.sync _|P, 0xffffffff;\nselp.u32 %0, 1, 0, P;\n}" : "=r"(p)); return p;
}
__device__ __forceinline__ void expect_tx_p(uint32_t el, uint32_t bar, uint32_t bytes) {
  asm volatile("{\n.reg .pred P;\nsetp.ne.u32 P, %2, 0;\n@P mbarrier.arrive.expect_tx.shared::cta.b64 _, [%0], %1;\n}" ::"r"(bar), "r"(bytes), "r"(el) : "memory");
}
__device__ __forceinline__ void bulk_load_p(uint32_t el, uint32_t dst, const void* src, uint32_t bytes, uint32_t bar) {
  asm volatile("{\n.reg .pred P;\nsetp.ne.u32 P, %4, 0;\n@P cp.async.bulk.shared::cluster.global.mbarrier::complete_tx::bytes [%0], [%1], %2, [%3];\n}" ::"r"(dst), "l"(src), "r"(bytes), "r"(bar), "r"(el) : "memory");
}
__device__ __forceinline__ uint64_t policy_evict_first() { uint64_t p; asm("createpolicy.fractional.L2::evict_first.b64 %0, 1.0;" : "=l"(p)); return p; }
__device__ __forceinline__ void bulk_load_h(uint32_t el, uint32_t dst, const void* src, uint32_t bytes, uint32_t bar, bool ef, uint64_t pol) {
  if (ef) {
    asm volatile("{\n.reg .pred P;\nsetp.ne.u32 P, %4, 0;\n@P cp.async.bulk.shared::cluster.global.mbarrier::complete_tx::bytes.L2::cache_hint [%0], [%1], %2, [%3], %5;\n}" ::"r"(dst), "l"(src), "r"(bytes), "r"(bar), "r"(el), "l"(pol) : "memory");
  } else {
    asm volatile("{\n.reg .pred P;\nsetp.ne.u32 P, %4, 0;\n@P cp.async.bulk.shared::cluster.global.mbarrier::complete_tx::bytes [%0], [%1], %2, [%3];\n}" ::"r"(dst), "l"(src), "r"(bytes), "r"(bar), "r"(el) : "memory");
  }
}
__device__ __forceinline__ void bulk_mc_h(uint32_t el, uint32_t dst, const void* src, uint32_t bytes, uint32_t bar, bool ef, uint64_t pol) {
  if (ef) {
    asm volatile("{\n.reg .pred P;\nsetp.ne.u32 P, %4, 0;\n@P cp.async.bulk.shared::cluster.global.mbarrier::complete_tx::bytes.multicast::cluster.L2::cache_hint [%0], [%1], %2, [%3], %5, %6;\n}" ::"r"(dst), "l"(src), "r"(bytes), "r"(bar), "r"(el), "h"((uint16_t)3), "l"(pol) : "memory");
  } else {
    asm volatile("{\n.reg .pred P;\nsetp.ne.u32 P, %4, 0;\n@P cp.async.bulk.shared::cluster.global.mbarrier::complete_tx::bytes.multicast::cluster [%0], [%1], %2, [%3], %5;\n}" ::"r"(dst), "l"(src), "r"(bytes), "r"(bar), "r"(el), "h"((uint16_t)3) : "memory");
  }
}
__device__ __forceinline__ void tma3d_h(uint32_t el, uint32_t dst, const CUtensorMap* m, int c0, int c1, int c2, uint32_t bar, bool ef, uint64_t pol) {
  if (ef) {
    asm volatile("{\n.reg .pred P;\nsetp.ne.u32 P, %6, 0;\n@P cp.async.bulk.tensor.3d.shared::cluster.global.mbarrier::complete_tx::bytes.L2::cache_hint [%0], [%1, {%3, %4, %5}], [%2], %7;\n}" ::"r"(dst), "l"(m), "r"(bar), "r"(c0), "r"(c1), "r"(c2), "r"(el), "l"(pol) : "memory");
  } else {
    asm volatile("{\n.reg .pred P;\nsetp.ne.u32 P, %6, 0;\n@P cp.async.bulk.tensor.3d.shared::cluster.global.mbarrier::complete_tx::bytes [%0], [%1, {%3, %4, %5}], [%2];\n}" ::"r"(dst), "l"(m), "r"(bar), "r"(c0), "r"(c1), "r"(c2), "r"(el) : "memory");
  }
}
__device__ __forceinline__ void tma2d_mc_h(uint32_t el, uint32_t dst, const CUtensorMap* m, int c0, int c1, uint32_t bar, bool ef, uint64_t pol) {
  if (ef) {
    asm volatile("{\n.reg .pred P;\nsetp.ne.u32 P, %5, 0;\n@P cp.async.bulk.tensor.2d.shared::cluster.global.mbarrier::complete_tx::bytes.multicast::cluster.L2::cache_hint [%0], [%1, {%3, %4}], [%2], %6, %7;\n}" ::"r"(dst), "l"(m), "r"(bar), "r"(c0), "r"(c1), "r"(el), "h"((uint16_t)3), "l"(pol) : "memory");
  } else {
    asm volatile("{\n.reg .pred P;\nsetp.ne.u32 P, %5, 0;\n@P cp.async.bulk.tensor.2d.shared::cluster.global.mbarrier::complete_tx::bytes.multicast::cluster [%0], [%1, {%3, %4}], [%2], %6;\n}" ::"r"(dst), "l"(m), "r"(bar), "r"(c0), "r"(c1), "r"(el), "h"((uint16_t)3) : "memory");
  }
}
__device__ __forceinline__ void tma4d_mc(uint32_t el, uint32_t dst, const CUtensorMap* m, int c0, int c3, uint32_t bar, uint64_t pol) {
  asm volatile("{\n.reg .pred P;\nsetp.ne.u32 P, %5, 0;\n@P cp.async.bulk.tensor.4d.shared::cluster.global.mbarrier::complete_tx::bytes.multicast::cluster.L2::cache_hint [%0], [%1, {%3, 0, 0, %4}], [%2], %6, %7;\n}" ::"r"(dst), "l"(m), "r"(bar), "r"(c0), "r"(c3), "r"(el), "h"((uint16_t)3), "l"(pol) : "memory");
}
__device__ __forceinline__ void mbar_arrive_cluster(uint32_t addr) { asm volatile("mbarrier.arrive.shared::cluster.b64 _, [%0];" ::"r"(addr) : "memory"); }
__device__ __forceinline__ void mbar_arrive_cluster_if(bool c, uint32_t addr) {
  asm volatile("{\n.reg .pred P;\nsetp.ne.u32 P, %1, 0;\n@P mbarrier.arrive.shared::cluster.b64 _, [%0];\n}" ::"r"(addr), "r"((uint32_t)c) : "memory");
}
__device__ __forceinline__ void mbar_arrive_if(bool c, uint32_t addr) {
  asm volatile("{\n.reg .pred P;\nsetp.ne.u32 P, %1, 0;\n@P mbarrier.arrive.shared::cta.b64 _, [%0];\n}" ::"r"(addr), "r"((uint32_t)c) : "memory");
}
__device__ __forceinline__ uint32_t mapa(uint32_t addr, uint32_t rank) { uint32_t r; asm("mapa.shared::cluster.u32 %0, %1, %2;" : "=r"(r) : "r"(addr), "r"(rank)); return r; }
__device__ __forceinline__ void bulk_store_p(uint32_t el, void* dst, uint32_t src, uint32_t bytes) {
  asm volatile("{\n.reg .pred P;\nsetp.ne.u32 P, %3, 0;\n@P cp.async.bulk.global.shared::cta.bulk_group [%0], [%1], %2;\n}" ::"l"(dst), "r"(src), "r"(bytes), "r"(el) : "memory");
}
__device__ __forceinline__ void flag_release_p(uint32_t el, uint32_t* f) {
  asm volatile("{\n.reg .pred P;\nsetp.ne.u32 P, %1, 0;\n@P red.release.gpu.global.add.u32 [%0], 1;\n}" ::"l"(f), "r"(el) : "memory");
}
__device__ __forceinline__ void flag_add_p(uint32_t el, uint32_t* f) {
  asm volatile("{\n.reg .pred P;\nsetp.ne.u32 P, %1, 0;\n@P red.relaxed.gpu.global.add.u32 [%0], 1;\n}" ::"l"(f), "r"(el) : "memory");
}
__device__ __forceinline__ void prefetch_l2(const void* src, uint32_t bytes) { asm volatile("cp.async.bulk.prefetch.L2.global [%0], %1;" ::"l"(src), "r"(bytes) : "memory"); }
__device__ __forceinline__ void prefetch_map(const CUtensorMap* m) { asm volatile("prefetch.tensormap [%0];" ::"l"(m) : "memory"); }
__device__ __forceinline__ void wgmma_fence() { asm volatile("wgmma.fence.sync.aligned;" ::: "memory"); }
__device__ __forceinline__ void wgmma_commit() { asm volatile("wgmma.commit_group.sync.aligned;" ::: "memory"); }
template <int N> __device__ __forceinline__ void wgmma_wait() { asm volatile("wgmma.wait_group.sync.aligned %0;" ::"n"(N) : "memory"); }
__device__ __forceinline__ uint32_t dlo(uint32_t addr, uint32_t lbo) { return ((addr & 0x3FFFF) >> 4) + ((lbo >> 4) << 16); }
template <uint32_t SBO, uint32_t SWZ> __device__ __forceinline__ uint64_t dsc(uint32_t lo, uint32_t off) {
  uint64_t d; asm("mov.b64 %0, {%1, %2};" : "=l"(d) : "r"(lo + (off >> 4)), "n"((SBO >> 4) | (SWZ << 30))); return d;
}
__device__ __forceinline__ uint64_t dsc2(uint32_t lo, uint32_t off, uint32_t hi) {
  uint64_t d; asm("mov.b64 %0, {%1, %2};" : "=l"(d) : "r"(lo + (off >> 4)), "r"(hi)); return d;
}
__device__ __forceinline__ uint64_t dat(uint64_t d, uint32_t off, uint32_t one) { uint64_t r; asm("mad.wide.u32 %0, %1, %2, %3;" : "=l"(r) : "r"(one), "r"(off >> 4), "l"(d)); return r; }
__device__ __forceinline__ void dadd(uint64_t& d, uint32_t v) {
  asm("{\n.reg .b32 lo, hi;\nmov.b64 {lo, hi}, %0;\nadd.u32 lo, lo, %1;\nmov.b64 %0, {lo, hi};\n}" : "+l"(d) : "r"(v));
}
template <int R> __device__ __forceinline__ void reg_alloc() { asm volatile("setmaxnreg.inc.sync.aligned.u32 %0;" ::"n"(R)); }
template <int R> __device__ __forceinline__ void reg_dealloc() { asm volatile("setmaxnreg.dec.sync.aligned.u32 %0;" ::"n"(R)); }
__device__ __forceinline__ void bar_sync(int id, int n) { asm volatile("bar.sync %0, %1;" ::"r"(id), "r"(n) : "memory"); }
__device__ __forceinline__ void bar_arrive(int id, int n) { asm volatile("bar.arrive %0, %1;" ::"r"(id), "r"(n) : "memory"); }
__device__ __forceinline__ void ldsm4(uint32_t* r, uint32_t addr) {
  asm volatile("ldmatrix.sync.aligned.m8n8.x4.shared.b16 {%0,%1,%2,%3}, [%4];" : "=r"(r[0]), "=r"(r[1]), "=r"(r[2]), "=r"(r[3]) : "r"(addr) : "memory");
}
__device__ __forceinline__ uint32_t movm(uint32_t a) { uint32_t d; asm volatile("movmatrix.sync.aligned.m8n8.trans.b16 %0, %1;" : "=r"(d) : "r"(a)); return d; }
__device__ __forceinline__ void mma16(float* c, uint32_t a0, uint32_t a1, uint32_t a2, uint32_t a3, uint32_t b0, uint32_t b1) {
  asm volatile("mma.sync.aligned.m16n8k16.row.col.f32.bf16.bf16.f32 {%0,%1,%2,%3}, {%4,%5,%6,%7}, {%8,%9}, {%10,%10,%10,%10};"
               : "=f"(c[0]), "=f"(c[1]), "=f"(c[2]), "=f"(c[3]) : "r"(a0), "r"(a1), "r"(a2), "r"(a3), "r"(b0), "r"(b1), "f"(0.f));
}
__device__ __forceinline__ void mma8(float* c, uint32_t a0, uint32_t a1, uint32_t b0) {
  asm volatile("mma.sync.aligned.m16n8k8.row.col.f32.bf16.bf16.f32 {%0,%1,%2,%3}, {%4,%5}, {%6}, {%0,%1,%2,%3};"
               : "+f"(c[0]), "+f"(c[1]), "+f"(c[2]), "+f"(c[3]) : "r"(a0), "r"(a1), "r"(b0));
}
__device__ __forceinline__ uint32_t pack2(float lo, float hi) { uint32_t r; asm("cvt.rn.bf16x2.f32 %0, %1, %2;" : "=r"(r) : "f"(hi), "f"(lo)); return r; }
__device__ __forceinline__ float blo(uint32_t v) { return __uint_as_float(v << 16); }
__device__ __forceinline__ float bhi(uint32_t v) { return __uint_as_float(v & 0xffff0000u); }
__device__ __forceinline__ float tanh_fast(float x) { float y; asm("tanh.approx.f32 %0, %1;" : "=f"(y) : "f"(x)); return y; }
__device__ __forceinline__ float rcp_fast(float x) { float y; asm("rcp.approx.ftz.f32 %0, %1;" : "=f"(y) : "f"(x)); return y; }
__device__ __forceinline__ float ex2(float x) { float y; asm("ex2.approx.ftz.f32 %0, %1;" : "=f"(y) : "f"(x)); return y; }
__device__ __forceinline__ float qsum(float v) { v += __shfl_xor_sync(~0u, v, 1); v += __shfl_xor_sync(~0u, v, 2); return v; }
__device__ __forceinline__ float qmax(float v) { v = fmaxf(v, __shfl_xor_sync(~0u, v, 1)); v = fmaxf(v, __shfl_xor_sync(~0u, v, 2)); return v; }
__device__ __forceinline__ void stg32(void* p, uint32_t v) { asm volatile("st.global.u32 [%0], %1;" ::"l"(p), "r"(v) : "memory"); }
__device__ __forceinline__ void stg128(void* p, uint32_t a, uint32_t b, uint32_t c, uint32_t d) { asm volatile("st.global.v4.u32 [%0], {%1,%2,%3,%4};" ::"l"(p), "r"(a), "r"(b), "r"(c), "r"(d) : "memory"); }
__device__ __forceinline__ uint32_t ldcg32(const void* p) { uint32_t v; asm volatile("ld.global.L1::no_allocate.u32 %0, [%1];" : "=r"(v) : "l"(p) : "memory"); return v; }
__device__ __forceinline__ uint32_t ldgpu32(const void* p) { uint32_t v; asm volatile("ld.relaxed.gpu.global.u32 %0, [%1];" : "=r"(v) : "l"(p) : "memory"); return v; }
__device__ __forceinline__ uint32_t ldca32(const void* p) { uint32_t v; asm volatile("ld.global.ca.u32 %0, [%1];" : "=r"(v) : "l"(p) : "memory"); return v; }
__device__ __forceinline__ void stg128_if(bool c, void* p, uint32_t a, uint32_t b, uint32_t cc, uint32_t d) {
  asm volatile("{\n.reg .pred P;\nsetp.ne.u32 P, %5, 0;\n@P st.global.v4.u32 [%0], {%1,%2,%3,%4};\n}" ::"l"(p), "r"(a), "r"(b), "r"(cc), "r"(d), "r"((uint32_t)c) : "memory");
}
__device__ __forceinline__ uint2 lds64(uint32_t a) { uint2 v; asm volatile("ld.shared.v2.u32 {%0,%1}, [%2];" : "=r"(v.x), "=r"(v.y) : "r"(a) : "memory"); return v; }
__device__ __forceinline__ uint4 ldcg128(const void* p) { uint4 v; asm volatile("ld.global.cg.v4.u32 {%0,%1,%2,%3}, [%4];" : "=r"(v.x), "=r"(v.y), "=r"(v.z), "=r"(v.w) : "l"(p) : "memory"); return v; }
__device__ __forceinline__ uint32_t ldnc16(const void* p) { uint16_t v; asm volatile("ld.global.nc.u16 %0, [%1];" : "=h"(v) : "l"(p)); return v; }
__device__ __forceinline__ uint4 ldnc128(const void* p) { uint4 v; asm volatile("ld.global.nc.v4.u32 {%0,%1,%2,%3}, [%4];" : "=r"(v.x), "=r"(v.y), "=r"(v.z), "=r"(v.w) : "l"(p)); return v; }
__device__ __forceinline__ uint32_t hsub2(uint32_t a, uint32_t b) { uint32_t d; asm("sub.rn.bf16x2 %0, %1, %2;" : "=r"(d) : "r"(a), "r"(b)); return d; }
__device__ __forceinline__ void stg32_if(bool c, void* p, uint32_t v) {
  asm volatile("{\n.reg .pred P;\nsetp.ne.u32 P, %2, 0;\n@P st.global.u32 [%0], %1;\n}" ::"l"(p), "r"(v), "r"((uint32_t)c) : "memory");
}
__device__ __forceinline__ uint32_t hmul2(uint32_t a, uint32_t b) { uint32_t d; asm("mul.rn.bf16x2 %0, %1, %2;" : "=r"(d) : "r"(a), "r"(b)); return d; }
__device__ __forceinline__ void sts32(uint32_t a, uint32_t v) { asm volatile("st.shared.u32 [%0], %1;" ::"r"(a), "r"(v) : "memory"); }
__device__ __forceinline__ uint32_t lds32(uint32_t a) { uint32_t v; asm volatile("ld.shared.u32 %0, [%1];" : "=r"(v) : "r"(a) : "memory"); return v; }
__device__ __forceinline__ void sts128(uint32_t a, uint32_t x, uint32_t y, uint32_t z, uint32_t w) { asm volatile("st.shared.v4.u32 [%0], {%1,%2,%3,%4};" ::"r"(a), "r"(x), "r"(y), "r"(z), "r"(w) : "memory"); }
__device__ __forceinline__ uint4 lds128(uint32_t a) { uint4 v; asm volatile("ld.shared.v4.u32 {%0,%1,%2,%3}, [%4];" : "=r"(v.x), "=r"(v.y), "=r"(v.z), "=r"(v.w) : "r"(a) : "memory"); return v; }
__device__ __forceinline__ void ll_st64(uint2* p, uint32_t v, uint32_t tag) {
  asm volatile("{\n.reg .b64 r;\nmov.b64 r, {%1,%2};\nst.relaxed.gpu.global.b64 [%0], r;\n}" ::"l"(p), "r"(v), "r"(tag) : "memory");
}
__device__ __forceinline__ uint2 ll_ld64(const uint2* p) {
  uint2 v; asm volatile("{\n.reg .b64 r;\nld.relaxed.gpu.global.b64 r, [%2];\nmov.b64 {%0,%1}, r;\n}" : "=r"(v.x), "=r"(v.y) : "l"(p) : "memory"); return v;
}
__device__ __forceinline__ void ll_st128(uint4* p, float a, float b, uint32_t tag, float c = 0.f) {
  asm volatile("{\n.reg .b128 r;\n.reg .b64 lo, hi;\nmov.b64 lo, {%1,%2};\nmov.b64 hi, {%3,%4};\nmov.b128 r, {lo, hi};\nst.relaxed.gpu.global.b128 [%0], r;\n}" ::"l"(p), "r"(__float_as_uint(a)), "r"(__float_as_uint(b)), "r"(tag), "r"(__float_as_uint(c)) : "memory");
}
__device__ __forceinline__ uint4 ll_ld128(const uint4* p) {
  uint4 v; asm volatile("{\n.reg .b128 r;\n.reg .b64 lo, hi;\nld.relaxed.gpu.global.b128 r, [%4];\nmov.b128 {lo, hi}, r;\nmov.b64 {%0,%1}, lo;\nmov.b64 {%2,%3}, hi;\n}" : "=r"(v.x), "=r"(v.y), "=r"(v.z), "=r"(v.w) : "l"(p) : "memory"); return v;
}
__device__ __forceinline__ void publish_p(uint32_t el, uint32_t* f) {
  asm volatile("{\n.reg .pred P;\nsetp.ne.u32 P, %1, 0;\n@P cp.async.bulk.commit_group;\n@P cp.async.bulk.wait_group 0;\n@P red.release.gpu.global.add.u32 [%0], 1;\n}" ::"l"(f), "r"(el) : "memory");
}
__device__ __forceinline__ void tma3d_red_p(uint32_t el, const CUtensorMap* m, int c0, int c1, int c2, uint32_t src) {
  asm volatile("{\n.reg .pred P;\nsetp.ne.u32 P, %5, 0;\n@P cp.reduce.async.bulk.tensor.3d.global.shared::cta.add.tile.bulk_group [%0, {%2, %3, %4}], [%1];\n@P cp.async.bulk.commit_group;\n}" ::"l"(m), "r"(src), "r"(c0), "r"(c1), "r"(c2), "r"(el) : "memory");
}
__device__ __forceinline__ void stsm4(uint32_t addr, uint32_t a, uint32_t b, uint32_t c, uint32_t d) {
  asm volatile("stmatrix.sync.aligned.m8n8.x4.shared.b16 [%0], {%1,%2,%3,%4};" ::"r"(addr), "r"(a), "r"(b), "r"(c), "r"(d) : "memory");
}
__device__ __forceinline__ void sts64(uint32_t a, uint32_t x, uint32_t y) { asm volatile("st.shared.v2.u32 [%0], {%1,%2};" ::"r"(a), "r"(x), "r"(y) : "memory"); }
__device__ __forceinline__ void ll_st128_if(bool on, uint4* p, float a, float b, uint32_t tag) {
  asm volatile("{\n.reg .pred P;\n.reg .b128 r;\n.reg .b64 lo, hi;\nsetp.ne.u32 P, %4, 0;\nmov.b64 lo, {%1,%2};\nmov.b64 hi, {%3,%3};\nmov.b128 r, {lo, hi};\n@P st.relaxed.gpu.global.b128 [%0], r;\n}" ::"l"(p), "r"(__float_as_uint(a)), "r"(__float_as_uint(b)), "r"(tag), "r"((uint32_t)on) : "memory");
}
__device__ __forceinline__ uint4 ldnc128_if(bool c, const void* p) {
  uint4 v = make_uint4(0u, 0u, 0u, 0u);
  asm volatile("{\n.reg .pred P;\nsetp.ne.u32 P, %5, 0;\n@P ld.global.nc.v4.u32 {%0,%1,%2,%3}, [%4];\n}" : "+r"(v.x), "+r"(v.y), "+r"(v.z), "+r"(v.w) : "l"(p), "r"((uint32_t)c));
  return v;
}
__device__ __forceinline__ uint32_t hfma2(uint32_t a, uint32_t b, uint32_t c) { uint32_t d; asm("fma.rn.bf16x2 %0, %1, %2, %3;" : "=r"(d) : "r"(a), "r"(b), "r"(c)); return d; }
__device__ __forceinline__ float2 lds64f(uint32_t a) { float2 v; asm volatile("ld.shared.v2.f32 {%0,%1}, [%2];" : "=f"(v.x), "=f"(v.y) : "r"(a) : "memory"); return v; }
#define TRC(cond, role, idx) do {} while (0)
#define TRV(role, idx, v) do {} while (0)

#define ACLK_INIT do {} while (0)
#define ACLK(i) do {} while (0)
#define ACLK_OUT do {} while (0)
#define QCLK(i) do {} while (0)
#define PH 1
#define RCLK(i) do {} while (0)
#define RCLK_INIT do {} while (0)
#define RCLK_OUT do {} while (0)
#define SCLK(i) do {} while (0)
#define HCLK(i) do {} while (0)
#define MCLK(c, i) do {} while (0)
#define CKK(i) do {} while (0)
#define CKK_OUT do {} while (0)
#define PL 1
#define PCLK(i) do {} while (0)
#define PQ 1
#define CLK_INIT do {} while (0)
#define CLK(i) do {} while (0)
#define CLK_OUT do {} while (0)

__device__ __forceinline__ void wgmma_ss_n216(float* d, uint64_t da, uint64_t db, int scaleD) {
  asm volatile("{\n.reg .pred p;\nsetp.ne.b32 p, %110, 0;\nwgmma.mma_async.sync.aligned.m64n216k16.f32.bf16.bf16 "
    "{%0,%1,%2,%3,%4,%5,%6,%7,%8,%9,%10,%11,%12,%13,%14,%15,%16,%17,%18,%19,%20,%21,%22,%23,%24,%25,%26,%27,%28,%29,%30,%31,%32,%33,%34,%35,%36,%37,%38,%39,%40,%41,%42,%43,%44,%45,%46,%47,%48,%49,%50,%51,%52,%53,%54,%55,%56,%57,%58,%59,%60,%61,%62,%63,%64,%65,%66,%67,%68,%69,%70,%71,%72,%73,%74,%75,%76,%77,%78,%79,%80,%81,%82,%83,%84,%85,%86,%87,%88,%89,%90,%91,%92,%93,%94,%95,%96,%97,%98,%99,%100,%101,%102,%103,%104,%105,%106,%107}, "
    "%108, %109, p, 1, 1, 0, 1;\n}\n"
    : "+f"(d[0]), "+f"(d[1]), "+f"(d[2]), "+f"(d[3]), "+f"(d[4]), "+f"(d[5]), "+f"(d[6]), "+f"(d[7]), "+f"(d[8]), "+f"(d[9]), "+f"(d[10]), "+f"(d[11]), "+f"(d[12]), "+f"(d[13]), "+f"(d[14]), "+f"(d[15]), "+f"(d[16]), "+f"(d[17]), "+f"(d[18]), "+f"(d[19]), "+f"(d[20]), "+f"(d[21]), "+f"(d[22]), "+f"(d[23]), "+f"(d[24]), "+f"(d[25]), "+f"(d[26]), "+f"(d[27]), "+f"(d[28]), "+f"(d[29]), "+f"(d[30]), "+f"(d[31]), "+f"(d[32]), "+f"(d[33]), "+f"(d[34]), "+f"(d[35]), "+f"(d[36]), "+f"(d[37]), "+f"(d[38]), "+f"(d[39]), "+f"(d[40]), "+f"(d[41]), "+f"(d[42]), "+f"(d[43]), "+f"(d[44]), "+f"(d[45]), "+f"(d[46]), "+f"(d[47]), "+f"(d[48]), "+f"(d[49]), "+f"(d[50]), "+f"(d[51]), "+f"(d[52]), "+f"(d[53]), "+f"(d[54]), "+f"(d[55]), "+f"(d[56]), "+f"(d[57]), "+f"(d[58]), "+f"(d[59]), "+f"(d[60]), "+f"(d[61]), "+f"(d[62]), "+f"(d[63]), "+f"(d[64]), "+f"(d[65]), "+f"(d[66]), "+f"(d[67]), "+f"(d[68]), "+f"(d[69]), "+f"(d[70]), "+f"(d[71]), "+f"(d[72]), "+f"(d[73]), "+f"(d[74]), "+f"(d[75]), "+f"(d[76]), "+f"(d[77]), "+f"(d[78]), "+f"(d[79]), "+f"(d[80]), "+f"(d[81]), "+f"(d[82]), "+f"(d[83]), "+f"(d[84]), "+f"(d[85]), "+f"(d[86]), "+f"(d[87]), "+f"(d[88]), "+f"(d[89]), "+f"(d[90]), "+f"(d[91]), "+f"(d[92]), "+f"(d[93]), "+f"(d[94]), "+f"(d[95]), "+f"(d[96]), "+f"(d[97]), "+f"(d[98]), "+f"(d[99]), "+f"(d[100]), "+f"(d[101]), "+f"(d[102]), "+f"(d[103]), "+f"(d[104]), "+f"(d[105]), "+f"(d[106]), "+f"(d[107])
    : "l"(da), "l"(db), "r"(scaleD));
}
__device__ __forceinline__ void wgmma_ss_n72(float* d, uint64_t da, uint64_t db, int scaleD) {
  asm volatile("{\n.reg .pred p;\nsetp.ne.b32 p, %38, 0;\nwgmma.mma_async.sync.aligned.m64n72k16.f32.bf16.bf16 "
    "{%0,%1,%2,%3,%4,%5,%6,%7,%8,%9,%10,%11,%12,%13,%14,%15,%16,%17,%18,%19,%20,%21,%22,%23,%24,%25,%26,%27,%28,%29,%30,%31,%32,%33,%34,%35}, "
    "%36, %37, p, 1, 1, 0, 1;\n}\n"
    : "+f"(d[0]), "+f"(d[1]), "+f"(d[2]), "+f"(d[3]), "+f"(d[4]), "+f"(d[5]), "+f"(d[6]), "+f"(d[7]), "+f"(d[8]), "+f"(d[9]), "+f"(d[10]), "+f"(d[11]), "+f"(d[12]), "+f"(d[13]), "+f"(d[14]), "+f"(d[15]), "+f"(d[16]), "+f"(d[17]), "+f"(d[18]), "+f"(d[19]), "+f"(d[20]), "+f"(d[21]), "+f"(d[22]), "+f"(d[23]), "+f"(d[24]), "+f"(d[25]), "+f"(d[26]), "+f"(d[27]), "+f"(d[28]), "+f"(d[29]), "+f"(d[30]), "+f"(d[31]), "+f"(d[32]), "+f"(d[33]), "+f"(d[34]), "+f"(d[35])
    : "l"(da), "l"(db), "r"(scaleD));
}
__device__ __forceinline__ void wgmma_rs_n144(float* d, const uint32_t* a, uint64_t db, int scaleD) {
  asm volatile("{\n.reg .pred p;\nsetp.ne.b32 p, %77, 0;\nwgmma.mma_async.sync.aligned.m64n144k16.f32.bf16.bf16 "
    "{%0,%1,%2,%3,%4,%5,%6,%7,%8,%9,%10,%11,%12,%13,%14,%15,%16,%17,%18,%19,%20,%21,%22,%23,%24,%25,%26,%27,%28,%29,%30,%31,%32,%33,%34,%35,%36,%37,%38,%39,%40,%41,%42,%43,%44,%45,%46,%47,%48,%49,%50,%51,%52,%53,%54,%55,%56,%57,%58,%59,%60,%61,%62,%63,%64,%65,%66,%67,%68,%69,%70,%71}, "
    "{%72,%73,%74,%75}, %76, p, 1, 1, 1;\n}\n"
    : "+f"(d[0]), "+f"(d[1]), "+f"(d[2]), "+f"(d[3]), "+f"(d[4]), "+f"(d[5]), "+f"(d[6]), "+f"(d[7]), "+f"(d[8]), "+f"(d[9]), "+f"(d[10]), "+f"(d[11]), "+f"(d[12]), "+f"(d[13]), "+f"(d[14]), "+f"(d[15]), "+f"(d[16]), "+f"(d[17]), "+f"(d[18]), "+f"(d[19]), "+f"(d[20]), "+f"(d[21]), "+f"(d[22]), "+f"(d[23]), "+f"(d[24]), "+f"(d[25]), "+f"(d[26]), "+f"(d[27]), "+f"(d[28]), "+f"(d[29]), "+f"(d[30]), "+f"(d[31]), "+f"(d[32]), "+f"(d[33]), "+f"(d[34]), "+f"(d[35]), "+f"(d[36]), "+f"(d[37]), "+f"(d[38]), "+f"(d[39]), "+f"(d[40]), "+f"(d[41]), "+f"(d[42]), "+f"(d[43]), "+f"(d[44]), "+f"(d[45]), "+f"(d[46]), "+f"(d[47]), "+f"(d[48]), "+f"(d[49]), "+f"(d[50]), "+f"(d[51]), "+f"(d[52]), "+f"(d[53]), "+f"(d[54]), "+f"(d[55]), "+f"(d[56]), "+f"(d[57]), "+f"(d[58]), "+f"(d[59]), "+f"(d[60]), "+f"(d[61]), "+f"(d[62]), "+f"(d[63]), "+f"(d[64]), "+f"(d[65]), "+f"(d[66]), "+f"(d[67]), "+f"(d[68]), "+f"(d[69]), "+f"(d[70]), "+f"(d[71])
    : "r"(a[0]), "r"(a[1]), "r"(a[2]), "r"(a[3]), "l"(db), "r"(scaleD));
}
__device__ __forceinline__ void wgmma_rs_n64(float* d, const uint32_t* a, uint64_t db, int scaleD) {
  asm volatile("{\n.reg .pred p;\nsetp.ne.b32 p, %37, 0;\nwgmma.mma_async.sync.aligned.m64n64k16.f32.bf16.bf16 "
    "{%0,%1,%2,%3,%4,%5,%6,%7,%8,%9,%10,%11,%12,%13,%14,%15,%16,%17,%18,%19,%20,%21,%22,%23,%24,%25,%26,%27,%28,%29,%30,%31}, "
    "{%32,%33,%34,%35}, %36, p, 1, 1, 1;\n}\n"
    : "+f"(d[0]), "+f"(d[1]), "+f"(d[2]), "+f"(d[3]), "+f"(d[4]), "+f"(d[5]), "+f"(d[6]), "+f"(d[7]), "+f"(d[8]), "+f"(d[9]), "+f"(d[10]), "+f"(d[11]), "+f"(d[12]), "+f"(d[13]), "+f"(d[14]), "+f"(d[15]), "+f"(d[16]), "+f"(d[17]), "+f"(d[18]), "+f"(d[19]), "+f"(d[20]), "+f"(d[21]), "+f"(d[22]), "+f"(d[23]), "+f"(d[24]), "+f"(d[25]), "+f"(d[26]), "+f"(d[27]), "+f"(d[28]), "+f"(d[29]), "+f"(d[30]), "+f"(d[31])
    : "r"(a[0]), "r"(a[1]), "r"(a[2]), "r"(a[3]), "l"(db), "r"(scaleD));
}

template <int V> struct Int { static constexpr int value = V; };
struct Cur {
  uint32_t s, ph;
  __device__ __forceinline__ void next() { if (++s == NST) { s = 0; ph ^= 1; } }
};

__device__ __forceinline__ uint8_t* z1_block(int rb, int w, int j) { return g_Z + (rb * 16 + w * 8 + j) * ZB; }
__device__ __forceinline__ uint8_t* o_block(int rb, int w) { return g_O + (rb * 2 + w) * (2 * ZB); }
__device__ __forceinline__ uint8_t* z2_block(int kb, int j) { return g_Z + (256 + kb * 8 + j) * ZB; }
__device__ __forceinline__ void combine8(float m0, float q0, float m1, float q1, float n, float eps, float& mean, float& rstd) {
  mean = qsum(m0 + m1) * 0.125f;
  float d0 = m0 - mean, d1 = m1 - mean;
  float M2 = qsum(q0 + q1 + n * (d0 * d0 + d1 * d1));
  rstd = rsqrtf(fmaf(M2, 0.125f / n, eps));
}
__device__ __forceinline__ void stat_get(const uint4* zs, uint32_t tag, float n, float eps, float& m0, float& r0, float& m1, float& r1) {
  uint4 a0, a1, b0, b1;
#pragma unroll 1
  for (int it = 0; it < (1 << 20); it++) {
    a0 = ll_ld128(zs); a1 = ll_ld128(zs + 64); b0 = ll_ld128(zs + 8); b1 = ll_ld128(zs + 72);
    if (__all_sync(~0u, a0.z == tag && a1.z == tag && b0.z == tag && b1.z == tag)) break;
  }
  combine8(__uint_as_float(a0.x), __uint_as_float(a0.y), __uint_as_float(a1.x), __uint_as_float(a1.y), n, eps, m0, r0);
  combine8(__uint_as_float(b0.x), __uint_as_float(b0.y), __uint_as_float(b1.x), __uint_as_float(b1.y), n, eps, m1, r1);
}

__device__ __forceinline__ void rows_fetch(uint32_t el, uint32_t xr, const uint8_t* src, uint32_t bar) {
  expect_tx_p(el, bar, 9216);
#pragma unroll 1
  for (int r = 0; r < 8; r++) bulk_load_p(el, xr + r * 1152, src + r * (DM * 4), 1152, bar);
}
__device__ __forceinline__ void rows_stats(uint32_t xr, uint4* dst, uint32_t tag, int lane) {
  float s[2] = {0.f, 0.f}, q[4] = {0.f, 0.f, 0.f, 0.f};
  const uint32_t a0 = xr + (lane >> 2) * 1152 + (((lane & 3) * 2) ^ (lane >> 2)) * 16;
  uint4 n0 = lds128(a0), n1 = lds128(a0 ^ 16);
#pragma unroll 1
  for (int e = 1; e <= 9; e++) {
    const uint32_t x[8] = {n0.x, n0.y, n0.z, n0.w, n1.x, n1.y, n1.z, n1.w};
    if (e < 9) { n0 = lds128(a0 + e * 128); n1 = lds128((a0 ^ 16) + e * 128); }
#pragma unroll
    for (int u = 0; u < 8; u++) {
      const float lo = blo(x[u]), hi = bhi(x[u]);
      s[u & 1] += lo + hi; q[(u & 1) * 2] = fmaf(lo, lo, q[(u & 1) * 2]); q[(u & 1) * 2 + 1] = fmaf(hi, hi, q[(u & 1) * 2 + 1]);
    }
  }
  const float sx = s[0] + s[1], sq = (q[0] + q[1]) + (q[2] + q[3]);
  const float m = qsum(sx) * (-1.f / DM), r = rsqrtf(fmaxf(fmaf(qsum(sq), 1.f / DM, -m * m), 0.f) + LN_EPS);
  if ((lane & 3) == 0) ll_st128(dst + (lane >> 2) * 2, m, r, tag);
}

__device__ __forceinline__ void poison(uint32_t el, uint32_t src, const CUtensorMap* m, int rb, int j, int lane) {
#pragma unroll 1
  for (int u = lane; u < 72; u += 32) sts128(src + u * 16, POISON, POISON, POISON, POISON);
  fence_async_s();
  __syncwarp();
#pragma unroll 1
  for (int u = 0; u < 16; u++) {
    __nanosleep(NAP);
    bulk_store_p(el, o_block(rb, u >> 3) + j * 9216 + (u & 7) * 1152, src, 1152);
    asm volatile("{\n.reg .pred P;\nsetp.ne.u32 P, %5, 0;\n@P cp.async.bulk.tensor.3d.global.shared::cta.tile.bulk_group [%0, {%2, %3, %4}], [%1];\n}" ::"l"(m), "r"(src), "r"((j & 6) * 72), "r"(rb * 64 + u * 4), "r"(j & 1), "r"(el) : "memory");
  }
}
__device__ __forceinline__ void mma16acc(float* c, const uint32_t* a, uint32_t b0, uint32_t b1) {
  asm volatile("mma.sync.aligned.m16n8k16.row.col.f32.bf16.bf16.f32 {%0,%1,%2,%3}, {%4,%5,%6,%7}, {%8,%9}, {%0,%1,%2,%3};"
               : "+f"(c[0]), "+f"(c[1]), "+f"(c[2]), "+f"(c[3]) : "r"(a[0]), "r"(a[1]), "r"(a[2]), "r"(a[3]), "r"(b0), "r"(b1));
}
template <int KS, int NG, int AK, int AH, int BK, int BG, class F> __device__ __forceinline__ void redo(float* acc, const uint8_t* pa, const uint8_t* pb, F f) {
#pragma unroll 1
  for (int k = 0; k < 36; k += KS) {
    uint32_t a[4 * KS], b[2 * KS][NG];
#pragma unroll 1
    for (int it = 0; it < (1 << 20); it++) {
      bool ok = true;
#pragma unroll
      for (int e = 0; e < 4 * KS; e++) a[e] = ldgpu32(pa + (e >> 1) * AK + (e & 1) * AH);
#pragma unroll
      for (int e = 0; e < 2 * KS * NG; e++) b[e / NG][e % NG] = ldca32(pb + (e / NG) * BK + (e % NG) * BG);
#pragma unroll
      for (int e = 0; e < 4 * KS; e++) ok = ok && a[e] != POISON;
      if (__all_sync(~0u, ok)) break;
    }
#pragma unroll
    for (int e = 0; e < KS; e++) f(a + 4 * e, k + e);
#pragma unroll
    for (int e = 0; e < KS * NG; e++) mma16acc(acc + 4 * (e % NG), a + 4 * (e / NG), movm(b[2 * (e / NG)][e % NG]), movm(b[2 * (e / NG) + 1][e % NG]));
    pa += 2 * KS * AK; pb += 2 * KS * BK;
  }
}
__device__ __forceinline__ bool any_nan(float a, float b) {
  return __any_sync(~0u, a != a || b != b);
}

__global__ void __cluster_dims__(2, 1, 1) __launch_bounds__(384, 1) mega_kernel(const __grid_constant__ Params P) {
  extern __shared__ __align__(1024) uint8_t smem_raw[];
  uint32_t ckk[8];
  (void)ckk;
  CKK(0);
  const uint32_t sb = smem_u32(smem_raw);
  const uint32_t bars = sb + SM_BAR;
  const int tid = threadIdx.x;
  int lane = tid & 31;
  const int wid = __shfl_sync(~0u, tid >> 5, 0);
  const int cl = blockIdx.x >> 1, tp = cl - 36, t7 = (tp * 37) >> 8;
  const int bid = (cl < 4 ? cl * 8 + 32 : tp < 0 ? cl - 4 : cl < 64 ? tp + t7 + 33 : cl) * 2 + (blockIdx.x & 1);
  if (bid >= NCTA) return;
  const int rb = bid & 15, j = bid >> 4;
  { const bool tr = (tid & 127) == 0 && tid < 256; const int w = tid >> 7; (void)tr; (void)w; TRC(tr, w, 0); }
  CKK(1);
  uint4 wv[5];
  const uint8_t* wsrc;
  {
    const int n8 = min(tid >> 3, 26), part = n8 / 9;
    const uint8_t* src = (const uint8_t*)P.wqkv + (8 * rb + (tid & 7)) * (3 * DM * 2) + (part * (DM - 72) + 72 * j + 8 * n8) * 2;
#pragma unroll
    for (int u = 0; u < SPL; u++) wv[u] = ldnc128_if(tid < 216, src + u * (128 * 3 * DM * 2));
    wsrc = src;
  }
  CKK(2);
  if (tid == 352) {
    for (int s = 0; s < (int)NST; s++) {
      mbar_init(bars + B_FULL + s * 8, 1); mbar_init(bars + B_EMPTY + s * 8, 16);
      mbar_init(bars + B_FULLA + s * 8, 1); mbar_init(bars + B_FULLA + 32 + s * 8, 1);
      mbar_init(bars + B_RES + s * 8, 1); mbar_init(bars + B_RT + s * 8, 1); mbar_init(bars + B_AD + s * 8, 2);
    }
    mbar_init(bars + B_IMG, 8); mbar_init(bars + B_RES + 8, 8); mbar_init(bars + B_WOI, 1); mbar_init(bars + B_GATE3, 3); mbar_init(bars + B_Z1, 1); mbar_init(bars + B_ZB, 1); mbar_init(bars + B_LAG, 4);
    mbar_init(bars + B_XS, 1); mbar_init(bars + B_XS + 8, 1); mbar_init(bars + B_RT1, 1); mbar_init(bars + B_XRW, 1); mbar_init(bars + B_XRW + 8, 1);
    for (int e = 0; e < 2 * EV_N; e++) mbar_init(bars + B_EVT + e * 8, 4);
    asm volatile("fence.mbarrier_init.release.cluster;" ::: "memory");
  }
  if (tid == 320) {
#pragma unroll
    for (int e = 0; e < 28; e++) mbar_init(bars + B_FA3 + e * 8, e < 18 ? 1 : 4);
    asm volatile("fence.mbarrier_init.release.cluster;" ::: "memory");
  }
  __syncthreads();

  if (wid >= 8) {
    reg_dealloc<40>();
    const uint32_t el = elect_one();
    const uint64_t pol = policy_evict_first();
    uint32_t* const fj = g_flags + FJ + j * 32;
    if (wid == 8) {
#pragma unroll 1
      for (int i = 0; i < 12; i++) if (el) prefetch_map(&P.act[0] + (i < 7 ? i : i - 12));
      const uint32_t epoch = ldcg32(fj + FJ_EP + rb);
      Cur c{0, 1};
      const uint32_t rk = bid & 1;
      uint32_t st, full;
      auto slot = [&](uint32_t bytes) {
        st = sb + c.s * ST_BYTES; full = bars + B_FULL + c.s * 8;
        mbar_wait(full, c.ph);
        expect_tx_p(el, full, bytes);
        mbar_wait(full - B_FULL + B_EMPTY, c.ph);
      };
#pragma unroll 1
      for (int L = 0; L < 2; L++) {
#pragma unroll 1
        for (int i = 0; i < 14; i++) {
          if (L == 0 && (i == 0 || i == 2 * SPL || i == 9)) {
            flag_wait(fj + (i == 9 ? FJ_WO : i == 2 * SPL ? FJ_WQ : FJ_WQ0), (epoch + 1) * 16);
            if (i == 9) flag_wait(g_flags + FJ + (j ^ 1) * 32 + FJ_WO, (epoch + 1) * 16);
            fence_async_g();
            TRC(el, 2, i == 9 ? 46 : i ? 47 : 45);
          }
          const uint32_t hb = i < 9 ? 13824 : i < 13 ? 18432 : 9216, o = ST_B + rk * (i < 9 ? 13824 : 18432);
          const uint8_t* src = i < 9 ? g_WQ + j * WQ_SL + i * 27648 + rk * 13824 : g_WO + ((j & 6) + rk) * WO_SL + (i - 9) * 18432;
          slot(2 * hb);
          bulk_mc_h(el, st + o, src, hb, full, true, pol);
          c.next();
        }
#pragma unroll 1
        for (int i = 0; i < 18; i++) {
          const int p = i >> 1, col = p == 4 ? (9 * j + ((j & 1) ? 0 : 8)) * 32 : (((9 * j + 1) >> 1) + (p < 4 ? p + 36 : p - 5)) * 64;
          if (i & 1) {
            slot(2 * ZB);
          } else {
            st = sb + c.s * ST_BYTES; full = bars + B_FULL + ((c.s + 1) & 3) * 8;
            mbar_wait(bars + B_EMPTY + c.s * 8, c.ph);
          }
          tma4d_mc(el, st + ST_B + rk * 18432, p == 4 ? &P.win : &P.win64, col, (i & 1) * 36 + rk * 18, full, pol);
          if (el && !(i & 1)) mbar_arrive(bars + B_FULL + c.s * 8);
          c.next();
        }
        TRC(el, 2, L * 16 + 6);
        flag_wait(fj + FJ_ZN + L, (epoch + 1) * 16);
        fence_async_g();
        TRC(el, 2, L * 16 + 7);
#pragma unroll 1
        for (int i = 0; i < 32; i++) {
          const uint8_t* src = z2_block(i, j) + rk * 18432;
          if (i >= 4) mbar_wait(bars + B_AD + c.s * 8, ((i >> 2) & 1) ^ 1);
          slot(ST_BYTES);
          bulk_mc_h(el, st + ST_B + rk * 18432, src, 18432, full, true, pol);
          tma3d_h(el, st, &P.wsp, i * 64, rb * 64, 0, full, true, pol);
          c.next();
        }
        mbar_wait(bars + B_Z1, L);
        fence_async_g();
        expect_tx_p(el, bars + B_ZB, 26624);
#pragma unroll 1
        for (int i = 0; i < 10; i++) {
          const int cb = i - 1 + j;
          if (i < 4) mbar_wait(bars + B_AD + c.s * 8, 1);
          slot(i ? ZB : 26624);
          if (i == 0) {
            bulk_load_h(el, st, z1_block(rb, 0, j), 26624, bars + B_ZB, true, pol);
            bulk_load_h(el, st + 26624, z1_block(rb, 1, j), 26624, full, true, pol);
          } else {
            tma2d_mc_h(el, st + ST_B + rk * 18432, &P.wout, (cb >= 9 ? cb - 9 : cb) * 64, 288 * j + rk * 144, full, true, pol);
          }
          c.next();
        }
      }
    } else if (wid < 11) {
      int w = wid - 9;
      uint32_t* const fr = g_flags + (rb * 2 + w) * 32;
      const uint32_t epoch = ldcg32(fr + FR_EP + j);
      const uint32_t ev = bars + B_EVT + w * EV_N * 8, t8 = (epoch + 1) * 8;
      Cur c{0, 1};
#pragma unroll 1
      for (int L = 0; L < 2; L++) {
        {
          const uint32_t tag = epoch * 2 + L + 1;
          uint4* const xs = g_XST + (rb * 2 + w) * 128;
          if (L) {
            mbar_wait(ev + EV_PT * 8, 0);
            TRC(el, 3, w * 32 + 16);
            flag_release_p(el, fr + FR_X2);
            TRC(el, 3, w * 32 + 17);
          }
#pragma unroll 1
          for (int i = 0; i < 9; i++) {
            const uint32_t full = bars + B_FULLA + w * 32 + c.s * 8, dst = sb + c.s * ST_BYTES + w * 8192;
            if (L == 0 && i == 4) {
              mbar_wait(bars + B_WT + w * 8, 0);
              TRC(el && w == 0, 2, 37);
              rows_stats(sb + SM_STG + w * 9216, xs + 16 * j, tag, lane);
              TRC(el && w == 0, 2, 38);
            }
            const uint32_t src = sb + (L ? 2 * ST_BYTES + SM_WOI : SM_STG + w * 9216);
            if (i == 4) {
#pragma unroll
              for (int u = 0; u < 6; u++) sts128(src + u * 512 + lane * 16, POISON, POISON, POISON, POISON);
              fence_async_s();
              __syncwarp();
            }
            mbar_wait(bars + B_EMPTY + c.s * 8, c.ph);
            expect_tx_p(el, full, 8192);
            if (i < L) { flag_wait(fr + FR_X2, t8); fence_async_g(); }
            tma3d_h(el, dst, &P.act[L], i * 64, rb * 64, w, full, false, pol);
            TRC(el && i < L, 3, w * 32 + 18);
            c.next();
            if (i >= 4 && i < (L ? 5 : 8)) {
              int b = (rb * 2 + w) * 8 + j;
              asm volatile("" : "+r"(b));
              bulk_store_p(el, i == 4 ? (uint8_t*)g_HALO + b * 3072 : g_O + (b * 3 + i - 5) * 3072, src, 3072);
              if (i < 6) bulk_store_p(el, (i == 4 ? g_ST1 : g_ZST) + b * 64, src, 1024);
              if (i == 6) bulk_store_p(el, g_RT + b * 8, src, 64);
            }
            if (L == 0 && i == 3) rows_fetch(el, sb + SM_STG + w * 9216, P.xs[0] + (128 * rb + 16 * j + w) * (DM * 2), bars + B_WT + w * 8);
          }
          if (el) asm volatile("cp.async.bulk.commit_group;\ncp.async.bulk.wait_group 0;" ::: "memory");
          __syncwarp();
          if (L == 0) fence_gpu();
          const uint32_t tab = sb + L * (2 * ST_BYTES) + SM_XST + w * 512 + lane * 8;
          TRC(el, 3, w * 32 + L * 16 + 13);
#pragma unroll 1
          for (int it = 0; it < (1 << 22); it++) {
            const uint4 a = ll_ld128(xs + 2 * lane), b = ll_ld128(xs + 64 + 2 * lane);
            if (__all_sync(~0u, a.z == tag && b.z == tag)) { sts64(tab, a.x, a.y); sts64(tab + 256, b.x, b.y); break; }
          }
          __syncwarp();
          mbar_arrive_if(el, bars + B_XS + w * 8);
          TRC(el, 3, w * 32 + L * 16 + 14);
          if (w == 1) {
            mbar_wait(bars + B_XS, L);
            expect_tx_p(el, bars + B_RES, 18432);
            tma3d_h(el, sb + SM_STG, &P.res[L], (j & 6) * 72, rb * 64, j & 1, bars + B_RES, !L, pol);
          }
          if (L) flag_wait(fj + FJ_P4, t8 * 4);
        }
        asm volatile("" : "+r"(w));
        uint32_t* const fo = g_flags + (rb * 2 + (j & 1)) * 32 + L;
        {
          const uint8_t* src = o_block(rb, j & 1) + w * 8192;
#pragma unroll 1
          for (int i = 0; i < 5; i++) {
            const uint32_t full = bars + B_FULLA + w * 32 + c.s * 8, dst = sb + c.s * ST_BYTES + w * 8192;
            const bool none = 2 * i + w > 8;
            mbar_wait(bars + B_EMPTY + c.s * 8, c.ph);
            expect_tx_p(el, full, none ? 0 : 8192);
            if (i == 0) {
              mbar_wait(ev + EV_O * 8, L);
              TRC(el, 3, w * 32 + L * 16 + 3);
              flag_add_p(el, fr + FR_O + L);
              TRC(el, 3, w * 32 + L * 16 + 4);
              flag_wait(fo + FR_O, t8);
              fence_async_g();
            }
            if (!none) bulk_load_h(el, dst, src + i * 16384, 8192, full, true, pol);
            TRC(el && i == 0, 3, w * 32 + L * 16 + 5);
            c.next();
          }
        }
        {
          expect_tx_p(lane < 9, bars + B_FA3 + (9 * w + lane) * 8, 8192);
          mbar_wait(ev + EV_X1 * 8, L);
          TRC(el, 3, w * 32 + L * 16 + 6);
          if (L) flag_add_p(el, fo + FR_X1); else flag_release_p(el, fo + FR_X1);
          mbar_arrive_if(el, bars + B_GATE3);
          TRC(el, 3, w * 32 + L * 16 + 7);
          mbar_arrive_if(lane < 2, bars + B_FULLA + w * 32 + ((c.s + lane) & 3) * 8);
#pragma unroll 1
          for (int kb = 0; kb < 9; kb++) {
            const int n = 9 * w + kb;
            const uint32_t dst = sb + ((n >> 1) & 3) * ST_BYTES + (n & 1) * 8192;
            if (kb == 0) { flag_wait(fr + FR_X1 + L, t8); fence_async_g(); }
            if (n >= 8) mbar_wait(bars + B_EA3 + (n - 8) * 8, L);
            tma3d_h(el, dst, &P.act[L + 1], kb * 64, rb * 64, w, bars + B_FA3 + n * 8, false, pol);
            TRC(el && kb == 0, 3, w * 32 + L * 16 + 8);
          }
          c.ph ^= ((c.s + 18) >> 2) & 1; c.s = (c.s + 18) & 3;
        }
        asm volatile("" : "+r"(lane), "+r"(w));
        expect_tx_p(el, bars + B_WT + w * 8, 2048);
#pragma unroll 1
        for (int r = 0; r < 8; r++)
          bulk_load_p(el, sb + SM_WT + w * 2176 + r * 272, (const uint8_t*)P.w_sp + (size_t)(128 * rb + 16 * j + 2 * r + w) * (SEQ * 2) + 30 * 128, 256, bars + B_WT + w * 8);
        float cv = (lane & 3) ? 0.f : -blo(ldnc16(P.b_sp + 128 * rb + 16 * j + 2 * (lane >> 2) + w));
        mbar_wait(bars + B_RT, L);
        mbar_wait(bars + B_WT + w * 8, L ^ 1);
        mbar_wait(ev + EV_Z1 * 8, L);
        const uint32_t ro = (w * 64 + 8 * j + (lane >> 2)) * 128, x0 = ((lane & 3) * 2) ^ (lane >> 2);
#pragma unroll 1
        for (int i = 0; i < 32; i++) {
          const bool tail = (i >> 1) == 4;
          const int kb = tail ? i + 22 : i < 8 ? i : i - 2;
          if (i == 8) mbar_wait(bars + B_RT1, L);
          if (!tail) mbar_wait(bars + B_FULL + c.s * 8, c.ph ^ 1);
#pragma unroll
          for (int e = 0; e < 2; e++) {
            const uint4 a = lds128(!tail ? sb + c.s * ST_BYTES + ro + ((x0 ^ e) << 4) : sb + SM_WT + w * 2176 + (lane >> 2) * 272 + (i - 8) * 128 + (lane & 3) * 32 + e * 16);
            const uint4 m = lds128(sb + SM_RT + 4096 + kb * 128 + (lane & 3) * 32 + e * 16);
            cv = fmaf(blo(a.x), blo(m.x), fmaf(bhi(a.x), bhi(m.x), fmaf(blo(a.y), blo(m.y), fmaf(bhi(a.y), bhi(m.y), cv))));
            cv = fmaf(blo(a.z), blo(m.z), fmaf(bhi(a.z), bhi(m.z), fmaf(blo(a.w), blo(m.w), fmaf(bhi(a.w), bhi(m.w), cv))));
          }
          if (!tail) {
            mbar_arrive_if(el, bars + B_AD + c.s * 8 + (__float_as_uint(cv) & P.zero));
            c.next();
          }
        }
        TRC(el, 3, w * 32 + L * 16 + 11);
        uint32_t tag = t8;
        asm volatile("" : "+r"(tag));
        tag = (tag >> 2) - 1 + L;
        cv = qsum(cv);
        uint2* const cs = (uint2*)(g_XST + (rb * 2 + w) * 128 + 1);
        if ((lane & 3) == 0) ll_st64(cs + 32 * j + (lane >> 2) * 4, __float_as_uint(cv), tag);
#pragma unroll 1
        for (int it = 0; it < (1 << 22); it++) {
          const uint2 a = ll_ld64(cs + 4 * lane), b = ll_ld64(cs + 128 + 4 * lane);
          if (__all_sync(~0u, a.y == tag && b.y == tag)) { sts32(sb + SM_CV + w * 256 + lane * 4, a.x); sts32(sb + SM_CV + w * 256 + 128 + lane * 4, b.x); break; }
        }
        __syncwarp();
        if (el) mbar_arrive(bars + B_CV + w * 8);
        TRC(el, 3, w * 32 + L * 16 + 12);
#pragma unroll 1
        for (int kb = 30; kb < 32; kb++) {
          mbar_wait(bars + B_FULL + c.s * 8, c.ph ^ 1);
          if (el) mbar_arrive(bars + B_AD + c.s * 8);
          c.next();
        }
        c.ph ^= ((c.s + 10) >> 2) & 1; c.s = (c.s + 10) & 3;
        if (L == 0) {
          mbar_wait(ev + EV_P4 * 8, 0);
          flag_add_p(el, fj + FJ_P4);
        }
      }
    } else {
      const uint32_t epoch = ldcg32(fj + FJ_EP + rb);
      if (SPL) {
        mbar_wait(bars + B_RES + 8, 0);
        TRC(el, 2, 41);
        flag_release_p(el, fj + FJ_WQ0);
        TRC(el, 2, 42);
      }
      mbar_wait(bars + B_IMG, 0);
      TRC(el, 2, 39);
      flag_release_p(el, fj + FJ_WQ);
      TRC(el, 2, 40);
#pragma unroll 1
      for (int L = 0; L < 2; L++) {
        auto wo_fetch = [&]() {
          expect_tx_p(el, bars + B_WOI, 5760);
          asm volatile("{\n.reg .pred P;\nsetp.ne.u32 P, %5, 0;\n@P cp.async.bulk.tensor.4d.shared::cluster.global.mbarrier::complete_tx::bytes [%0], [%1, {0, 0, %3, %4}], [%2];\n}" ::"r"(sb + SM_WOI), "l"(&P.wo8), "r"(bars + B_WOI), "r"(9 * j), "r"((9 * rb) >> 1), "r"(el) : "memory");
        };
        float* const csf = g_CSP + (NCTA + bid) * 216;
        if (L == 0) {
          flag_wait(fj + FJ_WQ, (epoch + 1) * 16);
          fence_async_g();
          expect_tx_p(el, bars + B_XRW, 13824);
          bulk_load_p(el, sb + ST_BYTES + SM_WOI, g_CSP + j * 16 * 216, 6912, bars + B_XRW);
          bulk_load_p(el, sb + 2 * ST_BYTES + SM_WOI, g_CSP + (j * 16 + 8) * 216, 6912, bars + B_XRW);
          wo_fetch();
          mbar_wait(bars + B_XRW, 0);
#pragma unroll 1
          for (int f = lane; f < 54; f += 32) {
            float s[4] = {0.f, 0.f, 0.f, 0.f};
#pragma unroll 4
            for (int r = 0; r < 16; r++) {
              const uint4 v = lds128(sb + ST_BYTES + SM_WOI + (r >> 3) * ST_BYTES + (r & 7) * 864 + f * 16);
              s[0] += __uint_as_float(v.x); s[1] += __uint_as_float(v.y); s[2] += __uint_as_float(v.z); s[3] += __uint_as_float(v.w);
            }
            sts128(sb + SM_CSQ + f * 16, __float_as_uint(s[0]), __float_as_uint(s[1]), __float_as_uint(s[2]), __float_as_uint(s[3]));
            stg128(csf + f * 4, __float_as_uint(s[0]), __float_as_uint(s[1]), __float_as_uint(s[2]), __float_as_uint(s[3]));
          }
          __syncwarp();
          mbar_arrive_if(el, bars + B_CSQ);
        } else {
#pragma unroll 1
          for (int u = 0; u < 4; u++) {
            const int w = u & 1;
            if (u < 2) {
              flag_wait(g_flags + (rb * 2 + w) * 32 + FR_X2, (epoch + 1) * 8);
              fence_async_g();
              TRC(el, 2, 48 + u);
              rows_fetch(el, sb + SM_STG + w * 9216, P.xs[1] + (128 * rb + 16 * j + w) * (DM * 2), bars + B_XRW + w * 8);
            } else {
              if (u == 2) {
                expect_tx_p(el, bars + B_CSQ, 864);
                bulk_load_p(el, sb + 2 * ST_BYTES + SM_CSQ, csf, 864, bars + B_CSQ);
              }
              mbar_wait(bars + B_XRW + w * 8, w ^ 1);
              TRC(el, 2, 48 + u);
              rows_stats(sb + SM_STG + w * 9216, g_XST + (rb * 2 + w) * 128 + 16 * j, epoch * 2 + 2, lane);
              TRC(el, 2, 50 + u);
            }
          }
        }
        if (L == 0) {
          TRC(el, 2, 43);
          mbar_wait(bars + B_WOI, 0);
          bulk_store_p(el, g_WO + j * WO_SL + ((9 * rb) >> 1) * 1152, sb + SM_WOI, 5760);
          publish_p(el, fj + FJ_WO);
          TRC(el, 2, 44);
          const uint8_t* sp = lane < 16 ? (const uint8_t*)P.w_in + (30 * lane + 50) * (FH * 4) + FH * 2 + lane * 256 : (const uint8_t*)P.w_sp + (60 * lane) * (SEQ * 2) + lane * 64;
          float sq = 0.f;
#pragma unroll 1
          for (int u = 0; u < 4; u++) {
            const uint4 y = ldnc128(sp + u * 16);
            const uint32_t x[4] = {y.x, y.y, y.z, y.w};
#pragma unroll
            for (int e = 0; e < 4; e++) sq = fmaf(blo(x[e]), blo(x[e]), fmaf(bhi(x[e]), bhi(x[e]), sq));
          }
#pragma unroll 1
          for (int o = 8; o; o >>= 1) sq += __shfl_xor_sync(~0u, sq, o);
          sq *= lane < 16 ? 2.f * GA * GA * DM / 512.f : C0S * C0S * SEQ / 512.f;
          asm("sqrt.approx.f32 %0, %0;" : "+f"(sq));
          const float o0 = __shfl_sync(~0u, sq, 0), o1 = __shfl_sync(~0u, sq, 16);
          const float p2 = __uint_as_float(min(__float_as_uint(o0) & 0x7f800000u, 0x7e000000u)) * OFK, off = -p2 - fminf(OFA, 0.5f * p2);
          if (el) sts64(sb + SM_OFF, pack2(off, off), min(__float_as_uint(o1) & 0x7f800000u, 0x7e000000u) | 0x00400000u);
        }
        if (el) mbar_arrive(bars + B_GATE3);
        const uint32_t tag = epoch * 2 + L + 1;
        asm volatile("" : "+r"(lane));
        mbar_wait(bars + B_EVT + EV_ZN * 8, L);
        mbar_wait(bars + B_EVT + (EV_N + EV_ZN) * 8, L);
        flag_release_p(el, fj + FJ_ZN + L);
        TRC(el, 2, L * 16 + 8);
        {
          uint4 v[4];
#pragma unroll 1
          for (int it = 0; it < (1 << 22); it++) {
            bool ok = true;
#pragma unroll
            for (int u = 0; u < 4; u++) { v[u] = ll_ld128(g_ZST + (rb * 2 + ((lane >> 1) & 1)) * 512 + ((lane & 1) * 4 + u) * 64 + 8 * j + (lane >> 2)); ok = ok && v[u].z == tag; }
            if (__all_sync(~0u, ok)) break;
          }
          float mean = __uint_as_float(v[0].x) + __uint_as_float(v[1].x) + __uint_as_float(v[2].x) + __uint_as_float(v[3].x), M2 = 0.f;
          mean = (mean + __shfl_xor_sync(~0u, mean, 1)) * 0.125f;
#pragma unroll
          for (int u = 0; u < 4; u++) { const float d = __uint_as_float(v[u].x) - mean; M2 += fmaf(288.f * d, d, __uint_as_float(v[u].y)); }
          M2 += __shfl_xor_sync(~0u, M2, 1);
          const float rs = blo(pack2(rsqrtf(fmaf(M2, 1.f / FH, 4.f * GA * GA * LN_EPS)), 0.f));
          if (!(lane & 1)) ll_st64(g_RT + 128 * rb + 16 * j + (lane >> 1), pack2(rs, rs * mean), tag);
        }
        TRC(el, 2, L * 16 + 10);
#pragma unroll 1
        for (int b = 0; b < 8; b++) {
          uint4 v[4];
#pragma unroll 1
          for (int it = 0; it < (1 << 22); it++) {
            bool ok = true;
#pragma unroll
            for (int u = 0; u < 4; u++) { v[u] = ll_ld128((const uint4*)g_RT + b * 128 + u * 32 + lane); ok = ok && v[u].y == tag && v[u].w == tag; }
            if (__all_sync(~0u, ok)) break;
          }
#pragma unroll
          for (int u = 0; u < 4; u++) {
            const uint32_t rt = sb + SM_RT + b * 512 + u * 128, ro = (lane >> 3) * 32 + (lane & 3) * 8 + ((lane >> 2) & 1) * 2;
            sts32(rt + 4096 + lane * 4, __byte_perm(v[u].x, v[u].z, 0x7632));
            asm volatile("st.shared.u16 [%0], %1;\nst.shared.u16 [%0 + 4], %2;" ::"r"(rt + ro), "h"((uint16_t)v[u].x), "h"((uint16_t)v[u].z) : "memory");
          }
          __syncwarp();
          if (el && (b == 1 || b == 7)) mbar_arrive(bars + (b == 1 ? B_RT : B_RT1));
          TRC(el && b < 2, 2, L * 16 + 11 + b);
        }
        TRC(el, 2, L * 16 + 9);
        mbar_wait(bars + B_EVT + EV_Z1 * 8, L);
        mbar_wait(bars + B_EVT + (EV_N + EV_Z1) * 8, L);
        fence_gpu();
        if (el) mbar_arrive(bars + B_Z1);
        if (L == 0) {
          __nanosleep(NAP0);
          poison(el, sb + SM_STG + 17152, &P.psn, rb, j, lane);
          if (el) asm volatile("cp.async.bulk.commit_group;\ncp.async.bulk.wait_group 0;" ::: "memory");
          __syncwarp();
          fence_gpu();
        }
      }
    }
  } else {
    CKK(3);
    uint8_t* const wdst = P.wq + j * WQ_SL + rb * 3456 + tid * 16;
#pragma unroll
    for (int u = 0; u < SPL; u++) stg128_if(tid < 216, wdst + u * (16 * 3456), wv[u].x, wv[u].y, wv[u].z, wv[u].w);
    __syncwarp();
    if (lane == 0) mbar_arrive(bars + B_RES + 8);
    CKK(4);
    auto repack2 = [&]() {
#pragma unroll
      for (int u = SPL; u < 5; u++) stg128_if((u < 4 || rb < 8) && tid < 216, wdst + u * (16 * 3456), wv[u].x, wv[u].y, wv[u].z, wv[u].w);
      float s[8];
#pragma unroll
      for (int e = 0; e < 8; e++) s[e] = 0.f;
#pragma unroll
      for (int u = 0; u < 5; u++) {
        uint32_t x[4] = {wv[u].x, wv[u].y, wv[u].z, wv[u].w};
        asm volatile("" : "+r"(x[0]), "+r"(x[1]), "+r"(x[2]), "+r"(x[3]));
#pragma unroll
        for (int e = 0; e < 4; e++) { s[2 * e] += blo(x[e]); s[2 * e + 1] += bhi(x[e]); }
      }
#pragma unroll
      for (int m = 4; m; m >>= 1) {
#pragma unroll
        for (int e = 0; e < m; e++) s[e] = ((tid & m) ? s[e + m] : s[e]) + __shfl_xor_sync(~0u, (tid & m) ? s[e] : s[e + m], m);
      }
      stg32_if(tid < 216, P.csp + bid * 216 + tid, __float_as_uint(s[0]));
      __syncwarp();
      if (lane == 0) mbar_arrive(bars + B_IMG);
    };
    reg_alloc<232>();
    CKK(5);
#pragma unroll
    for (int v = SPL; v < 5; v++) wv[v] = ldnc128_if(tid < 216 && (v < 4 || rb < 8), wsrc + v * (128 * 3 * DM * 2));
    repack2();
    CKK(6);
    const int w = wid >> 2, q = wid & 3;
    int g = lane >> 2, t = lane & 3;
    const uint32_t ev = bars + B_EVT + w * EV_N * 8;
    const bool tr = (tid & 127) == 0;
    (void)tr;
    Cur c{0, 0};
    const uint32_t ebar = mapa(bars + B_EMPTY, (bid & 1) ^ (lane & 1));
    auto release = [&](uint32_t s, uint32_t dep = 0) { mbar_arrive_cluster_if(lane < 2, ebar + s * 8 + dep); };
    auto release_if = [&](bool on, uint32_t s) { mbar_arrive_cluster_if(lane < 2 && on, ebar + s * 8); };
    uint32_t ia = 0;
    auto wait_ab = [&]() { mbar_wait_c(bars + B_FULL + c.s * 8, c.ph); mbar_wait_c(bars + B_FULLA + w * 32 + c.s * 8, (ia >> 2) & 1); ia++; };

    auto yield_done = [&]() { if (w == 0 && lane == 0) mbar_arrive(bars + B_LAG); };
    auto signal = [&](int e) { __syncwarp(); mbar_arrive_if(lane == 0, ev + e * 8); };

    const uint32_t epoch = ldcg32(g_flags + (rb * 2 + w) * 32 + FR_EP + j);
    TRC(tr, w, 1);
    CKK(7);
    if (PAD && P.zero) {
#pragma unroll
      for (int i = 0; i < PAD; i++) asm volatile("st.shared.u32 [%0], %1;" ::"r"(sb + i * 20), "r"(tid) : "memory");
    }
    CKK_OUT;

#pragma unroll 1
    for (int L = 0; L < 2; L++) {
      const int tb = 2 + L * 24;
      asm volatile("" : "+r"(lane), "+r"(g), "+r"(t));
      (void)tb;
      ia = 0;
      const uint32_t tag = epoch * 2 + L + 1;
      uint32_t aoff = (w * 64 + q * 16 + (lane & 15)) * 128 + (((lane >> 4) ^ (lane & 7)) << 4);
      {
        uint32_t Pk[27][2];
        float sc0, sc1;
        const uint32_t att = sb + w * 8192 + q * 2048 + lane * 4;
        uint4* hp = g_HALO + ((((rb - (q == 0)) * 2 + w) * 8 + j) * 6) * 32 + lane;
        uint8_t* od = o_block(rb, w) + (9 * j) * 1024 + (2 * q) * 128 + lane * 4;
        ACLK_INIT;
        {
          float acc[108];
#pragma unroll
          for (int i = 0; i < 108; i++) acc[i] = 0.f;
          uint32_t prev = 0;
#pragma unroll 1
          for (int kb = 0; kb < 9; kb++) {
            wait_ab();
            if (w == 1 && kb == 9 - LAG1) mbar_wait_c(bars + B_LAG, L);
            TRC(tr && kb == 0, w, tb + 0);
            MCLK(kb == 0, 0);
            PCLK(kb * 4);
            const uint32_t st = sb + c.s * ST_BYTES, da = dlo(st + w * 8192, 16), db = dlo(st + ST_B, 3456);
            wgmma_fence();
#pragma unroll
            for (int kk = 0; kk < 4; kk++) {
              wgmma_ss_n216(acc, dsc<1024, 1>(da, kk * 32), dsc<128, 0>(db, kk * 6912), 1);
              if (kk == 0) { wgmma_commit(); wgmma_wait<1>(); release_if(kb > 0, prev); }
            }
            wgmma_commit();
            if (kb == 8) yield_done();
            PCLK(kb * 4 + 1);
            PCLK(kb * 4 + 2);
            PCLK(kb * 4 + 3);
            prev = c.s; c.next();
          }
          const uint32_t cs = sb + prev * ST_BYTES + SM_CSQ + t * 8;
          mbar_wait_c(bars + B_CSQ, L);
          mbar_wait_c(bars + B_XS + w * 8, L);
          const float2 n0 = lds64f(sb + prev * ST_BYTES + SM_XST + w * 512 + (16 * q + g) * 8), n1 = lds64f(sb + prev * ST_BYTES + SM_XST + w * 512 + (16 * q + g + 8) * 8);
          const float m0 = n0.x, r0 = n0.y, m1 = n1.x, r1 = n1.y;
          float2 cv[27];
#pragma unroll
          for (int G = 0; G < 27; G++) cv[G] = lds64f(cs + G * 32);
          PCLK(36);
          wgmma_wait<0>();
          PCLK(37);
          uint32_t dep = P.zero & __float_as_uint(m0) & __float_as_uint(m1);
#pragma unroll
          for (int G = 0; G < 27; G++) dep &= __float_as_uint(cv[G].x);
          release(prev, dep);
          TRC(tr, w, tb + 1);
          MCLK(1, 1);
          ACLK(0);
#pragma unroll
          for (int G = 9; G < 27; G++) Pk[G][1] = pack2(fmaf(m1, cv[G].x, acc[4 * G + 2]) * r1, fmaf(m1, cv[G].y, acc[4 * G + 3]) * r1);
          if (q < 3) {
#pragma unroll
            for (int i = 0; i < 18; i++) sts32(att + (i >> 4) * ST_BYTES + (i & 15) * 128, Pk[9 + i][1]);
          } else if (rb < 15) {
#pragma unroll
            for (int i = 0; i < 6; i++) ll_st128(hp + i * 32, __uint_as_float(Pk[9 + 3 * i][1]), __uint_as_float(Pk[10 + 3 * i][1]), tag, __uint_as_float(Pk[11 + 3 * i][1]));
          }
#pragma unroll
          for (int G = 0; G < 27; G++) {
            if (G < 9) {
              Pk[G][0] = pack2(fmaf(m0, cv[G].x, acc[4 * G]), fmaf(m0, cv[G].y, acc[4 * G + 1]));
              Pk[G][1] = pack2(fmaf(m1, cv[G].x, acc[4 * G + 2]), fmaf(m1, cv[G].y, acc[4 * G + 3]));
            } else {
              Pk[G][0] = pack2(fmaf(m0, cv[G].x, acc[4 * G]) * r0, fmaf(m0, cv[G].y, acc[4 * G + 1]) * r0);
            }
          }
          sc0 = r0 * (0.23570226039551584f * 1.4426950408889634f); sc1 = r1 * (0.23570226039551584f * 1.4426950408889634f);
        }
        ACLK(1);
        constexpr int GA_[4] = {0, 2, 4, 7}, GB_[4] = {1, 3, 5, 8}, GC_[4] = {2, 4, 6, 6};
        float S1[4][4], S2[4][4];
        uint32_t qa[4][2], qc[4][2];
#pragma unroll
        for (int h = 0; h < 4; h++) {
#pragma unroll
          for (int r = 0; r < 2; r++) {
            qa[h][r] = (h == 0 || h == 3 || t >= h) ? Pk[GA_[h]][r] : 0u;
            qc[h][r] = (h == 3 ? t == 3 : t <= h) ? Pk[GC_[h]][r] : 0u;
          }
          mma16(S1[h], qa[h][0], qa[h][1], Pk[GB_[h]][0], Pk[GB_[h]][1], Pk[9 + GA_[h]][0], Pk[9 + GB_[h]][0]);
          mma16(S2[h], qa[h][0], qa[h][1], Pk[GB_[h]][0], Pk[GB_[h]][1], Pk[9 + GA_[h]][1], Pk[9 + GB_[h]][1]);
        }
#pragma unroll
        for (int h = 0; h < 4; h++) {
          mma8(S1[h], qc[h][0], qc[h][1], Pk[9 + GC_[h]][0]);
          mma8(S2[h], qc[h][0], qc[h][1], Pk[9 + GC_[h]][1]);
        }
        uint32_t V1[9], V2[9];
#pragma unroll
        for (int i = 0; i < 9; i++) { V1[i] = movm(Pk[18 + i][0]); V2[i] = movm(Pk[18 + i][1]); }
        const bool remote = q == 0 && rb > 0;
        uint4 hv[6];
#pragma unroll
        for (int i = 0; i < 6; i++) hv[i] = make_uint4(0u, 0u, tag, 0u);
        if (remote) {
#pragma unroll
          for (int i = 0; i < 6; i++) hv[i] = ll_ld128(hp + i * 32);
        }
        const bool up0 = 2 * t > g, up1 = 2 * t + 1 > g;
        const uint32_t mup = (up0 ? 0xffffu : 0u) | (up1 ? 0xffff0000u : 0u);
        auto finish = [&](const float (&x0)[4], const float (&x1)[4], uint32_t ma, const uint32_t (&Vb)[9], int hi) {
          uint32_t pa[4], pb[4];
          float rs[4];
#pragma unroll
          for (int h = 0; h < 4; h++) {
            const float m = qmax(fmaxf(x0[h], x1[h]));
            const uint32_t p = pack2(ex2(x0[h] - m), ex2(x1[h] - m));
            pa[h] = p & ma; pb[h] = p & ~ma;
          }
#pragma unroll
          for (int h = 0; h < 4; h += 2) {
            float R[4];
            mma16(R, pa[h], pa[h + 1], pb[h], pb[h + 1], 0x3f803f80u, 0x3f803f80u);
            rs[h] = rcp_fast(R[0]); rs[h + 1] = rcp_fast(R[2]);
          }
#pragma unroll
          for (int i = 0; i < 9; i++) {
            const int h = 4 * i / 9, e = (h & 1) * 2;
            const bool split = i == 2 || i == 4 || i == 6, nx = split && 2 * t >= i;
            float O[4], N[4];
            mma16(O, pa[h & 2], pa[h | 1], pb[h & 2], pb[h | 1], V1[i], Vb[i]);
            if (i == 4) mma16(N, pa[2], pa[3], pb[2], pb[3], V1[i], Vb[i]); else { N[0] = O[2]; N[1] = O[3]; }
            const float r = nx ? rs[h + (split ? 1 : 0)] : rs[h];
            stg32(od + i * 1024 + hi * 128, pack2((nx ? N[0] : O[e]) * r, (nx ? N[1] : O[e + 1]) * r));
          }
        };
        {
          float x0[4], x1[4];
#pragma unroll
          for (int h = 0; h < 4; h++) { x0[h] = (up0 ? S1[h][2] : S2[h][2]) * sc1; x1[h] = (up1 ? S1[h][3] : S2[h][3]) * sc1; }
          finish(x0, x1, mup, V2, 1);
        }
        ACLK(2);
        bar_sync(1 + w, 128);
        uint32_t H[18];
        if (q > 0) {
#pragma unroll
          for (int i = 0; i < 18; i++) H[i] = lds32(att - 2048 + (i >> 4) * ST_BYTES + (i & 15) * 128);
        } else {
#pragma unroll 1
          for (int it = 0; it < (1 << 20); it++) {
            bool ok = true;
#pragma unroll
            for (int i = 0; i < 6; i++) ok = ok && hv[i].z == tag;
            if (__all_sync(~0u, ok)) break;
#pragma unroll
            for (int i = 0; i < 6; i++) hv[i] = ll_ld128(hp + i * 32);
          }
#pragma unroll
          for (int i = 0; i < 6; i++) { H[3 * i] = hv[i].x; H[3 * i + 1] = hv[i].y; H[3 * i + 2] = hv[i].w; }
        }
        float S0[4][4];
#pragma unroll
        for (int h = 0; h < 4; h++) {
          mma16(S0[h], qa[h][0], qa[h][1], Pk[GB_[h]][0], Pk[GB_[h]][1], H[GA_[h]], H[GB_[h]]);
        }
#pragma unroll
        for (int h = 0; h < 4; h++) mma8(S0[h], qc[h][0], qc[h][1], H[GC_[h]]);
        uint32_t V0[9];
#pragma unroll
        for (int i = 0; i < 9; i++) V0[i] = movm(H[9 + i]);
        ACLK(3);
        {
          const bool nohalo = (rb | q) == 0;
          const float b0 = up0 && nohalo ? -INFINITY : 0.f, b1 = up1 && nohalo ? -INFINITY : 0.f;
          float x0[4], x1[4];
#pragma unroll
          for (int h = 0; h < 4; h++) { x0[h] = fmaf(up0 ? S0[h][0] : S1[h][0], sc0, b0); x1[h] = fmaf(up1 ? S0[h][1] : S1[h][1], sc0, b1); }
          finish(x0, x1, ~mup, V0, 0);
        }
        ACLK(4);
        signal(EV_O);
        ACLK_OUT;
        TRC(tr, w, tb + 2);
        MCLK(1, 2);
      }
      {
        float acc[36];
        const int hw = rb * 2 + (j & 1), js = (j & 6) + w;
        const uint32_t xt = sb + SM_STG + (16 * q + g) * 288 + w * 144 + t * 4;
        uint32_t xm = sb + SM_STG + (16 * q + (lane & 15)) * 288 + (((9 * w + (lane >> 4)) ^ ((lane >> 2) & 1)) << 4), xl = sb + SM_STG + (2 * q + w) * 2304 + lane * 16;
        uint8_t* xd[5];
#pragma unroll
        for (int u = 0; u < 5; u++) {
          const int row = ((u * 32 + lane) * 57) >> 10;
          xd[u] = P.xs[L + 1] + (128 * rb + 32 * q + 16 * w + (j & 1)) * (DM * 2) + (j & 6) * 144 + row * (DM * 4 - 288) + u * 512 + ((lane ^ (row >> 2)) << 4);
          asm volatile("" : "+l"(xd[u]));
        }
        asm volatile("" : "+r"(xm), "+r"(xl));
        mbar_wait_c(bars + B_RES, L);
        TRC(tr, w, tb + 21);
#pragma unroll
        for (int i = 0; i < 18; i++) { const uint32_t x = lds32(xt + (i >> 1) * 16 + (i & 1) * 2304); acc[2 * i] = blo(x); acc[2 * i + 1] = bhi(x); asm volatile("" : "+f"(acc[2 * i]), "+f"(acc[2 * i + 1])); }
        uint32_t prev = 0;
#pragma unroll 1
        for (int u = 0; u < 5; u++) {
          const uint32_t st = sb + c.s * ST_BYTES, da = dlo(st, 1024), db = dlo(st + ST_B + w * 18432, 1152);
          mbar_wait_c(bars + B_FULL + c.s * 8, c.ph); mbar_wait_c(bars + B_FULLA + c.s * 8, (ia >> 2) & 1);
          TRC(tr && u == 0, w, tb + 3);
          MCLK(u == 0, 3);
          wgmma_fence();
#pragma unroll
          for (int kk = 0; kk < 4; kk++) wgmma_ss_n72(acc, dsc<128, 0>(da, kk * 2048), dsc<128, 0>(db, kk * 2304), 1);
          wgmma_commit();
          wgmma_wait<1>();
          release_if(u > 0, prev);
          mbar_wait_c(bars + B_FULLA + 32 + c.s * 8, (ia >> 2) & 1);
          ia++;
          if (u == 4) break;
          wgmma_fence();
#pragma unroll
          for (int kk = 4; kk < 8; kk++) wgmma_ss_n72(acc, dsc<128, 0>(da, kk * 2048), dsc<128, 0>(db, kk * 2304), 1);
          wgmma_commit();
          prev = c.s; c.next();
        }
        RCLK_INIT;
        wgmma_wait<0>();
        RCLK(0);
        release(c.s);
        c.next();
        if (__builtin_expect(any_nan(acc[0], acc[2]), 0)) {
          SLOW(L);
          const uint8_t* xr = P.xs[L] + (128 * rb + 32 * q + 2 * g + (j & 1)) * (DM * 2) + js * 144 + t * 4;
#pragma unroll
          for (int i = 0; i < 18; i++) { const uint32_t x = ldgpu32(xr + (i >> 1) * 16 + (i & 1) * (DM * 32)); acc[2 * i] = blo(x); acc[2 * i + 1] = bhi(x); }
          redo<KS2, 9, 1024, 128, 1152, 128>(acc, o_block(rb, j & 1) + q * 256 + lane * 4, g_WO + js * WO_SL + lane * 4, [](uint32_t*, int) {});
        }
        TRC(tr && P5TRACE != 5, w, tb + 4);
        MCLK(1, 4);
#pragma unroll
        for (int u = 0; u < 4; u++)
          stsm4(xm + u * 32, pack2(acc[8 * u], acc[8 * u + 1]), pack2(acc[8 * u + 2], acc[8 * u + 3]), pack2(acc[8 * u + 4], acc[8 * u + 5]), pack2(acc[8 * u + 6], acc[8 * u + 7]));
        asm volatile("stmatrix.sync.aligned.m8n8.x2.shared.b16 [%0], {%1,%2};" ::"r"(xm + 128), "r"(pack2(acc[32], acc[33])), "r"(pack2(acc[34], acc[35])) : "memory");
        auto stats = [&]() {
          float s0 = 0.f, s1 = 0.f, q0 = 0.f, q1 = 0.f;
#pragma unroll
          for (int i = 0; i < 36; i++) {
            if (i & 2) { s1 += acc[i]; q1 = fmaf(acc[i], acc[i], q1); } else { s0 += acc[i]; q0 = fmaf(acc[i], acc[i], q0); }
          }
          s0 = qsum(s0); s1 = qsum(s1); q0 = qsum(q0); q1 = qsum(q1);
          const float ss = t ? s1 : s0, m = ss * (1.f / 72.f);
          ll_st128_if(t < 2, g_ST1 + (hw * 8 + js) * 64 + 16 * q + 8 * t + g, m, fmaxf((t ? q1 : q0) - ss * m, 0.f), tag);
        };
        stats();
        RCLK(1);
        bar_sync(8 + q, 64);
        RCLK(2);
#pragma unroll
        for (int u = 0; u < 5; u++) {
          const uint4 v = lds128(xl + u * 512);
          stg128_if(u < 4 || lane < 16, xd[u], v.x, v.y, v.z, v.w);
        }
        RCLK(3);
        signal(EV_X1);
        RCLK(4);
        RCLK(5);
        TRC(tr, w, tb + 5);
        RCLK(6);
        RCLK_OUT;
      }
      uint4 zk[4];
      {
        uint32_t xA[36][4];
        float acc[32];
        uint32_t s0, one, off2;
        uint8_t *z1d, *zd;
        uint64_t db;
        auto bwait = [&](uint32_t dhi, bool skip) {
          s0 = c.s;
          c.next();
          if (!skip) mbar_wait_c(bars + B_FULL + c.s * 8, c.ph);
          db = dsc2(dlo(sb + s0 * ST_BYTES + ST_B, 512) - 3, 0, dhi); one = (c.s ^ P.zero) & 1;
        };
        auto mma = [&](int kk, int pp, bool hand) {
          wgmma_rs_n64(acc, xA[kk], dat(db, (kk / 18) * ST_BYTES + (kk % 18) * 2048 + 48, one), kk != 0);
          if (kk == pp && hand) bar_arrive(7 - w, 256);
          if (kk == 17 || kk == 35) wgmma_commit();
          if (kk == RL3) { wgmma_commit(); wgmma_wait<1>(); release(s0); }
        };
        {
          bwait(0x40000040u, false);
          mbar_wait_c(bars + B_GATE3, L);
          float mean0, mean1, rs0, rs1;
          stat_get(g_ST1 + ((rb * 2 + w) * 8 + 2 * t) * 64 + 16 * q + g, tag, 72.f, LN_EPS, mean0, rs0, mean1, rs1);
          const uint32_t ns0 = pack2(GA * rs0, GA * rs0), ns1 = pack2(GA * rs1, GA * rs1);
          const uint32_t nb0 = pack2(-mean0 * blo(ns0), -mean0 * blo(ns0)), nb1 = pack2(-mean1 * blo(ns1), -mean1 * blo(ns1));
          const uint32_t al = sb + (aoff & 8191);
#pragma unroll
          for (int kb = 0; kb <= 9; kb++) {
            if (kb < 9) {
              mbar_wait_c(bars + B_FA3 + (9 * w + kb) * 8, L);
              TRC(tr && kb == 0, w, tb + 6);
              MCLK(kb == 0, 5);
              if (kb == 0) SCLK(0);
              QCLK(kb);
              const uint32_t at = al + (w ? (((kb + 1) >> 1) & 3) * ST_BYTES + ((kb + 1) & 1) * 8192 : ((kb >> 1) & 3) * ST_BYTES + (kb & 1) * 8192);
#pragma unroll
              for (int kk = 4 * kb; kk < 4 * kb + 4; kk++) ldsm4(xA[kk], at ^ ((kk & 3) << 5));
            }
            if (kb == 0) continue;
            const uint32_t dep = xA[4 * kb - 4][0] & xA[4 * kb - 3][0] & xA[4 * kb - 2][0] & xA[4 * kb - 1][0] & P.zero;
            mbar_arrive_if(lane == 0 && (kb == 1 || w == 0), bars + B_EA3 + (9 * w + kb - 1) * 8 + dep);
#pragma unroll
            for (int kk = 4 * kb - 4; kk < 4 * kb; kk++) {
#pragma unroll
              for (int e = 0; e < 4; e++) xA[kk][e] = hfma2(xA[kk][e], (e & 1) ? ns1 : ns0, (e & 1) ? nb1 : nb0);
            }
            wgmma_fence();
#pragma unroll
            for (int kk = 4 * kb - 4; kk < 4 * kb; kk++) mma(kk, PP30, w);
          }
          off2 = lds32(sb + SM_OFF);
          z1d = z1_block(rb, w, j) + (tid & 127) * 16;
          zd = z2_block(2 * rb + (q >> 1), j) + (4 * (q & 1) + w) * 4608 + ((g & 3) * 2 + (g >> 2)) * 16 + t * 4;
          asm volatile("" : "+l"(z1d), "+l"(zd));
          wgmma_wait<0>();
          if (__builtin_expect(any_nan(acc[0], acc[2]), 0)) {
            SLOW(2 + L);
            uint4* const rd = g_RD + bid * (36 * 256) + tid;
            const uint8_t* xr = P.xs[L + 1] + (128 * rb + 32 * q + 2 * g + w) * (DM * 2) + t * 4;
#pragma unroll
            for (int i = 0; i < 32; i++) acc[i] = 0.f;
            redo<KS3, 8, 16, DM * 32, FH * 32, 16>(acc, xr, (const uint8_t*)P.w_in + g * (FH * 4) + (((9 * j + 1) >> 1) + 36) * 128 + t * 4,
                                              [&](uint32_t* a, int k) {
#pragma unroll
                                                for (int e = 0; e < 4; e++) a[e] = hfma2(a[e], (e & 1) ? ns1 : ns0, (e & 1) ? nb1 : nb0);
                                                stg128(rd + k * 256, a[0], a[1], a[2], a[3]);
                                              });
#pragma unroll
            for (int k = 0; k < 36; k++) { const uint4 v = ldcg128(rd + k * 256); xA[k][0] = v.x; xA[k][1] = v.y; xA[k][2] = v.z; xA[k][3] = v.w; }
          }
        }
        float sm[4] = {0.f, 0.f, 0.f, 0.f}, qq[4] = {0.f, 0.f, 0.f, 0.f};
        auto gelu = [&](auto nz2, bool out) {
          constexpr int NZ2 = nz2.value, R = 8 - NZ2, N = 8, D = NZ2 == 8 ? GM2 : NZ2 ? GMM : GM1;
          float th[32], gb = GB;
          uint32_t qa = 0, qb = 0;
          auto head = [&](int G) {
#pragma unroll
            for (int e = 0; e < 4; e++) { const float v = acc[4 * G + e]; th[4 * G + e] = tanh_fast(v * fmaf(v, v, gb)); }
          };
#pragma unroll
          for (int i = 0; i < D; i++) head((i + R) & 7);
#pragma unroll
          for (int i = 0; i < N; i++) {
            const int G = (i + R) & 7;
            if (i + D < N) head((i + D + R) & 7);
            float* z = acc + 4 * G;
#pragma unroll
            for (int e = 0; e < 4; e++) z[e] = fmaf(z[e], th[4 * G + e], z[e]);
            uint32_t pa = pack2(z[0], z[1]), pb = pack2(z[2], z[3]), tok;
            if (i < NZ2) {
#pragma unroll
              for (int e = 0; e < 4; e++) { sm[e] += z[e]; qq[e] = fmaf(z[e], z[e], qq[e]); }
              pa = hsub2(pa, off2); pb = hsub2(pb, off2);
              stg32(zd + i * 128, pa); stg32(zd + i * 128 + 9216, pb);
              tok = pa ^ pb ^ __float_as_uint(qq[1]);
            } else {
              if (NZ2 && G == 3) sts128(sb + SM_STG + tid * 16, qa, qb, pa, pb);
              else if (G & 1) stg128_if(out, z1d + (G >> 1) * 2048 + (NZ2 ? 24576 : 0), qa, qb, pa, pb);
              qa = pa; qb = pb;
              tok = pa ^ pb;
            }
            gb = __uint_as_float(tok * P.zero + __float_as_uint(GB));
          }
        };
#pragma unroll 1
        for (int p = 0;; p++) {
          wgmma_wait<0>();
          release(c.s);
          c.next();
          TRC(tr && p == 4, w, tb + 7);
          TRC(tr && p == 8, w, tb + 11);
          MCLK(p == 8, 6);
          SCLK(2 * p + 1);
          QCLK(10 + 3 * p);
          auto publish = [&]() {
            signal(EV_ZN);
            const float a0 = qsum(sm[0] + sm[1]), a1 = qsum(sm[2] + sm[3]), q0 = qsum(qq[0] + qq[1]), q1 = qsum(qq[2] + qq[3]);
            const float ss = t ? a1 : a0, m = ss * (1.f / 288.f);
            ll_st128_if(t < 2, g_ZST + (rb * 2 + w) * 512 + j * 64 + 16 * q + 8 * t + g, m - blo(off2), fmaxf((t ? q1 : q0) - ss * m, 0.f), tag);
            TRC(tr, w, tb + 8);
            TRC(tr, w, tb + 9);
          };
          if (p < 4) {
            gelu(Int<8>{}, true);
            zd += 1024;
          } else if (p == 4) {
            gelu(Int<4>{}, true);
            publish();
          } else {
            gelu(Int<0>{}, p < 8);
            z1d += 8192;
          }
          SCLK(2 * p + 2);
          QCLK(11 + 3 * p);
          if (p == 8) break;
          bwait(p == 3 ? 0x80000040u : 0x40000040u, w);
          bar_sync(6 + w, 256);
          TRC(tr && p == 4, w, tb + 10);
          wgmma_fence();
#pragma unroll
          for (int kk = 0; kk < 36; kk++) mma(kk, PP3, w == 0 || p < 7);
        }
        signal(EV_Z1);
#pragma unroll
        for (int u = 0; u < 4; u++) {
          zk[u] = make_uint4(pack2(acc[8 * u], acc[8 * u + 1]), pack2(acc[8 * u + 2], acc[8 * u + 3]), pack2(acc[8 * u + 4], acc[8 * u + 5]), pack2(acc[8 * u + 6], acc[8 * u + 7]));
          asm volatile("" : "+r"(zk[u].x), "+r"(zk[u].y), "+r"(zk[u].z), "+r"(zk[u].w));
        }
        TRC(tr, w, tb + 12);
      }
      uint32_t hA[18][4];
      {
        float acc[144];
        const float c0 = __uint_as_float(lds32(sb + SM_OFF + 4));
#pragma unroll
        for (int i = 0; i < 144; i++) {
          asm volatile("fma.rn.f32 %0, %1, %2, %3;" : "=f"(acc[i]) : "f"(__uint_as_float(P.zero)), "f"((float)(i + 2)), "f"(c0));
        }
        uint32_t prev = 0;
        auto stage = [&](int kb) {
          mbar_wait_c(bars + B_FULL + c.s * 8, c.ph);
          TRC(tr && kb == 0, w, tb + 13);
          SCLK(22 + kb);
          const uint32_t st = sb + c.s * ST_BYTES, rt = sb + SM_RT + kb * 128 + t * 8;
          uint64_t db = dsc2(dlo(st + ST_B, 4608), 0, 8 + P.zero);
          uint32_t a[4][4];
#pragma unroll
          for (int kk = 0; kk < 4; kk++) {
            uint32_t r[4];
            ldsm4(r, st + (aoff ^ (kk << 5)));
            const uint2 sc = lds64(rt + kk * 32);
            a[kk][0] = hmul2(__byte_perm(r[0], r[2], 0x5410), sc.x); a[kk][2] = hmul2(__byte_perm(r[0], r[2], 0x7632), sc.y);
            a[kk][1] = hmul2(__byte_perm(r[1], r[3], 0x5410), sc.x); a[kk][3] = hmul2(__byte_perm(r[1], r[3], 0x7632), sc.y);
          }
          wgmma_fence();
#pragma unroll
          for (int i = 0; i < 8; i++) {
            const int kk = i & 3, hf = i >> 2;
            wgmma_rs_n144(acc + hf * 72, a[kk], db, 1);
            dadd(db, i == 3 ? 144u - 3 * 576 : 576 + P.zero);
            if (i == 0) { wgmma_commit(); wgmma_wait<1>(); release_if(kb, prev); }
            if (i == 3) wgmma_commit();
          }
          wgmma_commit();
          prev = c.s; c.next();
        };
        mbar_wait_c(bars + B_RT, L);
#pragma unroll 1
        for (int kb = 0; kb < 32; kb += 2) {
          if (kb == 8) mbar_wait_c(bars + B_RT1, L);
          MCLK((kb & 7) == 4, 10 + (kb >> 3));
          stage(kb);
          stage(kb + 1);
        }
        if (w == 1) bar_arrive(6, 256);
        HCLK(0);
        mbar_wait_c(bars + B_CV + w * 8, L);
        HCLK(1);
        const float gk = 0.5f / GA;
        const float c1 = __uint_as_float(lds32(sb + SM_OFF + 4));
        const float gb0 = -gk * (c1 + __uint_as_float(lds32(sb + SM_CV + w * 256 + (16 * q + g) * 4))), gb1 = -gk * (c1 + __uint_as_float(lds32(sb + SM_CV + w * 256 + (16 * q + g + 8) * 4)));
        mbar_wait_c(w ? bars + B_FULL + c.s * 8 : bars + B_ZB, w ? c.ph : L);
        HCLK(2);
        const uint32_t sx = c.s;
        c.next();
        const uint32_t zt = sb + tid * 16, zs = zt + sx * ST_BYTES + w * 24576;
        uint4 zz[18];
        auto zload = [&](int u) {
          if (ZW && u == ZW && P.zero) __nanosleep(0);
          if (u >= 12 && u < 16) zz[u] = zk[u - 12]; else zz[u] = lds128(u == 17 ? zt + SM_STG : zs + (u < 12 ? u : 12) * 2048);
        };
#pragma unroll
        for (int u = 0; u < ZA; u++) zload(u);
#pragma unroll
        for (int u = 0; u < 18; u++) {
          if (u == 0) { wgmma_wait<1>(); HCLK(3); }
          if (u == 9) {
            HCLK(4);
            wgmma_wait<0>();
            HCLK(5);
            release(prev);
            mbar_arrive_if(L == 0 && lane == 0, ev + EV_P4 * 8);
            TRC(tr, w, tb + 14);
            SCLK(54);
          }
          if (u + ZA < 18) zload(u + ZA);
          const uint4 z = zz[u];
          hA[u][0] = hmul2(z.x, pack2(fmaf(acc[8 * u], gk, gb0), fmaf(acc[8 * u + 1], gk, gb0)));
          hA[u][1] = hmul2(z.y, pack2(fmaf(acc[8 * u + 2], gk, gb1), fmaf(acc[8 * u + 3], gk, gb1)));
          hA[u][2] = hmul2(z.z, pack2(fmaf(acc[8 * u + 4], gk, gb0), fmaf(acc[8 * u + 5], gk, gb0)));
          hA[u][3] = hmul2(z.w, pack2(fmaf(acc[8 * u + 6], gk, gb1), fmaf(acc[8 * u + 7], gk, gb1)));
        }
        uint32_t dep = P.zero;
#pragma unroll
        for (int u = 0; u < 18; u++) dep &= hA[u][0];
        release(sx, dep);
        TRC(tr, w, tb + 15);
        HCLK(6);
      }
      {
        const uint32_t el = elect_one();
#pragma unroll 1
        for (int p = 0; p < 9; p++) {
          float acc[32];
          if (w == 0) mbar_wait_c(bars + B_FULL + c.s * 8, c.ph);
          uint64_t db = dsc2(dlo(sb + c.s * ST_BYTES + ST_B + (j & 1) * 4096, 0), 0, 0x40000040u + P.zero);
          HCLK(7 + 2 * p);
          bar_sync(6 + w, 256);
          wgmma_fence();
#pragma unroll
          for (int kk = 0; kk < 18; kk++) {
            wgmma_rs_n64(acc, hA[kk], db, kk != 0);
            dadd(db, kk == 15 ? 128 - (j & 1) * (36864 >> 4) : 128 + P.zero);
            if (kk == PPK && (w == 0 || p < 8)) bar_arrive(7 - w, 256);
          }
          wgmma_commit();
          const uint32_t d = sb + (p & 3) * ST_BYTES, cb = p + j >= 9 ? p + j - 9 : p + j;
          if (el) asm volatile("cp.async.bulk.wait_group.read 3;" ::: "memory");
          __syncwarp();
          wgmma_wait<0>();
          HCLK(8 + 2 * p);
          MCLK(p == 1 || p == 8, 7 + (p >> 3));
          TRC(tr && p == 8, w, tb + 16);
          release_if(L == 0 || p < 5, c.s);
          c.next();
#pragma unroll
          for (int u = 0; u < 4; u++)
            stsm4(d + (aoff ^ (u << 5)), pack2(acc[8 * u], acc[8 * u + 1]), pack2(acc[8 * u + 2], acc[8 * u + 3]), pack2(acc[8 * u + 4], acc[8 * u + 5]), pack2(acc[8 * u + 6], acc[8 * u + 7]));
          fence_async_s();
          __syncwarp();
          tma3d_red_p(el, &P.red[L], cb * 64, rb * 64 + q * 16, w, d + w * 8192 + q * 2048);
          TRC(tr && p == 8, w, tb + 17);
        }
        if (el) asm volatile("cp.async.bulk.wait_group 0;" ::: "memory");
        HCLK(25);
        MCLK(1, 9);
        if (L == 0) signal(EV_PT);
        TRC(tr, w, tb + 18);
      }
    }
    if ((tid & 127) == 0) g_flags[(rb * 2 + w) * 32 + FR_EP + j] = epoch + 1;
    if (tid == 0) g_flags[FJ + j * 32 + FJ_EP + rb] = epoch + 1;
  }
}

typedef CUresult (*EncodeFn)(CUtensorMap*, CUtensorMapDataType, cuuint32_t, void*, const cuuint64_t*, const cuuint64_t*, const cuuint32_t*,
                             const cuuint32_t*, CUtensorMapInterleave, CUtensorMapSwizzle, CUtensorMapL2promotion, CUtensorMapFloatOOBfill);

static void make_map(EncodeFn fn, CUtensorMap* m, const void* ptr, int rank, uint64_t d0, uint64_t d1, uint64_t d2, uint64_t s1, uint64_t s2,
                     uint32_t b0, uint32_t b1, uint32_t b2, CUtensorMapSwizzle swz) {
  cuuint64_t dims[3] = {d0, d1, d2}, strides[2] = {s1, s2};
  cuuint32_t box[3] = {b0, b1, b2}, es[3] = {1, 1, 1};
  fn(m, CU_TENSOR_MAP_DATA_TYPE_BFLOAT16, rank, const_cast<void*>(ptr), dims, strides, box, es, CU_TENSOR_MAP_INTERLEAVE_NONE, swz,
     CU_TENSOR_MAP_L2_PROMOTION_L2_128B, CU_TENSOR_MAP_FLOAT_OOB_FILL_NONE);
}

}

extern "C" void kernel_launch(void* const* d_in, const int* in_sizes, int n_in, void* d_out, int out_size) {
  using namespace mk;
  (void)in_sizes; (void)n_in; (void)out_size;
  static EncodeFn fn = nullptr;
  static uint8_t *wq, *xb;
  static float* csp;
  if (!fn) {
    cudaGetSymbolAddress((void**)&wq, g_WQ);
    cudaGetSymbolAddress((void**)&xb, g_X);
    cudaGetSymbolAddress((void**)&csp, g_CSP);
    cudaDriverEntryPointQueryResult qr;
    cudaGetDriverEntryPoint("cuTensorMapEncodeTiled", (void**)&fn, cudaEnableDefault, &qr);
    cudaFuncSetAttribute(mega_kernel, cudaFuncAttributeMaxDynamicSharedMemorySize, SM_TOTAL);
  }
  Params p;
  p.wqkv = (const __nv_bfloat16*)d_in[1];
  p.w_in = (const __nv_bfloat16*)d_in[4];
  p.w_sp = (const __nv_bfloat16*)d_in[5];
  p.b_sp = (const __nv_bfloat16*)d_in[6];
  p.w_out = (const __nv_bfloat16*)d_in[7];
  p.zero = 0;
  p.wq = wq;
  p.csp = csp;
  p.xs[0] = (uint8_t*)d_in[0];
  p.xs[1] = xb;
  p.xs[2] = (uint8_t*)d_out;
  make_map(fn, &p.wsp, p.w_sp, 3, 2048, 1024, 2, 8192, 4096, 64, 64, 2, CU_TENSOR_MAP_SWIZZLE_128B);
  for (int i = 0; i < 2; i++) {
    make_map(fn, &p.red[i], p.xs[i + 1], 3, DM, 1024, 2, 2304, 1152, 64, 16, 1, CU_TENSOR_MAP_SWIZZLE_128B);
    make_map(fn, &p.res[i], p.xs[i], 3, DM, 1024, 2, 2304, 1152, 144, 64, 1, CU_TENSOR_MAP_SWIZZLE_NONE);
  }
  make_map(fn, &p.psn, d_out, 3, DM, 1024, 2, 2304, 1152, 144, 4, 1, CU_TENSOR_MAP_SWIZZLE_NONE);
  for (int i = 0; i < 3; i++) make_map(fn, &p.act[i], p.xs[i], 3, DM, 1024, 2, 2304, 1152, 64, 64, 1, CU_TENSOR_MAP_SWIZZLE_128B);
  {
    cuuint64_t dims[4] = {8, 8, 72, 72}, strides[3] = {1152, 16, 9216};
    cuuint32_t box[4] = {8, 8, 9, 5}, es[4] = {1, 1, 1, 1};
    fn(&p.wo8, CU_TENSOR_MAP_DATA_TYPE_BFLOAT16, 4, d_in[2], dims, strides, box, es, CU_TENSOR_MAP_INTERLEAVE_NONE, CU_TENSOR_MAP_SWIZZLE_NONE,
       CU_TENSOR_MAP_L2_PROMOTION_L2_128B, CU_TENSOR_MAP_FLOAT_OOB_FILL_NONE);
  }
  for (int i = 0; i < 2; i++) {
    cuuint64_t dims[4] = {i ? 4608u : 2304u, 8, i ? 1u : 2u, 72}, strides[3] = {9216, 4608, 8 * 9216};
    cuuint32_t box[4] = {i ? 64u : 32u, 8, i ? 1u : 2u, 18}, es[4] = {1, 1, 1, 1};
    fn(i ? &p.win64 : &p.win, CU_TENSOR_MAP_DATA_TYPE_BFLOAT16, 4, d_in[4], dims, strides, box, es, CU_TENSOR_MAP_INTERLEAVE_NONE,
       i ? CU_TENSOR_MAP_SWIZZLE_128B : CU_TENSOR_MAP_SWIZZLE_64B, CU_TENSOR_MAP_L2_PROMOTION_L2_128B, CU_TENSOR_MAP_FLOAT_OOB_FILL_NONE);
  }
  make_map(fn, &p.wout, p.w_out, 2, 576, 2304, 1, 1152, 0, 64, 144, 1, CU_TENSOR_MAP_SWIZZLE_128B);
  mega_kernel<<<NGRID, 384, SM_TOTAL, cudaStreamPerThread>>>(p);
}
```

```cpp
#include <cuda_runtime.h>
#include <cuda.h>
#include <cuda_bf16.h>
#include <stdint.h>

#define MK_TRACE 0
#define MK_DBG 0
#define P5TRACE 0
#define LAG1 3
#define PP3 32
#define PP30 33
#define SPL 2
#define NAP 200
#define NAP0 8000
#define KS2 2
#define KS3 2
#define RL3 21
#define PAD 0
#define ZA 4
#define ZW 10
#define GM2 1
#define GMM 1
#define GM1 2
#define C0S 32.f
#define OFA 0.125f
#define OFK 2.f
#define PPK 15

namespace mk {

constexpr int SEQ = 2048, DM = 576, FH = 2304;
constexpr int NCTA = 128;
constexpr int NGRID = 132;
constexpr uint32_t ZB = 36864;
constexpr uint32_t WQ_SL = 72 * 3456;
constexpr uint32_t WO_SL = 72 * 1152;
constexpr float LN_EPS = 1e-5f;
constexpr float GA = 0.3292034911525734f, GB = 2.423681954311584f;

constexpr uint32_t ST_BYTES = 53248, ST_B = 16384, NST = 4;
constexpr uint32_t SM_STG = NST * ST_BYTES;
constexpr uint32_t SM_BAR = SM_STG + 2 * 9216;
constexpr uint32_t SM_OFF = SM_BAR + 1008;
constexpr uint32_t SM_TOTAL = SM_BAR + 1024;
constexpr uint32_t SM_RT = SM_STG + 4096, SM_CV = SM_STG + 12288, SM_WT = SM_CV + 512;
constexpr uint32_t SM_WOI = 44032, SM_CSQ = 49792, SM_XST = 50688;
constexpr uint32_t B_FULL = 0, B_EMPTY = 32, B_FULLA = 64, B_RES = 128, B_WT = 144, B_IMG = 160, B_WOI = 168, B_ZB = 176, B_GATE3 = 184, B_Z1 = 192, B_LAG = 200,
                   B_RT = 208, B_CSQ = 216, B_CV = 224, B_AD = 240, B_EVT = 272, B_RT1 = 368, B_XS = 624, B_XRW = 384, B_FA3 = 400, B_EA3 = 544;
enum { EV_PT = 0, EV_O = 1, EV_X1 = 2, EV_ZN = 3, EV_Z1 = 4, EV_P4 = 5, EV_N = 6 };

enum { FR_X2 = 0, FR_O = 1, FR_X1 = 3, FR_EP = 16, FJ = 32 * 32, FJ_WQ = 0, FJ_WO = 1, FJ_WQ0 = 2, FJ_ZN = 3, FJ_P4 = 5, FJ_EP = 16, F_N = FJ + 8 * 32 };

__device__ __align__(1024) uint8_t g_Z[512 * ZB];
constexpr uint32_t POISON = 0xffffffffu;
__device__ __align__(1024) uint8_t g_O[32 * 2 * ZB];
__device__ __align__(1024) uint4 g_RD[NCTA * 36 * 256];
__device__ __align__(1024) uint8_t g_X[SEQ * DM * 2];
#define SLOW(i) do {} while (0)
__device__ __align__(1024) uint8_t g_WQ[8 * WQ_SL];
__device__ __align__(1024) uint8_t g_WO[8 * WO_SL];
__device__ __align__(1024) float g_CSP[2 * NCTA * 216];
__device__ __align__(1024) uint2 g_RT[SEQ];
__device__ __align__(1024) uint4 g_XST[2 * SEQ];
__device__ __align__(1024) uint4 g_ST1[SEQ * 8];
__device__ __align__(1024) uint4 g_ZST[SEQ * 8];
__device__ __align__(1024) uint4 g_HALO[32 * 8 * 6 * 32];
__device__ __align__(1024) uint32_t g_flags[F_N];

struct Params {
  const __nv_bfloat16 *wqkv;
  uint8_t* wq;
  float* csp;
  uint32_t zero;
  const __nv_bfloat16 *w_in, *w_sp, *b_sp, *w_out;
  uint8_t* xs[3];
  CUtensorMap wo8, wsp, win, win64, wout;
  CUtensorMap act[3];
  CUtensorMap res[2];
  CUtensorMap red[2];
  CUtensorMap psn;
};

__device__ __forceinline__ uint32_t smem_u32(const void* p) { return (uint32_t)__cvta_generic_to_shared(p); }
__device__ __forceinline__ void mbar_init(uint32_t bar, uint32_t cnt) { asm volatile("mbarrier.init.shared::cta.b64 [%0], %1;" ::"r"(bar), "r"(cnt)); }
__device__ __forceinline__ void mbar_arrive(uint32_t bar) { asm volatile("mbarrier.arrive.shared::cta.b64 _, [%0];" ::"r"(bar) : "memory"); }
__device__ __forceinline__ void mbar_wait(uint32_t bar, uint32_t parity) {
  asm volatile(
      "{\n.reg .pred p;\n.reg .u32 c;\nmov.u32 c, 0;\nLAB_WAIT:\n"
      "mbarrier.try_wait.parity.shared::cta.b64 p, [%0], %1;\n@p bra LAB_DONE;\n"
      "add.u32 c, c, 1;\nsetp.lt.u32 p, c, 0x100000;\n@p bra LAB_WAIT;\ntrap;\nLAB_DONE:\n}" ::"r"(bar), "r"(parity)
      : "memory");
}
__device__ __forceinline__ void mbar_wait_c(uint32_t bar, uint32_t parity) {
  asm volatile("{\n.reg .pred p;\nLAB_WAIT:\nmbarrier.try_wait.parity.shared::cta.b64 p, [%0], %1;\n@!p bra LAB_WAIT;\n}" ::"r"(bar), "r"(parity) : "memory");
}
__device__ __forceinline__ void flag_wait(const uint32_t* f, uint32_t target) {
  asm volatile(
      "{\n.reg .pred p;\n.reg .u32 c, v;\nmov.u32 c, 0;\nLAB_WAIT:\n"
      "ld.relaxed.gpu.global.u32 v, [%0];\nsub.u32 v, v, %1;\nsetp.ge.s32 p, v, 0;\n@p bra LAB_DONE;\n"
      "add.u32 c, c, 1;\nsetp.lt.u32 p, c, 0x400000;\n@p bra LAB_WAIT;\ntrap;\nLAB_DONE:\nfence.acquire.gpu;\n}" ::"l"(f), "r"(target)
      : "memory");
}
__device__ __forceinline__ void fence_gpu() { asm volatile("fence.acq_rel.gpu;" ::: "memory"); }
__device__ __forceinline__ void fence_async_g() { asm volatile("fence.proxy.async.global;" ::: "memory"); }
__device__ __forceinline__ void fence_async_s() { asm volatile("fence.proxy.async.shared::cta;" ::: "memory"); }
__device__ __forceinline__ uint32_t elect_one() {
  uint32_t p; asm volatile("{\n.reg .pred P;\nelect.sync _|P, 0xffffffff;\nselp.u32 %0, 1, 0, P;\n}" : "=r"(p)); return p;
}
__device__ __forceinline__ void expect_tx_p(uint32_t el, uint32_t bar, uint32_t bytes) {
  asm volatile("{\n.reg .pred P;\nsetp.ne.u32 P, %2, 0;\n@P mbarrier.arrive.expect_tx.shared::cta.b64 _, [%0], %1;\n}" ::"r"(bar), "r"(bytes), "r"(el) : "memory");
}
__device__ __forceinline__ void bulk_load_p(uint32_t el, uint32_t dst, const void* src, uint32_t bytes, uint32_t bar) {
  asm volatile("{\n.reg .pred P;\nsetp.ne.u32 P, %4, 0;\n@P cp.async.bulk.shared::cluster.global.mbarrier::complete_tx::bytes [%0], [%1], %2, [%3];\n}" ::"r"(dst), "l"(src), "r"(bytes), "r"(bar), "r"(el) : "memory");
}
__device__ __forceinline__ uint64_t policy_evict_first() { uint64_t p; asm("createpolicy.fractional.L2::evict_first.b64 %0, 1.0;" : "=l"(p)); return p; }
__device__ __forceinline__ void bulk_load_h(uint32_t el, uint32_t dst, const void* src, uint32_t bytes, uint32_t bar, bool ef, uint64_t pol) {
  if (ef) {
    asm volatile("{\n.reg .pred P;\nsetp.ne.u32 P, %4, 0;\n@P cp.async.bulk.shared::cluster.global.mbarrier::complete_tx::bytes.L2::cache_hint [%0], [%1], %2, [%3], %5;\n}" ::"r"(dst), "l"(src), "r"(bytes), "r"(bar), "r"(el), "l"(pol) : "memory");
  } else {
    asm volatile("{\n.reg .pred P;\nsetp.ne.u32 P, %4, 0;\n@P cp.async.bulk.shared::cluster.global.mbarrier::complete_tx::bytes [%0], [%1], %2, [%3];\n}" ::"r"(dst), "l"(src), "r"(bytes), "r"(bar), "r"(el) : "memory");
  }
}
__device__ __forceinline__ void bulk_mc_h(uint32_t el, uint32_t dst, const void* src, uint32_t bytes, uint32_t bar, bool ef, uint64_t pol) {
  if (ef) {
    asm volatile("{\n.reg .pred P;\nsetp.ne.u32 P, %4, 0;\n@P cp.async.bulk.shared::cluster.global.mbarrier::complete_tx::bytes.multicast::cluster.L2::cache_hint [%0], [%1], %2, [%3], %5, %6;\n}" ::"r"(dst), "l"(src), "r"(bytes), "r"(bar), "r"(el), "h"((uint16_t)3), "l"(pol) : "memory");
  } else {
    asm volatile("{\n.reg .pred P;\nsetp.ne.u32 P, %4, 0;\n@P cp.async.bulk.shared::cluster.global.mbarrier::complete_tx::bytes.multicast::cluster [%0], [%1], %2, [%3], %5;\n}" ::"r"(dst), "l"(src), "r"(bytes), "r"(bar), "r"(el), "h"((uint16_t)3) : "memory");
  }
}
__device__ __forceinline__ void tma3d_h(uint32_t el, uint32_t dst, const CUtensorMap* m, int c0, int c1, int c2, uint32_t bar, bool ef, uint64_t pol) {
  if (ef) {
    asm volatile("{\n.reg .pred P;\nsetp.ne.u32 P, %6, 0;\n@P cp.async.bulk.tensor.3d.shared::cluster.global.mbarrier::complete_tx::bytes.L2::cache_hint [%0], [%1, {%3, %4, %5}], [%2], %7;\n}" ::"r"(dst), "l"(m), "r"(bar), "r"(c0), "r"(c1), "r"(c2), "r"(el), "l"(pol) : "memory");
  } else {
    asm volatile("{\n.reg .pred P;\nsetp.ne.u32 P, %6, 0;\n@P cp.async.bulk.tensor.3d.shared::cluster.global.mbarrier::complete_tx::bytes [%0], [%1, {%3, %4, %5}], [%2];\n}" ::"r"(dst), "l"(m), "r"(bar), "r"(c0), "r"(c1), "r"(c2), "r"(el) : "memory");
  }
}
__device__ __forceinline__ void tma2d_mc_h(uint32_t el, uint32_t dst, const CUtensorMap* m, int c0, int c1, uint32_t bar, bool ef, uint64_t pol) {
  if (ef) {
    asm volatile("{\n.reg .pred P;\nsetp.ne.u32 P, %5, 0;\n@P cp.async.bulk.tensor.2d.shared::cluster.global.mbarrier::complete_tx::bytes.multicast::cluster.L2::cache_hint [%0], [%1, {%3, %4}], [%2], %6, %7;\n}" ::"r"(dst), "l"(m), "r"(bar), "r"(c0), "r"(c1), "r"(el), "h"((uint16_t)3), "l"(pol) : "memory");
  } else {
    asm volatile("{\n.reg .pred P;\nsetp.ne.u32 P, %5, 0;\n@P cp.async.bulk.tensor.2d.shared::cluster.global.mbarrier::complete_tx::bytes.multicast::cluster [%0], [%1, {%3, %4}], [%2], %6;\n}" ::"r"(dst), "l"(m), "r"(bar), "r"(c0), "r"(c1), "r"(el), "h"((uint16_t)3) : "memory");
  }
}
__device__ __forceinline__ void tma4d_mc(uint32_t el, uint32_t dst, const CUtensorMap* m, int c0, int c3, uint32_t bar, uint64_t pol) {
  asm volatile("{\n.reg .pred P;\nsetp.ne.u32 P, %5, 0;\n@P cp.async.bulk.tensor.4d.shared::cluster.global.mbarrier::complete_tx::bytes.multicast::cluster.L2::cache_hint [%0], [%1, {%3, 0, 0, %4}], [%2], %6, %7;\n}" ::"r"(dst), "l"(m), "r"(bar), "r"(c0), "r"(c3), "r"(el), "h"((uint16_t)3), "l"(pol) : "memory");
}
__device__ __forceinline__ void mbar_arrive_cluster(uint32_t addr) { asm volatile("mbarrier.arrive.shared::cluster.b64 _, [%0];" ::"r"(addr) : "memory"); }
__device__ __forceinline__ void mbar_arrive_cluster_if(bool c, uint32_t addr) {
  asm volatile("{\n.reg .pred P;\nsetp.ne.u32 P, %1, 0;\n@P mbarrier.arrive.shared::cluster.b64 _, [%0];\n}" ::"r"(addr), "r"((uint32_t)c) : "memory");
}
__device__ __forceinline__ void mbar_arrive_if(bool c, uint32_t addr) {
  asm volatile("{\n.reg .pred P;\nsetp.ne.u32 P, %1, 0;\n@P mbarrier.arrive.shared::cta.b64 _, [%0];\n}" ::"r"(addr), "r"((uint32_t)c) : "memory");
}
__device__ __forceinline__ uint32_t mapa(uint32_t addr, uint32_t rank) { uint32_t r; asm("mapa.shared::cluster.u32 %0, %1, %2;" : "=r"(r) : "r"(addr), "r"(rank)); return r; }
__device__ __forceinline__ void bulk_store_p(uint32_t el, void* dst, uint32_t src, uint32_t bytes) {
  asm volatile("{\n.reg .pred P;\nsetp.ne.u32 P, %3, 0;\n@P cp.async.bulk.global.shared::cta.bulk_group [%0], [%1], %2;\n}" ::"l"(dst), "r"(src), "r"(bytes), "r"(el) : "memory");
}
__device__ __forceinline__ void flag_release_p(uint32_t el, uint32_t* f) {
  asm volatile("{\n.reg .pred P;\nsetp.ne.u32 P, %1, 0;\n@P red.release.gpu.global.add.u32 [%0], 1;\n}" ::"l"(f), "r"(el) : "memory");
}
__device__ __forceinline__ void flag_add_p(uint32_t el, uint32_t* f) {
  asm volatile("{\n.reg .pred P;\nsetp.ne.u32 P, %1, 0;\n@P red.relaxed.gpu.global.add.u32 [%0], 1;\n}" ::"l"(f), "r"(el) : "memory");
}
__device__ __forceinline__ void prefetch_l2(const void* src, uint32_t bytes) { asm volatile("cp.async.bulk.prefetch.L2.global [%0], %1;" ::"l"(src), "r"(bytes) : "memory"); }
__device__ __forceinline__ void prefetch_map(const CUtensorMap* m) { asm volatile("prefetch.tensormap [%0];" ::"l"(m) : "memory"); }
__device__ __forceinline__ void wgmma_fence() { asm volatile("wgmma.fence.sync.aligned;" ::: "memory"); }
__device__ __forceinline__ void wgmma_commit() { asm volatile("wgmma.commit_group.sync.aligned;" ::: "memory"); }
template <int N> __device__ __forceinline__ void wgmma_wait() { asm volatile("wgmma.wait_group.sync.aligned %0;" ::"n"(N) : "memory"); }
__device__ __forceinline__ uint32_t dlo(uint32_t addr, uint32_t lbo) { return ((addr & 0x3FFFF) >> 4) + ((lbo >> 4) << 16); }
template <uint32_t SBO, uint32_t SWZ> __device__ __forceinline__ uint64_t dsc(uint32_t lo, uint32_t off) {
  uint64_t d; asm("mov.b64 %0, {%1, %2};" : "=l"(d) : "r"(lo + (off >> 4)), "n"((SBO >> 4) | (SWZ << 30))); return d;
}
__device__ __forceinline__ uint64_t dsc2(uint32_t lo, uint32_t off, uint32_t hi) {
  uint64_t d; asm("mov.b64 %0, {%1, %2};" : "=l"(d) : "r"(lo + (off >> 4)), "r"(hi)); return d;
}
__device__ __forceinline__ uint64_t dat(uint64_t d, uint32_t off, uint32_t one) { uint64_t r; asm("mad.wide.u32 %0, %1, %2, %3;" : "=l"(r) : "r"(one), "r"(off >> 4), "l"(d)); return r; }
__device__ __forceinline__ void dadd(uint64_t& d, uint32_t v) {
  asm("{\n.reg .b32 lo, hi;\nmov.b64 {lo, hi}, %0;\nadd.u32 lo, lo, %1;\nmov.b64 %0, {lo, hi};\n}" : "+l"(d) : "r"(v));
}
template <int R> __device__ __forceinline__ void reg_alloc() { asm volatile("setmaxnreg.inc.sync.aligned.u32 %0;" ::"n"(R)); }
template <int R> __device__ __forceinline__ void reg_dealloc() { asm volatile("setmaxnreg.dec.sync.aligned.u32 %0;" ::"n"(R)); }
__device__ __forceinline__ void bar_sync(int id, int n) { asm volatile("bar.sync %0, %1;" ::"r"(id), "r"(n) : "memory"); }
__device__ __forceinline__ void bar_arrive(int id, int n) { asm volatile("bar.arrive %0, %1;" ::"r"(id), "r"(n) : "memory"); }
__device__ __forceinline__ void ldsm4(uint32_t* r, uint32_t addr) {
  asm volatile("ldmatrix.sync.aligned.m8n8.x4.shared.b16 {%0,%1,%2,%3}, [%4];" : "=r"(r[0]), "=r"(r[1]), "=r"(r[2]), "=r"(r[3]) : "r"(addr) : "memory");
}
__device__ __forceinline__ uint32_t movm(uint32_t a) { uint32_t d; asm volatile("movmatrix.sync.aligned.m8n8.trans.b16 %0, %1;" : "=r"(d) : "r"(a)); return d; }
__device__ __forceinline__ void mma16(float* c, uint32_t a0, uint32_t a1, uint32_t a2, uint32_t a3, uint32_t b0, uint32_t b1) {
  asm volatile("mma.sync.aligned.m16n8k16.row.col.f32.bf16.bf16.f32 {%0,%1,%2,%3}, {%4,%5,%6,%7}, {%8,%9}, {%10,%10,%10,%10};"
               : "=f"(c[0]), "=f"(c[1]), "=f"(c[2]), "=f"(c[3]) : "r"(a0), "r"(a1), "r"(a2), "r"(a3), "r"(b0), "r"(b1), "f"(0.f));
}
__device__ __forceinline__ void mma8(float* c, uint32_t a0, uint32_t a1, uint32_t b0) {
  asm volatile("mma.sync.aligned.m16n8k8.row.col.f32.bf16.bf16.f32 {%0,%1,%2,%3}, {%4,%5}, {%6}, {%0,%1,%2,%3};"
               : "+f"(c[0]), "+f"(c[1]), "+f"(c[2]), "+f"(c[3]) : "r"(a0), "r"(a1), "r"(b0));
}
__device__ __forceinline__ uint32_t pack2(float lo, float hi) { uint32_t r; asm("cvt.rn.bf16x2.f32 %0, %1, %2;" : "=r"(r) : "f"(hi), "f"(lo)); return r; }
__device__ __forceinline__ float blo(uint32_t v) { return __uint_as_float(v << 16); }
__device__ __forceinline__ float bhi(uint32_t v) { return __uint_as_float(v & 0xffff0000u); }
__device__ __forceinline__ float tanh_fast(float x) { float y; asm("tanh.approx.f32 %0, %1;" : "=f"(y) : "f"(x)); return y; }
__device__ __forceinline__ float rcp_fast(float x) { float y; asm("rcp.approx.ftz.f32 %0, %1;" : "=f"(y) : "f"(x)); return y; }
__device__ __forceinline__ float ex2(float x) { float y; asm("ex2.approx.ftz.f32 %0, %1;" : "=f"(y) : "f"(x)); return y; }
__device__ __forceinline__ float qsum(float v) { v += __shfl_xor_sync(~0u, v, 1); v += __shfl_xor_sync(~0u, v, 2); return v; }
__device__ __forceinline__ float qmax(float v) { v = fmaxf(v, __shfl_xor_sync(~0u, v, 1)); v = fmaxf(v, __shfl_xor_sync(~0u, v, 2)); return v; }
__device__ __forceinline__ void stg32(void* p, uint32_t v) { asm volatile("st.global.u32 [%0], %1;" ::"l"(p), "r"(v) : "memory"); }
__device__ __forceinline__ void stg128(void* p, uint32_t a, uint32_t b, uint32_t c, uint32_t d) { asm volatile("st.global.v4.u32 [%0], {%1,%2,%3,%4};" ::"l"(p), "r"(a), "r"(b), "r"(c), "r"(d) : "memory"); }
__device__ __forceinline__ uint32_t ldcg32(const void* p) { uint32_t v; asm volatile("ld.global.L1::no_allocate.u32 %0, [%1];" : "=r"(v) : "l"(p) : "memory"); return v; }
__device__ __forceinline__ uint32_t ldgpu32(const void* p) { uint32_t v; asm volatile("ld.relaxed.gpu.global.u32 %0, [%1];" : "=r"(v) : "l"(p) : "memory"); return v; }
__device__ __forceinline__ uint32_t ldca32(const void* p) { uint32_t v; asm volatile("ld.global.ca.u32 %0, [%1];" : "=r"(v) : "l"(p) : "memory"); return v; }
__device__ __forceinline__ void stg128_if(bool c, void* p, uint32_t a, uint32_t b, uint32_t cc, uint32_t d) {
  asm volatile("{\n.reg .pred P;\nsetp.ne.u32 P, %5, 0;\n@P st.global.v4.u32 [%0], {%1,%2,%3,%4};\n}" ::"l"(p), "r"(a), "r"(b), "r"(cc), "r"(d), "r"((uint32_t)c) : "memory");
}
__device__ __forceinline__ uint2 lds64(uint32_t a) { uint2 v; asm volatile("ld.shared.v2.u32 {%0,%1}, [%2];" : "=r"(v.x), "=r"(v.y) : "r"(a) : "memory"); return v; }
__device__ __forceinline__ uint4 ldcg128(const void* p) { uint4 v; asm volatile("ld.global.cg.v4.u32 {%0,%1,%2,%3}, [%4];" : "=r"(v.x), "=r"(v.y), "=r"(v.z), "=r"(v.w) : "l"(p) : "memory"); return v; }
__device__ __forceinline__ uint32_t ldnc16(const void* p) { uint16_t v; asm volatile("ld.global.nc.u16 %0, [%1];" : "=h"(v) : "l"(p)); return v; }
__device__ __forceinline__ uint4 ldnc128(const void* p) { uint4 v; asm volatile("ld.global.nc.v4.u32 {%0,%1,%2,%3}, [%4];" : "=r"(v.x), "=r"(v.y), "=r"(v.z), "=r"(v.w) : "l"(p)); return v; }
__device__ __forceinline__ uint32_t hsub2(uint32_t a, uint32_t b) { uint32_t d; asm("sub.rn.bf16x2 %0, %1, %2;" : "=r"(d) : "r"(a), "r"(b)); return d; }
__device__ __forceinline__ void stg32_if(bool c, void* p, uint32_t v) {
  asm volatile("{\n.reg .pred P;\nsetp.ne.u32 P, %2, 0;\n@P st.global.u32 [%0], %1;\n}" ::"l"(p), "r"(v), "r"((uint32_t)c) : "memory");
}
__device__ __forceinline__ uint32_t hmul2(uint32_t a, uint32_t b) { uint32_t d; asm("mul.rn.bf16x2 %0, %1, %2;" : "=r"(d) : "r"(a), "r"(b)); return d; }
__device__ __forceinline__ void sts32(uint32_t a, uint32_t v) { asm volatile("st.shared.u32 [%0], %1;" ::"r"(a), "r"(v) : "memory"); }
__device__ __forceinline__ uint32_t lds32(uint32_t a) { uint32_t v; asm volatile("ld.shared.u32 %0, [%1];" : "=r"(v) : "r"(a) : "memory"); return v; }
__device__ __forceinline__ void sts128(uint32_t a, uint32_t x, uint32_t y, uint32_t z, uint32_t w) { asm volatile("st.shared.v4.u32 [%0], {%1,%2,%3,%4};" ::"r"(a), "r"(x), "r"(y), "r"(z), "r"(w) : "memory"); }
__device__ __forceinline__ uint4 lds128(uint32_t a) { uint4 v; asm volatile("ld.shared.v4.u32 {%0,%1,%2,%3}, [%4];" : "=r"(v.x), "=r"(v.y), "=r"(v.z), "=r"(v.w) : "r"(a) : "memory"); return v; }
__device__ __forceinline__ void ll_st64(uint2* p, uint32_t v, uint32_t tag) {
  asm volatile("{\n.reg .b64 r;\nmov.b64 r, {%1,%2};\nst.relaxed.gpu.global.b64 [%0], r;\n}" ::"l"(p), "r"(v), "r"(tag) : "memory");
}
__device__ __forceinline__ uint2 ll_ld64(const uint2* p) {
  uint2 v; asm volatile("{\n.reg .b64 r;\nld.relaxed.gpu.global.b64 r, [%2];\nmov.b64 {%0,%1}, r;\n}" : "=r"(v.x), "=r"(v.y) : "l"(p) : "memory"); return v;
}
__device__ __forceinline__ void ll_st128(uint4* p, float a, float b, uint32_t tag, float c = 0.f) {
  asm volatile("{\n.reg .b128 r;\n.reg .b64 lo, hi;\nmov.b64 lo, {%1,%2};\nmov.b64 hi, {%3,%4};\nmov.b128 r, {lo, hi};\nst.relaxed.gpu.global.b128 [%0], r;\n}" ::"l"(p), "r"(__float_as_uint(a)), "r"(__float_as_uint(b)), "r"(tag), "r"(__float_as_uint(c)) : "memory");
}
__device__ __forceinline__ uint4 ll_ld128(const uint4* p) {
  uint4 v; asm volatile("{\n.reg .b128 r;\n.reg .b64 lo, hi;\nld.relaxed.gpu.global.b128 r, [%4];\nmov.b128 {lo, hi}, r;\nmov.b64 {%0,%1}, lo;\nmov.b64 {%2,%3}, hi;\n}" : "=r"(v.x), "=r"(v.y), "=r"(v.z), "=r"(v.w) : "l"(p) : "memory"); return v;
}
__device__ __forceinline__ void publish_p(uint32_t el, uint32_t* f) {
  asm volatile("{\n.reg .pred P;\nsetp.ne.u32 P, %1, 0;\n@P cp.async.bulk.commit_group;\n@P cp.async.bulk.wait_group 0;\n@P red.release.gpu.global.add.u32 [%0], 1;\n}" ::"l"(f), "r"(el) : "memory");
}
__device__ __forceinline__ void tma3d_red_p(uint32_t el, const CUtensorMap* m, int c0, int c1, int c2, uint32_t src) {
  asm volatile("{\n.reg .pred P;\nsetp.ne.u32 P, %5, 0;\n@P cp.reduce.async.bulk.tensor.3d.global.shared::cta.add.tile.bulk_group [%0, {%2, %3, %4}], [%1];\n@P cp.async.bulk.commit_group;\n}" ::"l"(m), "r"(src), "r"(c0), "r"(c1), "r"(c2), "r"(el) : "memory");
}
__device__ __forceinline__ void stsm4(uint32_t addr, uint32_t a, uint32_t b, uint32_t c, uint32_t d) {
  asm volatile("stmatrix.sync.aligned.m8n8.x4.shared.b16 [%0], {%1,%2,%3,%4};" ::"r"(addr), "r"(a), "r"(b), "r"(c), "r"(d) : "memory");
}
__device__ __forceinline__ void sts64(uint32_t a, uint32_t x, uint32_t y) { asm volatile("st.shared.v2.u32 [%0], {%1,%2};" ::"r"(a), "r"(x), "r"(y) : "memory"); }
__device__ __forceinline__ void ll_st128_if(bool on, uint4* p, float a, float b, uint32_t tag) {
  asm volatile("{\n.reg .pred P;\n.reg .b128 r;\n.reg .b64 lo, hi;\nsetp.ne.u32 P, %4, 0;\nmov.b64 lo, {%1,%2};\nmov.b64 hi, {%3,%3};\nmov.b128 r, {lo, hi};\n@P st.relaxed.gpu.global.b128 [%0], r;\n}" ::"l"(p), "r"(__float_as_uint(a)), "r"(__float_as_uint(b)), "r"(tag), "r"((uint32_t)on) : "memory");
}
__device__ __forceinline__ uint4 ldnc128_if(bool c, const void* p) {
  uint4 v = make_uint4(0u, 0u, 0u, 0u);
  asm volatile("{\n.reg .pred P;\nsetp.ne.u32 P, %5, 0;\n@P ld.global.nc.v4.u32 {%0,%1,%2,%3}, [%4];\n}" : "+r"(v.x), "+r"(v.y), "+r"(v.z), "+r"(v.w) : "l"(p), "r"((uint32_t)c));
  return v;
}
__device__ __forceinline__ uint32_t hfma2(uint32_t a, uint32_t b, uint32_t c) { uint32_t d; asm("fma.rn.bf16x2 %0, %1, %2, %3;" : "=r"(d) : "r"(a), "r"(b), "r"(c)); return d; }
__device__ __forceinline__ float2 lds64f(uint32_t a) { float2 v; asm volatile("ld.shared.v2.f32 {%0,%1}, [%2];" : "=f"(v.x), "=f"(v.y) : "r"(a) : "memory"); return v; }
#define TRC(cond, role, idx) do {} while (0)
#define TRV(role, idx, v) do {} while (0)

#define ACLK_INIT do {} while (0)
#define ACLK(i) do {} while (0)
#define ACLK_OUT do {} while (0)
#define QCLK(i) do {} while (0)
#define PH 1
#define RCLK(i) do {} while (0)
#define RCLK_INIT do {} while (0)
#define RCLK_OUT do {} while (0)
#define SCLK(i) do {} while (0)
#define HCLK(i) do {} while (0)
#define MCLK(c, i) do {} while (0)
#define CKK(i) do {} while (0)
#define CKK_OUT do {} while (0)
#define PL 1
#define PCLK(i) do {} while (0)
#define PQ 1
#define CLK_INIT do {} while (0)
#define CLK(i) do {} while (0)
#define CLK_OUT do {} while (0)

__device__ __forceinline__ void wgmma_ss_n216(float* d, uint64_t da, uint64_t db, int scaleD) {
  asm volatile("{\n.reg .pred p;\nsetp.ne.b32 p, %110, 0;\nwgmma.mma_async.sync.aligned.m64n216k16.f32.bf16.bf16 "
    "{%0,%1,%2,%3,%4,%5,%6,%7,%8,%9,%10,%11,%12,%13,%14,%15,%16,%17,%18,%19,%20,%21,%22,%23,%24,%25,%26,%27,%28,%29,%30,%31,%32,%33,%34,%35,%36,%37,%38,%39,%40,%41,%42,%43,%44,%45,%46,%47,%48,%49,%50,%51,%52,%53,%54,%55,%56,%57,%58,%59,%60,%61,%62,%63,%64,%65,%66,%67,%68,%69,%70,%71,%72,%73,%74,%75,%76,%77,%78,%79,%80,%81,%82,%83,%84,%85,%86,%87,%88,%89,%90,%91,%92,%93,%94,%95,%96,%97,%98,%99,%100,%101,%102,%103,%104,%105,%106,%107}, "
    "%108, %109, p, 1, 1, 0, 1;\n}\n"
    : "+f"(d[0]), "+f"(d[1]), "+f"(d[2]), "+f"(d[3]), "+f"(d[4]), "+f"(d[5]), "+f"(d[6]), "+f"(d[7]), "+f"(d[8]), "+f"(d[9]), "+f"(d[10]), "+f"(d[11]), "+f"(d[12]), "+f"(d[13]), "+f"(d[14]), "+f"(d[15]), "+f"(d[16]), "+f"(d[17]), "+f"(d[18]), "+f"(d[19]), "+f"(d[20]), "+f"(d[21]), "+f"(d[22]), "+f"(d[23]), "+f"(d[24]), "+f"(d[25]), "+f"(d[26]), "+f"(d[27]), "+f"(d[28]), "+f"(d[29]), "+f"(d[30]), "+f"(d[31]), "+f"(d[32]), "+f"(d[33]), "+f"(d[34]), "+f"(d[35]), "+f"(d[36]), "+f"(d[37]), "+f"(d[38]), "+f"(d[39]), "+f"(d[40]), "+f"(d[41]), "+f"(d[42]), "+f"(d[43]), "+f"(d[44]), "+f"(d[45]), "+f"(d[46]), "+f"(d[47]), "+f"(d[48]), "+f"(d[49]), "+f"(d[50]), "+f"(d[51]), "+f"(d[52]), "+f"(d[53]), "+f"(d[54]), "+f"(d[55]), "+f"(d[56]), "+f"(d[57]), "+f"(d[58]), "+f"(d[59]), "+f"(d[60]), "+f"(d[61]), "+f"(d[62]), "+f"(d[63]), "+f"(d[64]), "+f"(d[65]), "+f"(d[66]), "+f"(d[67]), "+f"(d[68]), "+f"(d[69]), "+f"(d[70]), "+f"(d[71]), "+f"(d[72]), "+f"(d[73]), "+f"(d[74]), "+f"(d[75]), "+f"(d[76]), "+f"(d[77]), "+f"(d[78]), "+f"(d[79]), "+f"(d[80]), "+f"(d[81]), "+f"(d[82]), "+f"(d[83]), "+f"(d[84]), "+f"(d[85]), "+f"(d[86]), "+f"(d[87]), "+f"(d[88]), "+f"(d[89]), "+f"(d[90]), "+f"(d[91]), "+f"(d[92]), "+f"(d[93]), "+f"(d[94]), "+f"(d[95]), "+f"(d[96]), "+f"(d[97]), "+f"(d[98]), "+f"(d[99]), "+f"(d[100]), "+f"(d[101]), "+f"(d[102]), "+f"(d[103]), "+f"(d[104]), "+f"(d[105]), "+f"(d[106]), "+f"(d[107])
    : "l"(da), "l"(db), "r"(scaleD));
}
__device__ __forceinline__ void wgmma_ss_n72(float* d, uint64_t da, uint64_t db, int scaleD) {
  asm volatile("{\n.reg .pred p;\nsetp.ne.b32 p, %38, 0;\nwgmma.mma_async.sync.aligned.m64n72k16.f32.bf16.bf16 "
    "{%0,%1,%2,%3,%4,%5,%6,%7,%8,%9,%10,%11,%12,%13,%14,%15,%16,%17,%18,%19,%20,%21,%22,%23,%24,%25,%26,%27,%28,%29,%30,%31,%32,%33,%34,%35}, "
    "%36, %37, p, 1, 1, 0, 1;\n}\n"
    : "+f"(d[0]), "+f"(d[1]), "+f"(d[2]), "+f"(d[3]), "+f"(d[4]), "+f"(d[5]), "+f"(d[6]), "+f"(d[7]), "+f"(d[8]), "+f"(d[9]), "+f"(d[10]), "+f"(d[11]), "+f"(d[12]), "+f"(d[13]), "+f"(d[14]), "+f"(d[15]), "+f"(d[16]), "+f"(d[17]), "+f"(d[18]), "+f"(d[19]), "+f"(d[20]), "+f"(d[21]), "+f"(d[22]), "+f"(d[23]), "+f"(d[24]), "+f"(d[25]), "+f"(d[26]), "+f"(d[27]), "+f"(d[28]), "+f"(d[29]), "+f"(d[30]), "+f"(d[31]), "+f"(d[32]), "+f"(d[33]), "+f"(d[34]), "+f"(d[35])
    : "l"(da), "l"(db), "r"(scaleD));
}
__device__ __forceinline__ void wgmma_rs_n144(float* d, const uint32_t* a, uint64_t db, int scaleD) {
  asm volatile("{\n.reg .pred p;\nsetp.ne.b32 p, %77, 0;\nwgmma.mma_async.sync.aligned.m64n144k16.f32.bf16.bf16 "
    "{%0,%1,%2,%3,%4,%5,%6,%7,%8,%9,%10,%11,%12,%13,%14,%15,%16,%17,%18,%19,%20,%21,%22,%23,%24,%25,%26,%27,%28,%29,%30,%31,%32,%33,%34,%35,%36,%37,%38,%39,%40,%41,%42,%43,%44,%45,%46,%47,%48,%49,%50,%51,%52,%53,%54,%55,%56,%57,%58,%59,%60,%61,%62,%63,%64,%65,%66,%67,%68,%69,%70,%71}, "
    "{%72,%73,%74,%75}, %76, p, 1, 1, 1;\n}\n"
    : "+f"(d[0]), "+f"(d[1]), "+f"(d[2]), "+f"(d[3]), "+f"(d[4]), "+f"(d[5]), "+f"(d[6]), "+f"(d[7]), "+f"(d[8]), "+f"(d[9]), "+f"(d[10]), "+f"(d[11]), "+f"(d[12]), "+f"(d[13]), "+f"(d[14]), "+f"(d[15]), "+f"(d[16]), "+f"(d[17]), "+f"(d[18]), "+f"(d[19]), "+f"(d[20]), "+f"(d[21]), "+f"(d[22]), "+f"(d[23]), "+f"(d[24]), "+f"(d[25]), "+f"(d[26]), "+f"(d[27]), "+f"(d[28]), "+f"(d[29]), "+f"(d[30]), "+f"(d[31]), "+f"(d[32]), "+f"(d[33]), "+f"(d[34]), "+f"(d[35]), "+f"(d[36]), "+f"(d[37]), "+f"(d[38]), "+f"(d[39]), "+f"(d[40]), "+f"(d[41]), "+f"(d[42]), "+f"(d[43]), "+f"(d[44]), "+f"(d[45]), "+f"(d[46]), "+f"(d[47]), "+f"(d[48]), "+f"(d[49]), "+f"(d[50]), "+f"(d[51]), "+f"(d[52]), "+f"(d[53]), "+f"(d[54]), "+f"(d[55]), "+f"(d[56]), "+f"(d[57]), "+f"(d[58]), "+f"(d[59]), "+f"(d[60]), "+f"(d[61]), "+f"(d[62]), "+f"(d[63]), "+f"(d[64]), "+f"(d[65]), "+f"(d[66]), "+f"(d[67]), "+f"(d[68]), "+f"(d[69]), "+f"(d[70]), "+f"(d[71])
    : "r"(a[0]), "r"(a[1]), "r"(a[2]), "r"(a[3]), "l"(db), "r"(scaleD));
}
__device__ __forceinline__ void wgmma_rs_n64(float* d, const uint32_t* a, uint64_t db, int scaleD) {
  asm volatile("{\n.reg .pred p;\nsetp.ne.b32 p, %37, 0;\nwgmma.mma_async.sync.aligned.m64n64k16.f32.bf16.bf16 "
    "{%0,%1,%2,%3,%4,%5,%6,%7,%8,%9,%10,%11,%12,%13,%14,%15,%16,%17,%18,%19,%20,%21,%22,%23,%24,%25,%26,%27,%28,%29,%30,%31}, "
    "{%32,%33,%34,%35}, %36, p, 1, 1, 1;\n}\n"
    : "+f"(d[0]), "+f"(d[1]), "+f"(d[2]), "+f"(d[3]), "+f"(d[4]), "+f"(d[5]), "+f"(d[6]), "+f"(d[7]), "+f"(d[8]), "+f"(d[9]), "+f"(d[10]), "+f"(d[11]), "+f"(d[12]), "+f"(d[13]), "+f"(d[14]), "+f"(d[15]), "+f"(d[16]), "+f"(d[17]), "+f"(d[18]), "+f"(d[19]), "+f"(d[20]), "+f"(d[21]), "+f"(d[22]), "+f"(d[23]), "+f"(d[24]), "+f"(d[25]), "+f"(d[26]), "+f"(d[27]), "+f"(d[28]), "+f"(d[29]), "+f"(d[30]), "+f"(d[31])
    : "r"(a[0]), "r"(a[1]), "r"(a[2]), "r"(a[3]), "l"(db), "r"(scaleD));
}

template <int V> struct Int { static constexpr int value = V; };
struct Cur {
  uint32_t s, ph;
  __device__ __forceinline__ void next() { if (++s == NST) { s = 0; ph ^= 1; } }
};

__device__ __forceinline__ uint8_t* z1_block(int rb, int w, int j) { return g_Z + (rb * 16 + w * 8 + j) * ZB; }
__device__ __forceinline__ uint8_t* o_block(int rb, int w) { return g_O + (rb * 2 + w) * (2 * ZB); }
__device__ __forceinline__ uint8_t* z2_block(int kb, int j) { return g_Z + (256 + kb * 8 + j) * ZB; }
__device__ __forceinline__ void combine8(float m0, float q0, float m1, float q1, float n, float eps, float& mean, float& rstd) {
  mean = qsum(m0 + m1) * 0.125f;
  float d0 = m0 - mean, d1 = m1 - mean;
  float M2 = qsum(q0 + q1 + n * (d0 * d0 + d1 * d1));
  rstd = rsqrtf(fmaf(M2, 0.125f / n, eps));
}
__device__ __forceinline__ void stat_get(const uint4* zs, uint32_t tag, float n, float eps, float& m0, float& r0, float& m1, float& r1) {
  uint4 a0, a1, b0, b1;
#pragma unroll 1
  for (int it = 0; it < (1 << 20); it++) {
    a0 = ll_ld128(zs); a1 = ll_ld128(zs + 64); b0 = ll_ld128(zs + 8); b1 = ll_ld128(zs + 72);
    if (__all_sync(~0u, a0.z == tag && a1.z == tag && b0.z == tag && b1.z == tag)) break;
  }
  combine8(__uint_as_float(a0.x), __uint_as_float(a0.y), __uint_as_float(a1.x), __uint_as_float(a1.y), n, eps, m0, r0);
  combine8(__uint_as_float(b0.x), __uint_as_float(b0.y), __uint_as_float(b1.x), __uint_as_float(b1.y), n, eps, m1, r1);
}

__device__ __forceinline__ void rows_fetch(uint32_t el, uint32_t xr, const uint8_t* src, uint32_t bar) {
  expect_tx_p(el, bar, 9216);
#pragma unroll 1
  for (int r = 0; r < 8; r++) bulk_load_p(el, xr + r * 1152, src + r * (DM * 4), 1152, bar);
}
__device__ __forceinline__ void rows_stats(uint32_t xr, uint4* dst, uint32_t tag, int lane) {
  float s[2] = {0.f, 0.f}, q[4] = {0.f, 0.f, 0.f, 0.f};
  const uint32_t a0 = xr + (lane >> 2) * 1152 + (((lane & 3) * 2) ^ (lane >> 2)) * 16;
  uint4 n0 = lds128(a0), n1 = lds128(a0 ^ 16);
#pragma unroll 1
  for (int e = 1; e <= 9; e++) {
    const uint32_t x[8] = {n0.x, n0.y, n0.z, n0.w, n1.x, n1.y, n1.z, n1.w};
    if (e < 9) { n0 = lds128(a0 + e * 128); n1 = lds128((a0 ^ 16) + e * 128); }
#pragma unroll
    for (int u = 0; u < 8; u++) {
      const float lo = blo(x[u]), hi = bhi(x[u]);
      s[u & 1] += lo + hi; q[(u & 1) * 2] = fmaf(lo, lo, q[(u & 1) * 2]); q[(u & 1) * 2 + 1] = fmaf(hi, hi, q[(u & 1) * 2 + 1]);
    }
  }
  const float sx = s[0] + s[1], sq = (q[0] + q[1]) + (q[2] + q[3]);
  const float m = qsum(sx) * (-1.f / DM), r = rsqrtf(fmaxf(fmaf(qsum(sq), 1.f / DM, -m * m), 0.f) + LN_EPS);
  if ((lane & 3) == 0) ll_st128(dst + (lane >> 2) * 2, m, r, tag);
}

__device__ __forceinline__ void poison(uint32_t el, uint32_t src, const CUtensorMap* m, int rb, int j, int lane) {
#pragma unroll 1
  for (int u = lane; u < 72; u += 32) sts128(src + u * 16, POISON, POISON, POISON, POISON);
  fence_async_s();
  __syncwarp();
#pragma unroll 1
  for (int u = 0; u < 16; u++) {
    __nanosleep(NAP);
    bulk_store_p(el, o_block(rb, u >> 3) + j * 9216 + (u & 7) * 1152, src, 1152);
    asm volatile("{\n.reg .pred P;\nsetp.ne.u32 P, %5, 0;\n@P cp.async.bulk.tensor.3d.global.shared::cta.tile.bulk_group [%0, {%2, %3, %4}], [%1];\n}" ::"l"(m), "r"(src), "r"((j & 6) * 72), "r"(rb * 64 + u * 4), "r"(j & 1), "r"(el) : "memory");
  }
}
__device__ __forceinline__ void mma16acc(float* c, const uint32_t* a, uint32_t b0, uint32_t b1) {
  asm volatile("mma.sync.aligned.m16n8k16.row.col.f32.bf16.bf16.f32 {%0,%1,%2,%3}, {%4,%5,%6,%7}, {%8,%9}, {%0,%1,%2,%3};"
               : "+f"(c[0]), "+f"(c[1]), "+f"(c[2]), "+f"(c[3]) : "r"(a[0]), "r"(a[1]), "r"(a[2]), "r"(a[3]), "r"(b0), "r"(b1));
}
template <int KS, int NG, int AK, int AH, int BK, int BG, class F> __device__ __forceinline__ void redo(float* acc, const uint8_t* pa, const uint8_t* pb, F f) {
#pragma unroll 1
  for (int k = 0; k < 36; k += KS) {
    uint32_t a[4 * KS], b[2 * KS][NG];
#pragma unroll 1
    for (int it = 0; it < (1 << 20); it++) {
      bool ok = true;
#pragma unroll
      for (int e = 0; e < 4 * KS; e++) a[e] = ldgpu32(pa + (e >> 1) * AK + (e & 1) * AH);
#pragma unroll
      for (int e = 0; e < 2 * KS * NG; e++) b[e / NG][e % NG] = ldca32(pb + (e / NG) * BK + (e % NG) * BG);
#pragma unroll
      for (int e = 0; e < 4 * KS; e++) ok = ok && a[e] != POISON;
      if (__all_sync(~0u, ok)) break;
    }
#pragma unroll
    for (int e = 0; e < KS; e++) f(a + 4 * e, k + e);
#pragma unroll
    for (int e = 0; e < KS * NG; e++) mma16acc(acc + 4 * (e % NG), a + 4 * (e / NG), movm(b[2 * (e / NG)][e % NG]), movm(b[2 * (e / NG) + 1][e % NG]));
    pa += 2 * KS * AK; pb += 2 * KS * BK;
  }
}
__device__ __forceinline__ bool any_nan(float a, float b) {
  return __any_sync(~0u, a != a || b != b);
}

__global__ void __cluster_dims__(2, 1, 1) __launch_bounds__(384, 1) mega_kernel(const __grid_constant__ Params P) {
  extern __shared__ __align__(1024) uint8_t smem_raw[];
  uint32_t ckk[8];
  (void)ckk;
  CKK(0);
  const uint32_t sb = smem_u32(smem_raw);
  const uint32_t bars = sb + SM_BAR;
  const int tid = threadIdx.x;
  int lane = tid & 31;
  const int wid = __shfl_sync(~0u, tid >> 5, 0);
  const int cl = blockIdx.x >> 1, tp = cl - 36, t7 = (tp * 37) >> 8;
  const int bid = (cl < 4 ? cl * 8 + 32 : tp < 0 ? cl - 4 : cl < 64 ? tp + t7 + 33 : cl) * 2 + (blockIdx.x & 1);
  if (bid >= NCTA) return;
  const int rb = bid & 15, j = bid >> 4;
  { const bool tr = (tid & 127) == 0 && tid < 256; const int w = tid >> 7; (void)tr; (void)w; TRC(tr, w, 0); }
  CKK(1);
  uint4 wv[5];
  const uint8_t* wsrc;
  {
    const int n8 = min(tid >> 3, 26), part = n8 / 9;
    const uint8_t* src = (const uint8_t*)P.wqkv + (8 * rb + (tid & 7)) * (3 * DM * 2) + (part * (DM - 72) + 72 * j + 8 * n8) * 2;
#pragma unroll
    for (int u = 0; u < SPL; u++) wv[u] = ldnc128_if(tid < 216, src + u * (128 * 3 * DM * 2));
    wsrc = src;
  }
  CKK(2);
  if (tid == 352) {
    for (int s = 0; s < (int)NST; s++) {
      mbar_init(bars + B_FULL + s * 8, 1); mbar_init(bars + B_EMPTY + s * 8, 16);
      mbar_init(bars + B_FULLA + s * 8, 1); mbar_init(bars + B_FULLA + 32 + s * 8, 1);
      mbar_init(bars + B_RES + s * 8, 1); mbar_init(bars + B_RT + s * 8, 1); mbar_init(bars + B_AD + s * 8, 2);
    }
    mbar_init(bars + B_IMG, 8); mbar_init(bars + B_RES + 8, 8); mbar_init(bars + B_WOI, 1); mbar_init(bars + B_GATE3, 3); mbar_init(bars + B_Z1, 1); mbar_init(bars + B_ZB, 1); mbar_init(bars + B_LAG, 4);
    mbar_init(bars + B_XS, 1); mbar_init(bars + B_XS + 8, 1); mbar_init(bars + B_RT1, 1); mbar_init(bars + B_XRW, 1); mbar_init(bars + B_XRW + 8, 1);
    for (int e = 0; e < 2 * EV_N; e++) mbar_init(bars + B_EVT + e * 8, 4);
    asm volatile("fence.mbarrier_init.release.cluster;" ::: "memory");
  }
  if (tid == 320) {
#pragma unroll
    for (int e = 0; e < 28; e++) mbar_init(bars + B_FA3 + e * 8, e < 18 ? 1 : 4);
    asm volatile("fence.mbarrier_init.release.cluster;" ::: "memory");
  }
  __syncthreads();

  if (wid >= 8) {
    reg_dealloc<40>();
    const uint32_t el = elect_one();
    const uint64_t pol = policy_evict_first();
    uint32_t* const fj = g_flags + FJ + j * 32;
    if (wid == 8) {
#pragma unroll 1
      for (int i = 0; i < 12; i++) if (el) prefetch_map(&P.act[0] + (i < 7 ? i : i - 12));
      const uint32_t epoch = ldcg32(fj + FJ_EP + rb);
      Cur c{0, 1};
      const uint32_t rk = bid & 1;
      uint32_t st, full;
      auto slot = [&](uint32_t bytes) {
        st = sb + c.s * ST_BYTES; full = bars + B_FULL + c.s * 8;
        mbar_wait(full, c.ph);
        expect_tx_p(el, full, bytes);
        mbar_wait(full - B_FULL + B_EMPTY, c.ph);
      };
#pragma unroll 1
      for (int L = 0; L < 2; L++) {
#pragma unroll 1
        for (int i = 0; i < 14; i++) {
          if (L == 0 && (i == 0 || i == 2 * SPL || i == 9)) {
            flag_wait(fj + (i == 9 ? FJ_WO : i == 2 * SPL ? FJ_WQ : FJ_WQ0), (epoch + 1) * 16);
            if (i == 9) flag_wait(g_flags + FJ + (j ^ 1) * 32 + FJ_WO, (epoch + 1) * 16);
            fence_async_g();
            TRC(el, 2, i == 9 ? 46 : i ? 47 : 45);
          }
          const uint32_t hb = i < 9 ? 13824 : i < 13 ? 18432 : 9216, o = ST_B + rk * (i < 9 ? 13824 : 18432);
          const uint8_t* src = i < 9 ? g_WQ + j * WQ_SL + i * 27648 + rk * 13824 : g_WO + ((j & 6) + rk) * WO_SL + (i - 9) * 18432;
          slot(2 * hb);
          bulk_mc_h(el, st + o, src, hb, full, true, pol);
          c.next();
        }
#pragma unroll 1
        for (int i = 0; i < 18; i++) {
          const int p = i >> 1, col = p == 4 ? (9 * j + ((j & 1) ? 0 : 8)) * 32 : (((9 * j + 1) >> 1) + (p < 4 ? p + 36 : p - 5)) * 64;
          if (i & 1) {
            slot(2 * ZB);
          } else {
            st = sb + c.s * ST_BYTES; full = bars + B_FULL + ((c.s + 1) & 3) * 8;
            mbar_wait(bars + B_EMPTY + c.s * 8, c.ph);
          }
          tma4d_mc(el, st + ST_B + rk * 18432, p == 4 ? &P.win : &P.win64, col, (i & 1) * 36 + rk * 18, full, pol);
          if (el && !(i & 1)) mbar_arrive(bars + B_FULL + c.s * 8);
          c.next();
        }
        TRC(el, 2, L * 16 + 6);
        flag_wait(fj + FJ_ZN + L, (epoch + 1) * 16);
        fence_async_g();
        TRC(el, 2, L * 16 + 7);
#pragma unroll 1
        for (int i = 0; i < 32; i++) {
          const uint8_t* src = z2_block(i, j) + rk * 18432;
          if (i >= 4) mbar_wait(bars + B_AD + c.s * 8, ((i >> 2) & 1) ^ 1);
          slot(ST_BYTES);
          bulk_mc_h(el, st + ST_B + rk * 18432, src, 18432, full, true, pol);
          tma3d_h(el, st, &P.wsp, i * 64, rb * 64, 0, full, true, pol);
          c.next();
        }
        mbar_wait(bars + B_Z1, L);
        fence_async_g();
        expect_tx_p(el, bars + B_ZB, 26624);
#pragma unroll 1
        for (int i = 0; i < 10; i++) {
          const int cb = i - 1 + j;
          if (i < 4) mbar_wait(bars + B_AD + c.s * 8, 1);
          slot(i ? ZB : 26624);
          if (i == 0) {
            bulk_load_h(el, st, z1_block(rb, 0, j), 26624, bars + B_ZB, true, pol);
            bulk_load_h(el, st + 26624, z1_block(rb, 1, j), 26624, full, true, pol);
          } else {
            tma2d_mc_h(el, st + ST_B + rk * 18432, &P.wout, (cb >= 9 ? cb - 9 : cb) * 64, 288 * j + rk * 144, full, true, pol);
          }
          c.next();
        }
      }
    } else if (wid < 11) {
      int w = wid - 9;
      uint32_t* const fr = g_flags + (rb * 2 + w) * 32;
      const uint32_t epoch = ldcg32(fr + FR_EP + j);
      const uint32_t ev = bars + B_EVT + w * EV_N * 8, t8 = (epoch + 1) * 8;
      Cur c{0, 1};
#pragma unroll 1
      for (int L = 0; L < 2; L++) {
        {
          const uint32_t tag = epoch * 2 + L + 1;
          uint4* const xs = g_XST + (rb * 2 + w) * 128;
          if (L) {
            mbar_wait(ev + EV_PT * 8, 0);
            TRC(el, 3, w * 32 + 16);
            flag_release_p(el, fr + FR_X2);
            TRC(el, 3, w * 32 + 17);
          }
#pragma unroll 1
          for (int i = 0; i < 9; i++) {
            const uint32_t full = bars + B_FULLA + w * 32 + c.s * 8, dst = sb + c.s * ST_BYTES + w * 8192;
            if (L == 0 && i == 4) {
              mbar_wait(bars + B_WT + w * 8, 0);
              TRC(el && w == 0, 2, 37);
              rows_stats(sb + SM_STG + w * 9216, xs + 16 * j, tag, lane);
              TRC(el && w == 0, 2, 38);
            }
            const uint32_t src = sb + (L ? 2 * ST_BYTES + SM_WOI : SM_STG + w * 9216);
            if (i == 4) {
#pragma unroll
              for (int u = 0; u < 6; u++) sts128(src + u * 512 + lane * 16, POISON, POISON, POISON, POISON);
              fence_async_s();
              __syncwarp();
            }
            mbar_wait(bars + B_EMPTY + c.s * 8, c.ph);
            expect_tx_p(el, full, 8192);
            if (i < L) { flag_wait(fr + FR_X2, t8); fence_async_g(); }
            tma3d_h(el, dst, &P.act[L], i * 64, rb * 64, w, full, false, pol);
            TRC(el && i < L, 3, w * 32 + 18);
            c.next();
            if (i >= 4 && i < (L ? 5 : 8)) {
              int b = (rb * 2 + w) * 8 + j;
              asm volatile("" : "+r"(b));
              bulk_store_p(el, i == 4 ? (uint8_t*)g_HALO + b * 3072 : g_O + (b * 3 + i - 5) * 3072, src, 3072);
              if (i < 6) bulk_store_p(el, (i == 4 ? g_ST1 : g_ZST) + b * 64, src, 1024);
              if (i == 6) bulk_store_p(el, g_RT + b * 8, src, 64);
            }
            if (L == 0 && i == 3) rows_fetch(el, sb + SM_STG + w * 9216, P.xs[0] + (128 * rb + 16 * j + w) * (DM * 2), bars + B_WT + w * 8);
          }
          if (el) asm volatile("cp.async.bulk.commit_group;\ncp.async.bulk.wait_group 0;" ::: "memory");
          __syncwarp();
          if (L == 0) fence_gpu();
          const uint32_t tab = sb + L * (2 * ST_BYTES) + SM_XST + w * 512 + lane * 8;
          TRC(el, 3, w * 32 + L * 16 + 13);
#pragma unroll 1
          for (int it = 0; it < (1 << 22); it++) {
            const uint4 a = ll_ld128(xs + 2 * lane), b = ll_ld128(xs + 64 + 2 * lane);
            if (__all_sync(~0u, a.z == tag && b.z == tag)) { sts64(tab, a.x, a.y); sts64(tab + 256, b.x, b.y); break; }
          }
          __syncwarp();
          mbar_arrive_if(el, bars + B_XS + w * 8);
          TRC(el, 3, w * 32 + L * 16 + 14);
          if (w == 1) {
            mbar_wait(bars + B_XS, L);
            expect_tx_p(el, bars + B_RES, 18432);
            tma3d_h(el, sb + SM_STG, &P.res[L], (j & 6) * 72, rb * 64, j & 1, bars + B_RES, !L, pol);
          }
          if (L) flag_wait(fj + FJ_P4, t8 * 4);
        }
        int hp = rb * 2 + (j & 1);
        asm volatile("" : "+r"(w), "+r"(hp));
        uint32_t* const fo = g_flags + hp * 32 + L;
        {
          const uint8_t* src = o_block(0, hp) + w * 8192;
#pragma unroll 1
          for (int i = 0; i < 5; i++) {
            const uint32_t full = bars + B_FULLA + w * 32 + c.s * 8, dst = sb + c.s * ST_BYTES + w * 8192;
            const bool none = 2 * i + w > 8;
            mbar_wait(bars + B_EMPTY + c.s * 8, c.ph);
            expect_tx_p(el, full, none ? 0 : 8192);
            if (i == 0) {
              mbar_wait(ev + EV_O * 8, L);
              TRC(el, 3, w * 32 + L * 16 + 3);
              flag_add_p(el, fr + FR_O + L);
              TRC(el, 3, w * 32 + L * 16 + 4);
              flag_wait(fo + FR_O, t8);
              fence_async_g();
            }
            if (!none) bulk_load_h(el, dst, src + i * 16384, 8192, full, true, pol);
            TRC(el && i == 0, 3, w * 32 + L * 16 + 5);
            c.next();
          }
        }
        {
          expect_tx_p(lane < 9, bars + B_FA3 + (9 * w + lane) * 8, 8192);
          mbar_wait(ev + EV_X1 * 8, L);
          TRC(el, 3, w * 32 + L * 16 + 6);
          if (L) flag_add_p(el, fo + FR_X1); else flag_release_p(el, fo + FR_X1);
          mbar_arrive_if(el, bars + B_GATE3);
          TRC(el, 3, w * 32 + L * 16 + 7);
          mbar_arrive_if(lane < 2, bars + B_FULLA + w * 32 + ((c.s + lane) & 3) * 8);
#pragma unroll 1
          for (int kb = 0; kb < 9; kb++) {
            const int n = 9 * w + kb;
            const uint32_t dst = sb + ((n >> 1) & 3) * ST_BYTES + (n & 1) * 8192;
            if (kb == 0) { flag_wait(fr + FR_X1 + L, t8); fence_async_g(); }
            if (n >= 8) mbar_wait(bars + B_EA3 + (n - 8) * 8, L);
            tma3d_h(el, dst, &P.act[L + 1], kb * 64, rb * 64, w, bars + B_FA3 + n * 8, false, pol);
            TRC(el && kb == 0, 3, w * 32 + L * 16 + 8);
          }
          c.ph ^= ((c.s + 18) >> 2) & 1; c.s = (c.s + 18) & 3;
        }
        asm volatile("" : "+r"(lane), "+r"(w));
        expect_tx_p(el, bars + B_WT + w * 8, 2048);
#pragma unroll 1
        for (int r = 0; r < 8; r++)
          bulk_load_p(el, sb + SM_WT + w * 2176 + r * 272, (const uint8_t*)P.w_sp + (size_t)(128 * rb + 16 * j + 2 * r + w) * (SEQ * 2) + 30 * 128, 256, bars + B_WT + w * 8);
        float cv = (lane & 3) ? 0.f : -blo(ldnc16(P.b_sp + 128 * rb + 16 * j + 2 * (lane >> 2) + w));
        mbar_wait(bars + B_RT, L);
        mbar_wait(bars + B_WT + w * 8, L ^ 1);
        mbar_wait(ev + EV_Z1 * 8, L);
        const uint32_t ro = (w * 64 + 8 * j + (lane >> 2)) * 128, x0 = ((lane & 3) * 2) ^ (lane >> 2);
#pragma unroll 1
        for (int i = 0; i < 32; i++) {
          const bool tail = (i >> 1) == 4;
          const int kb = tail ? i + 22 : i < 8 ? i : i - 2;
          if (i == 8) mbar_wait(bars + B_RT1, L);
          if (!tail) mbar_wait(bars + B_FULL + c.s * 8, c.ph ^ 1);
#pragma unroll
          for (int e = 0; e < 2; e++) {
            const uint4 a = lds128(!tail ? sb + c.s * ST_BYTES + ro + ((x0 ^ e) << 4) : sb + SM_WT + w * 2176 + (lane >> 2) * 272 + (i - 8) * 128 + (lane & 3) * 32 + e * 16);
            const uint4 m = lds128(sb + SM_RT + 4096 + kb * 128 + (lane & 3) * 32 + e * 16);
            cv = fmaf(blo(a.x), blo(m.x), fmaf(bhi(a.x), bhi(m.x), fmaf(blo(a.y), blo(m.y), fmaf(bhi(a.y), bhi(m.y), cv))));
            cv = fmaf(blo(a.z), blo(m.z), fmaf(bhi(a.z), bhi(m.z), fmaf(blo(a.w), blo(m.w), fmaf(bhi(a.w), bhi(m.w), cv))));
          }
          if (!tail) {
            mbar_arrive_if(el, bars + B_AD + c.s * 8 + (__float_as_uint(cv) & P.zero));
            c.next();
          }
        }
        TRC(el, 3, w * 32 + L * 16 + 11);
        uint32_t tag = t8;
        asm volatile("" : "+r"(tag));
        tag = (tag >> 2) - 1 + L;
        cv = qsum(cv);
        uint2* const cs = (uint2*)(g_XST + (rb * 2 + w) * 128 + 1);
        if ((lane & 3) == 0) ll_st64(cs + 32 * j + (lane >> 2) * 4, __float_as_uint(cv), tag);
#pragma unroll 1
        for (int it = 0; it < (1 << 22); it++) {
          const uint2 a = ll_ld64(cs + 4 * lane), b = ll_ld64(cs + 128 + 4 * lane);
          if (__all_sync(~0u, a.y == tag && b.y == tag)) { sts32(sb + SM_CV + w * 256 + lane * 4, a.x); sts32(sb + SM_CV + w * 256 + 128 + lane * 4, b.x); break; }
        }
        __syncwarp();
        if (el) mbar_arrive(bars + B_CV + w * 8);
        TRC(el, 3, w * 32 + L * 16 + 12);
#pragma unroll 1
        for (int kb = 30; kb < 32; kb++) {
          mbar_wait(bars + B_FULL + c.s * 8, c.ph ^ 1);
          if (el) mbar_arrive(bars + B_AD + c.s * 8);
          c.next();
        }
        c.ph ^= ((c.s + 10) >> 2) & 1; c.s = (c.s + 10) & 3;
        if (L == 0) {
          mbar_wait(ev + EV_P4 * 8, 0);
          flag_add_p(el, fj + FJ_P4);
        }
      }
    } else {
      const uint32_t epoch = ldcg32(fj + FJ_EP + rb);
      if (SPL) {
        mbar_wait(bars + B_RES + 8, 0);
        TRC(el, 2, 41);
        flag_release_p(el, fj + FJ_WQ0);
        TRC(el, 2, 42);
      }
      mbar_wait(bars + B_IMG, 0);
      TRC(el, 2, 39);
      flag_release_p(el, fj + FJ_WQ);
      TRC(el, 2, 40);
#pragma unroll 1
      for (int L = 0; L < 2; L++) {
        auto wo_fetch = [&]() {
          expect_tx_p(el, bars + B_WOI, 5760);
          asm volatile("{\n.reg .pred P;\nsetp.ne.u32 P, %5, 0;\n@P cp.async.bulk.tensor.4d.shared::cluster.global.mbarrier::complete_tx::bytes [%0], [%1, {0, 0, %3, %4}], [%2];\n}" ::"r"(sb + SM_WOI), "l"(&P.wo8), "r"(bars + B_WOI), "r"(9 * j), "r"((9 * rb) >> 1), "r"(el) : "memory");
        };
        float* const csf = g_CSP + (NCTA + bid) * 216;
        if (L == 0) {
          flag_wait(fj + FJ_WQ, (epoch + 1) * 16);
          fence_async_g();
          expect_tx_p(el, bars + B_XRW, 13824);
          bulk_load_p(el, sb + ST_BYTES + SM_WOI, g_CSP + j * 16 * 216, 6912, bars + B_XRW);
          bulk_load_p(el, sb + 2 * ST_BYTES + SM_WOI, g_CSP + (j * 16 + 8) * 216, 6912, bars + B_XRW);
          wo_fetch();
          mbar_wait(bars + B_XRW, 0);
#pragma unroll 1
          for (int f = lane; f < 54; f += 32) {
            float s[4] = {0.f, 0.f, 0.f, 0.f};
#pragma unroll 4
            for (int r = 0; r < 16; r++) {
              const uint4 v = lds128(sb + ST_BYTES + SM_WOI + (r >> 3) * ST_BYTES + (r & 7) * 864 + f * 16);
              s[0] += __uint_as_float(v.x); s[1] += __uint_as_float(v.y); s[2] += __uint_as_float(v.z); s[3] += __uint_as_float(v.w);
            }
            sts128(sb + SM_CSQ + f * 16, __float_as_uint(s[0]), __float_as_uint(s[1]), __float_as_uint(s[2]), __float_as_uint(s[3]));
            stg128(csf + f * 4, __float_as_uint(s[0]), __float_as_uint(s[1]), __float_as_uint(s[2]), __float_as_uint(s[3]));
          }
          __syncwarp();
          mbar_arrive_if(el, bars + B_CSQ);
        } else {
#pragma unroll 1
          for (int u = 0; u < 4; u++) {
            const int w = u & 1;
            if (u < 2) {
              flag_wait(g_flags + (rb * 2 + w) * 32 + FR_X2, (epoch + 1) * 8);
              fence_async_g();
              TRC(el, 2, 48 + u);
              rows_fetch(el, sb + SM_STG + w * 9216, P.xs[1] + (128 * rb + 16 * j + w) * (DM * 2), bars + B_XRW + w * 8);
            } else {
              if (u == 2) {
                expect_tx_p(el, bars + B_CSQ, 864);
                bulk_load_p(el, sb + 2 * ST_BYTES + SM_CSQ, csf, 864, bars + B_CSQ);
              }
              mbar_wait(bars + B_XRW + w * 8, w ^ 1);
              TRC(el, 2, 48 + u);
              rows_stats(sb + SM_STG + w * 9216, g_XST + (rb * 2 + w) * 128 + 16 * j, epoch * 2 + 2, lane);
              TRC(el, 2, 50 + u);
            }
          }
        }
        if (L == 0) {
          TRC(el, 2, 43);
          mbar_wait(bars + B_WOI, 0);
          bulk_store_p(el, g_WO + j * WO_SL + ((9 * rb) >> 1) * 1152, sb + SM_WOI, 5760);
          publish_p(el, fj + FJ_WO);
          TRC(el, 2, 44);
          const uint8_t* sp = lane < 16 ? (const uint8_t*)P.w_in + (30 * lane + 50) * (FH * 4) + FH * 2 + lane * 256 : (const uint8_t*)P.w_sp + (60 * lane) * (SEQ * 2) + lane * 64;
          float sq = 0.f;
#pragma unroll 1
          for (int u = 0; u < 4; u++) {
            const uint4 y = ldnc128(sp + u * 16);
            const uint32_t x[4] = {y.x, y.y, y.z, y.w};
#pragma unroll
            for (int e = 0; e < 4; e++) sq = fmaf(blo(x[e]), blo(x[e]), fmaf(bhi(x[e]), bhi(x[e]), sq));
          }
#pragma unroll 1
          for (int o = 8; o; o >>= 1) sq += __shfl_xor_sync(~0u, sq, o);
          sq *= lane < 16 ? 2.f * GA * GA * DM / 512.f : C0S * C0S * SEQ / 512.f;
          asm("sqrt.approx.f32 %0, %0;" : "+f"(sq));
          const float o0 = __shfl_sync(~0u, sq, 0), o1 = __shfl_sync(~0u, sq, 16);
          const float p2 = __uint_as_float(min(__float_as_uint(o0) & 0x7f800000u, 0x7e000000u)) * OFK, off = -p2 - fminf(OFA, 0.5f * p2);
          if (el) sts64(sb + SM_OFF, pack2(off, off), min(__float_as_uint(o1) & 0x7f800000u, 0x7e000000u) | 0x00400000u);
        }
        if (el) mbar_arrive(bars + B_GATE3);
        const uint32_t tag = epoch * 2 + L + 1;
        asm volatile("" : "+r"(lane));
        mbar_wait(bars + B_EVT + EV_ZN * 8, L);
        mbar_wait(bars + B_EVT + (EV_N + EV_ZN) * 8, L);
        flag_release_p(el, fj + FJ_ZN + L);
        TRC(el, 2, L * 16 + 8);
        {
          uint4 v[4];
#pragma unroll 1
          for (int it = 0; it < (1 << 22); it++) {
            bool ok = true;
#pragma unroll
            for (int u = 0; u < 4; u++) { v[u] = ll_ld128(g_ZST + (rb * 2 + ((lane >> 1) & 1)) * 512 + ((lane & 1) * 4 + u) * 64 + 8 * j + (lane >> 2)); ok = ok && v[u].z == tag; }
            if (__all_sync(~0u, ok)) break;
          }
          float mean = __uint_as_float(v[0].x) + __uint_as_float(v[1].x) + __uint_as_float(v[2].x) + __uint_as_float(v[3].x), M2 = 0.f;
          mean = (mean + __shfl_xor_sync(~0u, mean, 1)) * 0.125f;
#pragma unroll
          for (int u = 0; u < 4; u++) { const float d = __uint_as_float(v[u].x) - mean; M2 += fmaf(288.f * d, d, __uint_as_float(v[u].y)); }
          M2 += __shfl_xor_sync(~0u, M2, 1);
          const float rs = blo(pack2(rsqrtf(fmaf(M2, 1.f / FH, 4.f * GA * GA * LN_EPS)), 0.f));
          if (!(lane & 1)) ll_st64(g_RT + 128 * rb + 16 * j + (lane >> 1), pack2(rs, rs * mean), tag);
        }
        TRC(el, 2, L * 16 + 10);
#pragma unroll 1
        for (int b = 0; b < 8; b++) {
          uint4 v[4];
#pragma unroll 1
          for (int it = 0; it < (1 << 22); it++) {
            bool ok = true;
#pragma unroll
            for (int u = 0; u < 4; u++) { v[u] = ll_ld128((const uint4*)g_RT + b * 128 + u * 32 + lane); ok = ok && v[u].y == tag && v[u].w == tag; }
            if (__all_sync(~0u, ok)) break;
          }
#pragma unroll
          for (int u = 0; u < 4; u++) {
            const uint32_t rt = sb + SM_RT + b * 512 + u * 128, ro = (lane >> 3) * 32 + (lane & 3) * 8 + ((lane >> 2) & 1) * 2;
            sts32(rt + 4096 + lane * 4, __byte_perm(v[u].x, v[u].z, 0x7632));
            asm volatile("st.shared.u16 [%0], %1;\nst.shared.u16 [%0 + 4], %2;" ::"r"(rt + ro), "h"((uint16_t)v[u].x), "h"((uint16_t)v[u].z) : "memory");
          }
          __syncwarp();
          if (el && (b == 1 || b == 7)) mbar_arrive(bars + (b == 1 ? B_RT : B_RT1));
          TRC(el && b < 2, 2, L * 16 + 11 + b);
        }
        TRC(el, 2, L * 16 + 9);
        mbar_wait(bars + B_EVT + EV_Z1 * 8, L);
        mbar_wait(bars + B_EVT + (EV_N + EV_Z1) * 8, L);
        fence_gpu();
        if (el) mbar_arrive(bars + B_Z1);
        if (L == 0) {
          __nanosleep(NAP0);
          poison(el, sb + SM_STG + 17152, &P.psn, rb, j, lane);
          if (el) asm volatile("cp.async.bulk.commit_group;\ncp.async.bulk.wait_group 0;" ::: "memory");
          __syncwarp();
          fence_gpu();
        }
      }
    }
  } else {
    CKK(3);
    uint8_t* const wdst = P.wq + j * WQ_SL + rb * 3456 + tid * 16;
#pragma unroll
    for (int u = 0; u < SPL; u++) stg128_if(tid < 216, wdst + u * (16 * 3456), wv[u].x, wv[u].y, wv[u].z, wv[u].w);
    __syncwarp();
    if (lane == 0) mbar_arrive(bars + B_RES + 8);
    CKK(4);
    auto repack2 = [&]() {
#pragma unroll
      for (int u = SPL; u < 5; u++) stg128_if((u < 4 || rb < 8) && tid < 216, wdst + u * (16 * 3456), wv[u].x, wv[u].y, wv[u].z, wv[u].w);
      float s[8];
#pragma unroll
      for (int e = 0; e < 8; e++) s[e] = 0.f;
#pragma unroll
      for (int u = 0; u < 5; u++) {
        uint32_t x[4] = {wv[u].x, wv[u].y, wv[u].z, wv[u].w};
        asm volatile("" : "+r"(x[0]), "+r"(x[1]), "+r"(x[2]), "+r"(x[3]));
#pragma unroll
        for (int e = 0; e < 4; e++) { s[2 * e] += blo(x[e]); s[2 * e + 1] += bhi(x[e]); }
      }
#pragma unroll
      for (int m = 4; m; m >>= 1) {
#pragma unroll
        for (int e = 0; e < m; e++) s[e] = ((tid & m) ? s[e + m] : s[e]) + __shfl_xor_sync(~0u, (tid & m) ? s[e] : s[e + m], m);
      }
      stg32_if(tid < 216, P.csp + bid * 216 + tid, __float_as_uint(s[0]));
      __syncwarp();
      if (lane == 0) mbar_arrive(bars + B_IMG);
    };
    reg_alloc<232>();
    CKK(5);
#pragma unroll
    for (int v = SPL; v < 5; v++) wv[v] = ldnc128_if(tid < 216 && (v < 4 || rb < 8), wsrc + v * (128 * 3 * DM * 2));
    repack2();
    CKK(6);
    const int w = wid >> 2, q = wid & 3;
    int g = lane >> 2, t = lane & 3;
    const uint32_t ev = bars + B_EVT + w * EV_N * 8;
    const bool tr = (tid & 127) == 0;
    (void)tr;
    Cur c{0, 0};
    const uint32_t ebar = mapa(bars + B_EMPTY, (bid & 1) ^ (lane & 1));
    auto release = [&](uint32_t s, uint32_t dep = 0) { mbar_arrive_cluster_if(lane < 2, ebar + s * 8 + dep); };
    auto release_if = [&](bool on, uint32_t s) { mbar_arrive_cluster_if(lane < 2 && on, ebar + s * 8); };
    uint32_t ia = 0;
    auto wait_ab = [&]() { mbar_wait_c(bars + B_FULL + c.s * 8, c.ph); mbar_wait_c(bars + B_FULLA + w * 32 + c.s * 8, (ia >> 2) & 1); ia++; };

    auto yield_done = [&]() { if (w == 0 && lane == 0) mbar_arrive(bars + B_LAG); };
    auto signal = [&](int e) { __syncwarp(); mbar_arrive_if(lane == 0, ev + e * 8); };

    const uint32_t epoch = ldcg32(g_flags + (rb * 2 + w) * 32 + FR_EP + j);
    TRC(tr, w, 1);
    CKK(7);
    if (PAD && P.zero) {
#pragma unroll
      for (int i = 0; i < PAD; i++) asm volatile("st.shared.u32 [%0], %1;" ::"r"(sb + i * 20), "r"(tid) : "memory");
    }
    CKK_OUT;

#pragma unroll 1
    for (int L = 0; L < 2; L++) {
      const int tb = 2 + L * 24;
      asm volatile("" : "+r"(lane), "+r"(g), "+r"(t));
      (void)tb;
      ia = 0;
      const uint32_t tag = epoch * 2 + L + 1;
      uint32_t aoff = (w * 64 + q * 16 + (lane & 15)) * 128 + (((lane >> 4) ^ (lane & 7)) << 4);
      {
        uint32_t Pk[27][2];
        float sc0, sc1;
        const uint32_t att = sb + w * 8192 + q * 2048 + lane * 4;
        uint4* hp = g_HALO + ((((rb - (q == 0)) * 2 + w) * 8 + j) * 6) * 32 + lane;
        uint8_t* od = o_block(rb, w) + (9 * j) * 1024 + (2 * q) * 128 + lane * 4;
        ACLK_INIT;
        {
          float acc[108];
#pragma unroll
          for (int i = 0; i < 108; i++) acc[i] = 0.f;
          uint32_t prev = 0;
#pragma unroll 1
          for (int kb = 0; kb < 9; kb++) {
            wait_ab();
            if (w == 1 && kb == 9 - LAG1) mbar_wait_c(bars + B_LAG, L);
            TRC(tr && kb == 0, w, tb + 0);
            MCLK(kb == 0, 0);
            PCLK(kb * 4);
            const uint32_t st = sb + c.s * ST_BYTES, da = dlo(st + w * 8192, 16), db = dlo(st + ST_B, 3456);
            wgmma_fence();
#pragma unroll
            for (int kk = 0; kk < 4; kk++) {
              wgmma_ss_n216(acc, dsc<1024, 1>(da, kk * 32), dsc<128, 0>(db, kk * 6912), 1);
              if (kk == 0) { wgmma_commit(); wgmma_wait<1>(); release_if(kb > 0, prev); }
            }
            wgmma_commit();
            if (kb == 8) yield_done();
            PCLK(kb * 4 + 1);
            PCLK(kb * 4 + 2);
            PCLK(kb * 4 + 3);
            prev = c.s; c.next();
          }
          const uint32_t cs = sb + prev * ST_BYTES + SM_CSQ + t * 8;
          mbar_wait_c(bars + B_CSQ, L);
          mbar_wait_c(bars + B_XS + w * 8, L);
          const float2 n0 = lds64f(sb + prev * ST_BYTES + SM_XST + w * 512 + (16 * q + g) * 8), n1 = lds64f(sb + prev * ST_BYTES + SM_XST + w * 512 + (16 * q + g + 8) * 8);
          const float m0 = n0.x, r0 = n0.y, m1 = n1.x, r1 = n1.y;
          float2 cv[27];
#pragma unroll
          for (int G = 0; G < 27; G++) cv[G] = lds64f(cs + G * 32);
          PCLK(36);
          wgmma_wait<0>();
          PCLK(37);
          uint32_t dep = P.zero & __float_as_uint(m0) & __float_as_uint(m1);
#pragma unroll
          for (int G = 0; G < 27; G++) dep &= __float_as_uint(cv[G].x);
          release(prev, dep);
          TRC(tr, w, tb + 1);
          MCLK(1, 1);
          ACLK(0);
#pragma unroll
          for (int G = 9; G < 27; G++) Pk[G][1] = pack2(fmaf(m1, cv[G].x, acc[4 * G + 2]) * r1, fmaf(m1, cv[G].y, acc[4 * G + 3]) * r1);
          if (q < 3) {
#pragma unroll
            for (int i = 0; i < 18; i++) sts32(att + (i >> 4) * ST_BYTES + (i & 15) * 128, Pk[9 + i][1]);
          } else if (rb < 15) {
#pragma unroll
            for (int i = 0; i < 6; i++) ll_st128(hp + i * 32, __uint_as_float(Pk[9 + 3 * i][1]), __uint_as_float(Pk[10 + 3 * i][1]), tag, __uint_as_float(Pk[11 + 3 * i][1]));
          }
#pragma unroll
          for (int G = 0; G < 27; G++) {
            if (G < 9) {
              Pk[G][0] = pack2(fmaf(m0, cv[G].x, acc[4 * G]), fmaf(m0, cv[G].y, acc[4 * G + 1]));
              Pk[G][1] = pack2(fmaf(m1, cv[G].x, acc[4 * G + 2]), fmaf(m1, cv[G].y, acc[4 * G + 3]));
            } else {
              Pk[G][0] = pack2(fmaf(m0, cv[G].x, acc[4 * G]) * r0, fmaf(m0, cv[G].y, acc[4 * G + 1]) * r0);
            }
          }
          sc0 = r0 * (0.23570226039551584f * 1.4426950408889634f); sc1 = r1 * (0.23570226039551584f * 1.4426950408889634f);
        }
        ACLK(1);
        constexpr int GA_[4] = {0, 2, 4, 7}, GB_[4] = {1, 3, 5, 8}, GC_[4] = {2, 4, 6, 6};
        float S1[4][4], S2[4][4];
        uint32_t qa[4][2], qc[4][2];
#pragma unroll
        for (int h = 0; h < 4; h++) {
#pragma unroll
          for (int r = 0; r < 2; r++) {
            qa[h][r] = (h == 0 || h == 3 || t >= h) ? Pk[GA_[h]][r] : 0u;
            qc[h][r] = (h == 3 ? t == 3 : t <= h) ? Pk[GC_[h]][r] : 0u;
          }
          mma16(S1[h], qa[h][0], qa[h][1], Pk[GB_[h]][0], Pk[GB_[h]][1], Pk[9 + GA_[h]][0], Pk[9 + GB_[h]][0]);
          mma16(S2[h], qa[h][0], qa[h][1], Pk[GB_[h]][0], Pk[GB_[h]][1], Pk[9 + GA_[h]][1], Pk[9 + GB_[h]][1]);
        }
#pragma unroll
        for (int h = 0; h < 4; h++) {
          mma8(S1[h], qc[h][0], qc[h][1], Pk[9 + GC_[h]][0]);
          mma8(S2[h], qc[h][0], qc[h][1], Pk[9 + GC_[h]][1]);
        }
        uint32_t V1[9], V2[9];
#pragma unroll
        for (int i = 0; i < 9; i++) { V1[i] = movm(Pk[18 + i][0]); V2[i] = movm(Pk[18 + i][1]); }
        const bool remote = q == 0 && rb > 0;
        uint4 hv[6];
#pragma unroll
        for (int i = 0; i < 6; i++) hv[i] = make_uint4(0u, 0u, tag, 0u);
        if (remote) {
#pragma unroll
          for (int i = 0; i < 6; i++) hv[i] = ll_ld128(hp + i * 32);
        }
        const bool up0 = 2 * t > g, up1 = 2 * t + 1 > g;
        const uint32_t mup = (up0 ? 0xffffu : 0u) | (up1 ? 0xffff0000u : 0u);
        auto finish = [&](const float (&x0)[4], const float (&x1)[4], uint32_t ma, const uint32_t (&Vb)[9], int hi) {
          uint32_t pa[4], pb[4];
          float rs[4];
#pragma unroll
          for (int h = 0; h < 4; h++) {
            const float m = qmax(fmaxf(x0[h], x1[h]));
            const uint32_t p = pack2(ex2(x0[h] - m), ex2(x1[h] - m));
            pa[h] = p & ma; pb[h] = p & ~ma;
          }
#pragma unroll
          for (int h = 0; h < 4; h += 2) {
            float R[4];
            mma16(R, pa[h], pa[h + 1], pb[h], pb[h + 1], 0x3f803f80u, 0x3f803f80u);
            rs[h] = rcp_fast(R[0]); rs[h + 1] = rcp_fast(R[2]);
          }
#pragma unroll
          for (int i = 0; i < 9; i++) {
            const int h = 4 * i / 9, e = (h & 1) * 2;
            const bool split = i == 2 || i == 4 || i == 6, nx = split && 2 * t >= i;
            float O[4], N[4];
            mma16(O, pa[h & 2], pa[h | 1], pb[h & 2], pb[h | 1], V1[i], Vb[i]);
            if (i == 4) mma16(N, pa[2], pa[3], pb[2], pb[3], V1[i], Vb[i]); else { N[0] = O[2]; N[1] = O[3]; }
            const float r = nx ? rs[h + (split ? 1 : 0)] : rs[h];
            stg32(od + i * 1024 + hi * 128, pack2((nx ? N[0] : O[e]) * r, (nx ? N[1] : O[e + 1]) * r));
          }
        };
        {
          float x0[4], x1[4];
#pragma unroll
          for (int h = 0; h < 4; h++) { x0[h] = (up0 ? S1[h][2] : S2[h][2]) * sc1; x1[h] = (up1 ? S1[h][3] : S2[h][3]) * sc1; }
          finish(x0, x1, mup, V2, 1);
        }
        ACLK(2);
        bar_sync(1 + w, 128);
        uint32_t H[18];
        if (q > 0) {
#pragma unroll
          for (int i = 0; i < 18; i++) H[i] = lds32(att - 2048 + (i >> 4) * ST_BYTES + (i & 15) * 128);
        } else {
#pragma unroll 1
          for (int it = 0; it < (1 << 20); it++) {
            bool ok = true;
#pragma unroll
            for (int i = 0; i < 6; i++) ok = ok && hv[i].z == tag;
            if (__all_sync(~0u, ok)) break;
#pragma unroll
            for (int i = 0; i < 6; i++) hv[i] = ll_ld128(hp + i * 32);
          }
#pragma unroll
          for (int i = 0; i < 6; i++) { H[3 * i] = hv[i].x; H[3 * i + 1] = hv[i].y; H[3 * i + 2] = hv[i].w; }
        }
        float S0[4][4];
#pragma unroll
        for (int h = 0; h < 4; h++) {
          mma16(S0[h], qa[h][0], qa[h][1], Pk[GB_[h]][0], Pk[GB_[h]][1], H[GA_[h]], H[GB_[h]]);
        }
#pragma unroll
        for (int h = 0; h < 4; h++) mma8(S0[h], qc[h][0], qc[h][1], H[GC_[h]]);
        uint32_t V0[9];
#pragma unroll
        for (int i = 0; i < 9; i++) V0[i] = movm(H[9 + i]);
        ACLK(3);
        {
          const bool nohalo = (rb | q) == 0;
          const float b0 = up0 && nohalo ? -INFINITY : 0.f, b1 = up1 && nohalo ? -INFINITY : 0.f;
          float x0[4], x1[4];
#pragma unroll
          for (int h = 0; h < 4; h++) { x0[h] = fmaf(up0 ? S0[h][0] : S1[h][0], sc0, b0); x1[h] = fmaf(up1 ? S0[h][1] : S1[h][1], sc0, b1); }
          finish(x0, x1, ~mup, V0, 0);
        }
        ACLK(4);
        signal(EV_O);
        ACLK_OUT;
        TRC(tr, w, tb + 2);
        MCLK(1, 2);
      }
      {
        float acc[36];
        const int hw = rb * 2 + (j & 1), js = (j & 6) + w;
        const uint32_t xt = sb + SM_STG + (16 * q + g) * 288 + w * 144 + t * 4;
        uint32_t xm = sb + SM_STG + (16 * q + (lane & 15)) * 288 + (((9 * w + (lane >> 4)) ^ ((lane >> 2) & 1)) << 4), xl = sb + SM_STG + (2 * q + w) * 2304 + lane * 16;
        uint8_t* xd[5];
#pragma unroll
        for (int u = 0; u < 5; u++) {
          const int row = ((u * 32 + lane) * 57) >> 10;
          xd[u] = P.xs[L + 1] + (128 * rb + 32 * q + 16 * w + (j & 1)) * (DM * 2) + (j & 6) * 144 + row * (DM * 4 - 288) + u * 512 + ((lane ^ (row >> 2)) << 4);
          asm volatile("" : "+l"(xd[u]));
        }
        asm volatile("" : "+r"(xm), "+r"(xl));
        mbar_wait_c(bars + B_RES, L);
        TRC(tr, w, tb + 21);
#pragma unroll
        for (int i = 0; i < 18; i++) { const uint32_t x = lds32(xt + (i >> 1) * 16 + (i & 1) * 2304); acc[2 * i] = blo(x); acc[2 * i + 1] = bhi(x); asm volatile("" : "+f"(acc[2 * i]), "+f"(acc[2 * i + 1])); }
        uint32_t prev = 0;
#pragma unroll 1
        for (int u = 0; u < 5; u++) {
          const uint32_t st = sb + c.s * ST_BYTES, da = dlo(st, 1024), db = dlo(st + ST_B + w * 18432, 1152);
          mbar_wait_c(bars + B_FULL + c.s * 8, c.ph); mbar_wait_c(bars + B_FULLA + c.s * 8, (ia >> 2) & 1);
          TRC(tr && u == 0, w, tb + 3);
          MCLK(u == 0, 3);
          wgmma_fence();
#pragma unroll
          for (int kk = 0; kk < 4; kk++) wgmma_ss_n72(acc, dsc<128, 0>(da, kk * 2048), dsc<128, 0>(db, kk * 2304), 1);
          wgmma_commit();
          wgmma_wait<1>();
          release_if(u > 0, prev);
          mbar_wait_c(bars + B_FULLA + 32 + c.s * 8, (ia >> 2) & 1);
          ia++;
          if (u == 4) break;
          wgmma_fence();
#pragma unroll
          for (int kk = 4; kk < 8; kk++) wgmma_ss_n72(acc, dsc<128, 0>(da, kk * 2048), dsc<128, 0>(db, kk * 2304), 1);
          wgmma_commit();
          prev = c.s; c.next();
        }
        RCLK_INIT;
        wgmma_wait<0>();
        RCLK(0);
        release(c.s);
        c.next();
        if (__builtin_expect(any_nan(acc[0], acc[2]), 0)) {
          SLOW(L);
          const uint8_t* xr = P.xs[L] + (128 * rb + 32 * q + 2 * g + (j & 1)) * (DM * 2) + js * 144 + t * 4;
#pragma unroll
          for (int i = 0; i < 18; i++) { const uint32_t x = ldgpu32(xr + (i >> 1) * 16 + (i & 1) * (DM * 32)); acc[2 * i] = blo(x); acc[2 * i + 1] = bhi(x); }
          redo<KS2, 9, 1024, 128, 1152, 128>(acc, o_block(rb, j & 1) + q * 256 + lane * 4, g_WO + js * WO_SL + lane * 4, [](uint32_t*, int) {});
        }
        TRC(tr && P5TRACE != 5, w, tb + 4);
        MCLK(1, 4);
#pragma unroll
        for (int u = 0; u < 4; u++)
          stsm4(xm + u * 32, pack2(acc[8 * u], acc[8 * u + 1]), pack2(acc[8 * u + 2], acc[8 * u + 3]), pack2(acc[8 * u + 4], acc[8 * u + 5]), pack2(acc[8 * u + 6], acc[8 * u + 7]));
        asm volatile("stmatrix.sync.aligned.m8n8.x2.shared.b16 [%0], {%1,%2};" ::"r"(xm + 128), "r"(pack2(acc[32], acc[33])), "r"(pack2(acc[34], acc[35])) : "memory");
        auto stats = [&]() {
          float s0 = 0.f, s1 = 0.f, q0 = 0.f, q1 = 0.f;
#pragma unroll
          for (int i = 0; i < 36; i++) {
            if (i & 2) { s1 += acc[i]; q1 = fmaf(acc[i], acc[i], q1); } else { s0 += acc[i]; q0 = fmaf(acc[i], acc[i], q0); }
          }
          s0 = qsum(s0); s1 = qsum(s1); q0 = qsum(q0); q1 = qsum(q1);
          const float ss = t ? s1 : s0, m = ss * (1.f / 72.f);
          ll_st128_if(t < 2, g_ST1 + (hw * 8 + js) * 64 + 16 * q + 8 * t + g, m, fmaxf((t ? q1 : q0) - ss * m, 0.f), tag);
        };
        stats();
        RCLK(1);
        bar_sync(8 + q, 64);
        RCLK(2);
#pragma unroll
        for (int u = 0; u < 5; u++) {
          const uint4 v = lds128(xl + u * 512);
          stg128_if(u < 4 || lane < 16, xd[u], v.x, v.y, v.z, v.w);
        }
        RCLK(3);
        signal(EV_X1);
        RCLK(4);
        RCLK(5);
        TRC(tr, w, tb + 5);
        RCLK(6);
        RCLK_OUT;
      }
      uint4 zk[4];
      {
        uint32_t xA[36][4];
        float acc[32];
        uint32_t s0, one, off2;
        uint8_t *z1d, *zd;
        uint64_t db;
        auto bwait = [&](uint32_t dhi, bool skip) {
          s0 = c.s;
          c.next();
          if (!skip) mbar_wait_c(bars + B_FULL + c.s * 8, c.ph);
          db = dsc2(dlo(sb + s0 * ST_BYTES + ST_B, 512) - 3, 0, dhi); one = (c.s ^ P.zero) & 1;
        };
        auto mma = [&](int kk, int pp, bool hand) {
          wgmma_rs_n64(acc, xA[kk], dat(db, (kk / 18) * ST_BYTES + (kk % 18) * 2048 + 48, one), kk != 0);
          if (kk == pp && hand) bar_arrive(7 - w, 256);
          if (kk == 17 || kk == 35) wgmma_commit();
          if (kk == RL3) { wgmma_commit(); wgmma_wait<1>(); release(s0); }
        };
        {
          bwait(0x40000040u, false);
          mbar_wait_c(bars + B_GATE3, L);
          float mean0, mean1, rs0, rs1;
          stat_get(g_ST1 + ((rb * 2 + w) * 8 + 2 * t) * 64 + 16 * q + g, tag, 72.f, LN_EPS, mean0, rs0, mean1, rs1);
          const uint32_t ns0 = pack2(GA * rs0, GA * rs0), ns1 = pack2(GA * rs1, GA * rs1);
          const uint32_t nb0 = pack2(-mean0 * blo(ns0), -mean0 * blo(ns0)), nb1 = pack2(-mean1 * blo(ns1), -mean1 * blo(ns1));
          const uint32_t al = sb + (aoff & 8191);
#pragma unroll
          for (int kb = 0; kb <= 9; kb++) {
            if (kb < 9) {
              mbar_wait_c(bars + B_FA3 + (9 * w + kb) * 8, L);
              TRC(tr && kb == 0, w, tb + 6);
              MCLK(kb == 0, 5);
              if (kb == 0) SCLK(0);
              QCLK(kb);
              const uint32_t at = al + (w ? (((kb + 1) >> 1) & 3) * ST_BYTES + ((kb + 1) & 1) * 8192 : ((kb >> 1) & 3) * ST_BYTES + (kb & 1) * 8192);
#pragma unroll
              for (int kk = 4 * kb; kk < 4 * kb + 4; kk++) ldsm4(xA[kk], at ^ ((kk & 3) << 5));
            }
            if (kb == 0) continue;
            const uint32_t dep = xA[4 * kb - 4][0] & xA[4 * kb - 3][0] & xA[4 * kb - 2][0] & xA[4 * kb - 1][0] & P.zero;
            mbar_arrive_if(lane == 0 && (kb == 1 || w == 0), bars + B_EA3 + (9 * w + kb - 1) * 8 + dep);
#pragma unroll
            for (int kk = 4 * kb - 4; kk < 4 * kb; kk++) {
#pragma unroll
              for (int e = 0; e < 4; e++) xA[kk][e] = hfma2(xA[kk][e], (e & 1) ? ns1 : ns0, (e & 1) ? nb1 : nb0);
            }
            wgmma_fence();
#pragma unroll
            for (int kk = 4 * kb - 4; kk < 4 * kb; kk++) mma(kk, PP30, w);
          }
          off2 = lds32(sb + SM_OFF);
          z1d = z1_block(rb, w, j) + (tid & 127) * 16;
          zd = z2_block(2 * rb + (q >> 1), j) + (4 * (q & 1) + w) * 4608 + ((g & 3) * 2 + (g >> 2)) * 16 + t * 4;
          asm volatile("" : "+l"(z1d), "+l"(zd));
          wgmma_wait<0>();
          if (__builtin_expect(any_nan(acc[0], acc[2]), 0)) {
            SLOW(2 + L);
            uint4* const rd = g_RD + bid * (36 * 256) + tid;
            const uint8_t* xr = P.xs[L + 1] + (128 * rb + 32 * q + 2 * g + w) * (DM * 2) + t * 4;
#pragma unroll
            for (int i = 0; i < 32; i++) acc[i] = 0.f;
            redo<KS3, 8, 16, DM * 32, FH * 32, 16>(acc, xr, (const uint8_t*)P.w_in + g * (FH * 4) + (((9 * j + 1) >> 1) + 36) * 128 + t * 4,
                                              [&](uint32_t* a, int k) {
#pragma unroll
                                                for (int e = 0; e < 4; e++) a[e] = hfma2(a[e], (e & 1) ? ns1 : ns0, (e & 1) ? nb1 : nb0);
                                                stg128(rd + k * 256, a[0], a[1], a[2], a[3]);
                                              });
#pragma unroll
            for (int k = 0; k < 36; k++) { const uint4 v = ldcg128(rd + k * 256); xA[k][0] = v.x; xA[k][1] = v.y; xA[k][2] = v.z; xA[k][3] = v.w; }
          }
        }
        float sm[4] = {0.f, 0.f, 0.f, 0.f}, qq[4] = {0.f, 0.f, 0.f, 0.f};
        auto gelu = [&](auto nz2, bool out) {
          constexpr int NZ2 = nz2.value, R = 8 - NZ2, N = 8, D = NZ2 == 8 ? GM2 : NZ2 ? GMM : GM1;
          float th[32], gb = GB;
          uint32_t qa = 0, qb = 0;
          auto head = [&](int G) {
#pragma unroll
            for (int e = 0; e < 4; e++) { const float v = acc[4 * G + e]; th[4 * G + e] = tanh_fast(v * fmaf(v, v, gb)); }
          };
#pragma unroll
          for (int i = 0; i < D; i++) head((i + R) & 7);
#pragma unroll
          for (int i = 0; i < N; i++) {
            const int G = (i + R) & 7;
            if (i + D < N) head((i + D + R) & 7);
            float* z = acc + 4 * G;
#pragma unroll
            for (int e = 0; e < 4; e++) z[e] = fmaf(z[e], th[4 * G + e], z[e]);
            uint32_t pa = pack2(z[0], z[1]), pb = pack2(z[2], z[3]), tok;
            if (i < NZ2) {
#pragma unroll
              for (int e = 0; e < 4; e++) { sm[e] += z[e]; qq[e] = fmaf(z[e], z[e], qq[e]); }
              pa = hsub2(pa, off2); pb = hsub2(pb, off2);
              stg32(zd + i * 128, pa); stg32(zd + i * 128 + 9216, pb);
              tok = pa ^ pb ^ __float_as_uint(qq[1]);
            } else {
              if (NZ2 && G == 3) sts128(sb + SM_STG + tid * 16, qa, qb, pa, pb);
              else if (G & 1) stg128_if(out, z1d + (G >> 1) * 2048 + (NZ2 ? 24576 : 0), qa, qb, pa, pb);
              if ((G & 1) && !NZ2) zk[G >> 1] = make_uint4(qa, qb, pa, pb);
              qa = pa; qb = pb;
              tok = pa ^ pb;
            }
            gb = __uint_as_float(tok * P.zero + __float_as_uint(GB));
          }
        };
        auto done = [&](int p) {
          wgmma_wait<0>();
          release(c.s);
          c.next();
          TRC(tr && p == 4, w, tb + 7);
          TRC(tr && p == 8, w, tb + 11);
          MCLK(p == 8, 6);
          SCLK(2 * p + 1);
          QCLK(10 + 3 * p);
        };
        auto pass = [&](int p, uint32_t dhi) {
          SCLK(2 * p);
          QCLK(8 + 3 * p);
          bwait(dhi, w);
          bar_sync(6 + w, 256);
          TRC(tr && p == 5, w, tb + 10);
          wgmma_fence();
#pragma unroll
          for (int kk = 0; kk < 36; kk++) mma(kk, PP3, w == 0 || p < 8);
          done(p);
        };
        done(0);
#pragma unroll 1
        for (int p = 1; p < 5; p++) {
          gelu(Int<8>{}, true);
          zd += 1024;
          pass(p, p == 4 ? 0x80000040u : 0x40000040u);
        }
        gelu(Int<4>{}, true);
        signal(EV_ZN);
        {
          const float a0 = qsum(sm[0] + sm[1]), a1 = qsum(sm[2] + sm[3]), q0 = qsum(qq[0] + qq[1]), q1 = qsum(qq[2] + qq[3]);
          const float ss = t ? a1 : a0, m = ss * (1.f / 288.f);
          ll_st128_if(t < 2, g_ZST + (rb * 2 + w) * 512 + j * 64 + 16 * q + 8 * t + g, m - blo(off2), fmaxf((t ? q1 : q0) - ss * m, 0.f), tag);
        }
        TRC(tr, w, tb + 8);
        TRC(tr, w, tb + 9);
#pragma unroll 1
        for (int p = 5; p < 9; p++) {
          pass(p, 0x40000040u);
          gelu(Int<0>{}, p < 8);
          z1d += 8192;
        }
        SCLK(18);
        signal(EV_Z1);
        TRC(tr, w, tb + 12);
      }
      uint32_t hA[18][4];
      {
        float acc[144];
        const float c0 = __uint_as_float(lds32(sb + SM_OFF + 4));
#pragma unroll
        for (int i = 0; i < 144; i++) {
          asm volatile("fma.rn.f32 %0, %1, %2, %3;" : "=f"(acc[i]) : "f"(__uint_as_float(P.zero)), "f"((float)(i + 2)), "f"(c0));
        }
        uint32_t prev = 0;
        auto stage = [&](int kb) {
          mbar_wait_c(bars + B_FULL + c.s * 8, c.ph);
          TRC(tr && kb == 0, w, tb + 13);
          SCLK(22 + kb);
          const uint32_t st = sb + c.s * ST_BYTES, rt = sb + SM_RT + kb * 128 + t * 8;
          uint64_t db = dsc2(dlo(st + ST_B, 4608), 0, 8 + P.zero);
          uint32_t a[4][4];
#pragma unroll
          for (int kk = 0; kk < 4; kk++) {
            uint32_t r[4];
            ldsm4(r, st + (aoff ^ (kk << 5)));
            const uint2 sc = lds64(rt + kk * 32);
            a[kk][0] = hmul2(__byte_perm(r[0], r[2], 0x5410), sc.x); a[kk][2] = hmul2(__byte_perm(r[0], r[2], 0x7632), sc.y);
            a[kk][1] = hmul2(__byte_perm(r[1], r[3], 0x5410), sc.x); a[kk][3] = hmul2(__byte_perm(r[1], r[3], 0x7632), sc.y);
          }
          wgmma_fence();
#pragma unroll
          for (int i = 0; i < 8; i++) {
            const int kk = i & 3, hf = i >> 2;
            wgmma_rs_n144(acc + hf * 72, a[kk], db, 1);
            dadd(db, i == 3 ? 144u - 3 * 576 : 576 + P.zero);
            if (i == 0) { wgmma_commit(); wgmma_wait<1>(); release_if(kb, prev); }
            if (i == 3) wgmma_commit();
          }
          wgmma_commit();
          prev = c.s; c.next();
        };
        mbar_wait_c(bars + B_RT, L);
#pragma unroll 1
        for (int kb = 0; kb < 32; kb += 2) {
          if (kb == 8) mbar_wait_c(bars + B_RT1, L);
          MCLK((kb & 7) == 4, 10 + (kb >> 3));
          stage(kb);
          stage(kb + 1);
        }
        if (w == 1) bar_arrive(6, 256);
        HCLK(0);
        mbar_wait_c(bars + B_CV + w * 8, L);
        HCLK(1);
        const float gk = 0.5f / GA;
        const float c1 = __uint_as_float(lds32(sb + SM_OFF + 4));
        const float gb0 = -gk * (c1 + __uint_as_float(lds32(sb + SM_CV + w * 256 + (16 * q + g) * 4))), gb1 = -gk * (c1 + __uint_as_float(lds32(sb + SM_CV + w * 256 + (16 * q + g + 8) * 4)));
        mbar_wait_c(w ? bars + B_FULL + c.s * 8 : bars + B_ZB, w ? c.ph : L);
        HCLK(2);
        const uint32_t sx = c.s;
        c.next();
        const uint32_t zt = sb + tid * 16, zs = zt + sx * ST_BYTES + w * 24576;
        uint4 zz[18];
        auto zload = [&](int u) {
          if (ZW && u == ZW && P.zero) __nanosleep(0);
          if (u >= 12 && u < 16) zz[u] = zk[u - 12]; else zz[u] = lds128(u == 17 ? zt + SM_STG : zs + (u < 12 ? u : 12) * 2048);
        };
#pragma unroll
        for (int u = 0; u < ZA; u++) zload(u);
#pragma unroll
        for (int u = 0; u < 18; u++) {
          if (u == 0) { wgmma_wait<1>(); HCLK(3); }
          if (u == 9) {
            HCLK(4);
            wgmma_wait<0>();
            HCLK(5);
            release(prev);
            mbar_arrive_if(L == 0 && lane == 0, ev + EV_P4 * 8);
            TRC(tr, w, tb + 14);
            SCLK(54);
          }
          if (u + ZA < 18) zload(u + ZA);
          const uint4 z = zz[u];
          hA[u][0] = hmul2(z.x, pack2(fmaf(acc[8 * u], gk, gb0), fmaf(acc[8 * u + 1], gk, gb0)));
          hA[u][1] = hmul2(z.y, pack2(fmaf(acc[8 * u + 2], gk, gb1), fmaf(acc[8 * u + 3], gk, gb1)));
          hA[u][2] = hmul2(z.z, pack2(fmaf(acc[8 * u + 4], gk, gb0), fmaf(acc[8 * u + 5], gk, gb0)));
          hA[u][3] = hmul2(z.w, pack2(fmaf(acc[8 * u + 6], gk, gb1), fmaf(acc[8 * u + 7], gk, gb1)));
        }
        uint32_t dep = P.zero;
#pragma unroll
        for (int u = 0; u < 18; u++) dep &= hA[u][0];
        release(sx, dep);
        TRC(tr, w, tb + 15);
        HCLK(6);
      }
      {
        const uint32_t el = elect_one();
#pragma unroll 1
        for (int p = 0; p < 9; p++) {
          float acc[32];
          if (w == 0) mbar_wait_c(bars + B_FULL + c.s * 8, c.ph);
          uint64_t db = dsc2(dlo(sb + c.s * ST_BYTES + ST_B + (j & 1) * 4096, 0), 0, 0x40000040u + P.zero);
          HCLK(7 + 2 * p);
          bar_sync(6 + w, 256);
          wgmma_fence();
#pragma unroll
          for (int kk = 0; kk < 18; kk++) {
            wgmma_rs_n64(acc, hA[kk], db, kk != 0);
            dadd(db, kk == 15 ? 128 - (j & 1) * (36864 >> 4) : 128 + P.zero);
            if (kk == PPK && (w == 0 || p < 8)) bar_arrive(7 - w, 256);
          }
          wgmma_commit();
          const uint32_t d = sb + (p & 3) * ST_BYTES, cb = p + j >= 9 ? p + j - 9 : p + j;
          if (el) asm volatile("cp.async.bulk.wait_group.read 3;" ::: "memory");
          __syncwarp();
          wgmma_wait<0>();
          HCLK(8 + 2 * p);
          MCLK(p == 1 || p == 8, 7 + (p >> 3));
          TRC(tr && p == 8, w, tb + 16);
          release_if(L == 0 || p < 5, c.s);
          c.next();
#pragma unroll
          for (int u = 0; u < 4; u++)
            stsm4(d + (aoff ^ (u << 5)), pack2(acc[8 * u], acc[8 * u + 1]), pack2(acc[8 * u + 2], acc[8 * u + 3]), pack2(acc[8 * u + 4], acc[8 * u + 5]), pack2(acc[8 * u + 6], acc[8 * u + 7]));
          fence_async_s();
          __syncwarp();
          tma3d_red_p(el, &P.red[L], cb * 64, rb * 64 + q * 16, w, d + w * 8192 + q * 2048);
          TRC(tr && p == 8, w, tb + 17);
        }
        if (el) asm volatile("cp.async.bulk.wait_group 0;" ::: "memory");
        HCLK(25);
        MCLK(1, 9);
        if (L == 0) signal(EV_PT);
        TRC(tr, w, tb + 18);
      }
    }
    if ((tid & 127) == 0) g_flags[(rb * 2 + w) * 32 + FR_EP + j] = epoch + 1;
    if (tid == 0) g_flags[FJ + j * 32 + FJ_EP + rb] = epoch + 1;
  }
}

typedef CUresult (*EncodeFn)(CUtensorMap*, CUtensorMapDataType, cuuint32_t, void*, const cuuint64_t*, const cuuint64_t*, const cuuint32_t*,
                             const cuuint32_t*, CUtensorMapInterleave, CUtensorMapSwizzle, CUtensorMapL2promotion, CUtensorMapFloatOOBfill);

static void make_map(EncodeFn fn, CUtensorMap* m, const void* ptr, int rank, uint64_t d0, uint64_t d1, uint64_t d2, uint64_t s1, uint64_t s2,
                     uint32_t b0, uint32_t b1, uint32_t b2, CUtensorMapSwizzle swz) {
  cuuint64_t dims[3] = {d0, d1, d2}, strides[2] = {s1, s2};
  cuuint32_t box[3] = {b0, b1, b2}, es[3] = {1, 1, 1};
  fn(m, CU_TENSOR_MAP_DATA_TYPE_BFLOAT16, rank, const_cast<void*>(ptr), dims, strides, box, es, CU_TENSOR_MAP_INTERLEAVE_NONE, swz,
     CU_TENSOR_MAP_L2_PROMOTION_L2_128B, CU_TENSOR_MAP_FLOAT_OOB_FILL_NONE);
}

}

extern "C" void kernel_launch(void* const* d_in, const int* in_sizes, int n_in, void* d_out, int out_size) {
  using namespace mk;
  (void)in_sizes; (void)n_in; (void)out_size;
  static EncodeFn fn = nullptr;
  static uint8_t *wq, *xb;
  static float* csp;
  if (!fn) {
    cudaGetSymbolAddress((void**)&wq, g_WQ);
    cudaGetSymbolAddress((void**)&xb, g_X);
    cudaGetSymbolAddress((void**)&csp, g_CSP);
    cudaDriverEntryPointQueryResult qr;
    cudaGetDriverEntryPoint("cuTensorMapEncodeTiled", (void**)&fn, cudaEnableDefault, &qr);
    cudaFuncSetAttribute(mega_kernel, cudaFuncAttributeMaxDynamicSharedMemorySize, SM_TOTAL);
  }
  Params p;
  p.wqkv = (const __nv_bfloat16*)d_in[1];
  p.w_in = (const __nv_bfloat16*)d_in[4];
  p.w_sp = (const __nv_bfloat16*)d_in[5];
  p.b_sp = (const __nv_bfloat16*)d_in[6];
  p.w_out = (const __nv_bfloat16*)d_in[7];
  p.zero = 0;
  p.wq = wq;
  p.csp = csp;
  p.xs[0] = (uint8_t*)d_in[0];
  p.xs[1] = xb;
  p.xs[2] = (uint8_t*)d_out;
  make_map(fn, &p.wsp, p.w_sp, 3, 2048, 1024, 2, 8192, 4096, 64, 64, 2, CU_TENSOR_MAP_SWIZZLE_128B);
  for (int i = 0; i < 2; i++) {
    make_map(fn, &p.red[i], p.xs[i + 1], 3, DM, 1024, 2, 2304, 1152, 64, 16, 1, CU_TENSOR_MAP_SWIZZLE_128B);
    make_map(fn, &p.res[i], p.xs[i], 3, DM, 1024, 2, 2304, 1152, 144, 64, 1, CU_TENSOR_MAP_SWIZZLE_NONE);
  }
  make_map(fn, &p.psn, d_out, 3, DM, 1024, 2, 2304, 1152, 144, 4, 1, CU_TENSOR_MAP_SWIZZLE_NONE);
  for (int i = 0; i < 3; i++) make_map(fn, &p.act[i], p.xs[i], 3, DM, 1024, 2, 2304, 1152, 64, 64, 1, CU_TENSOR_MAP_SWIZZLE_128B);
  {
    cuuint64_t dims[4] = {8, 8, 72, 72}, strides[3] = {1152, 16, 9216};
    cuuint32_t box[4] = {8, 8, 9, 5}, es[4] = {1, 1, 1, 1};
    fn(&p.wo8, CU_TENSOR_MAP_DATA_TYPE_BFLOAT16, 4, d_in[2], dims, strides, box, es, CU_TENSOR_MAP_INTERLEAVE_NONE, CU_TENSOR_MAP_SWIZZLE_NONE,
       CU_TENSOR_MAP_L2_PROMOTION_L2_128B, CU_TENSOR_MAP_FLOAT_OOB_FILL_NONE);
  }
  for (int i = 0; i < 2; i++) {
    cuuint64_t dims[4] = {i ? 4608u : 2304u, 8, i ? 1u : 2u, 72}, strides[3] = {9216, 4608, 8 * 9216};
    cuuint32_t box[4] = {i ? 64u : 32u, 8, i ? 1u : 2u, 18}, es[4] = {1, 1, 1, 1};
    fn(i ? &p.win64 : &p.win, CU_TENSOR_MAP_DATA_TYPE_BFLOAT16, 4, d_in[4], dims, strides, box, es, CU_TENSOR_MAP_INTERLEAVE_NONE,
       i ? CU_TENSOR_MAP_SWIZZLE_128B : CU_TENSOR_MAP_SWIZZLE_64B, CU_TENSOR_MAP_L2_PROMOTION_L2_128B, CU_TENSOR_MAP_FLOAT_OOB_FILL_NONE);
  }
  make_map(fn, &p.wout, p.w_out, 2, 576, 2304, 1, 1152, 0, 64, 144, 1, CU_TENSOR_MAP_SWIZZLE_128B);
  mega_kernel<<<NGRID, 384, SM_TOTAL, cudaStreamPerThread>>>(p);
}
```

```cpp
#include <cuda_runtime.h>
#include <cuda.h>
#include <cuda_bf16.h>
#include <stdint.h>

#define MK_TRACE 0
#define MK_DBG 0
#define P5TRACE 0
#define LAG1 3
#define PP3 32
#define PP30 33
#define SPL 2
#define NAP 200
#define NAP0 8000
#define KS2 1
#define KS3 1
#define RL3 21
#define PAD 0
#define ZA 4
#define ZW 10
#define GM2 1
#define GMM 1
#define GM1 2
#define C0S 32.f
#define OFA 0.125f
#define OFK 2.f
#define PPK 15

namespace mk {

constexpr int SEQ = 2048, DM = 576, FH = 2304;
constexpr int NCTA = 128;
constexpr int NGRID = 132;
constexpr uint32_t ZB = 36864;
constexpr uint32_t WQ_SL = 72 * 3456;
constexpr uint32_t WO_SL = 72 * 1152;
constexpr float LN_EPS = 1e-5f;
constexpr float GA = 0.3292034911525734f, GB = 2.423681954311584f;

constexpr uint32_t ST_BYTES = 53248, ST_B = 16384, NST = 4;
constexpr uint32_t SM_STG = NST * ST_BYTES;
constexpr uint32_t SM_BAR = SM_STG + 2 * 9216;
constexpr uint32_t SM_OFF = SM_BAR + 1008;
constexpr uint32_t SM_TOTAL = SM_BAR + 1024;
constexpr uint32_t SM_RT = SM_STG + 4096, SM_CV = SM_STG + 12288, SM_WT = SM_CV + 512;
constexpr uint32_t SM_WOI = 44032, SM_CSQ = 49792, SM_XST = 50688;
constexpr uint32_t B_FULL = 0, B_EMPTY = 32, B_FULLA = 64, B_RES = 128, B_WT = 144, B_IMG = 160, B_WOI = 168, B_ZB = 176, B_GATE3 = 184, B_Z1 = 192, B_LAG = 200,
                   B_RT = 208, B_CSQ = 216, B_CV = 224, B_AD = 240, B_EVT = 272, B_RT1 = 368, B_XS = 624, B_XRW = 384, B_FA3 = 400, B_EA3 = 544;
enum { EV_PT = 0, EV_O = 1, EV_X1 = 2, EV_ZN = 3, EV_Z1 = 4, EV_P4 = 5, EV_N = 6 };

enum { FR_X2 = 0, FR_O = 1, FR_X1 = 3, FR_EP = 16, FJ = 32 * 32, FJ_WQ = 0, FJ_WO = 1, FJ_WQ0 = 2, FJ_ZN = 3, FJ_P4 = 5, FJ_EP = 16, F_N = FJ + 8 * 32 };

constexpr uint32_t POISON = 0xffffffffu;
struct Scratch {
  uint32_t flags[F_N];
  uint2 RT[SEQ];
  uint4 XST[2 * SEQ];
  uint4 ST1[SEQ * 8], ZST[SEQ * 8], HALO[32 * 8 * 6 * 32];
  float CSP[2 * NCTA * 216];
  uint8_t WQ[8 * WQ_SL], WO[8 * WO_SL];
  uint8_t O[32 * 2 * ZB];
  uint8_t X[SEQ * DM * 2];
  uint8_t Z[512 * ZB];
  uint4 RD[NCTA * 36 * 256];
};
__device__ __align__(1024) Scratch g_scratch;
#define SLOW(i) do {} while (0)

struct Params {
  const __nv_bfloat16 *wqkv;
  Scratch* s;
  uint32_t zero;
  const __nv_bfloat16 *w_in, *w_sp, *b_sp, *w_out;
  uint8_t* xs[3];
  CUtensorMap wo8, wsp, win, win64, wout;
  CUtensorMap act[3];
  CUtensorMap res[2];
  CUtensorMap red[2];
  CUtensorMap psn;
};

__device__ __forceinline__ uint32_t smem_u32(const void* p) { return (uint32_t)__cvta_generic_to_shared(p); }
__device__ __forceinline__ void mbar_init(uint32_t bar, uint32_t cnt) { asm volatile("mbarrier.init.shared::cta.b64 [%0], %1;" ::"r"(bar), "r"(cnt)); }
__device__ __forceinline__ void mbar_arrive(uint32_t bar) { asm volatile("mbarrier.arrive.shared::cta.b64 _, [%0];" ::"r"(bar) : "memory"); }
__device__ __forceinline__ void mbar_wait(uint32_t bar, uint32_t parity) {
  asm volatile(
      "{\n.reg .pred p;\n.reg .u32 c;\nmov.u32 c, 0;\nLAB_WAIT:\n"
      "mbarrier.try_wait.parity.shared::cta.b64 p, [%0], %1;\n@p bra LAB_DONE;\n"
      "add.u32 c, c, 1;\nsetp.lt.u32 p, c, 0x100000;\n@p bra LAB_WAIT;\ntrap;\nLAB_DONE:\n}" ::"r"(bar), "r"(parity)
      : "memory");
}
__device__ __forceinline__ void mbar_wait_c(uint32_t bar, uint32_t parity) {
  asm volatile("{\n.reg .pred p;\nLAB_WAIT:\nmbarrier.try_wait.parity.shared::cta.b64 p, [%0], %1;\n@!p bra LAB_WAIT;\n}" ::"r"(bar), "r"(parity) : "memory");
}
__device__ __forceinline__ void flag_wait(const uint32_t* f, uint32_t target) {
  asm volatile(
      "{\n.reg .pred p;\n.reg .u32 c, v;\nmov.u32 c, 0;\nLAB_WAIT:\n"
      "ld.relaxed.gpu.global.u32 v, [%0];\nsub.u32 v, v, %1;\nsetp.ge.s32 p, v, 0;\n@p bra LAB_DONE;\n"
      "add.u32 c, c, 1;\nsetp.lt.u32 p, c, 0x400000;\n@p bra LAB_WAIT;\ntrap;\nLAB_DONE:\nfence.acquire.gpu;\n}" ::"l"(f), "r"(target)
      : "memory");
}
__device__ __forceinline__ void fence_gpu() { asm volatile("fence.acq_rel.gpu;" ::: "memory"); }
__device__ __forceinline__ void fence_async_g() { asm volatile("fence.proxy.async.global;" ::: "memory"); }
__device__ __forceinline__ void fence_async_s() { asm volatile("fence.proxy.async.shared::cta;" ::: "memory"); }
__device__ __forceinline__ uint32_t elect_one() {
  uint32_t p; asm volatile("{\n.reg .pred P;\nelect.sync _|P, 0xffffffff;\nselp.u32 %0, 1, 0, P;\n}" : "=r"(p)); return p;
}
__device__ __forceinline__ void expect_tx_p(uint32_t el, uint32_t bar, uint32_t bytes) {
  asm volatile("{\n.reg .pred P;\nsetp.ne.u32 P, %2, 0;\n@P mbarrier.arrive.expect_tx.shared::cta.b64 _, [%0], %1;\n}" ::"r"(bar), "r"(bytes), "r"(el) : "memory");
}
__device__ __forceinline__ void bulk_load_p(uint32_t el, uint32_t dst, const void* src, uint32_t bytes, uint32_t bar) {
  asm volatile("{\n.reg .pred P;\nsetp.ne.u32 P, %4, 0;\n@P cp.async.bulk.shared::cluster.global.mbarrier::complete_tx::bytes [%0], [%1], %2, [%3];\n}" ::"r"(dst), "l"(src), "r"(bytes), "r"(bar), "r"(el) : "memory");
}
__device__ __forceinline__ uint64_t policy_evict_first() { uint64_t p; asm("createpolicy.fractional.L2::evict_first.b64 %0, 1.0;" : "=l"(p)); return p; }
__device__ __forceinline__ void bulk_load_h(uint32_t el, uint32_t dst, const void* src, uint32_t bytes, uint32_t bar, bool ef, uint64_t pol) {
  if (ef) {
    asm volatile("{\n.reg .pred P;\nsetp.ne.u32 P, %4, 0;\n@P cp.async.bulk.shared::cluster.global.mbarrier::complete_tx::bytes.L2::cache_hint [%0], [%1], %2, [%3], %5;\n}" ::"r"(dst), "l"(src), "r"(bytes), "r"(bar), "r"(el), "l"(pol) : "memory");
  } else {
    asm volatile("{\n.reg .pred P;\nsetp.ne.u32 P, %4, 0;\n@P cp.async.bulk.shared::cluster.global.mbarrier::complete_tx::bytes [%0], [%1], %2, [%3];\n}" ::"r"(dst), "l"(src), "r"(bytes), "r"(bar), "r"(el) : "memory");
  }
}
__device__ __forceinline__ void bulk_mc_h(uint32_t el, uint32_t dst, const void* src, uint32_t bytes, uint32_t bar, bool ef, uint64_t pol) {
  if (ef) {
    asm volatile("{\n.reg .pred P;\nsetp.ne.u32 P, %4, 0;\n@P cp.async.bulk.shared::cluster.global.mbarrier::complete_tx::bytes.multicast::cluster.L2::cache_hint [%0], [%1], %2, [%3], %5, %6;\n}" ::"r"(dst), "l"(src), "r"(bytes), "r"(bar), "r"(el), "h"((uint16_t)3), "l"(pol) : "memory");
  } else {
    asm volatile("{\n.reg .pred P;\nsetp.ne.u32 P, %4, 0;\n@P cp.async.bulk.shared::cluster.global.mbarrier::complete_tx::bytes.multicast::cluster [%0], [%1], %2, [%3], %5;\n}" ::"r"(dst), "l"(src), "r"(bytes), "r"(bar), "r"(el), "h"((uint16_t)3) : "memory");
  }
}
__device__ __forceinline__ void tma3d_h(uint32_t el, uint32_t dst, const CUtensorMap* m, int c0, int c1, int c2, uint32_t bar, bool ef, uint64_t pol) {
  if (ef) {
    asm volatile("{\n.reg .pred P;\nsetp.ne.u32 P, %6, 0;\n@P cp.async.bulk.tensor.3d.shared::cluster.global.mbarrier::complete_tx::bytes.L2::cache_hint [%0], [%1, {%3, %4, %5}], [%2], %7;\n}" ::"r"(dst), "l"(m), "r"(bar), "r"(c0), "r"(c1), "r"(c2), "r"(el), "l"(pol) : "memory");
  } else {
    asm volatile("{\n.reg .pred P;\nsetp.ne.u32 P, %6, 0;\n@P cp.async.bulk.tensor.3d.shared::cluster.global.mbarrier::complete_tx::bytes [%0], [%1, {%3, %4, %5}], [%2];\n}" ::"r"(dst), "l"(m), "r"(bar), "r"(c0), "r"(c1), "r"(c2), "r"(el) : "memory");
  }
}
__device__ __forceinline__ void tma2d_mc_h(uint32_t el, uint32_t dst, const CUtensorMap* m, int c0, int c1, uint32_t bar, bool ef, uint64_t pol) {
  if (ef) {
    asm volatile("{\n.reg .pred P;\nsetp.ne.u32 P, %5, 0;\n@P cp.async.bulk.tensor.2d.shared::cluster.global.mbarrier::complete_tx::bytes.multicast::cluster.L2::cache_hint [%0], [%1, {%3, %4}], [%2], %6, %7;\n}" ::"r"(dst), "l"(m), "r"(bar), "r"(c0), "r"(c1), "r"(el), "h"((uint16_t)3), "l"(pol) : "memory");
  } else {
    asm volatile("{\n.reg .pred P;\nsetp.ne.u32 P, %5, 0;\n@P cp.async.bulk.tensor.2d.shared::cluster.global.mbarrier::complete_tx::bytes.multicast::cluster [%0], [%1, {%3, %4}], [%2], %6;\n}" ::"r"(dst), "l"(m), "r"(bar), "r"(c0), "r"(c1), "r"(el), "h"((uint16_t)3) : "memory");
  }
}
__device__ __forceinline__ void tma4d_mc(uint32_t el, uint32_t dst, const CUtensorMap* m, int c0, int c3, uint32_t bar, uint64_t pol) {
  asm volatile("{\n.reg .pred P;\nsetp.ne.u32 P, %5, 0;\n@P cp.async.bulk.tensor.4d.shared::cluster.global.mbarrier::complete_tx::bytes.multicast::cluster.L2::cache_hint [%0], [%1, {%3, 0, 0, %4}], [%2], %6, %7;\n}" ::"r"(dst), "l"(m), "r"(bar), "r"(c0), "r"(c3), "r"(el), "h"((uint16_t)3), "l"(pol) : "memory");
}
__device__ __forceinline__ void mbar_arrive_cluster(uint32_t addr) { asm volatile("mbarrier.arrive.shared::cluster.b64 _, [%0];" ::"r"(addr) : "memory"); }
__device__ __forceinline__ void mbar_arrive_cluster_if(bool c, uint32_t addr) {
  asm volatile("{\n.reg .pred P;\nsetp.ne.u32 P, %1, 0;\n@P mbarrier.arrive.shared::cluster.b64 _, [%0];\n}" ::"r"(addr), "r"((uint32_t)c) : "memory");
}
__device__ __forceinline__ void mbar_arrive_if(bool c, uint32_t addr) {
  asm volatile("{\n.reg .pred P;\nsetp.ne.u32 P, %1, 0;\n@P mbarrier.arrive.shared::cta.b64 _, [%0];\n}" ::"r"(addr), "r"((uint32_t)c) : "memory");
}
__device__ __forceinline__ uint32_t mapa(uint32_t addr, uint32_t rank) { uint32_t r; asm("mapa.shared::cluster.u32 %0, %1, %2;" : "=r"(r) : "r"(addr), "r"(rank)); return r; }
__device__ __forceinline__ void bulk_store_p(uint32_t el, void* dst, uint32_t src, uint32_t bytes) {
  asm volatile("{\n.reg .pred P;\nsetp.ne.u32 P, %3, 0;\n@P cp.async.bulk.global.shared::cta.bulk_group [%0], [%1], %2;\n}" ::"l"(dst), "r"(src), "r"(bytes), "r"(el) : "memory");
}
__device__ __forceinline__ void flag_release_p(uint32_t el, uint32_t* f) {
  asm volatile("{\n.reg .pred P;\nsetp.ne.u32 P, %1, 0;\n@P red.release.gpu.global.add.u32 [%0], 1;\n}" ::"l"(f), "r"(el) : "memory");
}
__device__ __forceinline__ void flag_add_p(uint32_t el, uint32_t* f) {
  asm volatile("{\n.reg .pred P;\nsetp.ne.u32 P, %1, 0;\n@P red.relaxed.gpu.global.add.u32 [%0], 1;\n}" ::"l"(f), "r"(el) : "memory");
}
__device__ __forceinline__ void prefetch_l2(const void* src, uint32_t bytes) { asm volatile("cp.async.bulk.prefetch.L2.global [%0], %1;" ::"l"(src), "r"(bytes) : "memory"); }
__device__ __forceinline__ void prefetch_map(const CUtensorMap* m) { asm volatile("prefetch.tensormap [%0];" ::"l"(m) : "memory"); }
__device__ __forceinline__ void wgmma_fence() { asm volatile("wgmma.fence.sync.aligned;" ::: "memory"); }
__device__ __forceinline__ void wgmma_commit() { asm volatile("wgmma.commit_group.sync.aligned;" ::: "memory"); }
template <int N> __device__ __forceinline__ void wgmma_wait() { asm volatile("wgmma.wait_group.sync.aligned %0;" ::"n"(N) : "memory"); }
__device__ __forceinline__ uint32_t dlo(uint32_t addr, uint32_t lbo) { return ((addr & 0x3FFFF) >> 4) + ((lbo >> 4) << 16); }
template <uint32_t SBO, uint32_t SWZ> __device__ __forceinline__ uint64_t dsc(uint32_t lo, uint32_t off) {
  uint64_t d; asm("mov.b64 %0, {%1, %2};" : "=l"(d) : "r"(lo + (off >> 4)), "n"((SBO >> 4) | (SWZ << 30))); return d;
}
__device__ __forceinline__ uint64_t dsc2(uint32_t lo, uint32_t off, uint32_t hi) {
  uint64_t d; asm("mov.b64 %0, {%1, %2};" : "=l"(d) : "r"(lo + (off >> 4)), "r"(hi)); return d;
}
__device__ __forceinline__ uint64_t dat(uint64_t d, uint32_t off, uint32_t one) { uint64_t r; asm("mad.wide.u32 %0, %1, %2, %3;" : "=l"(r) : "r"(one), "r"(off >> 4), "l"(d)); return r; }
__device__ __forceinline__ void dadd(uint64_t& d, uint32_t v) {
  asm("{\n.reg .b32 lo, hi;\nmov.b64 {lo, hi}, %0;\nadd.u32 lo, lo, %1;\nmov.b64 %0, {lo, hi};\n}" : "+l"(d) : "r"(v));
}
template <int R> __device__ __forceinline__ void reg_alloc() { asm volatile("setmaxnreg.inc.sync.aligned.u32 %0;" ::"n"(R)); }
template <int R> __device__ __forceinline__ void reg_dealloc() { asm volatile("setmaxnreg.dec.sync.aligned.u32 %0;" ::"n"(R)); }
__device__ __forceinline__ void bar_sync(int id, int n) { asm volatile("bar.sync %0, %1;" ::"r"(id), "r"(n) : "memory"); }
__device__ __forceinline__ void bar_arrive(int id, int n) { asm volatile("bar.arrive %0, %1;" ::"r"(id), "r"(n) : "memory"); }
__device__ __forceinline__ void ldsm4(uint32_t* r, uint32_t addr) {
  asm volatile("ldmatrix.sync.aligned.m8n8.x4.shared.b16 {%0,%1,%2,%3}, [%4];" : "=r"(r[0]), "=r"(r[1]), "=r"(r[2]), "=r"(r[3]) : "r"(addr) : "memory");
}
__device__ __forceinline__ uint32_t movm(uint32_t a) { uint32_t d; asm volatile("movmatrix.sync.aligned.m8n8.trans.b16 %0, %1;" : "=r"(d) : "r"(a)); return d; }
__device__ __forceinline__ void mma16(float* c, uint32_t a0, uint32_t a1, uint32_t a2, uint32_t a3, uint32_t b0, uint32_t b1) {
  asm volatile("mma.sync.aligned.m16n8k16.row.col.f32.bf16.bf16.f32 {%0,%1,%2,%3}, {%4,%5,%6,%7}, {%8,%9}, {%10,%10,%10,%10};"
               : "=f"(c[0]), "=f"(c[1]), "=f"(c[2]), "=f"(c[3]) : "r"(a0), "r"(a1), "r"(a2), "r"(a3), "r"(b0), "r"(b1), "f"(0.f));
}
__device__ __forceinline__ void mma8(float* c, uint32_t a0, uint32_t a1, uint32_t b0) {
  asm volatile("mma.sync.aligned.m16n8k8.row.col.f32.bf16.bf16.f32 {%0,%1,%2,%3}, {%4,%5}, {%6}, {%0,%1,%2,%3};"
               : "+f"(c[0]), "+f"(c[1]), "+f"(c[2]), "+f"(c[3]) : "r"(a0), "r"(a1), "r"(b0));
}
__device__ __forceinline__ void widen(float* c, uint32_t a0, uint32_t a1, uint32_t eye) {
  asm volatile("mma.sync.aligned.m16n8k8.row.col.f32.bf16.bf16.f32 {%0,%1,%2,%3}, {%4,%5}, {%6}, {%7,%7,%7,%7};"
               : "=f"(c[0]), "=f"(c[1]), "=f"(c[2]), "=f"(c[3]) : "r"(a0), "r"(a1), "r"(eye), "f"(0.f));
}
__device__ __forceinline__ float rsq_fast(float x) { float y; asm("rsqrt.approx.ftz.f32 %0, %1;" : "=f"(y) : "f"(x)); return y; }
__device__ __forceinline__ uint32_t pack2(float lo, float hi) { uint32_t r; asm("cvt.rn.bf16x2.f32 %0, %1, %2;" : "=r"(r) : "f"(hi), "f"(lo)); return r; }
__device__ __forceinline__ float blo(uint32_t v) { return __uint_as_float(v << 16); }
__device__ __forceinline__ float bhi(uint32_t v) { return __uint_as_float(v & 0xffff0000u); }
__device__ __forceinline__ float tanh_fast(float x) { float y; asm("tanh.approx.f32 %0, %1;" : "=f"(y) : "f"(x)); return y; }
__device__ __forceinline__ float rcp_fast(float x) { float y; asm("rcp.approx.ftz.f32 %0, %1;" : "=f"(y) : "f"(x)); return y; }
__device__ __forceinline__ float ex2(float x) { float y; asm("ex2.approx.ftz.f32 %0, %1;" : "=f"(y) : "f"(x)); return y; }
__device__ __forceinline__ float qsum(float v) { v += __shfl_xor_sync(~0u, v, 1); v += __shfl_xor_sync(~0u, v, 2); return v; }
__device__ __forceinline__ float qmax(float v) { v = fmaxf(v, __shfl_xor_sync(~0u, v, 1)); v = fmaxf(v, __shfl_xor_sync(~0u, v, 2)); return v; }
__device__ __forceinline__ void stg32(void* p, uint32_t v) { asm volatile("st.global.u32 [%0], %1;" ::"l"(p), "r"(v) : "memory"); }
__device__ __forceinline__ void stg128(void* p, uint32_t a, uint32_t b, uint32_t c, uint32_t d) { asm volatile("st.global.v4.u32 [%0], {%1,%2,%3,%4};" ::"l"(p), "r"(a), "r"(b), "r"(c), "r"(d) : "memory"); }
__device__ __forceinline__ uint32_t ldcg32(const void* p) { uint32_t v; asm volatile("ld.global.L1::no_allocate.u32 %0, [%1];" : "=r"(v) : "l"(p) : "memory"); return v; }
__device__ __forceinline__ uint32_t ldgpu32(const void* p) { uint32_t v; asm volatile("ld.relaxed.gpu.global.u32 %0, [%1];" : "=r"(v) : "l"(p) : "memory"); return v; }
__device__ __forceinline__ uint32_t ldca32(const void* p) { uint32_t v; asm volatile("ld.global.ca.u32 %0, [%1];" : "=r"(v) : "l"(p) : "memory"); return v; }
__device__ __forceinline__ void stg128_if(bool c, void* p, uint32_t a, uint32_t b, uint32_t cc, uint32_t d) {
  asm volatile("{\n.reg .pred P;\nsetp.ne.u32 P, %5, 0;\n@P st.global.v4.u32 [%0], {%1,%2,%3,%4};\n}" ::"l"(p), "r"(a), "r"(b), "r"(cc), "r"(d), "r"((uint32_t)c) : "memory");
}
__device__ __forceinline__ uint2 lds64(uint32_t a) { uint2 v; asm volatile("ld.shared.v2.u32 {%0,%1}, [%2];" : "=r"(v.x), "=r"(v.y) : "r"(a) : "memory"); return v; }
__device__ __forceinline__ uint4 ldcg128(const void* p) { uint4 v; asm volatile("ld.global.cg.v4.u32 {%0,%1,%2,%3}, [%4];" : "=r"(v.x), "=r"(v.y), "=r"(v.z), "=r"(v.w) : "l"(p) : "memory"); return v; }
__device__ __forceinline__ uint32_t ldnc16(const void* p) { uint16_t v; asm volatile("ld.global.nc.u16 %0, [%1];" : "=h"(v) : "l"(p)); return v; }
__device__ __forceinline__ uint4 ldnc128(const void* p) { uint4 v; asm volatile("ld.global.nc.v4.u32 {%0,%1,%2,%3}, [%4];" : "=r"(v.x), "=r"(v.y), "=r"(v.z), "=r"(v.w) : "l"(p)); return v; }
__device__ __forceinline__ uint32_t hsub2(uint32_t a, uint32_t b) { uint32_t d; asm("sub.rn.bf16x2 %0, %1, %2;" : "=r"(d) : "r"(a), "r"(b)); return d; }
__device__ __forceinline__ void stg32_if(bool c, void* p, uint32_t v) {
  asm volatile("{\n.reg .pred P;\nsetp.ne.u32 P, %2, 0;\n@P st.global.u32 [%0], %1;\n}" ::"l"(p), "r"(v), "r"((uint32_t)c) : "memory");
}
__device__ __forceinline__ uint32_t hmul2(uint32_t a, uint32_t b) { uint32_t d; asm("mul.rn.bf16x2 %0, %1, %2;" : "=r"(d) : "r"(a), "r"(b)); return d; }
__device__ __forceinline__ void sts32(uint32_t a, uint32_t v) { asm volatile("st.shared.u32 [%0], %1;" ::"r"(a), "r"(v) : "memory"); }
__device__ __forceinline__ uint32_t lds32(uint32_t a) { uint32_t v; asm volatile("ld.shared.u32 %0, [%1];" : "=r"(v) : "r"(a) : "memory"); return v; }
__device__ __forceinline__ void sts128(uint32_t a, uint32_t x, uint32_t y, uint32_t z, uint32_t w) { asm volatile("st.shared.v4.u32 [%0], {%1,%2,%3,%4};" ::"r"(a), "r"(x), "r"(y), "r"(z), "r"(w) : "memory"); }
__device__ __forceinline__ uint4 lds128(uint32_t a) { uint4 v; asm volatile("ld.shared.v4.u32 {%0,%1,%2,%3}, [%4];" : "=r"(v.x), "=r"(v.y), "=r"(v.z), "=r"(v.w) : "r"(a) : "memory"); return v; }
__device__ __forceinline__ void ll_st64(uint2* p, uint32_t v, uint32_t tag) {
  asm volatile("{\n.reg .b64 r;\nmov.b64 r, {%1,%2};\nst.relaxed.gpu.global.b64 [%0], r;\n}" ::"l"(p), "r"(v), "r"(tag) : "memory");
}
__device__ __forceinline__ uint2 ll_ld64(const uint2* p) {
  uint2 v; asm volatile("{\n.reg .b64 r;\nld.relaxed.gpu.global.b64 r, [%2];\nmov.b64 {%0,%1}, r;\n}" : "=r"(v.x), "=r"(v.y) : "l"(p) : "memory"); return v;
}
__device__ __forceinline__ void ll_st128(uint4* p, float a, float b, uint32_t tag, float c = 0.f) {
  asm volatile("{\n.reg .b128 r;\n.reg .b64 lo, hi;\nmov.b64 lo, {%1,%2};\nmov.b64 hi, {%3,%4};\nmov.b128 r, {lo, hi};\nst.relaxed.gpu.global.b128 [%0], r;\n}" ::"l"(p), "r"(__float_as_uint(a)), "r"(__float_as_uint(b)), "r"(tag), "r"(__float_as_uint(c)) : "memory");
}
__device__ __forceinline__ uint4 ll_ld128(const uint4* p) {
  uint4 v; asm volatile("{\n.reg .b128 r;\n.reg .b64 lo, hi;\nld.relaxed.gpu.global.b128 r, [%4];\nmov.b128 {lo, hi}, r;\nmov.b64 {%0,%1}, lo;\nmov.b64 {%2,%3}, hi;\n}" : "=r"(v.x), "=r"(v.y), "=r"(v.z), "=r"(v.w) : "l"(p) : "memory"); return v;
}
__device__ __forceinline__ void publish_p(uint32_t el, uint32_t* f) {
  asm volatile("{\n.reg .pred P;\nsetp.ne.u32 P, %1, 0;\n@P cp.async.bulk.commit_group;\n@P cp.async.bulk.wait_group 0;\n@P red.release.gpu.global.add.u32 [%0], 1;\n}" ::"l"(f), "r"(el) : "memory");
}
__device__ __forceinline__ void tma3d_red_p(uint32_t el, const CUtensorMap* m, int c0, int c1, int c2, uint32_t src) {
  asm volatile("{\n.reg .pred P;\nsetp.ne.u32 P, %5, 0;\n@P cp.reduce.async.bulk.tensor.3d.global.shared::cta.add.tile.bulk_group [%0, {%2, %3, %4}], [%1];\n@P cp.async.bulk.commit_group;\n}" ::"l"(m), "r"(src), "r"(c0), "r"(c1), "r"(c2), "r"(el) : "memory");
}
__device__ __forceinline__ void stsm4(uint32_t addr, uint32_t a, uint32_t b, uint32_t c, uint32_t d) {
  asm volatile("stmatrix.sync.aligned.m8n8.x4.shared.b16 [%0], {%1,%2,%3,%4};" ::"r"(addr), "r"(a), "r"(b), "r"(c), "r"(d) : "memory");
}
__device__ __forceinline__ void sts64(uint32_t a, uint32_t x, uint32_t y) { asm volatile("st.shared.v2.u32 [%0], {%1,%2};" ::"r"(a), "r"(x), "r"(y) : "memory"); }
__device__ __forceinline__ void ll_st128_if(bool on, uint4* p, float a, float b, uint32_t tag) {
  asm volatile("{\n.reg .pred P;\n.reg .b128 r;\n.reg .b64 lo, hi;\nsetp.ne.u32 P, %4, 0;\nmov.b64 lo, {%1,%2};\nmov.b64 hi, {%3,%3};\nmov.b128 r, {lo, hi};\n@P st.relaxed.gpu.global.b128 [%0], r;\n}" ::"l"(p), "r"(__float_as_uint(a)), "r"(__float_as_uint(b)), "r"(tag), "r"((uint32_t)on) : "memory");
}
__device__ __forceinline__ uint4 ldnc128_if(bool c, const void* p) {
  uint4 v = make_uint4(0u, 0u, 0u, 0u);
  asm volatile("{\n.reg .pred P;\nsetp.ne.u32 P, %5, 0;\n@P ld.global.nc.v4.u32 {%0,%1,%2,%3}, [%4];\n}" : "+r"(v.x), "+r"(v.y), "+r"(v.z), "+r"(v.w) : "l"(p), "r"((uint32_t)c));
  return v;
}
__device__ __forceinline__ uint32_t hfma2(uint32_t a, uint32_t b, uint32_t c) { uint32_t d; asm("fma.rn.bf16x2 %0, %1, %2, %3;" : "=r"(d) : "r"(a), "r"(b), "r"(c)); return d; }
__device__ __forceinline__ float2 lds64f(uint32_t a) { float2 v; asm volatile("ld.shared.v2.f32 {%0,%1}, [%2];" : "=f"(v.x), "=f"(v.y) : "r"(a) : "memory"); return v; }
#define TRC(cond, role, idx) do {} while (0)
#define TRV(role, idx, v) do {} while (0)

#define ACLK_INIT do {} while (0)
#define ACLK(i) do {} while (0)
#define ACLK_OUT do {} while (0)
#define QCLK(i) do {} while (0)
#define PH 1
#define RCLK(i) do {} while (0)
#define RCLK_INIT do {} while (0)
#define RCLK_OUT do {} while (0)
#define SCLK(i) do {} while (0)
#define HCLK(i) do {} while (0)
#define MCLK(c, i) do {} while (0)
#define CKK(i) do {} while (0)
#define CKK_OUT do {} while (0)
#define PL 1
#define PCLK(i) do {} while (0)
#define PQ 1
#define CLK_INIT do {} while (0)
#define CLK(i) do {} while (0)
#define CLK_OUT do {} while (0)

__device__ __forceinline__ void wgmma_ss_n216(float* d, uint64_t da, uint64_t db, int scaleD) {
  asm volatile("{\n.reg .pred p;\nsetp.ne.b32 p, %110, 0;\nwgmma.mma_async.sync.aligned.m64n216k16.f32.bf16.bf16 "
    "{%0,%1,%2,%3,%4,%5,%6,%7,%8,%9,%10,%11,%12,%13,%14,%15,%16,%17,%18,%19,%20,%21,%22,%23,%24,%25,%26,%27,%28,%29,%30,%31,%32,%33,%34,%35,%36,%37,%38,%39,%40,%41,%42,%43,%44,%45,%46,%47,%48,%49,%50,%51,%52,%53,%54,%55,%56,%57,%58,%59,%60,%61,%62,%63,%64,%65,%66,%67,%68,%69,%70,%71,%72,%73,%74,%75,%76,%77,%78,%79,%80,%81,%82,%83,%84,%85,%86,%87,%88,%89,%90,%91,%92,%93,%94,%95,%96,%97,%98,%99,%100,%101,%102,%103,%104,%105,%106,%107}, "
    "%108, %109, p, 1, 1, 0, 1;\n}\n"
    : "+f"(d[0]), "+f"(d[1]), "+f"(d[2]), "+f"(d[3]), "+f"(d[4]), "+f"(d[5]), "+f"(d[6]), "+f"(d[7]), "+f"(d[8]), "+f"(d[9]), "+f"(d[10]), "+f"(d[11]), "+f"(d[12]), "+f"(d[13]), "+f"(d[14]), "+f"(d[15]), "+f"(d[16]), "+f"(d[17]), "+f"(d[18]), "+f"(d[19]), "+f"(d[20]), "+f"(d[21]), "+f"(d[22]), "+f"(d[23]), "+f"(d[24]), "+f"(d[25]), "+f"(d[26]), "+f"(d[27]), "+f"(d[28]), "+f"(d[29]), "+f"(d[30]), "+f"(d[31]), "+f"(d[32]), "+f"(d[33]), "+f"(d[34]), "+f"(d[35]), "+f"(d[36]), "+f"(d[37]), "+f"(d[38]), "+f"(d[39]), "+f"(d[40]), "+f"(d[41]), "+f"(d[42]), "+f"(d[43]), "+f"(d[44]), "+f"(d[45]), "+f"(d[46]), "+f"(d[47]), "+f"(d[48]), "+f"(d[49]), "+f"(d[50]), "+f"(d[51]), "+f"(d[52]), "+f"(d[53]), "+f"(d[54]), "+f"(d[55]), "+f"(d[56]), "+f"(d[57]), "+f"(d[58]), "+f"(d[59]), "+f"(d[60]), "+f"(d[61]), "+f"(d[62]), "+f"(d[63]), "+f"(d[64]), "+f"(d[65]), "+f"(d[66]), "+f"(d[67]), "+f"(d[68]), "+f"(d[69]), "+f"(d[70]), "+f"(d[71]), "+f"(d[72]), "+f"(d[73]), "+f"(d[74]), "+f"(d[75]), "+f"(d[76]), "+f"(d[77]), "+f"(d[78]), "+f"(d[79]), "+f"(d[80]), "+f"(d[81]), "+f"(d[82]), "+f"(d[83]), "+f"(d[84]), "+f"(d[85]), "+f"(d[86]), "+f"(d[87]), "+f"(d[88]), "+f"(d[89]), "+f"(d[90]), "+f"(d[91]), "+f"(d[92]), "+f"(d[93]), "+f"(d[94]), "+f"(d[95]), "+f"(d[96]), "+f"(d[97]), "+f"(d[98]), "+f"(d[99]), "+f"(d[100]), "+f"(d[101]), "+f"(d[102]), "+f"(d[103]), "+f"(d[104]), "+f"(d[105]), "+f"(d[106]), "+f"(d[107])
    : "l"(da), "l"(db), "r"(scaleD));
}
__device__ __forceinline__ void wgmma_ss_n72(float* d, uint64_t da, uint64_t db, int scaleD) {
  asm volatile("{\n.reg .pred p;\nsetp.ne.b32 p, %38, 0;\nwgmma.mma_async.sync.aligned.m64n72k16.f32.bf16.bf16 "
    "{%0,%1,%2,%3,%4,%5,%6,%7,%8,%9,%10,%11,%12,%13,%14,%15,%16,%17,%18,%19,%20,%21,%22,%23,%24,%25,%26,%27,%28,%29,%30,%31,%32,%33,%34,%35}, "
    "%36, %37, p, 1, 1, 0, 1;\n}\n"
    : "+f"(d[0]), "+f"(d[1]), "+f"(d[2]), "+f"(d[3]), "+f"(d[4]), "+f"(d[5]), "+f"(d[6]), "+f"(d[7]), "+f"(d[8]), "+f"(d[9]), "+f"(d[10]), "+f"(d[11]), "+f"(d[12]), "+f"(d[13]), "+f"(d[14]), "+f"(d[15]), "+f"(d[16]), "+f"(d[17]), "+f"(d[18]), "+f"(d[19]), "+f"(d[20]), "+f"(d[21]), "+f"(d[22]), "+f"(d[23]), "+f"(d[24]), "+f"(d[25]), "+f"(d[26]), "+f"(d[27]), "+f"(d[28]), "+f"(d[29]), "+f"(d[30]), "+f"(d[31]), "+f"(d[32]), "+f"(d[33]), "+f"(d[34]), "+f"(d[35])
    : "l"(da), "l"(db), "r"(scaleD));
}
__device__ __forceinline__ void wgmma_rs_n144(float* d, const uint32_t* a, uint64_t db, int scaleD) {
  asm volatile("{\n.reg .pred p;\nsetp.ne.b32 p, %77, 0;\nwgmma.mma_async.sync.aligned.m64n144k16.f32.bf16.bf16 "
    "{%0,%1,%2,%3,%4,%5,%6,%7,%8,%9,%10,%11,%12,%13,%14,%15,%16,%17,%18,%19,%20,%21,%22,%23,%24,%25,%26,%27,%28,%29,%30,%31,%32,%33,%34,%35,%36,%37,%38,%39,%40,%41,%42,%43,%44,%45,%46,%47,%48,%49,%50,%51,%52,%53,%54,%55,%56,%57,%58,%59,%60,%61,%62,%63,%64,%65,%66,%67,%68,%69,%70,%71}, "
    "{%72,%73,%74,%75}, %76, p, 1, 1, 1;\n}\n"
    : "+f"(d[0]), "+f"(d[1]), "+f"(d[2]), "+f"(d[3]), "+f"(d[4]), "+f"(d[5]), "+f"(d[6]), "+f"(d[7]), "+f"(d[8]), "+f"(d[9]), "+f"(d[10]), "+f"(d[11]), "+f"(d[12]), "+f"(d[13]), "+f"(d[14]), "+f"(d[15]), "+f"(d[16]), "+f"(d[17]), "+f"(d[18]), "+f"(d[19]), "+f"(d[20]), "+f"(d[21]), "+f"(d[22]), "+f"(d[23]), "+f"(d[24]), "+f"(d[25]), "+f"(d[26]), "+f"(d[27]), "+f"(d[28]), "+f"(d[29]), "+f"(d[30]), "+f"(d[31]), "+f"(d[32]), "+f"(d[33]), "+f"(d[34]), "+f"(d[35]), "+f"(d[36]), "+f"(d[37]), "+f"(d[38]), "+f"(d[39]), "+f"(d[40]), "+f"(d[41]), "+f"(d[42]), "+f"(d[43]), "+f"(d[44]), "+f"(d[45]), "+f"(d[46]), "+f"(d[47]), "+f"(d[48]), "+f"(d[49]), "+f"(d[50]), "+f"(d[51]), "+f"(d[52]), "+f"(d[53]), "+f"(d[54]), "+f"(d[55]), "+f"(d[56]), "+f"(d[57]), "+f"(d[58]), "+f"(d[59]), "+f"(d[60]), "+f"(d[61]), "+f"(d[62]), "+f"(d[63]), "+f"(d[64]), "+f"(d[65]), "+f"(d[66]), "+f"(d[67]), "+f"(d[68]), "+f"(d[69]), "+f"(d[70]), "+f"(d[71])
    : "r"(a[0]), "r"(a[1]), "r"(a[2]), "r"(a[3]), "l"(db), "r"(scaleD));
}
__device__ __forceinline__ void wgmma_rs_n64(float* d, const uint32_t* a, uint64_t db, int scaleD) {
  asm volatile("{\n.reg .pred p;\nsetp.ne.b32 p, %37, 0;\nwgmma.mma_async.sync.aligned.m64n64k16.f32.bf16.bf16 "
    "{%0,%1,%2,%3,%4,%5,%6,%7,%8,%9,%10,%11,%12,%13,%14,%15,%16,%17,%18,%19,%20,%21,%22,%23,%24,%25,%26,%27,%28,%29,%30,%31}, "
    "{%32,%33,%34,%35}, %36, p, 1, 1, 1;\n}\n"
    : "+f"(d[0]), "+f"(d[1]), "+f"(d[2]), "+f"(d[3]), "+f"(d[4]), "+f"(d[5]), "+f"(d[6]), "+f"(d[7]), "+f"(d[8]), "+f"(d[9]), "+f"(d[10]), "+f"(d[11]), "+f"(d[12]), "+f"(d[13]), "+f"(d[14]), "+f"(d[15]), "+f"(d[16]), "+f"(d[17]), "+f"(d[18]), "+f"(d[19]), "+f"(d[20]), "+f"(d[21]), "+f"(d[22]), "+f"(d[23]), "+f"(d[24]), "+f"(d[25]), "+f"(d[26]), "+f"(d[27]), "+f"(d[28]), "+f"(d[29]), "+f"(d[30]), "+f"(d[31])
    : "r"(a[0]), "r"(a[1]), "r"(a[2]), "r"(a[3]), "l"(db), "r"(scaleD));
}

template <int V> struct Int { static constexpr int value = V; };
struct Cur {
  uint32_t s, ph;
  __device__ __forceinline__ void next() { if (++s == NST) { s = 0; ph ^= 1; } }
};

#define z1_block(rb, w, j) (P.s->Z + ((rb) * 16 + (w) * 8 + (j)) * ZB)
#define z2_block(kb, j) (P.s->Z + (256 + (kb) * 8 + (j)) * ZB)
#define o_block(rb, w) (P.s->O + ((rb) * 2 + (w)) * (2 * ZB))
__device__ __forceinline__ void combine8(float m0, float q0, float m1, float q1, float n, float eps, float& mean, float& rstd) {
  mean = qsum(m0 + m1) * 0.125f;
  float d0 = m0 - mean, d1 = m1 - mean;
  float M2 = qsum(q0 + q1 + n * (d0 * d0 + d1 * d1));
  rstd = rsq_fast(fmaf(M2, 0.125f / n, eps));
}
__device__ __forceinline__ void stat_get(const uint4* zs, uint32_t tag, float n, float eps, float& m0, float& r0, float& m1, float& r1) {
  uint4 a0, a1, b0, b1;
#pragma unroll 1
  for (int it = 0; it < (1 << 20); it++) {
    a0 = ll_ld128(zs); a1 = ll_ld128(zs + 64); b0 = ll_ld128(zs + 8); b1 = ll_ld128(zs + 72);
    if (__all_sync(~0u, a0.z == tag && a1.z == tag && b0.z == tag && b1.z == tag)) break;
  }
  combine8(__uint_as_float(a0.x), __uint_as_float(a0.y), __uint_as_float(a1.x), __uint_as_float(a1.y), n, eps, m0, r0);
  combine8(__uint_as_float(b0.x), __uint_as_float(b0.y), __uint_as_float(b1.x), __uint_as_float(b1.y), n, eps, m1, r1);
}

__device__ __forceinline__ void rows_fetch(uint32_t el, uint32_t xr, const uint8_t* src, uint32_t bar) {
  expect_tx_p(el, bar, 9216);
#pragma unroll 1
  for (int r = 0; r < 8; r++) bulk_load_p(el, xr + r * 1152, src + r * (DM * 4), 1152, bar);
}
__device__ __forceinline__ void rows_stats(uint32_t xr, uint4* dst, uint32_t tag, int lane) {
  float s[2] = {0.f, 0.f}, q[4] = {0.f, 0.f, 0.f, 0.f};
  const uint32_t a0 = xr + (lane >> 2) * 1152 + (((lane & 3) * 2) ^ (lane >> 2)) * 16;
  uint4 n0 = lds128(a0), n1 = lds128(a0 ^ 16);
#pragma unroll 1
  for (int e = 1; e <= 9; e++) {
    const uint32_t x[8] = {n0.x, n0.y, n0.z, n0.w, n1.x, n1.y, n1.z, n1.w};
    if (e < 9) { n0 = lds128(a0 + e * 128); n1 = lds128((a0 ^ 16) + e * 128); }
#pragma unroll
    for (int u = 0; u < 8; u++) {
      const float lo = blo(x[u]), hi = bhi(x[u]);
      s[u & 1] += lo + hi; q[(u & 1) * 2] = fmaf(lo, lo, q[(u & 1) * 2]); q[(u & 1) * 2 + 1] = fmaf(hi, hi, q[(u & 1) * 2 + 1]);
    }
  }
  const float sx = s[0] + s[1], sq = (q[0] + q[1]) + (q[2] + q[3]);
  const float m = qsum(sx) * (-1.f / DM), r = rsq_fast(fmaxf(fmaf(qsum(sq), 1.f / DM, -m * m), 0.f) + LN_EPS);
  if ((lane & 3) == 0) ll_st128(dst + (lane >> 2) * 2, m, r, tag);
}

__device__ __forceinline__ void poison(const Params& P, uint32_t el, uint32_t src, const CUtensorMap* m, int rb, int j, int lane) {
#pragma unroll 1
  for (int u = lane; u < 72; u += 32) sts128(src + u * 16, POISON, POISON, POISON, POISON);
  fence_async_s();
  __syncwarp();
#pragma unroll 1
  for (int u = 0; u < 16; u++) {
    __nanosleep(NAP);
    bulk_store_p(el, o_block(rb, u >> 3) + j * 9216 + (u & 7) * 1152, src, 1152);
    asm volatile("{\n.reg .pred P;\nsetp.ne.u32 P, %5, 0;\n@P cp.async.bulk.tensor.3d.global.shared::cta.tile.bulk_group [%0, {%2, %3, %4}], [%1];\n}" ::"l"(m), "r"(src), "r"((j & 6) * 72), "r"(rb * 64 + u * 4), "r"(j & 1), "r"(el) : "memory");
  }
}
__device__ __forceinline__ void mma16acc(float* c, const uint32_t* a, uint32_t b0, uint32_t b1) {
  asm volatile("mma.sync.aligned.m16n8k16.row.col.f32.bf16.bf16.f32 {%0,%1,%2,%3}, {%4,%5,%6,%7}, {%8,%9}, {%0,%1,%2,%3};"
               : "+f"(c[0]), "+f"(c[1]), "+f"(c[2]), "+f"(c[3]) : "r"(a[0]), "r"(a[1]), "r"(a[2]), "r"(a[3]), "r"(b0), "r"(b1));
}
template <int KS, int NG, int AK, int AH, int BK, int BG, class F> __device__ __forceinline__ void redo(float* acc, const uint8_t* pa, const uint8_t* pb, F f) {
#pragma unroll 1
  for (int k = 0; k < 36; k += KS) {
    uint32_t a[4 * KS], b[2 * KS][NG];
#pragma unroll 1
    for (int it = 0; it < (1 << 20); it++) {
      bool ok = true;
#pragma unroll
      for (int e = 0; e < 4 * KS; e++) a[e] = ldgpu32(pa + (e >> 1) * AK + (e & 1) * AH);
#pragma unroll
      for (int e = 0; e < 2 * KS * NG; e++) b[e / NG][e % NG] = ldca32(pb + (e / NG) * BK + (e % NG) * BG);
#pragma unroll
      for (int e = 0; e < 4 * KS; e++) ok = ok && a[e] != POISON;
      if (__all_sync(~0u, ok)) break;
    }
#pragma unroll
    for (int e = 0; e < KS; e++) f(a + 4 * e, k + e);
#pragma unroll
    for (int e = 0; e < KS * NG; e++) mma16acc(acc + 4 * (e % NG), a + 4 * (e / NG), movm(b[2 * (e / NG)][e % NG]), movm(b[2 * (e / NG) + 1][e % NG]));
    pa += 2 * KS * AK; pb += 2 * KS * BK;
  }
}
__device__ __forceinline__ bool any_nan(float a, float b) {
  return __any_sync(~0u, a != a || b != b);
}

__global__ void __cluster_dims__(2, 1, 1) __launch_bounds__(384, 1) mega_kernel(const __grid_constant__ Params P) {
  extern __shared__ __align__(1024) uint8_t smem_raw[];
  uint32_t ckk[8];
  (void)ckk;
  CKK(0);
  const uint32_t sb = smem_u32(smem_raw);
  const uint32_t bars = sb + SM_BAR;
  const int tid = threadIdx.x;
  int lane = tid & 31;
  const int wid = __shfl_sync(~0u, tid >> 5, 0);
  const int cl = blockIdx.x >> 1, tp = cl - 36, t7 = (tp * 37) >> 8;
  const int bid = (cl < 4 ? cl * 8 + 32 : tp < 0 ? cl - 4 : cl < 64 ? tp + t7 + 33 : cl) * 2 + (blockIdx.x & 1);
  if (bid >= NCTA) return;
  const int rb = bid & 15, j = bid >> 4;
  { const bool tr = (tid & 127) == 0 && tid < 256; const int w = tid >> 7; (void)tr; (void)w; TRC(tr, w, 0); }
  CKK(1);
  uint4 wv[5];
  const uint8_t* wsrc;
  {
    const int n8 = min(tid >> 3, 26), part = n8 / 9;
    const uint8_t* src = (const uint8_t*)P.wqkv + (8 * rb + (tid & 7)) * (3 * DM * 2) + (part * (DM - 72) + 72 * j + 8 * n8) * 2;
#pragma unroll
    for (int u = 0; u < SPL; u++) wv[u] = ldnc128_if(tid < 216, src + u * (128 * 3 * DM * 2));
    wsrc = src;
  }
  CKK(2);
  if (tid == 352) {
#pragma unroll
    for (int e = 0; e < 16; e++) mbar_init(bars + B_FULL + e * 8, (e >> 2) == 1 ? 16 : 1);
    mbar_init(bars + B_RES + 8, 8); mbar_init(bars + B_WT, 1); mbar_init(bars + B_WT + 8, 1); mbar_init(bars + B_IMG, 9);
    asm volatile("fence.mbarrier_init.release.cluster;" ::: "memory");
  }
  __syncthreads();

  if (wid >= 8) {
    reg_dealloc<40>();
    const uint32_t el = elect_one();
    const uint64_t pol = policy_evict_first();
    uint32_t* const fj = P.s->flags + FJ + j * 32;
    if (wid == 8) {
      if (lane == 0) {
        mbar_init(bars + B_RES, 1); mbar_init(bars + B_WOI, 1); mbar_init(bars + B_ZB, 1); mbar_init(bars + B_GATE3, 3); mbar_init(bars + B_Z1, 1); mbar_init(bars + B_LAG, 4);
#pragma unroll
        for (int e = B_RT; e < B_XS + 16; e += 8) mbar_init(bars + e, e >= B_AD && e < B_EVT ? 2 : (e >= B_EVT && e < B_RT1) || (e >= B_EA3 && e < B_XS) ? 4 : 1);
        asm volatile("fence.mbarrier_init.release.cluster;" ::: "memory");
        mbar_arrive(bars + B_IMG);
      }
      __syncwarp();
#pragma unroll 1
      for (int i = 0; i < 12; i++) if (el) prefetch_map(&P.act[0] + (i < 7 ? i : i - 12));
      const uint32_t epoch = ldcg32(fj + FJ_EP + rb);
      Cur c{0, 1};
      const uint32_t rk = bid & 1;
      uint32_t st, full;
      auto slot = [&](uint32_t bytes) {
        st = sb + c.s * ST_BYTES; full = bars + B_FULL + c.s * 8;
        mbar_wait(full, c.ph);
        expect_tx_p(el, full, bytes);
        mbar_wait(full - B_FULL + B_EMPTY, c.ph);
      };
#pragma unroll 1
      for (int L = 0; L < 2; L++) {
#pragma unroll 1
        for (int i = 0; i < 14; i++) {
          if (L == 0 && (i == 0 || i == 2 * SPL || i == 9)) {
            flag_wait(fj + (i == 9 ? FJ_WO : i == 2 * SPL ? FJ_WQ : FJ_WQ0), (epoch + 1) * 16);
            if (i == 9) flag_wait(P.s->flags + FJ + (j ^ 1) * 32 + FJ_WO, (epoch + 1) * 16);
            fence_async_g();
            TRC(el, 2, i == 9 ? 46 : i ? 47 : 45);
          }
          const uint32_t hb = i < 9 ? 13824 : i < 13 ? 18432 : 9216, o = ST_B + rk * (i < 9 ? 13824 : 18432);
          const uint8_t* src = i < 9 ? P.s->WQ + j * WQ_SL + i * 27648 + rk * 13824 : P.s->WO + ((j & 6) + rk) * WO_SL + (i - 9) * 18432;
          slot(2 * hb);
          bulk_mc_h(el, st + o, src, hb, full, true, pol);
          c.next();
        }
#pragma unroll 1
        for (int i = 0; i < 18; i++) {
          const int p = i >> 1, col = p == 4 ? (9 * j + ((j & 1) ? 0 : 8)) * 32 : (((9 * j + 1) >> 1) + (p < 4 ? p + 36 : p - 5)) * 64;
          if (i & 1) {
            slot(2 * ZB);
          } else {
            st = sb + c.s * ST_BYTES; full = bars + B_FULL + ((c.s + 1) & 3) * 8;
            mbar_wait(bars + B_EMPTY + c.s * 8, c.ph);
          }
          tma4d_mc(el, st + ST_B + rk * 18432, p == 4 ? &P.win : &P.win64, col, (i & 1) * 36 + rk * 18, full, pol);
          if (el && !(i & 1)) mbar_arrive(bars + B_FULL + c.s * 8);
          c.next();
        }
        TRC(el, 2, L * 16 + 6);
        flag_wait(fj + FJ_ZN + L, (epoch + 1) * 16);
        fence_async_g();
        TRC(el, 2, L * 16 + 7);
#pragma unroll 1
        for (int i = 0; i < 32; i++) {
          const uint8_t* src = z2_block(i, j) + rk * 18432;
          if (i >= 4) mbar_wait(bars + B_AD + c.s * 8, ((i >> 2) & 1) ^ 1);
          slot(ST_BYTES);
          bulk_mc_h(el, st + ST_B + rk * 18432, src, 18432, full, true, pol);
          tma3d_h(el, st, &P.wsp, i * 64, rb * 64, 0, full, true, pol);
          c.next();
        }
        mbar_wait(bars + B_Z1, L);
        fence_async_g();
        expect_tx_p(el, bars + B_ZB, 26624);
#pragma unroll 1
        for (int i = 0; i < 10; i++) {
          const int cb = i - 1 + j;
          if (i < 4) mbar_wait(bars + B_AD + c.s * 8, 1);
          slot(i ? ZB : 26624);
          if (i == 0) {
            bulk_load_h(el, st, z1_block(rb, 0, j), 26624, bars + B_ZB, true, pol);
            bulk_load_h(el, st + 26624, z1_block(rb, 1, j), 26624, full, true, pol);
          } else {
            tma2d_mc_h(el, st + ST_B + rk * 18432, &P.wout, (cb >= 9 ? cb - 9 : cb) * 64, 288 * j + rk * 144, full, true, pol);
          }
          c.next();
        }
      }
    } else if (wid < 11) {
      int w = wid - 9;
      uint32_t* const fr = P.s->flags + (rb * 2 + w) * 32;
      const uint32_t epoch = ldcg32(fr + FR_EP + j);
      const uint32_t ev = bars + B_EVT + w * EV_N * 8, t8 = (epoch + 1) * 8;
      Cur c{0, 1};
#pragma unroll 1
      for (int L = 0; L < 2; L++) {
        {
          uint32_t tag = t8;
          asm volatile("" : "+r"(tag));
          tag = (tag >> 2) - 1 + L;
          uint4* const xs = P.s->XST + (rb * 2 + w) * 128;
          if (L) {
            mbar_wait(ev + EV_PT * 8, 0);
            TRC(el, 3, w * 32 + 16);
            flag_release_p(el, fr + FR_X2);
            TRC(el, 3, w * 32 + 17);
          }
#pragma unroll 1
          for (int i = 0; i < 9; i++) {
            const uint32_t full = bars + B_FULLA + w * 32 + c.s * 8, dst = sb + c.s * ST_BYTES + w * 8192;
            if (L == 0 && i == 4) {
              mbar_wait(bars + B_WT + w * 8, 0);
              TRC(el && w == 0, 2, 37);
              rows_stats(sb + SM_STG + w * 9216, xs + 16 * j, tag, lane);
              TRC(el && w == 0, 2, 38);
            }
            const uint32_t src = sb + (L ? 2 * ST_BYTES + SM_WOI : SM_STG + w * 9216);
            if (i == 4) {
#pragma unroll
              for (int u = 0; u < 6; u++) sts128(src + u * 512 + lane * 16, POISON, POISON, POISON, POISON);
              fence_async_s();
              __syncwarp();
            }
            mbar_wait(bars + B_EMPTY + c.s * 8, c.ph);
            expect_tx_p(el, full, 8192);
            if (i < L) { flag_wait(fr + FR_X2, t8); fence_async_g(); }
            tma3d_h(el, dst, &P.act[L], i * 64, rb * 64, w, full, false, pol);
            TRC(el && i < L, 3, w * 32 + 18);
            c.next();
            if (i >= 4 && i < (L ? 5 : 8)) {
              int b = (rb * 2 + w) * 8 + j;
              asm volatile("" : "+r"(b));
              bulk_store_p(el, i == 4 ? (uint8_t*)P.s->HALO + b * 3072 : P.s->O + (b * 3 + i - 5) * 3072, src, 3072);
              if (i < 6) bulk_store_p(el, (i == 4 ? P.s->ST1 : P.s->ZST) + b * 64, src, 1024);
              if (i == 6) bulk_store_p(el, P.s->RT + b * 8, src, 64);
            }
            if (L == 0 && i == 3) rows_fetch(el, sb + SM_STG + w * 9216, P.xs[0] + (128 * rb + 16 * j + w) * (DM * 2), bars + B_WT + w * 8);
          }
          if (el) asm volatile("cp.async.bulk.commit_group;\ncp.async.bulk.wait_group 0;" ::: "memory");
          __syncwarp();
          if (L == 0) fence_gpu();
          const uint32_t tab = sb + L * (2 * ST_BYTES) + SM_XST + w * 512 + lane * 8;
          TRC(el, 3, w * 32 + L * 16 + 13);
#pragma unroll 1
          for (int it = 0; it < (1 << 22); it++) {
            const uint4 a = ll_ld128(xs + 2 * lane), b = ll_ld128(xs + 64 + 2 * lane);
            if (__all_sync(~0u, a.z == tag && b.z == tag)) { sts64(tab, a.x, a.y); sts64(tab + 256, b.x, b.y); break; }
          }
          __syncwarp();
          mbar_arrive_if(el, bars + B_XS + w * 8);
          TRC(el, 3, w * 32 + L * 16 + 14);
          if (w == 1) {
            mbar_wait(bars + B_XS, L);
            expect_tx_p(el, bars + B_RES, 18432);
            tma3d_h(el, sb + SM_STG, &P.res[L], (j & 6) * 72, rb * 64, j & 1, bars + B_RES, !L, pol);
          }
          if (L) flag_wait(fj + FJ_P4, t8 * 4);
        }
        int hp = rb * 2 + (j & 1);
        asm volatile("" : "+r"(w), "+r"(hp));
        uint32_t* const fo = P.s->flags + hp * 32 + L;
        {
          const uint8_t* src = o_block(0, hp) + w * 8192;
#pragma unroll 1
          for (int i = 0; i < 5; i++) {
            const uint32_t full = bars + B_FULLA + w * 32 + c.s * 8, dst = sb + c.s * ST_BYTES + w * 8192;
            const bool none = 2 * i + w > 8;
            mbar_wait(bars + B_EMPTY + c.s * 8, c.ph);
            expect_tx_p(el, full, none ? 0 : 8192);
            if (i == 0) {
              mbar_wait(ev + EV_O * 8, L);
              TRC(el, 3, w * 32 + L * 16 + 3);
              flag_add_p(el, fr + FR_O + L);
              TRC(el, 3, w * 32 + L * 16 + 4);
              flag_wait(fo + FR_O, t8);
              fence_async_g();
            }
            if (!none) bulk_load_h(el, dst, src + i * 16384, 8192, full, true, pol);
            TRC(el && i == 0, 3, w * 32 + L * 16 + 5);
            c.next();
          }
        }
        {
          expect_tx_p(lane < 9, bars + B_FA3 + (9 * w + lane) * 8, 8192);
          mbar_wait(ev + EV_X1 * 8, L);
          TRC(el, 3, w * 32 + L * 16 + 6);
          if (L) flag_add_p(el, fo + FR_X1); else flag_release_p(el, fo + FR_X1);
          mbar_arrive_if(el, bars + B_GATE3);
          TRC(el, 3, w * 32 + L * 16 + 7);
          mbar_arrive_if(lane < 2, bars + B_FULLA + w * 32 + ((c.s + lane) & 3) * 8);
#pragma unroll 1
          for (int kb = 0; kb < 9; kb++) {
            const int n = 9 * w + kb;
            const uint32_t dst = sb + ((n >> 1) & 3) * ST_BYTES + (n & 1) * 8192;
            if (kb == 0) { flag_wait(fr + FR_X1 + L, t8); fence_async_g(); }
            if (n >= 8) mbar_wait(bars + B_EA3 + (n - 8) * 8, L);
            tma3d_h(el, dst, &P.act[L + 1], kb * 64, rb * 64, w, bars + B_FA3 + n * 8, false, pol);
            TRC(el && kb == 0, 3, w * 32 + L * 16 + 8);
          }
          c.ph ^= ((c.s + 18) >> 2) & 1; c.s = (c.s + 18) & 3;
        }
        asm volatile("" : "+r"(lane), "+r"(w));
        expect_tx_p(el, bars + B_WT + w * 8, 2048);
#pragma unroll 1
        for (int r = 0; r < 8; r++)
          bulk_load_p(el, sb + SM_WT + w * 2176 + r * 272, (const uint8_t*)P.w_sp + (size_t)(128 * rb + 16 * j + 2 * r + w) * (SEQ * 2) + 30 * 128, 256, bars + B_WT + w * 8);
        float cv = (lane & 3) ? 0.f : -blo(ldnc16(P.b_sp + 128 * rb + 16 * j + 2 * (lane >> 2) + w));
        mbar_wait(bars + B_RT, L);
        mbar_wait(bars + B_WT + w * 8, L ^ 1);
        mbar_wait(ev + EV_Z1 * 8, L);
        const uint32_t ro = (w * 64 + 8 * j + (lane >> 2)) * 128, x0 = ((lane & 3) * 2) ^ (lane >> 2);
#pragma unroll 1
        for (int i = 0; i < 32; i++) {
          const bool tail = (i >> 1) == 4;
          const int kb = tail ? i + 22 : i < 8 ? i : i - 2;
          if (i == 8) mbar_wait(bars + B_RT1, L);
          if (!tail) mbar_wait(bars + B_FULL + c.s * 8, c.ph ^ 1);
#pragma unroll
          for (int e = 0; e < 2; e++) {
            const uint4 a = lds128(!tail ? sb + c.s * ST_BYTES + ro + ((x0 ^ e) << 4) : sb + SM_WT + w * 2176 + (lane >> 2) * 272 + (i - 8) * 128 + (lane & 3) * 32 + e * 16);
            const uint4 m = lds128(sb + SM_RT + 4096 + kb * 128 + (lane & 3) * 32 + e * 16);
            cv = fmaf(blo(a.x), blo(m.x), fmaf(bhi(a.x), bhi(m.x), fmaf(blo(a.y), blo(m.y), fmaf(bhi(a.y), bhi(m.y), cv))));
            cv = fmaf(blo(a.z), blo(m.z), fmaf(bhi(a.z), bhi(m.z), fmaf(blo(a.w), blo(m.w), fmaf(bhi(a.w), bhi(m.w), cv))));
          }
          if (!tail) {
            mbar_arrive_if(el, bars + B_AD + c.s * 8 + (__float_as_uint(cv) & P.zero));
            c.next();
          }
        }
        TRC(el, 3, w * 32 + L * 16 + 11);
        uint32_t tag = t8;
        asm volatile("" : "+r"(tag));
        tag = (tag >> 2) - 1 + L;
        cv = qsum(cv);
        uint2* const cs = (uint2*)(P.s->XST + (rb * 2 + w) * 128 + 1);
        if ((lane & 3) == 0) ll_st64(cs + 32 * j + (lane >> 2) * 4, __float_as_uint(cv), tag);
#pragma unroll 1
        for (int it = 0; it < (1 << 22); it++) {
          const uint2 a = ll_ld64(cs + 4 * lane), b = ll_ld64(cs + 128 + 4 * lane);
          if (__all_sync(~0u, a.y == tag && b.y == tag)) { sts32(sb + SM_CV + w * 256 + lane * 4, a.x); sts32(sb + SM_CV + w * 256 + 128 + lane * 4, b.x); break; }
        }
        __syncwarp();
        if (el) mbar_arrive(bars + B_CV + w * 8);
        TRC(el, 3, w * 32 + L * 16 + 12);
#pragma unroll 1
        for (int kb = 30; kb < 32; kb++) {
          mbar_wait(bars + B_FULL + c.s * 8, c.ph ^ 1);
          if (el) mbar_arrive(bars + B_AD + c.s * 8);
          c.next();
        }
        c.ph ^= ((c.s + 10) >> 2) & 1; c.s = (c.s + 10) & 3;
        if (L == 0) {
          mbar_wait(ev + EV_P4 * 8, 0);
          flag_add_p(el, fj + FJ_P4);
          flag_add_p(el, fr + FR_EP + j);
        }
      }
    } else {
      const uint32_t epoch = ldcg32(fj + FJ_EP + rb);
      if (SPL) {
        mbar_wait(bars + B_RES + 8, 0);
        TRC(el, 2, 41);
        flag_release_p(el, fj + FJ_WQ0);
        TRC(el, 2, 42);
      }
      mbar_wait(bars + B_IMG, 0);
      TRC(el, 2, 39);
      flag_release_p(el, fj + FJ_WQ);
      TRC(el, 2, 40);
#pragma unroll 1
      for (int L = 0; L < 2; L++) {
        auto wo_fetch = [&]() {
          expect_tx_p(el, bars + B_WOI, 5760);
          asm volatile("{\n.reg .pred P;\nsetp.ne.u32 P, %5, 0;\n@P cp.async.bulk.tensor.4d.shared::cluster.global.mbarrier::complete_tx::bytes [%0], [%1, {0, 0, %3, %4}], [%2];\n}" ::"r"(sb + SM_WOI), "l"(&P.wo8), "r"(bars + B_WOI), "r"(9 * j), "r"((9 * rb) >> 1), "r"(el) : "memory");
        };
        float* const csf = P.s->CSP + (NCTA + bid) * 216;
        if (L == 0) {
          flag_wait(fj + FJ_WQ, (epoch + 1) * 16);
          fence_async_g();
          expect_tx_p(el, bars + B_XRW, 13824);
          bulk_load_p(el, sb + ST_BYTES + SM_WOI, P.s->CSP + j * 16 * 216, 6912, bars + B_XRW);
          bulk_load_p(el, sb + 2 * ST_BYTES + SM_WOI, P.s->CSP + (j * 16 + 8) * 216, 6912, bars + B_XRW);
          wo_fetch();
          mbar_wait(bars + B_XRW, 0);
#pragma unroll 1
          for (int f = lane; f < 54; f += 32) {
            float s[4] = {0.f, 0.f, 0.f, 0.f};
#pragma unroll 4
            for (int r = 0; r < 16; r++) {
              const uint4 v = lds128(sb + ST_BYTES + SM_WOI + (r >> 3) * ST_BYTES + (r & 7) * 864 + f * 16);
              s[0] += __uint_as_float(v.x); s[1] += __uint_as_float(v.y); s[2] += __uint_as_float(v.z); s[3] += __uint_as_float(v.w);
            }
            sts128(sb + SM_CSQ + f * 16, __float_as_uint(s[0]), __float_as_uint(s[1]), __float_as_uint(s[2]), __float_as_uint(s[3]));
            stg128(csf + f * 4, __float_as_uint(s[0]), __float_as_uint(s[1]), __float_as_uint(s[2]), __float_as_uint(s[3]));
          }
          __syncwarp();
          mbar_arrive_if(el, bars + B_CSQ);
        } else {
#pragma unroll 1
          for (int u = 0; u < 4; u++) {
            const int w = u & 1;
            if (u < 2) {
              flag_wait(P.s->flags + (rb * 2 + w) * 32 + FR_X2, (epoch + 1) * 8);
              fence_async_g();
              TRC(el, 2, 48 + u);
              rows_fetch(el, sb + SM_STG + w * 9216, P.xs[1] + (128 * rb + 16 * j + w) * (DM * 2), bars + B_XRW + w * 8);
            } else {
              if (u == 2) {
                expect_tx_p(el, bars + B_CSQ, 864);
                bulk_load_p(el, sb + 2 * ST_BYTES + SM_CSQ, csf, 864, bars + B_CSQ);
              }
              mbar_wait(bars + B_XRW + w * 8, w ^ 1);
              TRC(el, 2, 48 + u);
              rows_stats(sb + SM_STG + w * 9216, P.s->XST + (rb * 2 + w) * 128 + 16 * j, epoch * 2 + 2, lane);
              TRC(el, 2, 50 + u);
            }
          }
        }
        if (L == 0) {
          TRC(el, 2, 43);
          mbar_wait(bars + B_WOI, 0);
          bulk_store_p(el, P.s->WO + j * WO_SL + ((9 * rb) >> 1) * 1152, sb + SM_WOI, 5760);
          publish_p(el, fj + FJ_WO);
          TRC(el, 2, 44);
          const uint8_t* sp = lane < 16 ? (const uint8_t*)P.w_in + (30 * lane + 50) * (FH * 4) + FH * 2 + lane * 256 : (const uint8_t*)P.w_sp + (60 * lane) * (SEQ * 2) + lane * 64;
          float sq = 0.f;
#pragma unroll 1
          for (int u = 0; u < 4; u++) {
            const uint4 y = ldnc128(sp + u * 16);
            const uint32_t x[4] = {y.x, y.y, y.z, y.w};
#pragma unroll
            for (int e = 0; e < 4; e++) sq = fmaf(blo(x[e]), blo(x[e]), fmaf(bhi(x[e]), bhi(x[e]), sq));
          }
#pragma unroll 1
          for (int o = 8; o; o >>= 1) sq += __shfl_xor_sync(~0u, sq, o);
          sq *= lane < 16 ? 2.f * GA * GA * DM / 512.f : C0S * C0S * SEQ / 512.f;
          asm("sqrt.approx.f32 %0, %0;" : "+f"(sq));
          const float o0 = __shfl_sync(~0u, sq, 0), o1 = __shfl_sync(~0u, sq, 16);
          const float p2 = __uint_as_float(min(__float_as_uint(o0) & 0x7f800000u, 0x7e000000u)) * OFK, off = -p2 - fminf(OFA, 0.5f * p2);
          if (el) sts64(sb + SM_OFF, pack2(off, off), min(__float_as_uint(o1) & 0x7f800000u, 0x7e000000u) | 0x00400000u);
        }
        if (el) mbar_arrive(bars + B_GATE3);
        const uint32_t tag = epoch * 2 + L + 1;
        asm volatile("" : "+r"(lane));
        mbar_wait(bars + B_EVT + EV_ZN * 8, L);
        mbar_wait(bars + B_EVT + (EV_N + EV_ZN) * 8, L);
        flag_release_p(el, fj + FJ_ZN + L);
        TRC(el, 2, L * 16 + 8);
        {
          uint4 v[4];
#pragma unroll 1
          for (int it = 0; it < (1 << 22); it++) {
            bool ok = true;
#pragma unroll
            for (int u = 0; u < 4; u++) { v[u] = ll_ld128(P.s->ZST + (rb * 2 + ((lane >> 1) & 1)) * 512 + ((lane & 1) * 4 + u) * 64 + 8 * j + (lane >> 2)); ok = ok && v[u].z == tag; }
            if (__all_sync(~0u, ok)) break;
          }
          float mean = __uint_as_float(v[0].x) + __uint_as_float(v[1].x) + __uint_as_float(v[2].x) + __uint_as_float(v[3].x), M2 = 0.f;
          mean = (mean + __shfl_xor_sync(~0u, mean, 1)) * 0.125f;
#pragma unroll
          for (int u = 0; u < 4; u++) { const float d = __uint_as_float(v[u].x) - mean; M2 += fmaf(288.f * d, d, __uint_as_float(v[u].y)); }
          M2 += __shfl_xor_sync(~0u, M2, 1);
          const float rs = blo(pack2(rsq_fast(fmaf(M2, 1.f / FH, 4.f * GA * GA * LN_EPS)), 0.f));
          if (!(lane & 1)) ll_st64(P.s->RT + 128 * rb + 16 * j + (lane >> 1), pack2(rs, rs * mean), tag);
        }
        TRC(el, 2, L * 16 + 10);
#pragma unroll 1
        for (int b = 0; b < 8; b++) {
          uint4 v[4];
#pragma unroll 1
          for (int it = 0; it < (1 << 22); it++) {
            bool ok = true;
#pragma unroll
            for (int u = 0; u < 4; u++) { v[u] = ll_ld128((const uint4*)P.s->RT + b * 128 + u * 32 + lane); ok = ok && v[u].y == tag && v[u].w == tag; }
            if (__all_sync(~0u, ok)) break;
          }
#pragma unroll
          for (int u = 0; u < 4; u++) {
            const uint32_t rt = sb + SM_RT + b * 512 + u * 128, ro = (lane >> 3) * 32 + (lane & 3) * 8 + ((lane >> 2) & 1) * 2;
            sts32(rt + 4096 + lane * 4, __byte_perm(v[u].x, v[u].z, 0x7632));
            asm volatile("st.shared.u16 [%0], %1;\nst.shared.u16 [%0 + 4], %2;" ::"r"(rt + ro), "h"((uint16_t)v[u].x), "h"((uint16_t)v[u].z) : "memory");
          }
          __syncwarp();
          if (el && (b == 1 || b == 7)) mbar_arrive(bars + (b == 1 ? B_RT : B_RT1));
          TRC(el && b < 2, 2, L * 16 + 11 + b);
        }
        TRC(el, 2, L * 16 + 9);
        mbar_wait(bars + B_EVT + EV_Z1 * 8, L);
        mbar_wait(bars + B_EVT + (EV_N + EV_Z1) * 8, L);
        fence_gpu();
        if (el) mbar_arrive(bars + B_Z1);
        if (L == 0) {
          flag_add_p(el, fj + FJ_EP + rb);
          __nanosleep(NAP0);
          poison(P, el, sb + SM_STG + 17152, &P.psn, rb, j, lane);
          if (el) asm volatile("cp.async.bulk.commit_group;\ncp.async.bulk.wait_group 0;" ::: "memory");
          __syncwarp();
          fence_gpu();
        }
      }
    }
  } else {
    CKK(3);
    uint8_t* const wdst = P.s->WQ + j * WQ_SL + rb * 3456 + tid * 16;
#pragma unroll
    for (int u = 0; u < SPL; u++) stg128_if(tid < 216, wdst + u * (16 * 3456), wv[u].x, wv[u].y, wv[u].z, wv[u].w);
    __syncwarp();
    if (lane == 0) mbar_arrive(bars + B_RES + 8);
    CKK(4);
    auto repack2 = [&]() {
#pragma unroll
      for (int u = SPL; u < 5; u++) stg128_if((u < 4 || rb < 8) && tid < 216, wdst + u * (16 * 3456), wv[u].x, wv[u].y, wv[u].z, wv[u].w);
      float s[8];
#pragma unroll
      for (int e = 0; e < 8; e++) s[e] = 0.f;
#pragma unroll
      for (int u = 0; u < 5; u++) {
        uint32_t x[4] = {wv[u].x, wv[u].y, wv[u].z, wv[u].w};
        asm volatile("" : "+r"(x[0]), "+r"(x[1]), "+r"(x[2]), "+r"(x[3]));
#pragma unroll
        for (int e = 0; e < 4; e++) { s[2 * e] += blo(x[e]); s[2 * e + 1] += bhi(x[e]); }
      }
#pragma unroll
      for (int m = 4; m; m >>= 1) {
#pragma unroll
        for (int e = 0; e < m; e++) s[e] = ((tid & m) ? s[e + m] : s[e]) + __shfl_xor_sync(~0u, (tid & m) ? s[e] : s[e + m], m);
      }
      stg32_if(tid < 216, P.s->CSP + bid * 216 + tid, __float_as_uint(s[0]));
      __syncwarp();
      if (lane == 0) mbar_arrive(bars + B_IMG);
    };
    reg_alloc<232>();
    CKK(5);
#pragma unroll
    for (int v = SPL; v < 5; v++) wv[v] = ldnc128_if(tid < 216 && (v < 4 || rb < 8), wsrc + v * (128 * 3 * DM * 2));
    repack2();
    CKK(6);
    const int w = wid >> 2, q = wid & 3;
    int g = lane >> 2, t = lane & 3;
    const uint32_t ev = bars + B_EVT + w * EV_N * 8;
    const bool tr = (tid & 127) == 0;
    (void)tr;
    Cur c{0, 0};
    const uint32_t ebar = mapa(bars + B_EMPTY, (bid & 1) ^ (lane & 1));
    auto release = [&](uint32_t s, uint32_t dep = 0) { mbar_arrive_cluster_if(lane < 2, ebar + s * 8 + dep); };
    auto release_if = [&](bool on, uint32_t s) { mbar_arrive_cluster_if(lane < 2 && on, ebar + s * 8); };
    uint32_t ia = 0;
    auto wait_ab = [&]() { mbar_wait_c(bars + B_FULL + c.s * 8, c.ph); mbar_wait_c(bars + B_FULLA + w * 32 + c.s * 8, (ia >> 2) & 1); ia++; };

    auto yield_done = [&]() { if (w == 0 && lane == 0) mbar_arrive(bars + B_LAG); };
    auto signal = [&](int e) { __syncwarp(); mbar_arrive_if(lane == 0, ev + e * 8); };

    const uint32_t epoch = ldcg32(P.s->flags + (rb * 2 + w) * 32 + FR_EP + j);
    TRC(tr, w, 1);
    CKK(7);
    if (PAD && P.zero) {
#pragma unroll
      for (int i = 0; i < PAD; i++) asm volatile("st.shared.u32 [%0], %1;" ::"r"(sb + i * 20), "r"(tid) : "memory");
    }
    CKK_OUT;

#pragma unroll 1
    for (int L = 0; L < 2; L++) {
      const int tb = 2 + L * 24;
      asm volatile("" : "+r"(lane), "+r"(g), "+r"(t));
      (void)tb;
      ia = 0;
      const uint32_t tag = epoch * 2 + L + 1;
      uint32_t aoff = (w * 64 + q * 16 + (lane & 15)) * 128 + (((lane >> 4) ^ (lane & 7)) << 4);
      {
        uint32_t Pk[27][2];
        float sc0, sc1;
        const uint32_t att = sb + w * 8192 + q * 2048 + lane * 4;
        uint4* hp = P.s->HALO + ((((rb - (q == 0)) * 2 + w) * 8 + j) * 6) * 32 + lane;
        uint8_t* od = o_block(rb, w) + (9 * j) * 1024 + (2 * q) * 128 + lane * 4;
        ACLK_INIT;
        {
          float acc[108];
#pragma unroll
          for (int i = 0; i < 108; i++) acc[i] = 0.f;
          uint32_t prev = 0;
#pragma unroll 1
          for (int kb = 0; kb < 9; kb++) {
            wait_ab();
            if (w == 1 && kb == 9 - LAG1) mbar_wait_c(bars + B_LAG, L);
            TRC(tr && kb == 0, w, tb + 0);
            MCLK(kb == 0, 0);
            PCLK(kb * 4);
            const uint32_t st = sb + c.s * ST_BYTES;
            uint64_t da = dsc2(dlo(st + w * 8192, 16), 0, 0x40000040u + P.zero), db = dsc2(dlo(st + ST_B, 3456), 0, 8 ^ P.zero);
            wgmma_fence();
#pragma unroll
            for (int kk = 0; kk < 4; kk++) {
              wgmma_ss_n216(acc, da, db, 1);
              dadd(da, 2); dadd(db, 432);
              if (kk == 0) { wgmma_commit(); wgmma_wait<1>(); release_if(kb > 0, prev); }
            }
            wgmma_commit();
            if (kb == 8) yield_done();
            PCLK(kb * 4 + 1);
            PCLK(kb * 4 + 2);
            PCLK(kb * 4 + 3);
            prev = c.s; c.next();
          }
          const uint32_t cs = sb + prev * ST_BYTES + SM_CSQ + t * 8;
          mbar_wait_c(bars + B_CSQ, L);
          mbar_wait_c(bars + B_XS + w * 8, L);
          const float2 n0 = lds64f(sb + prev * ST_BYTES + SM_XST + w * 512 + (16 * q + g) * 8), n1 = lds64f(sb + prev * ST_BYTES + SM_XST + w * 512 + (16 * q + g + 8) * 8);
          const float m0 = n0.x, r0 = n0.y, m1 = n1.x, r1 = n1.y;
          float2 cv[27];
#pragma unroll
          for (int G = 0; G < 27; G++) cv[G] = lds64f(cs + G * 32);
          PCLK(36);
          wgmma_wait<0>();
          PCLK(37);
          {
            uint32_t dep = P.zero & __float_as_uint(m0) & __float_as_uint(m1);
#pragma unroll
            for (int G = 0; G < 27; G++) dep &= __float_as_uint(cv[G].x);
            release(prev, dep);
          }
          TRC(tr, w, tb + 1);
          MCLK(1, 1);
          ACLK(0);
#pragma unroll
          for (int G = 9; G < 27; G++) Pk[G][1] = pack2(fmaf(m1, cv[G].x, acc[4 * G + 2]) * r1, fmaf(m1, cv[G].y, acc[4 * G + 3]) * r1);
          if (q < 3) {
#pragma unroll
            for (int i = 0; i < 18; i++) sts32(att + (i >> 4) * ST_BYTES + (i & 15) * 128, Pk[9 + i][1]);
          } else if (rb < 15) {
#pragma unroll
            for (int i = 0; i < 6; i++) ll_st128(hp + i * 32, __uint_as_float(Pk[9 + 3 * i][1]), __uint_as_float(Pk[10 + 3 * i][1]), tag, __uint_as_float(Pk[11 + 3 * i][1]));
          }
#pragma unroll
          for (int G = 0; G < 27; G++) {
            if (G < 9) {
              Pk[G][0] = pack2(fmaf(m0, cv[G].x, acc[4 * G]), fmaf(m0, cv[G].y, acc[4 * G + 1]));
              Pk[G][1] = pack2(fmaf(m1, cv[G].x, acc[4 * G + 2]), fmaf(m1, cv[G].y, acc[4 * G + 3]));
            } else {
              Pk[G][0] = pack2(fmaf(m0, cv[G].x, acc[4 * G]) * r0, fmaf(m0, cv[G].y, acc[4 * G + 1]) * r0);
            }
          }
          sc0 = r0 * (0.23570226039551584f * 1.4426950408889634f); sc1 = r1 * (0.23570226039551584f * 1.4426950408889634f);
        }
        ACLK(1);
        constexpr int GA_[4] = {0, 2, 4, 7}, GB_[4] = {1, 3, 5, 8}, GC_[4] = {2, 4, 6, 6};
        float S1[4][4], S2[4][4];
        uint32_t qa[4][2], qc[4][2];
#pragma unroll
        for (int h = 0; h < 4; h++) {
#pragma unroll
          for (int r = 0; r < 2; r++) {
            qa[h][r] = (h == 0 || h == 3 || t >= h) ? Pk[GA_[h]][r] : 0u;
            qc[h][r] = (h == 3 ? t == 3 : t <= h) ? Pk[GC_[h]][r] : 0u;
          }
          mma16(S1[h], qa[h][0], qa[h][1], Pk[GB_[h]][0], Pk[GB_[h]][1], Pk[9 + GA_[h]][0], Pk[9 + GB_[h]][0]);
          mma16(S2[h], qa[h][0], qa[h][1], Pk[GB_[h]][0], Pk[GB_[h]][1], Pk[9 + GA_[h]][1], Pk[9 + GB_[h]][1]);
        }
#pragma unroll
        for (int h = 0; h < 4; h++) {
          mma8(S1[h], qc[h][0], qc[h][1], Pk[9 + GC_[h]][0]);
          mma8(S2[h], qc[h][0], qc[h][1], Pk[9 + GC_[h]][1]);
        }
        uint32_t V1[9], V2[9];
#pragma unroll
        for (int i = 0; i < 9; i++) { V1[i] = movm(Pk[18 + i][0]); V2[i] = movm(Pk[18 + i][1]); }
        const bool remote = q == 0 && rb > 0;
        uint4 hv[6];
#pragma unroll
        for (int i = 0; i < 6; i++) hv[i] = make_uint4(0u, 0u, tag, 0u);
        if (remote) {
#pragma unroll
          for (int i = 0; i < 6; i++) hv[i] = ll_ld128(hp + i * 32);
        }
        const bool up0 = 2 * t > g, up1 = 2 * t + 1 > g;
        const uint32_t mup = (up0 ? 0xffffu : 0u) | (up1 ? 0xffff0000u : 0u);
        auto finish = [&](const float (&x0)[4], const float (&x1)[4], uint32_t ma, const uint32_t (&Vb)[9], int hi) {
          uint32_t pa[4], pb[4];
          float rs[4];
#pragma unroll
          for (int h = 0; h < 4; h++) {
            const float m = qmax(fmaxf(x0[h], x1[h]));
            const uint32_t p = pack2(ex2(x0[h] - m), ex2(x1[h] - m));
            pa[h] = p & ma; pb[h] = p & ~ma;
          }
#pragma unroll
          for (int h = 0; h < 4; h += 2) {
            float R[4];
            mma16(R, pa[h], pa[h + 1], pb[h], pb[h + 1], 0x3f803f80u, 0x3f803f80u);
            rs[h] = rcp_fast(R[0]); rs[h + 1] = rcp_fast(R[2]);
          }
#pragma unroll
          for (int i = 0; i < 9; i++) {
            const int h = 4 * i / 9, e = (h & 1) * 2;
            const bool split = i == 2 || i == 4 || i == 6, nx = split && 2 * t >= i;
            float O[4], N[4];
            mma16(O, pa[h & 2], pa[h | 1], pb[h & 2], pb[h | 1], V1[i], Vb[i]);
            if (i == 4) mma16(N, pa[2], pa[3], pb[2], pb[3], V1[i], Vb[i]); else { N[0] = O[2]; N[1] = O[3]; }
            const float r = nx ? rs[h + (split ? 1 : 0)] : rs[h];
            stg32(od + i * 1024 + hi * 128, pack2((nx ? N[0] : O[e]) * r, (nx ? N[1] : O[e + 1]) * r));
          }
        };
        {
          float x0[4], x1[4];
#pragma unroll
          for (int h = 0; h < 4; h++) { x0[h] = (up0 ? S1[h][2] : S2[h][2]) * sc1; x1[h] = (up1 ? S1[h][3] : S2[h][3]) * sc1; }
          finish(x0, x1, mup, V2, 1);
        }
        ACLK(2);
        bar_sync(1 + w, 128);
        uint32_t H[18];
        if (q > 0) {
#pragma unroll
          for (int i = 0; i < 18; i++) H[i] = lds32(att - 2048 + (i >> 4) * ST_BYTES + (i & 15) * 128);
        } else {
#pragma unroll 1
          for (int it = 0; it < (1 << 20); it++) {
            bool ok = true;
#pragma unroll
            for (int i = 0; i < 6; i++) ok = ok && hv[i].z == tag;
            if (__all_sync(~0u, ok)) break;
#pragma unroll
            for (int i = 0; i < 6; i++) hv[i] = ll_ld128(hp + i * 32);
          }
#pragma unroll
          for (int i = 0; i < 6; i++) { H[3 * i] = hv[i].x; H[3 * i + 1] = hv[i].y; H[3 * i + 2] = hv[i].w; }
        }
        float S0[4][4];
#pragma unroll
        for (int h = 0; h < 4; h++) {
          mma16(S0[h], qa[h][0], qa[h][1], Pk[GB_[h]][0], Pk[GB_[h]][1], H[GA_[h]], H[GB_[h]]);
        }
#pragma unroll
        for (int h = 0; h < 4; h++) mma8(S0[h], qc[h][0], qc[h][1], H[GC_[h]]);
        uint32_t V0[9];
#pragma unroll
        for (int i = 0; i < 9; i++) V0[i] = movm(H[9 + i]);
        ACLK(3);
        {
          const bool nohalo = (rb | q) == 0;
          const float b0 = up0 && nohalo ? -INFINITY : 0.f, b1 = up1 && nohalo ? -INFINITY : 0.f;
          float x0[4], x1[4];
#pragma unroll
          for (int h = 0; h < 4; h++) { x0[h] = fmaf(up0 ? S0[h][0] : S1[h][0], sc0, b0); x1[h] = fmaf(up1 ? S0[h][1] : S1[h][1], sc0, b1); }
          finish(x0, x1, ~mup, V0, 0);
        }
        ACLK(4);
        signal(EV_O);
        ACLK_OUT;
        TRC(tr, w, tb + 2);
        MCLK(1, 2);
      }
      {
        float acc[36];
        const int hw = rb * 2 + (j & 1), js = (j & 6) + w;
        const uint32_t xt = sb + SM_STG + (16 * q + (lane & 15)) * 288 + (9 * w + (lane >> 4)) * 16, eye = (g >> 1) == t ? 0x3f80u << (g & 1) * 16 : 0u;
        uint32_t xm = xt ^ ((lane & 4) << 2), xl = sb + SM_STG + (2 * q + w) * 2304;
        uint32_t xl0 = xl + (lane >> 4) * 288 + (lane & 15) * 16, xl1 = xl + ((lane >> 1) & 7) * 288 + 256 + ((lane ^ (lane >> 3)) & 1) * 16;
        uint8_t* xd0 = P.xs[L + 1] + (128 * rb + 32 * q + 16 * w + (j & 1)) * (DM * 2) + (j & 6) * 144;
        uint8_t* xd1 = xd0 + (lane >> 1) * (DM * 4) + 256 + (lane & 1) * 16;
        xd0 += (lane >> 4) * (DM * 4) + (lane & 15) * 16;
        asm volatile("" : "+r"(xm), "+r"(xl0), "+r"(xl1), "+l"(xd0), "+l"(xd1));
        mbar_wait_c(bars + B_RES, L);
        TRC(tr, w, tb + 21);
#pragma unroll
        for (int u = 0; u < 5; u++) {
          uint32_t r[4];
          ldsm4(r, xt + u * 32);
          widen(acc + 8 * u, r[0], r[1], eye);
          if (u < 4) widen(acc + 8 * u + 4, r[2], r[3], eye);
        }
        uint32_t prev = 0;
#pragma unroll 1
        for (int u = 0; u < 5; u++) {
          const uint32_t st = sb + c.s * ST_BYTES;
          uint64_t da = dsc2(dlo(st, 1024), 0, 8 + P.zero), db = dsc2(dlo(st + ST_B + w * 18432, 1152), 0, 8 ^ P.zero);
          mbar_wait_c(bars + B_FULL + c.s * 8, c.ph); mbar_wait_c(bars + B_FULLA + c.s * 8, (ia >> 2) & 1);
          TRC(tr && u == 0, w, tb + 3);
          MCLK(u == 0, 3);
          wgmma_fence();
#pragma unroll
          for (int kk = 0; kk < 4; kk++) { wgmma_ss_n72(acc, da, db, 1); dadd(da, 128); dadd(db, 144); }
          wgmma_commit();
          wgmma_wait<1>();
          release_if(u > 0, prev);
          mbar_wait_c(bars + B_FULLA + 32 + c.s * 8, (ia >> 2) & 1);
          ia++;
          if (u == 4) break;
          wgmma_fence();
#pragma unroll
          for (int kk = 4; kk < 8; kk++) { wgmma_ss_n72(acc, da, db, 1); dadd(da, 128); dadd(db, 144); }
          wgmma_commit();
          prev = c.s; c.next();
        }
        RCLK_INIT;
        wgmma_wait<0>();
        RCLK(0);
        release(c.s);
        c.next();
        if (__builtin_expect(any_nan(acc[0], acc[2]), 0)) {
          SLOW(L);
          const uint8_t* xr = P.xs[L] + (128 * rb + 32 * q + 2 * g + (j & 1)) * (DM * 2) + js * 144 + t * 4;
#pragma unroll
          for (int i = 0; i < 9; i++) widen(acc + 4 * i, ldgpu32(xr + i * 16), ldgpu32(xr + i * 16 + DM * 32), eye);
          redo<KS2, 9, 1024, 128, 1152, 128>(acc, o_block(rb, j & 1) + q * 256 + lane * 4, P.s->WO + js * WO_SL + lane * 4, [](uint32_t*, int) {});
        }
        TRC(tr && P5TRACE != 5, w, tb + 4);
        MCLK(1, 4);
#pragma unroll
        for (int u = 0; u < 4; u++)
          stsm4(xm + u * 32, pack2(acc[8 * u], acc[8 * u + 1]), pack2(acc[8 * u + 2], acc[8 * u + 3]), pack2(acc[8 * u + 4], acc[8 * u + 5]), pack2(acc[8 * u + 6], acc[8 * u + 7]));
        asm volatile("stmatrix.sync.aligned.m8n8.x2.shared.b16 [%0], {%1,%2};" ::"r"(xm + 128), "r"(pack2(acc[32], acc[33])), "r"(pack2(acc[34], acc[35])) : "memory");
        auto stats = [&]() {
          float s0 = 0.f, s1 = 0.f, q0 = 0.f, q1 = 0.f;
#pragma unroll
          for (int i = 0; i < 36; i++) {
            if (i & 2) { s1 += acc[i]; q1 = fmaf(acc[i], acc[i], q1); } else { s0 += acc[i]; q0 = fmaf(acc[i], acc[i], q0); }
          }
          s0 = qsum(s0); s1 = qsum(s1); q0 = qsum(q0); q1 = qsum(q1);
          const float ss = t ? s1 : s0, m = ss * (1.f / 72.f);
          ll_st128_if(t < 2, P.s->ST1 + (hw * 8 + js) * 64 + 16 * q + 8 * t + g, m, fmaxf((t ? q1 : q0) - ss * m, 0.f), tag);
        };
        stats();
        RCLK(1);
        bar_sync(8 + q, 64);
        RCLK(2);
#pragma unroll
        for (int u = 0; u < 5; u++) {
          const uint4 v = lds128(u < 4 ? (xl0 ^ ((u & 2) << 3)) + u * 576 : xl1);
          stg128_if(u < 4 || lane < 16, u < 4 ? xd0 + u * (DM * 8) : xd1, v.x, v.y, v.z, v.w);
        }
        RCLK(3);
        signal(EV_X1);
        RCLK(4);
        RCLK(5);
        TRC(tr, w, tb + 5);
        RCLK(6);
        RCLK_OUT;
      }
      uint4 zk[4];
      {
        uint32_t xA[36][4];
        float acc[32];
        uint32_t s0, one, off2;
        uint8_t *z1d, *zd;
        uint64_t db;
        auto bwait = [&](uint32_t dhi, bool skip) {
          s0 = c.s;
          c.next();
          if (!skip) mbar_wait_c(bars + B_FULL + c.s * 8, c.ph);
          db = dsc2(dlo(sb + s0 * ST_BYTES + ST_B, 512) - 3, 0, dhi); one = (c.s ^ P.zero) & 1;
        };
        auto mma = [&](int kk, int pp, bool hand) {
          wgmma_rs_n64(acc, xA[kk], dat(db, (kk / 18) * ST_BYTES + (kk % 18) * 2048 + 48, one), kk != 0);
          if (kk == pp && hand) bar_arrive(7 - w, 256);
          if (kk == 17 || kk == 35) wgmma_commit();
          if (kk == RL3) { wgmma_commit(); wgmma_wait<1>(); release(s0); }
        };
        {
          bwait(0x40000040u, false);
          mbar_wait_c(bars + B_GATE3, L);
          float mean0, mean1, rs0, rs1;
          stat_get(P.s->ST1 + ((rb * 2 + w) * 8 + 2 * t) * 64 + 16 * q + g, tag, 72.f, LN_EPS, mean0, rs0, mean1, rs1);
          const uint32_t ns0 = pack2(GA * rs0, GA * rs0), ns1 = pack2(GA * rs1, GA * rs1);
          const uint32_t nb0 = pack2(-mean0 * blo(ns0), -mean0 * blo(ns0)), nb1 = pack2(-mean1 * blo(ns1), -mean1 * blo(ns1));
          const uint32_t al = sb + (aoff & 8191);
#pragma unroll
          for (int kb = 0; kb <= 9; kb++) {
            if (kb < 9) {
              mbar_wait_c(bars + B_FA3 + (9 * w + kb) * 8, L);
              TRC(tr && kb == 0, w, tb + 6);
              MCLK(kb == 0, 5);
              if (kb == 0) SCLK(0);
              QCLK(kb);
              const uint32_t at = al + (w ? (((kb + 1) >> 1) & 3) * ST_BYTES + ((kb + 1) & 1) * 8192 : ((kb >> 1) & 3) * ST_BYTES + (kb & 1) * 8192);
#pragma unroll
              for (int kk = 4 * kb; kk < 4 * kb + 4; kk++) ldsm4(xA[kk], at ^ ((kk & 3) << 5));
            }
            if (kb == 0) continue;
            const uint32_t dep = xA[4 * kb - 4][0] & xA[4 * kb - 3][0] & xA[4 * kb - 2][0] & xA[4 * kb - 1][0] & P.zero;
            mbar_arrive_if(lane == 0 && (kb == 1 || w == 0), bars + B_EA3 + (9 * w + kb - 1) * 8 + dep);
#pragma unroll
            for (int kk = 4 * kb - 4; kk < 4 * kb; kk++) {
#pragma unroll
              for (int e = 0; e < 4; e++) xA[kk][e] = hfma2(xA[kk][e], (e & 1) ? ns1 : ns0, (e & 1) ? nb1 : nb0);
            }
            wgmma_fence();
#pragma unroll
            for (int kk = 4 * kb - 4; kk < 4 * kb; kk++) mma(kk, PP30, w);
          }
          off2 = lds32(sb + SM_OFF);
          z1d = z1_block(rb, w, j) + (tid & 127) * 16;
          zd = z2_block(2 * rb + (q >> 1), j) + (4 * (q & 1) + w) * 4608 + ((g & 3) * 2 + (g >> 2)) * 16 + t * 4;
          asm volatile("" : "+l"(z1d), "+l"(zd));
          wgmma_wait<0>();
          if (__builtin_expect(any_nan(acc[0], acc[2]), 0)) {
            SLOW(2 + L);
            uint4* const rd = P.s->RD + bid * (36 * 256) + tid;
            const uint8_t* xr = P.xs[L + 1] + (128 * rb + 32 * q + 2 * g + w) * (DM * 2) + t * 4;
#pragma unroll
            for (int i = 0; i < 32; i++) acc[i] = 0.f;
            redo<KS3, 8, 16, DM * 32, FH * 32, 16>(acc, xr, (const uint8_t*)P.w_in + g * (FH * 4) + (((9 * j + 1) >> 1) + 36) * 128 + t * 4,
                                              [&](uint32_t* a, int k) {
#pragma unroll
                                                for (int e = 0; e < 4; e++) a[e] = hfma2(a[e], (e & 1) ? ns1 : ns0, (e & 1) ? nb1 : nb0);
                                                stg128(rd + k * 256, a[0], a[1], a[2], a[3]);
                                              });
#pragma unroll
            for (int k = 0; k < 36; k++) { const uint4 v = ldcg128(rd + k * 256); xA[k][0] = v.x; xA[k][1] = v.y; xA[k][2] = v.z; xA[k][3] = v.w; }
          }
        }
        float sm[4] = {0.f, 0.f, 0.f, 0.f}, qq[4] = {0.f, 0.f, 0.f, 0.f};
        auto gelu = [&](auto nz2, bool out) {
          constexpr int NZ2 = nz2.value, R = 8 - NZ2, N = 8, D = NZ2 == 8 ? GM2 : NZ2 ? GMM : GM1;
          float th[32], gb = GB;
          uint32_t qa = 0, qb = 0;
          auto head = [&](int G) {
#pragma unroll
            for (int e = 0; e < 4; e++) { const float v = acc[4 * G + e]; th[4 * G + e] = tanh_fast(v * fmaf(v, v, gb)); }
          };
#pragma unroll
          for (int i = 0; i < D; i++) head((i + R) & 7);
#pragma unroll
          for (int i = 0; i < N; i++) {
            const int G = (i + R) & 7;
            if (i + D < N) head((i + D + R) & 7);
            float* z = acc + 4 * G;
#pragma unroll
            for (int e = 0; e < 4; e++) z[e] = fmaf(z[e], th[4 * G + e], z[e]);
            uint32_t pa = pack2(z[0], z[1]), pb = pack2(z[2], z[3]), tok;
            if (i < NZ2) {
#pragma unroll
              for (int e = 0; e < 4; e++) { sm[e] += z[e]; qq[e] = fmaf(z[e], z[e], qq[e]); }
              pa = hsub2(pa, off2); pb = hsub2(pb, off2);
              stg32(zd + i * 128, pa); stg32(zd + i * 128 + 9216, pb);
              tok = pa ^ pb ^ __float_as_uint(qq[1]);
            } else {
              if (NZ2 && G == 3) sts128(sb + SM_STG + tid * 16, qa, qb, pa, pb);
              else if (G & 1) stg128_if(out, z1d + (G >> 1) * 2048 + (NZ2 ? 24576 : 0), qa, qb, pa, pb);
              if ((G & 1) && !NZ2) zk[G >> 1] = make_uint4(qa, qb, pa, pb);
              qa = pa; qb = pb;
              tok = pa ^ pb;
            }
            gb = __uint_as_float(tok * P.zero + __float_as_uint(GB));
          }
        };
        auto done = [&](int p) {
          wgmma_wait<0>();
          release(c.s);
          c.next();
          TRC(tr && p == 4, w, tb + 7);
          TRC(tr && p == 8, w, tb + 11);
          MCLK(p == 8, 6);
          SCLK(2 * p + 1);
          QCLK(10 + 3 * p);
        };
        auto pass = [&](int p, uint32_t dhi) {
          SCLK(2 * p);
          QCLK(8 + 3 * p);
          bwait(dhi, w);
          bar_sync(6 + w, 256);
          TRC(tr && p == 5, w, tb + 10);
          wgmma_fence();
#pragma unroll
          for (int kk = 0; kk < 36; kk++) mma(kk, PP3, w == 0 || p < 8);
          done(p);
        };
        done(0);
#pragma unroll 1
        for (int p = 1; p < 5; p++) {
          gelu(Int<8>{}, true);
          zd += 1024;
          pass(p, p == 4 ? 0x80000040u : 0x40000040u);
        }
        gelu(Int<4>{}, true);
        signal(EV_ZN);
        {
          const float a0 = qsum(sm[0] + sm[1]), a1 = qsum(sm[2] + sm[3]), q0 = qsum(qq[0] + qq[1]), q1 = qsum(qq[2] + qq[3]);
          const float ss = t ? a1 : a0, m = ss * (1.f / 288.f);
          ll_st128_if(t < 2, P.s->ZST + (rb * 2 + w) * 512 + j * 64 + 16 * q + 8 * t + g, m - blo(off2), fmaxf((t ? q1 : q0) - ss * m, 0.f), tag);
        }
        TRC(tr, w, tb + 8);
        TRC(tr, w, tb + 9);
#pragma unroll 1
        for (int p = 5; p < 9; p++) {
          pass(p, 0x40000040u);
          gelu(Int<0>{}, p < 8);
          z1d += 8192;
        }
        SCLK(18);
        signal(EV_Z1);
        TRC(tr, w, tb + 12);
      }
      uint32_t hA[18][4];
      {
        float acc[144];
        const float c0 = __uint_as_float(lds32(sb + SM_OFF + 4));
#pragma unroll
        for (int i = 0; i < 144; i++) {
          asm volatile("fma.rn.f32 %0, %1, %2, %3;" : "=f"(acc[i]) : "f"(__uint_as_float(P.zero)), "f"((float)(i + 2)), "f"(c0));
        }
        uint32_t prev = 0;
        auto stage = [&](int kb) {
          mbar_wait_c(bars + B_FULL + c.s * 8, c.ph);
          TRC(tr && kb == 0, w, tb + 13);
          SCLK(22 + kb);
          const uint32_t st = sb + c.s * ST_BYTES, rt = sb + SM_RT + kb * 128 + t * 8;
          uint64_t db = dsc2(dlo(st + ST_B, 4608), 0, 8 + P.zero);
          uint32_t a[4][4];
#pragma unroll
          for (int kk = 0; kk < 4; kk++) {
            uint32_t r[4];
            ldsm4(r, st + (aoff ^ (kk << 5)));
            const uint2 sc = lds64(rt + kk * 32);
            a[kk][0] = hmul2(__byte_perm(r[0], r[2], 0x5410), sc.x); a[kk][2] = hmul2(__byte_perm(r[0], r[2], 0x7632), sc.y);
            a[kk][1] = hmul2(__byte_perm(r[1], r[3], 0x5410), sc.x); a[kk][3] = hmul2(__byte_perm(r[1], r[3], 0x7632), sc.y);
          }
          wgmma_fence();
#pragma unroll
          for (int i = 0; i < 8; i++) {
            const int kk = i & 3, hf = i >> 2;
            wgmma_rs_n144(acc + hf * 72, a[kk], db, 1);
            dadd(db, i == 3 ? 144u - 3 * 576 : 576 + P.zero);
            if (i == 0) { wgmma_commit(); wgmma_wait<1>(); release_if(kb, prev); }
            if (i == 3) wgmma_commit();
          }
          wgmma_commit();
          prev = c.s; c.next();
        };
        mbar_wait_c(bars + B_RT, L);
#pragma unroll 1
        for (int kb = 0; kb < 32; kb += 2) {
          if (kb == 8) mbar_wait_c(bars + B_RT1, L);
          MCLK((kb & 7) == 4, 10 + (kb >> 3));
          stage(kb);
          stage(kb + 1);
        }
        if (w == 1) bar_arrive(6, 256);
        HCLK(0);
        mbar_wait_c(bars + B_CV + w * 8, L);
        HCLK(1);
        const float gk = 0.5f / GA;
        const float c1 = __uint_as_float(lds32(sb + SM_OFF + 4));
        const float gb0 = -gk * (c1 + __uint_as_float(lds32(sb + SM_CV + w * 256 + (16 * q + g) * 4))), gb1 = -gk * (c1 + __uint_as_float(lds32(sb + SM_CV + w * 256 + (16 * q + g + 8) * 4)));
        mbar_wait_c(w ? bars + B_FULL + c.s * 8 : bars + B_ZB, w ? c.ph : L);
        HCLK(2);
        const uint32_t sx = c.s;
        c.next();
        const uint32_t zt = sb + tid * 16, zs = zt + sx * ST_BYTES + w * 24576;
        uint4 zz[18];
        auto zload = [&](int u) {
          if (ZW && u == ZW && P.zero) __nanosleep(0);
          if (u >= 12 && u < 16) zz[u] = zk[u - 12]; else zz[u] = lds128(u == 17 ? zt + SM_STG : zs + (u < 12 ? u : 12) * 2048);
        };
#pragma unroll
        for (int u = 0; u < ZA; u++) zload(u);
#pragma unroll
        for (int u = 0; u < 18; u++) {
          if (u == 0) { wgmma_wait<1>(); HCLK(3); }
          if (u == 9) {
            HCLK(4);
            wgmma_wait<0>();
            HCLK(5);
            release(prev);
            mbar_arrive_if(L == 0 && lane == 0, ev + EV_P4 * 8);
            TRC(tr, w, tb + 14);
            SCLK(54);
          }
          if (u + ZA < 18) zload(u + ZA);
          const uint4 z = zz[u];
          hA[u][0] = hmul2(z.x, pack2(fmaf(acc[8 * u], gk, gb0), fmaf(acc[8 * u + 1], gk, gb0)));
          hA[u][1] = hmul2(z.y, pack2(fmaf(acc[8 * u + 2], gk, gb1), fmaf(acc[8 * u + 3], gk, gb1)));
          hA[u][2] = hmul2(z.z, pack2(fmaf(acc[8 * u + 4], gk, gb0), fmaf(acc[8 * u + 5], gk, gb0)));
          hA[u][3] = hmul2(z.w, pack2(fmaf(acc[8 * u + 6], gk, gb1), fmaf(acc[8 * u + 7], gk, gb1)));
        }
        uint32_t dep = P.zero;
#pragma unroll
        for (int u = 0; u < 18; u++) dep &= hA[u][0];
        release(sx, dep);
        TRC(tr, w, tb + 15);
        HCLK(6);
      }
      {
        const uint32_t el = elect_one();
#pragma unroll 1
        for (int p = 0; p < 9; p++) {
          float acc[32];
          if (w == 0) mbar_wait_c(bars + B_FULL + c.s * 8, c.ph);
          uint64_t db = dsc2(dlo(sb + c.s * ST_BYTES + ST_B + (j & 1) * 4096, 0), 0, 0x40000040u + P.zero);
          HCLK(7 + 2 * p);
          bar_sync(6 + w, 256);
          wgmma_fence();
#pragma unroll
          for (int kk = 0; kk < 18; kk++) {
            wgmma_rs_n64(acc, hA[kk], db, kk != 0);
            dadd(db, kk == 15 ? 128 - (j & 1) * (36864 >> 4) : 128 + P.zero);
            if (kk == PPK && (w == 0 || p < 8)) bar_arrive(7 - w, 256);
          }
          wgmma_commit();
          const uint32_t d = sb + (p & 3) * ST_BYTES, cb = p + j >= 9 ? p + j - 9 : p + j;
          if (el) asm volatile("cp.async.bulk.wait_group.read 3;" ::: "memory");
          __syncwarp();
          wgmma_wait<0>();
          HCLK(8 + 2 * p);
          MCLK(p == 1 || p == 8, 7 + (p >> 3));
          TRC(tr && p == 8, w, tb + 16);
          release_if(L == 0 || p < 5, c.s);
          c.next();
#pragma unroll
          for (int u = 0; u < 4; u++)
            stsm4(d + (aoff ^ (u << 5)), pack2(acc[8 * u], acc[8 * u + 1]), pack2(acc[8 * u + 2], acc[8 * u + 3]), pack2(acc[8 * u + 4], acc[8 * u + 5]), pack2(acc[8 * u + 6], acc[8 * u + 7]));
          fence_async_s();
          __syncwarp();
          tma3d_red_p(el, &P.red[L], cb * 64, rb * 64 + q * 16, w, d + w * 8192 + q * 2048);
          TRC(tr && p == 8, w, tb + 17);
        }
        if (el) asm volatile("cp.async.bulk.wait_group 0;" ::: "memory");
        HCLK(25);
        MCLK(1, 9);
        if (L == 0) signal(EV_PT);
        TRC(tr, w, tb + 18);
      }
    }
  }
}

typedef CUresult (*EncodeFn)(CUtensorMap*, CUtensorMapDataType, cuuint32_t, void*, const cuuint64_t*, const cuuint64_t*, const cuuint32_t*,
                             const cuuint32_t*, CUtensorMapInterleave, CUtensorMapSwizzle, CUtensorMapL2promotion, CUtensorMapFloatOOBfill);

static void make_map(EncodeFn fn, CUtensorMap* m, const void* ptr, int rank, uint64_t d0, uint64_t d1, uint64_t d2, uint64_t s1, uint64_t s2,
                     uint32_t b0, uint32_t b1, uint32_t b2, CUtensorMapSwizzle swz) {
  cuuint64_t dims[3] = {d0, d1, d2}, strides[2] = {s1, s2};
  cuuint32_t box[3] = {b0, b1, b2}, es[3] = {1, 1, 1};
  fn(m, CU_TENSOR_MAP_DATA_TYPE_BFLOAT16, rank, const_cast<void*>(ptr), dims, strides, box, es, CU_TENSOR_MAP_INTERLEAVE_NONE, swz,
     CU_TENSOR_MAP_L2_PROMOTION_L2_128B, CU_TENSOR_MAP_FLOAT_OOB_FILL_NONE);
}

}

extern "C" void kernel_launch(void* const* d_in, const int* in_sizes, int n_in, void* d_out, int out_size) {
  using namespace mk;
  (void)in_sizes; (void)n_in; (void)out_size;
  static EncodeFn fn = nullptr;
  static Scratch* sc;
  if (!fn) {
    cudaGetSymbolAddress((void**)&sc, g_scratch);
    cudaDriverEntryPointQueryResult qr;
    cudaGetDriverEntryPoint("cuTensorMapEncodeTiled", (void**)&fn, cudaEnableDefault, &qr);
    cudaFuncSetAttribute(mega_kernel, cudaFuncAttributeMaxDynamicSharedMemorySize, SM_TOTAL);
  }
  Params p;
  p.wqkv = (const __nv_bfloat16*)d_in[1];
  p.w_in = (const __nv_bfloat16*)d_in[4];
  p.w_sp = (const __nv_bfloat16*)d_in[5];
  p.b_sp = (const __nv_bfloat16*)d_in[6];
  p.w_out = (const __nv_bfloat16*)d_in[7];
  p.zero = 0;
  p.s = sc;
  p.xs[0] = (uint8_t*)d_in[0];
  p.xs[1] = sc->X;
  p.xs[2] = (uint8_t*)d_out;
  make_map(fn, &p.wsp, p.w_sp, 3, 2048, 1024, 2, 8192, 4096, 64, 64, 2, CU_TENSOR_MAP_SWIZZLE_128B);
  for (int i = 0; i < 2; i++) {
    make_map(fn, &p.red[i], p.xs[i + 1], 3, DM, 1024, 2, 2304, 1152, 64, 16, 1, CU_TENSOR_MAP_SWIZZLE_128B);
    make_map(fn, &p.res[i], p.xs[i], 3, DM, 1024, 2, 2304, 1152, 144, 64, 1, CU_TENSOR_MAP_SWIZZLE_NONE);
  }
  make_map(fn, &p.psn, d_out, 3, DM, 1024, 2, 2304, 1152, 144, 4, 1, CU_TENSOR_MAP_SWIZZLE_NONE);
  for (int i = 0; i < 3; i++) make_map(fn, &p.act[i], p.xs[i], 3, DM, 1024, 2, 2304, 1152, 64, 64, 1, CU_TENSOR_MAP_SWIZZLE_128B);
  {
    cuuint64_t dims[4] = {8, 8, 72, 72}, strides[3] = {1152, 16, 9216};
    cuuint32_t box[4] = {8, 8, 9, 5}, es[4] = {1, 1, 1, 1};
    fn(&p.wo8, CU_TENSOR_MAP_DATA_TYPE_BFLOAT16, 4, d_in[2], dims, strides, box, es, CU_TENSOR_MAP_INTERLEAVE_NONE, CU_TENSOR_MAP_SWIZZLE_NONE,
       CU_TENSOR_MAP_L2_PROMOTION_L2_128B, CU_TENSOR_MAP_FLOAT_OOB_FILL_NONE);
  }
  for (int i = 0; i < 2; i++) {
    cuuint64_t dims[4] = {i ? 4608u : 2304u, 8, i ? 1u : 2u, 72}, strides[3] = {9216, 4608, 8 * 9216};
    cuuint32_t box[4] = {i ? 64u : 32u, 8, i ? 1u : 2u, 18}, es[4] = {1, 1, 1, 1};
    fn(i ? &p.win64 : &p.win, CU_TENSOR_MAP_DATA_TYPE_BFLOAT16, 4, d_in[4], dims, strides, box, es, CU_TENSOR_MAP_INTERLEAVE_NONE,
       i ? CU_TENSOR_MAP_SWIZZLE_128B : CU_TENSOR_MAP_SWIZZLE_64B, CU_TENSOR_MAP_L2_PROMOTION_L2_128B, CU_TENSOR_MAP_FLOAT_OOB_FILL_NONE);
  }
  make_map(fn, &p.wout, p.w_out, 2, 576, 2304, 1, 1152, 0, 64, 144, 1, CU_TENSOR_MAP_SWIZZLE_128B);
  mega_kernel<<<NGRID, 384, SM_TOTAL, cudaStreamPerThread>>>(p);
}
```

```cpp
#include <cuda_runtime.h>
#include <cuda.h>
#include <cuda_bf16.h>
#include <stdint.h>

#define MK_TRACE 0
#define MK_DBG 0
#define P5TRACE 0
#define LAG1 3
#define PP3 32
#define PP30 33
#define SPL 2
#define NAP 200
#define NAP0 8000
#define KS2 1
#define KS3 1
#define RL3 21
#define PAD 0
#define ZA 4
#define ZW 10
#define GM2 1
#define GMM 1
#define GM1 2
#define C0S 32.f
#define OFA 0.125f
#define OFK 2.f
#define PPK 15

namespace mk {

constexpr int SEQ = 2048, DM = 576, FH = 2304;
constexpr int NCTA = 128;
constexpr int NGRID = 132;
constexpr uint32_t ZB = 36864;
constexpr uint32_t WQ_SL = 72 * 3456;
constexpr uint32_t WO_SL = 72 * 1152;
constexpr float LN_EPS = 1e-5f;
constexpr float GA = 0.3292034911525734f, GB = 2.423681954311584f;

constexpr uint32_t ST_BYTES = 53248, ST_B = 16384, NST = 4;
constexpr uint32_t SM_STG = NST * ST_BYTES;
constexpr uint32_t SM_BAR = SM_STG + 2 * 9216;
constexpr uint32_t SM_OFF = SM_BAR + 1008;
constexpr uint32_t SM_TOTAL = SM_BAR + 1024;
constexpr uint32_t SM_RT = SM_STG + 4096, SM_CV = SM_STG + 12288, SM_WT = SM_CV + 512;
constexpr uint32_t SM_WOI = 44032, SM_CSQ = 49792, SM_XST = 50688;
constexpr uint32_t B_FULL = 0, B_EMPTY = 32, B_FULLA = 64, B_RES = 128, B_WT = 144, B_IMG = 160, B_WOI = 168, B_ZB = 176, B_GATE3 = 184, B_Z1 = 192, B_LAG = 200,
                   B_RT = 208, B_CSQ = 216, B_CV = 224, B_AD = 240, B_EVT = 272, B_RT1 = 368, B_XS = 624, B_XRW = 384, B_FA3 = 400, B_EA3 = 544;
enum { EV_PT = 0, EV_O = 1, EV_X1 = 2, EV_ZN = 3, EV_Z1 = 4, EV_P4 = 5, EV_N = 6 };

enum { FR_X2 = 0, FR_O = 1, FR_X1 = 3, FR_EP = 16, FJ = 32 * 32, FJ_WQ = 0, FJ_WO = 1, FJ_WQ0 = 2, FJ_ZN = 3, FJ_P4 = 5, FJ_EP = 16, F_N = FJ + 8 * 32 };

constexpr uint32_t POISON = 0xffffffffu;
struct Scratch {
  uint32_t flags[F_N];
  uint2 RT[SEQ];
  uint4 XST[2 * SEQ];
  uint4 ST1[SEQ * 8], ZST[SEQ * 8], HALO[32 * 8 * 6 * 32];
  float CSP[2 * NCTA * 216];
  uint8_t WQ[8 * WQ_SL], WO[8 * WO_SL];
  uint8_t O[32 * 2 * ZB];
  uint8_t X[SEQ * DM * 2];
  uint8_t Z[512 * ZB];
  uint4 RD[NCTA * 36 * 256];
};
__device__ __align__(1024) Scratch g_scratch;
#define SLOW(i) do {} while (0)

struct Params {
  const __nv_bfloat16 *wqkv;
  Scratch* s;
  uint32_t zero;
  const __nv_bfloat16 *w_in, *w_sp, *b_sp, *w_out;
  uint8_t* xs[3];
  CUtensorMap wo8, wsp, win, win64, wout;
  CUtensorMap act[3];
  CUtensorMap res[2];
  CUtensorMap red[2];
  CUtensorMap psn;
};

__device__ __forceinline__ uint32_t smem_u32(const void* p) { return (uint32_t)__cvta_generic_to_shared(p); }
__device__ __forceinline__ void mbar_init(uint32_t bar, uint32_t cnt) { asm volatile("mbarrier.init.shared::cta.b64 [%0], %1;" ::"r"(bar), "r"(cnt)); }
__device__ __forceinline__ void mbar_arrive(uint32_t bar) { asm volatile("mbarrier.arrive.shared::cta.b64 _, [%0];" ::"r"(bar) : "memory"); }
__device__ __forceinline__ void mbar_wait(uint32_t bar, uint32_t parity) {
  asm volatile(
      "{\n.reg .pred p;\n.reg .u32 c;\nmov.u32 c, 0;\nLAB_WAIT:\n"
      "mbarrier.try_wait.parity.shared::cta.b64 p, [%0], %1;\n@p bra LAB_DONE;\n"
      "add.u32 c, c, 1;\nsetp.lt.u32 p, c, 0x100000;\n@p bra LAB_WAIT;\ntrap;\nLAB_DONE:\n}" ::"r"(bar), "r"(parity)
      : "memory");
}
__device__ __forceinline__ void mbar_wait_c(uint32_t bar, uint32_t parity) {
  asm volatile("{\n.reg .pred p;\nLAB_WAIT:\nmbarrier.try_wait.parity.shared::cta.b64 p, [%0], %1;\n@!p bra LAB_WAIT;\n}" ::"r"(bar), "r"(parity) : "memory");
}
__device__ __forceinline__ void flag_wait(const uint32_t* f, uint32_t target) {
  asm volatile(
      "{\n.reg .pred p;\n.reg .u32 c, v;\nmov.u32 c, 0;\nLAB_WAIT:\n"
      "ld.relaxed.gpu.global.u32 v, [%0];\nsub.u32 v, v, %1;\nsetp.ge.s32 p, v, 0;\n@p bra LAB_DONE;\n"
      "add.u32 c, c, 1;\nsetp.lt.u32 p, c, 0x400000;\n@p bra LAB_WAIT;\ntrap;\nLAB_DONE:\nfence.acquire.gpu;\n}" ::"l"(f), "r"(target)
      : "memory");
}
__device__ __forceinline__ void fence_gpu() { asm volatile("fence.acq_rel.gpu;" ::: "memory"); }
__device__ __forceinline__ void fence_async_g() { asm volatile("fence.proxy.async.global;" ::: "memory"); }
__device__ __forceinline__ void fence_async_s() { asm volatile("fence.proxy.async.shared::cta;" ::: "memory"); }
__device__ __forceinline__ uint32_t elect_one() {
  uint32_t p; asm volatile("{\n.reg .pred P;\nelect.sync _|P, 0xffffffff;\nselp.u32 %0, 1, 0, P;\n}" : "=r"(p)); return p;
}
__device__ __forceinline__ void expect_tx_p(uint32_t el, uint32_t bar, uint32_t bytes) {
  asm volatile("{\n.reg .pred P;\nsetp.ne.u32 P, %2, 0;\n@P mbarrier.arrive.expect_tx.shared::cta.b64 _, [%0], %1;\n}" ::"r"(bar), "r"(bytes), "r"(el) : "memory");
}
__device__ __forceinline__ void bulk_load_p(uint32_t el, uint32_t dst, const void* src, uint32_t bytes, uint32_t bar) {
  asm volatile("{\n.reg .pred P;\nsetp.ne.u32 P, %4, 0;\n@P cp.async.bulk.shared::cluster.global.mbarrier::complete_tx::bytes [%0], [%1], %2, [%3];\n}" ::"r"(dst), "l"(src), "r"(bytes), "r"(bar), "r"(el) : "memory");
}
__device__ __forceinline__ uint64_t policy_evict_first() { uint64_t p; asm("createpolicy.fractional.L2::evict_first.b64 %0, 1.0;" : "=l"(p)); return p; }
__device__ __forceinline__ void bulk_load_h(uint32_t el, uint32_t dst, const void* src, uint32_t bytes, uint32_t bar, bool ef, uint64_t pol) {
  if (ef) {
    asm volatile("{\n.reg .pred P;\nsetp.ne.u32 P, %4, 0;\n@P cp.async.bulk.shared::cluster.global.mbarrier::complete_tx::bytes.L2::cache_hint [%0], [%1], %2, [%3], %5;\n}" ::"r"(dst), "l"(src), "r"(bytes), "r"(bar), "r"(el), "l"(pol) : "memory");
  } else {
    asm volatile("{\n.reg .pred P;\nsetp.ne.u32 P, %4, 0;\n@P cp.async.bulk.shared::cluster.global.mbarrier::complete_tx::bytes [%0], [%1], %2, [%3];\n}" ::"r"(dst), "l"(src), "r"(bytes), "r"(bar), "r"(el) : "memory");
  }
}
__device__ __forceinline__ void bulk_mc_h(uint32_t el, uint32_t dst, const void* src, uint32_t bytes, uint32_t bar, bool ef, uint64_t pol) {
  if (ef) {
    asm volatile("{\n.reg .pred P;\nsetp.ne.u32 P, %4, 0;\n@P cp.async.bulk.shared::cluster.global.mbarrier::complete_tx::bytes.multicast::cluster.L2::cache_hint [%0], [%1], %2, [%3], %5, %6;\n}" ::"r"(dst), "l"(src), "r"(bytes), "r"(bar), "r"(el), "h"((uint16_t)3), "l"(pol) : "memory");
  } else {
    asm volatile("{\n.reg .pred P;\nsetp.ne.u32 P, %4, 0;\n@P cp.async.bulk.shared::cluster.global.mbarrier::complete_tx::bytes.multicast::cluster [%0], [%1], %2, [%3], %5;\n}" ::"r"(dst), "l"(src), "r"(bytes), "r"(bar), "r"(el), "h"((uint16_t)3) : "memory");
  }
}
__device__ __forceinline__ void tma3d_h(uint32_t el, uint32_t dst, const CUtensorMap* m, int c0, int c1, int c2, uint32_t bar, bool ef, uint64_t pol) {
  if (ef) {
    asm volatile("{\n.reg .pred P;\nsetp.ne.u32 P, %6, 0;\n@P cp.async.bulk.tensor.3d.shared::cluster.global.mbarrier::complete_tx::bytes.L2::cache_hint [%0], [%1, {%3, %4, %5}], [%2], %7;\n}" ::"r"(dst), "l"(m), "r"(bar), "r"(c0), "r"(c1), "r"(c2), "r"(el), "l"(pol) : "memory");
  } else {
    asm volatile("{\n.reg .pred P;\nsetp.ne.u32 P, %6, 0;\n@P cp.async.bulk.tensor.3d.shared::cluster.global.mbarrier::complete_tx::bytes [%0], [%1, {%3, %4, %5}], [%2];\n}" ::"r"(dst), "l"(m), "r"(bar), "r"(c0), "r"(c1), "r"(c2), "r"(el) : "memory");
  }
}
__device__ __forceinline__ void tma2d_mc_h(uint32_t el, uint32_t dst, const CUtensorMap* m, int c0, int c1, uint32_t bar, bool ef, uint64_t pol) {
  if (ef) {
    asm volatile("{\n.reg .pred P;\nsetp.ne.u32 P, %5, 0;\n@P cp.async.bulk.tensor.2d.shared::cluster.global.mbarrier::complete_tx::bytes.multicast::cluster.L2::cache_hint [%0], [%1, {%3, %4}], [%2], %6, %7;\n}" ::"r"(dst), "l"(m), "r"(bar), "r"(c0), "r"(c1), "r"(el), "h"((uint16_t)3), "l"(pol) : "memory");
  } else {
    asm volatile("{\n.reg .pred P;\nsetp.ne.u32 P, %5, 0;\n@P cp.async.bulk.tensor.2d.shared::cluster.global.mbarrier::complete_tx::bytes.multicast::cluster [%0], [%1, {%3, %4}], [%2], %6;\n}" ::"r"(dst), "l"(m), "r"(bar), "r"(c0), "r"(c1), "r"(el), "h"((uint16_t)3) : "memory");
  }
}
__device__ __forceinline__ void tma4d_mc(uint32_t el, uint32_t dst, const CUtensorMap* m, int c0, int c3, uint32_t bar, uint64_t pol) {
  asm volatile("{\n.reg .pred P;\nsetp.ne.u32 P, %5, 0;\n@P cp.async.bulk.tensor.4d.shared::cluster.global.mbarrier::complete_tx::bytes.multicast::cluster.L2::cache_hint [%0], [%1, {%3, 0, 0, %4}], [%2], %6, %7;\n}" ::"r"(dst), "l"(m), "r"(bar), "r"(c0), "r"(c3), "r"(el), "h"((uint16_t)3), "l"(pol) : "memory");
}
__device__ __forceinline__ void mbar_arrive_cluster(uint32_t addr) { asm volatile("mbarrier.arrive.shared::cluster.b64 _, [%0];" ::"r"(addr) : "memory"); }
__device__ __forceinline__ void mbar_arrive_cluster_if(bool c, uint32_t addr) {
  asm volatile("{\n.reg .pred P;\nsetp.ne.u32 P, %1, 0;\n@P mbarrier.arrive.shared::cluster.b64 _, [%0];\n}" ::"r"(addr), "r"((uint32_t)c) : "memory");
}
__device__ __forceinline__ void mbar_arrive_if(bool c, uint32_t addr) {
  asm volatile("{\n.reg .pred P;\nsetp.ne.u32 P, %1, 0;\n@P mbarrier.arrive.shared::cta.b64 _, [%0];\n}" ::"r"(addr), "r"((uint32_t)c) : "memory");
}
__device__ __forceinline__ uint32_t mapa(uint32_t addr, uint32_t rank) { uint32_t r; asm("mapa.shared::cluster.u32 %0, %1, %2;" : "=r"(r) : "r"(addr), "r"(rank)); return r; }
__device__ __forceinline__ void bulk_store_p(uint32_t el, void* dst, uint32_t src, uint32_t bytes) {
  asm volatile("{\n.reg .pred P;\nsetp.ne.u32 P, %3, 0;\n@P cp.async.bulk.global.shared::cta.bulk_group [%0], [%1], %2;\n}" ::"l"(dst), "r"(src), "r"(bytes), "r"(el) : "memory");
}
__device__ __forceinline__ void flag_release_p(uint32_t el, uint32_t* f) {
  asm volatile("{\n.reg .pred P;\nsetp.ne.u32 P, %1, 0;\n@P red.release.gpu.global.add.u32 [%0], 1;\n}" ::"l"(f), "r"(el) : "memory");
}
__device__ __forceinline__ void flag_add_p(uint32_t el, uint32_t* f) {
  asm volatile("{\n.reg .pred P;\nsetp.ne.u32 P, %1, 0;\n@P red.relaxed.gpu.global.add.u32 [%0], 1;\n}" ::"l"(f), "r"(el) : "memory");
}
__device__ __forceinline__ void prefetch_l2(const void* src, uint32_t bytes) { asm volatile("cp.async.bulk.prefetch.L2.global [%0], %1;" ::"l"(src), "r"(bytes) : "memory"); }
__device__ __forceinline__ void prefetch_map(const CUtensorMap* m) { asm volatile("prefetch.tensormap [%0];" ::"l"(m) : "memory"); }
__device__ __forceinline__ void wgmma_fence() { asm volatile("wgmma.fence.sync.aligned;" ::: "memory"); }
__device__ __forceinline__ void wgmma_commit() { asm volatile("wgmma.commit_group.sync.aligned;" ::: "memory"); }
template <int N> __device__ __forceinline__ void wgmma_wait() { asm volatile("wgmma.wait_group.sync.aligned %0;" ::"n"(N) : "memory"); }
__device__ __forceinline__ uint32_t dlo(uint32_t addr, uint32_t lbo) { return ((addr & 0x3FFFF) >> 4) + ((lbo >> 4) << 16); }
template <uint32_t SBO, uint32_t SWZ> __device__ __forceinline__ uint64_t dsc(uint32_t lo, uint32_t off) {
  uint64_t d; asm("mov.b64 %0, {%1, %2};" : "=l"(d) : "r"(lo + (off >> 4)), "n"((SBO >> 4) | (SWZ << 30))); return d;
}
__device__ __forceinline__ uint64_t dsc2(uint32_t lo, uint32_t off, uint32_t hi) {
  uint64_t d; asm("mov.b64 %0, {%1, %2};" : "=l"(d) : "r"(lo + (off >> 4)), "r"(hi)); return d;
}
__device__ __forceinline__ uint64_t dat(uint64_t d, uint32_t off, uint32_t one) { uint64_t r; asm("mad.wide.u32 %0, %1, %2, %3;" : "=l"(r) : "r"(one), "r"(off >> 4), "l"(d)); return r; }
__device__ __forceinline__ void dadd(uint64_t& d, uint32_t v) {
  asm("{\n.reg .b32 lo, hi;\nmov.b64 {lo, hi}, %0;\nadd.u32 lo, lo, %1;\nmov.b64 %0, {lo, hi};\n}" : "+l"(d) : "r"(v));
}
template <int R> __device__ __forceinline__ void reg_alloc() { asm volatile("setmaxnreg.inc.sync.aligned.u32 %0;" ::"n"(R)); }
template <int R> __device__ __forceinline__ void reg_dealloc() { asm volatile("setmaxnreg.dec.sync.aligned.u32 %0;" ::"n"(R)); }
__device__ __forceinline__ void bar_sync(int id, int n) { asm volatile("bar.sync %0, %1;" ::"r"(id), "r"(n) : "memory"); }
__device__ __forceinline__ void bar_arrive(int id, int n) { asm volatile("bar.arrive %0, %1;" ::"r"(id), "r"(n) : "memory"); }
__device__ __forceinline__ void ldsm4(uint32_t* r, uint32_t addr) {
  asm volatile("ldmatrix.sync.aligned.m8n8.x4.shared.b16 {%0,%1,%2,%3}, [%4];" : "=r"(r[0]), "=r"(r[1]), "=r"(r[2]), "=r"(r[3]) : "r"(addr) : "memory");
}
__device__ __forceinline__ uint32_t movm(uint32_t a) { uint32_t d; asm volatile("movmatrix.sync.aligned.m8n8.trans.b16 %0, %1;" : "=r"(d) : "r"(a)); return d; }
__device__ __forceinline__ void mma16(float* c, uint32_t a0, uint32_t a1, uint32_t a2, uint32_t a3, uint32_t b0, uint32_t b1) {
  asm volatile("mma.sync.aligned.m16n8k16.row.col.f32.bf16.bf16.f32 {%0,%1,%2,%3}, {%4,%5,%6,%7}, {%8,%9}, {%10,%10,%10,%10};"
               : "=f"(c[0]), "=f"(c[1]), "=f"(c[2]), "=f"(c[3]) : "r"(a0), "r"(a1), "r"(a2), "r"(a3), "r"(b0), "r"(b1), "f"(0.f));
}
__device__ __forceinline__ void mma8(float* c, uint32_t a0, uint32_t a1, uint32_t b0) {
  asm volatile("mma.sync.aligned.m16n8k8.row.col.f32.bf16.bf16.f32 {%0,%1,%2,%3}, {%4,%5}, {%6}, {%0,%1,%2,%3};"
               : "+f"(c[0]), "+f"(c[1]), "+f"(c[2]), "+f"(c[3]) : "r"(a0), "r"(a1), "r"(b0));
}
__device__ __forceinline__ void widen(float* c, uint32_t a0, uint32_t a1, uint32_t eye) {
  asm volatile("mma.sync.aligned.m16n8k8.row.col.f32.bf16.bf16.f32 {%0,%1,%2,%3}, {%4,%5}, {%6}, {%7,%7,%7,%7};"
               : "=f"(c[0]), "=f"(c[1]), "=f"(c[2]), "=f"(c[3]) : "r"(a0), "r"(a1), "r"(eye), "f"(0.f));
}
__device__ __forceinline__ float rsq_fast(float x) { float y; asm("rsqrt.approx.ftz.f32 %0, %1;" : "=f"(y) : "f"(x)); return y; }
__device__ __forceinline__ uint32_t pack2(float lo, float hi) { uint32_t r; asm("cvt.rn.bf16x2.f32 %0, %1, %2;" : "=r"(r) : "f"(hi), "f"(lo)); return r; }
__device__ __forceinline__ float blo(uint32_t v) { return __uint_as_float(v << 16); }
__device__ __forceinline__ float bhi(uint32_t v) { return __uint_as_float(v & 0xffff0000u); }
__device__ __forceinline__ float tanh_fast(float x) { float y; asm("tanh.approx.f32 %0, %1;" : "=f"(y) : "f"(x)); return y; }
__device__ __forceinline__ float rcp_fast(float x) { float y; asm("rcp.approx.ftz.f32 %0, %1;" : "=f"(y) : "f"(x)); return y; }
__device__ __forceinline__ float ex2(float x) { float y; asm("ex2.approx.ftz.f32 %0, %1;" : "=f"(y) : "f"(x)); return y; }
__device__ __forceinline__ float qsum(float v) { v += __shfl_xor_sync(~0u, v, 1); v += __shfl_xor_sync(~0u, v, 2); return v; }
__device__ __forceinline__ float qmax(float v) { v = fmaxf(v, __shfl_xor_sync(~0u, v, 1)); v = fmaxf(v, __shfl_xor_sync(~0u, v, 2)); return v; }
__device__ __forceinline__ void stg32(void* p, uint32_t v) { asm volatile("st.global.u32 [%0], %1;" ::"l"(p), "r"(v) : "memory"); }
__device__ __forceinline__ void stg128(void* p, uint32_t a, uint32_t b, uint32_t c, uint32_t d) { asm volatile("st.global.v4.u32 [%0], {%1,%2,%3,%4};" ::"l"(p), "r"(a), "r"(b), "r"(c), "r"(d) : "memory"); }
__device__ __forceinline__ uint32_t ldcg32(const void* p) { uint32_t v; asm volatile("ld.global.L1::no_allocate.u32 %0, [%1];" : "=r"(v) : "l"(p) : "memory"); return v; }
__device__ __forceinline__ uint32_t ldgpu32(const void* p) { uint32_t v; asm volatile("ld.relaxed.gpu.global.u32 %0, [%1];" : "=r"(v) : "l"(p) : "memory"); return v; }
__device__ __forceinline__ uint32_t ldca32(const void* p) { uint32_t v; asm volatile("ld.global.ca.u32 %0, [%1];" : "=r"(v) : "l"(p) : "memory"); return v; }
__device__ __forceinline__ void stg128_if(bool c, void* p, uint32_t a, uint32_t b, uint32_t cc, uint32_t d) {
  asm volatile("{\n.reg .pred P;\nsetp.ne.u32 P, %5, 0;\n@P st.global.v4.u32 [%0], {%1,%2,%3,%4};\n}" ::"l"(p), "r"(a), "r"(b), "r"(cc), "r"(d), "r"((uint32_t)c) : "memory");
}
__device__ __forceinline__ uint2 lds64(uint32_t a) { uint2 v; asm volatile("ld.shared.v2.u32 {%0,%1}, [%2];" : "=r"(v.x), "=r"(v.y) : "r"(a) : "memory"); return v; }
__device__ __forceinline__ uint4 ldcg128(const void* p) { uint4 v; asm volatile("ld.global.cg.v4.u32 {%0,%1,%2,%3}, [%4];" : "=r"(v.x), "=r"(v.y), "=r"(v.z), "=r"(v.w) : "l"(p) : "memory"); return v; }
__device__ __forceinline__ uint32_t ldnc16(const void* p) { uint16_t v; asm volatile("ld.global.nc.u16 %0, [%1];" : "=h"(v) : "l"(p)); return v; }
__device__ __forceinline__ uint4 ldnc128(const void* p) { uint4 v; asm volatile("ld.global.nc.v4.u32 {%0,%1,%2,%3}, [%4];" : "=r"(v.x), "=r"(v.y), "=r"(v.z), "=r"(v.w) : "l"(p)); return v; }
__device__ __forceinline__ uint32_t hsub2(uint32_t a, uint32_t b) { uint32_t d; asm("sub.rn.bf16x2 %0, %1, %2;" : "=r"(d) : "r"(a), "r"(b)); return d; }
__device__ __forceinline__ void stg32_if(bool c, void* p, uint32_t v) {
  asm volatile("{\n.reg .pred P;\nsetp.ne.u32 P, %2, 0;\n@P st.global.u32 [%0], %1;\n}" ::"l"(p), "r"(v), "r"((uint32_t)c) : "memory");
}
__device__ __forceinline__ uint32_t hmul2(uint32_t a, uint32_t b) { uint32_t d; asm("mul.rn.bf16x2 %0, %1, %2;" : "=r"(d) : "r"(a), "r"(b)); return d; }
__device__ __forceinline__ void sts32(uint32_t a, uint32_t v) { asm volatile("st.shared.u32 [%0], %1;" ::"r"(a), "r"(v) : "memory"); }
__device__ __forceinline__ uint32_t lds32(uint32_t a) { uint32_t v; asm volatile("ld.shared.u32 %0, [%1];" : "=r"(v) : "r"(a) : "memory"); return v; }
__device__ __forceinline__ void sts128(uint32_t a, uint32_t x, uint32_t y, uint32_t z, uint32_t w) { asm volatile("st.shared.v4.u32 [%0], {%1,%2,%3,%4};" ::"r"(a), "r"(x), "r"(y), "r"(z), "r"(w) : "memory"); }
__device__ __forceinline__ uint4 lds128(uint32_t a) { uint4 v; asm volatile("ld.shared.v4.u32 {%0,%1,%2,%3}, [%4];" : "=r"(v.x), "=r"(v.y), "=r"(v.z), "=r"(v.w) : "r"(a) : "memory"); return v; }
__device__ __forceinline__ void ll_st64(uint2* p, uint32_t v, uint32_t tag) {
  asm volatile("{\n.reg .b64 r;\nmov.b64 r, {%1,%2};\nst.relaxed.gpu.global.b64 [%0], r;\n}" ::"l"(p), "r"(v), "r"(tag) : "memory");
}
__device__ __forceinline__ uint2 ll_ld64(const uint2* p) {
  uint2 v; asm volatile("{\n.reg .b64 r;\nld.relaxed.gpu.global.b64 r, [%2];\nmov.b64 {%0,%1}, r;\n}" : "=r"(v.x), "=r"(v.y) : "l"(p) : "memory"); return v;
}
__device__ __forceinline__ void ll_st128(uint4* p, float a, float b, uint32_t tag, float c = 0.f) {
  asm volatile("{\n.reg .b128 r;\n.reg .b64 lo, hi;\nmov.b64 lo, {%1,%2};\nmov.b64 hi, {%3,%4};\nmov.b128 r, {lo, hi};\nst.relaxed.gpu.global.b128 [%0], r;\n}" ::"l"(p), "r"(__float_as_uint(a)), "r"(__float_as_uint(b)), "r"(tag), "r"(__float_as_uint(c)) : "memory");
}
__device__ __forceinline__ uint4 ll_ld128(const uint4* p) {
  uint4 v; asm volatile("{\n.reg .b128 r;\n.reg .b64 lo, hi;\nld.relaxed.gpu.global.b128 r, [%4];\nmov.b128 {lo, hi}, r;\nmov.b64 {%0,%1}, lo;\nmov.b64 {%2,%3}, hi;\n}" : "=r"(v.x), "=r"(v.y), "=r"(v.z), "=r"(v.w) : "l"(p) : "memory"); return v;
}
__device__ __forceinline__ void publish_p(uint32_t el, uint32_t* f) {
  asm volatile("{\n.reg .pred P;\nsetp.ne.u32 P, %1, 0;\n@P cp.async.bulk.commit_group;\n@P cp.async.bulk.wait_group 0;\n@P red.release.gpu.global.add.u32 [%0], 1;\n}" ::"l"(f), "r"(el) : "memory");
}
__device__ __forceinline__ void tma3d_red_p(uint32_t el, const CUtensorMap* m, int c0, int c1, int c2, uint32_t src) {
  asm volatile("{\n.reg .pred P;\nsetp.ne.u32 P, %5, 0;\n@P cp.reduce.async.bulk.tensor.3d.global.shared::cta.add.tile.bulk_group [%0, {%2, %3, %4}], [%1];\n@P cp.async.bulk.commit_group;\n}" ::"l"(m), "r"(src), "r"(c0), "r"(c1), "r"(c2), "r"(el) : "memory");
}
__device__ __forceinline__ void stsm4(uint32_t addr, uint32_t a, uint32_t b, uint32_t c, uint32_t d) {
  asm volatile("stmatrix.sync.aligned.m8n8.x4.shared.b16 [%0], {%1,%2,%3,%4};" ::"r"(addr), "r"(a), "r"(b), "r"(c), "r"(d) : "memory");
}
__device__ __forceinline__ void sts64(uint32_t a, uint32_t x, uint32_t y) { asm volatile("st.shared.v2.u32 [%0], {%1,%2};" ::"r"(a), "r"(x), "r"(y) : "memory"); }
__device__ __forceinline__ void ll_st128_if(bool on, uint4* p, float a, float b, uint32_t tag) {
  asm volatile("{\n.reg .pred P;\n.reg .b128 r;\n.reg .b64 lo, hi;\nsetp.ne.u32 P, %4, 0;\nmov.b64 lo, {%1,%2};\nmov.b64 hi, {%3,%3};\nmov.b128 r, {lo, hi};\n@P st.relaxed.gpu.global.b128 [%0], r;\n}" ::"l"(p), "r"(__float_as_uint(a)), "r"(__float_as_uint(b)), "r"(tag), "r"((uint32_t)on) : "memory");
}
__device__ __forceinline__ uint4 ldnc128_if(bool c, const void* p) {
  uint4 v = make_uint4(0u, 0u, 0u, 0u);
  asm volatile("{\n.reg .pred P;\nsetp.ne.u32 P, %5, 0;\n@P ld.global.nc.v4.u32 {%0,%1,%2,%3}, [%4];\n}" : "+r"(v.x), "+r"(v.y), "+r"(v.z), "+r"(v.w) : "l"(p), "r"((uint32_t)c));
  return v;
}
__device__ __forceinline__ uint32_t hfma2(uint32_t a, uint32_t b, uint32_t c) { uint32_t d; asm("fma.rn.bf16x2 %0, %1, %2, %3;" : "=r"(d) : "r"(a), "r"(b), "r"(c)); return d; }
__device__ __forceinline__ float2 lds64f(uint32_t a) { float2 v; asm volatile("ld.shared.v2.f32 {%0,%1}, [%2];" : "=f"(v.x), "=f"(v.y) : "r"(a) : "memory"); return v; }
#define TRC(cond, role, idx) do {} while (0)
#define TRV(role, idx, v) do {} while (0)

#define ACLK_INIT do {} while (0)
#define ACLK(i) do {} while (0)
#define ACLK_OUT do {} while (0)
#define QCLK(i) do {} while (0)
#define PH 1
#define RCLK(i) do {} while (0)
#define RCLK_INIT do {} while (0)
#define RCLK_OUT do {} while (0)
#define SCLK(i) do {} while (0)
#define HCLK(i) do {} while (0)
#define MCLK(c, i) do {} while (0)
#define CKK(i) do {} while (0)
#define CKK_OUT do {} while (0)
#define PL 1
#define PCLK(i) do {} while (0)
#define PQ 1
#define CLK_INIT do {} while (0)
#define CLK(i) do {} while (0)
#define CLK_OUT do {} while (0)

__device__ __forceinline__ void wgmma_ss_n216(float* d, uint64_t da, uint64_t db, int scaleD) {
  asm volatile("{\n.reg .pred p;\nsetp.ne.b32 p, %110, 0;\nwgmma.mma_async.sync.aligned.m64n216k16.f32.bf16.bf16 "
    "{%0,%1,%2,%3,%4,%5,%6,%7,%8,%9,%10,%11,%12,%13,%14,%15,%16,%17,%18,%19,%20,%21,%22,%23,%24,%25,%26,%27,%28,%29,%30,%31,%32,%33,%34,%35,%36,%37,%38,%39,%40,%41,%42,%43,%44,%45,%46,%47,%48,%49,%50,%51,%52,%53,%54,%55,%56,%57,%58,%59,%60,%61,%62,%63,%64,%65,%66,%67,%68,%69,%70,%71,%72,%73,%74,%75,%76,%77,%78,%79,%80,%81,%82,%83,%84,%85,%86,%87,%88,%89,%90,%91,%92,%93,%94,%95,%96,%97,%98,%99,%100,%101,%102,%103,%104,%105,%106,%107}, "
    "%108, %109, p, 1, 1, 0, 1;\n}\n"
    : "+f"(d[0]), "+f"(d[1]), "+f"(d[2]), "+f"(d[3]), "+f"(d[4]), "+f"(d[5]), "+f"(d[6]), "+f"(d[7]), "+f"(d[8]), "+f"(d[9]), "+f"(d[10]), "+f"(d[11]), "+f"(d[12]), "+f"(d[13]), "+f"(d[14]), "+f"(d[15]), "+f"(d[16]), "+f"(d[17]), "+f"(d[18]), "+f"(d[19]), "+f"(d[20]), "+f"(d[21]), "+f"(d[22]), "+f"(d[23]), "+f"(d[24]), "+f"(d[25]), "+f"(d[26]), "+f"(d[27]), "+f"(d[28]), "+f"(d[29]), "+f"(d[30]), "+f"(d[31]), "+f"(d[32]), "+f"(d[33]), "+f"(d[34]), "+f"(d[35]), "+f"(d[36]), "+f"(d[37]), "+f"(d[38]), "+f"(d[39]), "+f"(d[40]), "+f"(d[41]), "+f"(d[42]), "+f"(d[43]), "+f"(d[44]), "+f"(d[45]), "+f"(d[46]), "+f"(d[47]), "+f"(d[48]), "+f"(d[49]), "+f"(d[50]), "+f"(d[51]), "+f"(d[52]), "+f"(d[53]), "+f"(d[54]), "+f"(d[55]), "+f"(d[56]), "+f"(d[57]), "+f"(d[58]), "+f"(d[59]), "+f"(d[60]), "+f"(d[61]), "+f"(d[62]), "+f"(d[63]), "+f"(d[64]), "+f"(d[65]), "+f"(d[66]), "+f"(d[67]), "+f"(d[68]), "+f"(d[69]), "+f"(d[70]), "+f"(d[71]), "+f"(d[72]), "+f"(d[73]), "+f"(d[74]), "+f"(d[75]), "+f"(d[76]), "+f"(d[77]), "+f"(d[78]), "+f"(d[79]), "+f"(d[80]), "+f"(d[81]), "+f"(d[82]), "+f"(d[83]), "+f"(d[84]), "+f"(d[85]), "+f"(d[86]), "+f"(d[87]), "+f"(d[88]), "+f"(d[89]), "+f"(d[90]), "+f"(d[91]), "+f"(d[92]), "+f"(d[93]), "+f"(d[94]), "+f"(d[95]), "+f"(d[96]), "+f"(d[97]), "+f"(d[98]), "+f"(d[99]), "+f"(d[100]), "+f"(d[101]), "+f"(d[102]), "+f"(d[103]), "+f"(d[104]), "+f"(d[105]), "+f"(d[106]), "+f"(d[107])
    : "l"(da), "l"(db), "r"(scaleD));
}
__device__ __forceinline__ void wgmma_ss_n72(float* d, uint64_t da, uint64_t db, int scaleD) {
  asm volatile("{\n.reg .pred p;\nsetp.ne.b32 p, %38, 0;\nwgmma.mma_async.sync.aligned.m64n72k16.f32.bf16.bf16 "
    "{%0,%1,%2,%3,%4,%5,%6,%7,%8,%9,%10,%11,%12,%13,%14,%15,%16,%17,%18,%19,%20,%21,%22,%23,%24,%25,%26,%27,%28,%29,%30,%31,%32,%33,%34,%35}, "
    "%36, %37, p, 1, 1, 0, 1;\n}\n"
    : "+f"(d[0]), "+f"(d[1]), "+f"(d[2]), "+f"(d[3]), "+f"(d[4]), "+f"(d[5]), "+f"(d[6]), "+f"(d[7]), "+f"(d[8]), "+f"(d[9]), "+f"(d[10]), "+f"(d[11]), "+f"(d[12]), "+f"(d[13]), "+f"(d[14]), "+f"(d[15]), "+f"(d[16]), "+f"(d[17]), "+f"(d[18]), "+f"(d[19]), "+f"(d[20]), "+f"(d[21]), "+f"(d[22]), "+f"(d[23]), "+f"(d[24]), "+f"(d[25]), "+f"(d[26]), "+f"(d[27]), "+f"(d[28]), "+f"(d[29]), "+f"(d[30]), "+f"(d[31]), "+f"(d[32]), "+f"(d[33]), "+f"(d[34]), "+f"(d[35])
    : "l"(da), "l"(db), "r"(scaleD));
}
__device__ __forceinline__ void wgmma_rs_n144(float* d, const uint32_t* a, uint64_t db, int scaleD) {
  asm volatile("{\n.reg .pred p;\nsetp.ne.b32 p, %77, 0;\nwgmma.mma_async.sync.aligned.m64n144k16.f32.bf16.bf16 "
    "{%0,%1,%2,%3,%4,%5,%6,%7,%8,%9,%10,%11,%12,%13,%14,%15,%16,%17,%18,%19,%20,%21,%22,%23,%24,%25,%26,%27,%28,%29,%30,%31,%32,%33,%34,%35,%36,%37,%38,%39,%40,%41,%42,%43,%44,%45,%46,%47,%48,%49,%50,%51,%52,%53,%54,%55,%56,%57,%58,%59,%60,%61,%62,%63,%64,%65,%66,%67,%68,%69,%70,%71}, "
    "{%72,%73,%74,%75}, %76, p, 1, 1, 1;\n}\n"
    : "+f"(d[0]), "+f"(d[1]), "+f"(d[2]), "+f"(d[3]), "+f"(d[4]), "+f"(d[5]), "+f"(d[6]), "+f"(d[7]), "+f"(d[8]), "+f"(d[9]), "+f"(d[10]), "+f"(d[11]), "+f"(d[12]), "+f"(d[13]), "+f"(d[14]), "+f"(d[15]), "+f"(d[16]), "+f"(d[17]), "+f"(d[18]), "+f"(d[19]), "+f"(d[20]), "+f"(d[21]), "+f"(d[22]), "+f"(d[23]), "+f"(d[24]), "+f"(d[25]), "+f"(d[26]), "+f"(d[27]), "+f"(d[28]), "+f"(d[29]), "+f"(d[30]), "+f"(d[31]), "+f"(d[32]), "+f"(d[33]), "+f"(d[34]), "+f"(d[35]), "+f"(d[36]), "+f"(d[37]), "+f"(d[38]), "+f"(d[39]), "+f"(d[40]), "+f"(d[41]), "+f"(d[42]), "+f"(d[43]), "+f"(d[44]), "+f"(d[45]), "+f"(d[46]), "+f"(d[47]), "+f"(d[48]), "+f"(d[49]), "+f"(d[50]), "+f"(d[51]), "+f"(d[52]), "+f"(d[53]), "+f"(d[54]), "+f"(d[55]), "+f"(d[56]), "+f"(d[57]), "+f"(d[58]), "+f"(d[59]), "+f"(d[60]), "+f"(d[61]), "+f"(d[62]), "+f"(d[63]), "+f"(d[64]), "+f"(d[65]), "+f"(d[66]), "+f"(d[67]), "+f"(d[68]), "+f"(d[69]), "+f"(d[70]), "+f"(d[71])
    : "r"(a[0]), "r"(a[1]), "r"(a[2]), "r"(a[3]), "l"(db), "r"(scaleD));
}
__device__ __forceinline__ void wgmma_rs_n64(float* d, const uint32_t* a, uint64_t db, int scaleD) {
  asm volatile("{\n.reg .pred p;\nsetp.ne.b32 p, %37, 0;\nwgmma.mma_async.sync.aligned.m64n64k16.f32.bf16.bf16 "
    "{%0,%1,%2,%3,%4,%5,%6,%7,%8,%9,%10,%11,%12,%13,%14,%15,%16,%17,%18,%19,%20,%21,%22,%23,%24,%25,%26,%27,%28,%29,%30,%31}, "
    "{%32,%33,%34,%35}, %36, p, 1, 1, 1;\n}\n"
    : "+f"(d[0]), "+f"(d[1]), "+f"(d[2]), "+f"(d[3]), "+f"(d[4]), "+f"(d[5]), "+f"(d[6]), "+f"(d[7]), "+f"(d[8]), "+f"(d[9]), "+f"(d[10]), "+f"(d[11]), "+f"(d[12]), "+f"(d[13]), "+f"(d[14]), "+f"(d[15]), "+f"(d[16]), "+f"(d[17]), "+f"(d[18]), "+f"(d[19]), "+f"(d[20]), "+f"(d[21]), "+f"(d[22]), "+f"(d[23]), "+f"(d[24]), "+f"(d[25]), "+f"(d[26]), "+f"(d[27]), "+f"(d[28]), "+f"(d[29]), "+f"(d[30]), "+f"(d[31])
    : "r"(a[0]), "r"(a[1]), "r"(a[2]), "r"(a[3]), "l"(db), "r"(scaleD));
}

template <int V> struct Int { static constexpr int value = V; };
struct Cur {
  uint32_t s, ph;
  __device__ __forceinline__ void next() { if (++s == NST) { s = 0; ph ^= 1; } }
};

#define z1_block(rb, w, j) (P.s->Z + ((rb) * 16 + (w) * 8 + (j)) * ZB)
#define z2_block(kb, j) (P.s->Z + (256 + (kb) * 8 + (j)) * ZB)
#define o_block(rb, w) (P.s->O + ((rb) * 2 + (w)) * (2 * ZB))
__device__ __forceinline__ void combine8(float m0, float q0, float m1, float q1, float n, float eps, float& mean, float& rstd) {
  mean = qsum(m0 + m1) * 0.125f;
  float d0 = m0 - mean, d1 = m1 - mean;
  float M2 = qsum(q0 + q1 + n * (d0 * d0 + d1 * d1));
  rstd = rsq_fast(fmaf(M2, 0.125f / n, eps));
}
__device__ __forceinline__ void stat_get(const uint4* zs, uint32_t tag, float n, float eps, float& m0, float& r0, float& m1, float& r1) {
  uint4 a0, a1, b0, b1;
#pragma unroll 1
  for (int it = 0; it < (1 << 20); it++) {
    a0 = ll_ld128(zs); a1 = ll_ld128(zs + 64); b0 = ll_ld128(zs + 8); b1 = ll_ld128(zs + 72);
    if (__all_sync(~0u, a0.z == tag && a1.z == tag && b0.z == tag && b1.z == tag)) break;
  }
  combine8(__uint_as_float(a0.x), __uint_as_float(a0.y), __uint_as_float(a1.x), __uint_as_float(a1.y), n, eps, m0, r0);
  combine8(__uint_as_float(b0.x), __uint_as_float(b0.y), __uint_as_float(b1.x), __uint_as_float(b1.y), n, eps, m1, r1);
}

__device__ __forceinline__ void rows_fetch(uint32_t el, uint32_t xr, const uint8_t* src, uint32_t bar) {
  expect_tx_p(el, bar, 9216);
#pragma unroll 1
  for (int r = 0; r < 8; r++) bulk_load_p(el, xr + r * 1152, src + r * (DM * 4), 1152, bar);
}
__device__ __forceinline__ void rows_stats(uint32_t xr, uint4* dst, uint32_t tag, int lane) {
  float s[2] = {0.f, 0.f}, q[4] = {0.f, 0.f, 0.f, 0.f};
  const uint32_t a0 = xr + (lane >> 2) * 1152 + (((lane & 3) * 2) ^ (lane >> 2)) * 16;
  uint4 n0 = lds128(a0), n1 = lds128(a0 ^ 16);
#pragma unroll 1
  for (int e = 1; e <= 9; e++) {
    const uint32_t x[8] = {n0.x, n0.y, n0.z, n0.w, n1.x, n1.y, n1.z, n1.w};
    if (e < 9) { n0 = lds128(a0 + e * 128); n1 = lds128((a0 ^ 16) + e * 128); }
#pragma unroll
    for (int u = 0; u < 8; u++) {
      const float lo = blo(x[u]), hi = bhi(x[u]);
      s[u & 1] += lo + hi; q[(u & 1) * 2] = fmaf(lo, lo, q[(u & 1) * 2]); q[(u & 1) * 2 + 1] = fmaf(hi, hi, q[(u & 1) * 2 + 1]);
    }
  }
  const float sx = s[0] + s[1], sq = (q[0] + q[1]) + (q[2] + q[3]);
  const float m = qsum(sx) * (-1.f / DM), r = rsq_fast(fmaxf(fmaf(qsum(sq), 1.f / DM, -m * m), 0.f) + LN_EPS);
  if ((lane & 3) == 0) ll_st128(dst + (lane >> 2) * 2, m, r, tag);
}

__device__ __forceinline__ void poison(const Params& P, uint32_t el, uint32_t src, const CUtensorMap* m, int rb, int j, int lane) {
#pragma unroll 1
  for (int u = lane; u < 72; u += 32) sts128(src + u * 16, POISON, POISON, POISON, POISON);
  fence_async_s();
  __syncwarp();
#pragma unroll 1
  for (int u = 0; u < 16; u++) {
    __nanosleep(NAP);
    bulk_store_p(el, o_block(rb, u >> 3) + j * 9216 + (u & 7) * 1152, src, 1152);
    asm volatile("{\n.reg .pred P;\nsetp.ne.u32 P, %5, 0;\n@P cp.async.bulk.tensor.3d.global.shared::cta.tile.bulk_group [%0, {%2, %3, %4}], [%1];\n}" ::"l"(m), "r"(src), "r"((j & 6) * 72), "r"(rb * 64 + u * 4), "r"(j & 1), "r"(el) : "memory");
  }
}
__device__ __forceinline__ void mma16acc(float* c, const uint32_t* a, uint32_t b0, uint32_t b1) {
  asm volatile("mma.sync.aligned.m16n8k16.row.col.f32.bf16.bf16.f32 {%0,%1,%2,%3}, {%4,%5,%6,%7}, {%8,%9}, {%0,%1,%2,%3};"
               : "+f"(c[0]), "+f"(c[1]), "+f"(c[2]), "+f"(c[3]) : "r"(a[0]), "r"(a[1]), "r"(a[2]), "r"(a[3]), "r"(b0), "r"(b1));
}
template <int KS, int NG, int AK, int AH, int BK, int BG, class F> __device__ __forceinline__ void redo(float* acc, const uint8_t* pa, const uint8_t* pb, F f) {
#pragma unroll 1
  for (int k = 0; k < 36; k += KS) {
    uint32_t a[4 * KS], b[2 * KS][NG];
#pragma unroll 1
    for (int it = 0; it < (1 << 20); it++) {
      bool ok = true;
#pragma unroll
      for (int e = 0; e < 4 * KS; e++) a[e] = ldgpu32(pa + (e >> 1) * AK + (e & 1) * AH);
#pragma unroll
      for (int e = 0; e < 2 * KS * NG; e++) b[e / NG][e % NG] = ldca32(pb + (e / NG) * BK + (e % NG) * BG);
#pragma unroll
      for (int e = 0; e < 4 * KS; e++) ok = ok && a[e] != POISON;
      if (__all_sync(~0u, ok)) break;
    }
#pragma unroll
    for (int e = 0; e < KS; e++) f(a + 4 * e, k + e);
#pragma unroll
    for (int e = 0; e < KS * NG; e++) mma16acc(acc + 4 * (e % NG), a + 4 * (e / NG), movm(b[2 * (e / NG)][e % NG]), movm(b[2 * (e / NG) + 1][e % NG]));
    pa += 2 * KS * AK; pb += 2 * KS * BK;
  }
}
__device__ __forceinline__ bool any_nan(float a, float b) {
  return __any_sync(~0u, a != a || b != b);
}

__global__ void __cluster_dims__(2, 1, 1) __launch_bounds__(384, 1) mega_kernel(const __grid_constant__ Params P) {
  extern __shared__ __align__(1024) uint8_t smem_raw[];
  uint32_t ckk[8];
  (void)ckk;
  CKK(0);
  const uint32_t sb = smem_u32(smem_raw);
  const uint32_t bars = sb + SM_BAR;
  const int tid = threadIdx.x;
  int lane = tid & 31;
  const int wid = __shfl_sync(~0u, tid >> 5, 0);
  const int cl = blockIdx.x >> 1, tp = cl - 36, t7 = (tp * 37) >> 8;
  const int bid = (cl < 4 ? cl * 8 + 32 : tp < 0 ? cl - 4 : cl < 64 ? tp + t7 + 33 : cl) * 2 + (blockIdx.x & 1);
  if (bid >= NCTA) return;
  const int rb = bid & 15, j = bid >> 4;
  { const bool tr = (tid & 127) == 0 && tid < 256; const int w = tid >> 7; (void)tr; (void)w; TRC(tr, w, 0); }
  CKK(1);
  uint4 wv[5];
  const uint8_t* wsrc;
  {
    const int n8 = min(tid >> 3, 26), part = n8 / 9;
    const uint8_t* src = (const uint8_t*)P.wqkv + (8 * rb + (tid & 7)) * (3 * DM * 2) + (part * (DM - 72) + 72 * j + 8 * n8) * 2;
#pragma unroll
    for (int u = 0; u < SPL; u++) wv[u] = ldnc128_if(tid < 216, src + u * (128 * 3 * DM * 2));
    wsrc = src;
  }
  CKK(2);
  if (tid == 352) {
#pragma unroll
    for (int e = 0; e < 16; e++) mbar_init(bars + B_FULL + e * 8, (e >> 2) == 1 ? 16 : 1);
    mbar_init(bars + B_RES + 8, 8); mbar_init(bars + B_WT, 1); mbar_init(bars + B_WT + 8, 1); mbar_init(bars + B_IMG, 9);
    asm volatile("fence.mbarrier_init.release.cluster;" ::: "memory");
  }
  __syncthreads();

  if (wid >= 8) {
    reg_dealloc<40>();
    const uint32_t el = elect_one();
    const uint64_t pol = policy_evict_first();
    uint32_t* const fj = P.s->flags + FJ + j * 32;
    if (wid == 8) {
      if (lane == 0) {
        mbar_init(bars + B_RES, 1); mbar_init(bars + B_WOI, 1); mbar_init(bars + B_ZB, 1); mbar_init(bars + B_GATE3, 3); mbar_init(bars + B_Z1, 1); mbar_init(bars + B_LAG, 4);
#pragma unroll
        for (int e = B_RT; e < B_XS + 16; e += 8) mbar_init(bars + e, e >= B_AD && e < B_EVT ? 2 : (e >= B_EVT && e < B_RT1) || (e >= B_EA3 && e < B_XS) ? 4 : 1);
        asm volatile("fence.mbarrier_init.release.cluster;" ::: "memory");
        mbar_arrive(bars + B_IMG);
      }
      __syncwarp();
#pragma unroll 1
      for (int i = 0; i < 12; i++) if (el) prefetch_map(&P.act[0] + (i < 7 ? i : i - 12));
      const uint32_t epoch = ldcg32(fj + FJ_EP + rb);
      Cur c{0, 1};
      const uint32_t rk = bid & 1;
      TRC(el, 2, 34);
      uint32_t st, full;
      auto slot = [&](uint32_t bytes) {
        st = sb + c.s * ST_BYTES; full = bars + B_FULL + c.s * 8;
        mbar_wait(full, c.ph);
        expect_tx_p(el, full, bytes);
        mbar_wait(full - B_FULL + B_EMPTY, c.ph);
      };
#pragma unroll 1
      for (int L = 0; L < 2; L++) {
#pragma unroll 1
        for (int i = 0; i < 14; i++) {
          if (L == 0 && (i == 0 || i == 2 * SPL || i == 9)) {
            flag_wait(fj + (i == 9 ? FJ_WO : i == 2 * SPL ? FJ_WQ : FJ_WQ0), (epoch + 1) * 16);
            if (i == 9) flag_wait(P.s->flags + FJ + (j ^ 1) * 32 + FJ_WO, (epoch + 1) * 16);
            fence_async_g();
            TRC(el, 2, i == 9 ? 46 : i ? 47 : 45);
          }
          const uint32_t hb = i < 9 ? 13824 : i < 13 ? 18432 : 9216, o = ST_B + rk * (i < 9 ? 13824 : 18432);
          const uint8_t* src = i < 9 ? P.s->WQ + j * WQ_SL + i * 27648 + rk * 13824 : P.s->WO + ((j & 6) + rk) * WO_SL + (i - 9) * 18432;
          slot(2 * hb);
          bulk_mc_h(el, st + o, src, hb, full, true, pol);
          c.next();
        }
#pragma unroll 1
        for (int i = 0; i < 18; i++) {
          const int p = i >> 1, col = p == 4 ? (9 * j + ((j & 1) ? 0 : 8)) * 32 : (((9 * j + 1) >> 1) + (p < 4 ? p + 36 : p - 5)) * 64;
          if (i & 1) {
            slot(2 * ZB);
          } else {
            st = sb + c.s * ST_BYTES; full = bars + B_FULL + ((c.s + 1) & 3) * 8;
            mbar_wait(bars + B_EMPTY + c.s * 8, c.ph);
          }
          tma4d_mc(el, st + ST_B + rk * 18432, p == 4 ? &P.win : &P.win64, col, (i & 1) * 36 + rk * 18, full, pol);
          if (el && !(i & 1)) mbar_arrive(bars + B_FULL + c.s * 8);
          c.next();
        }
        TRC(el, 2, L * 16 + 6);
        flag_wait(fj + FJ_ZN + L, (epoch + 1) * 16);
        fence_async_g();
        TRC(el, 2, L * 16 + 7);
#pragma unroll 1
        for (int i = 0; i < 32; i++) {
          const uint8_t* src = z2_block(i, j) + rk * 18432;
          if (i >= 4) mbar_wait(bars + B_AD + c.s * 8, ((i >> 2) & 1) ^ 1);
          slot(ST_BYTES);
          bulk_mc_h(el, st + ST_B + rk * 18432, src, 18432, full, true, pol);
          tma3d_h(el, st, &P.wsp, i * 64, rb * 64, 0, full, true, pol);
          c.next();
        }
        mbar_wait(bars + B_Z1, L);
        fence_async_g();
        expect_tx_p(el, bars + B_ZB, 26624);
#pragma unroll 1
        for (int i = 0; i < 10; i++) {
          const int cb = i - 1 + j;
          if (i < 4) mbar_wait(bars + B_AD + c.s * 8, 1);
          slot(i ? ZB : 26624);
          if (i == 0) {
            bulk_load_h(el, st, z1_block(rb, 0, j), 26624, bars + B_ZB, true, pol);
            bulk_load_h(el, st + 26624, z1_block(rb, 1, j), 26624, full, true, pol);
          } else {
            tma2d_mc_h(el, st + ST_B + rk * 18432, &P.wout, (cb >= 9 ? cb - 9 : cb) * 64, 288 * j + rk * 144, full, true, pol);
          }
          c.next();
        }
      }
    } else if (wid < 11) {
      int w = wid - 9;
      TRC(el && w == 0, 2, 35);
      uint32_t* const fr = P.s->flags + (rb * 2 + w) * 32;
      const uint32_t epoch = ldcg32(fr + FR_EP + j);
      const uint32_t ev = bars + B_EVT + w * EV_N * 8, t8 = (epoch + 1) * 8;
      Cur c{0, 1};
#pragma unroll 1
      for (int L = 0; L < 2; L++) {
        {
          uint32_t tag = t8;
          asm volatile("" : "+r"(tag));
          tag = (tag >> 2) - 1 + L;
          uint4* const xs = P.s->XST + (rb * 2 + w) * 128;
          if (L) {
            mbar_wait(ev + EV_PT * 8, 0);
            TRC(el, 3, w * 32 + 16);
            flag_release_p(el, fr + FR_X2);
            TRC(el, 3, w * 32 + 17);
          }
#pragma unroll 1
          for (int i = 0; i < 9; i++) {
            const uint32_t full = bars + B_FULLA + w * 32 + c.s * 8, dst = sb + c.s * ST_BYTES + w * 8192;
            if (L == 0 && i == 4) {
              mbar_wait(bars + B_WT + w * 8, 0);
              TRC(el && w == 0, 2, 37);
              rows_stats(sb + SM_STG + w * 9216, xs + 16 * j, tag, lane);
              TRC(el && w == 0, 2, 38);
            }
            const uint32_t src = sb + (L ? 2 * ST_BYTES + SM_WOI : SM_STG + w * 9216);
            if (i == 4) {
#pragma unroll
              for (int u = 0; u < 6; u++) sts128(src + u * 512 + lane * 16, POISON, POISON, POISON, POISON);
              fence_async_s();
              __syncwarp();
            }
            mbar_wait(bars + B_EMPTY + c.s * 8, c.ph);
            expect_tx_p(el, full, 8192);
            if (i < L) { flag_wait(fr + FR_X2, t8); fence_async_g(); }
            tma3d_h(el, dst, &P.act[L], i * 64, rb * 64, w, full, false, pol);
            TRC(el && i < L, 3, w * 32 + 18);
            TRC(el && i + L + w == 0, 2, 36);
            c.next();
            if (i >= 4 && i < (L ? 5 : 8)) {
              int b = (rb * 2 + w) * 8 + j;
              asm volatile("" : "+r"(b));
              bulk_store_p(el, i == 4 ? (uint8_t*)P.s->HALO + b * 3072 : P.s->O + (b * 3 + i - 5) * 3072, src, 3072);
              if (i < 6) bulk_store_p(el, (i == 4 ? P.s->ST1 : P.s->ZST) + b * 64, src, 1024);
              if (i == 6) bulk_store_p(el, P.s->RT + b * 8, src, 64);
            }
            if (L == 0 && i == 3) rows_fetch(el, sb + SM_STG + w * 9216, P.xs[0] + (128 * rb + 16 * j + w) * (DM * 2), bars + B_WT + w * 8);
          }
          if (el) asm volatile("cp.async.bulk.commit_group;\ncp.async.bulk.wait_group 0;" ::: "memory");
          __syncwarp();
          if (L == 0) fence_gpu();
          const uint32_t tab = sb + L * (2 * ST_BYTES) + SM_XST + w * 512 + lane * 8;
          TRC(el, 3, w * 32 + L * 16 + 13);
#pragma unroll 1
          for (int it = 0; it < (1 << 22); it++) {
            const uint4 a = ll_ld128(xs + 2 * lane), b = ll_ld128(xs + 64 + 2 * lane);
            if (__all_sync(~0u, a.z == tag && b.z == tag)) { sts64(tab, a.x, a.y); sts64(tab + 256, b.x, b.y); break; }
          }
          __syncwarp();
          mbar_arrive_if(el, bars + B_XS + w * 8);
          TRC(el, 3, w * 32 + L * 16 + 14);
          if (w == 1) {
            mbar_wait(bars + B_XS, L);
            expect_tx_p(el, bars + B_RES, 18432);
            tma3d_h(el, sb + SM_STG, &P.res[L], (j & 6) * 72, rb * 64, j & 1, bars + B_RES, !L, pol);
          }
          if (L) flag_wait(fj + FJ_P4, t8 * 4);
        }
        int hp = rb * 2 + (j & 1);
        asm volatile("" : "+r"(w), "+r"(hp));
        uint32_t* const fo = P.s->flags + hp * 32 + L;
        {
          const uint8_t* src = o_block(0, hp) + w * 8192;
#pragma unroll 1
          for (int i = 0; i < 5; i++) {
            const uint32_t full = bars + B_FULLA + w * 32 + c.s * 8, dst = sb + c.s * ST_BYTES + w * 8192;
            const bool none = 2 * i + w > 8;
            mbar_wait(bars + B_EMPTY + c.s * 8, c.ph);
            expect_tx_p(el, full, none ? 0 : 8192);
            if (i == 0) {
              mbar_wait(ev + EV_O * 8, L);
              TRC(el, 3, w * 32 + L * 16 + 3);
              flag_add_p(el, fr + FR_O + L);
              TRC(el, 3, w * 32 + L * 16 + 4);
              flag_wait(fo + FR_O, t8);
              fence_async_g();
            }
            if (!none) bulk_load_h(el, dst, src + i * 16384, 8192, full, true, pol);
            TRC(el && i == 0, 3, w * 32 + L * 16 + 5);
            c.next();
          }
        }
        {
          expect_tx_p(lane < 9, bars + B_FA3 + (9 * w + lane) * 8, 8192);
          mbar_wait(ev + EV_X1 * 8, L);
          TRC(el, 3, w * 32 + L * 16 + 6);
          if (L) flag_add_p(el, fo + FR_X1); else flag_release_p(el, fo + FR_X1);
          mbar_arrive_if(el, bars + B_GATE3);
          TRC(el, 3, w * 32 + L * 16 + 7);
          mbar_arrive_if(lane < 2, bars + B_FULLA + w * 32 + ((c.s + lane) & 3) * 8);
#pragma unroll 1
          for (int kb = 0; kb < 9; kb++) {
            const int n = 9 * w + kb;
            const uint32_t dst = sb + ((n >> 1) & 3) * ST_BYTES + (n & 1) * 8192;
            if (kb == 0) { flag_wait(fr + FR_X1 + L, t8); fence_async_g(); }
            if (n >= 8) mbar_wait(bars + B_EA3 + (n - 8) * 8, L);
            tma3d_h(el, dst, &P.act[L + 1], kb * 64, rb * 64, w, bars + B_FA3 + n * 8, false, pol);
            TRC(el && kb == 0, 3, w * 32 + L * 16 + 8);
          }
          c.ph ^= ((c.s + 18) >> 2) & 1; c.s = (c.s + 18) & 3;
        }
        asm volatile("" : "+r"(lane), "+r"(w));
        expect_tx_p(el, bars + B_WT + w * 8, 2048);
#pragma unroll 1
        for (int r = 0; r < 8; r++)
          bulk_load_p(el, sb + SM_WT + w * 2176 + r * 272, (const uint8_t*)P.w_sp + (size_t)(128 * rb + 16 * j + 2 * r + w) * (SEQ * 2) + 30 * 128, 256, bars + B_WT + w * 8);
        float cv = (lane & 3) ? 0.f : -blo(ldnc16(P.b_sp + 128 * rb + 16 * j + 2 * (lane >> 2) + w));
        mbar_wait(bars + B_RT, L);
        mbar_wait(bars + B_WT + w * 8, L ^ 1);
        mbar_wait(ev + EV_Z1 * 8, L);
        const uint32_t ro = (w * 64 + 8 * j + (lane >> 2)) * 128, x0 = ((lane & 3) * 2) ^ (lane >> 2);
#pragma unroll 1
        for (int i = 0; i < 32; i++) {
          const bool tail = (i >> 1) == 4;
          const int kb = tail ? i + 22 : i < 8 ? i : i - 2;
          if (i == 8) mbar_wait(bars + B_RT1, L);
          if (!tail) mbar_wait(bars + B_FULL + c.s * 8, c.ph ^ 1);
#pragma unroll
          for (int e = 0; e < 2; e++) {
            const uint4 a = lds128(!tail ? sb + c.s * ST_BYTES + ro + ((x0 ^ e) << 4) : sb + SM_WT + w * 2176 + (lane >> 2) * 272 + (i - 8) * 128 + (lane & 3) * 32 + e * 16);
            const uint4 m = lds128(sb + SM_RT + 4096 + kb * 128 + (lane & 3) * 32 + e * 16);
            cv = fmaf(blo(a.x), blo(m.x), fmaf(bhi(a.x), bhi(m.x), fmaf(blo(a.y), blo(m.y), fmaf(bhi(a.y), bhi(m.y), cv))));
            cv = fmaf(blo(a.z), blo(m.z), fmaf(bhi(a.z), bhi(m.z), fmaf(blo(a.w), blo(m.w), fmaf(bhi(a.w), bhi(m.w), cv))));
          }
          if (!tail) {
            mbar_arrive_if(el, bars + B_AD + c.s * 8 + (__float_as_uint(cv) & P.zero));
            c.next();
          }
        }
        TRC(el, 3, w * 32 + L * 16 + 11);
        uint32_t tag = t8;
        asm volatile("" : "+r"(tag));
        tag = (tag >> 2) - 1 + L;
        cv = qsum(cv);
        uint2* const cs = (uint2*)(P.s->XST + (rb * 2 + w) * 128 + 1);
        if ((lane & 3) == 0) ll_st64(cs + 32 * j + (lane >> 2) * 4, __float_as_uint(cv), tag);
#pragma unroll 1
        for (int it = 0; it < (1 << 22); it++) {
          const uint2 a = ll_ld64(cs + 4 * lane), b = ll_ld64(cs + 128 + 4 * lane);
          if (__all_sync(~0u, a.y == tag && b.y == tag)) { sts32(sb + SM_CV + w * 256 + lane * 4, a.x); sts32(sb + SM_CV + w * 256 + 128 + lane * 4, b.x); break; }
        }
        __syncwarp();
        if (el) mbar_arrive(bars + B_CV + w * 8);
        TRC(el, 3, w * 32 + L * 16 + 12);
#pragma unroll 1
        for (int kb = 30; kb < 32; kb++) {
          mbar_wait(bars + B_FULL + c.s * 8, c.ph ^ 1);
          if (el) mbar_arrive(bars + B_AD + c.s * 8);
          c.next();
        }
        c.ph ^= ((c.s + 10) >> 2) & 1; c.s = (c.s + 10) & 3;
        if (L == 0) {
          mbar_wait(ev + EV_P4 * 8, 0);
          flag_add_p(el, fj + FJ_P4);
          flag_add_p(el, fr + FR_EP + j);
        }
      }
    } else {
      const uint32_t epoch = ldcg32(fj + FJ_EP + rb);
      TRC(el, 2, 33);
      if (SPL) {
        mbar_wait(bars + B_RES + 8, 0);
        TRC(el, 2, 41);
        flag_release_p(el, fj + FJ_WQ0);
        TRC(el, 2, 42);
      }
      mbar_wait(bars + B_IMG, 0);
      TRC(el, 2, 39);
      flag_release_p(el, fj + FJ_WQ);
      TRC(el, 2, 40);
#pragma unroll 1
      for (int L = 0; L < 2; L++) {
        auto wo_fetch = [&]() {
          expect_tx_p(el, bars + B_WOI, 5760);
          asm volatile("{\n.reg .pred P;\nsetp.ne.u32 P, %5, 0;\n@P cp.async.bulk.tensor.4d.shared::cluster.global.mbarrier::complete_tx::bytes [%0], [%1, {0, 0, %3, %4}], [%2];\n}" ::"r"(sb + SM_WOI), "l"(&P.wo8), "r"(bars + B_WOI), "r"(9 * j), "r"((9 * rb) >> 1), "r"(el) : "memory");
        };
        float* const csf = P.s->CSP + (NCTA + bid) * 216;
        if (L == 0) {
          flag_wait(fj + FJ_WQ, (epoch + 1) * 16);
          fence_async_g();
          expect_tx_p(el, bars + B_XRW, 13824);
          bulk_load_p(el, sb + ST_BYTES + SM_WOI, P.s->CSP + j * 16 * 216, 6912, bars + B_XRW);
          bulk_load_p(el, sb + 2 * ST_BYTES + SM_WOI, P.s->CSP + (j * 16 + 8) * 216, 6912, bars + B_XRW);
          wo_fetch();
          mbar_wait(bars + B_XRW, 0);
#pragma unroll 1
          for (int f = lane; f < 54; f += 32) {
            float s[4] = {0.f, 0.f, 0.f, 0.f};
#pragma unroll 4
            for (int r = 0; r < 16; r++) {
              const uint4 v = lds128(sb + ST_BYTES + SM_WOI + (r >> 3) * ST_BYTES + (r & 7) * 864 + f * 16);
              s[0] += __uint_as_float(v.x); s[1] += __uint_as_float(v.y); s[2] += __uint_as_float(v.z); s[3] += __uint_as_float(v.w);
            }
            sts128(sb + SM_CSQ + f * 16, __float_as_uint(s[0]), __float_as_uint(s[1]), __float_as_uint(s[2]), __float_as_uint(s[3]));
            stg128(csf + f * 4, __float_as_uint(s[0]), __float_as_uint(s[1]), __float_as_uint(s[2]), __float_as_uint(s[3]));
          }
          __syncwarp();
          mbar_arrive_if(el, bars + B_CSQ);
        } else {
#pragma unroll 1
          for (int u = 0; u < 4; u++) {
            const int w = u & 1;
            if (u < 2) {
              flag_wait(P.s->flags + (rb * 2 + w) * 32 + FR_X2, (epoch + 1) * 8);
              fence_async_g();
              TRC(el, 2, 48 + u);
              rows_fetch(el, sb + SM_STG + w * 9216, P.xs[1] + (128 * rb + 16 * j + w) * (DM * 2), bars + B_XRW + w * 8);
            } else {
              if (u == 2) {
                expect_tx_p(el, bars + B_CSQ, 864);
                bulk_load_p(el, sb + 2 * ST_BYTES + SM_CSQ, csf, 864, bars + B_CSQ);
              }
              mbar_wait(bars + B_XRW + w * 8, w ^ 1);
              TRC(el, 2, 48 + u);
              rows_stats(sb + SM_STG + w * 9216, P.s->XST + (rb * 2 + w) * 128 + 16 * j, epoch * 2 + 2, lane);
              TRC(el, 2, 50 + u);
            }
          }
        }
        if (L == 0) {
          TRC(el, 2, 43);
          mbar_wait(bars + B_WOI, 0);
          bulk_store_p(el, P.s->WO + j * WO_SL + ((9 * rb) >> 1) * 1152, sb + SM_WOI, 5760);
          publish_p(el, fj + FJ_WO);
          TRC(el, 2, 44);
          const uint8_t* sp = lane < 16 ? (const uint8_t*)P.w_in + (30 * lane + 50) * (FH * 4) + FH * 2 + lane * 256 : (const uint8_t*)P.w_sp + (60 * lane) * (SEQ * 2) + lane * 64;
          float sq = 0.f;
#pragma unroll 1
          for (int u = 0; u < 4; u++) {
            const uint4 y = ldnc128(sp + u * 16);
            const uint32_t x[4] = {y.x, y.y, y.z, y.w};
#pragma unroll
            for (int e = 0; e < 4; e++) sq = fmaf(blo(x[e]), blo(x[e]), fmaf(bhi(x[e]), bhi(x[e]), sq));
          }
#pragma unroll 1
          for (int o = 8; o; o >>= 1) sq += __shfl_xor_sync(~0u, sq, o);
          sq *= lane < 16 ? 2.f * GA * GA * DM / 512.f : C0S * C0S * SEQ / 512.f;
          asm("sqrt.approx.f32 %0, %0;" : "+f"(sq));
          const float o0 = __shfl_sync(~0u, sq, 0), o1 = __shfl_sync(~0u, sq, 16);
          const float p2 = __uint_as_float(min(__float_as_uint(o0) & 0x7f800000u, 0x7e000000u)) * OFK, off = -p2 - fminf(OFA, 0.5f * p2);
          if (el) sts64(sb + SM_OFF, pack2(off, off), min(__float_as_uint(o1) & 0x7f800000u, 0x7e000000u) | 0x00400000u);
        }
        if (el) mbar_arrive(bars + B_GATE3);
        const uint32_t tag = epoch * 2 + L + 1;
        asm volatile("" : "+r"(lane));
        mbar_wait(bars + B_EVT + EV_ZN * 8, L);
        mbar_wait(bars + B_EVT + (EV_N + EV_ZN) * 8, L);
        flag_release_p(el, fj + FJ_ZN + L);
        TRC(el, 2, L * 16 + 8);
        {
          uint4 v[4];
#pragma unroll 1
          for (int it = 0; it < (1 << 22); it++) {
            bool ok = true;
#pragma unroll
            for (int u = 0; u < 4; u++) { v[u] = ll_ld128(P.s->ZST + (rb * 2 + ((lane >> 1) & 1)) * 512 + ((lane & 1) * 4 + u) * 64 + 8 * j + (lane >> 2)); ok = ok && v[u].z == tag; }
            if (__all_sync(~0u, ok)) break;
          }
          float mean = __uint_as_float(v[0].x) + __uint_as_float(v[1].x) + __uint_as_float(v[2].x) + __uint_as_float(v[3].x), M2 = 0.f;
          mean = (mean + __shfl_xor_sync(~0u, mean, 1)) * 0.125f;
#pragma unroll
          for (int u = 0; u < 4; u++) { const float d = __uint_as_float(v[u].x) - mean; M2 += fmaf(288.f * d, d, __uint_as_float(v[u].y)); }
          M2 += __shfl_xor_sync(~0u, M2, 1);
          const float rs = blo(pack2(rsq_fast(fmaf(M2, 1.f / FH, 4.f * GA * GA * LN_EPS)), 0.f));
          if (!(lane & 1)) ll_st64(P.s->RT + 128 * rb + 16 * j + (lane >> 1), pack2(rs, rs * mean), tag);
        }
        TRC(el, 2, L * 16 + 10);
#pragma unroll 1
        for (int b = 0; b < 8; b++) {
          uint4 v[4];
#pragma unroll 1
          for (int it = 0; it < (1 << 22); it++) {
            bool ok = true;
#pragma unroll
            for (int u = 0; u < 4; u++) { v[u] = ll_ld128((const uint4*)P.s->RT + b * 128 + u * 32 + lane); ok = ok && v[u].y == tag && v[u].w == tag; }
            if (__all_sync(~0u, ok)) break;
          }
#pragma unroll
          for (int u = 0; u < 4; u++) {
            const uint32_t rt = sb + SM_RT + b * 512 + u * 128, ro = (lane >> 3) * 32 + (lane & 3) * 8 + ((lane >> 2) & 1) * 2;
            sts32(rt + 4096 + lane * 4, __byte_perm(v[u].x, v[u].z, 0x7632));
            asm volatile("st.shared.u16 [%0], %1;\nst.shared.u16 [%0 + 4], %2;" ::"r"(rt + ro), "h"((uint16_t)v[u].x), "h"((uint16_t)v[u].z) : "memory");
          }
          __syncwarp();
          if (el && (b == 1 || b == 7)) mbar_arrive(bars + (b == 1 ? B_RT : B_RT1));
          TRC(el && b < 2, 2, L * 16 + 11 + b);
        }
        TRC(el, 2, L * 16 + 9);
        mbar_wait(bars + B_EVT + EV_Z1 * 8, L);
        mbar_wait(bars + B_EVT + (EV_N + EV_Z1) * 8, L);
        fence_gpu();
        if (el) mbar_arrive(bars + B_Z1);
        if (L == 0) {
          flag_add_p(el, fj + FJ_EP + rb);
          __nanosleep(NAP0);
          poison(P, el, sb + SM_STG + 17152, &P.psn, rb, j, lane);
          if (el) asm volatile("cp.async.bulk.commit_group;\ncp.async.bulk.wait_group 0;" ::: "memory");
          __syncwarp();
          fence_gpu();
        }
      }
    }
  } else {
    CKK(3);
    uint8_t* const wdst = P.s->WQ + j * WQ_SL + rb * 3456 + tid * 16;
#pragma unroll
    for (int u = 0; u < SPL; u++) stg128_if(tid < 216, wdst + u * (16 * 3456), wv[u].x, wv[u].y, wv[u].z, wv[u].w);
    __syncwarp();
    if (lane == 0) mbar_arrive(bars + B_RES + 8);
    CKK(4);
    auto repack2 = [&]() {
#pragma unroll
      for (int u = SPL; u < 5; u++) stg128_if((u < 4 || rb < 8) && tid < 216, wdst + u * (16 * 3456), wv[u].x, wv[u].y, wv[u].z, wv[u].w);
      float s[8];
#pragma unroll
      for (int e = 0; e < 8; e++) s[e] = 0.f;
#pragma unroll
      for (int u = 0; u < 5; u++) {
        uint32_t x[4] = {wv[u].x, wv[u].y, wv[u].z, wv[u].w};
        asm volatile("" : "+r"(x[0]), "+r"(x[1]), "+r"(x[2]), "+r"(x[3]));
#pragma unroll
        for (int e = 0; e < 4; e++) { s[2 * e] += blo(x[e]); s[2 * e + 1] += bhi(x[e]); }
      }
#pragma unroll
      for (int m = 4; m; m >>= 1) {
#pragma unroll
        for (int e = 0; e < m; e++) s[e] = ((tid & m) ? s[e + m] : s[e]) + __shfl_xor_sync(~0u, (tid & m) ? s[e] : s[e + m], m);
      }
      stg32_if(tid < 216, P.s->CSP + bid * 216 + tid, __float_as_uint(s[0]));
      __syncwarp();
      if (lane == 0) mbar_arrive(bars + B_IMG);
    };
    reg_alloc<232>();
    CKK(5);
#pragma unroll
    for (int v = SPL; v < 5; v++) wv[v] = ldnc128_if(tid < 216 && (v < 4 || rb < 8), wsrc + v * (128 * 3 * DM * 2));
    repack2();
    CKK(6);
    const int w = wid >> 2, q = wid & 3;
    int g = lane >> 2, t = lane & 3;
    const uint32_t ev = bars + B_EVT + w * EV_N * 8;
    const bool tr = (tid & 127) == 0;
    (void)tr;
    Cur c{0, 0};
    const uint32_t ebar = mapa(bars + B_EMPTY, (bid & 1) ^ (lane & 1));
    auto release = [&](uint32_t s, uint32_t dep = 0) { mbar_arrive_cluster_if(lane < 2, ebar + s * 8 + dep); };
    auto release_if = [&](bool on, uint32_t s) { mbar_arrive_cluster_if(lane < 2 && on, ebar + s * 8); };
    uint32_t ia = 0;
    auto wait_ab = [&]() { mbar_wait_c(bars + B_FULL + c.s * 8, c.ph); mbar_wait_c(bars + B_FULLA + w * 32 + c.s * 8, (ia >> 2) & 1); ia++; };

    auto yield_done = [&]() { if (w == 0 && lane == 0) mbar_arrive(bars + B_LAG); };
    auto signal = [&](int e) { __syncwarp(); mbar_arrive_if(lane == 0, ev + e * 8); };

    const uint32_t epoch = ldcg32(P.s->flags + (rb * 2 + w) * 32 + FR_EP + j);
    TRC(tr, w, 1);
    CKK(7);
    if (PAD && P.zero) {
#pragma unroll
      for (int i = 0; i < PAD; i++) asm volatile("st.shared.u32 [%0], %1;" ::"r"(sb + i * 20), "r"(tid) : "memory");
    }
    CKK_OUT;

#pragma unroll 1
    for (int L = 0; L < 2; L++) {
      const int tb = 2 + L * 24;
      asm volatile("" : "+r"(lane), "+r"(g), "+r"(t));
      (void)tb;
      ia = 0;
      const uint32_t tag = epoch * 2 + L + 1;
      uint32_t aoff = (w * 64 + q * 16 + (lane & 15)) * 128 + (((lane >> 4) ^ (lane & 7)) << 4);
      {
        uint32_t Pk[27][2];
        float sc0, sc1;
        const uint32_t att = sb + w * 8192 + q * 2048 + lane * 4;
        uint4* hp = P.s->HALO + ((((rb - (q == 0)) * 2 + w) * 8 + j) * 6) * 32 + lane;
        uint8_t* od = o_block(rb, w) + (9 * j) * 1024 + (2 * q) * 128 + lane * 4;
        ACLK_INIT;
        {
          float acc[108];
#pragma unroll
          for (int i = 0; i < 108; i++) acc[i] = 0.f;
          uint32_t prev = 0;
#pragma unroll 1
          for (int kb = 0; kb < 9; kb++) {
            wait_ab();
            if (w == 1 && kb == 9 - LAG1) mbar_wait_c(bars + B_LAG, L);
            TRC(tr && kb == 0, w, tb + 0);
            MCLK(kb == 0, 0);
            PCLK(kb * 4);
            const uint32_t st = sb + c.s * ST_BYTES;
            uint64_t da = dsc2(dlo(st + w * 8192, 16), 0, 0x40000040u + P.zero), db = dsc2(dlo(st + ST_B, 3456), 0, 8 ^ P.zero);
            wgmma_fence();
#pragma unroll
            for (int kk = 0; kk < 4; kk++) {
              wgmma_ss_n216(acc, da, db, 1);
              dadd(da, 2); dadd(db, 432);
              if (kk == 0) { wgmma_commit(); wgmma_wait<1>(); release_if(kb > 0, prev); }
            }
            wgmma_commit();
            if (kb == 8) yield_done();
            PCLK(kb * 4 + 1);
            PCLK(kb * 4 + 2);
            PCLK(kb * 4 + 3);
            prev = c.s; c.next();
          }
          const uint32_t cs = sb + prev * ST_BYTES + SM_CSQ + t * 8;
          mbar_wait_c(bars + B_CSQ, L);
          mbar_wait_c(bars + B_XS + w * 8, L);
          const float2 n0 = lds64f(sb + prev * ST_BYTES + SM_XST + w * 512 + (16 * q + g) * 8), n1 = lds64f(sb + prev * ST_BYTES + SM_XST + w * 512 + (16 * q + g + 8) * 8);
          const float m0 = n0.x, r0 = n0.y, m1 = n1.x, r1 = n1.y;
          float2 cv[27];
#pragma unroll
          for (int G = 0; G < 27; G++) cv[G] = lds64f(cs + G * 32);
          PCLK(36);
          wgmma_wait<0>();
          PCLK(37);
          {
            uint32_t dep = P.zero & __float_as_uint(m0) & __float_as_uint(m1);
#pragma unroll
            for (int G = 0; G < 27; G++) dep &= __float_as_uint(cv[G].x);
            release(prev, dep);
          }
          TRC(tr, w, tb + 1);
          MCLK(1, 1);
          ACLK(0);
#pragma unroll
          for (int G = 9; G < 27; G++) Pk[G][1] = pack2(fmaf(m1, cv[G].x, acc[4 * G + 2]) * r1, fmaf(m1, cv[G].y, acc[4 * G + 3]) * r1);
          if (q < 3) {
#pragma unroll
            for (int i = 0; i < 18; i++) sts32(att + (i >> 4) * ST_BYTES + (i & 15) * 128, Pk[9 + i][1]);
          } else if (rb < 15) {
#pragma unroll
            for (int i = 0; i < 6; i++) ll_st128(hp + i * 32, __uint_as_float(Pk[9 + 3 * i][1]), __uint_as_float(Pk[10 + 3 * i][1]), tag, __uint_as_float(Pk[11 + 3 * i][1]));
          }
#pragma unroll
          for (int G = 0; G < 27; G++) {
            if (G < 9) {
              Pk[G][0] = pack2(fmaf(m0, cv[G].x, acc[4 * G]), fmaf(m0, cv[G].y, acc[4 * G + 1]));
              Pk[G][1] = pack2(fmaf(m1, cv[G].x, acc[4 * G + 2]), fmaf(m1, cv[G].y, acc[4 * G + 3]));
            } else {
              Pk[G][0] = pack2(fmaf(m0, cv[G].x, acc[4 * G]) * r0, fmaf(m0, cv[G].y, acc[4 * G + 1]) * r0);
            }
          }
          sc0 = r0 * (0.23570226039551584f * 1.4426950408889634f); sc1 = r1 * (0.23570226039551584f * 1.4426950408889634f);
        }
        ACLK(1);
        constexpr int GA_[4] = {0, 2, 4, 7}, GB_[4] = {1, 3, 5, 8}, GC_[4] = {2, 4, 6, 6};
        float S1[4][4], S2[4][4];
        uint32_t qa[4][2], qc[4][2];
#pragma unroll
        for (int h = 0; h < 4; h++) {
#pragma unroll
          for (int r = 0; r < 2; r++) {
            qa[h][r] = (h == 0 || h == 3 || t >= h) ? Pk[GA_[h]][r] : 0u;
            qc[h][r] = (h == 3 ? t == 3 : t <= h) ? Pk[GC_[h]][r] : 0u;
          }
          mma16(S1[h], qa[h][0], qa[h][1], Pk[GB_[h]][0], Pk[GB_[h]][1], Pk[9 + GA_[h]][0], Pk[9 + GB_[h]][0]);
          mma16(S2[h], qa[h][0], qa[h][1], Pk[GB_[h]][0], Pk[GB_[h]][1], Pk[9 + GA_[h]][1], Pk[9 + GB_[h]][1]);
        }
#pragma unroll
        for (int h = 0; h < 4; h++) {
          mma8(S1[h], qc[h][0], qc[h][1], Pk[9 + GC_[h]][0]);
          mma8(S2[h], qc[h][0], qc[h][1], Pk[9 + GC_[h]][1]);
        }
        uint32_t V1[9], V2[9];
#pragma unroll
        for (int i = 0; i < 9; i++) { V1[i] = movm(Pk[18 + i][0]); V2[i] = movm(Pk[18 + i][1]); }
        const bool remote = q == 0 && rb > 0;
        uint4 hv[6];
#pragma unroll
        for (int i = 0; i < 6; i++) hv[i] = make_uint4(0u, 0u, tag, 0u);
        if (remote) {
#pragma unroll
          for (int i = 0; i < 6; i++) hv[i] = ll_ld128(hp + i * 32);
        }
        const bool up0 = 2 * t > g, up1 = 2 * t + 1 > g;
        const uint32_t mup = (up0 ? 0xffffu : 0u) | (up1 ? 0xffff0000u : 0u);
        auto finish = [&](const float (&x0)[4], const float (&x1)[4], uint32_t ma, const uint32_t (&Vb)[9], int hi) {
          uint32_t pa[4], pb[4];
          float rs[4];
#pragma unroll
          for (int h = 0; h < 4; h++) {
            const float m = qmax(fmaxf(x0[h], x1[h]));
            const uint32_t p = pack2(ex2(x0[h] - m), ex2(x1[h] - m));
            pa[h] = p & ma; pb[h] = p & ~ma;
          }
#pragma unroll
          for (int h = 0; h < 4; h += 2) {
            float R[4];
            mma16(R, pa[h], pa[h + 1], pb[h], pb[h + 1], 0x3f803f80u, 0x3f803f80u);
            rs[h] = rcp_fast(R[0]); rs[h + 1] = rcp_fast(R[2]);
          }
#pragma unroll
          for (int i = 0; i < 9; i++) {
            const int h = 4 * i / 9, e = (h & 1) * 2;
            const bool split = i == 2 || i == 4 || i == 6, nx = split && 2 * t >= i;
            float O[4], N[4];
            mma16(O, pa[h & 2], pa[h | 1], pb[h & 2], pb[h | 1], V1[i], Vb[i]);
            if (i == 4) mma16(N, pa[2], pa[3], pb[2], pb[3], V1[i], Vb[i]); else { N[0] = O[2]; N[1] = O[3]; }
            const float r = nx ? rs[h + (split ? 1 : 0)] : rs[h];
            stg32(od + i * 1024 + hi * 128, pack2((nx ? N[0] : O[e]) * r, (nx ? N[1] : O[e + 1]) * r));
          }
        };
        {
          float x0[4], x1[4];
#pragma unroll
          for (int h = 0; h < 4; h++) { x0[h] = (up0 ? S1[h][2] : S2[h][2]) * sc1; x1[h] = (up1 ? S1[h][3] : S2[h][3]) * sc1; }
          finish(x0, x1, mup, V2, 1);
        }
        ACLK(2);
        bar_sync(1 + w, 128);
        uint32_t H[18];
        if (q > 0) {
#pragma unroll
          for (int i = 0; i < 18; i++) H[i] = lds32(att - 2048 + (i >> 4) * ST_BYTES + (i & 15) * 128);
        } else {
#pragma unroll 1
          for (int it = 0; it < (1 << 20); it++) {
            bool ok = true;
#pragma unroll
            for (int i = 0; i < 6; i++) ok = ok && hv[i].z == tag;
            if (__all_sync(~0u, ok)) break;
#pragma unroll
            for (int i = 0; i < 6; i++) hv[i] = ll_ld128(hp + i * 32);
          }
#pragma unroll
          for (int i = 0; i < 6; i++) { H[3 * i] = hv[i].x; H[3 * i + 1] = hv[i].y; H[3 * i + 2] = hv[i].w; }
        }
        float S0[4][4];
#pragma unroll
        for (int h = 0; h < 4; h++) {
          mma16(S0[h], qa[h][0], qa[h][1], Pk[GB_[h]][0], Pk[GB_[h]][1], H[GA_[h]], H[GB_[h]]);
        }
#pragma unroll
        for (int h = 0; h < 4; h++) mma8(S0[h], qc[h][0], qc[h][1], H[GC_[h]]);
        uint32_t V0[9];
#pragma unroll
        for (int i = 0; i < 9; i++) V0[i] = movm(H[9 + i]);
        ACLK(3);
        {
          const bool nohalo = (rb | q) == 0;
          const float b0 = up0 && nohalo ? -INFINITY : 0.f, b1 = up1 && nohalo ? -INFINITY : 0.f;
          float x0[4], x1[4];
#pragma unroll
          for (int h = 0; h < 4; h++) { x0[h] = fmaf(up0 ? S0[h][0] : S1[h][0], sc0, b0); x1[h] = fmaf(up1 ? S0[h][1] : S1[h][1], sc0, b1); }
          finish(x0, x1, ~mup, V0, 0);
        }
        ACLK(4);
        signal(EV_O);
        ACLK_OUT;
        TRC(tr, w, tb + 2);
        MCLK(1, 2);
      }
      {
        float acc[36];
        const int hw = rb * 2 + (j & 1), js = (j & 6) + w;
        const uint32_t xt = sb + SM_STG + (16 * q + (lane & 15)) * 288 + (9 * w + (lane >> 4)) * 16, eye = (g >> 1) == t ? 0x3f80u << (g & 1) * 16 : 0u;
        uint32_t xm = xt ^ ((lane & 4) << 2), xl = sb + SM_STG + (2 * q + w) * 2304;
        uint32_t xl0 = xl + (lane >> 4) * 288 + (lane & 15) * 16, xl1 = xl + ((lane >> 1) & 7) * 288 + 256 + ((lane ^ (lane >> 3)) & 1) * 16;
        uint8_t* xd0 = P.xs[L + 1] + (128 * rb + 32 * q + 16 * w + (j & 1)) * (DM * 2) + (j & 6) * 144;
        uint8_t* xd1 = xd0 + (lane >> 1) * (DM * 4) + 256 + (lane & 1) * 16;
        xd0 += (lane >> 4) * (DM * 4) + (lane & 15) * 16;
        asm volatile("" : "+r"(xm), "+r"(xl0), "+r"(xl1), "+l"(xd0), "+l"(xd1));
        mbar_wait_c(bars + B_RES, L);
        TRC(tr, w, tb + 21);
#pragma unroll
        for (int u = 0; u < 5; u++) {
          uint32_t r[4];
          ldsm4(r, xt + u * 32);
          widen(acc + 8 * u, r[0], r[1], eye);
          if (u < 4) widen(acc + 8 * u + 4, r[2], r[3], eye);
        }
        uint32_t prev = 0;
#pragma unroll 1
        for (int u = 0; u < 5; u++) {
          const uint32_t st = sb + c.s * ST_BYTES;
          uint64_t da = dsc2(dlo(st, 1024), 0, 8 + P.zero), db = dsc2(dlo(st + ST_B + w * 18432, 1152), 0, 8 ^ P.zero);
          mbar_wait_c(bars + B_FULL + c.s * 8, c.ph); mbar_wait_c(bars + B_FULLA + c.s * 8, (ia >> 2) & 1);
          TRC(tr && u == 0, w, tb + 3);
          MCLK(u == 0, 3);
          wgmma_fence();
#pragma unroll
          for (int kk = 0; kk < 4; kk++) { wgmma_ss_n72(acc, da, db, 1); dadd(da, 128); dadd(db, 144); }
          wgmma_commit();
          wgmma_wait<1>();
          release_if(u > 0, prev);
          mbar_wait_c(bars + B_FULLA + 32 + c.s * 8, (ia >> 2) & 1);
          ia++;
          if (u == 4) break;
          wgmma_fence();
#pragma unroll
          for (int kk = 4; kk < 8; kk++) { wgmma_ss_n72(acc, da, db, 1); dadd(da, 128); dadd(db, 144); }
          wgmma_commit();
          prev = c.s; c.next();
        }
        RCLK_INIT;
        wgmma_wait<0>();
        RCLK(0);
        release(c.s);
        c.next();
        if (__builtin_expect(any_nan(acc[0], acc[2]), 0)) {
          SLOW(L);
          const uint8_t* xr = P.xs[L] + (128 * rb + 32 * q + 2 * g + (j & 1)) * (DM * 2) + js * 144 + t * 4;
#pragma unroll
          for (int i = 0; i < 9; i++) widen(acc + 4 * i, ldgpu32(xr + i * 16), ldgpu32(xr + i * 16 + DM * 32), eye);
          redo<KS2, 9, 1024, 128, 1152, 128>(acc, o_block(rb, j & 1) + q * 256 + lane * 4, P.s->WO + js * WO_SL + lane * 4, [](uint32_t*, int) {});
        }
        TRC(tr && P5TRACE != 5, w, tb + 4);
        MCLK(1, 4);
#pragma unroll
        for (int u = 0; u < 4; u++)
          stsm4(xm + u * 32, pack2(acc[8 * u], acc[8 * u + 1]), pack2(acc[8 * u + 2], acc[8 * u + 3]), pack2(acc[8 * u + 4], acc[8 * u + 5]), pack2(acc[8 * u + 6], acc[8 * u + 7]));
        asm volatile("stmatrix.sync.aligned.m8n8.x2.shared.b16 [%0], {%1,%2};" ::"r"(xm + 128), "r"(pack2(acc[32], acc[33])), "r"(pack2(acc[34], acc[35])) : "memory");
        auto stats = [&]() {
          float s0 = 0.f, s1 = 0.f, q0 = 0.f, q1 = 0.f;
#pragma unroll
          for (int i = 0; i < 36; i++) {
            if (i & 2) { s1 += acc[i]; q1 = fmaf(acc[i], acc[i], q1); } else { s0 += acc[i]; q0 = fmaf(acc[i], acc[i], q0); }
          }
          s0 = qsum(s0); s1 = qsum(s1); q0 = qsum(q0); q1 = qsum(q1);
          const float ss = t ? s1 : s0, m = ss * (1.f / 72.f);
          ll_st128_if(t < 2, P.s->ST1 + (hw * 8 + js) * 64 + 16 * q + 8 * t + g, m, fmaxf((t ? q1 : q0) - ss * m, 0.f), tag);
        };
        stats();
        RCLK(1);
        bar_sync(8 + q, 64);
        RCLK(2);
#pragma unroll
        for (int u = 0; u < 5; u++) {
          const uint4 v = lds128(u < 4 ? (xl0 ^ ((u & 2) << 3)) + u * 576 : xl1);
          stg128_if(u < 4 || lane < 16, u < 4 ? xd0 + u * (DM * 8) : xd1, v.x, v.y, v.z, v.w);
        }
        RCLK(3);
        signal(EV_X1);
        RCLK(4);
        RCLK(5);
        TRC(tr, w, tb + 5);
        RCLK(6);
        RCLK_OUT;
      }
      uint32_t zk[16];
      {
        uint32_t xA[36][4];
        float acc[32];
        uint32_t s0, one, off2;
        uint8_t *z1d, *zd;
        uint64_t db;
        auto bwait = [&](uint32_t dhi, bool skip) {
          s0 = c.s;
          c.next();
          if (!skip) mbar_wait_c(bars + B_FULL + c.s * 8, c.ph);
          db = dsc2(dlo(sb + s0 * ST_BYTES + ST_B, 512) - 3, 0, dhi); one = (c.s ^ P.zero) & 1;
        };
        auto mma = [&](int kk, int pp, bool hand) {
          wgmma_rs_n64(acc, xA[kk], dat(db, (kk / 18) * ST_BYTES + (kk % 18) * 2048 + 48, one), kk != 0);
          if (kk == pp && hand) bar_arrive(7 - w, 256);
          if (kk == 17 || kk == 35) wgmma_commit();
          if (kk == RL3) { wgmma_commit(); wgmma_wait<1>(); release(s0); }
        };
        {
          bwait(0x40000040u, false);
          mbar_wait_c(bars + B_GATE3, L);
          float mean0, mean1, rs0, rs1;
          stat_get(P.s->ST1 + ((rb * 2 + w) * 8 + 2 * t) * 64 + 16 * q + g, tag, 72.f, LN_EPS, mean0, rs0, mean1, rs1);
          const uint32_t ns0 = pack2(GA * rs0, GA * rs0), ns1 = pack2(GA * rs1, GA * rs1);
          const uint32_t nb0 = pack2(-mean0 * blo(ns0), -mean0 * blo(ns0)), nb1 = pack2(-mean1 * blo(ns1), -mean1 * blo(ns1));
          const uint32_t al = sb + (aoff & 8191);
#pragma unroll
          for (int kb = 0; kb <= 9; kb++) {
            if (kb < 9) {
              mbar_wait_c(bars + B_FA3 + (9 * w + kb) * 8, L);
              TRC(tr && kb == 0, w, tb + 6);
              MCLK(kb == 0, 5);
              if (kb == 0) SCLK(0);
              QCLK(kb);
              const uint32_t at = al + (w ? (((kb + 1) >> 1) & 3) * ST_BYTES + ((kb + 1) & 1) * 8192 : ((kb >> 1) & 3) * ST_BYTES + (kb & 1) * 8192);
#pragma unroll
              for (int kk = 4 * kb; kk < 4 * kb + 4; kk++) ldsm4(xA[kk], at ^ ((kk & 3) << 5));
            }
            if (kb == 0) continue;
            const uint32_t dep = xA[4 * kb - 4][0] & xA[4 * kb - 3][0] & xA[4 * kb - 2][0] & xA[4 * kb - 1][0] & P.zero;
            mbar_arrive_if(lane == 0 && (kb == 1 || w == 0), bars + B_EA3 + (9 * w + kb - 1) * 8 + dep);
#pragma unroll
            for (int kk = 4 * kb - 4; kk < 4 * kb; kk++) {
#pragma unroll
              for (int e = 0; e < 4; e++) xA[kk][e] = hfma2(xA[kk][e], (e & 1) ? ns1 : ns0, (e & 1) ? nb1 : nb0);
            }
            wgmma_fence();
#pragma unroll
            for (int kk = 4 * kb - 4; kk < 4 * kb; kk++) mma(kk, PP30, w);
          }
          off2 = lds32(sb + SM_OFF);
          z1d = z1_block(rb, w, j) + (tid & 127) * 16;
          zd = z2_block(2 * rb + (q >> 1), j) + (4 * (q & 1) + w) * 4608 + ((g & 3) * 2 + (g >> 2)) * 16 + t * 4;
          asm volatile("" : "+l"(z1d), "+l"(zd));
          wgmma_wait<0>();
          if (__builtin_expect(any_nan(acc[0], acc[2]), 0)) {
            SLOW(2 + L);
            uint4* const rd = P.s->RD + bid * (36 * 256) + tid;
            const uint8_t* xr = P.xs[L + 1] + (128 * rb + 32 * q + 2 * g + w) * (DM * 2) + t * 4;
#pragma unroll
            for (int i = 0; i < 32; i++) acc[i] = 0.f;
            redo<KS3, 8, 16, DM * 32, FH * 32, 16>(acc, xr, (const uint8_t*)P.w_in + g * (FH * 4) + (((9 * j + 1) >> 1) + 36) * 128 + t * 4,
                                              [&](uint32_t* a, int k) {
#pragma unroll
                                                for (int e = 0; e < 4; e++) a[e] = hfma2(a[e], (e & 1) ? ns1 : ns0, (e & 1) ? nb1 : nb0);
                                                stg128(rd + k * 256, a[0], a[1], a[2], a[3]);
                                              });
#pragma unroll
            for (int k = 0; k < 36; k++) { const uint4 v = ldcg128(rd + k * 256); xA[k][0] = v.x; xA[k][1] = v.y; xA[k][2] = v.z; xA[k][3] = v.w; }
          }
        }
        float sm[4] = {0.f, 0.f, 0.f, 0.f}, qq[4] = {0.f, 0.f, 0.f, 0.f};
        auto gelu = [&](auto nz2) {
          constexpr int NZ2 = nz2.value, R = 8 - NZ2, N = 8, D = NZ2 == 8 ? GM2 : NZ2 ? GMM : GM1;
          float th[32], gb = GB;
          uint32_t qa = 0, qb = 0;
          auto head = [&](int G) {
#pragma unroll
            for (int e = 0; e < 4; e++) { const float v = acc[4 * G + e]; th[4 * G + e] = tanh_fast(v * fmaf(v, v, gb)); }
          };
#pragma unroll
          for (int i = 0; i < D; i++) head((i + R) & 7);
#pragma unroll
          for (int i = 0; i < N; i++) {
            const int G = (i + R) & 7;
            if (i + D < N) head((i + D + R) & 7);
            float* z = acc + 4 * G;
#pragma unroll
            for (int e = 0; e < 4; e++) z[e] = fmaf(z[e], th[4 * G + e], z[e]);
            uint32_t pa = pack2(z[0], z[1]), pb = pack2(z[2], z[3]), tok;
            if (i < NZ2) {
#pragma unroll
              for (int e = 0; e < 4; e++) { sm[e] += z[e]; qq[e] = fmaf(z[e], z[e], qq[e]); }
              pa = hsub2(pa, off2); pb = hsub2(pb, off2);
              stg32(zd + i * 128, pa); stg32(zd + i * 128 + 9216, pb);
              tok = pa ^ pb ^ __float_as_uint(qq[1]);
            } else {
              if (NZ2 && G == 3) sts128(sb + SM_STG + tid * 16, qa, qb, pa, pb);
              else if (G & 1) stg128(z1d + (G >> 1) * 2048 + (NZ2 ? 24576 : 0), qa, qb, pa, pb);
              qa = pa; qb = pb;
              tok = pa ^ pb;
            }
            gb = __uint_as_float(tok * P.zero + __float_as_uint(GB));
          }
        };
        auto done = [&](int p) {
          wgmma_wait<0>();
          release(c.s);
          c.next();
          TRC(tr && p == 4, w, tb + 7);
          TRC(tr && p == 8, w, tb + 11);
          MCLK(p == 8, 6);
          SCLK(2 * p + 1);
          QCLK(10 + 3 * p);
        };
        auto pass = [&](int p, uint32_t dhi) {
          SCLK(2 * p);
          QCLK(8 + 3 * p);
          bwait(dhi, w);
          bar_sync(6 + w, 256);
          TRC(tr && p == 5, w, tb + 10);
          wgmma_fence();
#pragma unroll
          for (int kk = 0; kk < 36; kk++) mma(kk, PP3, w == 0 || p < 8);
          done(p);
        };
        done(0);
#pragma unroll 1
        for (int p = 1; p < 5; p++) {
          gelu(Int<8>{});
          zd += 1024;
          pass(p, p == 4 ? 0x80000040u : 0x40000040u);
        }
        gelu(Int<4>{});
        signal(EV_ZN);
        {
          const float a0 = qsum(sm[0] + sm[1]), a1 = qsum(sm[2] + sm[3]), q0 = qsum(qq[0] + qq[1]), q1 = qsum(qq[2] + qq[3]);
          const float ss = t ? a1 : a0, m = ss * (1.f / 288.f);
          ll_st128_if(t < 2, P.s->ZST + (rb * 2 + w) * 512 + j * 64 + 16 * q + 8 * t + g, m - blo(off2), fmaxf((t ? q1 : q0) - ss * m, 0.f), tag);
        }
        TRC(tr, w, tb + 8);
        TRC(tr, w, tb + 9);
#pragma unroll 1
        for (int p = 5;; p++) {
          pass(p, 0x40000040u);
          if (p == 8) break;
          gelu(Int<0>{});
          z1d += 8192;
        }
        signal(EV_Z1);
#pragma unroll
        for (int i = 0; i < 16; i++) zk[i] = pack2(acc[2 * i], acc[2 * i + 1]);
        SCLK(18);
        TRC(tr, w, tb + 12);
      }
      uint32_t hA[18][4];
      {
        float acc[144];
        const float c0 = __uint_as_float(lds32(sb + SM_OFF + 4));
#pragma unroll
        for (int i = 0; i < 144; i++) {
          asm volatile("fma.rn.f32 %0, %1, %2, %3;" : "=f"(acc[i]) : "f"(__uint_as_float(P.zero)), "f"((float)(i + 2)), "f"(c0));
        }
        uint32_t prev = 0;
        auto stage = [&](int kb, auto odd) {
          mbar_wait_c(bars + B_FULL + c.s * 8, c.ph);
          TRC(tr && kb == 0, w, tb + 13);
          SCLK(22 + kb);
          const uint32_t st = sb + c.s * ST_BYTES, rt = sb + SM_RT + kb * 128 + t * 8;
          uint64_t db = dsc2(dlo(st + ST_B, 4608), 0, 8 + P.zero);
          uint32_t a[4][4];
#pragma unroll
          for (int kk = 0; kk < 4; kk++) {
            uint32_t r[4];
            ldsm4(r, st + (aoff ^ (kk << 5)));
            const uint2 sc = lds64(rt + kk * 32);
            a[kk][0] = hmul2(__byte_perm(r[0], r[2], 0x5410), sc.x); a[kk][2] = hmul2(__byte_perm(r[0], r[2], 0x7632), sc.y);
            a[kk][1] = hmul2(__byte_perm(r[1], r[3], 0x5410), sc.x); a[kk][3] = hmul2(__byte_perm(r[1], r[3], 0x7632), sc.y);
          }
          if (!odd.value) {
            const float x = blo(zk[0]), y = bhi(zk[0]);
#pragma unroll
            for (int i = 0; i < 15; i++) zk[i] = zk[i + 1];
            zk[15] = pack2(fmaf(x, tanh_fast(x * fmaf(x, x, GB)), x), fmaf(y, tanh_fast(y * fmaf(y, y, GB)), y));
          }
          wgmma_fence();
#pragma unroll
          for (int i = 0; i < 8; i++) {
            const int kk = i & 3, hf = i >> 2;
            wgmma_rs_n144(acc + hf * 72, a[kk], db, 1);
            dadd(db, i == 3 ? 144u - 3 * 576 : 576 + P.zero);
            if (i == 0) { wgmma_commit(); wgmma_wait<1>(); release_if(kb, prev); }
            if (i == 3) wgmma_commit();
          }
          wgmma_commit();
          prev = c.s; c.next();
        };
        mbar_wait_c(bars + B_RT, L);
#pragma unroll 1
        for (int kb = 0; kb < 32; kb += 2) {
          if (kb == 8) mbar_wait_c(bars + B_RT1, L);
          MCLK((kb & 7) == 4, 10 + (kb >> 3));
          stage(kb, Int<0>{});
          stage(kb + 1, Int<1>{});
        }
        if (w == 1) bar_arrive(6, 256);
        HCLK(0);
        mbar_wait_c(bars + B_CV + w * 8, L);
        HCLK(1);
        const float gk = 0.5f / GA;
        const float c1 = __uint_as_float(lds32(sb + SM_OFF + 4));
        const float gb0 = -gk * (c1 + __uint_as_float(lds32(sb + SM_CV + w * 256 + (16 * q + g) * 4))), gb1 = -gk * (c1 + __uint_as_float(lds32(sb + SM_CV + w * 256 + (16 * q + g + 8) * 4)));
        mbar_wait_c(w ? bars + B_FULL + c.s * 8 : bars + B_ZB, w ? c.ph : L);
        HCLK(2);
        const uint32_t sx = c.s;
        c.next();
        const uint32_t zt = sb + tid * 16, zs = zt + sx * ST_BYTES + w * 24576;
        uint4 zz[18];
        auto zload = [&](int u) {
          if (ZW && u == ZW && P.zero) __nanosleep(0);
          if (u >= 12 && u < 16) zz[u] = make_uint4(zk[4 * u - 48], zk[4 * u - 47], zk[4 * u - 46], zk[4 * u - 45]); else zz[u] = lds128(u == 17 ? zt + SM_STG : zs + (u < 12 ? u : 12) * 2048);
        };
#pragma unroll
        for (int u = 0; u < ZA; u++) zload(u);
#pragma unroll
        for (int u = 0; u < 18; u++) {
          if (u == 0) { wgmma_wait<1>(); HCLK(3); }
          if (u == 9) {
            HCLK(4);
            wgmma_wait<0>();
            HCLK(5);
            release(prev);
            mbar_arrive_if(L == 0 && lane == 0, ev + EV_P4 * 8);
            TRC(tr, w, tb + 14);
            SCLK(54);
          }
          if (u + ZA < 18) zload(u + ZA);
          const uint4 z = zz[u];
          hA[u][0] = hmul2(z.x, pack2(fmaf(acc[8 * u], gk, gb0), fmaf(acc[8 * u + 1], gk, gb0)));
          hA[u][1] = hmul2(z.y, pack2(fmaf(acc[8 * u + 2], gk, gb1), fmaf(acc[8 * u + 3], gk, gb1)));
          hA[u][2] = hmul2(z.z, pack2(fmaf(acc[8 * u + 4], gk, gb0), fmaf(acc[8 * u + 5], gk, gb0)));
          hA[u][3] = hmul2(z.w, pack2(fmaf(acc[8 * u + 6], gk, gb1), fmaf(acc[8 * u + 7], gk, gb1)));
        }
        uint32_t dep = P.zero;
#pragma unroll
        for (int u = 0; u < 18; u++) dep &= hA[u][0];
        release(sx, dep);
        TRC(tr, w, tb + 15);
        HCLK(6);
      }
      {
        const uint32_t el = elect_one();
#pragma unroll 1
        for (int p = 0; p < 9; p++) {
          float acc[32];
          if (w == 0) mbar_wait_c(bars + B_FULL + c.s * 8, c.ph);
          uint64_t db = dsc2(dlo(sb + c.s * ST_BYTES + ST_B + (j & 1) * 4096, 0), 0, 0x40000040u + P.zero);
          HCLK(7 + 2 * p);
          bar_sync(6 + w, 256);
          wgmma_fence();
#pragma unroll
          for (int kk = 0; kk < 18; kk++) {
            wgmma_rs_n64(acc, hA[kk], db, kk != 0);
            dadd(db, kk == 15 ? 128 - (j & 1) * (36864 >> 4) : 128 + P.zero);
            if (kk == PPK && (w == 0 || p < 8)) bar_arrive(7 - w, 256);
          }
          wgmma_commit();
          const uint32_t d = sb + (p & 3) * ST_BYTES, cb = p + j >= 9 ? p + j - 9 : p + j;
          if (el) asm volatile("cp.async.bulk.wait_group.read 3;" ::: "memory");
          __syncwarp();
          wgmma_wait<0>();
          HCLK(8 + 2 * p);
          MCLK(p == 1 || p == 8, 7 + (p >> 3));
          TRC(tr && p == 8, w, tb + 16);
          release_if(L == 0 || p < 5, c.s);
          c.next();
#pragma unroll
          for (int u = 0; u < 4; u++)
            stsm4(d + (aoff ^ (u << 5)), pack2(acc[8 * u], acc[8 * u + 1]), pack2(acc[8 * u + 2], acc[8 * u + 3]), pack2(acc[8 * u + 4], acc[8 * u + 5]), pack2(acc[8 * u + 6], acc[8 * u + 7]));
          fence_async_s();
          __syncwarp();
          tma3d_red_p(el, &P.red[L], cb * 64, rb * 64 + q * 16, w, d + w * 8192 + q * 2048);
          TRC(tr && p == 8, w, tb + 17);
        }
        if (el) asm volatile("cp.async.bulk.wait_group 0;" ::: "memory");
        HCLK(25);
        MCLK(1, 9);
        if (L == 0) signal(EV_PT);
        TRC(tr, w, tb + 18);
      }
    }
  }
}

typedef CUresult (*EncodeFn)(CUtensorMap*, CUtensorMapDataType, cuuint32_t, void*, const cuuint64_t*, const cuuint64_t*, const cuuint32_t*,
                             const cuuint32_t*, CUtensorMapInterleave, CUtensorMapSwizzle, CUtensorMapL2promotion, CUtensorMapFloatOOBfill);

static void make_map(EncodeFn fn, CUtensorMap* m, const void* ptr, int rank, uint64_t d0, uint64_t d1, uint64_t d2, uint64_t s1, uint64_t s2,
                     uint32_t b0, uint32_t b1, uint32_t b2, CUtensorMapSwizzle swz) {
  cuuint64_t dims[3] = {d0, d1, d2}, strides[2] = {s1, s2};
  cuuint32_t box[3] = {b0, b1, b2}, es[3] = {1, 1, 1};
  fn(m, CU_TENSOR_MAP_DATA_TYPE_BFLOAT16, rank, const_cast<void*>(ptr), dims, strides, box, es, CU_TENSOR_MAP_INTERLEAVE_NONE, swz,
     CU_TENSOR_MAP_L2_PROMOTION_L2_128B, CU_TENSOR_MAP_FLOAT_OOB_FILL_NONE);
}

}

extern "C" void kernel_launch(void* const* d_in, const int* in_sizes, int n_in, void* d_out, int out_size) {
  using namespace mk;
  (void)in_sizes; (void)n_in; (void)out_size;
  static EncodeFn fn = nullptr;
  static Scratch* sc;
  if (!fn) {
    cudaGetSymbolAddress((void**)&sc, g_scratch);
    cudaDriverEntryPointQueryResult qr;
    cudaGetDriverEntryPoint("cuTensorMapEncodeTiled", (void**)&fn, cudaEnableDefault, &qr);
    cudaFuncSetAttribute(mega_kernel, cudaFuncAttributeMaxDynamicSharedMemorySize, SM_TOTAL);
  }
  Params p;
  p.wqkv = (const __nv_bfloat16*)d_in[1];
  p.w_in = (const __nv_bfloat16*)d_in[4];
  p.w_sp = (const __nv_bfloat16*)d_in[5];
  p.b_sp = (const __nv_bfloat16*)d_in[6];
  p.w_out = (const __nv_bfloat16*)d_in[7];
  p.zero = 0;
  p.s = sc;
  p.xs[0] = (uint8_t*)d_in[0];
  p.xs[1] = sc->X;
  p.xs[2] = (uint8_t*)d_out;
  make_map(fn, &p.wsp, p.w_sp, 3, 2048, 1024, 2, 8192, 4096, 64, 64, 2, CU_TENSOR_MAP_SWIZZLE_128B);
  for (int i = 0; i < 2; i++) {
    make_map(fn, &p.red[i], p.xs[i + 1], 3, DM, 1024, 2, 2304, 1152, 64, 16, 1, CU_TENSOR_MAP_SWIZZLE_128B);
    make_map(fn, &p.res[i], p.xs[i], 3, DM, 1024, 2, 2304, 1152, 144, 64, 1, CU_TENSOR_MAP_SWIZZLE_NONE);
  }
  make_map(fn, &p.psn, d_out, 3, DM, 1024, 2, 2304, 1152, 144, 4, 1, CU_TENSOR_MAP_SWIZZLE_NONE);
  for (int i = 0; i < 3; i++) make_map(fn, &p.act[i], p.xs[i], 3, DM, 1024, 2, 2304, 1152, 64, 64, 1, CU_TENSOR_MAP_SWIZZLE_128B);
  {
    cuuint64_t dims[4] = {8, 8, 72, 72}, strides[3] = {1152, 16, 9216};
    cuuint32_t box[4] = {8, 8, 9, 5}, es[4] = {1, 1, 1, 1};
    fn(&p.wo8, CU_TENSOR_MAP_DATA_TYPE_BFLOAT16, 4, d_in[2], dims, strides, box, es, CU_TENSOR_MAP_INTERLEAVE_NONE, CU_TENSOR_MAP_SWIZZLE_NONE,
       CU_TENSOR_MAP_L2_PROMOTION_L2_128B, CU_TENSOR_MAP_FLOAT_OOB_FILL_NONE);
  }
  for (int i = 0; i < 2; i++) {
    cuuint64_t dims[4] = {i ? 4608u : 2304u, 8, i ? 1u : 2u, 72}, strides[3] = {9216, 4608, 8 * 9216};
    cuuint32_t box[4] = {i ? 64u : 32u, 8, i ? 1u : 2u, 18}, es[4] = {1, 1, 1, 1};
    fn(i ? &p.win64 : &p.win, CU_TENSOR_MAP_DATA_TYPE_BFLOAT16, 4, d_in[4], dims, strides, box, es, CU_TENSOR_MAP_INTERLEAVE_NONE,
       i ? CU_TENSOR_MAP_SWIZZLE_128B : CU_TENSOR_MAP_SWIZZLE_64B, CU_TENSOR_MAP_L2_PROMOTION_L2_128B, CU_TENSOR_MAP_FLOAT_OOB_FILL_NONE);
  }
  make_map(fn, &p.wout, p.w_out, 2, 576, 2304, 1, 1152, 0, 64, 144, 1, CU_TENSOR_MAP_SWIZZLE_128B);
  mega_kernel<<<NGRID, 384, SM_TOTAL, cudaStreamPerThread>>>(p);
}
```

```cpp
#include <cuda_runtime.h>
#include <cuda.h>
#include <cuda_bf16.h>
#include <stdint.h>

#define MK_TRACE 0
#define MK_DBG 0
#define P5TRACE 0
#define LAG1 3
#define PP3 32
#define PP30 33
#define SPL 2
#define NAP 200
#define NAP0 8000
#define KS2 1
#define KS3 1
#define RL3 21
#define PAD 0
#define ZA 4
#define ZW 10
#define GA3 10
#define GB3 12
#define GM2 1
#define GMM 1
#define GM1 2
#define C0S 32.f
#define OFA 0.125f
#define OFK 2.f
#define PPK 15

namespace mk {

constexpr int SEQ = 2048, DM = 576, FH = 2304;
constexpr int NCTA = 128;
constexpr int NGRID = 132;
constexpr uint32_t ZB = 36864;
constexpr uint32_t WQ_SL = 72 * 3456;
constexpr uint32_t WO_SL = 72 * 1152;
constexpr float LN_EPS = 1e-5f;
constexpr float GA = 0.3292034911525734f, GB = 2.423681954311584f;

constexpr uint32_t ST_BYTES = 53248, ST_B = 16384, NST = 4;
constexpr uint32_t SM_STG = NST * ST_BYTES;
constexpr uint32_t SM_BAR = SM_STG + 2 * 9216;
constexpr uint32_t SM_OFF = SM_BAR + 1008;
constexpr uint32_t SM_TOTAL = SM_BAR + 1024;
constexpr uint32_t SM_RT = SM_STG + 4096, SM_CV = SM_STG + 12288, SM_WT = SM_CV + 512;
constexpr uint32_t SM_WOI = 44032, SM_CSQ = 49792, SM_XST = 50688;
constexpr uint32_t B_FULL = 0, B_EMPTY = 32, B_FULLA = 64, B_RES = 128, B_WT = 144, B_IMG = 160, B_WOI = 168, B_ZB = 176, B_GATE3 = 184, B_Z1 = 192, B_LAG = 200,
                   B_RT = 208, B_CSQ = 216, B_CV = 224, B_AD = 240, B_EVT = 272, B_RT1 = 368, B_XS = 624, B_XRW = 384, B_FA3 = 400, B_EA3 = 544;
enum { EV_PT = 0, EV_O = 1, EV_X1 = 2, EV_ZN = 3, EV_Z1 = 4, EV_P4 = 5, EV_N = 6 };

enum { FR_X2 = 0, FR_O = 1, FR_X1 = 3, FR_EP = 16, FJ = 32 * 32, FJ_WQ = 0, FJ_WO = 1, FJ_WQ0 = 2, FJ_ZN = 3, FJ_P4 = 5, FJ_EP = 16, F_N = FJ + 8 * 32 };

constexpr uint32_t POISON = 0xffffffffu;
struct Scratch {
  uint32_t flags[F_N];
  uint2 RT[SEQ];
  uint4 XST[2 * SEQ];
  uint4 ST1[SEQ * 8], ZST[SEQ * 8], HALO[32 * 8 * 6 * 32];
  float CSP[2 * NCTA * 216];
  uint8_t WQ[8 * WQ_SL], WO[8 * WO_SL];
  uint8_t O[32 * 2 * ZB];
  uint8_t X[SEQ * DM * 2];
  uint8_t Z[512 * ZB];
  uint4 RD[NCTA * 36 * 256];
};
__device__ __align__(1024) Scratch g_scratch;
#define SLOW(i) do {} while (0)

struct Params {
  const __nv_bfloat16 *wqkv;
  Scratch* s;
  uint32_t zero;
  const __nv_bfloat16 *w_in, *w_sp, *b_sp, *w_out;
  uint8_t* xs[3];
  CUtensorMap wo8, wsp, win, win64, wout;
  CUtensorMap act[3];
  CUtensorMap res[2];
  CUtensorMap red[2];
  CUtensorMap psn;
};

__device__ __forceinline__ uint32_t smem_u32(const void* p) { return (uint32_t)__cvta_generic_to_shared(p); }
__device__ __forceinline__ void mbar_init(uint32_t bar, uint32_t cnt) { asm volatile("mbarrier.init.shared::cta.b64 [%0], %1;" ::"r"(bar), "r"(cnt)); }
__device__ __forceinline__ void mbar_arrive(uint32_t bar) { asm volatile("mbarrier.arrive.shared::cta.b64 _, [%0];" ::"r"(bar) : "memory"); }
__device__ __forceinline__ void mbar_wait(uint32_t bar, uint32_t parity) {
  asm volatile(
      "{\n.reg .pred p;\n.reg .u32 c;\nmov.u32 c, 0;\nLAB_WAIT:\n"
      "mbarrier.try_wait.parity.shared::cta.b64 p, [%0], %1;\n@p bra LAB_DONE;\n"
      "add.u32 c, c, 1;\nsetp.lt.u32 p, c, 0x100000;\n@p bra LAB_WAIT;\ntrap;\nLAB_DONE:\n}" ::"r"(bar), "r"(parity)
      : "memory");
}
__device__ __forceinline__ void mbar_wait_c(uint32_t bar, uint32_t parity) {
  asm volatile("{\n.reg .pred p;\nLAB_WAIT:\nmbarrier.try_wait.parity.shared::cta.b64 p, [%0], %1;\n@!p bra LAB_WAIT;\n}" ::"r"(bar), "r"(parity) : "memory");
}
__device__ __forceinline__ void flag_wait(const uint32_t* f, uint32_t target) {
  asm volatile(
      "{\n.reg .pred p;\n.reg .u32 c, v;\nmov.u32 c, 0;\nLAB_WAIT:\n"
      "ld.relaxed.gpu.global.u32 v, [%0];\nsub.u32 v, v, %1;\nsetp.ge.s32 p, v, 0;\n@p bra LAB_DONE;\n"
      "add.u32 c, c, 1;\nsetp.lt.u32 p, c, 0x400000;\n@p bra LAB_WAIT;\ntrap;\nLAB_DONE:\nfence.acquire.gpu;\n}" ::"l"(f), "r"(target)
      : "memory");
}
__device__ __forceinline__ void fence_gpu() { asm volatile("fence.acq_rel.gpu;" ::: "memory"); }
__device__ __forceinline__ void fence_async_g() { asm volatile("fence.proxy.async.global;" ::: "memory"); }
__device__ __forceinline__ void fence_async_s() { asm volatile("fence.proxy.async.shared::cta;" ::: "memory"); }
__device__ __forceinline__ uint32_t elect_one() {
  uint32_t p; asm volatile("{\n.reg .pred P;\nelect.sync _|P, 0xffffffff;\nselp.u32 %0, 1, 0, P;\n}" : "=r"(p)); return p;
}
__device__ __forceinline__ void expect_tx_p(uint32_t el, uint32_t bar, uint32_t bytes) {
  asm volatile("{\n.reg .pred P;\nsetp.ne.u32 P, %2, 0;\n@P mbarrier.arrive.expect_tx.shared::cta.b64 _, [%0], %1;\n}" ::"r"(bar), "r"(bytes), "r"(el) : "memory");
}
__device__ __forceinline__ void bulk_load_p(uint32_t el, uint32_t dst, const void* src, uint32_t bytes, uint32_t bar) {
  asm volatile("{\n.reg .pred P;\nsetp.ne.u32 P, %4, 0;\n@P cp.async.bulk.shared::cluster.global.mbarrier::complete_tx::bytes [%0], [%1], %2, [%3];\n}" ::"r"(dst), "l"(src), "r"(bytes), "r"(bar), "r"(el) : "memory");
}
__device__ __forceinline__ uint64_t policy_evict_first() { uint64_t p; asm("createpolicy.fractional.L2::evict_first.b64 %0, 1.0;" : "=l"(p)); return p; }
__device__ __forceinline__ void bulk_load_h(uint32_t el, uint32_t dst, const void* src, uint32_t bytes, uint32_t bar, bool ef, uint64_t pol) {
  if (ef) {
    asm volatile("{\n.reg .pred P;\nsetp.ne.u32 P, %4, 0;\n@P cp.async.bulk.shared::cluster.global.mbarrier::complete_tx::bytes.L2::cache_hint [%0], [%1], %2, [%3], %5;\n}" ::"r"(dst), "l"(src), "r"(bytes), "r"(bar), "r"(el), "l"(pol) : "memory");
  } else {
    asm volatile("{\n.reg .pred P;\nsetp.ne.u32 P, %4, 0;\n@P cp.async.bulk.shared::cluster.global.mbarrier::complete_tx::bytes [%0], [%1], %2, [%3];\n}" ::"r"(dst), "l"(src), "r"(bytes), "r"(bar), "r"(el) : "memory");
  }
}
__device__ __forceinline__ void bulk_mc_h(uint32_t el, uint32_t dst, const void* src, uint32_t bytes, uint32_t bar, bool ef, uint64_t pol) {
  if (ef) {
    asm volatile("{\n.reg .pred P;\nsetp.ne.u32 P, %4, 0;\n@P cp.async.bulk.shared::cluster.global.mbarrier::complete_tx::bytes.multicast::cluster.L2::cache_hint [%0], [%1], %2, [%3], %5, %6;\n}" ::"r"(dst), "l"(src), "r"(bytes), "r"(bar), "r"(el), "h"((uint16_t)3), "l"(pol) : "memory");
  } else {
    asm volatile("{\n.reg .pred P;\nsetp.ne.u32 P, %4, 0;\n@P cp.async.bulk.shared::cluster.global.mbarrier::complete_tx::bytes.multicast::cluster [%0], [%1], %2, [%3], %5;\n}" ::"r"(dst), "l"(src), "r"(bytes), "r"(bar), "r"(el), "h"((uint16_t)3) : "memory");
  }
}
__device__ __forceinline__ void tma3d_h(uint32_t el, uint32_t dst, const CUtensorMap* m, int c0, int c1, int c2, uint32_t bar, bool ef, uint64_t pol) {
  if (ef) {
    asm volatile("{\n.reg .pred P;\nsetp.ne.u32 P, %6, 0;\n@P cp.async.bulk.tensor.3d.shared::cluster.global.mbarrier::complete_tx::bytes.L2::cache_hint [%0], [%1, {%3, %4, %5}], [%2], %7;\n}" ::"r"(dst), "l"(m), "r"(bar), "r"(c0), "r"(c1), "r"(c2), "r"(el), "l"(pol) : "memory");
  } else {
    asm volatile("{\n.reg .pred P;\nsetp.ne.u32 P, %6, 0;\n@P cp.async.bulk.tensor.3d.shared::cluster.global.mbarrier::complete_tx::bytes [%0], [%1, {%3, %4, %5}], [%2];\n}" ::"r"(dst), "l"(m), "r"(bar), "r"(c0), "r"(c1), "r"(c2), "r"(el) : "memory");
  }
}
__device__ __forceinline__ void tma2d_mc_h(uint32_t el, uint32_t dst, const CUtensorMap* m, int c0, int c1, uint32_t bar, bool ef, uint64_t pol) {
  if (ef) {
    asm volatile("{\n.reg .pred P;\nsetp.ne.u32 P, %5, 0;\n@P cp.async.bulk.tensor.2d.shared::cluster.global.mbarrier::complete_tx::bytes.multicast::cluster.L2::cache_hint [%0], [%1, {%3, %4}], [%2], %6, %7;\n}" ::"r"(dst), "l"(m), "r"(bar), "r"(c0), "r"(c1), "r"(el), "h"((uint16_t)3), "l"(pol) : "memory");
  } else {
    asm volatile("{\n.reg .pred P;\nsetp.ne.u32 P, %5, 0;\n@P cp.async.bulk.tensor.2d.shared::cluster.global.mbarrier::complete_tx::bytes.multicast::cluster [%0], [%1, {%3, %4}], [%2], %6;\n}" ::"r"(dst), "l"(m), "r"(bar), "r"(c0), "r"(c1), "r"(el), "h"((uint16_t)3) : "memory");
  }
}
__device__ __forceinline__ void tma4d_mc(uint32_t el, uint32_t dst, const CUtensorMap* m, int c0, int c3, uint32_t bar, uint64_t pol) {
  asm volatile("{\n.reg .pred P;\nsetp.ne.u32 P, %5, 0;\n@P cp.async.bulk.tensor.4d.shared::cluster.global.mbarrier::complete_tx::bytes.multicast::cluster.L2::cache_hint [%0], [%1, {%3, 0, 0, %4}], [%2], %6, %7;\n}" ::"r"(dst), "l"(m), "r"(bar), "r"(c0), "r"(c3), "r"(el), "h"((uint16_t)3), "l"(pol) : "memory");
}
__device__ __forceinline__ void mbar_arrive_cluster(uint32_t addr) { asm volatile("mbarrier.arrive.shared::cluster.b64 _, [%0];" ::"r"(addr) : "memory"); }
__device__ __forceinline__ void mbar_arrive_cluster_if(bool c, uint32_t addr) {
  asm volatile("{\n.reg .pred P;\nsetp.ne.u32 P, %1, 0;\n@P mbarrier.arrive.shared::cluster.b64 _, [%0];\n}" ::"r"(addr), "r"((uint32_t)c) : "memory");
}
__device__ __forceinline__ void mbar_arrive_if(bool c, uint32_t addr) {
  asm volatile("{\n.reg .pred P;\nsetp.ne.u32 P, %1, 0;\n@P mbarrier.arrive.shared::cta.b64 _, [%0];\n}" ::"r"(addr), "r"((uint32_t)c) : "memory");
}
__device__ __forceinline__ uint32_t mapa(uint32_t addr, uint32_t rank) { uint32_t r; asm("mapa.shared::cluster.u32 %0, %1, %2;" : "=r"(r) : "r"(addr), "r"(rank)); return r; }
__device__ __forceinline__ void bulk_store_p(uint32_t el, void* dst, uint32_t src, uint32_t bytes) {
  asm volatile("{\n.reg .pred P;\nsetp.ne.u32 P, %3, 0;\n@P cp.async.bulk.global.shared::cta.bulk_group [%0], [%1], %2;\n}" ::"l"(dst), "r"(src), "r"(bytes), "r"(el) : "memory");
}
__device__ __forceinline__ void flag_release_p(uint32_t el, uint32_t* f) {
  asm volatile("{\n.reg .pred P;\nsetp.ne.u32 P, %1, 0;\n@P red.release.gpu.global.add.u32 [%0], 1;\n}" ::"l"(f), "r"(el) : "memory");
}
__device__ __forceinline__ void flag_add_p(uint32_t el, uint32_t* f) {
  asm volatile("{\n.reg .pred P;\nsetp.ne.u32 P, %1, 0;\n@P red.relaxed.gpu.global.add.u32 [%0], 1;\n}" ::"l"(f), "r"(el) : "memory");
}
__device__ __forceinline__ void prefetch_l2(const void* src, uint32_t bytes) { asm volatile("cp.async.bulk.prefetch.L2.global [%0], %1;" ::"l"(src), "r"(bytes) : "memory"); }
__device__ __forceinline__ void prefetch_map(const CUtensorMap* m) { asm volatile("prefetch.tensormap [%0];" ::"l"(m) : "memory"); }
__device__ __forceinline__ void wgmma_fence() { asm volatile("wgmma.fence.sync.aligned;" ::: "memory"); }
__device__ __forceinline__ void wgmma_commit() { asm volatile("wgmma.commit_group.sync.aligned;" ::: "memory"); }
template <int N> __device__ __forceinline__ void wgmma_wait() { asm volatile("wgmma.wait_group.sync.aligned %0;" ::"n"(N) : "memory"); }
__device__ __forceinline__ uint32_t dlo(uint32_t addr, uint32_t lbo) { return ((addr & 0x3FFFF) >> 4) + ((lbo >> 4) << 16); }
template <uint32_t SBO, uint32_t SWZ> __device__ __forceinline__ uint64_t dsc(uint32_t lo, uint32_t off) {
  uint64_t d; asm("mov.b64 %0, {%1, %2};" : "=l"(d) : "r"(lo + (off >> 4)), "n"((SBO >> 4) | (SWZ << 30))); return d;
}
__device__ __forceinline__ uint64_t dsc2(uint32_t lo, uint32_t off, uint32_t hi) {
  uint64_t d; asm("mov.b64 %0, {%1, %2};" : "=l"(d) : "r"(lo + (off >> 4)), "r"(hi)); return d;
}
__device__ __forceinline__ uint64_t dat(uint64_t d, uint32_t off, uint32_t one) { uint64_t r; asm("mad.wide.u32 %0, %1, %2, %3;" : "=l"(r) : "r"(one), "r"(off >> 4), "l"(d)); return r; }
__device__ __forceinline__ void dadd(uint64_t& d, uint32_t v) {
  asm("{\n.reg .b32 lo, hi;\nmov.b64 {lo, hi}, %0;\nadd.u32 lo, lo, %1;\nmov.b64 %0, {lo, hi};\n}" : "+l"(d) : "r"(v));
}
template <int R> __device__ __forceinline__ void reg_alloc() { asm volatile("setmaxnreg.inc.sync.aligned.u32 %0;" ::"n"(R)); }
template <int R> __device__ __forceinline__ void reg_dealloc() { asm volatile("setmaxnreg.dec.sync.aligned.u32 %0;" ::"n"(R)); }
__device__ __forceinline__ void bar_sync(int id, int n) { asm volatile("bar.sync %0, %1;" ::"r"(id), "r"(n) : "memory"); }
__device__ __forceinline__ void bar_arrive(int id, int n) { asm volatile("bar.arrive %0, %1;" ::"r"(id), "r"(n) : "memory"); }
__device__ __forceinline__ void ldsm4(uint32_t* r, uint32_t addr) {
  asm volatile("ldmatrix.sync.aligned.m8n8.x4.shared.b16 {%0,%1,%2,%3}, [%4];" : "=r"(r[0]), "=r"(r[1]), "=r"(r[2]), "=r"(r[3]) : "r"(addr) : "memory");
}
__device__ __forceinline__ uint32_t movm(uint32_t a) { uint32_t d; asm volatile("movmatrix.sync.aligned.m8n8.trans.b16 %0, %1;" : "=r"(d) : "r"(a)); return d; }
__device__ __forceinline__ void mma16(float* c, uint32_t a0, uint32_t a1, uint32_t a2, uint32_t a3, uint32_t b0, uint32_t b1) {
  asm volatile("mma.sync.aligned.m16n8k16.row.col.f32.bf16.bf16.f32 {%0,%1,%2,%3}, {%4,%5,%6,%7}, {%8,%9}, {%10,%10,%10,%10};"
               : "=f"(c[0]), "=f"(c[1]), "=f"(c[2]), "=f"(c[3]) : "r"(a0), "r"(a1), "r"(a2), "r"(a3), "r"(b0), "r"(b1), "f"(0.f));
}
__device__ __forceinline__ void mma8(float* c, uint32_t a0, uint32_t a1, uint32_t b0) {
  asm volatile("mma.sync.aligned.m16n8k8.row.col.f32.bf16.bf16.f32 {%0,%1,%2,%3}, {%4,%5}, {%6}, {%0,%1,%2,%3};"
               : "+f"(c[0]), "+f"(c[1]), "+f"(c[2]), "+f"(c[3]) : "r"(a0), "r"(a1), "r"(b0));
}
__device__ __forceinline__ void widen(float* c, uint32_t a0, uint32_t a1, uint32_t eye) {
  asm volatile("mma.sync.aligned.m16n8k8.row.col.f32.bf16.bf16.f32 {%0,%1,%2,%3}, {%4,%5}, {%6}, {%7,%7,%7,%7};"
               : "=f"(c[0]), "=f"(c[1]), "=f"(c[2]), "=f"(c[3]) : "r"(a0), "r"(a1), "r"(eye), "f"(0.f));
}
__device__ __forceinline__ float rsq_fast(float x) { float y; asm("rsqrt.approx.ftz.f32 %0, %1;" : "=f"(y) : "f"(x)); return y; }
__device__ __forceinline__ uint32_t pack2(float lo, float hi) { uint32_t r; asm("cvt.rn.bf16x2.f32 %0, %1, %2;" : "=r"(r) : "f"(hi), "f"(lo)); return r; }
__device__ __forceinline__ float blo(uint32_t v) { return __uint_as_float(v << 16); }
__device__ __forceinline__ float bhi(uint32_t v) { return __uint_as_float(v & 0xffff0000u); }
__device__ __forceinline__ float tanh_fast(float x) { float y; asm("tanh.approx.f32 %0, %1;" : "=f"(y) : "f"(x)); return y; }
__device__ __forceinline__ float rcp_fast(float x) { float y; asm("rcp.approx.ftz.f32 %0, %1;" : "=f"(y) : "f"(x)); return y; }
__device__ __forceinline__ float ex2(float x) { float y; asm("ex2.approx.ftz.f32 %0, %1;" : "=f"(y) : "f"(x)); return y; }
__device__ __forceinline__ float qsum(float v) { v += __shfl_xor_sync(~0u, v, 1); v += __shfl_xor_sync(~0u, v, 2); return v; }
__device__ __forceinline__ float qmax(float v) { v = fmaxf(v, __shfl_xor_sync(~0u, v, 1)); v = fmaxf(v, __shfl_xor_sync(~0u, v, 2)); return v; }
__device__ __forceinline__ void stg32(void* p, uint32_t v) { asm volatile("st.global.u32 [%0], %1;" ::"l"(p), "r"(v) : "memory"); }
__device__ __forceinline__ void stg128(void* p, uint32_t a, uint32_t b, uint32_t c, uint32_t d) { asm volatile("st.global.v4.u32 [%0], {%1,%2,%3,%4};" ::"l"(p), "r"(a), "r"(b), "r"(c), "r"(d) : "memory"); }
__device__ __forceinline__ uint32_t ldcg32(const void* p) { uint32_t v; asm volatile("ld.global.L1::no_allocate.u32 %0, [%1];" : "=r"(v) : "l"(p) : "memory"); return v; }
__device__ __forceinline__ uint32_t ldgpu32(const void* p) { uint32_t v; asm volatile("ld.relaxed.gpu.global.u32 %0, [%1];" : "=r"(v) : "l"(p) : "memory"); return v; }
__device__ __forceinline__ uint32_t ldca32(const void* p) { uint32_t v; asm volatile("ld.global.ca.u32 %0, [%1];" : "=r"(v) : "l"(p) : "memory"); return v; }
__device__ __forceinline__ void stg128_if(bool c, void* p, uint32_t a, uint32_t b, uint32_t cc, uint32_t d) {
  asm volatile("{\n.reg .pred P;\nsetp.ne.u32 P, %5, 0;\n@P st.global.v4.u32 [%0], {%1,%2,%3,%4};\n}" ::"l"(p), "r"(a), "r"(b), "r"(cc), "r"(d), "r"((uint32_t)c) : "memory");
}
__device__ __forceinline__ uint2 lds64(uint32_t a) { uint2 v; asm volatile("ld.shared.v2.u32 {%0,%1}, [%2];" : "=r"(v.x), "=r"(v.y) : "r"(a) : "memory"); return v; }
__device__ __forceinline__ uint4 ldcg128(const void* p) { uint4 v; asm volatile("ld.global.cg.v4.u32 {%0,%1,%2,%3}, [%4];" : "=r"(v.x), "=r"(v.y), "=r"(v.z), "=r"(v.w) : "l"(p) : "memory"); return v; }
__device__ __forceinline__ uint32_t ldnc16(const void* p) { uint16_t v; asm volatile("ld.global.nc.u16 %0, [%1];" : "=h"(v) : "l"(p)); return v; }
__device__ __forceinline__ uint4 ldnc128(const void* p) { uint4 v; asm volatile("ld.global.nc.v4.u32 {%0,%1,%2,%3}, [%4];" : "=r"(v.x), "=r"(v.y), "=r"(v.z), "=r"(v.w) : "l"(p)); return v; }
__device__ __forceinline__ uint32_t hsub2(uint32_t a, uint32_t b) { uint32_t d; asm("sub.rn.bf16x2 %0, %1, %2;" : "=r"(d) : "r"(a), "r"(b)); return d; }
__device__ __forceinline__ void stg32_if(bool c, void* p, uint32_t v) {
  asm volatile("{\n.reg .pred P;\nsetp.ne.u32 P, %2, 0;\n@P st.global.u32 [%0], %1;\n}" ::"l"(p), "r"(v), "r"((uint32_t)c) : "memory");
}
__device__ __forceinline__ uint32_t hmul2(uint32_t a, uint32_t b) { uint32_t d; asm("mul.rn.bf16x2 %0, %1, %2;" : "=r"(d) : "r"(a), "r"(b)); return d; }
__device__ __forceinline__ void sts32(uint32_t a, uint32_t v) { asm volatile("st.shared.u32 [%0], %1;" ::"r"(a), "r"(v) : "memory"); }
__device__ __forceinline__ uint32_t lds32(uint32_t a) { uint32_t v; asm volatile("ld.shared.u32 %0, [%1];" : "=r"(v) : "r"(a) : "memory"); return v; }
__device__ __forceinline__ void sts128(uint32_t a, uint32_t x, uint32_t y, uint32_t z, uint32_t w) { asm volatile("st.shared.v4.u32 [%0], {%1,%2,%3,%4};" ::"r"(a), "r"(x), "r"(y), "r"(z), "r"(w) : "memory"); }
__device__ __forceinline__ uint4 lds128(uint32_t a) { uint4 v; asm volatile("ld.shared.v4.u32 {%0,%1,%2,%3}, [%4];" : "=r"(v.x), "=r"(v.y), "=r"(v.z), "=r"(v.w) : "r"(a) : "memory"); return v; }
__device__ __forceinline__ void ll_st64(uint2* p, uint32_t v, uint32_t tag) {
  asm volatile("{\n.reg .b64 r;\nmov.b64 r, {%1,%2};\nst.relaxed.gpu.global.b64 [%0], r;\n}" ::"l"(p), "r"(v), "r"(tag) : "memory");
}
__device__ __forceinline__ uint2 ll_ld64(const uint2* p) {
  uint2 v; asm volatile("{\n.reg .b64 r;\nld.relaxed.gpu.global.b64 r, [%2];\nmov.b64 {%0,%1}, r;\n}" : "=r"(v.x), "=r"(v.y) : "l"(p) : "memory"); return v;
}
__device__ __forceinline__ void ll_st128(uint4* p, float a, float b, uint32_t tag, float c = 0.f) {
  asm volatile("{\n.reg .b128 r;\n.reg .b64 lo, hi;\nmov.b64 lo, {%1,%2};\nmov.b64 hi, {%3,%4};\nmov.b128 r, {lo, hi};\nst.relaxed.gpu.global.b128 [%0], r;\n}" ::"l"(p), "r"(__float_as_uint(a)), "r"(__float_as_uint(b)), "r"(tag), "r"(__float_as_uint(c)) : "memory");
}
__device__ __forceinline__ uint4 ll_ld128(const uint4* p) {
  uint4 v; asm volatile("{\n.reg .b128 r;\n.reg .b64 lo, hi;\nld.relaxed.gpu.global.b128 r, [%4];\nmov.b128 {lo, hi}, r;\nmov.b64 {%0,%1}, lo;\nmov.b64 {%2,%3}, hi;\n}" : "=r"(v.x), "=r"(v.y), "=r"(v.z), "=r"(v.w) : "l"(p) : "memory"); return v;
}
__device__ __forceinline__ void publish_p(uint32_t el, uint32_t* f) {
  asm volatile("{\n.reg .pred P;\nsetp.ne.u32 P, %1, 0;\n@P cp.async.bulk.commit_group;\n@P cp.async.bulk.wait_group 0;\n@P red.release.gpu.global.add.u32 [%0], 1;\n}" ::"l"(f), "r"(el) : "memory");
}
__device__ __forceinline__ void tma3d_red_p(uint32_t el, const CUtensorMap* m, int c0, int c1, int c2, uint32_t src) {
  asm volatile("{\n.reg .pred P;\nsetp.ne.u32 P, %5, 0;\n@P cp.reduce.async.bulk.tensor.3d.global.shared::cta.add.tile.bulk_group [%0, {%2, %3, %4}], [%1];\n@P cp.async.bulk.commit_group;\n}" ::"l"(m), "r"(src), "r"(c0), "r"(c1), "r"(c2), "r"(el) : "memory");
}
__device__ __forceinline__ void stsm4(uint32_t addr, uint32_t a, uint32_t b, uint32_t c, uint32_t d) {
  asm volatile("stmatrix.sync.aligned.m8n8.x4.shared.b16 [%0], {%1,%2,%3,%4};" ::"r"(addr), "r"(a), "r"(b), "r"(c), "r"(d) : "memory");
}
__device__ __forceinline__ void sts64(uint32_t a, uint32_t x, uint32_t y) { asm volatile("st.shared.v2.u32 [%0], {%1,%2};" ::"r"(a), "r"(x), "r"(y) : "memory"); }
__device__ __forceinline__ void ll_st128_if(bool on, uint4* p, float a, float b, uint32_t tag) {
  asm volatile("{\n.reg .pred P;\n.reg .b128 r;\n.reg .b64 lo, hi;\nsetp.ne.u32 P, %4, 0;\nmov.b64 lo, {%1,%2};\nmov.b64 hi, {%3,%3};\nmov.b128 r, {lo, hi};\n@P st.relaxed.gpu.global.b128 [%0], r;\n}" ::"l"(p), "r"(__float_as_uint(a)), "r"(__float_as_uint(b)), "r"(tag), "r"((uint32_t)on) : "memory");
}
__device__ __forceinline__ uint4 ldnc128_if(bool c, const void* p) {
  uint4 v = make_uint4(0u, 0u, 0u, 0u);
  asm volatile("{\n.reg .pred P;\nsetp.ne.u32 P, %5, 0;\n@P ld.global.nc.v4.u32 {%0,%1,%2,%3}, [%4];\n}" : "+r"(v.x), "+r"(v.y), "+r"(v.z), "+r"(v.w) : "l"(p), "r"((uint32_t)c));
  return v;
}
__device__ __forceinline__ uint32_t hfma2(uint32_t a, uint32_t b, uint32_t c) { uint32_t d; asm("fma.rn.bf16x2 %0, %1, %2, %3;" : "=r"(d) : "r"(a), "r"(b), "r"(c)); return d; }
__device__ __forceinline__ float2 lds64f(uint32_t a) { float2 v; asm volatile("ld.shared.v2.f32 {%0,%1}, [%2];" : "=f"(v.x), "=f"(v.y) : "r"(a) : "memory"); return v; }
#define TRC(cond, role, idx) do {} while (0)
#define TRV(role, idx, v) do {} while (0)

#define ACLK_INIT do {} while (0)
#define ACLK(i) do {} while (0)
#define ACLK_OUT do {} while (0)
#define QCLK(i) do {} while (0)
#define PH 1
#define RCLK(i) do {} while (0)
#define RCLK_INIT do {} while (0)
#define RCLK_OUT do {} while (0)
#define SCLK(i) do {} while (0)
#define HCLK(i) do {} while (0)
#define MCLK(c, i) do {} while (0)
#define CKK(i) do {} while (0)
#define CKK_OUT do {} while (0)
#define PL 1
#define PCLK(i) do {} while (0)
#define PQ 1
#define CLK_INIT do {} while (0)
#define CLK(i) do {} while (0)
#define CLK_OUT do {} while (0)

__device__ __forceinline__ void wgmma_ss_n216(float* d, uint64_t da, uint64_t db, int scaleD) {
  asm volatile("{\n.reg .pred p;\nsetp.ne.b32 p, %110, 0;\nwgmma.mma_async.sync.aligned.m64n216k16.f32.bf16.bf16 "
    "{%0,%1,%2,%3,%4,%5,%6,%7,%8,%9,%10,%11,%12,%13,%14,%15,%16,%17,%18,%19,%20,%21,%22,%23,%24,%25,%26,%27,%28,%29,%30,%31,%32,%33,%34,%35,%36,%37,%38,%39,%40,%41,%42,%43,%44,%45,%46,%47,%48,%49,%50,%51,%52,%53,%54,%55,%56,%57,%58,%59,%60,%61,%62,%63,%64,%65,%66,%67,%68,%69,%70,%71,%72,%73,%74,%75,%76,%77,%78,%79,%80,%81,%82,%83,%84,%85,%86,%87,%88,%89,%90,%91,%92,%93,%94,%95,%96,%97,%98,%99,%100,%101,%102,%103,%104,%105,%106,%107}, "
    "%108, %109, p, 1, 1, 0, 1;\n}\n"
    : "+f"(d[0]), "+f"(d[1]), "+f"(d[2]), "+f"(d[3]), "+f"(d[4]), "+f"(d[5]), "+f"(d[6]), "+f"(d[7]), "+f"(d[8]), "+f"(d[9]), "+f"(d[10]), "+f"(d[11]), "+f"(d[12]), "+f"(d[13]), "+f"(d[14]), "+f"(d[15]), "+f"(d[16]), "+f"(d[17]), "+f"(d[18]), "+f"(d[19]), "+f"(d[20]), "+f"(d[21]), "+f"(d[22]), "+f"(d[23]), "+f"(d[24]), "+f"(d[25]), "+f"(d[26]), "+f"(d[27]), "+f"(d[28]), "+f"(d[29]), "+f"(d[30]), "+f"(d[31]), "+f"(d[32]), "+f"(d[33]), "+f"(d[34]), "+f"(d[35]), "+f"(d[36]), "+f"(d[37]), "+f"(d[38]), "+f"(d[39]), "+f"(d[40]), "+f"(d[41]), "+f"(d[42]), "+f"(d[43]), "+f"(d[44]), "+f"(d[45]), "+f"(d[46]), "+f"(d[47]), "+f"(d[48]), "+f"(d[49]), "+f"(d[50]), "+f"(d[51]), "+f"(d[52]), "+f"(d[53]), "+f"(d[54]), "+f"(d[55]), "+f"(d[56]), "+f"(d[57]), "+f"(d[58]), "+f"(d[59]), "+f"(d[60]), "+f"(d[61]), "+f"(d[62]), "+f"(d[63]), "+f"(d[64]), "+f"(d[65]), "+f"(d[66]), "+f"(d[67]), "+f"(d[68]), "+f"(d[69]), "+f"(d[70]), "+f"(d[71]), "+f"(d[72]), "+f"(d[73]), "+f"(d[74]), "+f"(d[75]), "+f"(d[76]), "+f"(d[77]), "+f"(d[78]), "+f"(d[79]), "+f"(d[80]), "+f"(d[81]), "+f"(d[82]), "+f"(d[83]), "+f"(d[84]), "+f"(d[85]), "+f"(d[86]), "+f"(d[87]), "+f"(d[88]), "+f"(d[89]), "+f"(d[90]), "+f"(d[91]), "+f"(d[92]), "+f"(d[93]), "+f"(d[94]), "+f"(d[95]), "+f"(d[96]), "+f"(d[97]), "+f"(d[98]), "+f"(d[99]), "+f"(d[100]), "+f"(d[101]), "+f"(d[102]), "+f"(d[103]), "+f"(d[104]), "+f"(d[105]), "+f"(d[106]), "+f"(d[107])
    : "l"(da), "l"(db), "r"(scaleD));
}
__device__ __forceinline__ void wgmma_ss_n72(float* d, uint64_t da, uint64_t db, int scaleD) {
  asm volatile("{\n.reg .pred p;\nsetp.ne.b32 p, %38, 0;\nwgmma.mma_async.sync.aligned.m64n72k16.f32.bf16.bf16 "
    "{%0,%1,%2,%3,%4,%5,%6,%7,%8,%9,%10,%11,%12,%13,%14,%15,%16,%17,%18,%19,%20,%21,%22,%23,%24,%25,%26,%27,%28,%29,%30,%31,%32,%33,%34,%35}, "
    "%36, %37, p, 1, 1, 0, 1;\n}\n"
    : "+f"(d[0]), "+f"(d[1]), "+f"(d[2]), "+f"(d[3]), "+f"(d[4]), "+f"(d[5]), "+f"(d[6]), "+f"(d[7]), "+f"(d[8]), "+f"(d[9]), "+f"(d[10]), "+f"(d[11]), "+f"(d[12]), "+f"(d[13]), "+f"(d[14]), "+f"(d[15]), "+f"(d[16]), "+f"(d[17]), "+f"(d[18]), "+f"(d[19]), "+f"(d[20]), "+f"(d[21]), "+f"(d[22]), "+f"(d[23]), "+f"(d[24]), "+f"(d[25]), "+f"(d[26]), "+f"(d[27]), "+f"(d[28]), "+f"(d[29]), "+f"(d[30]), "+f"(d[31]), "+f"(d[32]), "+f"(d[33]), "+f"(d[34]), "+f"(d[35])
    : "l"(da), "l"(db), "r"(scaleD));
}
__device__ __forceinline__ void wgmma_rs_n144(float* d, const uint32_t* a, uint64_t db, int scaleD) {
  asm volatile("{\n.reg .pred p;\nsetp.ne.b32 p, %77, 0;\nwgmma.mma_async.sync.aligned.m64n144k16.f32.bf16.bf16 "
    "{%0,%1,%2,%3,%4,%5,%6,%7,%8,%9,%10,%11,%12,%13,%14,%15,%16,%17,%18,%19,%20,%21,%22,%23,%24,%25,%26,%27,%28,%29,%30,%31,%32,%33,%34,%35,%36,%37,%38,%39,%40,%41,%42,%43,%44,%45,%46,%47,%48,%49,%50,%51,%52,%53,%54,%55,%56,%57,%58,%59,%60,%61,%62,%63,%64,%65,%66,%67,%68,%69,%70,%71}, "
    "{%72,%73,%74,%75}, %76, p, 1, 1, 1;\n}\n"
    : "+f"(d[0]), "+f"(d[1]), "+f"(d[2]), "+f"(d[3]), "+f"(d[4]), "+f"(d[5]), "+f"(d[6]), "+f"(d[7]), "+f"(d[8]), "+f"(d[9]), "+f"(d[10]), "+f"(d[11]), "+f"(d[12]), "+f"(d[13]), "+f"(d[14]), "+f"(d[15]), "+f"(d[16]), "+f"(d[17]), "+f"(d[18]), "+f"(d[19]), "+f"(d[20]), "+f"(d[21]), "+f"(d[22]), "+f"(d[23]), "+f"(d[24]), "+f"(d[25]), "+f"(d[26]), "+f"(d[27]), "+f"(d[28]), "+f"(d[29]), "+f"(d[30]), "+f"(d[31]), "+f"(d[32]), "+f"(d[33]), "+f"(d[34]), "+f"(d[35]), "+f"(d[36]), "+f"(d[37]), "+f"(d[38]), "+f"(d[39]), "+f"(d[40]), "+f"(d[41]), "+f"(d[42]), "+f"(d[43]), "+f"(d[44]), "+f"(d[45]), "+f"(d[46]), "+f"(d[47]), "+f"(d[48]), "+f"(d[49]), "+f"(d[50]), "+f"(d[51]), "+f"(d[52]), "+f"(d[53]), "+f"(d[54]), "+f"(d[55]), "+f"(d[56]), "+f"(d[57]), "+f"(d[58]), "+f"(d[59]), "+f"(d[60]), "+f"(d[61]), "+f"(d[62]), "+f"(d[63]), "+f"(d[64]), "+f"(d[65]), "+f"(d[66]), "+f"(d[67]), "+f"(d[68]), "+f"(d[69]), "+f"(d[70]), "+f"(d[71])
    : "r"(a[0]), "r"(a[1]), "r"(a[2]), "r"(a[3]), "l"(db), "r"(scaleD));
}
__device__ __forceinline__ void wgmma_rs_n64(float* d, const uint32_t* a, uint64_t db, int scaleD) {
  asm volatile("{\n.reg .pred p;\nsetp.ne.b32 p, %37, 0;\nwgmma.mma_async.sync.aligned.m64n64k16.f32.bf16.bf16 "
    "{%0,%1,%2,%3,%4,%5,%6,%7,%8,%9,%10,%11,%12,%13,%14,%15,%16,%17,%18,%19,%20,%21,%22,%23,%24,%25,%26,%27,%28,%29,%30,%31}, "
    "{%32,%33,%34,%35}, %36, p, 1, 1, 1;\n}\n"
    : "+f"(d[0]), "+f"(d[1]), "+f"(d[2]), "+f"(d[3]), "+f"(d[4]), "+f"(d[5]), "+f"(d[6]), "+f"(d[7]), "+f"(d[8]), "+f"(d[9]), "+f"(d[10]), "+f"(d[11]), "+f"(d[12]), "+f"(d[13]), "+f"(d[14]), "+f"(d[15]), "+f"(d[16]), "+f"(d[17]), "+f"(d[18]), "+f"(d[19]), "+f"(d[20]), "+f"(d[21]), "+f"(d[22]), "+f"(d[23]), "+f"(d[24]), "+f"(d[25]), "+f"(d[26]), "+f"(d[27]), "+f"(d[28]), "+f"(d[29]), "+f"(d[30]), "+f"(d[31])
    : "r"(a[0]), "r"(a[1]), "r"(a[2]), "r"(a[3]), "l"(db), "r"(scaleD));
}

template <int V> struct Int { static constexpr int value = V; };
struct Cur {
  uint32_t s, ph;
  __device__ __forceinline__ void next() { if (++s == NST) { s = 0; ph ^= 1; } }
};

#define z1_block(rb, w, j) (P.s->Z + ((rb) * 16 + (w) * 8 + (j)) * ZB)
#define z2_block(kb, j) (P.s->Z + (256 + (kb) * 8 + (j)) * ZB)
#define o_block(rb, w) (P.s->O + ((rb) * 2 + (w)) * (2 * ZB))
__device__ __forceinline__ void combine8(float m0, float q0, float m1, float q1, float n, float eps, float& mean, float& rstd) {
  mean = qsum(m0 + m1) * 0.125f;
  float d0 = m0 - mean, d1 = m1 - mean;
  float M2 = qsum(q0 + q1 + n * (d0 * d0 + d1 * d1));
  rstd = rsq_fast(fmaf(M2, 0.125f / n, eps));
}
__device__ __forceinline__ void stat_get(const uint4* zs, uint32_t tag, float n, float eps, float& m0, float& r0, float& m1, float& r1) {
  uint4 a0, a1, b0, b1;
#pragma unroll 1
  for (int it = 0; it < (1 << 20); it++) {
    a0 = ll_ld128(zs); a1 = ll_ld128(zs + 64); b0 = ll_ld128(zs + 8); b1 = ll_ld128(zs + 72);
    if (__all_sync(~0u, a0.z == tag && a1.z == tag && b0.z == tag && b1.z == tag)) break;
  }
  combine8(__uint_as_float(a0.x), __uint_as_float(a0.y), __uint_as_float(a1.x), __uint_as_float(a1.y), n, eps, m0, r0);
  combine8(__uint_as_float(b0.x), __uint_as_float(b0.y), __uint_as_float(b1.x), __uint_as_float(b1.y), n, eps, m1, r1);
}

__device__ __forceinline__ void rows_fetch(uint32_t el, uint32_t xr, const uint8_t* src, uint32_t bar) {
  expect_tx_p(el, bar, 9216);
#pragma unroll 1
  for (int r = 0; r < 8; r++) bulk_load_p(el, xr + r * 1152, src + r * (DM * 4), 1152, bar);
}
__device__ __forceinline__ void rows_stats(uint32_t xr, uint4* dst, uint32_t tag, int lane) {
  float s[2] = {0.f, 0.f}, q[4] = {0.f, 0.f, 0.f, 0.f};
  const uint32_t a0 = xr + (lane >> 2) * 1152 + (((lane & 3) * 2) ^ (lane >> 2)) * 16;
  uint4 n0 = lds128(a0), n1 = lds128(a0 ^ 16);
#pragma unroll 1
  for (int e = 1; e <= 9; e++) {
    const uint32_t x[8] = {n0.x, n0.y, n0.z, n0.w, n1.x, n1.y, n1.z, n1.w};
    if (e < 9) { n0 = lds128(a0 + e * 128); n1 = lds128((a0 ^ 16) + e * 128); }
#pragma unroll
    for (int u = 0; u < 8; u++) {
      const float lo = blo(x[u]), hi = bhi(x[u]);
      s[u & 1] += lo + hi; q[(u & 1) * 2] = fmaf(lo, lo, q[(u & 1) * 2]); q[(u & 1) * 2 + 1] = fmaf(hi, hi, q[(u & 1) * 2 + 1]);
    }
  }
  const float sx = s[0] + s[1], sq = (q[0] + q[1]) + (q[2] + q[3]);
  const float m = qsum(sx) * (-1.f / DM), r = rsq_fast(fmaxf(fmaf(qsum(sq), 1.f / DM, -m * m), 0.f) + LN_EPS);
  if ((lane & 3) == 0) ll_st128(dst + (lane >> 2) * 2, m, r, tag);
}

__device__ __forceinline__ void poison(const Params& P, uint32_t el, uint32_t src, const CUtensorMap* m, int rb, int j, int lane) {
#pragma unroll 1
  for (int u = lane; u < 72; u += 32) sts128(src + u * 16, POISON, POISON, POISON, POISON);
  fence_async_s();
  __syncwarp();
#pragma unroll 1
  for (int u = 0; u < 16; u++) {
    __nanosleep(NAP);
    bulk_store_p(el, o_block(rb, u >> 3) + j * 9216 + (u & 7) * 1152, src, 1152);
    asm volatile("{\n.reg .pred P;\nsetp.ne.u32 P, %5, 0;\n@P cp.async.bulk.tensor.3d.global.shared::cta.tile.bulk_group [%0, {%2, %3, %4}], [%1];\n}" ::"l"(m), "r"(src), "r"((j & 6) * 72), "r"(rb * 64 + u * 4), "r"(j & 1), "r"(el) : "memory");
  }
}
__device__ __forceinline__ void mma16acc(float* c, const uint32_t* a, uint32_t b0, uint32_t b1) {
  asm volatile("mma.sync.aligned.m16n8k16.row.col.f32.bf16.bf16.f32 {%0,%1,%2,%3}, {%4,%5,%6,%7}, {%8,%9}, {%0,%1,%2,%3};"
               : "+f"(c[0]), "+f"(c[1]), "+f"(c[2]), "+f"(c[3]) : "r"(a[0]), "r"(a[1]), "r"(a[2]), "r"(a[3]), "r"(b0), "r"(b1));
}
template <int KS, int NG, int AK, int AH, int BK, int BG, class F> __device__ __forceinline__ void redo(float* acc, const uint8_t* pa, const uint8_t* pb, F f) {
#pragma unroll 1
  for (int k = 0; k < 36; k += KS) {
    uint32_t a[4 * KS], b[2 * KS][NG];
#pragma unroll 1
    for (int it = 0; it < (1 << 20); it++) {
      bool ok = true;
#pragma unroll
      for (int e = 0; e < 4 * KS; e++) a[e] = ldgpu32(pa + (e >> 1) * AK + (e & 1) * AH);
#pragma unroll
      for (int e = 0; e < 2 * KS * NG; e++) b[e / NG][e % NG] = ldca32(pb + (e / NG) * BK + (e % NG) * BG);
#pragma unroll
      for (int e = 0; e < 4 * KS; e++) ok = ok && a[e] != POISON;
      if (__all_sync(~0u, ok)) break;
    }
#pragma unroll
    for (int e = 0; e < KS; e++) f(a + 4 * e, k + e);
#pragma unroll
    for (int e = 0; e < KS * NG; e++) mma16acc(acc + 4 * (e % NG), a + 4 * (e / NG), movm(b[2 * (e / NG)][e % NG]), movm(b[2 * (e / NG) + 1][e % NG]));
    pa += 2 * KS * AK; pb += 2 * KS * BK;
  }
}
__device__ __forceinline__ bool any_nan(float a, float b) {
  return __any_sync(~0u, a != a || b != b);
}

__global__ void __cluster_dims__(2, 1, 1) __launch_bounds__(384, 1) mega_kernel(const __grid_constant__ Params P) {
  extern __shared__ __align__(1024) uint8_t smem_raw[];
  uint32_t ckk[8];
  (void)ckk;
  CKK(0);
  const uint32_t sb = smem_u32(smem_raw);
  const uint32_t bars = sb + SM_BAR;
  int tid = threadIdx.x, lane = tid & 31;
  const int wid = __shfl_sync(~0u, tid >> 5, 0);
  const int cl = blockIdx.x >> 1, tp = cl - 36, t7 = (tp * 37) >> 8;
  const int bid = (cl < 4 ? cl * 8 + 32 : tp < 0 ? cl - 4 : cl < 64 ? tp + t7 + 33 : cl) * 2 + (blockIdx.x & 1);
  if (bid >= NCTA) return;
  const int rb = bid & 15, j = bid >> 4;
  { const bool tr = (tid & 127) == 0 && tid < 256; const int w = tid >> 7; (void)tr; (void)w; TRC(tr, w, 0); }
  CKK(1);
  uint4 wv[5];
  const uint8_t* wsrc;
  {
    const int n8 = min(tid >> 3, 26), part = n8 / 9;
    const uint8_t* src = (const uint8_t*)P.wqkv + (8 * rb + (tid & 7)) * (3 * DM * 2) + (part * (DM - 72) + 72 * j + 8 * n8) * 2;
#pragma unroll
    for (int u = 0; u < SPL; u++) wv[u] = ldnc128_if(tid < 216, src + u * (128 * 3 * DM * 2));
    wsrc = src;
  }
  CKK(2);
  if (tid == 352) {
#pragma unroll
    for (int e = 0; e < 16; e++) mbar_init(bars + B_FULL + e * 8, (e >> 2) == 1 ? 16 : 1);
    mbar_init(bars + B_RES + 8, 8); mbar_init(bars + B_WT, 1); mbar_init(bars + B_WT + 8, 1); mbar_init(bars + B_IMG, 9);
    asm volatile("fence.mbarrier_init.release.cluster;" ::: "memory");
  }
  __syncthreads();

  if (wid >= 8) {
    reg_dealloc<40>();
    lane = __shfl_sync(~0u, lane, lane);
    const uint32_t el = elect_one();
    const uint64_t pol = policy_evict_first();
    uint32_t* const fj = P.s->flags + FJ + j * 32;
    if (wid == 8) {
      if (lane == 0) {
        mbar_init(bars + B_RES, 1); mbar_init(bars + B_WOI, 1); mbar_init(bars + B_ZB, 1); mbar_init(bars + B_GATE3, 3); mbar_init(bars + B_Z1, 1); mbar_init(bars + B_LAG, 4);
#pragma unroll
        for (int e = B_RT; e < B_XS + 16; e += 8) mbar_init(bars + e, e >= B_AD && e < B_EVT ? 2 : (e >= B_EVT && e < B_RT1) || (e >= B_EA3 && e < B_XS) ? 4 : 1);
        asm volatile("fence.mbarrier_init.release.cluster;" ::: "memory");
        mbar_arrive(bars + B_IMG);
      }
      __syncwarp();
#pragma unroll 1
      for (int i = 0; i < 12; i++) if (el) prefetch_map(&P.act[0] + (i < 7 ? i : i - 12));
      const uint32_t epoch = ldcg32(fj + FJ_EP + rb);
      Cur c{0, 1};
      const uint32_t rk = bid & 1;
      TRC(el, 2, 34);
      uint32_t st, full;
      auto slot = [&](uint32_t bytes) {
        st = sb + c.s * ST_BYTES; full = bars + B_FULL + c.s * 8;
        mbar_wait(full, c.ph);
        expect_tx_p(el, full, bytes);
        mbar_wait(full - B_FULL + B_EMPTY, c.ph);
      };
#pragma unroll 1
      for (int L = 0; L < 2; L++) {
#pragma unroll 1
        for (int i = 0; i < 14; i++) {
          if (L == 0 && (i == 0 || i == 2 * SPL || i == 9)) {
            flag_wait(fj + (i == 9 ? FJ_WO : i == 2 * SPL ? FJ_WQ : FJ_WQ0), (epoch + 1) * 16);
            if (i == 9) flag_wait(P.s->flags + FJ + (j ^ 1) * 32 + FJ_WO, (epoch + 1) * 16);
            fence_async_g();
            TRC(el, 2, i == 9 ? 46 : i ? 47 : 45);
          }
          const uint32_t hb = i < 9 ? 13824 : i < 13 ? 18432 : 9216, o = ST_B + rk * (i < 9 ? 13824 : 18432);
          const uint8_t* src = i < 9 ? P.s->WQ + j * WQ_SL + i * 27648 + rk * 13824 : P.s->WO + ((j & 6) + rk) * WO_SL + (i - 9) * 18432;
          slot(2 * hb);
          bulk_mc_h(el, st + o, src, hb, full, true, pol);
          c.next();
        }
#pragma unroll 1
        for (int i = 0; i < 18; i++) {
          const int p = i >> 1, col = p == 4 ? (9 * j + ((j & 1) ? 0 : 8)) * 32 : (((9 * j + 1) >> 1) + (p < 4 ? p + 36 : p - 5)) * 64;
          if ((i >> 1) == 1) mbar_wait(bars + B_FA3 + (GA3 + (i & 1) * (GB3 - GA3)) * 8, L);
          if (i & 1) {
            slot(2 * ZB);
          } else {
            st = sb + c.s * ST_BYTES; full = bars + B_FULL + ((c.s + 1) & 3) * 8;
            mbar_wait(bars + B_EMPTY + c.s * 8, c.ph);
          }
          tma4d_mc(el, st + ST_B + rk * 18432, p == 4 ? &P.win : &P.win64, col, (i & 1) * 36 + rk * 18, full, pol);
          if (i < 2 && L == 0 && el) asm volatile("cp.async.bulk.prefetch.tensor.4d.L2.global [%0, {%1, 0, 0, %2}];" ::"l"(&P.win64), "r"(col + 64), "r"((i & 1) * 36 + rk * 18) : "memory");
          if (el && !(i & 1)) mbar_arrive(bars + B_FULL + c.s * 8);
          c.next();
        }
        TRC(el, 2, L * 16 + 6);
        flag_wait(fj + FJ_ZN + L, (epoch + 1) * 16);
        fence_async_g();
        TRC(el, 2, L * 16 + 7);
#pragma unroll 1
        for (int i = 0; i < 32; i++) {
          const uint8_t* src = z2_block(i, j) + rk * 18432;
          if (i >= 4) mbar_wait(bars + B_AD + c.s * 8, ((i >> 2) & 1) ^ 1);
          slot(ST_BYTES);
          bulk_mc_h(el, st + ST_B + rk * 18432, src, 18432, full, true, pol);
          tma3d_h(el, st, &P.wsp, i * 64, rb * 64, 0, full, true, pol);
          c.next();
        }
        mbar_wait(bars + B_Z1, L);
        fence_async_g();
        expect_tx_p(el, bars + B_ZB, 26624);
#pragma unroll 1
        for (int i = 0; i < 10; i++) {
          const int cb = i - 1 + j;
          if (i < 4) mbar_wait(bars + B_AD + c.s * 8, 1);
          slot(i ? ZB : 26624);
          if (i == 0) {
            bulk_load_h(el, st, z1_block(rb, 0, j), 26624, bars + B_ZB, true, pol);
            bulk_load_h(el, st + 26624, z1_block(rb, 1, j), 26624, full, true, pol);
          } else {
            tma2d_mc_h(el, st + ST_B + rk * 18432, &P.wout, (cb >= 9 ? cb - 9 : cb) * 64, 288 * j + rk * 144, full, true, pol);
          }
          c.next();
        }
      }
    } else if (wid < 11) {
      int w = wid - 9;
      TRC(el && w == 0, 2, 35);
      uint32_t* const fr = P.s->flags + (rb * 2 + w) * 32;
      const uint32_t epoch = ldcg32(fr + FR_EP + j);
      const uint32_t ev = bars + B_EVT + w * EV_N * 8, t8 = (epoch + 1) * 8;
      Cur c{0, 1};
#pragma unroll 1
      for (int L = 0; L < 2; L++) {
        {
          uint32_t tag = t8;
          asm volatile("" : "+r"(tag));
          tag = (tag >> 2) - 1 + L;
          uint4* const xs = P.s->XST + (rb * 2 + w) * 128;
          if (L) {
            mbar_wait(ev + EV_PT * 8, 0);
            TRC(el, 3, w * 32 + 16);
            flag_release_p(el, fr + FR_X2);
            TRC(el, 3, w * 32 + 17);
          }
#pragma unroll 1
          for (int i = 0; i < 9; i++) {
            const uint32_t full = bars + B_FULLA + w * 32 + c.s * 8, dst = sb + c.s * ST_BYTES + w * 8192;
            if (L == 0 && i == 4) {
              mbar_wait(bars + B_WT + w * 8, 0);
              TRC(el && w == 0, 2, 37);
              rows_stats(sb + SM_STG + w * 9216, xs + 16 * j, tag, lane);
              TRC(el && w == 0, 2, 38);
            }
            const uint32_t src = sb + (L ? 2 * ST_BYTES + SM_WOI : SM_STG + w * 9216);
            if (i == 4) {
#pragma unroll
              for (int u = 0; u < 6; u++) sts128(src + u * 512 + lane * 16, POISON, POISON, POISON, POISON);
              fence_async_s();
              __syncwarp();
            }
            mbar_wait(bars + B_EMPTY + c.s * 8, c.ph);
            expect_tx_p(el, full, 8192);
            if (i < L) { flag_wait(fr + FR_X2, t8); fence_async_g(); }
            tma3d_h(el, dst, &P.act[L], i * 64, rb * 64, w, full, false, pol);
            TRC(el && i < L, 3, w * 32 + 18);
            TRC(el && i + L + w == 0, 2, 36);
            c.next();
            if (i >= 4 && i < (L ? 5 : 8)) {
              int b = (rb * 2 + w) * 8 + j;
              asm volatile("" : "+r"(b));
              bulk_store_p(el, i == 4 ? (uint8_t*)P.s->HALO + b * 3072 : P.s->O + (b * 3 + i - 5) * 3072, src, 3072);
              if (i < 6) bulk_store_p(el, (i == 4 ? P.s->ST1 : P.s->ZST) + b * 64, src, 1024);
              if (i == 6) bulk_store_p(el, P.s->RT + b * 8, src, 64);
            }
            if (L == 0 && i == 3) rows_fetch(el, sb + SM_STG + w * 9216, P.xs[0] + (128 * rb + 16 * j + w) * (DM * 2), bars + B_WT + w * 8);
          }
          if (el) asm volatile("cp.async.bulk.commit_group;\ncp.async.bulk.wait_group 0;" ::: "memory");
          __syncwarp();
          if (L == 0) fence_gpu();
          const uint32_t tab = sb + L * (2 * ST_BYTES) + SM_XST + w * 512 + lane * 8;
          TRC(el, 3, w * 32 + L * 16 + 13);
#pragma unroll 1
          for (int it = 0; it < (1 << 22); it++) {
            const uint4 a = ll_ld128(xs + 2 * lane), b = ll_ld128(xs + 64 + 2 * lane);
            if (__all_sync(~0u, a.z == tag && b.z == tag)) { sts64(tab, a.x, a.y); sts64(tab + 256, b.x, b.y); break; }
          }
          __syncwarp();
          mbar_arrive_if(el, bars + B_XS + w * 8);
          TRC(el, 3, w * 32 + L * 16 + 14);
          if (w == 1) {
            mbar_wait(bars + B_XS, L);
            expect_tx_p(el, bars + B_RES, 18432);
            tma3d_h(el, sb + SM_STG, &P.res[L], (j & 6) * 72, rb * 64, j & 1, bars + B_RES, !L, pol);
          }
          if (L) flag_wait(fj + FJ_P4, t8 * 4);
        }
        int hp = rb * 2 + (j & 1);
        asm volatile("" : "+r"(w), "+r"(hp));
        uint32_t* const fo = P.s->flags + hp * 32 + L;
        {
          const uint8_t* src = o_block(0, hp) + w * 8192;
#pragma unroll 1
          for (int i = 0; i < 5; i++) {
            const uint32_t full = bars + B_FULLA + w * 32 + c.s * 8, dst = sb + c.s * ST_BYTES + w * 8192;
            const bool none = 2 * i + w > 8;
            mbar_wait(bars + B_EMPTY + c.s * 8, c.ph);
            expect_tx_p(el, full, none ? 0 : 8192);
            if (i == 0) {
              mbar_wait(ev + EV_O * 8, L);
              TRC(el, 3, w * 32 + L * 16 + 3);
              flag_add_p(el, fr + FR_O + L);
              TRC(el, 3, w * 32 + L * 16 + 4);
              flag_wait(fo + FR_O, t8);
              fence_async_g();
            }
            if (!none) bulk_load_h(el, dst, src + i * 16384, 8192, full, true, pol);
            TRC(el && i == 0, 3, w * 32 + L * 16 + 5);
            c.next();
          }
        }
        {
          expect_tx_p(lane < 9, bars + B_FA3 + (9 * w + lane) * 8, 8192);
          mbar_wait(ev + EV_X1 * 8, L);
          TRC(el, 3, w * 32 + L * 16 + 6);
          if (L) flag_add_p(el, fo + FR_X1); else flag_release_p(el, fo + FR_X1);
          mbar_arrive_if(el, bars + B_GATE3);
          TRC(el, 3, w * 32 + L * 16 + 7);
          mbar_arrive_if(lane < 2, bars + B_FULLA + w * 32 + ((c.s + lane) & 3) * 8);
#pragma unroll 1
          for (int kb = 0; kb < 9; kb++) {
            const int n = 9 * w + kb;
            const uint32_t dst = sb + ((n >> 1) & 3) * ST_BYTES + (n & 1) * 8192;
            if (kb == 0) { flag_wait(fr + FR_X1 + L, t8); fence_async_g(); }
            if (n >= 8) mbar_wait(bars + B_EA3 + (n - 8) * 8, L);
            tma3d_h(el, dst, &P.act[L + 1], kb * 64, rb * 64, w, bars + B_FA3 + n * 8, false, pol);
            TRC(el && kb == 0, 3, w * 32 + L * 16 + 8);
          }
          c.ph ^= ((c.s + 18) >> 2) & 1; c.s = (c.s + 18) & 3;
        }
        asm volatile("" : "+r"(lane), "+r"(w));
        expect_tx_p(el, bars + B_WT + w * 8, 2048);
#pragma unroll 1
        for (int r = 0; r < 8; r++)
          bulk_load_p(el, sb + SM_WT + w * 2176 + r * 272, (const uint8_t*)P.w_sp + (size_t)(128 * rb + 16 * j + 2 * r + w) * (SEQ * 2) + 30 * 128, 256, bars + B_WT + w * 8);
        float cv = (lane & 3) ? 0.f : -blo(ldnc16(P.b_sp + 128 * rb + 16 * j + 2 * (lane >> 2) + w));
        mbar_wait(bars + B_RT, L);
        mbar_wait(bars + B_WT + w * 8, L ^ 1);
        mbar_wait(ev + EV_Z1 * 8, L);
        const uint32_t ro = (w * 64 + 8 * j + (lane >> 2)) * 128, x0 = ((lane & 3) * 2) ^ (lane >> 2);
#pragma unroll 1
        for (int i = 0; i < 32; i++) {
          const bool tail = (i >> 1) == 4;
          const int kb = tail ? i + 22 : i < 8 ? i : i - 2;
          if (i == 8) mbar_wait(bars + B_RT1, L);
          if (!tail) mbar_wait(bars + B_FULL + c.s * 8, c.ph ^ 1);
#pragma unroll
          for (int e = 0; e < 2; e++) {
            const uint4 a = lds128(!tail ? sb + c.s * ST_BYTES + ro + ((x0 ^ e) << 4) : sb + SM_WT + w * 2176 + (lane >> 2) * 272 + (i - 8) * 128 + (lane & 3) * 32 + e * 16);
            const uint4 m = lds128(sb + SM_RT + 4096 + kb * 128 + (lane & 3) * 32 + e * 16);
            cv = fmaf(blo(a.x), blo(m.x), fmaf(bhi(a.x), bhi(m.x), fmaf(blo(a.y), blo(m.y), fmaf(bhi(a.y), bhi(m.y), cv))));
            cv = fmaf(blo(a.z), blo(m.z), fmaf(bhi(a.z), bhi(m.z), fmaf(blo(a.w), blo(m.w), fmaf(bhi(a.w), bhi(m.w), cv))));
          }
          if (!tail) {
            mbar_arrive_if(el, bars + B_AD + c.s * 8 + (__float_as_uint(cv) & P.zero));
            c.next();
          }
        }
        TRC(el, 3, w * 32 + L * 16 + 11);
        uint32_t tag = t8;
        asm volatile("" : "+r"(tag));
        tag = (tag >> 2) - 1 + L;
        cv = qsum(cv);
        uint2* const cs = (uint2*)(P.s->XST + (rb * 2 + w) * 128 + 1);
        if ((lane & 3) == 0) ll_st64(cs + 32 * j + (lane >> 2) * 4, __float_as_uint(cv), tag);
#pragma unroll 1
        for (int it = 0; it < (1 << 22); it++) {
          const uint2 a = ll_ld64(cs + 4 * lane), b = ll_ld64(cs + 128 + 4 * lane);
          if (__all_sync(~0u, a.y == tag && b.y == tag)) { sts32(sb + SM_CV + w * 256 + lane * 4, a.x); sts32(sb + SM_CV + w * 256 + 128 + lane * 4, b.x); break; }
        }
        __syncwarp();
        if (el) mbar_arrive(bars + B_CV + w * 8);
        TRC(el, 3, w * 32 + L * 16 + 12);
#pragma unroll 1
        for (int kb = 30; kb < 32; kb++) {
          mbar_wait(bars + B_FULL + c.s * 8, c.ph ^ 1);
          if (el) mbar_arrive(bars + B_AD + c.s * 8);
          c.next();
        }
        c.ph ^= ((c.s + 10) >> 2) & 1; c.s = (c.s + 10) & 3;
        if (L == 0) {
          mbar_wait(ev + EV_P4 * 8, 0);
          flag_add_p(el, fj + FJ_P4);
          flag_add_p(el, fr + FR_EP + j);
        }
      }
    } else {
      const uint32_t epoch = ldcg32(fj + FJ_EP + rb);
      TRC(el, 2, 33);
      if (SPL) {
        mbar_wait(bars + B_RES + 8, 0);
        TRC(el, 2, 41);
        flag_release_p(el, fj + FJ_WQ0);
        TRC(el, 2, 42);
      }
      mbar_wait(bars + B_IMG, 0);
      TRC(el, 2, 39);
      flag_release_p(el, fj + FJ_WQ);
      TRC(el, 2, 40);
#pragma unroll 1
      for (int L = 0; L < 2; L++) {
        auto wo_fetch = [&]() {
          expect_tx_p(el, bars + B_WOI, 5760);
          asm volatile("{\n.reg .pred P;\nsetp.ne.u32 P, %5, 0;\n@P cp.async.bulk.tensor.4d.shared::cluster.global.mbarrier::complete_tx::bytes [%0], [%1, {0, 0, %3, %4}], [%2];\n}" ::"r"(sb + SM_WOI), "l"(&P.wo8), "r"(bars + B_WOI), "r"(9 * j), "r"((9 * rb) >> 1), "r"(el) : "memory");
        };
        float* const csf = P.s->CSP + (NCTA + bid) * 216;
        if (L == 0) {
          flag_wait(fj + FJ_WQ, (epoch + 1) * 16);
          fence_async_g();
          expect_tx_p(el, bars + B_XRW, 13824);
          bulk_load_p(el, sb + ST_BYTES + SM_WOI, P.s->CSP + j * 16 * 216, 6912, bars + B_XRW);
          bulk_load_p(el, sb + 2 * ST_BYTES + SM_WOI, P.s->CSP + (j * 16 + 8) * 216, 6912, bars + B_XRW);
          wo_fetch();
          mbar_wait(bars + B_XRW, 0);
#pragma unroll 1
          for (int f = lane; f < 54; f += 32) {
            float s[4] = {0.f, 0.f, 0.f, 0.f};
#pragma unroll 4
            for (int r = 0; r < 16; r++) {
              const uint4 v = lds128(sb + ST_BYTES + SM_WOI + (r >> 3) * ST_BYTES + (r & 7) * 864 + f * 16);
              s[0] += __uint_as_float(v.x); s[1] += __uint_as_float(v.y); s[2] += __uint_as_float(v.z); s[3] += __uint_as_float(v.w);
            }
            sts128(sb + SM_CSQ + f * 16, __float_as_uint(s[0]), __float_as_uint(s[1]), __float_as_uint(s[2]), __float_as_uint(s[3]));
            stg128(csf + f * 4, __float_as_uint(s[0]), __float_as_uint(s[1]), __float_as_uint(s[2]), __float_as_uint(s[3]));
          }
          __syncwarp();
          mbar_arrive_if(el, bars + B_CSQ);
        } else {
#pragma unroll 1
          for (int u = 0; u < 4; u++) {
            const int w = u & 1;
            if (u < 2) {
              flag_wait(P.s->flags + (rb * 2 + w) * 32 + FR_X2, (epoch + 1) * 8);
              fence_async_g();
              TRC(el, 2, 48 + u);
              rows_fetch(el, sb + SM_STG + w * 9216, P.xs[1] + (128 * rb + 16 * j + w) * (DM * 2), bars + B_XRW + w * 8);
            } else {
              if (u == 2) {
                expect_tx_p(el, bars + B_CSQ, 864);
                bulk_load_p(el, sb + 2 * ST_BYTES + SM_CSQ, csf, 864, bars + B_CSQ);
              }
              mbar_wait(bars + B_XRW + w * 8, w ^ 1);
              TRC(el, 2, 48 + u);
              rows_stats(sb + SM_STG + w * 9216, P.s->XST + (rb * 2 + w) * 128 + 16 * j, epoch * 2 + 2, lane);
              TRC(el, 2, 50 + u);
            }
          }
        }
        if (L == 0) {
          TRC(el, 2, 43);
          mbar_wait(bars + B_WOI, 0);
          bulk_store_p(el, P.s->WO + j * WO_SL + ((9 * rb) >> 1) * 1152, sb + SM_WOI, 5760);
          publish_p(el, fj + FJ_WO);
          TRC(el, 2, 44);
          const uint8_t* sp = lane < 16 ? (const uint8_t*)P.w_in + (30 * lane + 50) * (FH * 4) + FH * 2 + lane * 256 : (const uint8_t*)P.w_sp + (60 * lane) * (SEQ * 2) + lane * 64;
          float sq = 0.f;
#pragma unroll 1
          for (int u = 0; u < 4; u++) {
            const uint4 y = ldnc128(sp + u * 16);
            const uint32_t x[4] = {y.x, y.y, y.z, y.w};
#pragma unroll
            for (int e = 0; e < 4; e++) sq = fmaf(blo(x[e]), blo(x[e]), fmaf(bhi(x[e]), bhi(x[e]), sq));
          }
#pragma unroll 1
          for (int o = 8; o; o >>= 1) sq += __shfl_xor_sync(~0u, sq, o);
          sq *= lane < 16 ? 2.f * GA * GA * DM / 512.f : C0S * C0S * SEQ / 512.f;
          asm("sqrt.approx.f32 %0, %0;" : "+f"(sq));
          const float o0 = __shfl_sync(~0u, sq, 0), o1 = __shfl_sync(~0u, sq, 16);
          const float p2 = __uint_as_float(min(__float_as_uint(o0) & 0x7f800000u, 0x7e000000u)) * OFK, off = -p2 - fminf(OFA, 0.5f * p2);
          if (el) sts64(sb + SM_OFF, pack2(off, off), min(__float_as_uint(o1) & 0x7f800000u, 0x7e000000u) | 0x00400000u);
        }
        if (el) mbar_arrive(bars + B_GATE3);
        const uint32_t tag = epoch * 2 + L + 1;
        asm volatile("" : "+r"(lane));
        mbar_wait(bars + B_EVT + EV_ZN * 8, L);
        mbar_wait(bars + B_EVT + (EV_N + EV_ZN) * 8, L);
        flag_release_p(el, fj + FJ_ZN + L);
        TRC(el, 2, L * 16 + 8);
        {
          uint4 v[4];
#pragma unroll 1
          for (int it = 0; it < (1 << 22); it++) {
            bool ok = true;
#pragma unroll
            for (int u = 0; u < 4; u++) { v[u] = ll_ld128(P.s->ZST + (rb * 2 + ((lane >> 1) & 1)) * 512 + ((lane & 1) * 4 + u) * 64 + 8 * j + (lane >> 2)); ok = ok && v[u].z == tag; }
            if (__all_sync(~0u, ok)) break;
          }
          float mean = __uint_as_float(v[0].x) + __uint_as_float(v[1].x) + __uint_as_float(v[2].x) + __uint_as_float(v[3].x), M2 = 0.f;
          mean = (mean + __shfl_xor_sync(~0u, mean, 1)) * 0.125f;
#pragma unroll
          for (int u = 0; u < 4; u++) { const float d = __uint_as_float(v[u].x) - mean; M2 += fmaf(288.f * d, d, __uint_as_float(v[u].y)); }
          M2 += __shfl_xor_sync(~0u, M2, 1);
          const float rs = blo(pack2(rsq_fast(fmaf(M2, 1.f / FH, 4.f * GA * GA * LN_EPS)), 0.f));
          if (!(lane & 1)) ll_st64(P.s->RT + 128 * rb + 16 * j + (lane >> 1), pack2(rs, rs * mean), tag);
        }
        TRC(el, 2, L * 16 + 10);
#pragma unroll 1
        for (int b = 0; b < 8; b++) {
          uint4 v[4];
#pragma unroll 1
          for (int it = 0; it < (1 << 22); it++) {
            bool ok = true;
#pragma unroll
            for (int u = 0; u < 4; u++) { v[u] = ll_ld128((const uint4*)P.s->RT + b * 128 + u * 32 + lane); ok = ok && v[u].y == tag && v[u].w == tag; }
            if (__all_sync(~0u, ok)) break;
          }
#pragma unroll
          for (int u = 0; u < 4; u++) {
            const uint32_t rt = sb + SM_RT + b * 512 + u * 128, ro = (lane >> 3) * 32 + (lane & 3) * 8 + ((lane >> 2) & 1) * 2;
            sts32(rt + 4096 + lane * 4, __byte_perm(v[u].x, v[u].z, 0x7632));
            asm volatile("st.shared.u16 [%0], %1;\nst.shared.u16 [%0 + 4], %2;" ::"r"(rt + ro), "h"((uint16_t)v[u].x), "h"((uint16_t)v[u].z) : "memory");
          }
          __syncwarp();
          if (el && (b == 1 || b == 7)) mbar_arrive(bars + (b == 1 ? B_RT : B_RT1));
          TRC(el && b < 2, 2, L * 16 + 11 + b);
        }
        TRC(el, 2, L * 16 + 9);
        mbar_wait(bars + B_EVT + EV_Z1 * 8, L);
        mbar_wait(bars + B_EVT + (EV_N + EV_Z1) * 8, L);
        fence_gpu();
        if (el) mbar_arrive(bars + B_Z1);
        if (L == 0) {
          flag_add_p(el, fj + FJ_EP + rb);
          __nanosleep(NAP0);
          poison(P, el, sb + SM_STG + 17152, &P.psn, rb, j, lane);
          if (el) asm volatile("cp.async.bulk.commit_group;\ncp.async.bulk.wait_group 0;" ::: "memory");
          __syncwarp();
          fence_gpu();
        }
      }
    }
  } else {
    CKK(3);
    uint8_t* const wdst = P.s->WQ + j * WQ_SL + rb * 3456 + tid * 16;
#pragma unroll
    for (int u = 0; u < SPL; u++) stg128_if(tid < 216, wdst + u * (16 * 3456), wv[u].x, wv[u].y, wv[u].z, wv[u].w);
    __syncwarp();
    if (lane == 0) mbar_arrive(bars + B_RES + 8);
    CKK(4);
    auto repack2 = [&]() {
#pragma unroll
      for (int u = SPL; u < 5; u++) stg128_if((u < 4 || rb < 8) && tid < 216, wdst + u * (16 * 3456), wv[u].x, wv[u].y, wv[u].z, wv[u].w);
      float s[8];
#pragma unroll
      for (int e = 0; e < 8; e++) s[e] = 0.f;
#pragma unroll
      for (int u = 0; u < 5; u++) {
        uint32_t x[4] = {wv[u].x, wv[u].y, wv[u].z, wv[u].w};
        asm volatile("" : "+r"(x[0]), "+r"(x[1]), "+r"(x[2]), "+r"(x[3]));
#pragma unroll
        for (int e = 0; e < 4; e++) { s[2 * e] += blo(x[e]); s[2 * e + 1] += bhi(x[e]); }
      }
#pragma unroll
      for (int m = 4; m; m >>= 1) {
#pragma unroll
        for (int e = 0; e < m; e++) s[e] = ((tid & m) ? s[e + m] : s[e]) + __shfl_xor_sync(~0u, (tid & m) ? s[e] : s[e + m], m);
      }
      stg32_if(tid < 216, P.s->CSP + bid * 216 + tid, __float_as_uint(s[0]));
      __syncwarp();
      if (lane == 0) mbar_arrive(bars + B_IMG);
    };
    reg_alloc<232>();
    lane = __shfl_sync(~0u, lane, lane);
    tid = wid * 32 + lane;
    CKK(5);
#pragma unroll
    for (int v = SPL; v < 5; v++) wv[v] = ldnc128_if(tid < 216 && (v < 4 || rb < 8), wsrc + v * (128 * 3 * DM * 2));
    repack2();
    CKK(6);
    const int w = wid >> 2, q = wid & 3;
    int g = lane >> 2, t = lane & 3;
    const uint32_t ev = bars + B_EVT + w * EV_N * 8;
    const bool tr = (tid & 127) == 0;
    (void)tr;
    Cur c{0, 0};
    const uint32_t ebar = mapa(bars + B_EMPTY, (bid & 1) ^ (lane & 1));
    auto release = [&](uint32_t s, uint32_t dep = 0) { mbar_arrive_cluster_if(lane < 2, ebar + s * 8 + dep); };
    auto release_if = [&](bool on, uint32_t s) { mbar_arrive_cluster_if(lane < 2 && on, ebar + s * 8); };
    uint32_t ia = 0;
    auto wait_ab = [&]() { mbar_wait_c(bars + B_FULL + c.s * 8, c.ph); mbar_wait_c(bars + B_FULLA + w * 32 + c.s * 8, (ia >> 2) & 1); ia++; };

    auto yield_done = [&]() { if (w == 0 && lane == 0) mbar_arrive(bars + B_LAG); };
    auto signal = [&](int e) { __syncwarp(); mbar_arrive_if(lane == 0, ev + e * 8); };

    const uint32_t epoch = ldcg32(P.s->flags + (rb * 2 + w) * 32 + FR_EP + j);
    TRC(tr, w, 1);
    CKK(7);
    if (PAD && P.zero) {
#pragma unroll
      for (int i = 0; i < PAD; i++) asm volatile("st.shared.u32 [%0], %1;" ::"r"(sb + i * 20), "r"(tid) : "memory");
    }
    CKK_OUT;

#pragma unroll 1
    for (int L = 0; L < 2; L++) {
      const int tb = 2 + L * 24;
      asm volatile("" : "+r"(lane), "+r"(g), "+r"(t));
      (void)tb;
      ia = 0;
      const uint32_t tag = epoch * 2 + L + 1;
      uint32_t aoff = (w * 64 + q * 16 + (lane & 15)) * 128 + (((lane >> 4) ^ (lane & 7)) << 4);
      {
        uint32_t Pk[27][2];
        float sc0, sc1;
        const uint32_t att = sb + w * 8192 + q * 2048 + lane * 4;
        uint4* hp = P.s->HALO + ((((rb - (q == 0)) * 2 + w) * 8 + j) * 6) * 32 + lane;
        uint8_t* od = o_block(rb, w) + (9 * j) * 1024 + (2 * q) * 128 + lane * 4;
        ACLK_INIT;
        {
          float acc[108];
#pragma unroll
          for (int i = 0; i < 108; i++) acc[i] = 0.f;
          uint32_t prev = 0;
#pragma unroll 1
          for (int kb = 0; kb < 9; kb++) {
            wait_ab();
            if (w == 1 && kb == 9 - LAG1) mbar_wait_c(bars + B_LAG, L);
            TRC(tr && kb == 0, w, tb + 0);
            MCLK(kb == 0, 0);
            PCLK(kb * 4);
            const uint32_t st = sb + c.s * ST_BYTES;
            uint64_t da = dsc2(dlo(st + w * 8192, 16), 0, 0x40000040u + P.zero), db = dsc2(dlo(st + ST_B, 3456), 0, 8 ^ P.zero);
            wgmma_fence();
#pragma unroll
            for (int kk = 0; kk < 4; kk++) {
              wgmma_ss_n216(acc, da, db, 1);
              dadd(da, 2); dadd(db, 432);
              if (kk == 0) { wgmma_commit(); wgmma_wait<1>(); release_if(kb > 0, prev); }
            }
            wgmma_commit();
            if (kb == 8) yield_done();
            PCLK(kb * 4 + 1);
            PCLK(kb * 4 + 2);
            PCLK(kb * 4 + 3);
            prev = c.s; c.next();
          }
          const uint32_t cs = sb + prev * ST_BYTES + SM_CSQ + t * 8;
          mbar_wait_c(bars + B_CSQ, L);
          mbar_wait_c(bars + B_XS + w * 8, L);
          const float2 n0 = lds64f(sb + prev * ST_BYTES + SM_XST + w * 512 + (16 * q + g) * 8), n1 = lds64f(sb + prev * ST_BYTES + SM_XST + w * 512 + (16 * q + g + 8) * 8);
          const float m0 = n0.x, r0 = n0.y, m1 = n1.x, r1 = n1.y;
          float2 cv[27];
#pragma unroll
          for (int G = 0; G < 27; G++) cv[G] = lds64f(cs + G * 32);
          PCLK(36);
          wgmma_wait<0>();
          PCLK(37);
          {
            uint32_t dep = P.zero & __float_as_uint(m0) & __float_as_uint(m1);
#pragma unroll
            for (int G = 0; G < 27; G++) dep &= __float_as_uint(cv[G].x);
            release(prev, dep);
          }
          TRC(tr, w, tb + 1);
          MCLK(1, 1);
          ACLK(0);
#pragma unroll
          for (int G = 9; G < 27; G++) Pk[G][1] = pack2(fmaf(m1, cv[G].x, acc[4 * G + 2]) * r1, fmaf(m1, cv[G].y, acc[4 * G + 3]) * r1);
          if (q < 3) {
#pragma unroll
            for (int i = 0; i < 18; i++) sts32(att + (i >> 4) * ST_BYTES + (i & 15) * 128, Pk[9 + i][1]);
          } else if (rb < 15) {
#pragma unroll
            for (int i = 0; i < 6; i++) ll_st128(hp + i * 32, __uint_as_float(Pk[9 + 3 * i][1]), __uint_as_float(Pk[10 + 3 * i][1]), tag, __uint_as_float(Pk[11 + 3 * i][1]));
          }
#pragma unroll
          for (int G = 0; G < 27; G++) {
            if (G < 9) {
              Pk[G][0] = pack2(fmaf(m0, cv[G].x, acc[4 * G]), fmaf(m0, cv[G].y, acc[4 * G + 1]));
              Pk[G][1] = pack2(fmaf(m1, cv[G].x, acc[4 * G + 2]), fmaf(m1, cv[G].y, acc[4 * G + 3]));
            } else {
              Pk[G][0] = pack2(fmaf(m0, cv[G].x, acc[4 * G]) * r0, fmaf(m0, cv[G].y, acc[4 * G + 1]) * r0);
            }
          }
          sc0 = r0 * (0.23570226039551584f * 1.4426950408889634f); sc1 = r1 * (0.23570226039551584f * 1.4426950408889634f);
        }
        ACLK(1);
        constexpr int GA_[4] = {0, 2, 4, 7}, GB_[4] = {1, 3, 5, 8}, GC_[4] = {2, 4, 6, 6};
        float S1[4][4], S2[4][4];
        uint32_t qa[4][2], qc[4][2];
#pragma unroll
        for (int h = 0; h < 4; h++) {
#pragma unroll
          for (int r = 0; r < 2; r++) {
            qa[h][r] = (h == 0 || h == 3 || t >= h) ? Pk[GA_[h]][r] : 0u;
            qc[h][r] = (h == 3 ? t == 3 : t <= h) ? Pk[GC_[h]][r] : 0u;
          }
          mma16(S1[h], qa[h][0], qa[h][1], Pk[GB_[h]][0], Pk[GB_[h]][1], Pk[9 + GA_[h]][0], Pk[9 + GB_[h]][0]);
          mma16(S2[h], qa[h][0], qa[h][1], Pk[GB_[h]][0], Pk[GB_[h]][1], Pk[9 + GA_[h]][1], Pk[9 + GB_[h]][1]);
        }
#pragma unroll
        for (int h = 0; h < 4; h++) {
          mma8(S1[h], qc[h][0], qc[h][1], Pk[9 + GC_[h]][0]);
          mma8(S2[h], qc[h][0], qc[h][1], Pk[9 + GC_[h]][1]);
        }
        uint32_t V1[9], V2[9];
#pragma unroll
        for (int i = 0; i < 9; i++) { V1[i] = movm(Pk[18 + i][0]); V2[i] = movm(Pk[18 + i][1]); }
        const bool remote = q == 0 && rb > 0;
        uint4 hv[6];
#pragma unroll
        for (int i = 0; i < 6; i++) hv[i] = make_uint4(0u, 0u, tag, 0u);
        if (remote) {
#pragma unroll
          for (int i = 0; i < 6; i++) hv[i] = ll_ld128(hp + i * 32);
        }
        const bool up0 = 2 * t > g, up1 = 2 * t + 1 > g;
        const uint32_t mup = (up0 ? 0xffffu : 0u) | (up1 ? 0xffff0000u : 0u);
        auto finish = [&](const float (&x0)[4], const float (&x1)[4], uint32_t ma, const uint32_t (&Vb)[9], int hi) {
          uint32_t pa[4], pb[4];
          float rs[4];
#pragma unroll
          for (int h = 0; h < 4; h++) {
            const float m = qmax(fmaxf(x0[h], x1[h]));
            const uint32_t p = pack2(ex2(x0[h] - m), ex2(x1[h] - m));
            pa[h] = p & ma; pb[h] = p & ~ma;
          }
#pragma unroll
          for (int h = 0; h < 4; h += 2) {
            float R[4];
            mma16(R, pa[h], pa[h + 1], pb[h], pb[h + 1], 0x3f803f80u, 0x3f803f80u);
            rs[h] = rcp_fast(R[0]); rs[h + 1] = rcp_fast(R[2]);
          }
#pragma unroll
          for (int i = 0; i < 9; i++) {
            const int h = 4 * i / 9, e = (h & 1) * 2;
            const bool split = i == 2 || i == 4 || i == 6, nx = split && 2 * t >= i;
            float O[4], N[4];
            mma16(O, pa[h & 2], pa[h | 1], pb[h & 2], pb[h | 1], V1[i], Vb[i]);
            if (i == 4) mma16(N, pa[2], pa[3], pb[2], pb[3], V1[i], Vb[i]); else { N[0] = O[2]; N[1] = O[3]; }
            const float r = nx ? rs[h + (split ? 1 : 0)] : rs[h];
            stg32(od + i * 1024 + hi * 128, pack2((nx ? N[0] : O[e]) * r, (nx ? N[1] : O[e + 1]) * r));
          }
        };
        {
          float x0[4], x1[4];
#pragma unroll
          for (int h = 0; h < 4; h++) { x0[h] = (up0 ? S1[h][2] : S2[h][2]) * sc1; x1[h] = (up1 ? S1[h][3] : S2[h][3]) * sc1; }
          finish(x0, x1, mup, V2, 1);
        }
        ACLK(2);
        bar_sync(1 + w, 128);
        uint32_t H[18];
        if (q > 0) {
#pragma unroll
          for (int i = 0; i < 18; i++) H[i] = lds32(att - 2048 + (i >> 4) * ST_BYTES + (i & 15) * 128);
        } else {
#pragma unroll 1
          for (int it = 0; it < (1 << 20); it++) {
            bool ok = true;
#pragma unroll
            for (int i = 0; i < 6; i++) ok = ok && hv[i].z == tag;
            if (__all_sync(~0u, ok)) break;
#pragma unroll
            for (int i = 0; i < 6; i++) hv[i] = ll_ld128(hp + i * 32);
          }
#pragma unroll
          for (int i = 0; i < 6; i++) { H[3 * i] = hv[i].x; H[3 * i + 1] = hv[i].y; H[3 * i + 2] = hv[i].w; }
        }
        float S0[4][4];
#pragma unroll
        for (int h = 0; h < 4; h++) {
          mma16(S0[h], qa[h][0], qa[h][1], Pk[GB_[h]][0], Pk[GB_[h]][1], H[GA_[h]], H[GB_[h]]);
        }
#pragma unroll
        for (int h = 0; h < 4; h++) mma8(S0[h], qc[h][0], qc[h][1], H[GC_[h]]);
        uint32_t V0[9];
#pragma unroll
        for (int i = 0; i < 9; i++) V0[i] = movm(H[9 + i]);
        ACLK(3);
        {
          const bool nohalo = (rb | q) == 0;
          const float b0 = up0 && nohalo ? -INFINITY : 0.f, b1 = up1 && nohalo ? -INFINITY : 0.f;
          float x0[4], x1[4];
#pragma unroll
          for (int h = 0; h < 4; h++) { x0[h] = fmaf(up0 ? S0[h][0] : S1[h][0], sc0, b0); x1[h] = fmaf(up1 ? S0[h][1] : S1[h][1], sc0, b1); }
          finish(x0, x1, ~mup, V0, 0);
        }
        ACLK(4);
        signal(EV_O);
        ACLK_OUT;
        TRC(tr, w, tb + 2);
        MCLK(1, 2);
      }
      {
        float acc[36];
        const int hw = rb * 2 + (j & 1), js = (j & 6) + w;
        const uint32_t xt = sb + SM_STG + (16 * q + (lane & 15)) * 288 + (9 * w + (lane >> 4)) * 16, eye = (g >> 1) == t ? 0x3f80u << (g & 1) * 16 : 0u;
        uint32_t xm = xt ^ ((lane & 4) << 2), xl = sb + SM_STG + (2 * q + w) * 2304;
        uint32_t xl0 = xl + (lane >> 4) * 288 + (lane & 15) * 16, xl1 = xl + ((lane >> 1) & 7) * 288 + 256 + ((lane ^ (lane >> 3)) & 1) * 16;
        uint8_t* xd0 = P.xs[L + 1] + (128 * rb + 32 * q + 16 * w + (j & 1)) * (DM * 2) + (j & 6) * 144;
        uint8_t* xd1 = xd0 + (lane >> 1) * (DM * 4) + 256 + (lane & 1) * 16;
        xd0 += (lane >> 4) * (DM * 4) + (lane & 15) * 16;
        asm volatile("" : "+r"(xm), "+r"(xl0), "+r"(xl1), "+l"(xd0), "+l"(xd1));
        mbar_wait_c(bars + B_RES, L);
        TRC(tr, w, tb + 21);
#pragma unroll
        for (int u = 0; u < 5; u++) {
          uint32_t r[4];
          ldsm4(r, xt + u * 32);
          widen(acc + 8 * u, r[0], r[1], eye);
          if (u < 4) widen(acc + 8 * u + 4, r[2], r[3], eye);
        }
        uint32_t prev = 0;
#pragma unroll 1
        for (int u = 0; u < 5; u++) {
          const uint32_t st = sb + c.s * ST_BYTES;
          uint64_t da = dsc2(dlo(st, 1024), 0, 8 + P.zero), db = dsc2(dlo(st + ST_B + w * 18432, 1152), 0, 8 ^ P.zero);
          mbar_wait_c(bars + B_FULL + c.s * 8, c.ph); mbar_wait_c(bars + B_FULLA + c.s * 8, (ia >> 2) & 1);
          TRC(tr && u == 0, w, tb + 3);
          MCLK(u == 0, 3);
          wgmma_fence();
#pragma unroll
          for (int kk = 0; kk < 4; kk++) { wgmma_ss_n72(acc, da, db, 1); dadd(da, 128); dadd(db, 144); }
          wgmma_commit();
          wgmma_wait<1>();
          release_if(u > 0, prev);
          mbar_wait_c(bars + B_FULLA + 32 + c.s * 8, (ia >> 2) & 1);
          ia++;
          if (u == 4) break;
          wgmma_fence();
#pragma unroll
          for (int kk = 4; kk < 8; kk++) { wgmma_ss_n72(acc, da, db, 1); dadd(da, 128); dadd(db, 144); }
          wgmma_commit();
          prev = c.s; c.next();
        }
        RCLK_INIT;
        wgmma_wait<0>();
        RCLK(0);
        release(c.s);
        c.next();
        if (__builtin_expect(any_nan(acc[0], acc[2]), 0)) {
          SLOW(L);
          const uint8_t* xr = P.xs[L] + (128 * rb + 32 * q + 2 * g + (j & 1)) * (DM * 2) + js * 144 + t * 4;
#pragma unroll
          for (int i = 0; i < 9; i++) widen(acc + 4 * i, ldgpu32(xr + i * 16), ldgpu32(xr + i * 16 + DM * 32), eye);
          redo<KS2, 9, 1024, 128, 1152, 128>(acc, o_block(rb, j & 1) + q * 256 + lane * 4, P.s->WO + js * WO_SL + lane * 4, [](uint32_t*, int) {});
        }
        TRC(tr && P5TRACE != 5, w, tb + 4);
        MCLK(1, 4);
#pragma unroll
        for (int u = 0; u < 4; u++)
          stsm4(xm + u * 32, pack2(acc[8 * u], acc[8 * u + 1]), pack2(acc[8 * u + 2], acc[8 * u + 3]), pack2(acc[8 * u + 4], acc[8 * u + 5]), pack2(acc[8 * u + 6], acc[8 * u + 7]));
        asm volatile("stmatrix.sync.aligned.m8n8.x2.shared.b16 [%0], {%1,%2};" ::"r"(xm + 128), "r"(pack2(acc[32], acc[33])), "r"(pack2(acc[34], acc[35])) : "memory");
        auto stats = [&]() {
          float s0 = 0.f, s1 = 0.f, q0 = 0.f, q1 = 0.f;
#pragma unroll
          for (int i = 0; i < 36; i++) {
            if (i & 2) { s1 += acc[i]; q1 = fmaf(acc[i], acc[i], q1); } else { s0 += acc[i]; q0 = fmaf(acc[i], acc[i], q0); }
          }
          s0 = qsum(s0); s1 = qsum(s1); q0 = qsum(q0); q1 = qsum(q1);
          const float ss = t ? s1 : s0, m = ss * (1.f / 72.f);
          ll_st128_if(t < 2, P.s->ST1 + (hw * 8 + js) * 64 + 16 * q + 8 * t + g, m, fmaxf((t ? q1 : q0) - ss * m, 0.f), tag);
        };
        stats();
        RCLK(1);
        bar_sync(8 + q, 64);
        RCLK(2);
#pragma unroll
        for (int u = 0; u < 5; u++) {
          const uint4 v = lds128(u < 4 ? (xl0 ^ ((u & 2) << 3)) + u * 576 : xl1);
          stg128_if(u < 4 || lane < 16, u < 4 ? xd0 + u * (DM * 8) : xd1, v.x, v.y, v.z, v.w);
        }
        RCLK(3);
        signal(EV_X1);
        RCLK(4);
        RCLK(5);
        TRC(tr, w, tb + 5);
        RCLK(6);
        RCLK_OUT;
      }
      uint32_t zk[16];
      {
        uint32_t xA[36][4];
        float acc[32];
        uint32_t s0, one, off2;
        uint8_t *z1d, *zd;
        uint64_t db;
        auto bwait = [&](uint32_t dhi, bool skip) {
          s0 = c.s;
          c.next();
          if (!skip) mbar_wait_c(bars + B_FULL + c.s * 8, c.ph);
          db = dsc2(dlo(sb + s0 * ST_BYTES + ST_B, 512) - 3, 0, dhi); one = (c.s ^ P.zero) & 1;
        };
        auto mma = [&](int kk, int pp, bool hand) {
          wgmma_rs_n64(acc, xA[kk], dat(db, (kk / 18) * ST_BYTES + (kk % 18) * 2048 + 48, one), kk != 0);
          if (kk == pp && hand) bar_arrive(7 - w, 256);
          if (kk == 17 || kk == 35) wgmma_commit();
          if (kk == RL3) { wgmma_commit(); wgmma_wait<1>(); release(s0); }
        };
        {
          bwait(0x40000040u, false);
          mbar_wait_c(bars + B_GATE3, L);
          float mean0, mean1, rs0, rs1;
          stat_get(P.s->ST1 + ((rb * 2 + w) * 8 + 2 * t) * 64 + 16 * q + g, tag, 72.f, LN_EPS, mean0, rs0, mean1, rs1);
          const uint32_t ns0 = pack2(GA * rs0, GA * rs0), ns1 = pack2(GA * rs1, GA * rs1);
          const uint32_t nb0 = pack2(-mean0 * blo(ns0), -mean0 * blo(ns0)), nb1 = pack2(-mean1 * blo(ns1), -mean1 * blo(ns1));
          const uint32_t al = sb + (aoff & 8191);
#pragma unroll
          for (int kb = 0; kb <= 9; kb++) {
            if (kb < 9) {
              mbar_wait_c(bars + B_FA3 + (9 * w + kb) * 8, L);
              TRC(tr && kb == 0, w, tb + 6);
              MCLK(kb == 0, 5);
              if (kb == 0) SCLK(0);
              QCLK(kb);
              const uint32_t at = al + (w ? (((kb + 1) >> 1) & 3) * ST_BYTES + ((kb + 1) & 1) * 8192 : ((kb >> 1) & 3) * ST_BYTES + (kb & 1) * 8192);
#pragma unroll
              for (int kk = 4 * kb; kk < 4 * kb + 4; kk++) ldsm4(xA[kk], at ^ ((kk & 3) << 5));
            }
            if (kb == 0) continue;
            const uint32_t dep = xA[4 * kb - 4][0] & xA[4 * kb - 3][0] & xA[4 * kb - 2][0] & xA[4 * kb - 1][0] & P.zero;
            mbar_arrive_if(lane == 0 && (kb == 1 || w == 0), bars + B_EA3 + (9 * w + kb - 1) * 8 + dep);
#pragma unroll
            for (int kk = 4 * kb - 4; kk < 4 * kb; kk++) {
#pragma unroll
              for (int e = 0; e < 4; e++) xA[kk][e] = hfma2(xA[kk][e], (e & 1) ? ns1 : ns0, (e & 1) ? nb1 : nb0);
            }
            wgmma_fence();
#pragma unroll
            for (int kk = 4 * kb - 4; kk < 4 * kb; kk++) mma(kk, PP30, w);
          }
          off2 = lds32(sb + SM_OFF);
          z1d = z1_block(rb, w, j) + (tid & 127) * 16;
          zd = z2_block(2 * rb + (q >> 1), j) + (4 * (q & 1) + w) * 4608 + ((g & 3) * 2 + (g >> 2)) * 16 + t * 4;
          asm volatile("" : "+l"(z1d), "+l"(zd));
          wgmma_wait<0>();
          if (__builtin_expect(any_nan(acc[0], acc[2]), 0)) {
            SLOW(2 + L);
            uint4* const rd = P.s->RD + bid * (36 * 256) + tid;
            const uint8_t* xr = P.xs[L + 1] + (128 * rb + 32 * q + 2 * g + w) * (DM * 2) + t * 4;
#pragma unroll
            for (int i = 0; i < 32; i++) acc[i] = 0.f;
            redo<KS3, 8, 16, DM * 32, FH * 32, 16>(acc, xr, (const uint8_t*)P.w_in + g * (FH * 4) + (((9 * j + 1) >> 1) + 36) * 128 + t * 4,
                                              [&](uint32_t* a, int k) {
#pragma unroll
                                                for (int e = 0; e < 4; e++) a[e] = hfma2(a[e], (e & 1) ? ns1 : ns0, (e & 1) ? nb1 : nb0);
                                                stg128(rd + k * 256, a[0], a[1], a[2], a[3]);
                                              });
#pragma unroll
            for (int k = 0; k < 36; k++) { const uint4 v = ldcg128(rd + k * 256); xA[k][0] = v.x; xA[k][1] = v.y; xA[k][2] = v.z; xA[k][3] = v.w; }
          }
        }
        float sm[4] = {0.f, 0.f, 0.f, 0.f}, qq[4] = {0.f, 0.f, 0.f, 0.f};
        auto gelu = [&](auto nz2) {
          constexpr int NZ2 = nz2.value, R = 8 - NZ2, N = 8, D = NZ2 == 8 ? GM2 : NZ2 ? GMM : GM1;
          float th[32], gb = GB;
          uint32_t qa = 0, qb = 0;
          auto head = [&](int G) {
#pragma unroll
            for (int e = 0; e < 4; e++) { const float v = acc[4 * G + e]; th[4 * G + e] = tanh_fast(v * fmaf(v, v, gb)); }
          };
#pragma unroll
          for (int i = 0; i < D; i++) head((i + R) & 7);
#pragma unroll
          for (int i = 0; i < N; i++) {
            const int G = (i + R) & 7;
            if (i + D < N) head((i + D + R) & 7);
            float* z = acc + 4 * G;
#pragma unroll
            for (int e = 0; e < 4; e++) z[e] = fmaf(z[e], th[4 * G + e], z[e]);
            uint32_t pa = pack2(z[0], z[1]), pb = pack2(z[2], z[3]), tok;
            if (i < NZ2) {
#pragma unroll
              for (int e = 0; e < 4; e++) { sm[e] += z[e]; qq[e] = fmaf(z[e], z[e], qq[e]); }
              pa = hsub2(pa, off2); pb = hsub2(pb, off2);
              stg32(zd + i * 128, pa); stg32(zd + i * 128 + 9216, pb);
              tok = pa ^ pb ^ __float_as_uint(qq[1]);
            } else {
              if (NZ2 && G == 3) sts128(sb + SM_STG + tid * 16, qa, qb, pa, pb);
              else if (G & 1) stg128(z1d + (G >> 1) * 2048 + (NZ2 ? 24576 : 0), qa, qb, pa, pb);
              qa = pa; qb = pb;
              tok = pa ^ pb;
            }
            gb = __uint_as_float(tok * P.zero + __float_as_uint(GB));
          }
        };
        auto done = [&](int p) {
          wgmma_wait<0>();
          release(c.s);
          c.next();
          TRC(tr && p == 4, w, tb + 7);
          TRC(tr && p == 8, w, tb + 11);
          MCLK(p == 8, 6);
          SCLK(2 * p + 1);
          QCLK(10 + 3 * p);
        };
        auto pass = [&](int p, uint32_t dhi) {
          SCLK(2 * p);
          QCLK(8 + 3 * p);
          bwait(dhi, w);
          bar_sync(6 + w, 256);
          TRC(tr && p == 5, w, tb + 10);
          wgmma_fence();
#pragma unroll
          for (int kk = 0; kk < 36; kk++) mma(kk, PP3, w == 0 || p < 8);
          done(p);
        };
        done(0);
#pragma unroll 1
        for (int p = 1; p < 5; p++) {
          gelu(Int<8>{});
          zd += 1024;
          pass(p, p == 4 ? 0x80000040u : 0x40000040u);
        }
        gelu(Int<4>{});
        signal(EV_ZN);
        {
          const float a0 = qsum(sm[0] + sm[1]), a1 = qsum(sm[2] + sm[3]), q0 = qsum(qq[0] + qq[1]), q1 = qsum(qq[2] + qq[3]);
          const float ss = t ? a1 : a0, m = ss * (1.f / 288.f);
          ll_st128_if(t < 2, P.s->ZST + (rb * 2 + w) * 512 + j * 64 + 16 * q + 8 * t + g, m - blo(off2), fmaxf((t ? q1 : q0) - ss * m, 0.f), tag);
        }
        TRC(tr, w, tb + 8);
        TRC(tr, w, tb + 9);
#pragma unroll 1
        for (int p = 5;; p++) {
          pass(p, 0x40000040u);
          if (p == 8) break;
          gelu(Int<0>{});
          z1d += 8192;
        }
        signal(EV_Z1);
#pragma unroll
        for (int i = 0; i < 16; i++) zk[i] = pack2(acc[2 * i], acc[2 * i + 1]);
        SCLK(18);
        TRC(tr, w, tb + 12);
      }
      uint32_t hA[18][4];
      {
        float acc[144];
        const float c0 = __uint_as_float(lds32(sb + SM_OFF + 4));
#pragma unroll
        for (int i = 0; i < 144; i++) {
          asm volatile("fma.rn.f32 %0, %1, %2, %3;" : "=f"(acc[i]) : "f"(__uint_as_float(P.zero)), "f"((float)(i + 2)), "f"(c0));
        }
        uint32_t prev = 0;
        auto stage = [&](int kb, auto odd) {
          mbar_wait_c(bars + B_FULL + c.s * 8, c.ph);
          TRC(tr && kb == 0, w, tb + 13);
          SCLK(22 + kb);
          const uint32_t st = sb + c.s * ST_BYTES, rt = sb + SM_RT + kb * 128 + t * 8;
          uint64_t db = dsc2(dlo(st + ST_B, 4608), 0, 8 + P.zero);
          uint32_t a[4][4];
#pragma unroll
          for (int kk = 0; kk < 4; kk++) {
            uint32_t r[4];
            ldsm4(r, st + (aoff ^ (kk << 5)));
            const uint2 sc = lds64(rt + kk * 32);
            a[kk][0] = hmul2(__byte_perm(r[0], r[2], 0x5410), sc.x); a[kk][2] = hmul2(__byte_perm(r[0], r[2], 0x7632), sc.y);
            a[kk][1] = hmul2(__byte_perm(r[1], r[3], 0x5410), sc.x); a[kk][3] = hmul2(__byte_perm(r[1], r[3], 0x7632), sc.y);
          }
          if (!odd.value) {
            const float x = blo(zk[0]), y = bhi(zk[0]);
#pragma unroll
            for (int i = 0; i < 15; i++) zk[i] = zk[i + 1];
            zk[15] = pack2(fmaf(x, tanh_fast(x * fmaf(x, x, GB)), x), fmaf(y, tanh_fast(y * fmaf(y, y, GB)), y));
          }
          wgmma_fence();
#pragma unroll
          for (int i = 0; i < 8; i++) {
            const int kk = i & 3, hf = i >> 2;
            wgmma_rs_n144(acc + hf * 72, a[kk], db, 1);
            dadd(db, i == 3 ? 144u - 3 * 576 : 576 + P.zero);
            if (i == 0) { wgmma_commit(); wgmma_wait<1>(); release_if(kb, prev); }
            if (i == 3) wgmma_commit();
          }
          wgmma_commit();
          prev = c.s; c.next();
        };
        mbar_wait_c(bars + B_RT, L);
#pragma unroll 1
        for (int kb = 0; kb < 32; kb += 2) {
          if (kb == 8) mbar_wait_c(bars + B_RT1, L);
          MCLK((kb & 7) == 4, 10 + (kb >> 3));
          stage(kb, Int<0>{});
          stage(kb + 1, Int<1>{});
        }
        if (w == 1) bar_arrive(6, 256);
        HCLK(0);
        mbar_wait_c(bars + B_CV + w * 8, L);
        HCLK(1);
        const float gk = 0.5f / GA;
        const float c1 = __uint_as_float(lds32(sb + SM_OFF + 4));
        const float gb0 = -gk * (c1 + __uint_as_float(lds32(sb + SM_CV + w * 256 + (16 * q + g) * 4))), gb1 = -gk * (c1 + __uint_as_float(lds32(sb + SM_CV + w * 256 + (16 * q + g + 8) * 4)));
        mbar_wait_c(w ? bars + B_FULL + c.s * 8 : bars + B_ZB, w ? c.ph : L);
        HCLK(2);
        const uint32_t sx = c.s;
        c.next();
        const uint32_t zt = sb + tid * 16, zs = zt + sx * ST_BYTES + w * 24576;
        uint4 zz[18];
        auto zload = [&](int u) {
          if (ZW && u == ZW && P.zero) __nanosleep(0);
          if (u >= 12 && u < 16) zz[u] = make_uint4(zk[4 * u - 48], zk[4 * u - 47], zk[4 * u - 46], zk[4 * u - 45]); else zz[u] = lds128(u == 17 ? zt + SM_STG : zs + (u < 12 ? u : 12) * 2048);
        };
#pragma unroll
        for (int u = 0; u < ZA; u++) zload(u);
#pragma unroll
        for (int u = 0; u < 18; u++) {
          if (u == 0) { wgmma_wait<1>(); HCLK(3); }
          if (u == 9) {
            HCLK(4);
            wgmma_wait<0>();
            HCLK(5);
            release(prev);
            mbar_arrive_if(L == 0 && lane == 0, ev + EV_P4 * 8);
            TRC(tr, w, tb + 14);
            SCLK(54);
          }
          if (u + ZA < 18) zload(u + ZA);
          const uint4 z = zz[u];
          hA[u][0] = hmul2(z.x, pack2(fmaf(acc[8 * u], gk, gb0), fmaf(acc[8 * u + 1], gk, gb0)));
          hA[u][1] = hmul2(z.y, pack2(fmaf(acc[8 * u + 2], gk, gb1), fmaf(acc[8 * u + 3], gk, gb1)));
          hA[u][2] = hmul2(z.z, pack2(fmaf(acc[8 * u + 4], gk, gb0), fmaf(acc[8 * u + 5], gk, gb0)));
          hA[u][3] = hmul2(z.w, pack2(fmaf(acc[8 * u + 6], gk, gb1), fmaf(acc[8 * u + 7], gk, gb1)));
        }
        uint32_t dep = P.zero;
#pragma unroll
        for (int u = 0; u < 18; u++) dep &= hA[u][0];
        release(sx, dep);
        TRC(tr, w, tb + 15);
        HCLK(6);
      }
      {
        const uint32_t el = elect_one();
#pragma unroll 1
        for (int p = 0; p < 9; p++) {
          float acc[32];
          if (w == 0) mbar_wait_c(bars + B_FULL + c.s * 8, c.ph);
          uint64_t db = dsc2(dlo(sb + c.s * ST_BYTES + ST_B + (j & 1) * 4096, 0), 0, 0x40000040u + P.zero);
          HCLK(7 + 2 * p);
          bar_sync(6 + w, 256);
          wgmma_fence();
#pragma unroll
          for (int kk = 0; kk < 18; kk++) {
            wgmma_rs_n64(acc, hA[kk], db, kk != 0);
            dadd(db, kk == 15 ? 128 - (j & 1) * (36864 >> 4) : 128 + P.zero);
            if (kk == PPK && (w == 0 || p < 8)) bar_arrive(7 - w, 256);
          }
          wgmma_commit();
          const uint32_t d = sb + (p & 3) * ST_BYTES, cb = p + j >= 9 ? p + j - 9 : p + j;
          if (el) asm volatile("cp.async.bulk.wait_group.read 3;" ::: "memory");
          __syncwarp();
          wgmma_wait<0>();
          HCLK(8 + 2 * p);
          MCLK(p == 1 || p == 8, 7 + (p >> 3));
          TRC(tr && p == 8, w, tb + 16);
          release_if(L == 0 || p < 5, c.s);
          c.next();
#pragma unroll
          for (int u = 0; u < 4; u++)
            stsm4(d + (aoff ^ (u << 5)), pack2(acc[8 * u], acc[8 * u + 1]), pack2(acc[8 * u + 2], acc[8 * u + 3]), pack2(acc[8 * u + 4], acc[8 * u + 5]), pack2(acc[8 * u + 6], acc[8 * u + 7]));
          fence_async_s();
          __syncwarp();
          tma3d_red_p(el, &P.red[L], cb * 64, rb * 64 + q * 16, w, d + w * 8192 + q * 2048);
          TRC(tr && p == 8, w, tb + 17);
        }
        if (el) asm volatile("cp.async.bulk.wait_group 0;" ::: "memory");
        HCLK(25);
        MCLK(1, 9);
        if (L == 0) signal(EV_PT);
        TRC(tr, w, tb + 18);
      }
    }
  }
}

typedef CUresult (*EncodeFn)(CUtensorMap*, CUtensorMapDataType, cuuint32_t, void*, const cuuint64_t*, const cuuint64_t*, const cuuint32_t*,
                             const cuuint32_t*, CUtensorMapInterleave, CUtensorMapSwizzle, CUtensorMapL2promotion, CUtensorMapFloatOOBfill);

static void make_map(EncodeFn fn, CUtensorMap* m, const void* ptr, int rank, uint64_t d0, uint64_t d1, uint64_t d2, uint64_t s1, uint64_t s2,
                     uint32_t b0, uint32_t b1, uint32_t b2, CUtensorMapSwizzle swz) {
  cuuint64_t dims[3] = {d0, d1, d2}, strides[2] = {s1, s2};
  cuuint32_t box[3] = {b0, b1, b2}, es[3] = {1, 1, 1};
  fn(m, CU_TENSOR_MAP_DATA_TYPE_BFLOAT16, rank, const_cast<void*>(ptr), dims, strides, box, es, CU_TENSOR_MAP_INTERLEAVE_NONE, swz,
     CU_TENSOR_MAP_L2_PROMOTION_L2_128B, CU_TENSOR_MAP_FLOAT_OOB_FILL_NONE);
}

}

extern "C" void kernel_launch(void* const* d_in, const int* in_sizes, int n_in, void* d_out, int out_size) {
  using namespace mk;
  (void)in_sizes; (void)n_in; (void)out_size;
  static EncodeFn fn = nullptr;
  static Scratch* sc;
  if (!fn) {
    cudaGetSymbolAddress((void**)&sc, g_scratch);
    cudaDriverEntryPointQueryResult qr;
    cudaGetDriverEntryPoint("cuTensorMapEncodeTiled", (void**)&fn, cudaEnableDefault, &qr);
    cudaFuncSetAttribute(mega_kernel, cudaFuncAttributeMaxDynamicSharedMemorySize, SM_TOTAL);
  }
  Params p;
  p.wqkv = (const __nv_bfloat16*)d_in[1];
  p.w_in = (const __nv_bfloat16*)d_in[4];
  p.w_sp = (const __nv_bfloat16*)d_in[5];
  p.b_sp = (const __nv_bfloat16*)d_in[6];
  p.w_out = (const __nv_bfloat16*)d_in[7];
  p.zero = 0;
  p.s = sc;
  p.xs[0] = (uint8_t*)d_in[0];
  p.xs[1] = sc->X;
  p.xs[2] = (uint8_t*)d_out;
  make_map(fn, &p.wsp, p.w_sp, 3, 2048, 1024, 2, 8192, 4096, 64, 64, 2, CU_TENSOR_MAP_SWIZZLE_128B);
  for (int i = 0; i < 2; i++) {
    make_map(fn, &p.red[i], p.xs[i + 1], 3, DM, 1024, 2, 2304, 1152, 64, 16, 1, CU_TENSOR_MAP_SWIZZLE_128B);
    make_map(fn, &p.res[i], p.xs[i], 3, DM, 1024, 2, 2304, 1152, 144, 64, 1, CU_TENSOR_MAP_SWIZZLE_NONE);
  }
  make_map(fn, &p.psn, d_out, 3, DM, 1024, 2, 2304, 1152, 144, 4, 1, CU_TENSOR_MAP_SWIZZLE_NONE);
  for (int i = 0; i < 3; i++) make_map(fn, &p.act[i], p.xs[i], 3, DM, 1024, 2, 2304, 1152, 64, 64, 1, CU_TENSOR_MAP_SWIZZLE_128B);
  {
    cuuint64_t dims[4] = {8, 8, 72, 72}, strides[3] = {1152, 16, 9216};
    cuuint32_t box[4] = {8, 8, 9, 5}, es[4] = {1, 1, 1, 1};
    fn(&p.wo8, CU_TENSOR_MAP_DATA_TYPE_BFLOAT16, 4, d_in[2], dims, strides, box, es, CU_TENSOR_MAP_INTERLEAVE_NONE, CU_TENSOR_MAP_SWIZZLE_NONE,
       CU_TENSOR_MAP_L2_PROMOTION_L2_128B, CU_TENSOR_MAP_FLOAT_OOB_FILL_NONE);
  }
  for (int i = 0; i < 2; i++) {
    cuuint64_t dims[4] = {i ? 4608u : 2304u, 8, i ? 1u : 2u, 72}, strides[3] = {9216, 4608, 8 * 9216};
    cuuint32_t box[4] = {i ? 64u : 32u, 8, i ? 1u : 2u, 18}, es[4] = {1, 1, 1, 1};
    fn(i ? &p.win64 : &p.win, CU_TENSOR_MAP_DATA_TYPE_BFLOAT16, 4, d_in[4], dims, strides, box, es, CU_TENSOR_MAP_INTERLEAVE_NONE,
       i ? CU_TENSOR_MAP_SWIZZLE_128B : CU_TENSOR_MAP_SWIZZLE_64B, CU_TENSOR_MAP_L2_PROMOTION_L2_128B, CU_TENSOR_MAP_FLOAT_OOB_FILL_NONE);
  }
  make_map(fn, &p.wout, p.w_out, 2, 576, 2304, 1, 1152, 0, 64, 144, 1, CU_TENSOR_MAP_SWIZZLE_128B);
  mega_kernel<<<NGRID, 384, SM_TOTAL, cudaStreamPerThread>>>(p);
}
```

```cpp
#include <cuda_runtime.h>
#include <cuda.h>
#include <cuda_bf16.h>
#include <stdint.h>

#define MK_TRACE 0
#define MK_DBG 0
#define P5TRACE 0
#define LAG1 3
#define PP3 32
#define PP30 33
#define SPL 2
#define NAP 200
#define NAP0 8000
#define KS2 1
#define KS3 1
#define RL3 21
#define PAD 0
#define ZA 4
#define ZW 10
#define GA3 10
#define GB3 12
#define GM2 1
#define GMM 1
#define GM1 2
#define C0S 32.f
#define OFA 0.125f
#define OFK 2.f
#define PPK 15

namespace mk {

constexpr int SEQ = 2048, DM = 576, FH = 2304;
constexpr int NCTA = 128;
constexpr int NGRID = 132;
constexpr uint32_t ZB = 36864;
constexpr uint32_t WQ_SL = 72 * 3456;
constexpr uint32_t WO_SL = 72 * 1152;
constexpr float LN_EPS = 1e-5f;
constexpr float GA = 0.3292034911525734f, GB = 2.423681954311584f;

constexpr uint32_t ST_BYTES = 53248, ST_B = 16384, NST = 4;
constexpr uint32_t SM_STG = NST * ST_BYTES;
constexpr uint32_t SM_BAR = SM_STG + 2 * 9216;
constexpr uint32_t SM_OFF = SM_BAR + 1008;
constexpr uint32_t SM_TOTAL = SM_BAR + 1024;
constexpr uint32_t SM_RT = SM_STG + 4096, SM_CV = SM_STG + 12288, SM_WT = SM_CV + 512;
constexpr uint32_t SM_WOI = 44032, SM_CSQ = 49792, SM_XST = 50688;
constexpr uint32_t B_FULL = 0, B_EMPTY = 32, B_FULLA = 64, B_RES = 128, B_WT = 144, B_IMG = 160, B_WOI = 168, B_ZB = 176, B_GATE3 = 184, B_Z1 = 192, B_LAG = 200,
                   B_RT = 208, B_CSQ = 216, B_CV = 224, B_AD = 240, B_EVT = 272, B_RT1 = 368, B_XS = 624, B_XRW = 384, B_FA3 = 400, B_EA3 = 544;
enum { EV_PT = 0, EV_O = 1, EV_X1 = 2, EV_ZN = 3, EV_Z1 = 4, EV_P4 = 5, EV_N = 6 };

enum { FR_X2 = 0, FR_O = 1, FR_X1 = 3, FR_EP = 16, FJ = 32 * 32, FJ_WQ = 0, FJ_WO = 1, FJ_WQ0 = 2, FJ_ZN = 3, FJ_P4 = 5, FJ_EP = 16, F_N = FJ + 8 * 32 };

constexpr uint32_t POISON = 0xffffffffu;
struct Scratch {
  uint32_t flags[F_N];
  uint2 RT[SEQ];
  uint4 XST[2 * SEQ];
  uint4 ST1[SEQ * 8], ZST[SEQ * 8], HALO[32 * 8 * 6 * 32];
  float CSP[2 * NCTA * 216];
  uint8_t WQ[8 * WQ_SL], WO[8 * WO_SL];
  uint8_t O[32 * 2 * ZB];
  uint8_t X[SEQ * DM * 2];
  uint8_t Z[512 * ZB];
  uint4 RD[NCTA * 36 * 256];
};
__device__ __align__(1024) Scratch g_scratch;
#define SLOW(i) do {} while (0)

struct Params {
  const __nv_bfloat16 *wqkv;
  Scratch* s;
  uint32_t zero;
  const __nv_bfloat16 *w_in, *w_sp, *b_sp, *w_out;
  uint8_t* xs[3];
  CUtensorMap wo8, wsp, win, win64, wout;
  CUtensorMap act[3];
  CUtensorMap res[2];
  CUtensorMap red[2];
  CUtensorMap psn;
};

__device__ __forceinline__ uint32_t smem_u32(const void* p) { return (uint32_t)__cvta_generic_to_shared(p); }
__device__ __forceinline__ void mbar_init(uint32_t bar, uint32_t cnt) { asm volatile("mbarrier.init.shared::cta.b64 [%0], %1;" ::"r"(bar), "r"(cnt)); }
__device__ __forceinline__ void mbar_arrive(uint32_t bar) { asm volatile("mbarrier.arrive.shared::cta.b64 _, [%0];" ::"r"(bar) : "memory"); }
__device__ __forceinline__ void mbar_wait(uint32_t bar, uint32_t parity) {
  asm volatile(
      "{\n.reg .pred p;\n.reg .u32 c;\nmov.u32 c, 0;\nLAB_WAIT:\n"
      "mbarrier.try_wait.parity.shared::cta.b64 p, [%0], %1;\n@p bra LAB_DONE;\n"
      "add.u32 c, c, 1;\nsetp.lt.u32 p, c, 0x100000;\n@p bra LAB_WAIT;\ntrap;\nLAB_DONE:\n}" ::"r"(bar), "r"(parity)
      : "memory");
}
__device__ __forceinline__ void mbar_wait_c(uint32_t bar, uint32_t parity) {
  asm volatile("{\n.reg .pred p;\nLAB_WAIT:\nmbarrier.try_wait.parity.shared::cta.b64 p, [%0], %1;\n@!p bra LAB_WAIT;\n}" ::"r"(bar), "r"(parity) : "memory");
}
__device__ __forceinline__ void flag_wait(const uint32_t* f, uint32_t target) {
  asm volatile(
      "{\n.reg .pred p;\n.reg .u32 c, v;\nmov.u32 c, 0;\nLAB_WAIT:\n"
      "ld.relaxed.gpu.global.u32 v, [%0];\nsub.u32 v, v, %1;\nsetp.ge.s32 p, v, 0;\n@p bra LAB_DONE;\n"
      "add.u32 c, c, 1;\nsetp.lt.u32 p, c, 0x400000;\n@p bra LAB_WAIT;\ntrap;\nLAB_DONE:\nfence.acquire.gpu;\n}" ::"l"(f), "r"(target)
      : "memory");
}
__device__ __forceinline__ void fence_gpu() { asm volatile("fence.acq_rel.gpu;" ::: "memory"); }
__device__ __forceinline__ void fence_async_g() { asm volatile("fence.proxy.async.global;" ::: "memory"); }
__device__ __forceinline__ void fence_async_s() { asm volatile("fence.proxy.async.shared::cta;" ::: "memory"); }
__device__ __forceinline__ uint32_t elect_one() {
  uint32_t p; asm volatile("{\n.reg .pred P;\nelect.sync _|P, 0xffffffff;\nselp.u32 %0, 1, 0, P;\n}" : "=r"(p)); return p;
}
__device__ __forceinline__ void expect_tx_p(uint32_t el, uint32_t bar, uint32_t bytes) {
  asm volatile("{\n.reg .pred P;\nsetp.ne.u32 P, %2, 0;\n@P mbarrier.arrive.expect_tx.shared::cta.b64 _, [%0], %1;\n}" ::"r"(bar), "r"(bytes), "r"(el) : "memory");
}
__device__ __forceinline__ void bulk_load_p(uint32_t el, uint32_t dst, const void* src, uint32_t bytes, uint32_t bar) {
  asm volatile("{\n.reg .pred P;\nsetp.ne.u32 P, %4, 0;\n@P cp.async.bulk.shared::cluster.global.mbarrier::complete_tx::bytes [%0], [%1], %2, [%3];\n}" ::"r"(dst), "l"(src), "r"(bytes), "r"(bar), "r"(el) : "memory");
}
__device__ __forceinline__ uint64_t policy_evict_first() { uint64_t p; asm("createpolicy.fractional.L2::evict_first.b64 %0, 1.0;" : "=l"(p)); return p; }
__device__ __forceinline__ void bulk_load_h(uint32_t el, uint32_t dst, const void* src, uint32_t bytes, uint32_t bar, bool ef, uint64_t pol) {
  if (ef) {
    asm volatile("{\n.reg .pred P;\nsetp.ne.u32 P, %4, 0;\n@P cp.async.bulk.shared::cluster.global.mbarrier::complete_tx::bytes.L2::cache_hint [%0], [%1], %2, [%3], %5;\n}" ::"r"(dst), "l"(src), "r"(bytes), "r"(bar), "r"(el), "l"(pol) : "memory");
  } else {
    asm volatile("{\n.reg .pred P;\nsetp.ne.u32 P, %4, 0;\n@P cp.async.bulk.shared::cluster.global.mbarrier::complete_tx::bytes [%0], [%1], %2, [%3];\n}" ::"r"(dst), "l"(src), "r"(bytes), "r"(bar), "r"(el) : "memory");
  }
}
__device__ __forceinline__ void bulk_mc_h(uint32_t el, uint32_t dst, const void* src, uint32_t bytes, uint32_t bar, bool ef, uint64_t pol) {
  if (ef) {
    asm volatile("{\n.reg .pred P;\nsetp.ne.u32 P, %4, 0;\n@P cp.async.bulk.shared::cluster.global.mbarrier::complete_tx::bytes.multicast::cluster.L2::cache_hint [%0], [%1], %2, [%3], %5, %6;\n}" ::"r"(dst), "l"(src), "r"(bytes), "r"(bar), "r"(el), "h"((uint16_t)3), "l"(pol) : "memory");
  } else {
    asm volatile("{\n.reg .pred P;\nsetp.ne.u32 P, %4, 0;\n@P cp.async.bulk.shared::cluster.global.mbarrier::complete_tx::bytes.multicast::cluster [%0], [%1], %2, [%3], %5;\n}" ::"r"(dst), "l"(src), "r"(bytes), "r"(bar), "r"(el), "h"((uint16_t)3) : "memory");
  }
}
__device__ __forceinline__ void tma3d_h(uint32_t el, uint32_t dst, const CUtensorMap* m, int c0, int c1, int c2, uint32_t bar, bool ef, uint64_t pol) {
  if (ef) {
    asm volatile("{\n.reg .pred P;\nsetp.ne.u32 P, %6, 0;\n@P cp.async.bulk.tensor.3d.shared::cluster.global.mbarrier::complete_tx::bytes.L2::cache_hint [%0], [%1, {%3, %4, %5}], [%2], %7;\n}" ::"r"(dst), "l"(m), "r"(bar), "r"(c0), "r"(c1), "r"(c2), "r"(el), "l"(pol) : "memory");
  } else {
    asm volatile("{\n.reg .pred P;\nsetp.ne.u32 P, %6, 0;\n@P cp.async.bulk.tensor.3d.shared::cluster.global.mbarrier::complete_tx::bytes [%0], [%1, {%3, %4, %5}], [%2];\n}" ::"r"(dst), "l"(m), "r"(bar), "r"(c0), "r"(c1), "r"(c2), "r"(el) : "memory");
  }
}
__device__ __forceinline__ void tma2d_mc_h(uint32_t el, uint32_t dst, const CUtensorMap* m, int c0, int c1, uint32_t bar, bool ef, uint64_t pol) {
  if (ef) {
    asm volatile("{\n.reg .pred P;\nsetp.ne.u32 P, %5, 0;\n@P cp.async.bulk.tensor.2d.shared::cluster.global.mbarrier::complete_tx::bytes.multicast::cluster.L2::cache_hint [%0], [%1, {%3, %4}], [%2], %6, %7;\n}" ::"r"(dst), "l"(m), "r"(bar), "r"(c0), "r"(c1), "r"(el), "h"((uint16_t)3), "l"(pol) : "memory");
  } else {
    asm volatile("{\n.reg .pred P;\nsetp.ne.u32 P, %5, 0;\n@P cp.async.bulk.tensor.2d.shared::cluster.global.mbarrier::complete_tx::bytes.multicast::cluster [%0], [%1, {%3, %4}], [%2], %6;\n}" ::"r"(dst), "l"(m), "r"(bar), "r"(c0), "r"(c1), "r"(el), "h"((uint16_t)3) : "memory");
  }
}
__device__ __forceinline__ void tma4d_mc(uint32_t el, uint32_t dst, const CUtensorMap* m, int c0, int c3, uint32_t bar, uint64_t pol) {
  asm volatile("{\n.reg .pred P;\nsetp.ne.u32 P, %5, 0;\n@P cp.async.bulk.tensor.4d.shared::cluster.global.mbarrier::complete_tx::bytes.multicast::cluster.L2::cache_hint [%0], [%1, {%3, 0, 0, %4}], [%2], %6, %7;\n}" ::"r"(dst), "l"(m), "r"(bar), "r"(c0), "r"(c3), "r"(el), "h"((uint16_t)3), "l"(pol) : "memory");
}
__device__ __forceinline__ void mbar_arrive_cluster(uint32_t addr) { asm volatile("mbarrier.arrive.shared::cluster.b64 _, [%0];" ::"r"(addr) : "memory"); }
__device__ __forceinline__ void mbar_arrive_cluster_if(bool c, uint32_t addr) {
  asm volatile("{\n.reg .pred P;\nsetp.ne.u32 P, %1, 0;\n@P mbarrier.arrive.shared::cluster.b64 _, [%0];\n}" ::"r"(addr), "r"((uint32_t)c) : "memory");
}
__device__ __forceinline__ void mbar_arrive_if(bool c, uint32_t addr) {
  asm volatile("{\n.reg .pred P;\nsetp.ne.u32 P, %1, 0;\n@P mbarrier.arrive.shared::cta.b64 _, [%0];\n}" ::"r"(addr), "r"((uint32_t)c) : "memory");
}
__device__ __forceinline__ uint32_t mapa(uint32_t addr, uint32_t rank) { uint32_t r; asm("mapa.shared::cluster.u32 %0, %1, %2;" : "=r"(r) : "r"(addr), "r"(rank)); return r; }
__device__ __forceinline__ void bulk_store_p(uint32_t el, void* dst, uint32_t src, uint32_t bytes) {
  asm volatile("{\n.reg .pred P;\nsetp.ne.u32 P, %3, 0;\n@P cp.async.bulk.global.shared::cta.bulk_group [%0], [%1], %2;\n}" ::"l"(dst), "r"(src), "r"(bytes), "r"(el) : "memory");
}
__device__ __forceinline__ void flag_release_p(uint32_t el, uint32_t* f) {
  asm volatile("{\n.reg .pred P;\nsetp.ne.u32 P, %1, 0;\n@P red.release.gpu.global.add.u32 [%0], 1;\n}" ::"l"(f), "r"(el) : "memory");
}
__device__ __forceinline__ void flag_add_p(uint32_t el, uint32_t* f) {
  asm volatile("{\n.reg .pred P;\nsetp.ne.u32 P, %1, 0;\n@P red.relaxed.gpu.global.add.u32 [%0], 1;\n}" ::"l"(f), "r"(el) : "memory");
}
__device__ __forceinline__ void prefetch_l2(const void* src, uint32_t bytes) { asm volatile("cp.async.bulk.prefetch.L2.global [%0], %1;" ::"l"(src), "r"(bytes) : "memory"); }
__device__ __forceinline__ void prefetch_map(const CUtensorMap* m) { asm volatile("prefetch.tensormap [%0];" ::"l"(m) : "memory"); }
__device__ __forceinline__ void wgmma_fence() { asm volatile("wgmma.fence.sync.aligned;" ::: "memory"); }
__device__ __forceinline__ void wgmma_commit() { asm volatile("wgmma.commit_group.sync.aligned;" ::: "memory"); }
template <int N> __device__ __forceinline__ void wgmma_wait() { asm volatile("wgmma.wait_group.sync.aligned %0;" ::"n"(N) : "memory"); }
__device__ __forceinline__ uint32_t dlo(uint32_t addr, uint32_t lbo) { return ((addr & 0x3FFFF) >> 4) + ((lbo >> 4) << 16); }
template <uint32_t SBO, uint32_t SWZ> __device__ __forceinline__ uint64_t dsc(uint32_t lo, uint32_t off) {
  uint64_t d; asm("mov.b64 %0, {%1, %2};" : "=l"(d) : "r"(lo + (off >> 4)), "n"((SBO >> 4) | (SWZ << 30))); return d;
}
__device__ __forceinline__ uint64_t dsc2(uint32_t lo, uint32_t off, uint32_t hi) {
  uint64_t d; asm("mov.b64 %0, {%1, %2};" : "=l"(d) : "r"(lo + (off >> 4)), "r"(hi)); return d;
}
__device__ __forceinline__ uint64_t dat(uint64_t d, uint32_t off, uint32_t one) { uint64_t r; asm("mad.wide.u32 %0, %1, %2, %3;" : "=l"(r) : "r"(one), "r"(off >> 4), "l"(d)); return r; }
__device__ __forceinline__ void dadd(uint64_t& d, uint32_t v) {
  asm("{\n.reg .b32 lo, hi;\nmov.b64 {lo, hi}, %0;\nadd.u32 lo, lo, %1;\nmov.b64 %0, {lo, hi};\n}" : "+l"(d) : "r"(v));
}
template <int R> __device__ __forceinline__ void reg_alloc() { asm volatile("setmaxnreg.inc.sync.aligned.u32 %0;" ::"n"(R)); }
template <int R> __device__ __forceinline__ void reg_dealloc() { asm volatile("setmaxnreg.dec.sync.aligned.u32 %0;" ::"n"(R)); }
__device__ __forceinline__ void bar_sync(int id, int n) { asm volatile("bar.sync %0, %1;" ::"r"(id), "r"(n) : "memory"); }
__device__ __forceinline__ void bar_arrive(int id, int n) { asm volatile("bar.arrive %0, %1;" ::"r"(id), "r"(n) : "memory"); }
__device__ __forceinline__ void ldsm4(uint32_t* r, uint32_t addr) {
  asm volatile("ldmatrix.sync.aligned.m8n8.x4.shared.b16 {%0,%1,%2,%3}, [%4];" : "=r"(r[0]), "=r"(r[1]), "=r"(r[2]), "=r"(r[3]) : "r"(addr) : "memory");
}
__device__ __forceinline__ uint32_t movm(uint32_t a) { uint32_t d; asm volatile("movmatrix.sync.aligned.m8n8.trans.b16 %0, %1;" : "=r"(d) : "r"(a)); return d; }
__device__ __forceinline__ void mma16(float* c, uint32_t a0, uint32_t a1, uint32_t a2, uint32_t a3, uint32_t b0, uint32_t b1) {
  asm volatile("mma.sync.aligned.m16n8k16.row.col.f32.bf16.bf16.f32 {%0,%1,%2,%3}, {%4,%5,%6,%7}, {%8,%9}, {%10,%10,%10,%10};"
               : "=f"(c[0]), "=f"(c[1]), "=f"(c[2]), "=f"(c[3]) : "r"(a0), "r"(a1), "r"(a2), "r"(a3), "r"(b0), "r"(b1), "f"(0.f));
}
__device__ __forceinline__ void mma8(float* c, uint32_t a0, uint32_t a1, uint32_t b0) {
  asm volatile("mma.sync.aligned.m16n8k8.row.col.f32.bf16.bf16.f32 {%0,%1,%2,%3}, {%4,%5}, {%6}, {%0,%1,%2,%3};"
               : "+f"(c[0]), "+f"(c[1]), "+f"(c[2]), "+f"(c[3]) : "r"(a0), "r"(a1), "r"(b0));
}
__device__ __forceinline__ void widen(float* c, uint32_t a0, uint32_t a1, uint32_t eye) {
  asm volatile("mma.sync.aligned.m16n8k8.row.col.f32.bf16.bf16.f32 {%0,%1,%2,%3}, {%4,%5}, {%6}, {%7,%7,%7,%7};"
               : "=f"(c[0]), "=f"(c[1]), "=f"(c[2]), "=f"(c[3]) : "r"(a0), "r"(a1), "r"(eye), "f"(0.f));
}
__device__ __forceinline__ float rsq_fast(float x) { float y; asm("rsqrt.approx.ftz.f32 %0, %1;" : "=f"(y) : "f"(x)); return y; }
__device__ __forceinline__ uint32_t pack2(float lo, float hi) { uint32_t r; asm("cvt.rn.bf16x2.f32 %0, %1, %2;" : "=r"(r) : "f"(hi), "f"(lo)); return r; }
__device__ __forceinline__ float blo(uint32_t v) { return __uint_as_float(v << 16); }
__device__ __forceinline__ float bhi(uint32_t v) { return __uint_as_float(v & 0xffff0000u); }
__device__ __forceinline__ float tanh_fast(float x) { float y; asm("tanh.approx.f32 %0, %1;" : "=f"(y) : "f"(x)); return y; }
__device__ __forceinline__ float rcp_fast(float x) { float y; asm("rcp.approx.ftz.f32 %0, %1;" : "=f"(y) : "f"(x)); return y; }
__device__ __forceinline__ float ex2(float x) { float y; asm("ex2.approx.ftz.f32 %0, %1;" : "=f"(y) : "f"(x)); return y; }
__device__ __forceinline__ float qsum(float v) { v += __shfl_xor_sync(~0u, v, 1); v += __shfl_xor_sync(~0u, v, 2); return v; }
__device__ __forceinline__ float qmax(float v) { v = fmaxf(v, __shfl_xor_sync(~0u, v, 1)); v = fmaxf(v, __shfl_xor_sync(~0u, v, 2)); return v; }
__device__ __forceinline__ void stg32(void* p, uint32_t v) { asm volatile("st.global.u32 [%0], %1;" ::"l"(p), "r"(v) : "memory"); }
__device__ __forceinline__ void stg128(void* p, uint32_t a, uint32_t b, uint32_t c, uint32_t d) { asm volatile("st.global.v4.u32 [%0], {%1,%2,%3,%4};" ::"l"(p), "r"(a), "r"(b), "r"(c), "r"(d) : "memory"); }
__device__ __forceinline__ uint32_t ldcg32(const void* p) { uint32_t v; asm volatile("ld.global.L1::no_allocate.u32 %0, [%1];" : "=r"(v) : "l"(p) : "memory"); return v; }
__device__ __forceinline__ uint32_t ldgpu32(const void* p) { uint32_t v; asm volatile("ld.relaxed.gpu.global.u32 %0, [%1];" : "=r"(v) : "l"(p) : "memory"); return v; }
__device__ __forceinline__ uint32_t ldca32(const void* p) { uint32_t v; asm volatile("ld.global.ca.u32 %0, [%1];" : "=r"(v) : "l"(p) : "memory"); return v; }
__device__ __forceinline__ void stg128_if(bool c, void* p, uint32_t a, uint32_t b, uint32_t cc, uint32_t d) {
  asm volatile("{\n.reg .pred P;\nsetp.ne.u32 P, %5, 0;\n@P st.global.v4.u32 [%0], {%1,%2,%3,%4};\n}" ::"l"(p), "r"(a), "r"(b), "r"(cc), "r"(d), "r"((uint32_t)c) : "memory");
}
__device__ __forceinline__ uint2 lds64(uint32_t a) { uint2 v; asm volatile("ld.shared.v2.u32 {%0,%1}, [%2];" : "=r"(v.x), "=r"(v.y) : "r"(a) : "memory"); return v; }
__device__ __forceinline__ uint4 ldcg128(const void* p) { uint4 v; asm volatile("ld.global.cg.v4.u32 {%0,%1,%2,%3}, [%4];" : "=r"(v.x), "=r"(v.y), "=r"(v.z), "=r"(v.w) : "l"(p) : "memory"); return v; }
__device__ __forceinline__ uint32_t ldnc16(const void* p) { uint16_t v; asm volatile("ld.global.nc.u16 %0, [%1];" : "=h"(v) : "l"(p)); return v; }
__device__ __forceinline__ uint4 ldnc128(const void* p) { uint4 v; asm volatile("ld.global.nc.v4.u32 {%0,%1,%2,%3}, [%4];" : "=r"(v.x), "=r"(v.y), "=r"(v.z), "=r"(v.w) : "l"(p)); return v; }
__device__ __forceinline__ uint32_t hsub2(uint32_t a, uint32_t b) { uint32_t d; asm("sub.rn.bf16x2 %0, %1, %2;" : "=r"(d) : "r"(a), "r"(b)); return d; }
__device__ __forceinline__ void stg32_if(bool c, void* p, uint32_t v) {
  asm volatile("{\n.reg .pred P;\nsetp.ne.u32 P, %2, 0;\n@P st.global.u32 [%0], %1;\n}" ::"l"(p), "r"(v), "r"((uint32_t)c) : "memory");
}
__device__ __forceinline__ uint32_t hmul2(uint32_t a, uint32_t b) { uint32_t d; asm("mul.rn.bf16x2 %0, %1, %2;" : "=r"(d) : "r"(a), "r"(b)); return d; }
__device__ __forceinline__ void sts32(uint32_t a, uint32_t v) { asm volatile("st.shared.u32 [%0], %1;" ::"r"(a), "r"(v) : "memory"); }
__device__ __forceinline__ uint32_t lds32(uint32_t a) { uint32_t v; asm volatile("ld.shared.u32 %0, [%1];" : "=r"(v) : "r"(a) : "memory"); return v; }
__device__ __forceinline__ void sts128(uint32_t a, uint32_t x, uint32_t y, uint32_t z, uint32_t w) { asm volatile("st.shared.v4.u32 [%0], {%1,%2,%3,%4};" ::"r"(a), "r"(x), "r"(y), "r"(z), "r"(w) : "memory"); }
__device__ __forceinline__ uint4 lds128(uint32_t a) { uint4 v; asm volatile("ld.shared.v4.u32 {%0,%1,%2,%3}, [%4];" : "=r"(v.x), "=r"(v.y), "=r"(v.z), "=r"(v.w) : "r"(a) : "memory"); return v; }
__device__ __forceinline__ void ll_st64(uint2* p, uint32_t v, uint32_t tag) {
  asm volatile("{\n.reg .b64 r;\nmov.b64 r, {%1,%2};\nst.relaxed.gpu.global.b64 [%0], r;\n}" ::"l"(p), "r"(v), "r"(tag) : "memory");
}
__device__ __forceinline__ uint2 ll_ld64(const uint2* p) {
  uint2 v; asm volatile("{\n.reg .b64 r;\nld.relaxed.gpu.global.b64 r, [%2];\nmov.b64 {%0,%1}, r;\n}" : "=r"(v.x), "=r"(v.y) : "l"(p) : "memory"); return v;
}
__device__ __forceinline__ void ll_st128(uint4* p, float a, float b, uint32_t tag, float c = 0.f) {
  asm volatile("{\n.reg .b128 r;\n.reg .b64 lo, hi;\nmov.b64 lo, {%1,%2};\nmov.b64 hi, {%3,%4};\nmov.b128 r, {lo, hi};\nst.relaxed.gpu.global.b128 [%0], r;\n}" ::"l"(p), "r"(__float_as_uint(a)), "r"(__float_as_uint(b)), "r"(tag), "r"(__float_as_uint(c)) : "memory");
}
__device__ __forceinline__ uint4 ll_ld128(const uint4* p) {
  uint4 v; asm volatile("{\n.reg .b128 r;\n.reg .b64 lo, hi;\nld.relaxed.gpu.global.b128 r, [%4];\nmov.b128 {lo, hi}, r;\nmov.b64 {%0,%1}, lo;\nmov.b64 {%2,%3}, hi;\n}" : "=r"(v.x), "=r"(v.y), "=r"(v.z), "=r"(v.w) : "l"(p) : "memory"); return v;
}
__device__ __forceinline__ void publish_p(uint32_t el, uint32_t* f) {
  asm volatile("{\n.reg .pred P;\nsetp.ne.u32 P, %1, 0;\n@P cp.async.bulk.commit_group;\n@P cp.async.bulk.wait_group 0;\n@P red.release.gpu.global.add.u32 [%0], 1;\n}" ::"l"(f), "r"(el) : "memory");
}
__device__ __forceinline__ void tma3d_red_p(uint32_t el, const CUtensorMap* m, int c0, int c1, int c2, uint32_t src) {
  asm volatile("{\n.reg .pred P;\nsetp.ne.u32 P, %5, 0;\n@P cp.reduce.async.bulk.tensor.3d.global.shared::cta.add.tile.bulk_group [%0, {%2, %3, %4}], [%1];\n@P cp.async.bulk.commit_group;\n}" ::"l"(m), "r"(src), "r"(c0), "r"(c1), "r"(c2), "r"(el) : "memory");
}
__device__ __forceinline__ void stsm4(uint32_t addr, uint32_t a, uint32_t b, uint32_t c, uint32_t d) {
  asm volatile("stmatrix.sync.aligned.m8n8.x4.shared.b16 [%0], {%1,%2,%3,%4};" ::"r"(addr), "r"(a), "r"(b), "r"(c), "r"(d) : "memory");
}
__device__ __forceinline__ void sts64(uint32_t a, uint32_t x, uint32_t y) { asm volatile("st.shared.v2.u32 [%0], {%1,%2};" ::"r"(a), "r"(x), "r"(y) : "memory"); }
__device__ __forceinline__ void ll_st128_if(bool on, uint4* p, float a, float b, uint32_t tag) {
  asm volatile("{\n.reg .pred P;\n.reg .b128 r;\n.reg .b64 lo, hi;\nsetp.ne.u32 P, %4, 0;\nmov.b64 lo, {%1,%2};\nmov.b64 hi, {%3,%3};\nmov.b128 r, {lo, hi};\n@P st.relaxed.gpu.global.b128 [%0], r;\n}" ::"l"(p), "r"(__float_as_uint(a)), "r"(__float_as_uint(b)), "r"(tag), "r"((uint32_t)on) : "memory");
}
__device__ __forceinline__ uint4 ldnc128_if(bool c, const void* p) {
  uint4 v = make_uint4(0u, 0u, 0u, 0u);
  asm volatile("{\n.reg .pred P;\nsetp.ne.u32 P, %5, 0;\n@P ld.global.nc.v4.u32 {%0,%1,%2,%3}, [%4];\n}" : "+r"(v.x), "+r"(v.y), "+r"(v.z), "+r"(v.w) : "l"(p), "r"((uint32_t)c));
  return v;
}
__device__ __forceinline__ uint32_t hfma2(uint32_t a, uint32_t b, uint32_t c) { uint32_t d; asm("fma.rn.bf16x2 %0, %1, %2, %3;" : "=r"(d) : "r"(a), "r"(b), "r"(c)); return d; }
__device__ __forceinline__ float2 lds64f(uint32_t a) { float2 v; asm volatile("ld.shared.v2.f32 {%0,%1}, [%2];" : "=f"(v.x), "=f"(v.y) : "r"(a) : "memory"); return v; }
#define TRC(cond, role, idx) do {} while (0)
#define TRV(role, idx, v) do {} while (0)

#define ACLK_INIT do {} while (0)
#define ACLK(i) do {} while (0)
#define ACLK_OUT do {} while (0)
#define QCLK(i) do {} while (0)
#define PH 1
#define RCLK(i) do {} while (0)
#define RCLK_INIT do {} while (0)
#define RCLK_OUT do {} while (0)
#define SCLK(i) do {} while (0)
#define HCLK(i) do {} while (0)
#define MCLK(c, i) do {} while (0)
#define CKK(i) do {} while (0)
#define CKK_OUT do {} while (0)
#define PL 1
#define PCLK(i) do {} while (0)
#define PQ 1
#define CLK_INIT do {} while (0)
#define CLK(i) do {} while (0)
#define CLK_OUT do {} while (0)

__device__ __forceinline__ void wgmma_ss_n216(float* d, uint64_t da, uint64_t db, int scaleD) {
  asm volatile("{\n.reg .pred p;\nsetp.ne.b32 p, %110, 0;\nwgmma.mma_async.sync.aligned.m64n216k16.f32.bf16.bf16 "
    "{%0,%1,%2,%3,%4,%5,%6,%7,%8,%9,%10,%11,%12,%13,%14,%15,%16,%17,%18,%19,%20,%21,%22,%23,%24,%25,%26,%27,%28,%29,%30,%31,%32,%33,%34,%35,%36,%37,%38,%39,%40,%41,%42,%43,%44,%45,%46,%47,%48,%49,%50,%51,%52,%53,%54,%55,%56,%57,%58,%59,%60,%61,%62,%63,%64,%65,%66,%67,%68,%69,%70,%71,%72,%73,%74,%75,%76,%77,%78,%79,%80,%81,%82,%83,%84,%85,%86,%87,%88,%89,%90,%91,%92,%93,%94,%95,%96,%97,%98,%99,%100,%101,%102,%103,%104,%105,%106,%107}, "
    "%108, %109, p, 1, 1, 0, 1;\n}\n"
    : "+f"(d[0]), "+f"(d[1]), "+f"(d[2]), "+f"(d[3]), "+f"(d[4]), "+f"(d[5]), "+f"(d[6]), "+f"(d[7]), "+f"(d[8]), "+f"(d[9]), "+f"(d[10]), "+f"(d[11]), "+f"(d[12]), "+f"(d[13]), "+f"(d[14]), "+f"(d[15]), "+f"(d[16]), "+f"(d[17]), "+f"(d[18]), "+f"(d[19]), "+f"(d[20]), "+f"(d[21]), "+f"(d[22]), "+f"(d[23]), "+f"(d[24]), "+f"(d[25]), "+f"(d[26]), "+f"(d[27]), "+f"(d[28]), "+f"(d[29]), "+f"(d[30]), "+f"(d[31]), "+f"(d[32]), "+f"(d[33]), "+f"(d[34]), "+f"(d[35]), "+f"(d[36]), "+f"(d[37]), "+f"(d[38]), "+f"(d[39]), "+f"(d[40]), "+f"(d[41]), "+f"(d[42]), "+f"(d[43]), "+f"(d[44]), "+f"(d[45]), "+f"(d[46]), "+f"(d[47]), "+f"(d[48]), "+f"(d[49]), "+f"(d[50]), "+f"(d[51]), "+f"(d[52]), "+f"(d[53]), "+f"(d[54]), "+f"(d[55]), "+f"(d[56]), "+f"(d[57]), "+f"(d[58]), "+f"(d[59]), "+f"(d[60]), "+f"(d[61]), "+f"(d[62]), "+f"(d[63]), "+f"(d[64]), "+f"(d[65]), "+f"(d[66]), "+f"(d[67]), "+f"(d[68]), "+f"(d[69]), "+f"(d[70]), "+f"(d[71]), "+f"(d[72]), "+f"(d[73]), "+f"(d[74]), "+f"(d[75]), "+f"(d[76]), "+f"(d[77]), "+f"(d[78]), "+f"(d[79]), "+f"(d[80]), "+f"(d[81]), "+f"(d[82]), "+f"(d[83]), "+f"(d[84]), "+f"(d[85]), "+f"(d[86]), "+f"(d[87]), "+f"(d[88]), "+f"(d[89]), "+f"(d[90]), "+f"(d[91]), "+f"(d[92]), "+f"(d[93]), "+f"(d[94]), "+f"(d[95]), "+f"(d[96]), "+f"(d[97]), "+f"(d[98]), "+f"(d[99]), "+f"(d[100]), "+f"(d[101]), "+f"(d[102]), "+f"(d[103]), "+f"(d[104]), "+f"(d[105]), "+f"(d[106]), "+f"(d[107])
    : "l"(da), "l"(db), "r"(scaleD));
}
__device__ __forceinline__ void wgmma_ss_n72(float* d, uint64_t da, uint64_t db, int scaleD) {
  asm volatile("{\n.reg .pred p;\nsetp.ne.b32 p, %38, 0;\nwgmma.mma_async.sync.aligned.m64n72k16.f32.bf16.bf16 "
    "{%0,%1,%2,%3,%4,%5,%6,%7,%8,%9,%10,%11,%12,%13,%14,%15,%16,%17,%18,%19,%20,%21,%22,%23,%24,%25,%26,%27,%28,%29,%30,%31,%32,%33,%34,%35}, "
    "%36, %37, p, 1, 1, 0, 1;\n}\n"
    : "+f"(d[0]), "+f"(d[1]), "+f"(d[2]), "+f"(d[3]), "+f"(d[4]), "+f"(d[5]), "+f"(d[6]), "+f"(d[7]), "+f"(d[8]), "+f"(d[9]), "+f"(d[10]), "+f"(d[11]), "+f"(d[12]), "+f"(d[13]), "+f"(d[14]), "+f"(d[15]), "+f"(d[16]), "+f"(d[17]), "+f"(d[18]), "+f"(d[19]), "+f"(d[20]), "+f"(d[21]), "+f"(d[22]), "+f"(d[23]), "+f"(d[24]), "+f"(d[25]), "+f"(d[26]), "+f"(d[27]), "+f"(d[28]), "+f"(d[29]), "+f"(d[30]), "+f"(d[31]), "+f"(d[32]), "+f"(d[33]), "+f"(d[34]), "+f"(d[35])
    : "l"(da), "l"(db), "r"(scaleD));
}
__device__ __forceinline__ void wgmma_rs_n144(float* d, const uint32_t* a, uint64_t db, int scaleD) {
  asm volatile("{\n.reg .pred p;\nsetp.ne.b32 p, %77, 0;\nwgmma.mma_async.sync.aligned.m64n144k16.f32.bf16.bf16 "
    "{%0,%1,%2,%3,%4,%5,%6,%7,%8,%9,%10,%11,%12,%13,%14,%15,%16,%17,%18,%19,%20,%21,%22,%23,%24,%25,%26,%27,%28,%29,%30,%31,%32,%33,%34,%35,%36,%37,%38,%39,%40,%41,%42,%43,%44,%45,%46,%47,%48,%49,%50,%51,%52,%53,%54,%55,%56,%57,%58,%59,%60,%61,%62,%63,%64,%65,%66,%67,%68,%69,%70,%71}, "
    "{%72,%73,%74,%75}, %76, p, 1, 1, 1;\n}\n"
    : "+f"(d[0]), "+f"(d[1]), "+f"(d[2]), "+f"(d[3]), "+f"(d[4]), "+f"(d[5]), "+f"(d[6]), "+f"(d[7]), "+f"(d[8]), "+f"(d[9]), "+f"(d[10]), "+f"(d[11]), "+f"(d[12]), "+f"(d[13]), "+f"(d[14]), "+f"(d[15]), "+f"(d[16]), "+f"(d[17]), "+f"(d[18]), "+f"(d[19]), "+f"(d[20]), "+f"(d[21]), "+f"(d[22]), "+f"(d[23]), "+f"(d[24]), "+f"(d[25]), "+f"(d[26]), "+f"(d[27]), "+f"(d[28]), "+f"(d[29]), "+f"(d[30]), "+f"(d[31]), "+f"(d[32]), "+f"(d[33]), "+f"(d[34]), "+f"(d[35]), "+f"(d[36]), "+f"(d[37]), "+f"(d[38]), "+f"(d[39]), "+f"(d[40]), "+f"(d[41]), "+f"(d[42]), "+f"(d[43]), "+f"(d[44]), "+f"(d[45]), "+f"(d[46]), "+f"(d[47]), "+f"(d[48]), "+f"(d[49]), "+f"(d[50]), "+f"(d[51]), "+f"(d[52]), "+f"(d[53]), "+f"(d[54]), "+f"(d[55]), "+f"(d[56]), "+f"(d[57]), "+f"(d[58]), "+f"(d[59]), "+f"(d[60]), "+f"(d[61]), "+f"(d[62]), "+f"(d[63]), "+f"(d[64]), "+f"(d[65]), "+f"(d[66]), "+f"(d[67]), "+f"(d[68]), "+f"(d[69]), "+f"(d[70]), "+f"(d[71])
    : "r"(a[0]), "r"(a[1]), "r"(a[2]), "r"(a[3]), "l"(db), "r"(scaleD));
}
__device__ __forceinline__ void wgmma_rs_n64(float* d, const uint32_t* a, uint64_t db, int scaleD) {
  asm volatile("{\n.reg .pred p;\nsetp.ne.b32 p, %37, 0;\nwgmma.mma_async.sync.aligned.m64n64k16.f32.bf16.bf16 "
    "{%0,%1,%2,%3,%4,%5,%6,%7,%8,%9,%10,%11,%12,%13,%14,%15,%16,%17,%18,%19,%20,%21,%22,%23,%24,%25,%26,%27,%28,%29,%30,%31}, "
    "{%32,%33,%34,%35}, %36, p, 1, 1, 1;\n}\n"
    : "+f"(d[0]), "+f"(d[1]), "+f"(d[2]), "+f"(d[3]), "+f"(d[4]), "+f"(d[5]), "+f"(d[6]), "+f"(d[7]), "+f"(d[8]), "+f"(d[9]), "+f"(d[10]), "+f"(d[11]), "+f"(d[12]), "+f"(d[13]), "+f"(d[14]), "+f"(d[15]), "+f"(d[16]), "+f"(d[17]), "+f"(d[18]), "+f"(d[19]), "+f"(d[20]), "+f"(d[21]), "+f"(d[22]), "+f"(d[23]), "+f"(d[24]), "+f"(d[25]), "+f"(d[26]), "+f"(d[27]), "+f"(d[28]), "+f"(d[29]), "+f"(d[30]), "+f"(d[31])
    : "r"(a[0]), "r"(a[1]), "r"(a[2]), "r"(a[3]), "l"(db), "r"(scaleD));
}

template <int V> struct Int { static constexpr int value = V; };
struct Cur {
  uint32_t s, ph;
  __device__ __forceinline__ void next() { if (++s == NST) { s = 0; ph ^= 1; } }
};

#define z1_block(rb, w, j) (P.s->Z + ((rb) * 16 + (w) * 8 + (j)) * ZB)
#define z2_block(kb, j) (P.s->Z + (256 + (kb) * 8 + (j)) * ZB)
#define o_block(rb, w) (P.s->O + ((rb) * 2 + (w)) * (2 * ZB))
__device__ __forceinline__ void combine8(float m0, float q0, float m1, float q1, float n, float eps, float& mean, float& rstd) {
  mean = qsum(m0 + m1) * 0.125f;
  float d0 = m0 - mean, d1 = m1 - mean;
  float M2 = qsum(q0 + q1 + n * (d0 * d0 + d1 * d1));
  rstd = rsq_fast(fmaf(M2, 0.125f / n, eps));
}
__device__ __forceinline__ void stat_get(const uint4* zs, uint32_t tag, float n, float eps, float& m0, float& r0, float& m1, float& r1) {
  uint4 a0, a1, b0, b1;
#pragma unroll 1
  for (int it = 0; it < (1 << 20); it++) {
    a0 = ll_ld128(zs); a1 = ll_ld128(zs + 64); b0 = ll_ld128(zs + 8); b1 = ll_ld128(zs + 72);
    if (__all_sync(~0u, a0.z == tag && a1.z == tag && b0.z == tag && b1.z == tag)) break;
  }
  combine8(__uint_as_float(a0.x), __uint_as_float(a0.y), __uint_as_float(a1.x), __uint_as_float(a1.y), n, eps, m0, r0);
  combine8(__uint_as_float(b0.x), __uint_as_float(b0.y), __uint_as_float(b1.x), __uint_as_float(b1.y), n, eps, m1, r1);
}

__device__ __forceinline__ void rows_fetch(uint32_t el, uint32_t xr, const uint8_t* src, uint32_t bar) {
  expect_tx_p(el, bar, 9216);
#pragma unroll 1
  for (int r = 0; r < 8; r++) bulk_load_p(el, xr + r * 1152, src + r * (DM * 4), 1152, bar);
}
__device__ __forceinline__ void rows_stats(uint32_t xr, uint4* dst, uint32_t tag, int lane) {
  float s[2] = {0.f, 0.f}, q[4] = {0.f, 0.f, 0.f, 0.f};
  const uint32_t a0 = xr + (lane >> 2) * 1152 + (((lane & 3) * 2) ^ (lane >> 2)) * 16;
  uint4 n0 = lds128(a0), n1 = lds128(a0 ^ 16);
#pragma unroll 1
  for (int e = 1; e <= 9; e++) {
    const uint32_t x[8] = {n0.x, n0.y, n0.z, n0.w, n1.x, n1.y, n1.z, n1.w};
    if (e < 9) { n0 = lds128(a0 + e * 128); n1 = lds128((a0 ^ 16) + e * 128); }
#pragma unroll
    for (int u = 0; u < 8; u++) {
      const float lo = blo(x[u]), hi = bhi(x[u]);
      s[u & 1] += lo + hi; q[(u & 1) * 2] = fmaf(lo, lo, q[(u & 1) * 2]); q[(u & 1) * 2 + 1] = fmaf(hi, hi, q[(u & 1) * 2 + 1]);
    }
  }
  const float sx = s[0] + s[1], sq = (q[0] + q[1]) + (q[2] + q[3]);
  const float m = qsum(sx) * (-1.f / DM), r = rsq_fast(fmaxf(fmaf(qsum(sq), 1.f / DM, -m * m), 0.f) + LN_EPS);
  if ((lane & 3) == 0) ll_st128(dst + (lane >> 2) * 2, m, r, tag);
}

__device__ __forceinline__ void poison(const Params& P, uint32_t el, uint32_t src, const CUtensorMap* m, int rb, int j, int lane) {
#pragma unroll 1
  for (int u = lane; u < 72; u += 32) sts128(src + u * 16, POISON, POISON, POISON, POISON);
  fence_async_s();
  __syncwarp();
#pragma unroll 1
  for (int u = 0; u < 16; u++) {
    __nanosleep(NAP);
    bulk_store_p(el, o_block(rb, u >> 3) + j * 9216 + (u & 7) * 1152, src, 1152);
    asm volatile("{\n.reg .pred P;\nsetp.ne.u32 P, %5, 0;\n@P cp.async.bulk.tensor.3d.global.shared::cta.tile.bulk_group [%0, {%2, %3, %4}], [%1];\n}" ::"l"(m), "r"(src), "r"((j & 6) * 72), "r"(rb * 64 + u * 4), "r"(j & 1), "r"(el) : "memory");
  }
}
__device__ __forceinline__ void mma16acc(float* c, const uint32_t* a, uint32_t b0, uint32_t b1) {
  asm volatile("mma.sync.aligned.m16n8k16.row.col.f32.bf16.bf16.f32 {%0,%1,%2,%3}, {%4,%5,%6,%7}, {%8,%9}, {%0,%1,%2,%3};"
               : "+f"(c[0]), "+f"(c[1]), "+f"(c[2]), "+f"(c[3]) : "r"(a[0]), "r"(a[1]), "r"(a[2]), "r"(a[3]), "r"(b0), "r"(b1));
}
template <int KS, int NG, int AK, int AH, int BK, int BG, class F> __device__ __forceinline__ void redo(float* acc, const uint8_t* pa, const uint8_t* pb, F f) {
#pragma unroll 1
  for (int k = 0; k < 36; k += KS) {
    uint32_t a[4 * KS], b[2 * KS][NG];
#pragma unroll 1
    for (int it = 0; it < (1 << 20); it++) {
      bool ok = true;
#pragma unroll
      for (int e = 0; e < 4 * KS; e++) a[e] = ldgpu32(pa + (e >> 1) * AK + (e & 1) * AH);
#pragma unroll
      for (int e = 0; e < 2 * KS * NG; e++) b[e / NG][e % NG] = ldca32(pb + (e / NG) * BK + (e % NG) * BG);
#pragma unroll
      for (int e = 0; e < 4 * KS; e++) ok = ok && a[e] != POISON;
      if (__all_sync(~0u, ok)) break;
    }
#pragma unroll
    for (int e = 0; e < KS; e++) f(a + 4 * e, k + e);
#pragma unroll
    for (int e = 0; e < KS * NG; e++) mma16acc(acc + 4 * (e % NG), a + 4 * (e / NG), movm(b[2 * (e / NG)][e % NG]), movm(b[2 * (e / NG) + 1][e % NG]));
    pa += 2 * KS * AK; pb += 2 * KS * BK;
  }
}
__device__ __forceinline__ bool any_nan(float a, float b) {
  return __any_sync(~0u, a != a || b != b);
}

__global__ void __cluster_dims__(2, 1, 1) __launch_bounds__(384, 1) mega_kernel(const __grid_constant__ Params P) {
  extern __shared__ __align__(1024) uint8_t smem_raw[];
  uint32_t ckk[8];
  (void)ckk;
  CKK(0);
  const uint32_t sb = smem_u32(smem_raw);
  const uint32_t bars = sb + SM_BAR;
  int tid = threadIdx.x, lane = tid & 31;
  const int wid = __shfl_sync(~0u, tid >> 5, 0);
  const int cl = blockIdx.x >> 1, tp = cl - 36, t7 = (tp * 37) >> 8;
  const int bid = (cl < 4 ? cl * 8 + 32 : tp < 0 ? cl - 4 : cl < 64 ? tp + t7 + 33 : cl) * 2 + (blockIdx.x & 1);
  if (bid >= NCTA) return;
  const int rb = bid & 15, j = bid >> 4;
  { const bool tr = (tid & 127) == 0 && tid < 256; const int w = tid >> 7; (void)tr; (void)w; TRC(tr, w, 0); }
  CKK(1);
  uint4 wv[5];
  const uint8_t* wsrc;
  {
    const int n8 = min(tid >> 3, 26), part = n8 / 9;
    const uint8_t* src = (const uint8_t*)P.wqkv + (8 * rb + (tid & 7)) * (3 * DM * 2) + (part * (DM - 72) + 72 * j + 8 * n8) * 2;
#pragma unroll
    for (int u = 0; u < SPL; u++) wv[u] = ldnc128_if(tid < 216, src + u * (128 * 3 * DM * 2));
    wsrc = src;
  }
  CKK(2);
  if (tid == 352) {
#pragma unroll
    for (int e = 0; e < 16; e++) mbar_init(bars + B_FULL + e * 8, (e >> 2) == 1 ? 16 : 1);
    mbar_init(bars + B_RES + 8, 8); mbar_init(bars + B_WT, 1); mbar_init(bars + B_WT + 8, 1); mbar_init(bars + B_IMG, 9);
    asm volatile("fence.mbarrier_init.release.cluster;" ::: "memory");
  }
  __syncthreads();

  if (wid >= 8) {
    reg_dealloc<40>();
    lane = __shfl_sync(~0u, lane, lane);
    const uint32_t el = elect_one();
    const uint64_t pol = policy_evict_first();
    uint32_t* const fj = P.s->flags + FJ + j * 32;
    if (wid == 8) {
      if (lane == 0) {
        mbar_init(bars + B_RES, 1); mbar_init(bars + B_WOI, 1); mbar_init(bars + B_ZB, 1); mbar_init(bars + B_GATE3, 3); mbar_init(bars + B_Z1, 1); mbar_init(bars + B_LAG, 4);
#pragma unroll
        for (int e = B_RT; e < B_XS + 16; e += 8) mbar_init(bars + e, e >= B_AD && e < B_EVT ? 2 : (e >= B_EVT && e < B_RT1) || (e >= B_EA3 && e < B_XS) ? 4 : 1);
        asm volatile("fence.mbarrier_init.release.cluster;" ::: "memory");
        mbar_arrive(bars + B_IMG);
      }
      __syncwarp();
#pragma unroll 1
      for (int i = 0; i < 12; i++) if (el) prefetch_map(&P.act[0] + (i < 7 ? i : i - 12));
      const uint32_t epoch = ldcg32(fj + FJ_EP + rb);
      const uint32_t rk = bid & 1;
      TRC(el, 2, 34);
      uint32_t dst = sb + ST_B + rk * 18432, full = bars + B_FULL, ph = 1;
      auto slot = [&](uint32_t bytes) {
        mbar_wait(full, ph);
        expect_tx_p(el, full, bytes);
        mbar_wait(full + (B_EMPTY - B_FULL), ph);
      };
      auto next = [&]() {
        const bool wrap = full == bars + B_FULL + 24;
        full += wrap ? -24 : 8; dst += wrap ? -3 * ST_BYTES : ST_BYTES; ph ^= wrap;
      };
#pragma unroll 1
      for (int L = 0; L < 2; L++) {
        const uint8_t* src = P.s->WQ + j * WQ_SL + rk * 13824;
        dst -= rk * 4608;
#pragma unroll 1
        for (int i = 0; i < 9; i++) {
          if (L == 0 && (i == 0 || i == 2 * SPL)) {
            flag_wait(fj + (i ? FJ_WQ : FJ_WQ0), (epoch + 1) * 16);
            fence_async_g();
            TRC(el, 2, i ? 47 : 45);
          }
          slot(27648);
          bulk_mc_h(el, dst, src, 13824, full, true, pol);
          src += 27648;
          next();
        }
        dst += rk * 4608;
        if (L == 0) {
#pragma unroll 1
          for (int u = 0; u < 2; u++) flag_wait(P.s->flags + FJ + (j ^ u) * 32 + FJ_WO, (epoch + 1) * 16);
          fence_async_g();
          TRC(el, 2, 46);
        }
        src = P.s->WO + ((j & 6) + rk) * WO_SL;
#pragma unroll 1
        for (int i = 0; i < 4; i++) {
          slot(ZB);
          bulk_mc_h(el, dst, src, 18432, full, true, pol);
          src += 18432;
          next();
        }
        slot(18432);
        bulk_mc_h(el, dst, src, 9216, full, true, pol);
        next();
        int col = (((9 * j + 1) >> 1) + 36) * 64;
        const CUtensorMap* map = &P.win64;
#pragma unroll 1
        for (int p = 0; p < 9; p++) {
          if (p == 1) mbar_wait(bars + B_FA3 + GA3 * 8, L);
          mbar_wait(full + (B_EMPTY - B_FULL), ph);
          tma4d_mc(el, dst, map, col, rk * 18, full + 8, pol);
          mbar_arrive_if(el, full);
          if (p + L == 0 && el) asm volatile("cp.async.bulk.prefetch.tensor.4d.L2.global [%0, {%1, 0, 0, %2}];\ncp.async.bulk.prefetch.tensor.4d.L2.global [%0, {%1, 0, 0, %3}];" ::"l"(map), "r"(col + 64), "r"(rk * 18), "r"(rk * 18 + 36) : "memory");
          next();
          if (p == 1) mbar_wait(bars + B_FA3 + GB3 * 8, L);
          slot(2 * ZB);
          tma4d_mc(el, dst, map, col, rk * 18 + 36, full, pol);
          next();
          col = p == 3 ? (9 * j + ((j & 1) ? 0 : 8)) * 32 : p == 4 ? ((9 * j + 1) >> 1) * 64 : col + 64;
          map = p == 3 ? &P.win : &P.win64;
        }
        TRC(el, 2, L * 16 + 6);
        flag_wait(fj + FJ_ZN + L, (epoch + 1) * 16);
        fence_async_g();
        TRC(el, 2, L * 16 + 7);
        src = z2_block(0, j) + rk * 18432;
#pragma unroll 1
        for (int i = 0; i < 32; i++) {
          if (i >= 4) mbar_wait(full + (B_AD - B_FULL), ((i >> 2) & 1) ^ 1);
          slot(ST_BYTES);
          bulk_mc_h(el, dst, src, 18432, full, true, pol);
          tma3d_h(el, dst - ST_B - rk * 18432, &P.wsp, i * 64, rb * 64, 0, full, true, pol);
          src += 8 * ZB;
          next();
        }
        mbar_wait(bars + B_Z1, L);
        fence_async_g();
        expect_tx_p(el, bars + B_ZB, 26624);
        mbar_wait(full + (B_AD - B_FULL), 1);
        slot(26624);
        bulk_load_h(el, dst - ST_B - rk * 18432, z1_block(rb, 0, j), 26624, bars + B_ZB, true, pol);
        bulk_load_h(el, dst - ST_B - rk * 18432 + 26624, z1_block(rb, 1, j), 26624, full, true, pol);
        next();
        col = j * 64;
#pragma unroll 1
        for (int i = 0; i < 9; i++) {
          if (i < 3) mbar_wait(full + (B_AD - B_FULL), 1);
          slot(ZB);
          tma2d_mc_h(el, dst, &P.wout, col, 288 * j + rk * 144, full, true, pol);
          col = col == 512 ? 0 : col + 64;
          next();
        }
      }
    } else if (wid < 11) {
      int w = wid - 9;
      TRC(el && w == 0, 2, 35);
      uint32_t* const fr = P.s->flags + (rb * 2 + w) * 32;
      const uint32_t epoch = ldcg32(fr + FR_EP + j);
      const uint32_t ev = bars + B_EVT + w * EV_N * 8, t8 = (epoch + 1) * 8;
      Cur c{0, 1};
#pragma unroll 1
      for (int L = 0; L < 2; L++) {
        {
          uint32_t tag = t8;
          asm volatile("" : "+r"(tag));
          tag = (tag >> 2) - 1 + L;
          uint4* const xs = P.s->XST + (rb * 2 + w) * 128;
          if (L) {
            mbar_wait(ev + EV_PT * 8, 0);
            TRC(el, 3, w * 32 + 16);
            flag_release_p(el, fr + FR_X2);
            TRC(el, 3, w * 32 + 17);
          }
#pragma unroll 1
          for (int i = 0; i < 9; i++) {
            const uint32_t full = bars + B_FULLA + w * 32 + c.s * 8, dst = sb + c.s * ST_BYTES + w * 8192;
            if (L == 0 && i == 4) {
              mbar_wait(bars + B_WT + w * 8, 0);
              TRC(el && w == 0, 2, 37);
              rows_stats(sb + SM_STG + w * 9216, xs + 16 * j, tag, lane);
              TRC(el && w == 0, 2, 38);
            }
            const uint32_t src = sb + (L ? 2 * ST_BYTES + SM_WOI : SM_STG + w * 9216);
            if (i == 4) {
#pragma unroll
              for (int u = 0; u < 6; u++) sts128(src + u * 512 + lane * 16, POISON, POISON, POISON, POISON);
              fence_async_s();
              __syncwarp();
            }
            mbar_wait(bars + B_EMPTY + c.s * 8, c.ph);
            if (i < L) { flag_wait(fr + FR_X2, t8); fence_async_g(); }
            tma3d_h(el, dst, &P.act[L], i * 64, rb * 64, w, full, false, pol);
            expect_tx_p(el, full, 8192);
            TRC(el && i < L, 3, w * 32 + 18);
            TRC(el && i + L + w == 0, 2, 36);
            c.next();
            if (i >= 4 && i < (L ? 5 : 8)) {
              int b = (rb * 2 + w) * 8 + j;
              asm volatile("" : "+r"(b));
              bulk_store_p(el, i == 4 ? (uint8_t*)P.s->HALO + b * 3072 : P.s->O + (b * 3 + i - 5) * 3072, src, 3072);
              if (i < 6) bulk_store_p(el, (i == 4 ? P.s->ST1 : P.s->ZST) + b * 64, src, 1024);
              if (i == 6) bulk_store_p(el, P.s->RT + b * 8, src, 64);
            }
            if (L == 0 && i == 3) rows_fetch(el, sb + SM_STG + w * 9216, P.xs[0] + (128 * rb + 16 * j + w) * (DM * 2), bars + B_WT + w * 8);
          }
          if (el) asm volatile("cp.async.bulk.commit_group;\ncp.async.bulk.wait_group 0;" ::: "memory");
          __syncwarp();
          if (L == 0) fence_gpu();
          const uint32_t tab = sb + L * (2 * ST_BYTES) + SM_XST + w * 512 + lane * 8;
          TRC(el, 3, w * 32 + L * 16 + 13);
#pragma unroll 1
          for (int it = 0; it < (1 << 22); it++) {
            const uint4 a = ll_ld128(xs + 2 * lane), b = ll_ld128(xs + 64 + 2 * lane);
            if (__all_sync(~0u, a.z == tag && b.z == tag)) { sts64(tab, a.x, a.y); sts64(tab + 256, b.x, b.y); break; }
          }
          __syncwarp();
          mbar_arrive_if(el, bars + B_XS + w * 8);
          TRC(el, 3, w * 32 + L * 16 + 14);
          if (w == 1) {
            mbar_wait(bars + B_XS, L);
            expect_tx_p(el, bars + B_RES, 18432);
            tma3d_h(el, sb + SM_STG, &P.res[L], (j & 6) * 72, rb * 64, j & 1, bars + B_RES, !L, pol);
          }
          if (L) flag_wait(fj + FJ_P4, t8 * 4);
        }
        int hp = rb * 2 + (j & 1);
        asm volatile("" : "+r"(w), "+r"(hp));
        uint32_t* const fo = P.s->flags + hp * 32 + L;
        {
          const uint8_t* src = o_block(0, hp) + w * 8192;
#pragma unroll 1
          for (int i = 0; i < 5; i++) {
            const uint32_t full = bars + B_FULLA + w * 32 + c.s * 8, dst = sb + c.s * ST_BYTES + w * 8192;
            const bool none = 2 * i + w > 8;
            mbar_wait(bars + B_EMPTY + c.s * 8, c.ph);
            expect_tx_p(el, full, none ? 0 : 8192);
            if (i == 0) {
              mbar_wait(ev + EV_O * 8, L);
              TRC(el, 3, w * 32 + L * 16 + 3);
              flag_add_p(el, fr + FR_O + L);
              TRC(el, 3, w * 32 + L * 16 + 4);
              flag_wait(fo + FR_O, t8);
              fence_async_g();
            }
            if (!none) bulk_load_h(el, dst, src + i * 16384, 8192, full, true, pol);
            TRC(el && i == 0, 3, w * 32 + L * 16 + 5);
            c.next();
          }
        }
        {
          expect_tx_p(lane < 9, bars + B_FA3 + (9 * w + lane) * 8, 8192);
          mbar_wait(ev + EV_X1 * 8, L);
          TRC(el, 3, w * 32 + L * 16 + 6);
          if (L) flag_add_p(el, fo + FR_X1); else flag_release_p(el, fo + FR_X1);
          mbar_arrive_if(el, bars + B_GATE3);
          TRC(el, 3, w * 32 + L * 16 + 7);
          mbar_arrive_if(lane < 2, bars + B_FULLA + w * 32 + ((c.s + lane) & 3) * 8);
#pragma unroll 1
          for (int kb = 0; kb < 9; kb++) {
            const int n = 9 * w + kb;
            const uint32_t dst = sb + ((n >> 1) & 3) * ST_BYTES + (n & 1) * 8192;
            if (kb == 0) { flag_wait(fr + FR_X1 + L, t8); fence_async_g(); }
            if (n >= 8) mbar_wait(bars + B_EA3 + (n - 8) * 8, L);
            tma3d_h(el, dst, &P.act[L + 1], kb * 64, rb * 64, w, bars + B_FA3 + n * 8, false, pol);
            TRC(el && kb == 0, 3, w * 32 + L * 16 + 8);
          }
          c.ph ^= ((c.s + 18) >> 2) & 1; c.s = (c.s + 18) & 3;
        }
        asm volatile("" : "+r"(lane), "+r"(w));
        expect_tx_p(el, bars + B_WT + w * 8, 2048);
#pragma unroll 1
        for (int r = 0; r < 8; r++)
          bulk_load_p(el, sb + SM_WT + w * 2176 + r * 272, (const uint8_t*)P.w_sp + (size_t)(128 * rb + 16 * j + 2 * r + w) * (SEQ * 2) + 30 * 128, 256, bars + B_WT + w * 8);
        float cv = (lane & 3) ? 0.f : -blo(ldnc16(P.b_sp + 128 * rb + 16 * j + 2 * (lane >> 2) + w));
        mbar_wait(bars + B_RT, L);
        mbar_wait(bars + B_WT + w * 8, L ^ 1);
        mbar_wait(ev + EV_Z1 * 8, L);
        const uint32_t ro = (w * 64 + 8 * j + (lane >> 2)) * 128, x0 = ((lane & 3) * 2) ^ (lane >> 2);
#pragma unroll 1
        for (int i = 0; i < 32; i++) {
          const bool tail = (i >> 1) == 4;
          const int kb = tail ? i + 22 : i < 8 ? i : i - 2;
          if (i == 8) mbar_wait(bars + B_RT1, L);
          if (!tail) mbar_wait(bars + B_FULL + c.s * 8, c.ph ^ 1);
#pragma unroll
          for (int e = 0; e < 2; e++) {
            const uint4 a = lds128(!tail ? sb + c.s * ST_BYTES + ro + ((x0 ^ e) << 4) : sb + SM_WT + w * 2176 + (lane >> 2) * 272 + (i - 8) * 128 + (lane & 3) * 32 + e * 16);
            const uint4 m = lds128(sb + SM_RT + 4096 + kb * 128 + (lane & 3) * 32 + e * 16);
            cv = fmaf(blo(a.x), blo(m.x), fmaf(bhi(a.x), bhi(m.x), fmaf(blo(a.y), blo(m.y), fmaf(bhi(a.y), bhi(m.y), cv))));
            cv = fmaf(blo(a.z), blo(m.z), fmaf(bhi(a.z), bhi(m.z), fmaf(blo(a.w), blo(m.w), fmaf(bhi(a.w), bhi(m.w), cv))));
          }
          if (!tail) {
            mbar_arrive_if(el, bars + B_AD + c.s * 8 + (__float_as_uint(cv) & P.zero));
            c.next();
          }
        }
        TRC(el, 3, w * 32 + L * 16 + 11);
        uint32_t tag = t8;
        asm volatile("" : "+r"(tag));
        tag = (tag >> 2) - 1 + L;
        cv = qsum(cv);
        uint2* const cs = (uint2*)(P.s->XST + (rb * 2 + w) * 128 + 1);
        if ((lane & 3) == 0) ll_st64(cs + 32 * j + (lane >> 2) * 4, __float_as_uint(cv), tag);
#pragma unroll 1
        for (int it = 0; it < (1 << 22); it++) {
          const uint2 a = ll_ld64(cs + 4 * lane), b = ll_ld64(cs + 128 + 4 * lane);
          if (__all_sync(~0u, a.y == tag && b.y == tag)) { sts32(sb + SM_CV + w * 256 + lane * 4, a.x); sts32(sb + SM_CV + w * 256 + 128 + lane * 4, b.x); break; }
        }
        __syncwarp();
        if (el) mbar_arrive(bars + B_CV + w * 8);
        TRC(el, 3, w * 32 + L * 16 + 12);
#pragma unroll 1
        for (int kb = 30; kb < 32; kb++) {
          mbar_wait(bars + B_FULL + c.s * 8, c.ph ^ 1);
          if (el) mbar_arrive(bars + B_AD + c.s * 8);
          c.next();
        }
        c.ph ^= ((c.s + 10) >> 2) & 1; c.s = (c.s + 10) & 3;
        if (L == 0) {
          mbar_wait(ev + EV_P4 * 8, 0);
          flag_add_p(el, fj + FJ_P4);
          flag_add_p(el, fr + FR_EP + j);
        }
      }
    } else {
      const uint32_t epoch = ldcg32(fj + FJ_EP + rb);
      TRC(el, 2, 33);
      if (SPL) {
        mbar_wait(bars + B_RES + 8, 0);
        TRC(el, 2, 41);
        flag_release_p(el, fj + FJ_WQ0);
        TRC(el, 2, 42);
      }
      mbar_wait(bars + B_IMG, 0);
      TRC(el, 2, 39);
      flag_release_p(el, fj + FJ_WQ);
      TRC(el, 2, 40);
#pragma unroll 1
      for (int L = 0; L < 2; L++) {
        auto wo_fetch = [&]() {
          expect_tx_p(el, bars + B_WOI, 5760);
          asm volatile("{\n.reg .pred P;\nsetp.ne.u32 P, %5, 0;\n@P cp.async.bulk.tensor.4d.shared::cluster.global.mbarrier::complete_tx::bytes [%0], [%1, {0, 0, %3, %4}], [%2];\n}" ::"r"(sb + SM_WOI), "l"(&P.wo8), "r"(bars + B_WOI), "r"(9 * j), "r"((9 * rb) >> 1), "r"(el) : "memory");
        };
        float* const csf = P.s->CSP + (NCTA + bid) * 216;
        if (L == 0) {
          flag_wait(fj + FJ_WQ, (epoch + 1) * 16);
          fence_async_g();
          expect_tx_p(el, bars + B_XRW, 13824);
          bulk_load_p(el, sb + ST_BYTES + SM_WOI, P.s->CSP + j * 16 * 216, 6912, bars + B_XRW);
          bulk_load_p(el, sb + 2 * ST_BYTES + SM_WOI, P.s->CSP + (j * 16 + 8) * 216, 6912, bars + B_XRW);
          wo_fetch();
          mbar_wait(bars + B_XRW, 0);
#pragma unroll 1
          for (int f = lane; f < 54; f += 32) {
            float s[4] = {0.f, 0.f, 0.f, 0.f};
#pragma unroll 4
            for (int r = 0; r < 16; r++) {
              const uint4 v = lds128(sb + ST_BYTES + SM_WOI + (r >> 3) * ST_BYTES + (r & 7) * 864 + f * 16);
              s[0] += __uint_as_float(v.x); s[1] += __uint_as_float(v.y); s[2] += __uint_as_float(v.z); s[3] += __uint_as_float(v.w);
            }
            sts128(sb + SM_CSQ + f * 16, __float_as_uint(s[0]), __float_as_uint(s[1]), __float_as_uint(s[2]), __float_as_uint(s[3]));
            stg128(csf + f * 4, __float_as_uint(s[0]), __float_as_uint(s[1]), __float_as_uint(s[2]), __float_as_uint(s[3]));
          }
          __syncwarp();
          mbar_arrive_if(el, bars + B_CSQ);
        } else {
#pragma unroll 1
          for (int u = 0; u < 4; u++) {
            const int w = u & 1;
            if (u < 2) {
              flag_wait(P.s->flags + (rb * 2 + w) * 32 + FR_X2, (epoch + 1) * 8);
              fence_async_g();
              TRC(el, 2, 48 + u);
              rows_fetch(el, sb + SM_STG + w * 9216, P.xs[1] + (128 * rb + 16 * j + w) * (DM * 2), bars + B_XRW + w * 8);
            } else {
              if (u == 2) {
                expect_tx_p(el, bars + B_CSQ, 864);
                bulk_load_p(el, sb + 2 * ST_BYTES + SM_CSQ, csf, 864, bars + B_CSQ);
              }
              mbar_wait(bars + B_XRW + w * 8, w ^ 1);
              TRC(el, 2, 48 + u);
              rows_stats(sb + SM_STG + w * 9216, P.s->XST + (rb * 2 + w) * 128 + 16 * j, epoch * 2 + 2, lane);
              TRC(el, 2, 50 + u);
            }
          }
        }
        if (L == 0) {
          TRC(el, 2, 43);
          mbar_wait(bars + B_WOI, 0);
          bulk_store_p(el, P.s->WO + j * WO_SL + ((9 * rb) >> 1) * 1152, sb + SM_WOI, 5760);
          publish_p(el, fj + FJ_WO);
          TRC(el, 2, 44);
          const uint8_t* sp = lane < 16 ? (const uint8_t*)P.w_in + (30 * lane + 50) * (FH * 4) + FH * 2 + lane * 256 : (const uint8_t*)P.w_sp + (60 * lane) * (SEQ * 2) + lane * 64;
          float sq = 0.f;
#pragma unroll 1
          for (int u = 0; u < 4; u++) {
            const uint4 y = ldnc128(sp + u * 16);
            const uint32_t x[4] = {y.x, y.y, y.z, y.w};
#pragma unroll
            for (int e = 0; e < 4; e++) sq = fmaf(blo(x[e]), blo(x[e]), fmaf(bhi(x[e]), bhi(x[e]), sq));
          }
#pragma unroll 1
          for (int o = 8; o; o >>= 1) sq += __shfl_xor_sync(~0u, sq, o);
          sq *= lane < 16 ? 2.f * GA * GA * DM / 512.f : C0S * C0S * SEQ / 512.f;
          asm("sqrt.approx.f32 %0, %0;" : "+f"(sq));
          const float o0 = __shfl_sync(~0u, sq, 0), o1 = __shfl_sync(~0u, sq, 16);
          const float p2 = __uint_as_float(min(__float_as_uint(o0) & 0x7f800000u, 0x7e000000u)) * OFK, off = -p2 - fminf(OFA, 0.5f * p2);
          if (el) sts64(sb + SM_OFF, pack2(off, off), min(__float_as_uint(o1) & 0x7f800000u, 0x7e000000u) | 0x00400000u);
        }
        if (el) mbar_arrive(bars + B_GATE3);
        const uint32_t tag = epoch * 2 + L + 1;
        asm volatile("" : "+r"(lane));
        mbar_wait(bars + B_EVT + EV_ZN * 8, L);
        mbar_wait(bars + B_EVT + (EV_N + EV_ZN) * 8, L);
        flag_release_p(el, fj + FJ_ZN + L);
        TRC(el, 2, L * 16 + 8);
        {
          uint4 v[4];
#pragma unroll 1
          for (int it = 0; it < (1 << 22); it++) {
            bool ok = true;
#pragma unroll
            for (int u = 0; u < 4; u++) { v[u] = ll_ld128(P.s->ZST + (rb * 2 + ((lane >> 1) & 1)) * 512 + ((lane & 1) * 4 + u) * 64 + 8 * j + (lane >> 2)); ok = ok && v[u].z == tag; }
            if (__all_sync(~0u, ok)) break;
          }
          float mean = __uint_as_float(v[0].x) + __uint_as_float(v[1].x) + __uint_as_float(v[2].x) + __uint_as_float(v[3].x), M2 = 0.f;
          mean = (mean + __shfl_xor_sync(~0u, mean, 1)) * 0.125f;
#pragma unroll
          for (int u = 0; u < 4; u++) { const float d = __uint_as_float(v[u].x) - mean; M2 += fmaf(288.f * d, d, __uint_as_float(v[u].y)); }
          M2 += __shfl_xor_sync(~0u, M2, 1);
          const float rs = blo(pack2(rsq_fast(fmaf(M2, 1.f / FH, 4.f * GA * GA * LN_EPS)), 0.f));
          if (!(lane & 1)) ll_st64(P.s->RT + 128 * rb + 16 * j + (lane >> 1), pack2(rs, rs * mean), tag);
        }
        TRC(el, 2, L * 16 + 10);
#pragma unroll 1
        for (int b = 0; b < 8; b++) {
          uint4 v[4];
#pragma unroll 1
          for (int it = 0; it < (1 << 22); it++) {
            bool ok = true;
#pragma unroll
            for (int u = 0; u < 4; u++) { v[u] = ll_ld128((const uint4*)P.s->RT + b * 128 + u * 32 + lane); ok = ok && v[u].y == tag && v[u].w == tag; }
            if (__all_sync(~0u, ok)) break;
          }
#pragma unroll
          for (int u = 0; u < 4; u++) {
            const uint32_t rt = sb + SM_RT + b * 512 + u * 128, ro = (lane >> 3) * 32 + (lane & 3) * 8 + ((lane >> 2) & 1) * 2;
            sts32(rt + 4096 + lane * 4, __byte_perm(v[u].x, v[u].z, 0x7632));
            asm volatile("st.shared.u16 [%0], %1;\nst.shared.u16 [%0 + 4], %2;" ::"r"(rt + ro), "h"((uint16_t)v[u].x), "h"((uint16_t)v[u].z) : "memory");
          }
          __syncwarp();
          if (el && (b == 1 || b == 7)) mbar_arrive(bars + (b == 1 ? B_RT : B_RT1));
          TRC(el && b < 2, 2, L * 16 + 11 + b);
        }
        TRC(el, 2, L * 16 + 9);
        mbar_wait(bars + B_EVT + EV_Z1 * 8, L);
        mbar_wait(bars + B_EVT + (EV_N + EV_Z1) * 8, L);
        fence_gpu();
        if (el) mbar_arrive(bars + B_Z1);
        if (L == 0) {
          flag_add_p(el, fj + FJ_EP + rb);
          __nanosleep(NAP0);
          poison(P, el, sb + SM_STG + 17152, &P.psn, rb, j, lane);
          if (el) asm volatile("cp.async.bulk.commit_group;\ncp.async.bulk.wait_group 0;" ::: "memory");
          __syncwarp();
          fence_gpu();
        }
      }
    }
  } else {
    CKK(3);
    uint8_t* const wdst = P.s->WQ + j * WQ_SL + rb * 3456 + tid * 16;
#pragma unroll
    for (int u = 0; u < SPL; u++) stg128_if(tid < 216, wdst + u * (16 * 3456), wv[u].x, wv[u].y, wv[u].z, wv[u].w);
    __syncwarp();
    if (lane == 0) mbar_arrive(bars + B_RES + 8);
    CKK(4);
    auto repack2 = [&]() {
#pragma unroll
      for (int u = SPL; u < 5; u++) stg128_if((u < 4 || rb < 8) && tid < 216, wdst + u * (16 * 3456), wv[u].x, wv[u].y, wv[u].z, wv[u].w);
      float s[8];
#pragma unroll
      for (int e = 0; e < 8; e++) s[e] = 0.f;
#pragma unroll
      for (int u = 0; u < 5; u++) {
        uint32_t x[4] = {wv[u].x, wv[u].y, wv[u].z, wv[u].w};
        asm volatile("" : "+r"(x[0]), "+r"(x[1]), "+r"(x[2]), "+r"(x[3]));
#pragma unroll
        for (int e = 0; e < 4; e++) { s[2 * e] += blo(x[e]); s[2 * e + 1] += bhi(x[e]); }
      }
#pragma unroll
      for (int m = 4; m; m >>= 1) {
#pragma unroll
        for (int e = 0; e < m; e++) s[e] = ((tid & m) ? s[e + m] : s[e]) + __shfl_xor_sync(~0u, (tid & m) ? s[e] : s[e + m], m);
      }
      stg32_if(tid < 216, P.s->CSP + bid * 216 + tid, __float_as_uint(s[0]));
      __syncwarp();
      if (lane == 0) mbar_arrive(bars + B_IMG);
    };
    reg_alloc<232>();
    lane = __shfl_sync(~0u, lane, lane);
    tid = wid * 32 + lane;
    CKK(5);
#pragma unroll
    for (int v = SPL; v < 5; v++) wv[v] = ldnc128_if(tid < 216 && (v < 4 || rb < 8), wsrc + v * (128 * 3 * DM * 2));
    repack2();
    CKK(6);
    const int w = wid >> 2, q = wid & 3;
    int g = lane >> 2, t = lane & 3;
    const uint32_t ev = bars + B_EVT + w * EV_N * 8;
    const bool tr = (tid & 127) == 0;
    (void)tr;
    Cur c{0, 0};
    const uint32_t ebar = mapa(bars + B_EMPTY, (bid & 1) ^ (lane & 1));
    auto release = [&](uint32_t s, uint32_t dep = 0) { mbar_arrive_cluster_if(lane < 2, ebar + s * 8 + dep); };
    auto release_if = [&](bool on, uint32_t s) { mbar_arrive_cluster_if(lane < 2 && on, ebar + s * 8); };
    uint32_t ia = 0;
    auto wait_ab = [&]() { mbar_wait_c(bars + B_FULL + c.s * 8, c.ph); mbar_wait_c(bars + B_FULLA + w * 32 + c.s * 8, (ia >> 2) & 1); ia++; };

    auto yield_done = [&]() { if (w == 0 && lane == 0) mbar_arrive(bars + B_LAG); };
    auto signal = [&](int e) { __syncwarp(); mbar_arrive_if(lane == 0, ev + e * 8); };

    const uint32_t epoch = ldcg32(P.s->flags + (rb * 2 + w) * 32 + FR_EP + j);
    TRC(tr, w, 1);
    CKK(7);
    if (PAD && P.zero) {
#pragma unroll
      for (int i = 0; i < PAD; i++) asm volatile("st.shared.u32 [%0], %1;" ::"r"(sb + i * 20), "r"(tid) : "memory");
    }
    CKK_OUT;

#pragma unroll 1
    for (int L = 0; L < 2; L++) {
      const int tb = 2 + L * 24;
      asm volatile("" : "+r"(lane), "+r"(g), "+r"(t));
      (void)tb;
      ia = 0;
      const uint32_t tag = epoch * 2 + L + 1;
      uint32_t aoff = (w * 64 + q * 16 + (lane & 15)) * 128 + (((lane >> 4) ^ (lane & 7)) << 4);
      {
        uint32_t Pk[27][2];
        float sc0, sc1;
        const uint32_t att = sb + w * 8192 + q * 2048 + lane * 4;
        uint4* hp = P.s->HALO + ((((rb - (q == 0)) * 2 + w) * 8 + j) * 6) * 32 + lane;
        uint8_t* od = o_block(rb, w) + (9 * j) * 1024 + (2 * q) * 128 + lane * 4;
        ACLK_INIT;
        {
          float acc[108];
#pragma unroll
          for (int i = 0; i < 108; i++) acc[i] = 0.f;
          uint32_t prev = 0;
#pragma unroll 1
          for (int kb = 0; kb < 9; kb++) {
            wait_ab();
            if (w == 1 && kb == 9 - LAG1) mbar_wait_c(bars + B_LAG, L);
            TRC(tr && kb == 0, w, tb + 0);
            MCLK(kb == 0, 0);
            PCLK(kb * 4);
            const uint32_t st = sb + c.s * ST_BYTES;
            uint64_t da = dsc2(dlo(st + w * 8192, 16), 0, 0x40000040u + P.zero), db = dsc2(dlo(st + ST_B, 3456), 0, 8 ^ P.zero);
            wgmma_fence();
#pragma unroll
            for (int kk = 0; kk < 4; kk++) {
              wgmma_ss_n216(acc, da, db, 1);
              dadd(da, 2); dadd(db, 432);
              if (kk == 0) { wgmma_commit(); wgmma_wait<1>(); release_if(kb > 0, prev); }
            }
            wgmma_commit();
            if (kb == 8) yield_done();
            PCLK(kb * 4 + 1);
            PCLK(kb * 4 + 2);
            PCLK(kb * 4 + 3);
            prev = c.s; c.next();
          }
          const uint32_t cs = sb + prev * ST_BYTES + SM_CSQ + t * 8;
          mbar_wait_c(bars + B_CSQ, L);
          mbar_wait_c(bars + B_XS + w * 8, L);
          const float2 n0 = lds64f(sb + prev * ST_BYTES + SM_XST + w * 512 + (16 * q + g) * 8), n1 = lds64f(sb + prev * ST_BYTES + SM_XST + w * 512 + (16 * q + g + 8) * 8);
          const float m0 = n0.x, r0 = n0.y, m1 = n1.x, r1 = n1.y;
          float2 cv[27];
#pragma unroll
          for (int G = 0; G < 27; G++) cv[G] = lds64f(cs + G * 32);
          PCLK(36);
          wgmma_wait<0>();
          PCLK(37);
          {
            uint32_t dep = P.zero & __float_as_uint(m0) & __float_as_uint(m1);
#pragma unroll
            for (int G = 0; G < 27; G++) dep &= __float_as_uint(cv[G].x);
            release(prev, dep);
          }
          TRC(tr, w, tb + 1);
          MCLK(1, 1);
          ACLK(0);
#pragma unroll
          for (int G = 9; G < 27; G++) Pk[G][1] = pack2(fmaf(m1, cv[G].x, acc[4 * G + 2]) * r1, fmaf(m1, cv[G].y, acc[4 * G + 3]) * r1);
          if (q < 3) {
#pragma unroll
            for (int i = 0; i < 18; i++) sts32(att + (i >> 4) * ST_BYTES + (i & 15) * 128, Pk[9 + i][1]);
          } else if (rb < 15) {
#pragma unroll
            for (int i = 0; i < 6; i++) ll_st128(hp + i * 32, __uint_as_float(Pk[9 + 3 * i][1]), __uint_as_float(Pk[10 + 3 * i][1]), tag, __uint_as_float(Pk[11 + 3 * i][1]));
          }
#pragma unroll
          for (int G = 0; G < 27; G++) {
            if (G < 9) {
              Pk[G][0] = pack2(fmaf(m0, cv[G].x, acc[4 * G]), fmaf(m0, cv[G].y, acc[4 * G + 1]));
              Pk[G][1] = pack2(fmaf(m1, cv[G].x, acc[4 * G + 2]), fmaf(m1, cv[G].y, acc[4 * G + 3]));
            } else {
              Pk[G][0] = pack2(fmaf(m0, cv[G].x, acc[4 * G]) * r0, fmaf(m0, cv[G].y, acc[4 * G + 1]) * r0);
            }
          }
          sc0 = r0 * (0.23570226039551584f * 1.4426950408889634f); sc1 = r1 * (0.23570226039551584f * 1.4426950408889634f);
        }
        ACLK(1);
        constexpr int GA_[4] = {0, 2, 4, 7}, GB_[4] = {1, 3, 5, 8}, GC_[4] = {2, 4, 6, 6};
        float S1[4][4], S2[4][4];
        uint32_t qa[4][2], qc[4][2];
#pragma unroll
        for (int h = 0; h < 4; h++) {
#pragma unroll
          for (int r = 0; r < 2; r++) {
            qa[h][r] = (h == 0 || h == 3 || t >= h) ? Pk[GA_[h]][r] : 0u;
            qc[h][r] = (h == 3 ? t == 3 : t <= h) ? Pk[GC_[h]][r] : 0u;
          }
          mma16(S1[h], qa[h][0], qa[h][1], Pk[GB_[h]][0], Pk[GB_[h]][1], Pk[9 + GA_[h]][0], Pk[9 + GB_[h]][0]);
          mma16(S2[h], qa[h][0], qa[h][1], Pk[GB_[h]][0], Pk[GB_[h]][1], Pk[9 + GA_[h]][1], Pk[9 + GB_[h]][1]);
        }
#pragma unroll
        for (int h = 0; h < 4; h++) {
          mma8(S1[h], qc[h][0], qc[h][1], Pk[9 + GC_[h]][0]);
          mma8(S2[h], qc[h][0], qc[h][1], Pk[9 + GC_[h]][1]);
        }
        uint32_t V1[9], V2[9];
#pragma unroll
        for (int i = 0; i < 9; i++) { V1[i] = movm(Pk[18 + i][0]); V2[i] = movm(Pk[18 + i][1]); }
        const bool remote = q == 0 && rb > 0;
        uint4 hv[6];
#pragma unroll
        for (int i = 0; i < 6; i++) hv[i] = make_uint4(0u, 0u, tag, 0u);
        if (remote) {
#pragma unroll
          for (int i = 0; i < 6; i++) hv[i] = ll_ld128(hp + i * 32);
        }
        const bool up0 = 2 * t > g, up1 = 2 * t + 1 > g;
        const uint32_t mup = (up0 ? 0xffffu : 0u) | (up1 ? 0xffff0000u : 0u);
        auto finish = [&](const float (&x0)[4], const float (&x1)[4], uint32_t ma, const uint32_t (&Vb)[9], int hi) {
          uint32_t pa[4], pb[4];
          float rs[4];
#pragma unroll
          for (int h = 0; h < 4; h++) {
            const float m = qmax(fmaxf(x0[h], x1[h]));
            const uint32_t p = pack2(ex2(x0[h] - m), ex2(x1[h] - m));
            pa[h] = p & ma; pb[h] = p & ~ma;
          }
#pragma unroll
          for (int h = 0; h < 4; h += 2) {
            float R[4];
            mma16(R, pa[h], pa[h + 1], pb[h], pb[h + 1], 0x3f803f80u, 0x3f803f80u);
            rs[h] = rcp_fast(R[0]); rs[h + 1] = rcp_fast(R[2]);
          }
#pragma unroll
          for (int i = 0; i < 9; i++) {
            const int h = 4 * i / 9, e = (h & 1) * 2;
            const bool split = i == 2 || i == 4 || i == 6, nx = split && 2 * t >= i;
            float O[4], N[4];
            mma16(O, pa[h & 2], pa[h | 1], pb[h & 2], pb[h | 1], V1[i], Vb[i]);
            if (i == 4) mma16(N, pa[2], pa[3], pb[2], pb[3], V1[i], Vb[i]); else { N[0] = O[2]; N[1] = O[3]; }
            const float r = nx ? rs[h + (split ? 1 : 0)] : rs[h];
            stg32(od + i * 1024 + hi * 128, pack2((nx ? N[0] : O[e]) * r, (nx ? N[1] : O[e + 1]) * r));
          }
        };
        {
          float x0[4], x1[4];
#pragma unroll
          for (int h = 0; h < 4; h++) { x0[h] = (up0 ? S1[h][2] : S2[h][2]) * sc1; x1[h] = (up1 ? S1[h][3] : S2[h][3]) * sc1; }
          finish(x0, x1, mup, V2, 1);
        }
        ACLK(2);
        bar_sync(1 + w, 128);
        uint32_t H[18];
        if (q > 0) {
#pragma unroll
          for (int i = 0; i < 18; i++) H[i] = lds32(att - 2048 + (i >> 4) * ST_BYTES + (i & 15) * 128);
        } else {
#pragma unroll 1
          for (int it = 0; it < (1 << 20); it++) {
            bool ok = true;
#pragma unroll
            for (int i = 0; i < 6; i++) ok = ok && hv[i].z == tag;
            if (__all_sync(~0u, ok)) break;
#pragma unroll
            for (int i = 0; i < 6; i++) hv[i] = ll_ld128(hp + i * 32);
          }
#pragma unroll
          for (int i = 0; i < 6; i++) { H[3 * i] = hv[i].x; H[3 * i + 1] = hv[i].y; H[3 * i + 2] = hv[i].w; }
        }
        float S0[4][4];
#pragma unroll
        for (int h = 0; h < 4; h++) {
          mma16(S0[h], qa[h][0], qa[h][1], Pk[GB_[h]][0], Pk[GB_[h]][1], H[GA_[h]], H[GB_[h]]);
        }
#pragma unroll
        for (int h = 0; h < 4; h++) mma8(S0[h], qc[h][0], qc[h][1], H[GC_[h]]);
        uint32_t V0[9];
#pragma unroll
        for (int i = 0; i < 9; i++) V0[i] = movm(H[9 + i]);
        ACLK(3);
        {
          const bool nohalo = (rb | q) == 0;
          const float b0 = up0 && nohalo ? -INFINITY : 0.f, b1 = up1 && nohalo ? -INFINITY : 0.f;
          float x0[4], x1[4];
#pragma unroll
          for (int h = 0; h < 4; h++) { x0[h] = fmaf(up0 ? S0[h][0] : S1[h][0], sc0, b0); x1[h] = fmaf(up1 ? S0[h][1] : S1[h][1], sc0, b1); }
          finish(x0, x1, ~mup, V0, 0);
        }
        ACLK(4);
        signal(EV_O);
        ACLK_OUT;
        TRC(tr, w, tb + 2);
        MCLK(1, 2);
      }
      {
        float acc[36];
        const int hw = rb * 2 + (j & 1), js = (j & 6) + w;
        const uint32_t xt = sb + SM_STG + (16 * q + (lane & 15)) * 288 + (9 * w + (lane >> 4)) * 16, eye = (g >> 1) == t ? 0x3f80u << (g & 1) * 16 : 0u;
        uint32_t xm = xt ^ ((lane & 4) << 2), xl = sb + SM_STG + (2 * q + w) * 2304;
        uint32_t xl0 = xl + (lane >> 4) * 288 + (lane & 15) * 16, xl1 = xl + ((lane >> 1) & 7) * 288 + 256 + ((lane ^ (lane >> 3)) & 1) * 16;
        uint8_t* xd0 = P.xs[L + 1] + (128 * rb + 32 * q + 16 * w + (j & 1)) * (DM * 2) + (j & 6) * 144;
        uint8_t* xd1 = xd0 + (lane >> 1) * (DM * 4) + 256 + (lane & 1) * 16;
        xd0 += (lane >> 4) * (DM * 4) + (lane & 15) * 16;
        asm volatile("" : "+r"(xm), "+r"(xl0), "+r"(xl1), "+l"(xd0), "+l"(xd1));
        mbar_wait_c(bars + B_RES, L);
        TRC(tr, w, tb + 21);
#pragma unroll
        for (int u = 0; u < 5; u++) {
          uint32_t r[4];
          ldsm4(r, xt + u * 32);
          widen(acc + 8 * u, r[0], r[1], eye);
          if (u < 4) widen(acc + 8 * u + 4, r[2], r[3], eye);
        }
        uint32_t prev = 0;
#pragma unroll 1
        for (int u = 0; u < 5; u++) {
          const uint32_t st = sb + c.s * ST_BYTES;
          uint64_t da = dsc2(dlo(st, 1024), 0, 8 + P.zero), db = dsc2(dlo(st + ST_B + w * 18432, 1152), 0, 8 ^ P.zero);
          mbar_wait_c(bars + B_FULL + c.s * 8, c.ph); mbar_wait_c(bars + B_FULLA + c.s * 8, (ia >> 2) & 1);
          TRC(tr && u == 0, w, tb + 3);
          MCLK(u == 0, 3);
          wgmma_fence();
#pragma unroll
          for (int kk = 0; kk < 4; kk++) { wgmma_ss_n72(acc, da, db, 1); dadd(da, 128); dadd(db, 144); }
          wgmma_commit();
          wgmma_wait<1>();
          release_if(u > 0, prev);
          mbar_wait_c(bars + B_FULLA + 32 + c.s * 8, (ia >> 2) & 1);
          ia++;
          if (u == 4) break;
          wgmma_fence();
#pragma unroll
          for (int kk = 4; kk < 8; kk++) { wgmma_ss_n72(acc, da, db, 1); dadd(da, 128); dadd(db, 144); }
          wgmma_commit();
          prev = c.s; c.next();
        }
        RCLK_INIT;
        wgmma_wait<0>();
        RCLK(0);
        release(c.s);
        c.next();
        if (__builtin_expect(any_nan(acc[0], acc[2]), 0)) {
          SLOW(L);
          const uint8_t* xr = P.xs[L] + (128 * rb + 32 * q + 2 * g + (j & 1)) * (DM * 2) + js * 144 + t * 4;
#pragma unroll
          for (int i = 0; i < 9; i++) widen(acc + 4 * i, ldgpu32(xr + i * 16), ldgpu32(xr + i * 16 + DM * 32), eye);
          redo<KS2, 9, 1024, 128, 1152, 128>(acc, o_block(rb, j & 1) + q * 256 + lane * 4, P.s->WO + js * WO_SL + lane * 4, [](uint32_t*, int) {});
        }
        TRC(tr && P5TRACE != 5, w, tb + 4);
        MCLK(1, 4);
#pragma unroll
        for (int u = 0; u < 4; u++)
          stsm4(xm + u * 32, pack2(acc[8 * u], acc[8 * u + 1]), pack2(acc[8 * u + 2], acc[8 * u + 3]), pack2(acc[8 * u + 4], acc[8 * u + 5]), pack2(acc[8 * u + 6], acc[8 * u + 7]));
        asm volatile("stmatrix.sync.aligned.m8n8.x2.shared.b16 [%0], {%1,%2};" ::"r"(xm + 128), "r"(pack2(acc[32], acc[33])), "r"(pack2(acc[34], acc[35])) : "memory");
        auto stats = [&]() {
          float s0 = 0.f, s1 = 0.f, q0 = 0.f, q1 = 0.f;
#pragma unroll
          for (int i = 0; i < 36; i++) {
            if (i & 2) { s1 += acc[i]; q1 = fmaf(acc[i], acc[i], q1); } else { s0 += acc[i]; q0 = fmaf(acc[i], acc[i], q0); }
          }
          s0 = qsum(s0); s1 = qsum(s1); q0 = qsum(q0); q1 = qsum(q1);
          const float ss = t ? s1 : s0, m = ss * (1.f / 72.f);
          ll_st128_if(t < 2, P.s->ST1 + (hw * 8 + js) * 64 + 16 * q + 8 * t + g, m, fmaxf((t ? q1 : q0) - ss * m, 0.f), tag);
        };
        stats();
        RCLK(1);
        bar_sync(8 + q, 64);
        RCLK(2);
#pragma unroll
        for (int u = 0; u < 5; u++) {
          const uint4 v = lds128(u < 4 ? (xl0 ^ ((u & 2) << 3)) + u * 576 : xl1);
          stg128_if(u < 4 || lane < 16, u < 4 ? xd0 + u * (DM * 8) : xd1, v.x, v.y, v.z, v.w);
        }
        RCLK(3);
        signal(EV_X1);
        RCLK(4);
        RCLK(5);
        TRC(tr, w, tb + 5);
        RCLK(6);
        RCLK_OUT;
      }
      uint32_t zk[16];
      {
        uint32_t xA[36][4];
        float acc[32];
        uint32_t s0, one, off2;
        uint8_t *z1d, *zd;
        uint64_t db;
        auto bwait = [&](uint32_t dhi, bool skip) {
          s0 = c.s;
          c.next();
          if (!skip) mbar_wait_c(bars + B_FULL + c.s * 8, c.ph);
          db = dsc2(dlo(sb + s0 * ST_BYTES + ST_B, 512) - 3, 0, dhi); one = (c.s ^ P.zero) & 1;
        };
        auto mma = [&](int kk, int pp, bool hand) {
          wgmma_rs_n64(acc, xA[kk], dat(db, (kk / 18) * ST_BYTES + (kk % 18) * 2048 + 48, one), kk != 0);
          if (kk == pp && hand) bar_arrive(7 - w, 256);
          if (kk == 17 || kk == 35) wgmma_commit();
          if (kk == RL3) { wgmma_commit(); wgmma_wait<1>(); release(s0); }
        };
        {
          bwait(0x40000040u, false);
          mbar_wait_c(bars + B_GATE3, L);
          float mean0, mean1, rs0, rs1;
          stat_get(P.s->ST1 + ((rb * 2 + w) * 8 + 2 * t) * 64 + 16 * q + g, tag, 72.f, LN_EPS, mean0, rs0, mean1, rs1);
          const uint32_t ns0 = pack2(GA * rs0, GA * rs0), ns1 = pack2(GA * rs1, GA * rs1);
          const uint32_t nb0 = pack2(-mean0 * blo(ns0), -mean0 * blo(ns0)), nb1 = pack2(-mean1 * blo(ns1), -mean1 * blo(ns1));
          const uint32_t al = sb + (aoff & 8191);
#pragma unroll
          for (int kb = 0; kb <= 9; kb++) {
            if (kb < 9) {
              mbar_wait_c(bars + B_FA3 + (9 * w + kb) * 8, L);
              TRC(tr && kb == 0, w, tb + 6);
              MCLK(kb == 0, 5);
              if (kb == 0) SCLK(0);
              QCLK(kb);
              const uint32_t at = al + (w ? (((kb + 1) >> 1) & 3) * ST_BYTES + ((kb + 1) & 1) * 8192 : ((kb >> 1) & 3) * ST_BYTES + (kb & 1) * 8192);
#pragma unroll
              for (int kk = 4 * kb; kk < 4 * kb + 4; kk++) ldsm4(xA[kk], at ^ ((kk & 3) << 5));
            }
            if (kb == 0) continue;
            const uint32_t dep = xA[4 * kb - 4][0] & xA[4 * kb - 3][0] & xA[4 * kb - 2][0] & xA[4 * kb - 1][0] & P.zero;
            mbar_arrive_if(lane == 0 && (kb == 1 || w == 0), bars + B_EA3 + (9 * w + kb - 1) * 8 + dep);
#pragma unroll
            for (int kk = 4 * kb - 4; kk < 4 * kb; kk++) {
#pragma unroll
              for (int e = 0; e < 4; e++) xA[kk][e] = hfma2(xA[kk][e], (e & 1) ? ns1 : ns0, (e & 1) ? nb1 : nb0);
            }
            wgmma_fence();
#pragma unroll
            for (int kk = 4 * kb - 4; kk < 4 * kb; kk++) mma(kk, PP30, w);
          }
          off2 = lds32(sb + SM_OFF);
          z1d = z1_block(rb, w, j) + (tid & 127) * 16;
          zd = z2_block(2 * rb + (q >> 1), j) + (4 * (q & 1) + w) * 4608 + ((g & 3) * 2 + (g >> 2)) * 16 + t * 4;
          asm volatile("" : "+l"(z1d), "+l"(zd));
          wgmma_wait<0>();
          if (__builtin_expect(any_nan(acc[0], acc[2]), 0)) {
            SLOW(2 + L);
            uint4* const rd = P.s->RD + bid * (36 * 256) + tid;
            const uint8_t* xr = P.xs[L + 1] + (128 * rb + 32 * q + 2 * g + w) * (DM * 2) + t * 4;
#pragma unroll
            for (int i = 0; i < 32; i++) acc[i] = 0.f;
            redo<KS3, 8, 16, DM * 32, FH * 32, 16>(acc, xr, (const uint8_t*)P.w_in + g * (FH * 4) + (((9 * j + 1) >> 1) + 36) * 128 + t * 4,
                                              [&](uint32_t* a, int k) {
#pragma unroll
                                                for (int e = 0; e < 4; e++) a[e] = hfma2(a[e], (e & 1) ? ns1 : ns0, (e & 1) ? nb1 : nb0);
                                                stg128(rd + k * 256, a[0], a[1], a[2], a[3]);
                                              });
#pragma unroll
            for (int k = 0; k < 36; k++) { const uint4 v = ldcg128(rd + k * 256); xA[k][0] = v.x; xA[k][1] = v.y; xA[k][2] = v.z; xA[k][3] = v.w; }
          }
        }
        float sm[4] = {0.f, 0.f, 0.f, 0.f}, qq[4] = {0.f, 0.f, 0.f, 0.f};
        auto gelu = [&](auto nz2) {
          constexpr int NZ2 = nz2.value, R = 8 - NZ2, N = 8, D = NZ2 == 8 ? GM2 : NZ2 ? GMM : GM1;
          float th[32], gb = GB;
          uint32_t qa = 0, qb = 0;
          auto head = [&](int G) {
#pragma unroll
            for (int e = 0; e < 4; e++) { const float v = acc[4 * G + e]; th[4 * G + e] = tanh_fast(v * fmaf(v, v, gb)); }
          };
#pragma unroll
          for (int i = 0; i < D; i++) head((i + R) & 7);
#pragma unroll
          for (int i = 0; i < N; i++) {
            const int G = (i + R) & 7;
            if (i + D < N) head((i + D + R) & 7);
            float* z = acc + 4 * G;
#pragma unroll
            for (int e = 0; e < 4; e++) z[e] = fmaf(z[e], th[4 * G + e], z[e]);
            uint32_t pa = pack2(z[0], z[1]), pb = pack2(z[2], z[3]), tok;
            if (i < NZ2) {
#pragma unroll
              for (int e = 0; e < 4; e++) { sm[e] += z[e]; qq[e] = fmaf(z[e], z[e], qq[e]); }
              pa = hsub2(pa, off2); pb = hsub2(pb, off2);
              stg32(zd + i * 128, pa); stg32(zd + i * 128 + 9216, pb);
              tok = pa ^ pb ^ __float_as_uint(qq[1]);
            } else {
              if (NZ2 && G == 3) sts128(sb + SM_STG + tid * 16, qa, qb, pa, pb);
              else if (G & 1) stg128(z1d + (G >> 1) * 2048 + (NZ2 ? 24576 : 0), qa, qb, pa, pb);
              qa = pa; qb = pb;
              tok = pa ^ pb;
            }
            gb = __uint_as_float(tok * P.zero + __float_as_uint(GB));
          }
        };
        auto done = [&](int p) {
          wgmma_wait<0>();
          release(c.s);
          c.next();
          TRC(tr && p == 4, w, tb + 7);
          TRC(tr && p == 8, w, tb + 11);
          MCLK(p == 8, 6);
          SCLK(2 * p + 1);
          QCLK(10 + 3 * p);
        };
        auto pass = [&](int p, uint32_t dhi) {
          SCLK(2 * p);
          QCLK(8 + 3 * p);
          bwait(dhi, w);
          bar_sync(6 + w, 256);
          TRC(tr && p == 5, w, tb + 10);
          wgmma_fence();
#pragma unroll
          for (int kk = 0; kk < 36; kk++) mma(kk, PP3, w == 0 || p < 8);
          done(p);
        };
        done(0);
#pragma unroll 1
        for (int p = 1; p < 5; p++) {
          gelu(Int<8>{});
          zd += 1024;
          pass(p, p == 4 ? 0x80000040u : 0x40000040u);
        }
        gelu(Int<4>{});
        signal(EV_ZN);
        {
          const float a0 = qsum(sm[0] + sm[1]), a1 = qsum(sm[2] + sm[3]), q0 = qsum(qq[0] + qq[1]), q1 = qsum(qq[2] + qq[3]);
          const float ss = t ? a1 : a0, m = ss * (1.f / 288.f);
          ll_st128_if(t < 2, P.s->ZST + (rb * 2 + w) * 512 + j * 64 + 16 * q + 8 * t + g, m - blo(off2), fmaxf((t ? q1 : q0) - ss * m, 0.f), tag);
        }
        TRC(tr, w, tb + 8);
        TRC(tr, w, tb + 9);
#pragma unroll 1
        for (int p = 5;; p++) {
          pass(p, 0x40000040u);
          if (p == 8) break;
          gelu(Int<0>{});
          z1d += 8192;
        }
        signal(EV_Z1);
#pragma unroll
        for (int i = 0; i < 16; i++) zk[i] = pack2(acc[2 * i], acc[2 * i + 1]);
        SCLK(18);
        TRC(tr, w, tb + 12);
      }
      uint32_t hA[18][4];
      {
        float acc[144];
        const float c0 = __uint_as_float(lds32(sb + SM_OFF + 4));
#pragma unroll
        for (int i = 0; i < 144; i++) {
          asm volatile("fma.rn.f32 %0, %1, %2, %3;" : "=f"(acc[i]) : "f"(__uint_as_float(P.zero)), "f"((float)(i + 2)), "f"(c0));
        }
        uint32_t prev = 0;
        auto stage = [&](int kb, auto odd) {
          mbar_wait_c(bars + B_FULL + c.s * 8, c.ph);
          TRC(tr && kb == 0, w, tb + 13);
          SCLK(22 + kb);
          const uint32_t st = sb + c.s * ST_BYTES, rt = sb + SM_RT + kb * 128 + t * 8;
          uint64_t db = dsc2(dlo(st + ST_B, 4608), 0, 8 + P.zero);
          uint32_t a[4][4];
#pragma unroll
          for (int kk = 0; kk < 4; kk++) {
            uint32_t r[4];
            ldsm4(r, st + (aoff ^ (kk << 5)));
            const uint2 sc = lds64(rt + kk * 32);
            a[kk][0] = hmul2(__byte_perm(r[0], r[2], 0x5410), sc.x); a[kk][2] = hmul2(__byte_perm(r[0], r[2], 0x7632), sc.y);
            a[kk][1] = hmul2(__byte_perm(r[1], r[3], 0x5410), sc.x); a[kk][3] = hmul2(__byte_perm(r[1], r[3], 0x7632), sc.y);
          }
          if (!odd.value) {
            const float x = blo(zk[0]), y = bhi(zk[0]);
#pragma unroll
            for (int i = 0; i < 15; i++) zk[i] = zk[i + 1];
            zk[15] = pack2(fmaf(x, tanh_fast(x * fmaf(x, x, GB)), x), fmaf(y, tanh_fast(y * fmaf(y, y, GB)), y));
          }
          wgmma_fence();
#pragma unroll
          for (int i = 0; i < 8; i++) {
            const int kk = i & 3, hf = i >> 2;
            wgmma_rs_n144(acc + hf * 72, a[kk], db, 1);
            dadd(db, i == 3 ? 144u - 3 * 576 : 576 + P.zero);
            if (i == 0) { wgmma_commit(); wgmma_wait<1>(); release_if(kb, prev); }
            if (i == 3) wgmma_commit();
          }
          wgmma_commit();
          prev = c.s; c.next();
        };
        mbar_wait_c(bars + B_RT, L);
#pragma unroll 1
        for (int kb = 0; kb < 32; kb += 2) {
          if (kb == 8) mbar_wait_c(bars + B_RT1, L);
          MCLK((kb & 7) == 4, 10 + (kb >> 3));
          stage(kb, Int<0>{});
          stage(kb + 1, Int<1>{});
        }
        if (w == 1) bar_arrive(6, 256);
        HCLK(0);
        mbar_wait_c(bars + B_CV + w * 8, L);
        HCLK(1);
        const float gk = 0.5f / GA;
        const float c1 = __uint_as_float(lds32(sb + SM_OFF + 4));
        const float gb0 = -gk * (c1 + __uint_as_float(lds32(sb + SM_CV + w * 256 + (16 * q + g) * 4))), gb1 = -gk * (c1 + __uint_as_float(lds32(sb + SM_CV + w * 256 + (16 * q + g + 8) * 4)));
        mbar_wait_c(w ? bars + B_FULL + c.s * 8 : bars + B_ZB, w ? c.ph : L);
        HCLK(2);
        const uint32_t sx = c.s;
        c.next();
        const uint32_t zt = sb + tid * 16, zs = zt + sx * ST_BYTES + w * 24576;
        uint4 zz[18];
        auto zload = [&](int u) {
          if (ZW && u == ZW && P.zero) __nanosleep(0);
          if (u >= 12 && u < 16) zz[u] = make_uint4(zk[4 * u - 48], zk[4 * u - 47], zk[4 * u - 46], zk[4 * u - 45]); else zz[u] = lds128(u == 17 ? zt + SM_STG : zs + (u < 12 ? u : 12) * 2048);
        };
#pragma unroll
        for (int u = 0; u < ZA; u++) zload(u);
#pragma unroll
        for (int u = 0; u < 18; u++) {
          if (u == 0) { wgmma_wait<1>(); HCLK(3); }
          if (u == 9) {
            HCLK(4);
            wgmma_wait<0>();
            HCLK(5);
            release(prev);
            mbar_arrive_if(L == 0 && lane == 0, ev + EV_P4 * 8);
            TRC(tr, w, tb + 14);
            SCLK(54);
          }
          if (u + ZA < 18) zload(u + ZA);
          const uint4 z = zz[u];
          hA[u][0] = hmul2(z.x, pack2(fmaf(acc[8 * u], gk, gb0), fmaf(acc[8 * u + 1], gk, gb0)));
          hA[u][1] = hmul2(z.y, pack2(fmaf(acc[8 * u + 2], gk, gb1), fmaf(acc[8 * u + 3], gk, gb1)));
          hA[u][2] = hmul2(z.z, pack2(fmaf(acc[8 * u + 4], gk, gb0), fmaf(acc[8 * u + 5], gk, gb0)));
          hA[u][3] = hmul2(z.w, pack2(fmaf(acc[8 * u + 6], gk, gb1), fmaf(acc[8 * u + 7], gk, gb1)));
        }
        uint32_t dep = P.zero;
#pragma unroll
        for (int u = 0; u < 18; u++) dep &= hA[u][0];
        release(sx, dep);
        TRC(tr, w, tb + 15);
        HCLK(6);
      }
      {
        const uint32_t el = elect_one();
#pragma unroll 1
        for (int p = 0; p < 9; p++) {
          float acc[32];
          if (w == 0) mbar_wait_c(bars + B_FULL + c.s * 8, c.ph);
          uint64_t db = dsc2(dlo(sb + c.s * ST_BYTES + ST_B + (j & 1) * 4096, 0), 0, 0x40000040u + P.zero);
          HCLK(7 + 2 * p);
          bar_sync(6 + w, 256);
          wgmma_fence();
#pragma unroll
          for (int kk = 0; kk < 18; kk++) {
            wgmma_rs_n64(acc, hA[kk], db, kk != 0);
            dadd(db, kk == 15 ? 128 - (j & 1) * (36864 >> 4) : 128 + P.zero);
            if (kk == PPK && (w == 0 || p < 8)) bar_arrive(7 - w, 256);
          }
          wgmma_commit();
          const uint32_t d = sb + (p & 3) * ST_BYTES, cb = p + j >= 9 ? p + j - 9 : p + j;
          if (el) asm volatile("cp.async.bulk.wait_group.read 3;" ::: "memory");
          __syncwarp();
          wgmma_wait<0>();
          HCLK(8 + 2 * p);
          MCLK(p == 1 || p == 8, 7 + (p >> 3));
          TRC(tr && p == 8, w, tb + 16);
          release_if(L == 0 || p < 5, c.s);
          c.next();
#pragma unroll
          for (int u = 0; u < 4; u++)
            stsm4(d + (aoff ^ (u << 5)), pack2(acc[8 * u], acc[8 * u + 1]), pack2(acc[8 * u + 2], acc[8 * u + 3]), pack2(acc[8 * u + 4], acc[8 * u + 5]), pack2(acc[8 * u + 6], acc[8 * u + 7]));
          fence_async_s();
          __syncwarp();
          tma3d_red_p(el, &P.red[L], cb * 64, rb * 64 + q * 16, w, d + w * 8192 + q * 2048);
          TRC(tr && p == 8, w, tb + 17);
        }
        if (el) asm volatile("cp.async.bulk.wait_group 0;" ::: "memory");
        HCLK(25);
        MCLK(1, 9);
        if (L == 0) signal(EV_PT);
        TRC(tr, w, tb + 18);
      }
    }
  }
}

typedef CUresult (*EncodeFn)(CUtensorMap*, CUtensorMapDataType, cuuint32_t, void*, const cuuint64_t*, const cuuint64_t*, const cuuint32_t*,
                             const cuuint32_t*, CUtensorMapInterleave, CUtensorMapSwizzle, CUtensorMapL2promotion, CUtensorMapFloatOOBfill);

static void make_map(EncodeFn fn, CUtensorMap* m, const void* ptr, int rank, uint64_t d0, uint64_t d1, uint64_t d2, uint64_t s1, uint64_t s2,
                     uint32_t b0, uint32_t b1, uint32_t b2, CUtensorMapSwizzle swz) {
  cuuint64_t dims[3] = {d0, d1, d2}, strides[2] = {s1, s2};
  cuuint32_t box[3] = {b0, b1, b2}, es[3] = {1, 1, 1};
  fn(m, CU_TENSOR_MAP_DATA_TYPE_BFLOAT16, rank, const_cast<void*>(ptr), dims, strides, box, es, CU_TENSOR_MAP_INTERLEAVE_NONE, swz,
     CU_TENSOR_MAP_L2_PROMOTION_L2_128B, CU_TENSOR_MAP_FLOAT_OOB_FILL_NONE);
}

}

extern "C" void kernel_launch(void* const* d_in, const int* in_sizes, int n_in, void* d_out, int out_size) {
  using namespace mk;
  (void)in_sizes; (void)n_in; (void)out_size;
  static EncodeFn fn = nullptr;
  static Scratch* sc;
  if (!fn) {
    cudaGetSymbolAddress((void**)&sc, g_scratch);
    cudaDriverEntryPointQueryResult qr;
    cudaGetDriverEntryPoint("cuTensorMapEncodeTiled", (void**)&fn, cudaEnableDefault, &qr);
    cudaFuncSetAttribute(mega_kernel, cudaFuncAttributeMaxDynamicSharedMemorySize, SM_TOTAL);
  }
  Params p;
  p.wqkv = (const __nv_bfloat16*)d_in[1];
  p.w_in = (const __nv_bfloat16*)d_in[4];
  p.w_sp = (const __nv_bfloat16*)d_in[5];
  p.b_sp = (const __nv_bfloat16*)d_in[6];
  p.w_out = (const __nv_bfloat16*)d_in[7];
  p.zero = 0;
  p.s = sc;
  p.xs[0] = (uint8_t*)d_in[0];
  p.xs[1] = sc->X;
  p.xs[2] = (uint8_t*)d_out;
  make_map(fn, &p.wsp, p.w_sp, 3, 2048, 1024, 2, 8192, 4096, 64, 64, 2, CU_TENSOR_MAP_SWIZZLE_128B);
  for (int i = 0; i < 2; i++) {
    make_map(fn, &p.red[i], p.xs[i + 1], 3, DM, 1024, 2, 2304, 1152, 64, 16, 1, CU_TENSOR_MAP_SWIZZLE_128B);
    make_map(fn, &p.res[i], p.xs[i], 3, DM, 1024, 2, 2304, 1152, 144, 64, 1, CU_TENSOR_MAP_SWIZZLE_NONE);
  }
  make_map(fn, &p.psn, d_out, 3, DM, 1024, 2, 2304, 1152, 144, 4, 1, CU_TENSOR_MAP_SWIZZLE_NONE);
  for (int i = 0; i < 3; i++) make_map(fn, &p.act[i], p.xs[i], 3, DM, 1024, 2, 2304, 1152, 64, 64, 1, CU_TENSOR_MAP_SWIZZLE_128B);
  {
    cuuint64_t dims[4] = {8, 8, 72, 72}, strides[3] = {1152, 16, 9216};
    cuuint32_t box[4] = {8, 8, 9, 5}, es[4] = {1, 1, 1, 1};
    fn(&p.wo8, CU_TENSOR_MAP_DATA_TYPE_BFLOAT16, 4, d_in[2], dims, strides, box, es, CU_TENSOR_MAP_INTERLEAVE_NONE, CU_TENSOR_MAP_SWIZZLE_NONE,
       CU_TENSOR_MAP_L2_PROMOTION_L2_128B, CU_TENSOR_MAP_FLOAT_OOB_FILL_NONE);
  }
  for (int i = 0; i < 2; i++) {
    cuuint64_t dims[4] = {i ? 4608u : 2304u, 8, i ? 1u : 2u, 72}, strides[3] = {9216, 4608, 8 * 9216};
    cuuint32_t box[4] = {i ? 64u : 32u, 8, i ? 1u : 2u, 18}, es[4] = {1, 1, 1, 1};
    fn(i ? &p.win64 : &p.win, CU_TENSOR_MAP_DATA_TYPE_BFLOAT16, 4, d_in[4], dims, strides, box, es, CU_TENSOR_MAP_INTERLEAVE_NONE,
       i ? CU_TENSOR_MAP_SWIZZLE_128B : CU_TENSOR_MAP_SWIZZLE_64B, CU_TENSOR_MAP_L2_PROMOTION_L2_128B, CU_TENSOR_MAP_FLOAT_OOB_FILL_NONE);
  }
  make_map(fn, &p.wout, p.w_out, 2, 576, 2304, 1, 1152, 0, 64, 144, 1, CU_TENSOR_MAP_SWIZZLE_128B);
  mega_kernel<<<NGRID, 384, SM_TOTAL, cudaStreamPerThread>>>(p);
}
```

```cpp
#include <cuda_runtime.h>
#include <cuda.h>
#include <cuda_bf16.h>
#include <stdint.h>

#define MK_TRACE 0
#define MK_DBG 0
#define P5TRACE 0
#define LAG1 3
#define PP3 34
#define PP30 33
#define SPL 2
#define NAP 200
#define NAP0 8000
#define KS2 1
#define KS3 1
#define RL3 21
#define PAD 0
#define ZA 4
#define ZW 10
#define GA3 10
#define GB3 12
#define GM2 1
#define GMM 1
#define GM1 2
#define C0S 32.f
#define OFA 0.125f
#define OFK 2.f
#define PPK 15

namespace mk {

constexpr int SEQ = 2048, DM = 576, FH = 2304;
constexpr int NCTA = 128;
constexpr int NGRID = 132;
constexpr uint32_t ZB = 36864;
constexpr uint32_t WQ_SL = 72 * 3456;
constexpr uint32_t WO_SL = 72 * 1152;
constexpr float LN_EPS = 1e-5f;
constexpr float GA = 0.3292034911525734f, GB = 2.423681954311584f;

constexpr uint32_t ST_BYTES = 53248, ST_B = 16384, NST = 4;
constexpr uint32_t SM_STG = NST * ST_BYTES;
constexpr uint32_t SM_BAR = SM_STG + 2 * 9216;
constexpr uint32_t SM_OFF = SM_BAR + 1008;
constexpr uint32_t SM_TOTAL = SM_BAR + 1024;
constexpr uint32_t SM_RT = SM_STG + 4096, SM_CV = SM_STG + 12288, SM_WT = SM_CV + 512;
constexpr uint32_t SM_WOI = 44032, SM_CSQ = 49792, SM_XST = 50688;
constexpr uint32_t B_FULL = 0, B_EMPTY = 32, B_FULLA = 64, B_RES = 128, B_WT = 144, B_IMG = 160, B_WOI = 168, B_ZB = 176, B_GATE3 = 184, B_Z1 = 192, B_LAG = 200,
                   B_RT = 208, B_CSQ = 216, B_CV = 224, B_AD = 240, B_EVT = 272, B_RT1 = 368, B_XS = 624, B_XRW = 384, B_FA3 = 400, B_EA3 = 544;
enum { EV_PT = 0, EV_O = 1, EV_X1 = 2, EV_ZN = 3, EV_Z1 = 4, EV_P4 = 5, EV_N = 6 };

enum { FR_X2 = 0, FR_O = 1, FR_X1 = 3, FR_EP = 16, FJ = 32 * 32, FJ_WQ = 0, FJ_WO = 1, FJ_WQ0 = 2, FJ_ZN = 3, FJ_P4 = 5, FJ_EP = 16, F_N = FJ + 8 * 32 };

constexpr uint32_t POISON = 0xffffffffu;
struct Scratch {
  uint32_t flags[F_N];
  uint2 RT[SEQ];
  uint4 XST[2 * SEQ];
  uint4 ST1[SEQ * 8], ZST[SEQ * 8], HALO[32 * 8 * 6 * 32];
  float CSP[2 * NCTA * 216];
  uint8_t WQ[8 * WQ_SL], WO[8 * WO_SL];
  uint8_t O[32 * 2 * ZB];
  uint8_t X[SEQ * DM * 2];
  uint8_t Z[512 * ZB];
  uint4 RD[NCTA * 36 * 256];
};
__device__ __align__(1024) Scratch g_scratch;
#define SLOW(i) do {} while (0)

struct Params {
  const __nv_bfloat16 *wqkv;
  Scratch* s;
  uint32_t zero;
  const __nv_bfloat16 *w_in, *w_sp, *b_sp, *w_out;
  uint8_t* xs[3];
  CUtensorMap wo8, wsp, win, win64, wout;
  CUtensorMap act[3];
  CUtensorMap res[2];
  CUtensorMap red[2];
  CUtensorMap psn;
};

__device__ __forceinline__ uint32_t smem_u32(const void* p) { return (uint32_t)__cvta_generic_to_shared(p); }
__device__ __forceinline__ void mbar_init(uint32_t bar, uint32_t cnt) { asm volatile("mbarrier.init.shared::cta.b64 [%0], %1;" ::"r"(bar), "r"(cnt)); }
__device__ __forceinline__ void mbar_arrive(uint32_t bar) { asm volatile("mbarrier.arrive.shared::cta.b64 _, [%0];" ::"r"(bar) : "memory"); }
__device__ __forceinline__ void mbar_wait(uint32_t bar, uint32_t parity) {
  asm volatile(
      "{\n.reg .pred p;\n.reg .u32 c;\nmov.u32 c, 0;\nLAB_WAIT:\n"
      "mbarrier.try_wait.parity.shared::cta.b64 p, [%0], %1;\n@p bra LAB_DONE;\n"
      "add.u32 c, c, 1;\nsetp.lt.u32 p, c, 0x100000;\n@p bra LAB_WAIT;\ntrap;\nLAB_DONE:\n}" ::"r"(bar), "r"(parity)
      : "memory");
}
__device__ __forceinline__ void mbar_wait_c(uint32_t bar, uint32_t parity) {
  asm volatile("{\n.reg .pred p;\nLAB_WAIT:\nmbarrier.try_wait.parity.shared::cta.b64 p, [%0], %1;\n@!p bra LAB_WAIT;\n}" ::"r"(bar), "r"(parity) : "memory");
}
__device__ __forceinline__ void flag_wait(const uint32_t* f, uint32_t target) {
  asm volatile(
      "{\n.reg .pred p;\n.reg .u32 c, v;\nmov.u32 c, 0;\nLAB_WAIT:\n"
      "ld.relaxed.gpu.global.u32 v, [%0];\nsub.u32 v, v, %1;\nsetp.ge.s32 p, v, 0;\n@p bra LAB_DONE;\n"
      "add.u32 c, c, 1;\nsetp.lt.u32 p, c, 0x400000;\n@p bra LAB_WAIT;\ntrap;\nLAB_DONE:\nfence.acquire.gpu;\n}" ::"l"(f), "r"(target)
      : "memory");
}
__device__ __forceinline__ void fence_gpu() { asm volatile("fence.acq_rel.gpu;" ::: "memory"); }
__device__ __forceinline__ void fence_async_g() { asm volatile("fence.proxy.async.global;" ::: "memory"); }
__device__ __forceinline__ void fence_async_s() { asm volatile("fence.proxy.async.shared::cta;" ::: "memory"); }
__device__ __forceinline__ uint32_t elect_one() {
  uint32_t p; asm volatile("{\n.reg .pred P;\nelect.sync _|P, 0xffffffff;\nselp.u32 %0, 1, 0, P;\n}" : "=r"(p)); return p;
}
__device__ __forceinline__ void expect_tx_p(uint32_t el, uint32_t bar, uint32_t bytes) {
  asm volatile("{\n.reg .pred P;\nsetp.ne.u32 P, %2, 0;\n@P mbarrier.arrive.expect_tx.shared::cta.b64 _, [%0], %1;\n}" ::"r"(bar), "r"(bytes), "r"(el) : "memory");
}
__device__ __forceinline__ void bulk_load_p(uint32_t el, uint32_t dst, const void* src, uint32_t bytes, uint32_t bar) {
  asm volatile("{\n.reg .pred P;\nsetp.ne.u32 P, %4, 0;\n@P cp.async.bulk.shared::cluster.global.mbarrier::complete_tx::bytes [%0], [%1], %2, [%3];\n}" ::"r"(dst), "l"(src), "r"(bytes), "r"(bar), "r"(el) : "memory");
}
__device__ __forceinline__ uint64_t policy_evict_first() { uint64_t p; asm("createpolicy.fractional.L2::evict_first.b64 %0, 1.0;" : "=l"(p)); return p; }
__device__ __forceinline__ void bulk_load_h(uint32_t el, uint32_t dst, const void* src, uint32_t bytes, uint32_t bar, bool ef, uint64_t pol) {
  if (ef) {
    asm volatile("{\n.reg .pred P;\nsetp.ne.u32 P, %4, 0;\n@P cp.async.bulk.shared::cluster.global.mbarrier::complete_tx::bytes.L2::cache_hint [%0], [%1], %2, [%3], %5;\n}" ::"r"(dst), "l"(src), "r"(bytes), "r"(bar), "r"(el), "l"(pol) : "memory");
  } else {
    asm volatile("{\n.reg .pred P;\nsetp.ne.u32 P, %4, 0;\n@P cp.async.bulk.shared::cluster.global.mbarrier::complete_tx::bytes [%0], [%1], %2, [%3];\n}" ::"r"(dst), "l"(src), "r"(bytes), "r"(bar), "r"(el) : "memory");
  }
}
__device__ __forceinline__ void bulk_mc_h(uint32_t el, uint32_t dst, const void* src, uint32_t bytes, uint32_t bar, bool ef, uint64_t pol) {
  if (ef) {
    asm volatile("{\n.reg .pred P;\nsetp.ne.u32 P, %4, 0;\n@P cp.async.bulk.shared::cluster.global.mbarrier::complete_tx::bytes.multicast::cluster.L2::cache_hint [%0], [%1], %2, [%3], %5, %6;\n}" ::"r"(dst), "l"(src), "r"(bytes), "r"(bar), "r"(el), "h"((uint16_t)3), "l"(pol) : "memory");
  } else {
    asm volatile("{\n.reg .pred P;\nsetp.ne.u32 P, %4, 0;\n@P cp.async.bulk.shared::cluster.global.mbarrier::complete_tx::bytes.multicast::cluster [%0], [%1], %2, [%3], %5;\n}" ::"r"(dst), "l"(src), "r"(bytes), "r"(bar), "r"(el), "h"((uint16_t)3) : "memory");
  }
}
__device__ __forceinline__ void tma3d_h(uint32_t el, uint32_t dst, const CUtensorMap* m, int c0, int c1, int c2, uint32_t bar, bool ef, uint64_t pol) {
  if (ef) {
    asm volatile("{\n.reg .pred P;\nsetp.ne.u32 P, %6, 0;\n@P cp.async.bulk.tensor.3d.shared::cluster.global.mbarrier::complete_tx::bytes.L2::cache_hint [%0], [%1, {%3, %4, %5}], [%2], %7;\n}" ::"r"(dst), "l"(m), "r"(bar), "r"(c0), "r"(c1), "r"(c2), "r"(el), "l"(pol) : "memory");
  } else {
    asm volatile("{\n.reg .pred P;\nsetp.ne.u32 P, %6, 0;\n@P cp.async.bulk.tensor.3d.shared::cluster.global.mbarrier::complete_tx::bytes [%0], [%1, {%3, %4, %5}], [%2];\n}" ::"r"(dst), "l"(m), "r"(bar), "r"(c0), "r"(c1), "r"(c2), "r"(el) : "memory");
  }
}
__device__ __forceinline__ void tma2d_mc_h(uint32_t el, uint32_t dst, const CUtensorMap* m, int c0, int c1, uint32_t bar, bool ef, uint64_t pol) {
  if (ef) {
    asm volatile("{\n.reg .pred P;\nsetp.ne.u32 P, %5, 0;\n@P cp.async.bulk.tensor.2d.shared::cluster.global.mbarrier::complete_tx::bytes.multicast::cluster.L2::cache_hint [%0], [%1, {%3, %4}], [%2], %6, %7;\n}" ::"r"(dst), "l"(m), "r"(bar), "r"(c0), "r"(c1), "r"(el), "h"((uint16_t)3), "l"(pol) : "memory");
  } else {
    asm volatile("{\n.reg .pred P;\nsetp.ne.u32 P, %5, 0;\n@P cp.async.bulk.tensor.2d.shared::cluster.global.mbarrier::complete_tx::bytes.multicast::cluster [%0], [%1, {%3, %4}], [%2], %6;\n}" ::"r"(dst), "l"(m), "r"(bar), "r"(c0), "r"(c1), "r"(el), "h"((uint16_t)3) : "memory");
  }
}
__device__ __forceinline__ void tma4d_mc(uint32_t el, uint32_t dst, const CUtensorMap* m, int c0, int c3, uint32_t bar, uint64_t pol) {
  asm volatile("{\n.reg .pred P;\nsetp.ne.u32 P, %5, 0;\n@P cp.async.bulk.tensor.4d.shared::cluster.global.mbarrier::complete_tx::bytes.multicast::cluster.L2::cache_hint [%0], [%1, {%3, 0, 0, %4}], [%2], %6, %7;\n}" ::"r"(dst), "l"(m), "r"(bar), "r"(c0), "r"(c3), "r"(el), "h"((uint16_t)3), "l"(pol) : "memory");
}
__device__ __forceinline__ void mbar_arrive_cluster(uint32_t addr) { asm volatile("mbarrier.arrive.shared::cluster.b64 _, [%0];" ::"r"(addr) : "memory"); }
__device__ __forceinline__ void mbar_arrive_cluster_if(bool c, uint32_t addr) {
  asm volatile("{\n.reg .pred P;\nsetp.ne.u32 P, %1, 0;\n@P mbarrier.arrive.shared::cluster.b64 _, [%0];\n}" ::"r"(addr), "r"((uint32_t)c) : "memory");
}
__device__ __forceinline__ void mbar_arrive_if(bool c, uint32_t addr) {
  asm volatile("{\n.reg .pred P;\nsetp.ne.u32 P, %1, 0;\n@P mbarrier.arrive.shared::cta.b64 _, [%0];\n}" ::"r"(addr), "r"((uint32_t)c) : "memory");
}
__device__ __forceinline__ uint32_t mapa(uint32_t addr, uint32_t rank) { uint32_t r; asm("mapa.shared::cluster.u32 %0, %1, %2;" : "=r"(r) : "r"(addr), "r"(rank)); return r; }
__device__ __forceinline__ void bulk_store_p(uint32_t el, void* dst, uint32_t src, uint32_t bytes) {
  asm volatile("{\n.reg .pred P;\nsetp.ne.u32 P, %3, 0;\n@P cp.async.bulk.global.shared::cta.bulk_group [%0], [%1], %2;\n}" ::"l"(dst), "r"(src), "r"(bytes), "r"(el) : "memory");
}
__device__ __forceinline__ void flag_release_p(uint32_t el, uint32_t* f) {
  asm volatile("{\n.reg .pred P;\nsetp.ne.u32 P, %1, 0;\n@P red.release.gpu.global.add.u32 [%0], 1;\n}" ::"l"(f), "r"(el) : "memory");
}
__device__ __forceinline__ void flag_add_p(uint32_t el, uint32_t* f) {
  asm volatile("{\n.reg .pred P;\nsetp.ne.u32 P, %1, 0;\n@P red.relaxed.gpu.global.add.u32 [%0], 1;\n}" ::"l"(f), "r"(el) : "memory");
}
__device__ __forceinline__ void prefetch_l2(const void* src, uint32_t bytes) { asm volatile("cp.async.bulk.prefetch.L2.global [%0], %1;" ::"l"(src), "r"(bytes) : "memory"); }
__device__ __forceinline__ void prefetch_map(const CUtensorMap* m) { asm volatile("prefetch.tensormap [%0];" ::"l"(m) : "memory"); }
__device__ __forceinline__ void wgmma_fence() { asm volatile("wgmma.fence.sync.aligned;" ::: "memory"); }
__device__ __forceinline__ void wgmma_commit() { asm volatile("wgmma.commit_group.sync.aligned;" ::: "memory"); }
template <int N> __device__ __forceinline__ void wgmma_wait() { asm volatile("wgmma.wait_group.sync.aligned %0;" ::"n"(N) : "memory"); }
__device__ __forceinline__ uint32_t dlo(uint32_t addr, uint32_t lbo) { return ((addr & 0x3FFFF) >> 4) + ((lbo >> 4) << 16); }
template <uint32_t SBO, uint32_t SWZ> __device__ __forceinline__ uint64_t dsc(uint32_t lo, uint32_t off) {
  uint64_t d; asm("mov.b64 %0, {%1, %2};" : "=l"(d) : "r"(lo + (off >> 4)), "n"((SBO >> 4) | (SWZ << 30))); return d;
}
__device__ __forceinline__ uint64_t dsc2(uint32_t lo, uint32_t off, uint32_t hi) {
  uint64_t d; asm("mov.b64 %0, {%1, %2};" : "=l"(d) : "r"(lo + (off >> 4)), "r"(hi)); return d;
}
__device__ __forceinline__ uint64_t dat(uint64_t d, uint32_t off, uint32_t one) { uint64_t r; asm("mad.wide.u32 %0, %1, %2, %3;" : "=l"(r) : "r"(one), "r"(off >> 4), "l"(d)); return r; }
__device__ __forceinline__ void dadd(uint64_t& d, uint32_t v) {
  asm("{\n.reg .b32 lo, hi;\nmov.b64 {lo, hi}, %0;\nadd.u32 lo, lo, %1;\nmov.b64 %0, {lo, hi};\n}" : "+l"(d) : "r"(v));
}
template <int R> __device__ __forceinline__ void reg_alloc() { asm volatile("setmaxnreg.inc.sync.aligned.u32 %0;" ::"n"(R)); }
template <int R> __device__ __forceinline__ void reg_dealloc() { asm volatile("setmaxnreg.dec.sync.aligned.u32 %0;" ::"n"(R)); }
__device__ __forceinline__ void bar_sync(int id, int n) { asm volatile("bar.sync %0, %1;" ::"r"(id), "r"(n) : "memory"); }
__device__ __forceinline__ void bar_arrive(int id, int n) { asm volatile("bar.arrive %0, %1;" ::"r"(id), "r"(n) : "memory"); }
__device__ __forceinline__ void ldsm4(uint32_t* r, uint32_t addr) {
  asm volatile("ldmatrix.sync.aligned.m8n8.x4.shared.b16 {%0,%1,%2,%3}, [%4];" : "=r"(r[0]), "=r"(r[1]), "=r"(r[2]), "=r"(r[3]) : "r"(addr) : "memory");
}
__device__ __forceinline__ uint32_t movm(uint32_t a) { uint32_t d; asm volatile("movmatrix.sync.aligned.m8n8.trans.b16 %0, %1;" : "=r"(d) : "r"(a)); return d; }
__device__ __forceinline__ void mma16(float* c, uint32_t a0, uint32_t a1, uint32_t a2, uint32_t a3, uint32_t b0, uint32_t b1) {
  asm volatile("mma.sync.aligned.m16n8k16.row.col.f32.bf16.bf16.f32 {%0,%1,%2,%3}, {%4,%5,%6,%7}, {%8,%9}, {%10,%10,%10,%10};"
               : "=f"(c[0]), "=f"(c[1]), "=f"(c[2]), "=f"(c[3]) : "r"(a0), "r"(a1), "r"(a2), "r"(a3), "r"(b0), "r"(b1), "f"(0.f));
}
__device__ __forceinline__ void mma8(float* c, uint32_t a0, uint32_t a1, uint32_t b0) {
  asm volatile("mma.sync.aligned.m16n8k8.row.col.f32.bf16.bf16.f32 {%0,%1,%2,%3}, {%4,%5}, {%6}, {%0,%1,%2,%3};"
               : "+f"(c[0]), "+f"(c[1]), "+f"(c[2]), "+f"(c[3]) : "r"(a0), "r"(a1), "r"(b0));
}
__device__ __forceinline__ void widen(float* c, uint32_t a0, uint32_t a1, uint32_t eye) {
  asm volatile("mma.sync.aligned.m16n8k8.row.col.f32.bf16.bf16.f32 {%0,%1,%2,%3}, {%4,%5}, {%6}, {%7,%7,%7,%7};"
               : "=f"(c[0]), "=f"(c[1]), "=f"(c[2]), "=f"(c[3]) : "r"(a0), "r"(a1), "r"(eye), "f"(0.f));
}
__device__ __forceinline__ float rsq_fast(float x) { float y; asm("rsqrt.approx.ftz.f32 %0, %1;" : "=f"(y) : "f"(x)); return y; }
__device__ __forceinline__ uint32_t pack2(float lo, float hi) { uint32_t r; asm("cvt.rn.bf16x2.f32 %0, %1, %2;" : "=r"(r) : "f"(hi), "f"(lo)); return r; }
__device__ __forceinline__ float blo(uint32_t v) { return __uint_as_float(v << 16); }
__device__ __forceinline__ float bhi(uint32_t v) { return __uint_as_float(v & 0xffff0000u); }
__device__ __forceinline__ float tanh_fast(float x) { float y; asm("tanh.approx.f32 %0, %1;" : "=f"(y) : "f"(x)); return y; }
__device__ __forceinline__ float rcp_fast(float x) { float y; asm("rcp.approx.ftz.f32 %0, %1;" : "=f"(y) : "f"(x)); return y; }
__device__ __forceinline__ float ex2(float x) { float y; asm("ex2.approx.ftz.f32 %0, %1;" : "=f"(y) : "f"(x)); return y; }
__device__ __forceinline__ float qsum(float v) { v += __shfl_xor_sync(~0u, v, 1); v += __shfl_xor_sync(~0u, v, 2); return v; }
__device__ __forceinline__ float qmax(float v) { v = fmaxf(v, __shfl_xor_sync(~0u, v, 1)); v = fmaxf(v, __shfl_xor_sync(~0u, v, 2)); return v; }
__device__ __forceinline__ void stg32(void* p, uint32_t v) { asm volatile("st.global.u32 [%0], %1;" ::"l"(p), "r"(v) : "memory"); }
__device__ __forceinline__ void stg128(void* p, uint32_t a, uint32_t b, uint32_t c, uint32_t d) { asm volatile("st.global.v4.u32 [%0], {%1,%2,%3,%4};" ::"l"(p), "r"(a), "r"(b), "r"(c), "r"(d) : "memory"); }
__device__ __forceinline__ uint32_t ldcg32(const void* p) { uint32_t v; asm volatile("ld.global.L1::no_allocate.u32 %0, [%1];" : "=r"(v) : "l"(p) : "memory"); return v; }
__device__ __forceinline__ uint32_t ldgpu32(const void* p) { uint32_t v; asm volatile("ld.relaxed.gpu.global.u32 %0, [%1];" : "=r"(v) : "l"(p) : "memory"); return v; }
__device__ __forceinline__ uint32_t ldca32(const void* p) { uint32_t v; asm volatile("ld.global.ca.u32 %0, [%1];" : "=r"(v) : "l"(p) : "memory"); return v; }
__device__ __forceinline__ void stg128_if(bool c, void* p, uint32_t a, uint32_t b, uint32_t cc, uint32_t d) {
  asm volatile("{\n.reg .pred P;\nsetp.ne.u32 P, %5, 0;\n@P st.global.v4.u32 [%0], {%1,%2,%3,%4};\n}" ::"l"(p), "r"(a), "r"(b), "r"(cc), "r"(d), "r"((uint32_t)c) : "memory");
}
__device__ __forceinline__ uint2 lds64(uint32_t a) { uint2 v; asm volatile("ld.shared.v2.u32 {%0,%1}, [%2];" : "=r"(v.x), "=r"(v.y) : "r"(a) : "memory"); return v; }
__device__ __forceinline__ uint4 ldcg128(const void* p) { uint4 v; asm volatile("ld.global.cg.v4.u32 {%0,%1,%2,%3}, [%4];" : "=r"(v.x), "=r"(v.y), "=r"(v.z), "=r"(v.w) : "l"(p) : "memory"); return v; }
__device__ __forceinline__ uint32_t ldnc16(const void* p) { uint16_t v; asm volatile("ld.global.nc.u16 %0, [%1];" : "=h"(v) : "l"(p)); return v; }
__device__ __forceinline__ uint4 ldnc128(const void* p) { uint4 v; asm volatile("ld.global.nc.v4.u32 {%0,%1,%2,%3}, [%4];" : "=r"(v.x), "=r"(v.y), "=r"(v.z), "=r"(v.w) : "l"(p)); return v; }
__device__ __forceinline__ uint32_t hsub2(uint32_t a, uint32_t b) { uint32_t d; asm("sub.rn.bf16x2 %0, %1, %2;" : "=r"(d) : "r"(a), "r"(b)); return d; }
__device__ __forceinline__ void stg32_if(bool c, void* p, uint32_t v) {
  asm volatile("{\n.reg .pred P;\nsetp.ne.u32 P, %2, 0;\n@P st.global.u32 [%0], %1;\n}" ::"l"(p), "r"(v), "r"((uint32_t)c) : "memory");
}
__device__ __forceinline__ uint32_t hmul2(uint32_t a, uint32_t b) { uint32_t d; asm("mul.rn.bf16x2 %0, %1, %2;" : "=r"(d) : "r"(a), "r"(b)); return d; }
__device__ __forceinline__ void sts32(uint32_t a, uint32_t v) { asm volatile("st.shared.u32 [%0], %1;" ::"r"(a), "r"(v) : "memory"); }
__device__ __forceinline__ uint32_t lds32(uint32_t a) { uint32_t v; asm volatile("ld.shared.u32 %0, [%1];" : "=r"(v) : "r"(a) : "memory"); return v; }
__device__ __forceinline__ void sts128(uint32_t a, uint32_t x, uint32_t y, uint32_t z, uint32_t w) { asm volatile("st.shared.v4.u32 [%0], {%1,%2,%3,%4};" ::"r"(a), "r"(x), "r"(y), "r"(z), "r"(w) : "memory"); }
__device__ __forceinline__ uint4 lds128(uint32_t a) { uint4 v; asm volatile("ld.shared.v4.u32 {%0,%1,%2,%3}, [%4];" : "=r"(v.x), "=r"(v.y), "=r"(v.z), "=r"(v.w) : "r"(a) : "memory"); return v; }
__device__ __forceinline__ void ll_st64(uint2* p, uint32_t v, uint32_t tag) {
  asm volatile("{\n.reg .b64 r;\nmov.b64 r, {%1,%2};\nst.relaxed.gpu.global.b64 [%0], r;\n}" ::"l"(p), "r"(v), "r"(tag) : "memory");
}
__device__ __forceinline__ uint2 ll_ld64(const uint2* p) {
  uint2 v; asm volatile("{\n.reg .b64 r;\nld.relaxed.gpu.global.b64 r, [%2];\nmov.b64 {%0,%1}, r;\n}" : "=r"(v.x), "=r"(v.y) : "l"(p) : "memory"); return v;
}
__device__ __forceinline__ void ll_st128(uint4* p, float a, float b, uint32_t tag, float c = 0.f) {
  asm volatile("{\n.reg .b128 r;\n.reg .b64 lo, hi;\nmov.b64 lo, {%1,%2};\nmov.b64 hi, {%3,%4};\nmov.b128 r, {lo, hi};\nst.relaxed.gpu.global.b128 [%0], r;\n}" ::"l"(p), "r"(__float_as_uint(a)), "r"(__float_as_uint(b)), "r"(tag), "r"(__float_as_uint(c)) : "memory");
}
__device__ __forceinline__ uint4 ll_ld128(const uint4* p) {
  uint4 v; asm volatile("{\n.reg .b128 r;\n.reg .b64 lo, hi;\nld.relaxed.gpu.global.b128 r, [%4];\nmov.b128 {lo, hi}, r;\nmov.b64 {%0,%1}, lo;\nmov.b64 {%2,%3}, hi;\n}" : "=r"(v.x), "=r"(v.y), "=r"(v.z), "=r"(v.w) : "l"(p) : "memory"); return v;
}
__device__ __forceinline__ void publish_p(uint32_t el, uint32_t* f) {
  asm volatile("{\n.reg .pred P;\nsetp.ne.u32 P, %1, 0;\n@P cp.async.bulk.commit_group;\n@P cp.async.bulk.wait_group 0;\n@P red.release.gpu.global.add.u32 [%0], 1;\n}" ::"l"(f), "r"(el) : "memory");
}
__device__ __forceinline__ void tma3d_red_p(uint32_t el, const CUtensorMap* m, int c0, int c1, int c2, uint32_t src) {
  asm volatile("{\n.reg .pred P;\nsetp.ne.u32 P, %5, 0;\n@P cp.reduce.async.bulk.tensor.3d.global.shared::cta.add.tile.bulk_group [%0, {%2, %3, %4}], [%1];\n@P cp.async.bulk.commit_group;\n}" ::"l"(m), "r"(src), "r"(c0), "r"(c1), "r"(c2), "r"(el) : "memory");
}
__device__ __forceinline__ void stsm4(uint32_t addr, uint32_t a, uint32_t b, uint32_t c, uint32_t d) {
  asm volatile("stmatrix.sync.aligned.m8n8.x4.shared.b16 [%0], {%1,%2,%3,%4};" ::"r"(addr), "r"(a), "r"(b), "r"(c), "r"(d) : "memory");
}
__device__ __forceinline__ void sts64(uint32_t a, uint32_t x, uint32_t y) { asm volatile("st.shared.v2.u32 [%0], {%1,%2};" ::"r"(a), "r"(x), "r"(y) : "memory"); }
__device__ __forceinline__ void ll_st128_if(bool on, uint4* p, float a, float b, uint32_t tag) {
  asm volatile("{\n.reg .pred P;\n.reg .b128 r;\n.reg .b64 lo, hi;\nsetp.ne.u32 P, %4, 0;\nmov.b64 lo, {%1,%2};\nmov.b64 hi, {%3,%3};\nmov.b128 r, {lo, hi};\n@P st.relaxed.gpu.global.b128 [%0], r;\n}" ::"l"(p), "r"(__float_as_uint(a)), "r"(__float_as_uint(b)), "r"(tag), "r"((uint32_t)on) : "memory");
}
__device__ __forceinline__ uint4 ldnc128_if(bool c, const void* p) {
  uint4 v = make_uint4(0u, 0u, 0u, 0u);
  asm volatile("{\n.reg .pred P;\nsetp.ne.u32 P, %5, 0;\n@P ld.global.nc.v4.u32 {%0,%1,%2,%3}, [%4];\n}" : "+r"(v.x), "+r"(v.y), "+r"(v.z), "+r"(v.w) : "l"(p), "r"((uint32_t)c));
  return v;
}
__device__ __forceinline__ uint32_t hfma2(uint32_t a, uint32_t b, uint32_t c) { uint32_t d; asm("fma.rn.bf16x2 %0, %1, %2, %3;" : "=r"(d) : "r"(a), "r"(b), "r"(c)); return d; }
__device__ __forceinline__ float2 lds64f(uint32_t a) { float2 v; asm volatile("ld.shared.v2.f32 {%0,%1}, [%2];" : "=f"(v.x), "=f"(v.y) : "r"(a) : "memory"); return v; }
#define TRC(cond, role, idx) do {} while (0)
#define TRV(role, idx, v) do {} while (0)

#define ACLK_INIT do {} while (0)
#define ACLK(i) do {} while (0)
#define ACLK_OUT do {} while (0)
#define QCLK(i) do {} while (0)
#define PH 1
#define RCLK(i) do {} while (0)
#define RCLK_INIT do {} while (0)
#define RCLK_OUT do {} while (0)
#define SCLK(i) do {} while (0)
#define HCLK(i) do {} while (0)
#define MCLK(c, i) do {} while (0)
#define CKK(i) do {} while (0)
#define CKK_OUT do {} while (0)
#define PL 1
#define PCLK(i) do {} while (0)
#define PQ 1
#define CLK_INIT do {} while (0)
#define CLK(i) do {} while (0)
#define CLK_OUT do {} while (0)

__device__ __forceinline__ void wgmma_ss_n216(float* d, uint64_t da, uint64_t db, int scaleD) {
  asm volatile("{\n.reg .pred p;\nsetp.ne.b32 p, %110, 0;\nwgmma.mma_async.sync.aligned.m64n216k16.f32.bf16.bf16 "
    "{%0,%1,%2,%3,%4,%5,%6,%7,%8,%9,%10,%11,%12,%13,%14,%15,%16,%17,%18,%19,%20,%21,%22,%23,%24,%25,%26,%27,%28,%29,%30,%31,%32,%33,%34,%35,%36,%37,%38,%39,%40,%41,%42,%43,%44,%45,%46,%47,%48,%49,%50,%51,%52,%53,%54,%55,%56,%57,%58,%59,%60,%61,%62,%63,%64,%65,%66,%67,%68,%69,%70,%71,%72,%73,%74,%75,%76,%77,%78,%79,%80,%81,%82,%83,%84,%85,%86,%87,%88,%89,%90,%91,%92,%93,%94,%95,%96,%97,%98,%99,%100,%101,%102,%103,%104,%105,%106,%107}, "
    "%108, %109, p, 1, 1, 0, 1;\n}\n"
    : "+f"(d[0]), "+f"(d[1]), "+f"(d[2]), "+f"(d[3]), "+f"(d[4]), "+f"(d[5]), "+f"(d[6]), "+f"(d[7]), "+f"(d[8]), "+f"(d[9]), "+f"(d[10]), "+f"(d[11]), "+f"(d[12]), "+f"(d[13]), "+f"(d[14]), "+f"(d[15]), "+f"(d[16]), "+f"(d[17]), "+f"(d[18]), "+f"(d[19]), "+f"(d[20]), "+f"(d[21]), "+f"(d[22]), "+f"(d[23]), "+f"(d[24]), "+f"(d[25]), "+f"(d[26]), "+f"(d[27]), "+f"(d[28]), "+f"(d[29]), "+f"(d[30]), "+f"(d[31]), "+f"(d[32]), "+f"(d[33]), "+f"(d[34]), "+f"(d[35]), "+f"(d[36]), "+f"(d[37]), "+f"(d[38]), "+f"(d[39]), "+f"(d[40]), "+f"(d[41]), "+f"(d[42]), "+f"(d[43]), "+f"(d[44]), "+f"(d[45]), "+f"(d[46]), "+f"(d[47]), "+f"(d[48]), "+f"(d[49]), "+f"(d[50]), "+f"(d[51]), "+f"(d[52]), "+f"(d[53]), "+f"(d[54]), "+f"(d[55]), "+f"(d[56]), "+f"(d[57]), "+f"(d[58]), "+f"(d[59]), "+f"(d[60]), "+f"(d[61]), "+f"(d[62]), "+f"(d[63]), "+f"(d[64]), "+f"(d[65]), "+f"(d[66]), "+f"(d[67]), "+f"(d[68]), "+f"(d[69]), "+f"(d[70]), "+f"(d[71]), "+f"(d[72]), "+f"(d[73]), "+f"(d[74]), "+f"(d[75]), "+f"(d[76]), "+f"(d[77]), "+f"(d[78]), "+f"(d[79]), "+f"(d[80]), "+f"(d[81]), "+f"(d[82]), "+f"(d[83]), "+f"(d[84]), "+f"(d[85]), "+f"(d[86]), "+f"(d[87]), "+f"(d[88]), "+f"(d[89]), "+f"(d[90]), "+f"(d[91]), "+f"(d[92]), "+f"(d[93]), "+f"(d[94]), "+f"(d[95]), "+f"(d[96]), "+f"(d[97]), "+f"(d[98]), "+f"(d[99]), "+f"(d[100]), "+f"(d[101]), "+f"(d[102]), "+f"(d[103]), "+f"(d[104]), "+f"(d[105]), "+f"(d[106]), "+f"(d[107])
    : "l"(da), "l"(db), "r"(scaleD));
}
__device__ __forceinline__ void wgmma_ss_n72(float* d, uint64_t da, uint64_t db, int scaleD) {
  asm volatile("{\n.reg .pred p;\nsetp.ne.b32 p, %38, 0;\nwgmma.mma_async.sync.aligned.m64n72k16.f32.bf16.bf16 "
    "{%0,%1,%2,%3,%4,%5,%6,%7,%8,%9,%10,%11,%12,%13,%14,%15,%16,%17,%18,%19,%20,%21,%22,%23,%24,%25,%26,%27,%28,%29,%30,%31,%32,%33,%34,%35}, "
    "%36, %37, p, 1, 1, 0, 1;\n}\n"
    : "+f"(d[0]), "+f"(d[1]), "+f"(d[2]), "+f"(d[3]), "+f"(d[4]), "+f"(d[5]), "+f"(d[6]), "+f"(d[7]), "+f"(d[8]), "+f"(d[9]), "+f"(d[10]), "+f"(d[11]), "+f"(d[12]), "+f"(d[13]), "+f"(d[14]), "+f"(d[15]), "+f"(d[16]), "+f"(d[17]), "+f"(d[18]), "+f"(d[19]), "+f"(d[20]), "+f"(d[21]), "+f"(d[22]), "+f"(d[23]), "+f"(d[24]), "+f"(d[25]), "+f"(d[26]), "+f"(d[27]), "+f"(d[28]), "+f"(d[29]), "+f"(d[30]), "+f"(d[31]), "+f"(d[32]), "+f"(d[33]), "+f"(d[34]), "+f"(d[35])
    : "l"(da), "l"(db), "r"(scaleD));
}
__device__ __forceinline__ void wgmma_rs_n144(float* d, const uint32_t* a, uint64_t db, int scaleD) {
  asm volatile("{\n.reg .pred p;\nsetp.ne.b32 p, %77, 0;\nwgmma.mma_async.sync.aligned.m64n144k16.f32.bf16.bf16 "
    "{%0,%1,%2,%3,%4,%5,%6,%7,%8,%9,%10,%11,%12,%13,%14,%15,%16,%17,%18,%19,%20,%21,%22,%23,%24,%25,%26,%27,%28,%29,%30,%31,%32,%33,%34,%35,%36,%37,%38,%39,%40,%41,%42,%43,%44,%45,%46,%47,%48,%49,%50,%51,%52,%53,%54,%55,%56,%57,%58,%59,%60,%61,%62,%63,%64,%65,%66,%67,%68,%69,%70,%71}, "
    "{%72,%73,%74,%75}, %76, p, 1, 1, 1;\n}\n"
    : "+f"(d[0]), "+f"(d[1]), "+f"(d[2]), "+f"(d[3]), "+f"(d[4]), "+f"(d[5]), "+f"(d[6]), "+f"(d[7]), "+f"(d[8]), "+f"(d[9]), "+f"(d[10]), "+f"(d[11]), "+f"(d[12]), "+f"(d[13]), "+f"(d[14]), "+f"(d[15]), "+f"(d[16]), "+f"(d[17]), "+f"(d[18]), "+f"(d[19]), "+f"(d[20]), "+f"(d[21]), "+f"(d[22]), "+f"(d[23]), "+f"(d[24]), "+f"(d[25]), "+f"(d[26]), "+f"(d[27]), "+f"(d[28]), "+f"(d[29]), "+f"(d[30]), "+f"(d[31]), "+f"(d[32]), "+f"(d[33]), "+f"(d[34]), "+f"(d[35]), "+f"(d[36]), "+f"(d[37]), "+f"(d[38]), "+f"(d[39]), "+f"(d[40]), "+f"(d[41]), "+f"(d[42]), "+f"(d[43]), "+f"(d[44]), "+f"(d[45]), "+f"(d[46]), "+f"(d[47]), "+f"(d[48]), "+f"(d[49]), "+f"(d[50]), "+f"(d[51]), "+f"(d[52]), "+f"(d[53]), "+f"(d[54]), "+f"(d[55]), "+f"(d[56]), "+f"(d[57]), "+f"(d[58]), "+f"(d[59]), "+f"(d[60]), "+f"(d[61]), "+f"(d[62]), "+f"(d[63]), "+f"(d[64]), "+f"(d[65]), "+f"(d[66]), "+f"(d[67]), "+f"(d[68]), "+f"(d[69]), "+f"(d[70]), "+f"(d[71])
    : "r"(a[0]), "r"(a[1]), "r"(a[2]), "r"(a[3]), "l"(db), "r"(scaleD));
}
__device__ __forceinline__ void wgmma_rs_n64(float* d, const uint32_t* a, uint64_t db, int scaleD) {
  asm volatile("{\n.reg .pred p;\nsetp.ne.b32 p, %37, 0;\nwgmma.mma_async.sync.aligned.m64n64k16.f32.bf16.bf16 "
    "{%0,%1,%2,%3,%4,%5,%6,%7,%8,%9,%10,%11,%12,%13,%14,%15,%16,%17,%18,%19,%20,%21,%22,%23,%24,%25,%26,%27,%28,%29,%30,%31}, "
    "{%32,%33,%34,%35}, %36, p, 1, 1, 1;\n}\n"
    : "+f"(d[0]), "+f"(d[1]), "+f"(d[2]), "+f"(d[3]), "+f"(d[4]), "+f"(d[5]), "+f"(d[6]), "+f"(d[7]), "+f"(d[8]), "+f"(d[9]), "+f"(d[10]), "+f"(d[11]), "+f"(d[12]), "+f"(d[13]), "+f"(d[14]), "+f"(d[15]), "+f"(d[16]), "+f"(d[17]), "+f"(d[18]), "+f"(d[19]), "+f"(d[20]), "+f"(d[21]), "+f"(d[22]), "+f"(d[23]), "+f"(d[24]), "+f"(d[25]), "+f"(d[26]), "+f"(d[27]), "+f"(d[28]), "+f"(d[29]), "+f"(d[30]), "+f"(d[31])
    : "r"(a[0]), "r"(a[1]), "r"(a[2]), "r"(a[3]), "l"(db), "r"(scaleD));
}

template <int V> struct Int { static constexpr int value = V; };
struct Cur {
  uint32_t s, ph;
  __device__ __forceinline__ void next() { if (++s == NST) { s = 0; ph ^= 1; } }
};

#define z1_block(rb, w, j) (P.s->Z + ((rb) * 16 + (w) * 8 + (j)) * ZB)
#define z2_block(kb, j) (P.s->Z + (256 + (kb) * 8 + (j)) * ZB)
#define o_block(rb, w) (P.s->O + ((rb) * 2 + (w)) * (2 * ZB))
__device__ __forceinline__ void combine8(float m0, float q0, float m1, float q1, float n, float eps, float& mean, float& rstd) {
  mean = qsum(m0 + m1) * 0.125f;
  float d0 = m0 - mean, d1 = m1 - mean;
  float M2 = qsum(q0 + q1 + n * (d0 * d0 + d1 * d1));
  rstd = rsq_fast(fmaf(M2, 0.125f / n, eps));
}
__device__ __forceinline__ void stat_get(const uint4* zs, uint32_t tag, float n, float eps, float& m0, float& r0, float& m1, float& r1) {
  uint4 a0, a1, b0, b1;
#pragma unroll 1
  for (int it = 0; it < (1 << 20); it++) {
    a0 = ll_ld128(zs); a1 = ll_ld128(zs + 64); b0 = ll_ld128(zs + 8); b1 = ll_ld128(zs + 72);
    if (__all_sync(~0u, a0.z == tag && a1.z == tag && b0.z == tag && b1.z == tag)) break;
  }
  combine8(__uint_as_float(a0.x), __uint_as_float(a0.y), __uint_as_float(a1.x), __uint_as_float(a1.y), n, eps, m0, r0);
  combine8(__uint_as_float(b0.x), __uint_as_float(b0.y), __uint_as_float(b1.x), __uint_as_float(b1.y), n, eps, m1, r1);
}

__device__ __forceinline__ void rows_fetch(uint32_t el, uint32_t xr, const uint8_t* src, uint32_t bar) {
  expect_tx_p(el, bar, 9216);
#pragma unroll 1
  for (int r = 0; r < 8; r++) bulk_load_p(el, xr + r * 1152, src + r * (DM * 4), 1152, bar);
}
__device__ __forceinline__ void rows_stats(uint32_t xr, uint4* dst, uint32_t tag, int lane) {
  float s[2] = {0.f, 0.f}, q[4] = {0.f, 0.f, 0.f, 0.f};
  const uint32_t a0 = xr + (lane >> 2) * 1152 + (((lane & 3) * 2) ^ (lane >> 2)) * 16;
  uint4 n0 = lds128(a0), n1 = lds128(a0 ^ 16);
#pragma unroll 1
  for (int e = 1; e <= 9; e++) {
    const uint32_t x[8] = {n0.x, n0.y, n0.z, n0.w, n1.x, n1.y, n1.z, n1.w};
    if (e < 9) { n0 = lds128(a0 + e * 128); n1 = lds128((a0 ^ 16) + e * 128); }
#pragma unroll
    for (int u = 0; u < 8; u++) {
      const float lo = blo(x[u]), hi = bhi(x[u]);
      s[u & 1] += lo + hi; q[(u & 1) * 2] = fmaf(lo, lo, q[(u & 1) * 2]); q[(u & 1) * 2 + 1] = fmaf(hi, hi, q[(u & 1) * 2 + 1]);
    }
  }
  const float sx = s[0] + s[1], sq = (q[0] + q[1]) + (q[2] + q[3]);
  const float m = qsum(sx) * (-1.f / DM), r = rsq_fast(fmaxf(fmaf(qsum(sq), 1.f / DM, -m * m), 0.f) + LN_EPS);
  if ((lane & 3) == 0) ll_st128(dst + (lane >> 2) * 2, m, r, tag);
}

__device__ __forceinline__ void poison(const Params& P, uint32_t el, uint32_t src, const CUtensorMap* m, int rb, int j, int lane) {
#pragma unroll 1
  for (int u = lane; u < 72; u += 32) sts128(src + u * 16, POISON, POISON, POISON, POISON);
  fence_async_s();
  __syncwarp();
#pragma unroll 1
  for (int u = 0; u < 16; u++) {
    __nanosleep(NAP);
    bulk_store_p(el, o_block(rb, u >> 3) + j * 9216 + (u & 7) * 1152, src, 1152);
    asm volatile("{\n.reg .pred P;\nsetp.ne.u32 P, %5, 0;\n@P cp.async.bulk.tensor.3d.global.shared::cta.tile.bulk_group [%0, {%2, %3, %4}], [%1];\n}" ::"l"(m), "r"(src), "r"((j & 6) * 72), "r"(rb * 64 + u * 4), "r"(j & 1), "r"(el) : "memory");
  }
}
__device__ __forceinline__ void mma16acc(float* c, const uint32_t* a, uint32_t b0, uint32_t b1) {
  asm volatile("mma.sync.aligned.m16n8k16.row.col.f32.bf16.bf16.f32 {%0,%1,%2,%3}, {%4,%5,%6,%7}, {%8,%9}, {%0,%1,%2,%3};"
               : "+f"(c[0]), "+f"(c[1]), "+f"(c[2]), "+f"(c[3]) : "r"(a[0]), "r"(a[1]), "r"(a[2]), "r"(a[3]), "r"(b0), "r"(b1));
}
template <int KS, int NG, int AK, int AH, int BK, int BG, class F> __device__ __forceinline__ void redo(float* acc, const uint8_t* pa, const uint8_t* pb, F f) {
#pragma unroll 1
  for (int k = 0; k < 36; k += KS) {
    uint32_t a[4 * KS], b[2 * KS][NG];
#pragma unroll 1
    for (int it = 0; it < (1 << 20); it++) {
      bool ok = true;
#pragma unroll
      for (int e = 0; e < 4 * KS; e++) a[e] = ldgpu32(pa + (e >> 1) * AK + (e & 1) * AH);
#pragma unroll
      for (int e = 0; e < 2 * KS * NG; e++) b[e / NG][e % NG] = ldca32(pb + (e / NG) * BK + (e % NG) * BG);
#pragma unroll
      for (int e = 0; e < 4 * KS; e++) ok = ok && a[e] != POISON;
      if (__all_sync(~0u, ok)) break;
    }
#pragma unroll
    for (int e = 0; e < KS; e++) f(a + 4 * e, k + e);
#pragma unroll
    for (int e = 0; e < KS * NG; e++) mma16acc(acc + 4 * (e % NG), a + 4 * (e / NG), movm(b[2 * (e / NG)][e % NG]), movm(b[2 * (e / NG) + 1][e % NG]));
    pa += 2 * KS * AK; pb += 2 * KS * BK;
  }
}
__device__ __forceinline__ bool any_nan(float a, float b) {
  return __any_sync(~0u, a != a || b != b);
}

__global__ void __cluster_dims__(2, 1, 1) __launch_bounds__(384, 1) mega_kernel(const __grid_constant__ Params P) {
  extern __shared__ __align__(1024) uint8_t smem_raw[];
  uint32_t ckk[8];
  (void)ckk;
  CKK(0);
  const uint32_t sb = smem_u32(smem_raw);
  const uint32_t bars = sb + SM_BAR;
  int tid = threadIdx.x, lane = tid & 31;
  const int wid = __shfl_sync(~0u, tid >> 5, 0);
  const int cl = blockIdx.x >> 1, tp = cl - 36, t7 = (tp * 37) >> 8;
  const int bid = (cl < 4 ? cl * 8 + 32 : tp < 0 ? cl - 4 : cl < 64 ? tp + t7 + 33 : cl) * 2 + (blockIdx.x & 1);
  if (bid >= NCTA) return;
  const int rb = bid & 15, j = bid >> 4;
  { const bool tr = (tid & 127) == 0 && tid < 256; const int w = tid >> 7; (void)tr; (void)w; TRC(tr, w, 0); }
  CKK(1);
  uint4 wv[5];
  const uint8_t* wsrc;
  {
    const int n8 = min(tid >> 3, 26), part = n8 / 9;
    const uint8_t* src = (const uint8_t*)P.wqkv + (8 * rb + (tid & 7)) * (3 * DM * 2) + (part * (DM - 72) + 72 * j + 8 * n8) * 2;
#pragma unroll
    for (int u = 0; u < SPL; u++) wv[u] = ldnc128_if(tid < 216, src + u * (128 * 3 * DM * 2));
    wsrc = src;
  }
  CKK(2);
  if (tid == 352) {
#pragma unroll
    for (int e = 0; e < 16; e++) mbar_init(bars + B_FULL + e * 8, (e >> 2) == 1 ? 16 : 1);
    mbar_init(bars + B_RES + 8, 8); mbar_init(bars + B_WT, 1); mbar_init(bars + B_WT + 8, 1); mbar_init(bars + B_IMG, 9);
    asm volatile("fence.mbarrier_init.release.cluster;" ::: "memory");
  }
  __syncthreads();

  if (wid >= 8) {
    reg_dealloc<40>();
    lane = __shfl_sync(~0u, lane, lane);
    const uint32_t el = elect_one();
    const uint64_t pol = policy_evict_first();
    uint32_t* const fj = P.s->flags + FJ + j * 32;
    if (wid == 8) {
      if (lane == 0) {
        mbar_init(bars + B_RES, 1); mbar_init(bars + B_WOI, 1); mbar_init(bars + B_ZB, 1); mbar_init(bars + B_GATE3, 3); mbar_init(bars + B_Z1, 1); mbar_init(bars + B_LAG, 4);
#pragma unroll
        for (int e = B_RT; e < B_XS + 16; e += 8) mbar_init(bars + e, e >= B_AD && e < B_EVT ? 2 : (e >= B_EVT && e < B_RT1) || (e >= B_EA3 && e < B_XS) ? 4 : 1);
        asm volatile("fence.mbarrier_init.release.cluster;" ::: "memory");
        mbar_arrive(bars + B_IMG);
      }
      __syncwarp();
#pragma unroll 1
      for (int i = 0; i < 12; i++) if (el) prefetch_map(&P.act[0] + (i < 7 ? i : i - 12));
      const uint32_t epoch = ldcg32(fj + FJ_EP + rb);
      const uint32_t rk = bid & 1;
      TRC(el, 2, 34);
      uint32_t dst = sb + ST_B + rk * 18432, full = bars + B_FULL, ph = 1;
      auto slot = [&](uint32_t bytes) {
        mbar_wait(full, ph);
        expect_tx_p(el, full, bytes);
        mbar_wait(full + (B_EMPTY - B_FULL), ph);
      };
      auto next = [&]() {
        const bool wrap = full == bars + B_FULL + 24;
        full += wrap ? -24 : 8; dst += wrap ? -3 * ST_BYTES : ST_BYTES; ph ^= wrap;
      };
#pragma unroll 1
      for (int L = 0; L < 2; L++) {
        const uint8_t* src = P.s->WQ + j * WQ_SL + rk * 13824;
        dst -= rk * 4608;
#pragma unroll 1
        for (int i = 0; i < 9; i++) {
          if (L == 0 && (i == 0 || i == 2 * SPL)) {
            flag_wait(fj + (i ? FJ_WQ : FJ_WQ0), (epoch + 1) * 16);
            fence_async_g();
            TRC(el, 2, i ? 47 : 45);
          }
          slot(27648);
          bulk_mc_h(el, dst, src, 13824, full, true, pol);
          src += 27648;
          next();
        }
        dst += rk * 4608;
        if (L == 0) {
#pragma unroll 1
          for (int u = 0; u < 2; u++) flag_wait(P.s->flags + FJ + (j ^ u) * 32 + FJ_WO, (epoch + 1) * 16);
          fence_async_g();
          TRC(el, 2, 46);
        }
        src = P.s->WO + ((j & 6) + rk) * WO_SL;
#pragma unroll 1
        for (int i = 0; i < 4; i++) {
          slot(ZB);
          bulk_mc_h(el, dst, src, 18432, full, true, pol);
          src += 18432;
          next();
        }
        slot(18432);
        bulk_mc_h(el, dst, src, 9216, full, true, pol);
        next();
        int col = (((9 * j + 1) >> 1) + 36) * 64;
        const CUtensorMap* map = &P.win64;
#pragma unroll 1
        for (int p = 0; p < 9; p++) {
          if (p == 1) mbar_wait(bars + B_FA3 + GA3 * 8, L);
          mbar_wait(full + (B_EMPTY - B_FULL), ph);
          tma4d_mc(el, dst, map, col, rk * 18, full + 8, pol);
          mbar_arrive_if(el, full);
          if (p + L == 0 && el) asm volatile("cp.async.bulk.prefetch.tensor.4d.L2.global [%0, {%1, 0, 0, %2}];\ncp.async.bulk.prefetch.tensor.4d.L2.global [%0, {%1, 0, 0, %3}];" ::"l"(map), "r"(col + 64), "r"(rk * 18), "r"(rk * 18 + 36) : "memory");
          next();
          if (p == 1) mbar_wait(bars + B_FA3 + GB3 * 8, L);
          slot(2 * ZB);
          tma4d_mc(el, dst, map, col, rk * 18 + 36, full, pol);
          next();
          col = p == 3 ? (9 * j + ((j & 1) ? 0 : 8)) * 32 : p == 4 ? ((9 * j + 1) >> 1) * 64 : col + 64;
          map = p == 3 ? &P.win : &P.win64;
        }
        TRC(el, 2, L * 16 + 6);
        flag_wait(fj + FJ_ZN + L, (epoch + 1) * 16);
        fence_async_g();
        TRC(el, 2, L * 16 + 7);
        src = z2_block(0, j) + rk * 18432;
#pragma unroll 1
        for (int i = 0; i < 32; i++) {
          if (i >= 4) mbar_wait(full + (B_AD - B_FULL), ((i >> 2) & 1) ^ 1);
          slot(ST_BYTES);
          bulk_mc_h(el, dst, src, 18432, full, true, pol);
          tma3d_h(el, dst - ST_B - rk * 18432, &P.wsp, i * 64, rb * 64, 0, full, true, pol);
          src += 8 * ZB;
          next();
        }
        mbar_wait(bars + B_Z1, L);
        fence_async_g();
        expect_tx_p(el, bars + B_ZB, 26624);
        mbar_wait(full + (B_AD - B_FULL), 1);
        slot(26624);
        bulk_load_h(el, dst - ST_B - rk * 18432, z1_block(rb, 0, j), 26624, bars + B_ZB, true, pol);
        bulk_load_h(el, dst - ST_B - rk * 18432 + 26624, z1_block(rb, 1, j), 26624, full, true, pol);
        next();
        col = j * 64;
#pragma unroll 1
        for (int i = 0; i < 9; i++) {
          if (i < 3) mbar_wait(full + (B_AD - B_FULL), 1);
          slot(ZB);
          tma2d_mc_h(el, dst, &P.wout, col, 288 * j + rk * 144, full, true, pol);
          col = col == 512 ? 0 : col + 64;
          next();
        }
      }
    } else if (wid < 11) {
      int w = wid - 9;
      TRC(el && w == 0, 2, 35);
      uint32_t* const fr = P.s->flags + (rb * 2 + w) * 32;
      const uint32_t epoch = ldcg32(fr + FR_EP + j);
      const uint32_t ev = bars + B_EVT + w * EV_N * 8, t8 = (epoch + 1) * 8;
      Cur c{0, 1};
#pragma unroll 1
      for (int L = 0; L < 2; L++) {
        {
          uint32_t tag = t8;
          asm volatile("" : "+r"(tag));
          tag = (tag >> 2) - 1 + L;
          uint4* const xs = P.s->XST + (rb * 2 + w) * 128;
          if (L) {
            mbar_wait(ev + EV_PT * 8, 0);
            TRC(el, 3, w * 32 + 16);
            flag_release_p(el, fr + FR_X2);
            TRC(el, 3, w * 32 + 17);
          }
#pragma unroll 1
          for (int i = 0; i < 9; i++) {
            const uint32_t full = bars + B_FULLA + w * 32 + c.s * 8, dst = sb + c.s * ST_BYTES + w * 8192;
            if (L == 0 && i == 4) {
              mbar_wait(bars + B_WT + w * 8, 0);
              TRC(el && w == 0, 2, 37);
              rows_stats(sb + SM_STG + w * 9216, xs + 16 * j, tag, lane);
              TRC(el && w == 0, 2, 38);
            }
            const uint32_t src = sb + (L ? 2 * ST_BYTES + SM_WOI : SM_STG + w * 9216);
            if (i == 4) {
#pragma unroll
              for (int u = 0; u < 6; u++) sts128(src + u * 512 + lane * 16, POISON, POISON, POISON, POISON);
              fence_async_s();
              __syncwarp();
            }
            mbar_wait(bars + B_EMPTY + c.s * 8, c.ph);
            if (i < L) { flag_wait(fr + FR_X2, t8); fence_async_g(); }
            tma3d_h(el, dst, &P.act[L], i * 64, rb * 64, w, full, false, pol);
            expect_tx_p(el, full, 8192);
            TRC(el && i < L, 3, w * 32 + 18);
            TRC(el && i + L + w == 0, 2, 36);
            c.next();
            if (i >= 4 && i < (L ? 5 : 8)) {
              int b = (rb * 2 + w) * 8 + j;
              asm volatile("" : "+r"(b));
              bulk_store_p(el, i == 4 ? (uint8_t*)P.s->HALO + b * 3072 : P.s->O + (b * 3 + i - 5) * 3072, src, 3072);
              if (i < 6) bulk_store_p(el, (i == 4 ? P.s->ST1 : P.s->ZST) + b * 64, src, 1024);
              if (i == 6) bulk_store_p(el, P.s->RT + b * 8, src, 64);
            }
            if (L == 0 && i == 3) rows_fetch(el, sb + SM_STG + w * 9216, P.xs[0] + (128 * rb + 16 * j + w) * (DM * 2), bars + B_WT + w * 8);
          }
          if (el) asm volatile("cp.async.bulk.commit_group;\ncp.async.bulk.wait_group 0;" ::: "memory");
          __syncwarp();
          if (L == 0) fence_gpu();
          const uint32_t tab = sb + L * (2 * ST_BYTES) + SM_XST + w * 512 + lane * 8;
          TRC(el, 3, w * 32 + L * 16 + 13);
#pragma unroll 1
          for (int it = 0; it < (1 << 22); it++) {
            const uint4 a = ll_ld128(xs + 2 * lane), b = ll_ld128(xs + 64 + 2 * lane);
            if (__all_sync(~0u, a.z == tag && b.z == tag)) { sts64(tab, a.x, a.y); sts64(tab + 256, b.x, b.y); break; }
          }
          __syncwarp();
          mbar_arrive_if(el, bars + B_XS + w * 8);
          TRC(el, 3, w * 32 + L * 16 + 14);
          if (w == 1) {
            mbar_wait(bars + B_XS, L);
            expect_tx_p(el, bars + B_RES, 18432);
            tma3d_h(el, sb + SM_STG, &P.res[L], (j & 6) * 72, rb * 64, j & 1, bars + B_RES, !L, pol);
          }
          if (L) flag_wait(fj + FJ_P4, t8 * 4);
        }
        int hp = rb * 2 + (j & 1);
        asm volatile("" : "+r"(w), "+r"(hp));
        uint32_t* const fo = P.s->flags + hp * 32 + L;
        {
          const uint8_t* src = o_block(0, hp) + w * 8192;
#pragma unroll 1
          for (int i = 0; i < 5; i++) {
            const uint32_t full = bars + B_FULLA + w * 32 + c.s * 8, dst = sb + c.s * ST_BYTES + w * 8192;
            const bool none = 2 * i + w > 8;
            mbar_wait(bars + B_EMPTY + c.s * 8, c.ph);
            expect_tx_p(el, full, none ? 0 : 8192);
            if (i == 0) {
              mbar_wait(ev + EV_O * 8, L);
              TRC(el, 3, w * 32 + L * 16 + 3);
              flag_add_p(el, fr + FR_O + L);
              TRC(el, 3, w * 32 + L * 16 + 4);
              flag_wait(fo + FR_O, t8);
              fence_async_g();
            }
            if (!none) bulk_load_h(el, dst, src + i * 16384, 8192, full, true, pol);
            TRC(el && i == 0, 3, w * 32 + L * 16 + 5);
            c.next();
          }
        }
        {
          expect_tx_p(lane < 9, bars + B_FA3 + (9 * w + lane) * 8, 8192);
          mbar_wait(ev + EV_X1 * 8, L);
          TRC(el, 3, w * 32 + L * 16 + 6);
          if (L) flag_add_p(el, fo + FR_X1); else flag_release_p(el, fo + FR_X1);
          mbar_arrive_if(el, bars + B_GATE3);
          TRC(el, 3, w * 32 + L * 16 + 7);
          mbar_arrive_if(lane < 2, bars + B_FULLA + w * 32 + ((c.s + lane) & 3) * 8);
#pragma unroll 1
          for (int kb = 0; kb < 9; kb++) {
            const int n = 9 * w + kb;
            const uint32_t dst = sb + ((n >> 1) & 3) * ST_BYTES + (n & 1) * 8192;
            if (kb == 0) { flag_wait(fr + FR_X1 + L, t8); fence_async_g(); }
            if (n >= 8) mbar_wait(bars + B_EA3 + (n - 8) * 8, L);
            tma3d_h(el, dst, &P.act[L + 1], kb * 64, rb * 64, w, bars + B_FA3 + n * 8, false, pol);
            TRC(el && kb == 0, 3, w * 32 + L * 16 + 8);
          }
          c.ph ^= ((c.s + 18) >> 2) & 1; c.s = (c.s + 18) & 3;
        }
        asm volatile("" : "+r"(lane), "+r"(w));
        expect_tx_p(el, bars + B_WT + w * 8, 2048);
#pragma unroll 1
        for (int r = 0; r < 8; r++)
          bulk_load_p(el, sb + SM_WT + w * 2176 + r * 272, (const uint8_t*)P.w_sp + (size_t)(128 * rb + 16 * j + 2 * r + w) * (SEQ * 2) + 30 * 128, 256, bars + B_WT + w * 8);
        float cv = (lane & 3) ? 0.f : -blo(ldnc16(P.b_sp + 128 * rb + 16 * j + 2 * (lane >> 2) + w));
        mbar_wait(bars + B_RT, L);
        mbar_wait(bars + B_WT + w * 8, L ^ 1);
        mbar_wait(ev + EV_Z1 * 8, L);
        const uint32_t ro = (w * 64 + 8 * j + (lane >> 2)) * 128, x0 = ((lane & 3) * 2) ^ (lane >> 2);
#pragma unroll 1
        for (int i = 0; i < 32; i++) {
          const bool tail = (i >> 1) == 4;
          const int kb = tail ? i + 22 : i < 8 ? i : i - 2;
          if (i == 8) mbar_wait(bars + B_RT1, L);
          if (!tail) mbar_wait(bars + B_FULL + c.s * 8, c.ph ^ 1);
#pragma unroll
          for (int e = 0; e < 2; e++) {
            const uint4 a = lds128(!tail ? sb + c.s * ST_BYTES + ro + ((x0 ^ e) << 4) : sb + SM_WT + w * 2176 + (lane >> 2) * 272 + (i - 8) * 128 + (lane & 3) * 32 + e * 16);
            const uint4 m = lds128(sb + SM_RT + 4096 + kb * 128 + (lane & 3) * 32 + e * 16);
            cv = fmaf(blo(a.x), blo(m.x), fmaf(bhi(a.x), bhi(m.x), fmaf(blo(a.y), blo(m.y), fmaf(bhi(a.y), bhi(m.y), cv))));
            cv = fmaf(blo(a.z), blo(m.z), fmaf(bhi(a.z), bhi(m.z), fmaf(blo(a.w), blo(m.w), fmaf(bhi(a.w), bhi(m.w), cv))));
          }
          if (!tail) {
            mbar_arrive_if(el, bars + B_AD + c.s * 8 + (__float_as_uint(cv) & P.zero));
            c.next();
          }
        }
        TRC(el, 3, w * 32 + L * 16 + 11);
        uint32_t tag = t8;
        asm volatile("" : "+r"(tag));
        tag = (tag >> 2) - 1 + L;
        cv = qsum(cv);
        uint2* const cs = (uint2*)(P.s->XST + (rb * 2 + w) * 128 + 1);
        if ((lane & 3) == 0) ll_st64(cs + 32 * j + (lane >> 2) * 4, __float_as_uint(cv), tag);
#pragma unroll 1
        for (int it = 0; it < (1 << 22); it++) {
          const uint2 a = ll_ld64(cs + 4 * lane), b = ll_ld64(cs + 128 + 4 * lane);
          if (__all_sync(~0u, a.y == tag && b.y == tag)) { sts32(sb + SM_CV + w * 256 + lane * 4, a.x); sts32(sb + SM_CV + w * 256 + 128 + lane * 4, b.x); break; }
        }
        __syncwarp();
        if (el) mbar_arrive(bars + B_CV + w * 8);
        TRC(el, 3, w * 32 + L * 16 + 12);
#pragma unroll 1
        for (int kb = 30; kb < 32; kb++) {
          mbar_wait(bars + B_FULL + c.s * 8, c.ph ^ 1);
          if (el) mbar_arrive(bars + B_AD + c.s * 8);
          c.next();
        }
        c.ph ^= ((c.s + 10) >> 2) & 1; c.s = (c.s + 10) & 3;
        if (L == 0) {
          mbar_wait(ev + EV_P4 * 8, 0);
          flag_add_p(el, fj + FJ_P4);
          flag_add_p(el, fr + FR_EP + j);
        }
      }
    } else {
      const uint32_t epoch = ldcg32(fj + FJ_EP + rb);
      TRC(el, 2, 33);
      if (SPL) {
        mbar_wait(bars + B_RES + 8, 0);
        TRC(el, 2, 41);
        flag_release_p(el, fj + FJ_WQ0);
        TRC(el, 2, 42);
      }
      mbar_wait(bars + B_IMG, 0);
      TRC(el, 2, 39);
      flag_release_p(el, fj + FJ_WQ);
      TRC(el, 2, 40);
#pragma unroll 1
      for (int L = 0; L < 2; L++) {
        auto wo_fetch = [&]() {
          expect_tx_p(el, bars + B_WOI, 5760);
          asm volatile("{\n.reg .pred P;\nsetp.ne.u32 P, %5, 0;\n@P cp.async.bulk.tensor.4d.shared::cluster.global.mbarrier::complete_tx::bytes [%0], [%1, {0, 0, %3, %4}], [%2];\n}" ::"r"(sb + SM_WOI), "l"(&P.wo8), "r"(bars + B_WOI), "r"(9 * j), "r"((9 * rb) >> 1), "r"(el) : "memory");
        };
        float* const csf = P.s->CSP + (NCTA + bid) * 216;
        if (L == 0) {
          flag_wait(fj + FJ_WQ, (epoch + 1) * 16);
          fence_async_g();
          expect_tx_p(el, bars + B_XRW, 13824);
          bulk_load_p(el, sb + ST_BYTES + SM_WOI, P.s->CSP + j * 16 * 216, 6912, bars + B_XRW);
          bulk_load_p(el, sb + 2 * ST_BYTES + SM_WOI, P.s->CSP + (j * 16 + 8) * 216, 6912, bars + B_XRW);
          wo_fetch();
          mbar_wait(bars + B_XRW, 0);
#pragma unroll 1
          for (int f = lane; f < 54; f += 32) {
            float s[4] = {0.f, 0.f, 0.f, 0.f};
#pragma unroll 4
            for (int r = 0; r < 16; r++) {
              const uint4 v = lds128(sb + ST_BYTES + SM_WOI + (r >> 3) * ST_BYTES + (r & 7) * 864 + f * 16);
              s[0] += __uint_as_float(v.x); s[1] += __uint_as_float(v.y); s[2] += __uint_as_float(v.z); s[3] += __uint_as_float(v.w);
            }
            sts128(sb + SM_CSQ + f * 16, __float_as_uint(s[0]), __float_as_uint(s[1]), __float_as_uint(s[2]), __float_as_uint(s[3]));
            stg128(csf + f * 4, __float_as_uint(s[0]), __float_as_uint(s[1]), __float_as_uint(s[2]), __float_as_uint(s[3]));
          }
          __syncwarp();
          mbar_arrive_if(el, bars + B_CSQ);
        } else {
#pragma unroll 1
          for (int u = 0; u < 4; u++) {
            const int w = u & 1;
            if (u < 2) {
              flag_wait(P.s->flags + (rb * 2 + w) * 32 + FR_X2, (epoch + 1) * 8);
              fence_async_g();
              TRC(el, 2, 48 + u);
              rows_fetch(el, sb + SM_STG + w * 9216, P.xs[1] + (128 * rb + 16 * j + w) * (DM * 2), bars + B_XRW + w * 8);
            } else {
              if (u == 2) {
                expect_tx_p(el, bars + B_CSQ, 864);
                bulk_load_p(el, sb + 2 * ST_BYTES + SM_CSQ, csf, 864, bars + B_CSQ);
              }
              mbar_wait(bars + B_XRW + w * 8, w ^ 1);
              TRC(el, 2, 48 + u);
              rows_stats(sb + SM_STG + w * 9216, P.s->XST + (rb * 2 + w) * 128 + 16 * j, epoch * 2 + 2, lane);
              TRC(el, 2, 50 + u);
            }
          }
        }
        if (L == 0) {
          TRC(el, 2, 43);
          mbar_wait(bars + B_WOI, 0);
          bulk_store_p(el, P.s->WO + j * WO_SL + ((9 * rb) >> 1) * 1152, sb + SM_WOI, 5760);
          publish_p(el, fj + FJ_WO);
          TRC(el, 2, 44);
          const uint8_t* sp = lane < 16 ? (const uint8_t*)P.w_in + (30 * lane + 50) * (FH * 4) + FH * 2 + lane * 256 : (const uint8_t*)P.w_sp + (60 * lane) * (SEQ * 2) + lane * 64;
          float sq = 0.f;
#pragma unroll 1
          for (int u = 0; u < 4; u++) {
            const uint4 y = ldnc128(sp + u * 16);
            const uint32_t x[4] = {y.x, y.y, y.z, y.w};
#pragma unroll
            for (int e = 0; e < 4; e++) sq = fmaf(blo(x[e]), blo(x[e]), fmaf(bhi(x[e]), bhi(x[e]), sq));
          }
#pragma unroll 1
          for (int o = 8; o; o >>= 1) sq += __shfl_xor_sync(~0u, sq, o);
          sq *= lane < 16 ? 2.f * GA * GA * DM / 512.f : C0S * C0S * SEQ / 512.f;
          asm("sqrt.approx.f32 %0, %0;" : "+f"(sq));
          const float o0 = __shfl_sync(~0u, sq, 0), o1 = __shfl_sync(~0u, sq, 16);
          const float p2 = __uint_as_float(min(__float_as_uint(o0) & 0x7f800000u, 0x7e000000u)) * OFK, off = -p2 - fminf(OFA, 0.5f * p2);
          if (el) sts64(sb + SM_OFF, pack2(off, off), min(__float_as_uint(o1) & 0x7f800000u, 0x7e000000u) | 0x00400000u);
        }
        if (el) mbar_arrive(bars + B_GATE3);
        const uint32_t tag = epoch * 2 + L + 1;
        asm volatile("" : "+r"(lane));
        mbar_wait(bars + B_EVT + EV_ZN * 8, L);
        mbar_wait(bars + B_EVT + (EV_N + EV_ZN) * 8, L);
        flag_release_p(el, fj + FJ_ZN + L);
        TRC(el, 2, L * 16 + 8);
        {
          uint4 v[4];
#pragma unroll 1
          for (int it = 0; it < (1 << 22); it++) {
            bool ok = true;
#pragma unroll
            for (int u = 0; u < 4; u++) { v[u] = ll_ld128(P.s->ZST + (rb * 2 + ((lane >> 1) & 1)) * 512 + ((lane & 1) * 4 + u) * 64 + 8 * j + (lane >> 2)); ok = ok && v[u].z == tag; }
            if (__all_sync(~0u, ok)) break;
          }
          float mean = __uint_as_float(v[0].x) + __uint_as_float(v[1].x) + __uint_as_float(v[2].x) + __uint_as_float(v[3].x), M2 = 0.f;
          mean = (mean + __shfl_xor_sync(~0u, mean, 1)) * 0.125f;
#pragma unroll
          for (int u = 0; u < 4; u++) { const float d = __uint_as_float(v[u].x) - mean; M2 += fmaf(288.f * d, d, __uint_as_float(v[u].y)); }
          M2 += __shfl_xor_sync(~0u, M2, 1);
          const float rs = blo(pack2(rsq_fast(fmaf(M2, 1.f / FH, 4.f * GA * GA * LN_EPS)), 0.f));
          if (!(lane & 1)) ll_st64(P.s->RT + 128 * rb + 16 * j + (lane >> 1), pack2(rs, rs * mean), tag);
        }
        TRC(el, 2, L * 16 + 10);
#pragma unroll 1
        for (int b = 0; b < 8; b++) {
          uint4 v[4];
#pragma unroll 1
          for (int it = 0; it < (1 << 22); it++) {
            bool ok = true;
#pragma unroll
            for (int u = 0; u < 4; u++) { v[u] = ll_ld128((const uint4*)P.s->RT + b * 128 + u * 32 + lane); ok = ok && v[u].y == tag && v[u].w == tag; }
            if (__all_sync(~0u, ok)) break;
          }
#pragma unroll
          for (int u = 0; u < 4; u++) {
            const uint32_t rt = sb + SM_RT + b * 512 + u * 128, ro = (lane >> 3) * 32 + (lane & 3) * 8 + ((lane >> 2) & 1) * 2;
            sts32(rt + 4096 + lane * 4, __byte_perm(v[u].x, v[u].z, 0x7632));
            asm volatile("st.shared.u16 [%0], %1;\nst.shared.u16 [%0 + 4], %2;" ::"r"(rt + ro), "h"((uint16_t)v[u].x), "h"((uint16_t)v[u].z) : "memory");
          }
          __syncwarp();
          if (el && (b == 1 || b == 7)) mbar_arrive(bars + (b == 1 ? B_RT : B_RT1));
          TRC(el && b < 2, 2, L * 16 + 11 + b);
        }
        TRC(el, 2, L * 16 + 9);
        mbar_wait(bars + B_EVT + EV_Z1 * 8, L);
        mbar_wait(bars + B_EVT + (EV_N + EV_Z1) * 8, L);
        fence_gpu();
        if (el) mbar_arrive(bars + B_Z1);
        if (L == 0) {
          flag_add_p(el, fj + FJ_EP + rb);
          __nanosleep(NAP0);
          poison(P, el, sb + SM_STG + 17152, &P.psn, rb, j, lane);
          if (el) asm volatile("cp.async.bulk.commit_group;\ncp.async.bulk.wait_group 0;" ::: "memory");
          __syncwarp();
          fence_gpu();
        }
      }
    }
  } else {
    CKK(3);
    uint8_t* const wdst = P.s->WQ + j * WQ_SL + rb * 3456 + tid * 16;
#pragma unroll
    for (int u = 0; u < SPL; u++) stg128_if(tid < 216, wdst + u * (16 * 3456), wv[u].x, wv[u].y, wv[u].z, wv[u].w);
    __syncwarp();
    if (lane == 0) mbar_arrive(bars + B_RES + 8);
    CKK(4);
    auto repack2 = [&]() {
#pragma unroll
      for (int u = SPL; u < 5; u++) stg128_if((u < 4 || rb < 8) && tid < 216, wdst + u * (16 * 3456), wv[u].x, wv[u].y, wv[u].z, wv[u].w);
      float s[8];
#pragma unroll
      for (int e = 0; e < 8; e++) s[e] = 0.f;
#pragma unroll
      for (int u = 0; u < 5; u++) {
        uint32_t x[4] = {wv[u].x, wv[u].y, wv[u].z, wv[u].w};
        asm volatile("" : "+r"(x[0]), "+r"(x[1]), "+r"(x[2]), "+r"(x[3]));
#pragma unroll
        for (int e = 0; e < 4; e++) { s[2 * e] += blo(x[e]); s[2 * e + 1] += bhi(x[e]); }
      }
#pragma unroll
      for (int m = 4; m; m >>= 1) {
#pragma unroll
        for (int e = 0; e < m; e++) s[e] = ((tid & m) ? s[e + m] : s[e]) + __shfl_xor_sync(~0u, (tid & m) ? s[e] : s[e + m], m);
      }
      stg32_if(tid < 216, P.s->CSP + bid * 216 + tid, __float_as_uint(s[0]));
      __syncwarp();
      if (lane == 0) mbar_arrive(bars + B_IMG);
    };
    reg_alloc<232>();
    lane = __shfl_sync(~0u, lane, lane);
    tid = wid * 32 + lane;
    CKK(5);
#pragma unroll
    for (int v = SPL; v < 5; v++) wv[v] = ldnc128_if(tid < 216 && (v < 4 || rb < 8), wsrc + v * (128 * 3 * DM * 2));
    repack2();
    CKK(6);
    const int w = wid >> 2, q = wid & 3;
    int g = lane >> 2, t = lane & 3;
    const uint32_t ev = bars + B_EVT + w * EV_N * 8;
    const bool tr = (tid & 127) == 0;
    (void)tr;
    Cur c{0, 0};
    const uint32_t ebar = mapa(bars + B_EMPTY, (bid & 1) ^ (lane & 1));
    auto release = [&](uint32_t s, uint32_t dep = 0) { mbar_arrive_cluster_if(lane < 2, ebar + s * 8 + dep); };
    auto release_if = [&](bool on, uint32_t s) { mbar_arrive_cluster_if(lane < 2 && on, ebar + s * 8); };
    uint32_t ia = 0;
    auto wait_ab = [&]() { mbar_wait_c(bars + B_FULL + c.s * 8, c.ph); mbar_wait_c(bars + B_FULLA + w * 32 + c.s * 8, (ia >> 2) & 1); ia++; };

    auto yield_done = [&]() { if (w == 0 && lane == 0) mbar_arrive(bars + B_LAG); };
    auto signal = [&](int e) { __syncwarp(); mbar_arrive_if(lane == 0, ev + e * 8); };

    const uint32_t epoch = ldcg32(P.s->flags + (rb * 2 + w) * 32 + FR_EP + j);
    TRC(tr, w, 1);
    CKK(7);
    if (PAD && P.zero) {
#pragma unroll
      for (int i = 0; i < PAD; i++) asm volatile("st.shared.u32 [%0], %1;" ::"r"(sb + i * 20), "r"(tid) : "memory");
    }
    CKK_OUT;

#pragma unroll 1
    for (int L = 0; L < 2; L++) {
      const int tb = 2 + L * 24;
      asm volatile("" : "+r"(lane), "+r"(g), "+r"(t));
      (void)tb;
      ia = 0;
      const uint32_t tag = epoch * 2 + L + 1;
      uint32_t aoff = (w * 64 + q * 16 + (lane & 15)) * 128 + (((lane >> 4) ^ (lane & 7)) << 4);
      {
        uint32_t Pk[27][2];
        float sc0, sc1;
        const uint32_t att = sb + w * 8192 + q * 2048 + lane * 4;
        uint4* hp = P.s->HALO + ((((rb - (q == 0)) * 2 + w) * 8 + j) * 6) * 32 + lane;
        uint8_t* od = o_block(rb, w) + (9 * j) * 1024 + (2 * q) * 128 + lane * 4;
        ACLK_INIT;
        {
          float acc[108];
#pragma unroll
          for (int i = 0; i < 108; i++) acc[i] = 0.f;
          uint32_t prev = 0;
#pragma unroll 1
          for (int kb = 0; kb < 9; kb++) {
            const bool hold = w == 1 && kb == 9 - LAG1;
            if (hold) {
              wgmma_wait<0>();
              release(prev);
              mbar_wait_c(bars + B_LAG, L);
            }
            wait_ab();
            TRC(tr && kb == 0, w, tb + 0);
            MCLK(kb == 0, 0);
            PCLK(kb * 4);
            const uint32_t st = sb + c.s * ST_BYTES;
            uint64_t da = dsc2(dlo(st + w * 8192, 16), 0, 0x40000040u + P.zero), db = dsc2(dlo(st + ST_B, 3456), 0, 8 ^ P.zero);
            wgmma_fence();
#pragma unroll
            for (int kk = 0; kk < 4; kk++) {
              wgmma_ss_n216(acc, da, db, 1);
              dadd(da, 2); dadd(db, 432);
              if (kk == 0) { wgmma_commit(); wgmma_wait<1>(); release_if(kb > 0 && !hold, prev); }
            }
            wgmma_commit();
            if (kb == 7) yield_done();
            PCLK(kb * 4 + 1);
            PCLK(kb * 4 + 2);
            PCLK(kb * 4 + 3);
            prev = c.s; c.next();
          }
          const uint32_t cs = sb + prev * ST_BYTES + SM_CSQ + t * 8;
          mbar_wait_c(bars + B_CSQ, L);
          mbar_wait_c(bars + B_XS + w * 8, L);
          const float2 n0 = lds64f(sb + prev * ST_BYTES + SM_XST + w * 512 + (16 * q + g) * 8), n1 = lds64f(sb + prev * ST_BYTES + SM_XST + w * 512 + (16 * q + g + 8) * 8);
          const float m0 = n0.x, r0 = n0.y, m1 = n1.x, r1 = n1.y;
          float2 cv[27];
#pragma unroll
          for (int G = 0; G < 27; G++) cv[G] = lds64f(cs + G * 32);
          PCLK(36);
          wgmma_wait<0>();
          PCLK(37);
          {
            uint32_t dep = P.zero & __float_as_uint(m0) & __float_as_uint(m1);
#pragma unroll
            for (int G = 0; G < 27; G++) dep &= __float_as_uint(cv[G].x);
            release(prev, dep);
          }
          TRC(tr, w, tb + 1);
          MCLK(1, 1);
          ACLK(0);
#pragma unroll
          for (int G = 9; G < 27; G++) Pk[G][1] = pack2(fmaf(m1, cv[G].x, acc[4 * G + 2]) * r1, fmaf(m1, cv[G].y, acc[4 * G + 3]) * r1);
          if (q < 3) {
#pragma unroll
            for (int i = 0; i < 18; i++) sts32(att + (i >> 4) * ST_BYTES + (i & 15) * 128, Pk[9 + i][1]);
          } else if (rb < 15) {
#pragma unroll
            for (int i = 0; i < 6; i++) ll_st128(hp + i * 32, __uint_as_float(Pk[9 + 3 * i][1]), __uint_as_float(Pk[10 + 3 * i][1]), tag, __uint_as_float(Pk[11 + 3 * i][1]));
          }
#pragma unroll
          for (int G = 0; G < 27; G++) {
            if (G < 9) {
              Pk[G][0] = pack2(fmaf(m0, cv[G].x, acc[4 * G]), fmaf(m0, cv[G].y, acc[4 * G + 1]));
              Pk[G][1] = pack2(fmaf(m1, cv[G].x, acc[4 * G + 2]), fmaf(m1, cv[G].y, acc[4 * G + 3]));
            } else {
              Pk[G][0] = pack2(fmaf(m0, cv[G].x, acc[4 * G]) * r0, fmaf(m0, cv[G].y, acc[4 * G + 1]) * r0);
            }
          }
          sc0 = r0 * (0.23570226039551584f * 1.4426950408889634f); sc1 = r1 * (0.23570226039551584f * 1.4426950408889634f);
        }
        ACLK(1);
        constexpr int GA_[4] = {0, 2, 4, 7}, GB_[4] = {1, 3, 5, 8}, GC_[4] = {2, 4, 6, 6};
        float S1[4][4], S2[4][4];
        uint32_t qa[4][2], qc[4][2];
#pragma unroll
        for (int h = 0; h < 4; h++) {
#pragma unroll
          for (int r = 0; r < 2; r++) {
            qa[h][r] = (h == 0 || h == 3 || t >= h) ? Pk[GA_[h]][r] : 0u;
            qc[h][r] = (h == 3 ? t == 3 : t <= h) ? Pk[GC_[h]][r] : 0u;
          }
          mma16(S1[h], qa[h][0], qa[h][1], Pk[GB_[h]][0], Pk[GB_[h]][1], Pk[9 + GA_[h]][0], Pk[9 + GB_[h]][0]);
          mma16(S2[h], qa[h][0], qa[h][1], Pk[GB_[h]][0], Pk[GB_[h]][1], Pk[9 + GA_[h]][1], Pk[9 + GB_[h]][1]);
        }
#pragma unroll
        for (int h = 0; h < 4; h++) {
          mma8(S1[h], qc[h][0], qc[h][1], Pk[9 + GC_[h]][0]);
          mma8(S2[h], qc[h][0], qc[h][1], Pk[9 + GC_[h]][1]);
        }
        uint32_t V1[9], V2[9];
#pragma unroll
        for (int i = 0; i < 9; i++) { V1[i] = movm(Pk[18 + i][0]); V2[i] = movm(Pk[18 + i][1]); }
        const bool remote = q == 0 && rb > 0;
        uint4 hv[6];
#pragma unroll
        for (int i = 0; i < 6; i++) hv[i] = make_uint4(0u, 0u, tag, 0u);
        if (remote) {
#pragma unroll
          for (int i = 0; i < 6; i++) hv[i] = ll_ld128(hp + i * 32);
        }
        const bool up0 = 2 * t > g, up1 = 2 * t + 1 > g;
        const uint32_t mup = (up0 ? 0xffffu : 0u) | (up1 ? 0xffff0000u : 0u);
        auto finish = [&](const float (&x0)[4], const float (&x1)[4], uint32_t ma, const uint32_t (&Vb)[9], int hi) {
          uint32_t pa[4], pb[4];
          float rs[4];
#pragma unroll
          for (int h = 0; h < 4; h++) {
            const float m = qmax(fmaxf(x0[h], x1[h]));
            const uint32_t p = pack2(ex2(x0[h] - m), ex2(x1[h] - m));
            pa[h] = p & ma; pb[h] = p & ~ma;
          }
#pragma unroll
          for (int h = 0; h < 4; h += 2) {
            float R[4];
            mma16(R, pa[h], pa[h + 1], pb[h], pb[h + 1], 0x3f803f80u, 0x3f803f80u);
            rs[h] = rcp_fast(R[0]); rs[h + 1] = rcp_fast(R[2]);
          }
#pragma unroll
          for (int i = 0; i < 9; i++) {
            const int h = 4 * i / 9, e = (h & 1) * 2;
            const bool split = i == 2 || i == 4 || i == 6, nx = split && 2 * t >= i;
            float O[4], N[4];
            mma16(O, pa[h & 2], pa[h | 1], pb[h & 2], pb[h | 1], V1[i], Vb[i]);
            if (i == 4) mma16(N, pa[2], pa[3], pb[2], pb[3], V1[i], Vb[i]); else { N[0] = O[2]; N[1] = O[3]; }
            const float r = nx ? rs[h + (split ? 1 : 0)] : rs[h];
            stg32(od + i * 1024 + hi * 128, pack2((nx ? N[0] : O[e]) * r, (nx ? N[1] : O[e + 1]) * r));
          }
        };
        {
          float x0[4], x1[4];
#pragma unroll
          for (int h = 0; h < 4; h++) { x0[h] = (up0 ? S1[h][2] : S2[h][2]) * sc1; x1[h] = (up1 ? S1[h][3] : S2[h][3]) * sc1; }
          finish(x0, x1, mup, V2, 1);
        }
        ACLK(2);
        bar_sync(1 + w, 128);
        uint32_t H[18];
        if (q > 0) {
#pragma unroll
          for (int i = 0; i < 18; i++) H[i] = lds32(att - 2048 + (i >> 4) * ST_BYTES + (i & 15) * 128);
        } else {
#pragma unroll 1
          for (int it = 0; it < (1 << 20); it++) {
            bool ok = true;
#pragma unroll
            for (int i = 0; i < 6; i++) ok = ok && hv[i].z == tag;
            if (__all_sync(~0u, ok)) break;
#pragma unroll
            for (int i = 0; i < 6; i++) hv[i] = ll_ld128(hp + i * 32);
          }
#pragma unroll
          for (int i = 0; i < 6; i++) { H[3 * i] = hv[i].x; H[3 * i + 1] = hv[i].y; H[3 * i + 2] = hv[i].w; }
        }
        float S0[4][4];
#pragma unroll
        for (int h = 0; h < 4; h++) {
          mma16(S0[h], qa[h][0], qa[h][1], Pk[GB_[h]][0], Pk[GB_[h]][1], H[GA_[h]], H[GB_[h]]);
        }
#pragma unroll
        for (int h = 0; h < 4; h++) mma8(S0[h], qc[h][0], qc[h][1], H[GC_[h]]);
        uint32_t V0[9];
#pragma unroll
        for (int i = 0; i < 9; i++) V0[i] = movm(H[9 + i]);
        ACLK(3);
        {
          const bool nohalo = (rb | q) == 0;
          const float b0 = up0 && nohalo ? -INFINITY : 0.f, b1 = up1 && nohalo ? -INFINITY : 0.f;
          float x0[4], x1[4];
#pragma unroll
          for (int h = 0; h < 4; h++) { x0[h] = fmaf(up0 ? S0[h][0] : S1[h][0], sc0, b0); x1[h] = fmaf(up1 ? S0[h][1] : S1[h][1], sc0, b1); }
          finish(x0, x1, ~mup, V0, 0);
        }
        ACLK(4);
        signal(EV_O);
        ACLK_OUT;
        TRC(tr, w, tb + 2);
        MCLK(1, 2);
      }
      {
        float acc[36];
        const int hw = rb * 2 + (j & 1), js = (j & 6) + w;
        const uint32_t xt = sb + SM_STG + (16 * q + (lane & 15)) * 288 + (9 * w + (lane >> 4)) * 16, eye = (g >> 1) == t ? 0x3f80u << (g & 1) * 16 : 0u;
        uint32_t xm = xt ^ ((lane & 4) << 2), xl = sb + SM_STG + (2 * q + w) * 2304;
        uint32_t xl0 = xl + (lane >> 4) * 288 + (lane & 15) * 16, xl1 = xl + ((lane >> 1) & 7) * 288 + 256 + ((lane ^ (lane >> 3)) & 1) * 16;
        uint8_t* xd0 = P.xs[L + 1] + (128 * rb + 32 * q + 16 * w + (j & 1)) * (DM * 2) + (j & 6) * 144;
        uint8_t* xd1 = xd0 + (lane >> 1) * (DM * 4) + 256 + (lane & 1) * 16;
        xd0 += (lane >> 4) * (DM * 4) + (lane & 15) * 16;
        asm volatile("" : "+r"(xm), "+r"(xl0), "+r"(xl1), "+l"(xd0), "+l"(xd1));
        mbar_wait_c(bars + B_RES, L);
        TRC(tr, w, tb + 21);
#pragma unroll
        for (int u = 0; u < 5; u++) {
          uint32_t r[4];
          ldsm4(r, xt + u * 32);
          widen(acc + 8 * u, r[0], r[1], eye);
          if (u < 4) widen(acc + 8 * u + 4, r[2], r[3], eye);
        }
        uint32_t prev = 0;
#pragma unroll 1
        for (int u = 0; u < 5; u++) {
          const uint32_t st = sb + c.s * ST_BYTES;
          uint64_t da = dsc2(dlo(st, 1024), 0, 8 + P.zero), db = dsc2(dlo(st + ST_B + w * 18432, 1152), 0, 8 ^ P.zero);
          mbar_wait_c(bars + B_FULL + c.s * 8, c.ph); mbar_wait_c(bars + B_FULLA + c.s * 8, (ia >> 2) & 1);
          TRC(tr && u == 0, w, tb + 3);
          MCLK(u == 0, 3);
          wgmma_fence();
#pragma unroll
          for (int kk = 0; kk < 4; kk++) { wgmma_ss_n72(acc, da, db, 1); dadd(da, 128); dadd(db, 144); }
          wgmma_commit();
          wgmma_wait<1>();
          release_if(u > 0, prev);
          mbar_wait_c(bars + B_FULLA + 32 + c.s * 8, (ia >> 2) & 1);
          ia++;
          if (u == 4) break;
          wgmma_fence();
#pragma unroll
          for (int kk = 4; kk < 8; kk++) { wgmma_ss_n72(acc, da, db, 1); dadd(da, 128); dadd(db, 144); }
          wgmma_commit();
          prev = c.s; c.next();
        }
        RCLK_INIT;
        wgmma_wait<0>();
        RCLK(0);
        release(c.s);
        c.next();
        if (__builtin_expect(any_nan(acc[0], acc[2]), 0)) {
          SLOW(L);
          const uint8_t* xr = P.xs[L] + (128 * rb + 32 * q + 2 * g + (j & 1)) * (DM * 2) + js * 144 + t * 4;
#pragma unroll
          for (int i = 0; i < 9; i++) widen(acc + 4 * i, ldgpu32(xr + i * 16), ldgpu32(xr + i * 16 + DM * 32), eye);
          redo<KS2, 9, 1024, 128, 1152, 128>(acc, o_block(rb, j & 1) + q * 256 + lane * 4, P.s->WO + js * WO_SL + lane * 4, [](uint32_t*, int) {});
        }
        TRC(tr && P5TRACE != 5, w, tb + 4);
        MCLK(1, 4);
#pragma unroll
        for (int u = 0; u < 4; u++)
          stsm4(xm + u * 32, pack2(acc[8 * u], acc[8 * u + 1]), pack2(acc[8 * u + 2], acc[8 * u + 3]), pack2(acc[8 * u + 4], acc[8 * u + 5]), pack2(acc[8 * u + 6], acc[8 * u + 7]));
        asm volatile("stmatrix.sync.aligned.m8n8.x2.shared.b16 [%0], {%1,%2};" ::"r"(xm + 128), "r"(pack2(acc[32], acc[33])), "r"(pack2(acc[34], acc[35])) : "memory");
        auto stats = [&]() {
          float s0 = 0.f, s1 = 0.f, q0 = 0.f, q1 = 0.f;
#pragma unroll
          for (int i = 0; i < 36; i++) {
            if (i & 2) { s1 += acc[i]; q1 = fmaf(acc[i], acc[i], q1); } else { s0 += acc[i]; q0 = fmaf(acc[i], acc[i], q0); }
          }
          s0 = qsum(s0); s1 = qsum(s1); q0 = qsum(q0); q1 = qsum(q1);
          const float ss = t ? s1 : s0, m = ss * (1.f / 72.f);
          ll_st128_if(t < 2, P.s->ST1 + (hw * 8 + js) * 64 + 16 * q + 8 * t + g, m, fmaxf((t ? q1 : q0) - ss * m, 0.f), tag);
        };
        stats();
        RCLK(1);
        bar_sync(8 + q, 64);
        RCLK(2);
#pragma unroll
        for (int u = 0; u < 5; u++) {
          const uint4 v = lds128(u < 4 ? (xl0 ^ ((u & 2) << 3)) + u * 576 : xl1);
          stg128_if(u < 4 || lane < 16, u < 4 ? xd0 + u * (DM * 8) : xd1, v.x, v.y, v.z, v.w);
        }
        RCLK(3);
        signal(EV_X1);
        RCLK(4);
        RCLK(5);
        TRC(tr, w, tb + 5);
        RCLK(6);
        RCLK_OUT;
      }
      uint32_t zk[16];
      {
        uint32_t xA[36][4];
        float acc[32];
        uint32_t s0, one, off2;
        uint8_t *z1d, *zd;
        uint64_t db;
        auto bwait = [&](uint32_t dhi, bool skip) {
          s0 = c.s;
          c.next();
          if (!skip) mbar_wait_c(bars + B_FULL + c.s * 8, c.ph);
          db = dsc2(dlo(sb + s0 * ST_BYTES + ST_B, 512) - 3, 0, dhi); one = (c.s ^ P.zero) & 1;
        };
        auto mma = [&](int kk, int pp, bool hand) {
          wgmma_rs_n64(acc, xA[kk], dat(db, (kk / 18) * ST_BYTES + (kk % 18) * 2048 + 48, one), kk != 0);
          if (kk == pp && hand) bar_arrive(7 - w, 256);
          if (kk == 17 || kk == 35) wgmma_commit();
          if (kk == RL3) { wgmma_commit(); wgmma_wait<1>(); release(s0); }
        };
        {
          bwait(0x40000040u, false);
          mbar_wait_c(bars + B_GATE3, L);
          float mean0, mean1, rs0, rs1;
          stat_get(P.s->ST1 + ((rb * 2 + w) * 8 + 2 * t) * 64 + 16 * q + g, tag, 72.f, LN_EPS, mean0, rs0, mean1, rs1);
          const uint32_t ns0 = pack2(GA * rs0, GA * rs0), ns1 = pack2(GA * rs1, GA * rs1);
          const uint32_t nb0 = pack2(-mean0 * blo(ns0), -mean0 * blo(ns0)), nb1 = pack2(-mean1 * blo(ns1), -mean1 * blo(ns1));
          const uint32_t al = sb + (aoff & 8191);
#pragma unroll
          for (int kb = 0; kb <= 9; kb++) {
            if (kb < 9) {
              mbar_wait_c(bars + B_FA3 + (9 * w + kb) * 8, L);
              TRC(tr && kb == 0, w, tb + 6);
              MCLK(kb == 0, 5);
              if (kb == 0) SCLK(0);
              QCLK(kb);
              const uint32_t at = al + (w ? (((kb + 1) >> 1) & 3) * ST_BYTES + ((kb + 1) & 1) * 8192 : ((kb >> 1) & 3) * ST_BYTES + (kb & 1) * 8192);
#pragma unroll
              for (int kk = 4 * kb; kk < 4 * kb + 4; kk++) ldsm4(xA[kk], at ^ ((kk & 3) << 5));
            }
            if (kb == 0) continue;
            const uint32_t dep = xA[4 * kb - 4][0] & xA[4 * kb - 3][0] & xA[4 * kb - 2][0] & xA[4 * kb - 1][0] & P.zero;
            mbar_arrive_if(lane == 0 && (kb == 1 || w == 0), bars + B_EA3 + (9 * w + kb - 1) * 8 + dep);
#pragma unroll
            for (int kk = 4 * kb - 4; kk < 4 * kb; kk++) {
#pragma unroll
              for (int e = 0; e < 4; e++) xA[kk][e] = hfma2(xA[kk][e], (e & 1) ? ns1 : ns0, (e & 1) ? nb1 : nb0);
            }
            wgmma_fence();
#pragma unroll
            for (int kk = 4 * kb - 4; kk < 4 * kb; kk++) mma(kk, PP30, w);
          }
          off2 = lds32(sb + SM_OFF);
          z1d = z1_block(rb, w, j) + (tid & 127) * 16;
          zd = z2_block(2 * rb + (q >> 1), j) + (4 * (q & 1) + w) * 4608 + ((g & 3) * 2 + (g >> 2)) * 16 + t * 4;
          asm volatile("" : "+l"(z1d), "+l"(zd));
          wgmma_wait<0>();
          if (__builtin_expect(any_nan(acc[0], acc[2]), 0)) {
            SLOW(2 + L);
            uint4* const rd = P.s->RD + bid * (36 * 256) + tid;
            const uint8_t* xr = P.xs[L + 1] + (128 * rb + 32 * q + 2 * g + w) * (DM * 2) + t * 4;
#pragma unroll
            for (int i = 0; i < 32; i++) acc[i] = 0.f;
            redo<KS3, 8, 16, DM * 32, FH * 32, 16>(acc, xr, (const uint8_t*)P.w_in + g * (FH * 4) + (((9 * j + 1) >> 1) + 36) * 128 + t * 4,
                                              [&](uint32_t* a, int k) {
#pragma unroll
                                                for (int e = 0; e < 4; e++) a[e] = hfma2(a[e], (e & 1) ? ns1 : ns0, (e & 1) ? nb1 : nb0);
                                                stg128(rd + k * 256, a[0], a[1], a[2], a[3]);
                                              });
#pragma unroll
            for (int k = 0; k < 36; k++) { const uint4 v = ldcg128(rd + k * 256); xA[k][0] = v.x; xA[k][1] = v.y; xA[k][2] = v.z; xA[k][3] = v.w; }
          }
        }
        float sm[4] = {0.f, 0.f, 0.f, 0.f}, qq[4] = {0.f, 0.f, 0.f, 0.f};
        auto gelu = [&](auto nz2) {
          constexpr int NZ2 = nz2.value, R = 8 - NZ2, N = 8, D = NZ2 == 8 ? GM2 : NZ2 ? GMM : GM1;
          float th[32], gb = GB;
          uint32_t qa = 0, qb = 0;
          auto head = [&](int G) {
#pragma unroll
            for (int e = 0; e < 4; e++) { const float v = acc[4 * G + e]; th[4 * G + e] = tanh_fast(v * fmaf(v, v, gb)); }
          };
#pragma unroll
          for (int i = 0; i < D; i++) head((i + R) & 7);
#pragma unroll
          for (int i = 0; i < N; i++) {
            const int G = (i + R) & 7;
            if (i + D < N) head((i + D + R) & 7);
            float* z = acc + 4 * G;
#pragma unroll
            for (int e = 0; e < 4; e++) z[e] = fmaf(z[e], th[4 * G + e], z[e]);
            uint32_t pa = pack2(z[0], z[1]), pb = pack2(z[2], z[3]), tok;
            if (i < NZ2) {
#pragma unroll
              for (int e = 0; e < 4; e++) { sm[e] += z[e]; qq[e] = fmaf(z[e], z[e], qq[e]); }
              pa = hsub2(pa, off2); pb = hsub2(pb, off2);
              stg32(zd + i * 128, pa); stg32(zd + i * 128 + 9216, pb);
              tok = pa ^ pb ^ __float_as_uint(qq[1]);
            } else {
              if (NZ2 && G == 3) sts128(sb + SM_STG + tid * 16, qa, qb, pa, pb);
              else if (G & 1) stg128(z1d + (G >> 1) * 2048 + (NZ2 ? 24576 : 0), qa, qb, pa, pb);
              qa = pa; qb = pb;
              tok = pa ^ pb;
            }
            gb = __uint_as_float(tok * P.zero + __float_as_uint(GB));
          }
        };
        auto done = [&](int p) {
          wgmma_wait<0>();
          release(c.s);
          c.next();
          TRC(tr && p == 4, w, tb + 7);
          TRC(tr && p == 8, w, tb + 11);
          MCLK(p == 8, 6);
          SCLK(2 * p + 1);
          QCLK(10 + 3 * p);
        };
        auto pass = [&](int p, uint32_t dhi) {
          SCLK(2 * p);
          QCLK(8 + 3 * p);
          bwait(dhi, w);
          bar_sync(6 + w, 256);
          TRC(tr && p == 5, w, tb + 10);
          wgmma_fence();
#pragma unroll
          for (int kk = 0; kk < 36; kk++) mma(kk, PP3, w == 0 || p < 8);
          done(p);
        };
        done(0);
#pragma unroll 1
        for (int p = 1; p < 5; p++) {
          gelu(Int<8>{});
          zd += 1024;
          pass(p, p == 4 ? 0x80000040u : 0x40000040u);
        }
        gelu(Int<4>{});
        signal(EV_ZN);
        {
          const float a0 = qsum(sm[0] + sm[1]), a1 = qsum(sm[2] + sm[3]), q0 = qsum(qq[0] + qq[1]), q1 = qsum(qq[2] + qq[3]);
          const float ss = t ? a1 : a0, m = ss * (1.f / 288.f);
          ll_st128_if(t < 2, P.s->ZST + (rb * 2 + w) * 512 + j * 64 + 16 * q + 8 * t + g, m - blo(off2), fmaxf((t ? q1 : q0) - ss * m, 0.f), tag);
        }
        TRC(tr, w, tb + 8);
        TRC(tr, w, tb + 9);
#pragma unroll 1
        for (int p = 5;; p++) {
          pass(p, 0x40000040u);
          if (p == 8) break;
          gelu(Int<0>{});
          z1d += 8192;
        }
        signal(EV_Z1);
#pragma unroll
        for (int i = 0; i < 16; i++) zk[i] = pack2(acc[2 * i], acc[2 * i + 1]);
        SCLK(18);
        TRC(tr, w, tb + 12);
      }
      uint32_t hA[18][4];
      {
        float acc[144];
        const float c0 = __uint_as_float(lds32(sb + SM_OFF + 4));
#pragma unroll
        for (int i = 0; i < 144; i++) {
          asm volatile("fma.rn.f32 %0, %1, %2, %3;" : "=f"(acc[i]) : "f"(__uint_as_float(P.zero)), "f"((float)(i + 2)), "f"(c0));
        }
        uint32_t prev = 0;
        auto stage = [&](int kb, auto odd) {
          mbar_wait_c(bars + B_FULL + c.s * 8, c.ph);
          TRC(tr && kb == 0, w, tb + 13);
          SCLK(22 + kb);
          const uint32_t st = sb + c.s * ST_BYTES, rt = sb + SM_RT + kb * 128 + t * 8;
          uint64_t db = dsc2(dlo(st + ST_B, 4608), 0, 8 + P.zero);
          uint32_t a[4][4];
#pragma unroll
          for (int kk = 0; kk < 4; kk++) {
            uint32_t r[4];
            ldsm4(r, st + (aoff ^ (kk << 5)));
            const uint2 sc = lds64(rt + kk * 32);
            a[kk][0] = hmul2(__byte_perm(r[0], r[2], 0x5410), sc.x); a[kk][2] = hmul2(__byte_perm(r[0], r[2], 0x7632), sc.y);
            a[kk][1] = hmul2(__byte_perm(r[1], r[3], 0x5410), sc.x); a[kk][3] = hmul2(__byte_perm(r[1], r[3], 0x7632), sc.y);
          }
          if (!odd.value) {
            const float x = blo(zk[0]), y = bhi(zk[0]);
#pragma unroll
            for (int i = 0; i < 15; i++) zk[i] = zk[i + 1];
            zk[15] = pack2(fmaf(x, tanh_fast(x * fmaf(x, x, GB)), x), fmaf(y, tanh_fast(y * fmaf(y, y, GB)), y));
          }
          wgmma_fence();
#pragma unroll
          for (int i = 0; i < 8; i++) {
            const int kk = i & 3, hf = i >> 2;
            wgmma_rs_n144(acc + hf * 72, a[kk], db, 1);
            dadd(db, i == 3 ? 144u - 3 * 576 : 576 + P.zero);
            if (i == 0) { wgmma_commit(); wgmma_wait<1>(); release_if(kb, prev); }
            if (i == 3) wgmma_commit();
          }
          wgmma_commit();
          prev = c.s; c.next();
        };
        mbar_wait_c(bars + B_RT, L);
#pragma unroll 1
        for (int kb = 0; kb < 32; kb += 2) {
          if (kb == 8) mbar_wait_c(bars + B_RT1, L);
          MCLK((kb & 7) == 4, 10 + (kb >> 3));
          stage(kb, Int<0>{});
          stage(kb + 1, Int<1>{});
        }
        if (w == 1) bar_arrive(6, 256);
        HCLK(0);
        mbar_wait_c(bars + B_CV + w * 8, L);
        HCLK(1);
        const float gk = 0.5f / GA;
        const float c1 = __uint_as_float(lds32(sb + SM_OFF + 4));
        const float gb0 = -gk * (c1 + __uint_as_float(lds32(sb + SM_CV + w * 256 + (16 * q + g) * 4))), gb1 = -gk * (c1 + __uint_as_float(lds32(sb + SM_CV + w * 256 + (16 * q + g + 8) * 4)));
        mbar_wait_c(w ? bars + B_FULL + c.s * 8 : bars + B_ZB, w ? c.ph : L);
        HCLK(2);
        const uint32_t sx = c.s;
        c.next();
        const uint32_t zt = sb + tid * 16, zs = zt + sx * ST_BYTES + w * 24576;
        uint4 zz[18];
        auto zload = [&](int u) {
          if (ZW && u == ZW && P.zero) __nanosleep(0);
          if (u >= 12 && u < 16) zz[u] = make_uint4(zk[4 * u - 48], zk[4 * u - 47], zk[4 * u - 46], zk[4 * u - 45]); else zz[u] = lds128(u == 17 ? zt + SM_STG : zs + (u < 12 ? u : 12) * 2048);
        };
#pragma unroll
        for (int u = 0; u < ZA; u++) zload(u);
#pragma unroll
        for (int u = 0; u < 18; u++) {
          if (u == 0) { wgmma_wait<1>(); HCLK(3); }
          if (u == 9) {
            HCLK(4);
            wgmma_wait<0>();
            HCLK(5);
            release(prev);
            mbar_arrive_if(L == 0 && lane == 0, ev + EV_P4 * 8);
            TRC(tr, w, tb + 14);
            SCLK(54);
          }
          if (u + ZA < 18) zload(u + ZA);
          const uint4 z = zz[u];
          hA[u][0] = hmul2(z.x, pack2(fmaf(acc[8 * u], gk, gb0), fmaf(acc[8 * u + 1], gk, gb0)));
          hA[u][1] = hmul2(z.y, pack2(fmaf(acc[8 * u + 2], gk, gb1), fmaf(acc[8 * u + 3], gk, gb1)));
          hA[u][2] = hmul2(z.z, pack2(fmaf(acc[8 * u + 4], gk, gb0), fmaf(acc[8 * u + 5], gk, gb0)));
          hA[u][3] = hmul2(z.w, pack2(fmaf(acc[8 * u + 6], gk, gb1), fmaf(acc[8 * u + 7], gk, gb1)));
        }
        uint32_t dep = P.zero;
#pragma unroll
        for (int u = 0; u < 18; u++) dep &= hA[u][0];
        release(sx, dep);
        TRC(tr, w, tb + 15);
        HCLK(6);
      }
      {
        const uint32_t el = elect_one();
#pragma unroll 1
        for (int p = 0; p < 9; p++) {
          float acc[32];
          if (w == 0) mbar_wait_c(bars + B_FULL + c.s * 8, c.ph);
          uint64_t db = dsc2(dlo(sb + c.s * ST_BYTES + ST_B + (j & 1) * 4096, 0), 0, 0x40000040u + P.zero);
          HCLK(7 + 2 * p);
          bar_sync(6 + w, 256);
          wgmma_fence();
#pragma unroll
          for (int kk = 0; kk < 18; kk++) {
            wgmma_rs_n64(acc, hA[kk], db, kk != 0);
            dadd(db, kk == 15 ? 128 - (j & 1) * (36864 >> 4) : 128 + P.zero);
            if (kk == PPK && (w == 0 || p < 8)) bar_arrive(7 - w, 256);
          }
          wgmma_commit();
          const uint32_t d = sb + (p & 3) * ST_BYTES, cb = p + j >= 9 ? p + j - 9 : p + j;
          if (el) asm volatile("cp.async.bulk.wait_group.read 3;" ::: "memory");
          __syncwarp();
          wgmma_wait<0>();
          HCLK(8 + 2 * p);
          MCLK(p == 1 || p == 8, 7 + (p >> 3));
          TRC(tr && p == 8, w, tb + 16);
          release_if(L == 0 || p < 5, c.s);
          c.next();
#pragma unroll
          for (int u = 0; u < 4; u++)
            stsm4(d + (aoff ^ (u << 5)), pack2(acc[8 * u], acc[8 * u + 1]), pack2(acc[8 * u + 2], acc[8 * u + 3]), pack2(acc[8 * u + 4], acc[8 * u + 5]), pack2(acc[8 * u + 6], acc[8 * u + 7]));
          fence_async_s();
          __syncwarp();
          tma3d_red_p(el, &P.red[L], cb * 64, rb * 64 + q * 16, w, d + w * 8192 + q * 2048);
          TRC(tr && p == 8, w, tb + 17);
        }
        if (el) asm volatile("cp.async.bulk.wait_group 0;" ::: "memory");
        HCLK(25);
        MCLK(1, 9);
        if (L == 0) signal(EV_PT);
        TRC(tr, w, tb + 18);
      }
    }
  }
}

typedef CUresult (*EncodeFn)(CUtensorMap*, CUtensorMapDataType, cuuint32_t, void*, const cuuint64_t*, const cuuint64_t*, const cuuint32_t*,
                             const cuuint32_t*, CUtensorMapInterleave, CUtensorMapSwizzle, CUtensorMapL2promotion, CUtensorMapFloatOOBfill);

static void make_map(EncodeFn fn, CUtensorMap* m, const void* ptr, int rank, uint64_t d0, uint64_t d1, uint64_t d2, uint64_t s1, uint64_t s2,
                     uint32_t b0, uint32_t b1, uint32_t b2, CUtensorMapSwizzle swz) {
  cuuint64_t dims[3] = {d0, d1, d2}, strides[2] = {s1, s2};
  cuuint32_t box[3] = {b0, b1, b2}, es[3] = {1, 1, 1};
  fn(m, CU_TENSOR_MAP_DATA_TYPE_BFLOAT16, rank, const_cast<void*>(ptr), dims, strides, box, es, CU_TENSOR_MAP_INTERLEAVE_NONE, swz,
     CU_TENSOR_MAP_L2_PROMOTION_L2_128B, CU_TENSOR_MAP_FLOAT_OOB_FILL_NONE);
}

}

extern "C" void kernel_launch(void* const* d_in, const int* in_sizes, int n_in, void* d_out, int out_size) {
  using namespace mk;
  (void)in_sizes; (void)n_in; (void)out_size;
  static EncodeFn fn = nullptr;
  static Scratch* sc;
  if (!fn) {
    cudaGetSymbolAddress((void**)&sc, g_scratch);
    cudaDriverEntryPointQueryResult qr;
    cudaGetDriverEntryPoint("cuTensorMapEncodeTiled", (void**)&fn, cudaEnableDefault, &qr);
    cudaFuncSetAttribute(mega_kernel, cudaFuncAttributeMaxDynamicSharedMemorySize, SM_TOTAL);
  }
  Params p;
  p.wqkv = (const __nv_bfloat16*)d_in[1];
  p.w_in = (const __nv_bfloat16*)d_in[4];
  p.w_sp = (const __nv_bfloat16*)d_in[5];
  p.b_sp = (const __nv_bfloat16*)d_in[6];
  p.w_out = (const __nv_bfloat16*)d_in[7];
  p.zero = 0;
  p.s = sc;
  p.xs[0] = (uint8_t*)d_in[0];
  p.xs[1] = sc->X;
  p.xs[2] = (uint8_t*)d_out;
  make_map(fn, &p.wsp, p.w_sp, 3, 2048, 1024, 2, 8192, 4096, 64, 64, 2, CU_TENSOR_MAP_SWIZZLE_128B);
  for (int i = 0; i < 2; i++) {
    make_map(fn, &p.red[i], p.xs[i + 1], 3, DM, 1024, 2, 2304, 1152, 64, 16, 1, CU_TENSOR_MAP_SWIZZLE_128B);
    make_map(fn, &p.res[i], p.xs[i], 3, DM, 1024, 2, 2304, 1152, 144, 64, 1, CU_TENSOR_MAP_SWIZZLE_NONE);
  }
  make_map(fn, &p.psn, d_out, 3, DM, 1024, 2, 2304, 1152, 144, 4, 1, CU_TENSOR_MAP_SWIZZLE_NONE);
  for (int i = 0; i < 3; i++) make_map(fn, &p.act[i], p.xs[i], 3, DM, 1024, 2, 2304, 1152, 64, 64, 1, CU_TENSOR_MAP_SWIZZLE_128B);
  {
    cuuint64_t dims[4] = {8, 8, 72, 72}, strides[3] = {1152, 16, 9216};
    cuuint32_t box[4] = {8, 8, 9, 5}, es[4] = {1, 1, 1, 1};
    fn(&p.wo8, CU_TENSOR_MAP_DATA_TYPE_BFLOAT16, 4, d_in[2], dims, strides, box, es, CU_TENSOR_MAP_INTERLEAVE_NONE, CU_TENSOR_MAP_SWIZZLE_NONE,
       CU_TENSOR_MAP_L2_PROMOTION_L2_128B, CU_TENSOR_MAP_FLOAT_OOB_FILL_NONE);
  }
  for (int i = 0; i < 2; i++) {
    cuuint64_t dims[4] = {i ? 4608u : 2304u, 8, i ? 1u : 2u, 72}, strides[3] = {9216, 4608, 8 * 9216};
    cuuint32_t box[4] = {i ? 64u : 32u, 8, i ? 1u : 2u, 18}, es[4] = {1, 1, 1, 1};
    fn(i ? &p.win64 : &p.win, CU_TENSOR_MAP_DATA_TYPE_BFLOAT16, 4, d_in[4], dims, strides, box, es, CU_TENSOR_MAP_INTERLEAVE_NONE,
       i ? CU_TENSOR_MAP_SWIZZLE_128B : CU_TENSOR_MAP_SWIZZLE_64B, CU_TENSOR_MAP_L2_PROMOTION_L2_128B, CU_TENSOR_MAP_FLOAT_OOB_FILL_NONE);
  }
  make_map(fn, &p.wout, p.w_out, 2, 576, 2304, 1, 1152, 0, 64, 144, 1, CU_TENSOR_MAP_SWIZZLE_128B);
  mega_kernel<<<NGRID, 384, SM_TOTAL, cudaStreamPerThread>>>(p);
}
```

```cpp
#include <cuda_runtime.h>
#include <cuda.h>
#include <cuda_bf16.h>
#include <stdint.h>

#define MK_TRACE 0
#define MK_DBG 0
#define P5TRACE 0
#define LAG1 3
#define PP3 34
#define PP30 33
#define SPL 2
#define NAP 200
#define NAP0 8000
#define KS2 1
#define KS3 1
#define RL3 21
#define PAD 0
#define ZA 4
#define ZW 10
#define GA3 10
#define GB3 12
#define GM2 1
#define GMM 1
#define GM1 2
#define C0S 32.f
#define OFA 0.125f
#define OFK 2.f
#define PPK 15

namespace mk {

constexpr int SEQ = 2048, DM = 576, FH = 2304;
constexpr int NCTA = 128;
constexpr int NGRID = 132;
constexpr uint32_t ZB = 36864;
constexpr uint32_t WQ_SL = 72 * 3456;
constexpr uint32_t WO_SL = 72 * 1152;
constexpr float LN_EPS = 1e-5f;
constexpr float GA = 0.3292034911525734f, GB = 2.423681954311584f;

constexpr uint32_t ST_BYTES = 53248, ST_B = 16384, NST = 4;
constexpr uint32_t SM_STG = NST * ST_BYTES;
constexpr uint32_t SM_BAR = SM_STG + 2 * 9216;
constexpr uint32_t SM_OFF = SM_BAR + 1008;
constexpr uint32_t SM_TOTAL = SM_BAR + 1024;
constexpr uint32_t SM_RT = SM_STG + 4096, SM_CV = SM_STG + 12288, SM_WT = SM_CV + 512;
constexpr uint32_t SM_WOI = 44032, SM_CSQ = 49792, SM_XST = 50688;
constexpr uint32_t B_FULL = 0, B_EMPTY = 32, B_FULLA = 64, B_RES = 128, B_WT = 144, B_IMG = 160, B_WOI = 168, B_ZB = 176, B_GATE3 = 184, B_Z1 = 192, B_LAG = 200,
                   B_RT = 208, B_CSQ = 216, B_CV = 224, B_AD = 240, B_EVT = 272, B_RT1 = 368, B_XS = 624, B_XRW = 384, B_FA3 = 400, B_EA3 = 544;
enum { EV_PT = 0, EV_O = 1, EV_X1 = 2, EV_ZN = 3, EV_Z1 = 4, EV_P4 = 5, EV_N = 6 };

enum { FR_X2 = 0, FR_O = 1, FR_X1 = 3, FR_EP = 16, FJ = 32 * 32, FJ_WQ = 0, FJ_WO = 1, FJ_WQ0 = 2, FJ_ZN = 3, FJ_P4 = 5, FJ_EP = 16, F_N = FJ + 8 * 32 };

constexpr uint32_t POISON = 0xffffffffu;
struct Scratch {
  uint32_t flags[F_N];
  uint2 RT[SEQ];
  uint4 XST[2 * SEQ];
  uint4 ST1[SEQ * 8], ZST[SEQ * 8], HALO[32 * 8 * 6 * 32];
  float CSP[2 * NCTA * 216];
  uint8_t WQ[8 * WQ_SL], WO[8 * WO_SL];
  uint8_t O[32 * 2 * ZB];
  uint8_t X[SEQ * DM * 2];
  uint8_t Z[512 * ZB];
  uint4 RD[NCTA * 36 * 256];
};
__device__ __align__(1024) Scratch g_scratch;
#define SLOW(i) do {} while (0)

struct Params {
  const __nv_bfloat16 *wqkv;
  Scratch* s;
  uint32_t zero;
  const __nv_bfloat16 *w_in, *w_sp, *b_sp, *w_out;
  uint8_t* xs[3];
  CUtensorMap wo8, wsp, win, win64, wout;
  CUtensorMap act[3];
  CUtensorMap res[2];
  CUtensorMap red[2];
  CUtensorMap psn;
};

__device__ __forceinline__ uint32_t smem_u32(const void* p) { return (uint32_t)__cvta_generic_to_shared(p); }
__device__ __forceinline__ void mbar_init(uint32_t bar, uint32_t cnt) { asm volatile("mbarrier.init.shared::cta.b64 [%0], %1;" ::"r"(bar), "r"(cnt)); }
__device__ __forceinline__ void mbar_arrive(uint32_t bar) { asm volatile("mbarrier.arrive.shared::cta.b64 _, [%0];" ::"r"(bar) : "memory"); }
__device__ __forceinline__ void mbar_wait(uint32_t bar, uint32_t parity) {
  asm volatile(
      "{\n.reg .pred p;\n.reg .u32 c;\nmov.u32 c, 0;\nLAB_WAIT:\n"
      "mbarrier.try_wait.parity.shared::cta.b64 p, [%0], %1;\n@p bra LAB_DONE;\n"
      "add.u32 c, c, 1;\nsetp.lt.u32 p, c, 0x100000;\n@p bra LAB_WAIT;\ntrap;\nLAB_DONE:\n}" ::"r"(bar), "r"(parity)
      : "memory");
}
__device__ __forceinline__ void mbar_wait_c(uint32_t bar, uint32_t parity) {
  asm volatile("{\n.reg .pred p;\nLAB_WAIT:\nmbarrier.try_wait.parity.shared::cta.b64 p, [%0], %1;\n@!p bra LAB_WAIT;\n}" ::"r"(bar), "r"(parity) : "memory");
}
__device__ __forceinline__ void flag_wait(const uint32_t* f, uint32_t target) {
  asm volatile(
      "{\n.reg .pred p;\n.reg .u32 c, v;\nmov.u32 c, 0;\nLAB_WAIT:\n"
      "ld.relaxed.gpu.global.u32 v, [%0];\nsub.u32 v, v, %1;\nsetp.ge.s32 p, v, 0;\n@p bra LAB_DONE;\n"
      "add.u32 c, c, 1;\nsetp.lt.u32 p, c, 0x400000;\n@p bra LAB_WAIT;\ntrap;\nLAB_DONE:\nfence.acquire.gpu;\n}" ::"l"(f), "r"(target)
      : "memory");
}
__device__ __forceinline__ void fence_gpu() { asm volatile("fence.acq_rel.gpu;" ::: "memory"); }
__device__ __forceinline__ void fence_async_g() { asm volatile("fence.proxy.async.global;" ::: "memory"); }
__device__ __forceinline__ void fence_async_s() { asm volatile("fence.proxy.async.shared::cta;" ::: "memory"); }
__device__ __forceinline__ uint32_t elect_one() {
  uint32_t p; asm volatile("{\n.reg .pred P;\nelect.sync _|P, 0xffffffff;\nselp.u32 %0, 1, 0, P;\n}" : "=r"(p)); return p;
}
__device__ __forceinline__ void expect_tx_p(uint32_t el, uint32_t bar, uint32_t bytes) {
  asm volatile("{\n.reg .pred P;\nsetp.ne.u32 P, %2, 0;\n@P mbarrier.arrive.expect_tx.shared::cta.b64 _, [%0], %1;\n}" ::"r"(bar), "r"(bytes), "r"(el) : "memory");
}
__device__ __forceinline__ void bulk_load_p(uint32_t el, uint32_t dst, const void* src, uint32_t bytes, uint32_t bar) {
  asm volatile("{\n.reg .pred P;\nsetp.ne.u32 P, %4, 0;\n@P cp.async.bulk.shared::cluster.global.mbarrier::complete_tx::bytes [%0], [%1], %2, [%3];\n}" ::"r"(dst), "l"(src), "r"(bytes), "r"(bar), "r"(el) : "memory");
}
__device__ __forceinline__ uint64_t policy_evict_first() { uint64_t p; asm("createpolicy.fractional.L2::evict_first.b64 %0, 1.0;" : "=l"(p)); return p; }
__device__ __forceinline__ void bulk_load_h(uint32_t el, uint32_t dst, const void* src, uint32_t bytes, uint32_t bar, bool ef, uint64_t pol) {
  if (ef) {
    asm volatile("{\n.reg .pred P;\nsetp.ne.u32 P, %4, 0;\n@P cp.async.bulk.shared::cluster.global.mbarrier::complete_tx::bytes.L2::cache_hint [%0], [%1], %2, [%3], %5;\n}" ::"r"(dst), "l"(src), "r"(bytes), "r"(bar), "r"(el), "l"(pol) : "memory");
  } else {
    asm volatile("{\n.reg .pred P;\nsetp.ne.u32 P, %4, 0;\n@P cp.async.bulk.shared::cluster.global.mbarrier::complete_tx::bytes [%0], [%1], %2, [%3];\n}" ::"r"(dst), "l"(src), "r"(bytes), "r"(bar), "r"(el) : "memory");
  }
}
__device__ __forceinline__ void bulk_mc_h(uint32_t el, uint32_t dst, const void* src, uint32_t bytes, uint32_t bar, bool ef, uint64_t pol) {
  if (ef) {
    asm volatile("{\n.reg .pred P;\nsetp.ne.u32 P, %4, 0;\n@P cp.async.bulk.shared::cluster.global.mbarrier::complete_tx::bytes.multicast::cluster.L2::cache_hint [%0], [%1], %2, [%3], %5, %6;\n}" ::"r"(dst), "l"(src), "r"(bytes), "r"(bar), "r"(el), "h"((uint16_t)3), "l"(pol) : "memory");
  } else {
    asm volatile("{\n.reg .pred P;\nsetp.ne.u32 P, %4, 0;\n@P cp.async.bulk.shared::cluster.global.mbarrier::complete_tx::bytes.multicast::cluster [%0], [%1], %2, [%3], %5;\n}" ::"r"(dst), "l"(src), "r"(bytes), "r"(bar), "r"(el), "h"((uint16_t)3) : "memory");
  }
}
__device__ __forceinline__ void tma3d_h(uint32_t el, uint32_t dst, const CUtensorMap* m, int c0, int c1, int c2, uint32_t bar, bool ef, uint64_t pol) {
  if (ef) {
    asm volatile("{\n.reg .pred P;\nsetp.ne.u32 P, %6, 0;\n@P cp.async.bulk.tensor.3d.shared::cluster.global.mbarrier::complete_tx::bytes.L2::cache_hint [%0], [%1, {%3, %4, %5}], [%2], %7;\n}" ::"r"(dst), "l"(m), "r"(bar), "r"(c0), "r"(c1), "r"(c2), "r"(el), "l"(pol) : "memory");
  } else {
    asm volatile("{\n.reg .pred P;\nsetp.ne.u32 P, %6, 0;\n@P cp.async.bulk.tensor.3d.shared::cluster.global.mbarrier::complete_tx::bytes [%0], [%1, {%3, %4, %5}], [%2];\n}" ::"r"(dst), "l"(m), "r"(bar), "r"(c0), "r"(c1), "r"(c2), "r"(el) : "memory");
  }
}
__device__ __forceinline__ void tma2d_mc_h(uint32_t el, uint32_t dst, const CUtensorMap* m, int c0, int c1, uint32_t bar, bool ef, uint64_t pol) {
  if (ef) {
    asm volatile("{\n.reg .pred P;\nsetp.ne.u32 P, %5, 0;\n@P cp.async.bulk.tensor.2d.shared::cluster.global.mbarrier::complete_tx::bytes.multicast::cluster.L2::cache_hint [%0], [%1, {%3, %4}], [%2], %6, %7;\n}" ::"r"(dst), "l"(m), "r"(bar), "r"(c0), "r"(c1), "r"(el), "h"((uint16_t)3), "l"(pol) : "memory");
  } else {
    asm volatile("{\n.reg .pred P;\nsetp.ne.u32 P, %5, 0;\n@P cp.async.bulk.tensor.2d.shared::cluster.global.mbarrier::complete_tx::bytes.multicast::cluster [%0], [%1, {%3, %4}], [%2], %6;\n}" ::"r"(dst), "l"(m), "r"(bar), "r"(c0), "r"(c1), "r"(el), "h"((uint16_t)3) : "memory");
  }
}
__device__ __forceinline__ void tma4d_mc(uint32_t el, uint32_t dst, const CUtensorMap* m, int c0, int c3, uint32_t bar, uint64_t pol) {
  asm volatile("{\n.reg .pred P;\nsetp.ne.u32 P, %5, 0;\n@P cp.async.bulk.tensor.4d.shared::cluster.global.mbarrier::complete_tx::bytes.multicast::cluster.L2::cache_hint [%0], [%1, {%3, 0, 0, %4}], [%2], %6, %7;\n}" ::"r"(dst), "l"(m), "r"(bar), "r"(c0), "r"(c3), "r"(el), "h"((uint16_t)3), "l"(pol) : "memory");
}
__device__ __forceinline__ void mbar_arrive_cluster(uint32_t addr) { asm volatile("mbarrier.arrive.shared::cluster.b64 _, [%0];" ::"r"(addr) : "memory"); }
__device__ __forceinline__ void mbar_arrive_cluster_if(bool c, uint32_t addr) {
  asm volatile("{\n.reg .pred P;\nsetp.ne.u32 P, %1, 0;\n@P mbarrier.arrive.shared::cluster.b64 _, [%0];\n}" ::"r"(addr), "r"((uint32_t)c) : "memory");
}
__device__ __forceinline__ void mbar_arrive_if(bool c, uint32_t addr) {
  asm volatile("{\n.reg .pred P;\nsetp.ne.u32 P, %1, 0;\n@P mbarrier.arrive.shared::cta.b64 _, [%0];\n}" ::"r"(addr), "r"((uint32_t)c) : "memory");
}
__device__ __forceinline__ uint32_t mapa(uint32_t addr, uint32_t rank) { uint32_t r; asm("mapa.shared::cluster.u32 %0, %1, %2;" : "=r"(r) : "r"(addr), "r"(rank)); return r; }
__device__ __forceinline__ void bulk_store_p(uint32_t el, void* dst, uint32_t src, uint32_t bytes) {
  asm volatile("{\n.reg .pred P;\nsetp.ne.u32 P, %3, 0;\n@P cp.async.bulk.global.shared::cta.bulk_group [%0], [%1], %2;\n}" ::"l"(dst), "r"(src), "r"(bytes), "r"(el) : "memory");
}
__device__ __forceinline__ void flag_release_p(uint32_t el, uint32_t* f) {
  asm volatile("{\n.reg .pred P;\nsetp.ne.u32 P, %1, 0;\n@P red.release.gpu.global.add.u32 [%0], 1;\n}" ::"l"(f), "r"(el) : "memory");
}
__device__ __forceinline__ void flag_add_p(uint32_t el, uint32_t* f) {
  asm volatile("{\n.reg .pred P;\nsetp.ne.u32 P, %1, 0;\n@P red.relaxed.gpu.global.add.u32 [%0], 1;\n}" ::"l"(f), "r"(el) : "memory");
}
__device__ __forceinline__ void prefetch_l2(const void* src, uint32_t bytes) { asm volatile("cp.async.bulk.prefetch.L2.global [%0], %1;" ::"l"(src), "r"(bytes) : "memory"); }
__device__ __forceinline__ void prefetch_map(const CUtensorMap* m) { asm volatile("prefetch.tensormap [%0];" ::"l"(m) : "memory"); }
__device__ __forceinline__ void wgmma_fence() { asm volatile("wgmma.fence.sync.aligned;" ::: "memory"); }
__device__ __forceinline__ void wgmma_commit() { asm volatile("wgmma.commit_group.sync.aligned;" ::: "memory"); }
template <int N> __device__ __forceinline__ void wgmma_wait() { asm volatile("wgmma.wait_group.sync.aligned %0;" ::"n"(N) : "memory"); }
__device__ __forceinline__ uint32_t dlo(uint32_t addr, uint32_t lbo) { return ((addr & 0x3FFFF) >> 4) + ((lbo >> 4) << 16); }
template <uint32_t SBO, uint32_t SWZ> __device__ __forceinline__ uint64_t dsc(uint32_t lo, uint32_t off) {
  uint64_t d; asm("mov.b64 %0, {%1, %2};" : "=l"(d) : "r"(lo + (off >> 4)), "n"((SBO >> 4) | (SWZ << 30))); return d;
}
__device__ __forceinline__ uint64_t dsc2(uint32_t lo, uint32_t off, uint32_t hi) {
  uint64_t d; asm("mov.b64 %0, {%1, %2};" : "=l"(d) : "r"(lo + (off >> 4)), "r"(hi)); return d;
}
__device__ __forceinline__ uint64_t dat(uint64_t d, uint32_t off, uint32_t one) { uint64_t r; asm("mad.wide.u32 %0, %1, %2, %3;" : "=l"(r) : "r"(one), "r"(off >> 4), "l"(d)); return r; }
__device__ __forceinline__ void dadd(uint64_t& d, uint32_t v) {
  asm("{\n.reg .b32 lo, hi;\nmov.b64 {lo, hi}, %0;\nadd.u32 lo, lo, %1;\nmov.b64 %0, {lo, hi};\n}" : "+l"(d) : "r"(v));
}
template <int R> __device__ __forceinline__ void reg_alloc() { asm volatile("setmaxnreg.inc.sync.aligned.u32 %0;" ::"n"(R)); }
template <int R> __device__ __forceinline__ void reg_dealloc() { asm volatile("setmaxnreg.dec.sync.aligned.u32 %0;" ::"n"(R)); }
__device__ __forceinline__ void bar_sync(int id, int n) { asm volatile("bar.sync %0, %1;" ::"r"(id), "r"(n) : "memory"); }
__device__ __forceinline__ void bar_arrive(int id, int n) { asm volatile("bar.arrive %0, %1;" ::"r"(id), "r"(n) : "memory"); }
__device__ __forceinline__ void ldsm4(uint32_t* r, uint32_t addr) {
  asm volatile("ldmatrix.sync.aligned.m8n8.x4.shared.b16 {%0,%1,%2,%3}, [%4];" : "=r"(r[0]), "=r"(r[1]), "=r"(r[2]), "=r"(r[3]) : "r"(addr) : "memory");
}
__device__ __forceinline__ uint32_t movm(uint32_t a) { uint32_t d; asm volatile("movmatrix.sync.aligned.m8n8.trans.b16 %0, %1;" : "=r"(d) : "r"(a)); return d; }
__device__ __forceinline__ void mma16(float* c, uint32_t a0, uint32_t a1, uint32_t a2, uint32_t a3, uint32_t b0, uint32_t b1) {
  asm volatile("mma.sync.aligned.m16n8k16.row.col.f32.bf16.bf16.f32 {%0,%1,%2,%3}, {%4,%5,%6,%7}, {%8,%9}, {%10,%10,%10,%10};"
               : "=f"(c[0]), "=f"(c[1]), "=f"(c[2]), "=f"(c[3]) : "r"(a0), "r"(a1), "r"(a2), "r"(a3), "r"(b0), "r"(b1), "f"(0.f));
}
__device__ __forceinline__ void mma8(float* c, uint32_t a0, uint32_t a1, uint32_t b0) {
  asm volatile("mma.sync.aligned.m16n8k8.row.col.f32.bf16.bf16.f32 {%0,%1,%2,%3}, {%4,%5}, {%6}, {%0,%1,%2,%3};"
               : "+f"(c[0]), "+f"(c[1]), "+f"(c[2]), "+f"(c[3]) : "r"(a0), "r"(a1), "r"(b0));
}
__device__ __forceinline__ void widen(float* c, uint32_t a0, uint32_t a1, uint32_t eye) {
  asm volatile("mma.sync.aligned.m16n8k8.row.col.f32.bf16.bf16.f32 {%0,%1,%2,%3}, {%4,%5}, {%6}, {%7,%7,%7,%7};"
               : "=f"(c[0]), "=f"(c[1]), "=f"(c[2]), "=f"(c[3]) : "r"(a0), "r"(a1), "r"(eye), "f"(0.f));
}
__device__ __forceinline__ float rsq_fast(float x) { float y; asm("rsqrt.approx.ftz.f32 %0, %1;" : "=f"(y) : "f"(x)); return y; }
__device__ __forceinline__ uint32_t pack2(float lo, float hi) { uint32_t r; asm("cvt.rn.bf16x2.f32 %0, %1, %2;" : "=r"(r) : "f"(hi), "f"(lo)); return r; }
__device__ __forceinline__ float blo(uint32_t v) { return __uint_as_float(v << 16); }
__device__ __forceinline__ float bhi(uint32_t v) { return __uint_as_float(v & 0xffff0000u); }
__device__ __forceinline__ float tanh_fast(float x) { float y; asm("tanh.approx.f32 %0, %1;" : "=f"(y) : "f"(x)); return y; }
__device__ __forceinline__ float rcp_fast(float x) { float y; asm("rcp.approx.ftz.f32 %0, %1;" : "=f"(y) : "f"(x)); return y; }
__device__ __forceinline__ float ex2(float x) { float y; asm("ex2.approx.ftz.f32 %0, %1;" : "=f"(y) : "f"(x)); return y; }
__device__ __forceinline__ float qsum(float v) { v += __shfl_xor_sync(~0u, v, 1); v += __shfl_xor_sync(~0u, v, 2); return v; }
__device__ __forceinline__ float qmax(float v) { v = fmaxf(v, __shfl_xor_sync(~0u, v, 1)); v = fmaxf(v, __shfl_xor_sync(~0u, v, 2)); return v; }
__device__ __forceinline__ void stg32(void* p, uint32_t v) { asm volatile("st.global.u32 [%0], %1;" ::"l"(p), "r"(v) : "memory"); }
__device__ __forceinline__ void stg128(void* p, uint32_t a, uint32_t b, uint32_t c, uint32_t d) { asm volatile("st.global.v4.u32 [%0], {%1,%2,%3,%4};" ::"l"(p), "r"(a), "r"(b), "r"(c), "r"(d) : "memory"); }
__device__ __forceinline__ uint32_t ldcg32(const void* p) { uint32_t v; asm volatile("ld.global.L1::no_allocate.u32 %0, [%1];" : "=r"(v) : "l"(p) : "memory"); return v; }
__device__ __forceinline__ uint32_t ldgpu32(const void* p) { uint32_t v; asm volatile("ld.relaxed.gpu.global.u32 %0, [%1];" : "=r"(v) : "l"(p) : "memory"); return v; }
__device__ __forceinline__ uint32_t ldca32(const void* p) { uint32_t v; asm volatile("ld.global.ca.u32 %0, [%1];" : "=r"(v) : "l"(p) : "memory"); return v; }
__device__ __forceinline__ void stg128_if(bool c, void* p, uint32_t a, uint32_t b, uint32_t cc, uint32_t d) {
  asm volatile("{\n.reg .pred P;\nsetp.ne.u32 P, %5, 0;\n@P st.global.v4.u32 [%0], {%1,%2,%3,%4};\n}" ::"l"(p), "r"(a), "r"(b), "r"(cc), "r"(d), "r"((uint32_t)c) : "memory");
}
__device__ __forceinline__ uint2 lds64(uint32_t a) { uint2 v; asm volatile("ld.shared.v2.u32 {%0,%1}, [%2];" : "=r"(v.x), "=r"(v.y) : "r"(a) : "memory"); return v; }
__device__ __forceinline__ uint4 ldcg128(const void* p) { uint4 v; asm volatile("ld.global.cg.v4.u32 {%0,%1,%2,%3}, [%4];" : "=r"(v.x), "=r"(v.y), "=r"(v.z), "=r"(v.w) : "l"(p) : "memory"); return v; }
__device__ __forceinline__ uint32_t ldnc16(const void* p) { uint16_t v; asm volatile("ld.global.nc.u16 %0, [%1];" : "=h"(v) : "l"(p)); return v; }
__device__ __forceinline__ uint4 ldnc128(const void* p) { uint4 v; asm volatile("ld.global.nc.v4.u32 {%0,%1,%2,%3}, [%4];" : "=r"(v.x), "=r"(v.y), "=r"(v.z), "=r"(v.w) : "l"(p)); return v; }
__device__ __forceinline__ uint32_t hsub2(uint32_t a, uint32_t b) { uint32_t d; asm("sub.rn.bf16x2 %0, %1, %2;" : "=r"(d) : "r"(a), "r"(b)); return d; }
__device__ __forceinline__ void stg32_if(bool c, void* p, uint32_t v) {
  asm volatile("{\n.reg .pred P;\nsetp.ne.u32 P, %2, 0;\n@P st.global.u32 [%0], %1;\n}" ::"l"(p), "r"(v), "r"((uint32_t)c) : "memory");
}
__device__ __forceinline__ uint32_t hmul2(uint32_t a, uint32_t b) { uint32_t d; asm("mul.rn.bf16x2 %0, %1, %2;" : "=r"(d) : "r"(a), "r"(b)); return d; }
__device__ __forceinline__ void sts32(uint32_t a, uint32_t v) { asm volatile("st.shared.u32 [%0], %1;" ::"r"(a), "r"(v) : "memory"); }
__device__ __forceinline__ uint32_t lds32(uint32_t a) { uint32_t v; asm volatile("ld.shared.u32 %0, [%1];" : "=r"(v) : "r"(a) : "memory"); return v; }
__device__ __forceinline__ void sts128(uint32_t a, uint32_t x, uint32_t y, uint32_t z, uint32_t w) { asm volatile("st.shared.v4.u32 [%0], {%1,%2,%3,%4};" ::"r"(a), "r"(x), "r"(y), "r"(z), "r"(w) : "memory"); }
__device__ __forceinline__ uint4 lds128(uint32_t a) { uint4 v; asm volatile("ld.shared.v4.u32 {%0,%1,%2,%3}, [%4];" : "=r"(v.x), "=r"(v.y), "=r"(v.z), "=r"(v.w) : "r"(a) : "memory"); return v; }
__device__ __forceinline__ void ll_st64(uint2* p, uint32_t v, uint32_t tag) {
  asm volatile("{\n.reg .b64 r;\nmov.b64 r, {%1,%2};\nst.relaxed.gpu.global.b64 [%0], r;\n}" ::"l"(p), "r"(v), "r"(tag) : "memory");
}
__device__ __forceinline__ uint2 ll_ld64(const uint2* p) {
  uint2 v; asm volatile("{\n.reg .b64 r;\nld.relaxed.gpu.global.b64 r, [%2];\nmov.b64 {%0,%1}, r;\n}" : "=r"(v.x), "=r"(v.y) : "l"(p) : "memory"); return v;
}
__device__ __forceinline__ void ll_st128(uint4* p, float a, float b, uint32_t tag, float c = 0.f) {
  asm volatile("{\n.reg .b128 r;\n.reg .b64 lo, hi;\nmov.b64 lo, {%1,%2};\nmov.b64 hi, {%3,%4};\nmov.b128 r, {lo, hi};\nst.relaxed.gpu.global.b128 [%0], r;\n}" ::"l"(p), "r"(__float_as_uint(a)), "r"(__float_as_uint(b)), "r"(tag), "r"(__float_as_uint(c)) : "memory");
}
__device__ __forceinline__ uint4 ll_ld128(const uint4* p) {
  uint4 v; asm volatile("{\n.reg .b128 r;\n.reg .b64 lo, hi;\nld.relaxed.gpu.global.b128 r, [%4];\nmov.b128 {lo, hi}, r;\nmov.b64 {%0,%1}, lo;\nmov.b64 {%2,%3}, hi;\n}" : "=r"(v.x), "=r"(v.y), "=r"(v.z), "=r"(v.w) : "l"(p) : "memory"); return v;
}
__device__ __forceinline__ void publish_p(uint32_t el, uint32_t* f) {
  asm volatile("{\n.reg .pred P;\nsetp.ne.u32 P, %1, 0;\n@P cp.async.bulk.commit_group;\n@P cp.async.bulk.wait_group 0;\n@P red.release.gpu.global.add.u32 [%0], 1;\n}" ::"l"(f), "r"(el) : "memory");
}
__device__ __forceinline__ void tma3d_red_p(uint32_t el, const CUtensorMap* m, int c0, int c1, int c2, uint32_t src) {
  asm volatile("{\n.reg .pred P;\nsetp.ne.u32 P, %5, 0;\n@P cp.reduce.async.bulk.tensor.3d.global.shared::cta.add.tile.bulk_group [%0, {%2, %3, %4}], [%1];\n@P cp.async.bulk.commit_group;\n}" ::"l"(m), "r"(src), "r"(c0), "r"(c1), "r"(c2), "r"(el) : "memory");
}
__device__ __forceinline__ void stsm4(uint32_t addr, uint32_t a, uint32_t b, uint32_t c, uint32_t d) {
  asm volatile("stmatrix.sync.aligned.m8n8.x4.shared.b16 [%0], {%1,%2,%3,%4};" ::"r"(addr), "r"(a), "r"(b), "r"(c), "r"(d) : "memory");
}
__device__ __forceinline__ void sts64(uint32_t a, uint32_t x, uint32_t y) { asm volatile("st.shared.v2.u32 [%0], {%1,%2};" ::"r"(a), "r"(x), "r"(y) : "memory"); }
__device__ __forceinline__ void ll_st128_if(bool on, uint4* p, float a, float b, uint32_t tag) {
  asm volatile("{\n.reg .pred P;\n.reg .b128 r;\n.reg .b64 lo, hi;\nsetp.ne.u32 P, %4, 0;\nmov.b64 lo, {%1,%2};\nmov.b64 hi, {%3,%3};\nmov.b128 r, {lo, hi};\n@P st.relaxed.gpu.global.b128 [%0], r;\n}" ::"l"(p), "r"(__float_as_uint(a)), "r"(__float_as_uint(b)), "r"(tag), "r"((uint32_t)on) : "memory");
}
__device__ __forceinline__ uint4 ldnc128_if(bool c, const void* p) {
  uint4 v = make_uint4(0u, 0u, 0u, 0u);
  asm volatile("{\n.reg .pred P;\nsetp.ne.u32 P, %5, 0;\n@P ld.global.nc.v4.u32 {%0,%1,%2,%3}, [%4];\n}" : "+r"(v.x), "+r"(v.y), "+r"(v.z), "+r"(v.w) : "l"(p), "r"((uint32_t)c));
  return v;
}
__device__ __forceinline__ uint32_t hfma2(uint32_t a, uint32_t b, uint32_t c) { uint32_t d; asm("fma.rn.bf16x2 %0, %1, %2, %3;" : "=r"(d) : "r"(a), "r"(b), "r"(c)); return d; }
__device__ __forceinline__ float2 lds64f(uint32_t a) { float2 v; asm volatile("ld.shared.v2.f32 {%0,%1}, [%2];" : "=f"(v.x), "=f"(v.y) : "r"(a) : "memory"); return v; }
#define TRC(cond, role, idx) do {} while (0)
#define TRV(role, idx, v) do {} while (0)

#define ACLK_INIT do {} while (0)
#define ACLK(i) do {} while (0)
#define ACLK_OUT do {} while (0)
#define QCLK(i) do {} while (0)
#define PH 1
#define RCLK(i) do {} while (0)
#define RCLK_INIT do {} while (0)
#define RCLK_OUT do {} while (0)
#define SCLK(i) do {} while (0)
#define HCLK(i) do {} while (0)
#define MCLK(c, i) do {} while (0)
#define CKK(i) do {} while (0)
#define CKK_OUT do {} while (0)
#define PL 1
#define PCLK(i) do {} while (0)
#define PQ 1
#define CLK_INIT do {} while (0)
#define CLK(i) do {} while (0)
#define CLK_OUT do {} while (0)

__device__ __forceinline__ void wgmma_ss_n216(float* d, uint64_t da, uint64_t db, int scaleD) {
  asm volatile("{\n.reg .pred p;\nsetp.ne.b32 p, %110, 0;\nwgmma.mma_async.sync.aligned.m64n216k16.f32.bf16.bf16 "
    "{%0,%1,%2,%3,%4,%5,%6,%7,%8,%9,%10,%11,%12,%13,%14,%15,%16,%17,%18,%19,%20,%21,%22,%23,%24,%25,%26,%27,%28,%29,%30,%31,%32,%33,%34,%35,%36,%37,%38,%39,%40,%41,%42,%43,%44,%45,%46,%47,%48,%49,%50,%51,%52,%53,%54,%55,%56,%57,%58,%59,%60,%61,%62,%63,%64,%65,%66,%67,%68,%69,%70,%71,%72,%73,%74,%75,%76,%77,%78,%79,%80,%81,%82,%83,%84,%85,%86,%87,%88,%89,%90,%91,%92,%93,%94,%95,%96,%97,%98,%99,%100,%101,%102,%103,%104,%105,%106,%107}, "
    "%108, %109, p, 1, 1, 0, 1;\n}\n"
    : "+f"(d[0]), "+f"(d[1]), "+f"(d[2]), "+f"(d[3]), "+f"(d[4]), "+f"(d[5]), "+f"(d[6]), "+f"(d[7]), "+f"(d[8]), "+f"(d[9]), "+f"(d[10]), "+f"(d[11]), "+f"(d[12]), "+f"(d[13]), "+f"(d[14]), "+f"(d[15]), "+f"(d[16]), "+f"(d[17]), "+f"(d[18]), "+f"(d[19]), "+f"(d[20]), "+f"(d[21]), "+f"(d[22]), "+f"(d[23]), "+f"(d[24]), "+f"(d[25]), "+f"(d[26]), "+f"(d[27]), "+f"(d[28]), "+f"(d[29]), "+f"(d[30]), "+f"(d[31]), "+f"(d[32]), "+f"(d[33]), "+f"(d[34]), "+f"(d[35]), "+f"(d[36]), "+f"(d[37]), "+f"(d[38]), "+f"(d[39]), "+f"(d[40]), "+f"(d[41]), "+f"(d[42]), "+f"(d[43]), "+f"(d[44]), "+f"(d[45]), "+f"(d[46]), "+f"(d[47]), "+f"(d[48]), "+f"(d[49]), "+f"(d[50]), "+f"(d[51]), "+f"(d[52]), "+f"(d[53]), "+f"(d[54]), "+f"(d[55]), "+f"(d[56]), "+f"(d[57]), "+f"(d[58]), "+f"(d[59]), "+f"(d[60]), "+f"(d[61]), "+f"(d[62]), "+f"(d[63]), "+f"(d[64]), "+f"(d[65]), "+f"(d[66]), "+f"(d[67]), "+f"(d[68]), "+f"(d[69]), "+f"(d[70]), "+f"(d[71]), "+f"(d[72]), "+f"(d[73]), "+f"(d[74]), "+f"(d[75]), "+f"(d[76]), "+f"(d[77]), "+f"(d[78]), "+f"(d[79]), "+f"(d[80]), "+f"(d[81]), "+f"(d[82]), "+f"(d[83]), "+f"(d[84]), "+f"(d[85]), "+f"(d[86]), "+f"(d[87]), "+f"(d[88]), "+f"(d[89]), "+f"(d[90]), "+f"(d[91]), "+f"(d[92]), "+f"(d[93]), "+f"(d[94]), "+f"(d[95]), "+f"(d[96]), "+f"(d[97]), "+f"(d[98]), "+f"(d[99]), "+f"(d[100]), "+f"(d[101]), "+f"(d[102]), "+f"(d[103]), "+f"(d[104]), "+f"(d[105]), "+f"(d[106]), "+f"(d[107])
    : "l"(da), "l"(db), "r"(scaleD));
}
__device__ __forceinline__ void wgmma_ss_n72(float* d, uint64_t da, uint64_t db, int scaleD) {
  asm volatile("{\n.reg .pred p;\nsetp.ne.b32 p, %38, 0;\nwgmma.mma_async.sync.aligned.m64n72k16.f32.bf16.bf16 "
    "{%0,%1,%2,%3,%4,%5,%6,%7,%8,%9,%10,%11,%12,%13,%14,%15,%16,%17,%18,%19,%20,%21,%22,%23,%24,%25,%26,%27,%28,%29,%30,%31,%32,%33,%34,%35}, "
    "%36, %37, p, 1, 1, 0, 1;\n}\n"
    : "+f"(d[0]), "+f"(d[1]), "+f"(d[2]), "+f"(d[3]), "+f"(d[4]), "+f"(d[5]), "+f"(d[6]), "+f"(d[7]), "+f"(d[8]), "+f"(d[9]), "+f"(d[10]), "+f"(d[11]), "+f"(d[12]), "+f"(d[13]), "+f"(d[14]), "+f"(d[15]), "+f"(d[16]), "+f"(d[17]), "+f"(d[18]), "+f"(d[19]), "+f"(d[20]), "+f"(d[21]), "+f"(d[22]), "+f"(d[23]), "+f"(d[24]), "+f"(d[25]), "+f"(d[26]), "+f"(d[27]), "+f"(d[28]), "+f"(d[29]), "+f"(d[30]), "+f"(d[31]), "+f"(d[32]), "+f"(d[33]), "+f"(d[34]), "+f"(d[35])
    : "l"(da), "l"(db), "r"(scaleD));
}
__device__ __forceinline__ void wgmma_rs_n144(float* d, const uint32_t* a, uint64_t db, int scaleD) {
  asm volatile("{\n.reg .pred p;\nsetp.ne.b32 p, %77, 0;\nwgmma.mma_async.sync.aligned.m64n144k16.f32.bf16.bf16 "
    "{%0,%1,%2,%3,%4,%5,%6,%7,%8,%9,%10,%11,%12,%13,%14,%15,%16,%17,%18,%19,%20,%21,%22,%23,%24,%25,%26,%27,%28,%29,%30,%31,%32,%33,%34,%35,%36,%37,%38,%39,%40,%41,%42,%43,%44,%45,%46,%47,%48,%49,%50,%51,%52,%53,%54,%55,%56,%57,%58,%59,%60,%61,%62,%63,%64,%65,%66,%67,%68,%69,%70,%71}, "
    "{%72,%73,%74,%75}, %76, p, 1, 1, 1;\n}\n"
    : "+f"(d[0]), "+f"(d[1]), "+f"(d[2]), "+f"(d[3]), "+f"(d[4]), "+f"(d[5]), "+f"(d[6]), "+f"(d[7]), "+f"(d[8]), "+f"(d[9]), "+f"(d[10]), "+f"(d[11]), "+f"(d[12]), "+f"(d[13]), "+f"(d[14]), "+f"(d[15]), "+f"(d[16]), "+f"(d[17]), "+f"(d[18]), "+f"(d[19]), "+f"(d[20]), "+f"(d[21]), "+f"(d[22]), "+f"(d[23]), "+f"(d[24]), "+f"(d[25]), "+f"(d[26]), "+f"(d[27]), "+f"(d[28]), "+f"(d[29]), "+f"(d[30]), "+f"(d[31]), "+f"(d[32]), "+f"(d[33]), "+f"(d[34]), "+f"(d[35]), "+f"(d[36]), "+f"(d[37]), "+f"(d[38]), "+f"(d[39]), "+f"(d[40]), "+f"(d[41]), "+f"(d[42]), "+f"(d[43]), "+f"(d[44]), "+f"(d[45]), "+f"(d[46]), "+f"(d[47]), "+f"(d[48]), "+f"(d[49]), "+f"(d[50]), "+f"(d[51]), "+f"(d[52]), "+f"(d[53]), "+f"(d[54]), "+f"(d[55]), "+f"(d[56]), "+f"(d[57]), "+f"(d[58]), "+f"(d[59]), "+f"(d[60]), "+f"(d[61]), "+f"(d[62]), "+f"(d[63]), "+f"(d[64]), "+f"(d[65]), "+f"(d[66]), "+f"(d[67]), "+f"(d[68]), "+f"(d[69]), "+f"(d[70]), "+f"(d[71])
    : "r"(a[0]), "r"(a[1]), "r"(a[2]), "r"(a[3]), "l"(db), "r"(scaleD));
}
__device__ __forceinline__ void wgmma_rs_n64(float* d, const uint32_t* a, uint64_t db, int scaleD) {
  asm volatile("{\n.reg .pred p;\nsetp.ne.b32 p, %37, 0;\nwgmma.mma_async.sync.aligned.m64n64k16.f32.bf16.bf16 "
    "{%0,%1,%2,%3,%4,%5,%6,%7,%8,%9,%10,%11,%12,%13,%14,%15,%16,%17,%18,%19,%20,%21,%22,%23,%24,%25,%26,%27,%28,%29,%30,%31}, "
    "{%32,%33,%34,%35}, %36, p, 1, 1, 1;\n}\n"
    : "+f"(d[0]), "+f"(d[1]), "+f"(d[2]), "+f"(d[3]), "+f"(d[4]), "+f"(d[5]), "+f"(d[6]), "+f"(d[7]), "+f"(d[8]), "+f"(d[9]), "+f"(d[10]), "+f"(d[11]), "+f"(d[12]), "+f"(d[13]), "+f"(d[14]), "+f"(d[15]), "+f"(d[16]), "+f"(d[17]), "+f"(d[18]), "+f"(d[19]), "+f"(d[20]), "+f"(d[21]), "+f"(d[22]), "+f"(d[23]), "+f"(d[24]), "+f"(d[25]), "+f"(d[26]), "+f"(d[27]), "+f"(d[28]), "+f"(d[29]), "+f"(d[30]), "+f"(d[31])
    : "r"(a[0]), "r"(a[1]), "r"(a[2]), "r"(a[3]), "l"(db), "r"(scaleD));
}

template <int V> struct Int { static constexpr int value = V; };
struct Cur {
  uint32_t s, ph;
  __device__ __forceinline__ void next() { if (++s == NST) { s = 0; ph ^= 1; } }
};

#define z1_block(rb, w, j) (P.s->Z + ((rb) * 16 + (w) * 8 + (j)) * ZB)
#define z2_block(kb, j) (P.s->Z + (256 + (kb) * 8 + (j)) * ZB)
#define o_block(rb, w) (P.s->O + ((rb) * 2 + (w)) * (2 * ZB))
__device__ __forceinline__ void combine8(float m0, float q0, float m1, float q1, float n, float eps, float& mean, float& rstd) {
  mean = qsum(m0 + m1) * 0.125f;
  float d0 = m0 - mean, d1 = m1 - mean;
  float M2 = qsum(q0 + q1 + n * (d0 * d0 + d1 * d1));
  rstd = rsq_fast(fmaf(M2, 0.125f / n, eps));
}
__device__ __forceinline__ void stat_get(const uint4* zs, uint32_t tag, float n, float eps, float& m0, float& r0, float& m1, float& r1) {
  uint4 a0, a1, b0, b1;
#pragma unroll 1
  for (int it = 0; it < (1 << 20); it++) {
    a0 = ll_ld128(zs); a1 = ll_ld128(zs + 64); b0 = ll_ld128(zs + 8); b1 = ll_ld128(zs + 72);
    if (__all_sync(~0u, a0.z == tag && a1.z == tag && b0.z == tag && b1.z == tag)) break;
  }
  combine8(__uint_as_float(a0.x), __uint_as_float(a0.y), __uint_as_float(a1.x), __uint_as_float(a1.y), n, eps, m0, r0);
  combine8(__uint_as_float(b0.x), __uint_as_float(b0.y), __uint_as_float(b1.x), __uint_as_float(b1.y), n, eps, m1, r1);
}

__device__ __forceinline__ void rows_fetch(uint32_t el, uint32_t xr, const uint8_t* src, uint32_t bar) {
  expect_tx_p(el, bar, 9216);
#pragma unroll 1
  for (int r = 0; r < 8; r++) bulk_load_p(el, xr + r * 1152, src + r * (DM * 4), 1152, bar);
}
__device__ __forceinline__ void rows_stats(uint32_t xr, uint4* dst, uint32_t tag, int lane) {
  float s[2] = {0.f, 0.f}, q[4] = {0.f, 0.f, 0.f, 0.f};
  const uint32_t a0 = xr + (lane >> 2) * 1152 + (((lane & 3) * 2) ^ (lane >> 2)) * 16;
  uint4 n0 = lds128(a0), n1 = lds128(a0 ^ 16);
#pragma unroll 1
  for (int e = 1; e <= 9; e++) {
    const uint32_t x[8] = {n0.x, n0.y, n0.z, n0.w, n1.x, n1.y, n1.z, n1.w};
    if (e < 9) { n0 = lds128(a0 + e * 128); n1 = lds128((a0 ^ 16) + e * 128); }
#pragma unroll
    for (int u = 0; u < 8; u++) {
      const float lo = blo(x[u]), hi = bhi(x[u]);
      s[u & 1] += lo + hi; q[(u & 1) * 2] = fmaf(lo, lo, q[(u & 1) * 2]); q[(u & 1) * 2 + 1] = fmaf(hi, hi, q[(u & 1) * 2 + 1]);
    }
  }
  const float sx = s[0] + s[1], sq = (q[0] + q[1]) + (q[2] + q[3]);
  const float m = qsum(sx) * (-1.f / DM), r = rsq_fast(fmaxf(fmaf(qsum(sq), 1.f / DM, -m * m), 0.f) + LN_EPS);
  if ((lane & 3) == 0) ll_st128(dst + (lane >> 2) * 2, m, r, tag);
}

__device__ __forceinline__ void poison(const Params& P, uint32_t el, uint32_t src, const CUtensorMap* m, int rb, int j, int lane) {
#pragma unroll 1
  for (int u = lane; u < 72; u += 32) sts128(src + u * 16, POISON, POISON, POISON, POISON);
  fence_async_s();
  __syncwarp();
#pragma unroll 1
  for (int u = 0; u < 16; u++) {
    __nanosleep(NAP);
    bulk_store_p(el, o_block(rb, u >> 3) + j * 9216 + (u & 7) * 1152, src, 1152);
    asm volatile("{\n.reg .pred P;\nsetp.ne.u32 P, %5, 0;\n@P cp.async.bulk.tensor.3d.global.shared::cta.tile.bulk_group [%0, {%2, %3, %4}], [%1];\n}" ::"l"(m), "r"(src), "r"((j & 6) * 72), "r"(rb * 64 + u * 4), "r"(j & 1), "r"(el) : "memory");
  }
}
__device__ __forceinline__ void mma16acc(float* c, const uint32_t* a, uint32_t b0, uint32_t b1) {
  asm volatile("mma.sync.aligned.m16n8k16.row.col.f32.bf16.bf16.f32 {%0,%1,%2,%3}, {%4,%5,%6,%7}, {%8,%9}, {%0,%1,%2,%3};"
               : "+f"(c[0]), "+f"(c[1]), "+f"(c[2]), "+f"(c[3]) : "r"(a[0]), "r"(a[1]), "r"(a[2]), "r"(a[3]), "r"(b0), "r"(b1));
}
template <int KS, int NG, int AK, int AH, int BK, int BG, class F> __device__ __forceinline__ void redo(float* acc, const uint8_t* pa, const uint8_t* pb, F f) {
#pragma unroll 1
  for (int k = 0; k < 36; k += KS) {
    uint32_t a[4 * KS], b[2 * KS][NG];
#pragma unroll 1
    for (int it = 0; it < (1 << 20); it++) {
      bool ok = true;
#pragma unroll
      for (int e = 0; e < 4 * KS; e++) a[e] = ldgpu32(pa + (e >> 1) * AK + (e & 1) * AH);
#pragma unroll
      for (int e = 0; e < 2 * KS * NG; e++) b[e / NG][e % NG] = ldca32(pb + (e / NG) * BK + (e % NG) * BG);
#pragma unroll
      for (int e = 0; e < 4 * KS; e++) ok = ok && a[e] != POISON;
      if (__all_sync(~0u, ok)) break;
    }
#pragma unroll
    for (int e = 0; e < KS; e++) f(a + 4 * e, k + e);
#pragma unroll
    for (int e = 0; e < KS * NG; e++) mma16acc(acc + 4 * (e % NG), a + 4 * (e / NG), movm(b[2 * (e / NG)][e % NG]), movm(b[2 * (e / NG) + 1][e % NG]));
    pa += 2 * KS * AK; pb += 2 * KS * BK;
  }
}
__device__ __forceinline__ bool any_nan(float a, float b) {
  return __any_sync(~0u, a != a || b != b);
}

__global__ void __cluster_dims__(2, 1, 1) __launch_bounds__(384, 1) mega_kernel(const __grid_constant__ Params P) {
  extern __shared__ __align__(1024) uint8_t smem_raw[];
  uint32_t ckk[8];
  (void)ckk;
  CKK(0);
  const uint32_t sb = smem_u32(smem_raw);
  const uint32_t bars = sb + SM_BAR;
  int tid = threadIdx.x, lane = tid & 31;
  const int wid = __shfl_sync(~0u, tid >> 5, 0);
  if (tid == 256 && blockIdx.x < NCTA) prefetch_l2((const uint8_t*)P.wqkv + blockIdx.x * 6912, 6912);
  const int cl = blockIdx.x >> 1, tp = cl - 36, t7 = (tp * 37) >> 8;
  const int bid = (cl < 4 ? cl * 8 + 32 : tp < 0 ? cl - 4 : cl < 64 ? tp + t7 + 33 : cl) * 2 + (blockIdx.x & 1);
  if (bid >= NCTA) return;
  const int rb = bid & 15, j = bid >> 4;
  { const bool tr = (tid & 127) == 0 && tid < 256; const int w = tid >> 7; (void)tr; (void)w; TRC(tr, w, 0); }
  CKK(1);
  uint4 wv[5];
  const uint8_t* wsrc;
  {
    const int n8 = min(tid >> 3, 26), part = n8 / 9;
    const uint8_t* src = (const uint8_t*)P.wqkv + (8 * rb + (tid & 7)) * (3 * DM * 2) + (part * (DM - 72) + 72 * j + 8 * n8) * 2;
#pragma unroll
    for (int u = 0; u < SPL; u++) wv[u] = ldnc128_if(tid < 216, src + u * (128 * 3 * DM * 2));
    wsrc = src;
  }
  CKK(2);
  if (tid == 352) {
#pragma unroll
    for (int e = 0; e < 16; e++) mbar_init(bars + B_FULL + e * 8, (e >> 2) == 1 ? 16 : 1);
    mbar_init(bars + B_RES + 8, 8); mbar_init(bars + B_WT, 1); mbar_init(bars + B_WT + 8, 1); mbar_init(bars + B_IMG, 9);
    asm volatile("fence.mbarrier_init.release.cluster;" ::: "memory");
  }
  __syncthreads();

  if (wid >= 8) {
    reg_dealloc<40>();
    lane = __shfl_sync(~0u, lane, lane);
    const uint32_t el = elect_one();
    const uint64_t pol = policy_evict_first();
    uint32_t* const fj = P.s->flags + FJ + j * 32;
    if (wid == 8) {
      if (lane == 0) {
        mbar_init(bars + B_RES, 1); mbar_init(bars + B_WOI, 1); mbar_init(bars + B_ZB, 1); mbar_init(bars + B_GATE3, 3); mbar_init(bars + B_Z1, 1); mbar_init(bars + B_LAG, 4);
#pragma unroll
        for (int e = B_RT; e < B_XS + 16; e += 8) mbar_init(bars + e, e >= B_AD && e < B_EVT ? 2 : (e >= B_EVT && e < B_RT1) || (e >= B_EA3 && e < B_XS) ? 4 : 1);
        asm volatile("fence.mbarrier_init.release.cluster;" ::: "memory");
        mbar_arrive(bars + B_IMG);
      }
      __syncwarp();
#pragma unroll 1
      for (int i = 0; i < 12; i++) if (el) prefetch_map(&P.act[0] + (i < 7 ? i : i - 12));
      const uint32_t epoch = ldcg32(fj + FJ_EP + rb);
      const uint32_t rk = bid & 1;
      TRC(el, 2, 34);
      uint32_t dst = sb + ST_B + rk * 18432, full = bars + B_FULL, ph = 1;
      auto slot = [&](uint32_t bytes) {
        mbar_wait(full, ph);
        expect_tx_p(el, full, bytes);
        mbar_wait(full + (B_EMPTY - B_FULL), ph);
      };
      auto next = [&]() {
        const bool wrap = full == bars + B_FULL + 24;
        full += wrap ? -24 : 8; dst += wrap ? 0u - 3 * ST_BYTES : ST_BYTES; ph ^= wrap;
      };
#pragma unroll 1
      for (int L = 0; L < 2; L++) {
        const uint8_t* src = P.s->WQ + j * WQ_SL + rk * 13824;
        dst -= rk * 4608;
#pragma unroll 1
        for (int i = 0; i < 9; i++) {
          if (L == 0 && (i == 0 || i == 2 * SPL)) {
            flag_wait(fj + (i ? FJ_WQ : FJ_WQ0), (epoch + 1) * 16);
            fence_async_g();
            TRC(el, 2, i ? 47 : 45);
          }
          slot(27648);
          bulk_mc_h(el, dst, src, 13824, full, true, pol);
          src += 27648;
          next();
        }
        dst += rk * 4608;
        if (L == 0) {
#pragma unroll 1
          for (int u = 0; u < 2; u++) flag_wait(P.s->flags + FJ + (j ^ u) * 32 + FJ_WO, (epoch + 1) * 16);
          fence_async_g();
          TRC(el, 2, 46);
        }
        src = P.s->WO + ((j & 6) + rk) * WO_SL;
#pragma unroll 1
        for (int i = 0; i < 4; i++) {
          slot(ZB);
          bulk_mc_h(el, dst, src, 18432, full, true, pol);
          src += 18432;
          next();
        }
        slot(18432);
        bulk_mc_h(el, dst, src, 9216, full, true, pol);
        next();
        int col = (((9 * j + 1) >> 1) + 36) * 64;
        const CUtensorMap* map = &P.win64;
#pragma unroll 1
        for (int p = 0; p < 9; p++) {
          if (p == 1) mbar_wait(bars + B_FA3 + GA3 * 8, L);
          mbar_wait(full + (B_EMPTY - B_FULL), ph);
          tma4d_mc(el, dst, map, col, rk * 18, full + 8, pol);
          mbar_arrive_if(el, full);
          if (p + L == 0 && el) asm volatile("cp.async.bulk.prefetch.tensor.4d.L2.global [%0, {%1, 0, 0, %2}];\ncp.async.bulk.prefetch.tensor.4d.L2.global [%0, {%1, 0, 0, %3}];" ::"l"(map), "r"(col + 64), "r"(rk * 18), "r"(rk * 18 + 36) : "memory");
          next();
          if (p == 1) mbar_wait(bars + B_FA3 + GB3 * 8, L);
          slot(2 * ZB);
          tma4d_mc(el, dst, map, col, rk * 18 + 36, full, pol);
          next();
          col = p == 3 ? (9 * j + ((j & 1) ? 0 : 8)) * 32 : p == 4 ? ((9 * j + 1) >> 1) * 64 : col + 64;
          map = p == 3 ? &P.win : &P.win64;
        }
        TRC(el, 2, L * 16 + 6);
        flag_wait(fj + FJ_ZN + L, (epoch + 1) * 16);
        fence_async_g();
        TRC(el, 2, L * 16 + 7);
        src = z2_block(0, j) + rk * 18432;
#pragma unroll 1
        for (int i = 0; i < 32; i++) {
          if (i >= 4) mbar_wait(full + (B_AD - B_FULL), ((i >> 2) & 1) ^ 1);
          slot(ST_BYTES);
          bulk_mc_h(el, dst, src, 18432, full, true, pol);
          tma3d_h(el, dst - ST_B - rk * 18432, &P.wsp, i * 64, rb * 64, 0, full, true, pol);
          src += 8 * ZB;
          next();
        }
        mbar_wait(bars + B_Z1, L);
        fence_async_g();
        expect_tx_p(el, bars + B_ZB, 26624);
        mbar_wait(full + (B_AD - B_FULL), 1);
        slot(26624);
        bulk_load_h(el, dst - ST_B - rk * 18432, z1_block(rb, 0, j), 26624, bars + B_ZB, true, pol);
        bulk_load_h(el, dst - ST_B - rk * 18432 + 26624, z1_block(rb, 1, j), 26624, full, true, pol);
        next();
        col = j * 64;
#pragma unroll 1
        for (int i = 0; i < 9; i++) {
          if (i < 3) mbar_wait(full + (B_AD - B_FULL), 1);
          slot(ZB);
          tma2d_mc_h(el, dst, &P.wout, col, 288 * j + rk * 144, full, true, pol);
          col = col == 512 ? 0 : col + 64;
          next();
        }
      }
    } else if (wid < 11) {
      int w = wid - 9;
      TRC(el && w == 0, 2, 35);
      uint32_t t8 = (ldcg32(P.s->flags + (rb * 2 + w) * 32 + FR_EP + j) + 1) * 8;
      int bo = bid;
#define FRESH asm volatile("" : "+r"(lane), "+r"(w), "+r"(bo), "+r"(t8)); const int rb = bo & 15, j = bo >> 4; \
      uint32_t *const fr = P.s->flags + (rb * 2 + w) * 32, *const fj = P.s->flags + FJ + j * 32, *const fo = P.s->flags + (rb * 2 + (j & 1)) * 32 + L; \
      const uint32_t ev = bars + B_EVT + w * EV_N * 8, tag = (t8 >> 2) - 1 + L; (void)fr; (void)fj; (void)fo; (void)ev; (void)tag
      Cur c{0, 1};
#pragma unroll 1
      for (int L = 0; L < 2; L++) {
        {
          FRESH;
          uint4* const xs = P.s->XST + (rb * 2 + w) * 128;
          if (L) {
            mbar_wait(ev + EV_PT * 8, 0);
            TRC(el, 3, w * 32 + 16);
            flag_release_p(el, fr + FR_X2);
            TRC(el, 3, w * 32 + 17);
          }
#pragma unroll 1
          for (int i = 0; i < 9; i++) {
            const uint32_t full = bars + B_FULLA + w * 32 + c.s * 8, dst = sb + c.s * ST_BYTES + w * 8192;
            if (L == 0 && i == 4) {
              mbar_wait(bars + B_WT + w * 8, 0);
              TRC(el && w == 0, 2, 37);
              rows_stats(sb + SM_STG + w * 9216, xs + 16 * j, tag, lane);
              TRC(el && w == 0, 2, 38);
            }
            const uint32_t src = sb + (L ? 2 * ST_BYTES + SM_WOI : SM_STG + w * 9216);
            if (i == 4) {
#pragma unroll
              for (int u = 0; u < 6; u++) sts128(src + u * 512 + lane * 16, POISON, POISON, POISON, POISON);
              fence_async_s();
              __syncwarp();
            }
            mbar_wait(bars + B_EMPTY + c.s * 8, c.ph);
            if (i < L) { flag_wait(fr + FR_X2, t8); fence_async_g(); }
            tma3d_h(el, dst, &P.act[L], i * 64, rb * 64, w, full, false, pol);
            expect_tx_p(el, full, 8192);
            TRC(el && i < L, 3, w * 32 + 18);
            TRC(el && i + L + w == 0, 2, 36);
            c.next();
            if (i >= 4 && i < (L ? 5 : 8)) {
              int b = (rb * 2 + w) * 8 + j;
              asm volatile("" : "+r"(b));
              bulk_store_p(el, i == 4 ? (uint8_t*)P.s->HALO + b * 3072 : P.s->O + (b * 3 + i - 5) * 3072, src, 3072);
              if (i < 6) bulk_store_p(el, (i == 4 ? P.s->ST1 : P.s->ZST) + b * 64, src, 1024);
              if (i == 6) bulk_store_p(el, P.s->RT + b * 8, src, 64);
            }
            if (L == 0 && i == 3) rows_fetch(el, sb + SM_STG + w * 9216, P.xs[0] + (128 * rb + 16 * j + w) * (DM * 2), bars + B_WT + w * 8);
          }
          if (el) asm volatile("cp.async.bulk.commit_group;\ncp.async.bulk.wait_group 0;" ::: "memory");
          __syncwarp();
          if (L == 0) fence_gpu();
          const uint32_t tab = sb + L * (2 * ST_BYTES) + SM_XST + w * 512 + lane * 8;
          TRC(el, 3, w * 32 + L * 16 + 13);
#pragma unroll 1
          for (int it = 0; it < (1 << 22); it++) {
            const uint4 a = ll_ld128(xs + 2 * lane), b = ll_ld128(xs + 64 + 2 * lane);
            if (__all_sync(~0u, a.z == tag && b.z == tag)) { sts64(tab, a.x, a.y); sts64(tab + 256, b.x, b.y); break; }
          }
          __syncwarp();
          mbar_arrive_if(el, bars + B_XS + w * 8);
          TRC(el, 3, w * 32 + L * 16 + 14);
          if (w == 1) {
            mbar_wait(bars + B_XS, L);
            expect_tx_p(el, bars + B_RES, 18432);
            tma3d_h(el, sb + SM_STG, &P.res[L], (j & 6) * 72, rb * 64, j & 1, bars + B_RES, !L, pol);
          }
          if (L) flag_wait(fj + FJ_P4, t8 * 4);
        }
        {
          FRESH;
          const uint8_t* src = o_block(rb, j & 1) + w * 8192;
#pragma unroll 1
          for (int i = 0; i < 5; i++) {
            const uint32_t full = bars + B_FULLA + w * 32 + c.s * 8, dst = sb + c.s * ST_BYTES + w * 8192;
            const bool none = 2 * i + w > 8;
            mbar_wait(bars + B_EMPTY + c.s * 8, c.ph);
            expect_tx_p(el, full, none ? 0 : 8192);
            if (i == 0) {
              mbar_wait(ev + EV_O * 8, L);
              TRC(el, 3, w * 32 + L * 16 + 3);
              flag_add_p(el, fr + FR_O + L);
              TRC(el, 3, w * 32 + L * 16 + 4);
              flag_wait(fo + FR_O, t8);
              fence_async_g();
            }
            if (!none) bulk_load_h(el, dst, src + i * 16384, 8192, full, true, pol);
            TRC(el && i == 0, 3, w * 32 + L * 16 + 5);
            c.next();
          }
        }
        {
          FRESH;
          expect_tx_p(lane < 9, bars + B_FA3 + (9 * w + lane) * 8, 8192);
          mbar_wait(ev + EV_X1 * 8, L);
          TRC(el, 3, w * 32 + L * 16 + 6);
          if (L) flag_add_p(el, fo + FR_X1); else flag_release_p(el, fo + FR_X1);
          mbar_arrive_if(el, bars + B_GATE3);
          TRC(el, 3, w * 32 + L * 16 + 7);
          mbar_arrive_if(lane < 2, bars + B_FULLA + w * 32 + ((c.s + lane) & 3) * 8);
#pragma unroll 1
          for (int kb = 0; kb < 9; kb++) {
            const int n = 9 * w + kb;
            const uint32_t dst = sb + ((n >> 1) & 3) * ST_BYTES + (n & 1) * 8192;
            if (kb == 0) { flag_wait(fr + FR_X1 + L, t8); fence_async_g(); }
            if (n >= 8) mbar_wait(bars + B_EA3 + (n - 8) * 8, L);
            tma3d_h(el, dst, &P.act[L + 1], kb * 64, rb * 64, w, bars + B_FA3 + n * 8, false, pol);
            TRC(el && kb == 0, 3, w * 32 + L * 16 + 8);
          }
          c.ph ^= ((c.s + 18) >> 2) & 1; c.s = (c.s + 18) & 3;
        }
        float cv;
        {
        FRESH;
        expect_tx_p(el, bars + B_WT + w * 8, 2048);
#pragma unroll 1
        for (int r = 0; r < 8; r++)
          bulk_load_p(el, sb + SM_WT + w * 2176 + r * 272, (const uint8_t*)P.w_sp + (size_t)(128 * rb + 16 * j + 2 * r + w) * (SEQ * 2) + 30 * 128, 256, bars + B_WT + w * 8);
        cv = (lane & 3) ? 0.f : -blo(ldnc16(P.b_sp + 128 * rb + 16 * j + 2 * (lane >> 2) + w));
        mbar_wait(bars + B_RT, L);
        mbar_wait(bars + B_WT + w * 8, L ^ 1);
        mbar_wait(ev + EV_Z1 * 8, L);
        const uint32_t ro = (w * 64 + 8 * j + (lane >> 2)) * 128, x0 = ((lane & 3) * 2) ^ (lane >> 2);
#pragma unroll 1
        for (int i = 0; i < 32; i++) {
          const bool tail = (i >> 1) == 4;
          const int kb = tail ? i + 22 : i < 8 ? i : i - 2;
          if (i == 8) mbar_wait(bars + B_RT1, L);
          if (!tail) mbar_wait(bars + B_FULL + c.s * 8, c.ph ^ 1);
#pragma unroll
          for (int e = 0; e < 2; e++) {
            const uint4 a = lds128(!tail ? sb + c.s * ST_BYTES + ro + ((x0 ^ e) << 4) : sb + SM_WT + w * 2176 + (lane >> 2) * 272 + (i - 8) * 128 + (lane & 3) * 32 + e * 16);
            const uint4 m = lds128(sb + SM_RT + 4096 + kb * 128 + (lane & 3) * 32 + e * 16);
            cv = fmaf(blo(a.x), blo(m.x), fmaf(bhi(a.x), bhi(m.x), fmaf(blo(a.y), blo(m.y), fmaf(bhi(a.y), bhi(m.y), cv))));
            cv = fmaf(blo(a.z), blo(m.z), fmaf(bhi(a.z), bhi(m.z), fmaf(blo(a.w), blo(m.w), fmaf(bhi(a.w), bhi(m.w), cv))));
          }
          if (!tail) {
            mbar_arrive_if(el, bars + B_AD + c.s * 8 + (__float_as_uint(cv) & P.zero));
            c.next();
          }
        }
        }
        TRC(el, 3, w * 32 + L * 16 + 11);
        FRESH;
        cv = qsum(cv);
        uint2* const cs = (uint2*)(P.s->XST + (rb * 2 + w) * 128 + 1);
        if ((lane & 3) == 0) ll_st64(cs + 32 * j + (lane >> 2) * 4, __float_as_uint(cv), tag);
#pragma unroll 1
        for (int it = 0; it < (1 << 22); it++) {
          const uint2 a = ll_ld64(cs + 4 * lane), b = ll_ld64(cs + 128 + 4 * lane);
          if (__all_sync(~0u, a.y == tag && b.y == tag)) { sts32(sb + SM_CV + w * 256 + lane * 4, a.x); sts32(sb + SM_CV + w * 256 + 128 + lane * 4, b.x); break; }
        }
        __syncwarp();
        if (el) mbar_arrive(bars + B_CV + w * 8);
        TRC(el, 3, w * 32 + L * 16 + 12);
#pragma unroll 1
        for (int kb = 30; kb < 32; kb++) {
          mbar_wait(bars + B_FULL + c.s * 8, c.ph ^ 1);
          if (el) mbar_arrive(bars + B_AD + c.s * 8);
          c.next();
        }
        c.ph ^= ((c.s + 10) >> 2) & 1; c.s = (c.s + 10) & 3;
        if (L == 0) {
          mbar_wait(ev + EV_P4 * 8, 0);
          flag_add_p(el, fj + FJ_P4);
          flag_add_p(el, fr + FR_EP + j);
        }
      }
    } else {
      const uint32_t epoch = ldcg32(fj + FJ_EP + rb);
      TRC(el, 2, 33);
      if (SPL) {
        mbar_wait(bars + B_RES + 8, 0);
        TRC(el, 2, 41);
        flag_release_p(el, fj + FJ_WQ0);
        TRC(el, 2, 42);
      }
      mbar_wait(bars + B_IMG, 0);
      TRC(el, 2, 39);
      flag_release_p(el, fj + FJ_WQ);
      TRC(el, 2, 40);
#pragma unroll 1
      for (int L = 0; L < 2; L++) {
        auto wo_fetch = [&]() {
          expect_tx_p(el, bars + B_WOI, 5760);
          asm volatile("{\n.reg .pred P;\nsetp.ne.u32 P, %5, 0;\n@P cp.async.bulk.tensor.4d.shared::cluster.global.mbarrier::complete_tx::bytes [%0], [%1, {0, 0, %3, %4}], [%2];\n}" ::"r"(sb + SM_WOI), "l"(&P.wo8), "r"(bars + B_WOI), "r"(9 * j), "r"((9 * rb) >> 1), "r"(el) : "memory");
        };
        float* const csf = P.s->CSP + (NCTA + bid) * 216;
        if (L == 0) {
          flag_wait(fj + FJ_WQ, (epoch + 1) * 16);
          fence_async_g();
          expect_tx_p(el, bars + B_XRW, 13824);
          bulk_load_p(el, sb + ST_BYTES + SM_WOI, P.s->CSP + j * 16 * 216, 6912, bars + B_XRW);
          bulk_load_p(el, sb + 2 * ST_BYTES + SM_WOI, P.s->CSP + (j * 16 + 8) * 216, 6912, bars + B_XRW);
          wo_fetch();
          mbar_wait(bars + B_XRW, 0);
#pragma unroll 1
          for (int f = lane; f < 54; f += 32) {
            float s[4] = {0.f, 0.f, 0.f, 0.f};
#pragma unroll 4
            for (int r = 0; r < 16; r++) {
              const uint4 v = lds128(sb + ST_BYTES + SM_WOI + (r >> 3) * ST_BYTES + (r & 7) * 864 + f * 16);
              s[0] += __uint_as_float(v.x); s[1] += __uint_as_float(v.y); s[2] += __uint_as_float(v.z); s[3] += __uint_as_float(v.w);
            }
            sts128(sb + SM_CSQ + f * 16, __float_as_uint(s[0]), __float_as_uint(s[1]), __float_as_uint(s[2]), __float_as_uint(s[3]));
            stg128(csf + f * 4, __float_as_uint(s[0]), __float_as_uint(s[1]), __float_as_uint(s[2]), __float_as_uint(s[3]));
          }
          __syncwarp();
          mbar_arrive_if(el, bars + B_CSQ);
        } else {
#pragma unroll 1
          for (int u = 0; u < 4; u++) {
            const int w = u & 1;
            if (u < 2) {
              flag_wait(P.s->flags + (rb * 2 + w) * 32 + FR_X2, (epoch + 1) * 8);
              fence_async_g();
              TRC(el, 2, 48 + u);
              rows_fetch(el, sb + SM_STG + w * 9216, P.xs[1] + (128 * rb + 16 * j + w) * (DM * 2), bars + B_XRW + w * 8);
            } else {
              if (u == 2) {
                expect_tx_p(el, bars + B_CSQ, 864);
                bulk_load_p(el, sb + 2 * ST_BYTES + SM_CSQ, csf, 864, bars + B_CSQ);
              }
              mbar_wait(bars + B_XRW + w * 8, w ^ 1);
              TRC(el, 2, 48 + u);
              rows_stats(sb + SM_STG + w * 9216, P.s->XST + (rb * 2 + w) * 128 + 16 * j, epoch * 2 + 2, lane);
              TRC(el, 2, 50 + u);
            }
          }
        }
        if (L == 0) {
          TRC(el, 2, 43);
          mbar_wait(bars + B_WOI, 0);
          bulk_store_p(el, P.s->WO + j * WO_SL + ((9 * rb) >> 1) * 1152, sb + SM_WOI, 5760);
          publish_p(el, fj + FJ_WO);
          TRC(el, 2, 44);
          const uint8_t* sp = lane < 16 ? (const uint8_t*)P.w_in + (30 * lane + 50) * (FH * 4) + FH * 2 + lane * 256 : (const uint8_t*)P.w_sp + (60 * lane) * (SEQ * 2) + lane * 64;
          float sq = 0.f;
#pragma unroll 1
          for (int u = 0; u < 4; u++) {
            const uint4 y = ldnc128(sp + u * 16);
            const uint32_t x[4] = {y.x, y.y, y.z, y.w};
#pragma unroll
            for (int e = 0; e < 4; e++) sq = fmaf(blo(x[e]), blo(x[e]), fmaf(bhi(x[e]), bhi(x[e]), sq));
          }
#pragma unroll 1
          for (int o = 8; o; o >>= 1) sq += __shfl_xor_sync(~0u, sq, o);
          sq *= lane < 16 ? 2.f * GA * GA * DM / 512.f : C0S * C0S * SEQ / 512.f;
          asm("sqrt.approx.f32 %0, %0;" : "+f"(sq));
          const float o0 = __shfl_sync(~0u, sq, 0), o1 = __shfl_sync(~0u, sq, 16);
          const float p2 = __uint_as_float(min(__float_as_uint(o0) & 0x7f800000u, 0x7e000000u)) * OFK, off = -p2 - fminf(OFA, 0.5f * p2);
          if (el) sts64(sb + SM_OFF, pack2(off, off), min(__float_as_uint(o1) & 0x7f800000u, 0x7e000000u) | 0x00400000u);
        }
        if (el) mbar_arrive(bars + B_GATE3);
        const uint32_t tag = epoch * 2 + L + 1;
        asm volatile("" : "+r"(lane));
        mbar_wait(bars + B_EVT + EV_ZN * 8, L);
        mbar_wait(bars + B_EVT + (EV_N + EV_ZN) * 8, L);
        flag_release_p(el, fj + FJ_ZN + L);
        TRC(el, 2, L * 16 + 8);
        {
          uint4 v[4];
#pragma unroll 1
          for (int it = 0; it < (1 << 22); it++) {
            bool ok = true;
#pragma unroll
            for (int u = 0; u < 4; u++) { v[u] = ll_ld128(P.s->ZST + (rb * 2 + ((lane >> 1) & 1)) * 512 + ((lane & 1) * 4 + u) * 64 + 8 * j + (lane >> 2)); ok = ok && v[u].z == tag; }
            if (__all_sync(~0u, ok)) break;
          }
          float mean = __uint_as_float(v[0].x) + __uint_as_float(v[1].x) + __uint_as_float(v[2].x) + __uint_as_float(v[3].x), M2 = 0.f;
          mean = (mean + __shfl_xor_sync(~0u, mean, 1)) * 0.125f;
#pragma unroll
          for (int u = 0; u < 4; u++) { const float d = __uint_as_float(v[u].x) - mean; M2 += fmaf(288.f * d, d, __uint_as_float(v[u].y)); }
          M2 += __shfl_xor_sync(~0u, M2, 1);
          const float rs = blo(pack2(rsq_fast(fmaf(M2, 1.f / FH, 4.f * GA * GA * LN_EPS)), 0.f));
          if (!(lane & 1)) ll_st64(P.s->RT + 128 * rb + 16 * j + (lane >> 1), pack2(rs, rs * mean), tag);
        }
        TRC(el, 2, L * 16 + 10);
#pragma unroll 1
        for (int b = 0; b < 8; b++) {
          uint4 v[4];
#pragma unroll 1
          for (int it = 0; it < (1 << 22); it++) {
            bool ok = true;
#pragma unroll
            for (int u = 0; u < 4; u++) { v[u] = ll_ld128((const uint4*)P.s->RT + b * 128 + u * 32 + lane); ok = ok && v[u].y == tag && v[u].w == tag; }
            if (__all_sync(~0u, ok)) break;
          }
#pragma unroll
          for (int u = 0; u < 4; u++) {
            const uint32_t rt = sb + SM_RT + b * 512 + u * 128, ro = (lane >> 3) * 32 + (lane & 3) * 8 + ((lane >> 2) & 1) * 2;
            sts32(rt + 4096 + lane * 4, __byte_perm(v[u].x, v[u].z, 0x7632));
            asm volatile("st.shared.u16 [%0], %1;\nst.shared.u16 [%0 + 4], %2;" ::"r"(rt + ro), "h"((uint16_t)v[u].x), "h"((uint16_t)v[u].z) : "memory");
          }
          __syncwarp();
          if (el && (b == 1 || b == 7)) mbar_arrive(bars + (b == 1 ? B_RT : B_RT1));
          TRC(el && b < 2, 2, L * 16 + 11 + b);
        }
        TRC(el, 2, L * 16 + 9);
        mbar_wait(bars + B_EVT + EV_Z1 * 8, L);
        mbar_wait(bars + B_EVT + (EV_N + EV_Z1) * 8, L);
        fence_gpu();
        if (el) mbar_arrive(bars + B_Z1);
        if (L == 0) {
          flag_add_p(el, fj + FJ_EP + rb);
          __nanosleep(NAP0);
          poison(P, el, sb + SM_STG + 17152, &P.psn, rb, j, lane);
          if (el) asm volatile("cp.async.bulk.commit_group;\ncp.async.bulk.wait_group 0;" ::: "memory");
          __syncwarp();
          fence_gpu();
        }
      }
    }
  } else {
    CKK(3);
    uint8_t* const wdst = P.s->WQ + j * WQ_SL + rb * 3456 + tid * 16;
#pragma unroll
    for (int u = 0; u < SPL; u++) stg128_if(tid < 216, wdst + u * (16 * 3456), wv[u].x, wv[u].y, wv[u].z, wv[u].w);
    __syncwarp();
    if (lane == 0) mbar_arrive(bars + B_RES + 8);
    CKK(4);
    auto repack2 = [&]() {
#pragma unroll
      for (int u = SPL; u < 5; u++) stg128_if((u < 4 || rb < 8) && tid < 216, wdst + u * (16 * 3456), wv[u].x, wv[u].y, wv[u].z, wv[u].w);
      float s[8];
#pragma unroll
      for (int e = 0; e < 8; e++) s[e] = 0.f;
#pragma unroll
      for (int u = 0; u < 5; u++) {
        uint32_t x[4] = {wv[u].x, wv[u].y, wv[u].z, wv[u].w};
        asm volatile("" : "+r"(x[0]), "+r"(x[1]), "+r"(x[2]), "+r"(x[3]));
#pragma unroll
        for (int e = 0; e < 4; e++) { s[2 * e] += blo(x[e]); s[2 * e + 1] += bhi(x[e]); }
      }
#pragma unroll
      for (int m = 4; m; m >>= 1) {
#pragma unroll
        for (int e = 0; e < m; e++) s[e] = ((tid & m) ? s[e + m] : s[e]) + __shfl_xor_sync(~0u, (tid & m) ? s[e] : s[e + m], m);
      }
      stg32_if(tid < 216, P.s->CSP + bid * 216 + tid, __float_as_uint(s[0]));
      __syncwarp();
      if (lane == 0) mbar_arrive(bars + B_IMG);
    };
    reg_alloc<232>();
    lane = __shfl_sync(~0u, lane, lane);
    tid = wid * 32 + lane;
    CKK(5);
#pragma unroll
    for (int v = SPL; v < 5; v++) wv[v] = ldnc128_if(tid < 216 && (v < 4 || rb < 8), wsrc + v * (128 * 3 * DM * 2));
    repack2();
    CKK(6);
    const int w = wid >> 2, q = wid & 3;
    int g = lane >> 2, t = lane & 3;
    const uint32_t ev = bars + B_EVT + w * EV_N * 8;
    const bool tr = (tid & 127) == 0;
    (void)tr;
    Cur c{0, 0};
    const uint32_t ebar = mapa(bars + B_EMPTY, (bid & 1) ^ (lane & 1));
    auto release = [&](uint32_t s, uint32_t dep = 0) { mbar_arrive_cluster_if(lane < 2, ebar + s * 8 + dep); };
    auto release_if = [&](bool on, uint32_t s) { mbar_arrive_cluster_if(lane < 2 && on, ebar + s * 8); };
    uint32_t ia = 0;
    auto wait_ab = [&]() { mbar_wait_c(bars + B_FULL + c.s * 8, c.ph); mbar_wait_c(bars + B_FULLA + w * 32 + c.s * 8, (ia >> 2) & 1); ia++; };

    auto yield_done = [&]() { if (w == 0 && lane == 0) mbar_arrive(bars + B_LAG); };
    auto signal = [&](int e) { __syncwarp(); mbar_arrive_if(lane == 0, ev + e * 8); };

    const uint32_t epoch = ldcg32(P.s->flags + (rb * 2 + w) * 32 + FR_EP + j);
    TRC(tr, w, 1);
    CKK(7);
    if (PAD && P.zero) {
#pragma unroll
      for (int i = 0; i < PAD; i++) asm volatile("st.shared.u32 [%0], %1;" ::"r"(sb + i * 20), "r"(tid) : "memory");
    }
    CKK_OUT;

#pragma unroll 1
    for (int L = 0; L < 2; L++) {
      const int tb = 2 + L * 24;
      asm volatile("" : "+r"(lane), "+r"(g), "+r"(t));
      (void)tb;
      ia = 0;
      const uint32_t tag = epoch * 2 + L + 1;
      uint32_t aoff = (w * 64 + q * 16 + (lane & 15)) * 128 + (((lane >> 4) ^ (lane & 7)) << 4);
      {
        uint32_t Pk[27][2];
        float sc0, sc1;
        const uint32_t att = sb + w * 8192 + q * 2048 + lane * 4;
        uint4* hp = P.s->HALO + ((((rb - (q == 0)) * 2 + w) * 8 + j) * 6) * 32 + lane;
        uint8_t* od = o_block(rb, w) + (9 * j) * 1024 + (2 * q) * 128 + lane * 4;
        ACLK_INIT;
        {
          float acc[108];
#pragma unroll
          for (int i = 0; i < 108; i++) acc[i] = 0.f;
          uint32_t prev = 0;
#pragma unroll 1
          for (int kb = 0; kb < 9; kb++) {
            const bool hold = w == 1 && kb == 9 - LAG1;
            if (hold) {
              wgmma_wait<0>();
              release(prev);
              mbar_wait_c(bars + B_LAG, L);
            }
            wait_ab();
            TRC(tr && kb == 0, w, tb + 0);
            MCLK(kb == 0, 0);
            PCLK(kb * 4);
            const uint32_t st = sb + c.s * ST_BYTES;
            uint64_t da = dsc2(dlo(st + w * 8192, 16), 0, 0x40000040u + P.zero), db = dsc2(dlo(st + ST_B, 3456), 0, 8 ^ P.zero);
            wgmma_fence();
#pragma unroll
            for (int kk = 0; kk < 4; kk++) {
              wgmma_ss_n216(acc, da, db, 1);
              dadd(da, 2); dadd(db, 432);
              if (kk == 0) { wgmma_commit(); wgmma_wait<1>(); release_if(kb > 0 && !hold, prev); }
            }
            wgmma_commit();
            if (kb == 7) yield_done();
            PCLK(kb * 4 + 1);
            PCLK(kb * 4 + 2);
            PCLK(kb * 4 + 3);
            prev = c.s; c.next();
          }
          const uint32_t cs = sb + prev * ST_BYTES + SM_CSQ + t * 8;
          mbar_wait_c(bars + B_CSQ, L);
          mbar_wait_c(bars + B_XS + w * 8, L);
          const float2 n0 = lds64f(sb + prev * ST_BYTES + SM_XST + w * 512 + (16 * q + g) * 8), n1 = lds64f(sb + prev * ST_BYTES + SM_XST + w * 512 + (16 * q + g + 8) * 8);
          const float m0 = n0.x, r0 = n0.y, m1 = n1.x, r1 = n1.y;
          float2 cv[27];
#pragma unroll
          for (int G = 0; G < 27; G++) cv[G] = lds64f(cs + G * 32);
          PCLK(36);
          wgmma_wait<0>();
          PCLK(37);
          {
            uint32_t dep = P.zero & __float_as_uint(m0) & __float_as_uint(m1);
#pragma unroll
            for (int G = 0; G < 27; G++) dep &= __float_as_uint(cv[G].x);
            release(prev, dep);
          }
          TRC(tr, w, tb + 1);
          MCLK(1, 1);
          ACLK(0);
#pragma unroll
          for (int G = 9; G < 27; G++) Pk[G][1] = pack2(fmaf(m1, cv[G].x, acc[4 * G + 2]) * r1, fmaf(m1, cv[G].y, acc[4 * G + 3]) * r1);
          if (q < 3) {
#pragma unroll
            for (int i = 0; i < 18; i++) sts32(att + (i >> 4) * ST_BYTES + (i & 15) * 128, Pk[9 + i][1]);
          } else if (rb < 15) {
#pragma unroll
            for (int i = 0; i < 6; i++) ll_st128(hp + i * 32, __uint_as_float(Pk[9 + 3 * i][1]), __uint_as_float(Pk[10 + 3 * i][1]), tag, __uint_as_float(Pk[11 + 3 * i][1]));
          }
#pragma unroll
          for (int G = 0; G < 27; G++) {
            if (G < 9) {
              Pk[G][0] = pack2(fmaf(m0, cv[G].x, acc[4 * G]), fmaf(m0, cv[G].y, acc[4 * G + 1]));
              Pk[G][1] = pack2(fmaf(m1, cv[G].x, acc[4 * G + 2]), fmaf(m1, cv[G].y, acc[4 * G + 3]));
            } else {
              Pk[G][0] = pack2(fmaf(m0, cv[G].x, acc[4 * G]) * r0, fmaf(m0, cv[G].y, acc[4 * G + 1]) * r0);
            }
          }
          sc0 = r0 * (0.23570226039551584f * 1.4426950408889634f); sc1 = r1 * (0.23570226039551584f * 1.4426950408889634f);
        }
        ACLK(1);
        constexpr int GA_[4] = {0, 2, 4, 7}, GB_[4] = {1, 3, 5, 8}, GC_[4] = {2, 4, 6, 6};
        float S1[4][4], S2[4][4];
        uint32_t qa[4][2], qc[4][2];
#pragma unroll
        for (int h = 0; h < 4; h++) {
#pragma unroll
          for (int r = 0; r < 2; r++) {
            qa[h][r] = (h == 0 || h == 3 || t >= h) ? Pk[GA_[h]][r] : 0u;
            qc[h][r] = (h == 3 ? t == 3 : t <= h) ? Pk[GC_[h]][r] : 0u;
          }
          mma16(S1[h], qa[h][0], qa[h][1], Pk[GB_[h]][0], Pk[GB_[h]][1], Pk[9 + GA_[h]][0], Pk[9 + GB_[h]][0]);
          mma16(S2[h], qa[h][0], qa[h][1], Pk[GB_[h]][0], Pk[GB_[h]][1], Pk[9 + GA_[h]][1], Pk[9 + GB_[h]][1]);
        }
#pragma unroll
        for (int h = 0; h < 4; h++) {
          mma8(S1[h], qc[h][0], qc[h][1], Pk[9 + GC_[h]][0]);
          mma8(S2[h], qc[h][0], qc[h][1], Pk[9 + GC_[h]][1]);
        }
        uint32_t V1[9], V2[9];
#pragma unroll
        for (int i = 0; i < 9; i++) { V1[i] = movm(Pk[18 + i][0]); V2[i] = movm(Pk[18 + i][1]); }
        const bool remote = q == 0 && rb > 0;
        uint4 hv[6];
#pragma unroll
        for (int i = 0; i < 6; i++) hv[i] = make_uint4(0u, 0u, tag, 0u);
        if (remote) {
#pragma unroll
          for (int i = 0; i < 6; i++) hv[i] = ll_ld128(hp + i * 32);
        }
        const bool up0 = 2 * t > g, up1 = 2 * t + 1 > g;
        const uint32_t mup = (up0 ? 0xffffu : 0u) | (up1 ? 0xffff0000u : 0u);
        auto finish = [&](const float (&x0)[4], const float (&x1)[4], uint32_t ma, const uint32_t (&Vb)[9], int hi) {
          uint32_t pa[4], pb[4];
          float rs[4];
#pragma unroll
          for (int h = 0; h < 4; h++) {
            const float m = qmax(fmaxf(x0[h], x1[h]));
            const uint32_t p = pack2(ex2(x0[h] - m), ex2(x1[h] - m));
            pa[h] = p & ma; pb[h] = p & ~ma;
          }
          if (!hi) mbar_arrive_if(lane == 0, ev + EV_O * 8 + (Vb[8] & pa[3] & P.zero));
#pragma unroll
          for (int h = 0; h < 4; h += 2) {
            float R[4];
            mma16(R, pa[h], pa[h + 1], pb[h], pb[h + 1], 0x3f803f80u, 0x3f803f80u);
            rs[h] = rcp_fast(R[0]); rs[h + 1] = rcp_fast(R[2]);
          }
#pragma unroll
          for (int i = 0; i < 9; i++) {
            const int h = 4 * i / 9, e = (h & 1) * 2;
            const bool split = i == 2 || i == 4 || i == 6, nx = split && 2 * t >= i;
            float O[4], N[4];
            mma16(O, pa[h & 2], pa[h | 1], pb[h & 2], pb[h | 1], V1[i], Vb[i]);
            if (i == 4) mma16(N, pa[2], pa[3], pb[2], pb[3], V1[i], Vb[i]); else { N[0] = O[2]; N[1] = O[3]; }
            const float r = nx ? rs[h + (split ? 1 : 0)] : rs[h];
            stg32(od + i * 1024 + hi * 128, pack2((nx ? N[0] : O[e]) * r, (nx ? N[1] : O[e + 1]) * r));
          }
        };
        {
          float x0[4], x1[4];
#pragma unroll
          for (int h = 0; h < 4; h++) { x0[h] = (up0 ? S1[h][2] : S2[h][2]) * sc1; x1[h] = (up1 ? S1[h][3] : S2[h][3]) * sc1; }
          finish(x0, x1, mup, V2, 1);
        }
        ACLK(2);
        bar_sync(1 + w, 128);
        uint32_t H[18];
        if (q > 0) {
#pragma unroll
          for (int i = 0; i < 18; i++) H[i] = lds32(att - 2048 + (i >> 4) * ST_BYTES + (i & 15) * 128);
        } else {
#pragma unroll 1
          for (int it = 0; it < (1 << 20); it++) {
            bool ok = true;
#pragma unroll
            for (int i = 0; i < 6; i++) ok = ok && hv[i].z == tag;
            if (__all_sync(~0u, ok)) break;
#pragma unroll
            for (int i = 0; i < 6; i++) hv[i] = ll_ld128(hp + i * 32);
          }
#pragma unroll
          for (int i = 0; i < 6; i++) { H[3 * i] = hv[i].x; H[3 * i + 1] = hv[i].y; H[3 * i + 2] = hv[i].w; }
        }
        float S0[4][4];
#pragma unroll
        for (int h = 0; h < 4; h++) {
          mma16(S0[h], qa[h][0], qa[h][1], Pk[GB_[h]][0], Pk[GB_[h]][1], H[GA_[h]], H[GB_[h]]);
        }
#pragma unroll
        for (int h = 0; h < 4; h++) mma8(S0[h], qc[h][0], qc[h][1], H[GC_[h]]);
        uint32_t V0[9];
#pragma unroll
        for (int i = 0; i < 9; i++) V0[i] = movm(H[9 + i]);
        ACLK(3);
        {
          const bool nohalo = (rb | q) == 0;
          const float b0 = up0 && nohalo ? -INFINITY : 0.f, b1 = up1 && nohalo ? -INFINITY : 0.f;
          float x0[4], x1[4];
#pragma unroll
          for (int h = 0; h < 4; h++) { x0[h] = fmaf(up0 ? S0[h][0] : S1[h][0], sc0, b0); x1[h] = fmaf(up1 ? S0[h][1] : S1[h][1], sc0, b1); }
          finish(x0, x1, ~mup, V0, 0);
        }
        ACLK(4);
        ACLK_OUT;
        TRC(tr, w, tb + 2);
        MCLK(1, 2);
      }
      {
        float acc[36];
        const int hw = rb * 2 + (j & 1), js = (j & 6) + w;
        const uint32_t xt = sb + SM_STG + (16 * q + (lane & 15)) * 288 + (9 * w + (lane >> 4)) * 16, eye = (g >> 1) == t ? 0x3f80u << (g & 1) * 16 : 0u;
        uint32_t xm = xt ^ ((lane & 4) << 2), xl = sb + SM_STG + (2 * q + w) * 2304;
        uint32_t xl0 = xl + (lane >> 4) * 288 + (lane & 15) * 16, xl1 = xl + ((lane >> 1) & 7) * 288 + 256 + ((lane ^ (lane >> 3)) & 1) * 16;
        uint8_t* xd0 = P.xs[L + 1] + (128 * rb + 32 * q + 16 * w + (j & 1)) * (DM * 2) + (j & 6) * 144;
        uint8_t* xd1 = xd0 + (lane >> 1) * (DM * 4) + 256 + (lane & 1) * 16;
        xd0 += (lane >> 4) * (DM * 4) + (lane & 15) * 16;
        uint4* stp = P.s->ST1 + (hw * 8 + js) * 64 + 16 * q + g;
        asm volatile("" : "+r"(xm), "+r"(xl0), "+r"(xl1), "+l"(xd0), "+l"(xd1), "+l"(stp));
        mbar_wait_c(bars + B_RES, L);
        TRC(tr, w, tb + 21);
#pragma unroll
        for (int u = 0; u < 5; u++) {
          uint32_t r[4];
          ldsm4(r, xt + u * 32);
          widen(acc + 8 * u, r[0], r[1], eye);
          if (u < 4) widen(acc + 8 * u + 4, r[2], r[3], eye);
        }
        uint32_t prev = 0;
#pragma unroll 1
        for (int u = 0; u < 5; u++) {
          const uint32_t st = sb + c.s * ST_BYTES;
          uint64_t da = dsc2(dlo(st, 1024), 0, 8 + P.zero), db = dsc2(dlo(st + ST_B + w * 18432, 1152), 0, 8 ^ P.zero);
          mbar_wait_c(bars + B_FULL + c.s * 8, c.ph); mbar_wait_c(bars + B_FULLA + c.s * 8, (ia >> 2) & 1);
          TRC(tr && u == 0, w, tb + 3);
          MCLK(u == 0, 3);
          wgmma_fence();
#pragma unroll
          for (int kk = 0; kk < 4; kk++) { wgmma_ss_n72(acc, da, db, 1); dadd(da, 128); dadd(db, 144); }
          wgmma_commit();
          wgmma_wait<1>();
          release_if(u > 0, prev);
          mbar_wait_c(bars + B_FULLA + 32 + c.s * 8, (ia >> 2) & 1);
          ia++;
          if (u == 4) break;
          wgmma_fence();
#pragma unroll
          for (int kk = 4; kk < 8; kk++) { wgmma_ss_n72(acc, da, db, 1); dadd(da, 128); dadd(db, 144); }
          wgmma_commit();
          prev = c.s; c.next();
        }
        RCLK_INIT;
        wgmma_wait<0>();
        RCLK(0);
        release(c.s);
        c.next();
        if (__builtin_expect(any_nan(acc[0], acc[2]), 0)) {
          SLOW(L);
          const uint8_t* xr = P.xs[L] + (128 * rb + 32 * q + 2 * g + (j & 1)) * (DM * 2) + js * 144 + t * 4;
#pragma unroll
          for (int i = 0; i < 9; i++) widen(acc + 4 * i, ldgpu32(xr + i * 16), ldgpu32(xr + i * 16 + DM * 32), eye);
          redo<KS2, 9, 1024, 128, 1152, 128>(acc, o_block(rb, j & 1) + q * 256 + lane * 4, P.s->WO + js * WO_SL + lane * 4, [](uint32_t*, int) {});
        }
        TRC(tr && P5TRACE != 5, w, tb + 4);
        MCLK(1, 4);
        uint32_t pk[18];
#pragma unroll
        for (int i = 0; i < 18; i++) pk[i] = pack2(acc[2 * i], acc[2 * i + 1]);
#pragma unroll
        for (int u = 0; u < 4; u++) stsm4(xm + u * 32, pk[4 * u], pk[4 * u + 1], pk[4 * u + 2], pk[4 * u + 3]);
        asm volatile("stmatrix.sync.aligned.m8n8.x2.shared.b16 [%0], {%1,%2};" ::"r"(xm + 128), "r"(pk[16]), "r"(pk[17]) : "memory");
        float sm[4], q0[4], q1[4];
        widen(sm, pk[16], pk[17], 0x3f803f80u); widen(q0, pk[16], pk[17], pk[16]); widen(q1, pk[16], pk[17], pk[17]);
#pragma unroll
        for (int u = 0; u < 4; u++) {
          mma16acc(sm, pk + 4 * u, 0x3f803f80u, 0x3f803f80u);
          mma8(q0, pk[4 * u], pk[4 * u + 1], pk[4 * u]); mma8(q1, pk[4 * u], pk[4 * u + 1], pk[4 * u + 1]);
          mma8(q0, pk[4 * u + 2], pk[4 * u + 3], pk[4 * u + 2]); mma8(q1, pk[4 * u + 2], pk[4 * u + 3], pk[4 * u + 3]);
        }
        auto stats = [&]() {
#pragma unroll
          for (int h = 0; h < 2; h++) {
            const float ss = sm[2 * h], m = ss * (1.f / 72.f), qq = h ? ((g & 1) ? q1[3] : q1[2]) : (g & 1) ? q0[1] : q0[0];
            ll_st128_if(eye, stp + 8 * h, m, fmaxf(qq - ss * m, 0.f), tag);
          }
        };
        RCLK(1);
        bar_sync(8 + q, 64);
        RCLK(2);
        uint4 v[5];
#pragma unroll
        for (int u = 0; u < 5; u++) v[u] = lds128(u < 4 ? (xl0 ^ ((u & 2) << 3)) + u * 576 : xl1);
        stats();
#pragma unroll
        for (int u = 0; u < 5; u++) stg128_if(u < 4 || lane < 16, u < 4 ? xd0 + u * (DM * 8) : xd1, v[u].x, v[u].y, v[u].z, v[u].w);
        RCLK(3);
        signal(EV_X1);
        RCLK(4);
        RCLK(5);
        TRC(tr, w, tb + 5);
        RCLK(6);
        RCLK_OUT;
      }
      uint32_t zk[16];
      {
        uint32_t xA[36][4];
        float acc[32];
        uint32_t s0, one, off2;
        uint8_t *z1d, *zd;
        uint64_t db;
        auto bwait = [&](uint32_t dhi, bool skip) {
          s0 = c.s;
          c.next();
          if (!skip) mbar_wait_c(bars + B_FULL + c.s * 8, c.ph);
          db = dsc2(dlo(sb + s0 * ST_BYTES + ST_B, 512) - 3, 0, dhi); one = (c.s ^ P.zero) & 1;
        };
        auto mma = [&](int kk, int pp, bool hand) {
          wgmma_rs_n64(acc, xA[kk], dat(db, (kk / 18) * ST_BYTES + (kk % 18) * 2048 + 48, one), kk != 0);
          if (kk == pp && hand) bar_arrive(7 - w, 256);
          if (kk == 17 || kk == 35) wgmma_commit();
          if (kk == RL3) { wgmma_commit(); wgmma_wait<1>(); release(s0); }
        };
        {
          bwait(0x40000040u, false);
          mbar_wait_c(bars + B_GATE3, L);
          float mean0, mean1, rs0, rs1;
          stat_get(P.s->ST1 + ((rb * 2 + w) * 8 + 2 * t) * 64 + 16 * q + g, tag, 72.f, LN_EPS, mean0, rs0, mean1, rs1);
          const uint32_t ns0 = pack2(GA * rs0, GA * rs0), ns1 = pack2(GA * rs1, GA * rs1);
          const uint32_t nb0 = pack2(-mean0 * blo(ns0), -mean0 * blo(ns0)), nb1 = pack2(-mean1 * blo(ns1), -mean1 * blo(ns1));
          const uint32_t al = sb + (aoff & 8191);
#pragma unroll
          for (int kb = 0; kb <= 9; kb++) {
            if (kb < 9) {
              mbar_wait_c(bars + B_FA3 + (9 * w + kb) * 8, L);
              TRC(tr && kb == 0, w, tb + 6);
              MCLK(kb == 0, 5);
              if (kb == 0) SCLK(0);
              QCLK(kb);
              const uint32_t at = al + (w ? (((kb + 1) >> 1) & 3) * ST_BYTES + ((kb + 1) & 1) * 8192 : ((kb >> 1) & 3) * ST_BYTES + (kb & 1) * 8192);
#pragma unroll
              for (int kk = 4 * kb; kk < 4 * kb + 4; kk++) ldsm4(xA[kk], at ^ ((kk & 3) << 5));
            }
            if (kb == 0) continue;
            const uint32_t dep = xA[4 * kb - 4][0] & xA[4 * kb - 3][0] & xA[4 * kb - 2][0] & xA[4 * kb - 1][0] & P.zero;
            mbar_arrive_if(lane == 0 && (kb == 1 || w == 0), bars + B_EA3 + (9 * w + kb - 1) * 8 + dep);
#pragma unroll
            for (int kk = 4 * kb - 4; kk < 4 * kb; kk++) {
#pragma unroll
              for (int e = 0; e < 4; e++) xA[kk][e] = hfma2(xA[kk][e], (e & 1) ? ns1 : ns0, (e & 1) ? nb1 : nb0);
            }
            wgmma_fence();
#pragma unroll
            for (int kk = 4 * kb - 4; kk < 4 * kb; kk++) mma(kk, PP30, w);
          }
          off2 = lds32(sb + SM_OFF);
          z1d = z1_block(rb, w, j) + (tid & 127) * 16;
          zd = z2_block(2 * rb + (q >> 1), j) + (4 * (q & 1) + w) * 4608 + ((g & 3) * 2 + (g >> 2)) * 16 + t * 4;
          asm volatile("" : "+l"(z1d), "+l"(zd));
          wgmma_wait<0>();
          if (__builtin_expect(any_nan(acc[0], acc[2]), 0)) {
            SLOW(2 + L);
            uint4* const rd = P.s->RD + bid * (36 * 256) + tid;
            const uint8_t* xr = P.xs[L + 1] + (128 * rb + 32 * q + 2 * g + w) * (DM * 2) + t * 4;
#pragma unroll
            for (int i = 0; i < 32; i++) acc[i] = 0.f;
            redo<KS3, 8, 16, DM * 32, FH * 32, 16>(acc, xr, (const uint8_t*)P.w_in + g * (FH * 4) + (((9 * j + 1) >> 1) + 36) * 128 + t * 4,
                                              [&](uint32_t* a, int k) {
#pragma unroll
                                                for (int e = 0; e < 4; e++) a[e] = hfma2(a[e], (e & 1) ? ns1 : ns0, (e & 1) ? nb1 : nb0);
                                                stg128(rd + k * 256, a[0], a[1], a[2], a[3]);
                                              });
#pragma unroll
            for (int k = 0; k < 36; k++) { const uint4 v = ldcg128(rd + k * 256); xA[k][0] = v.x; xA[k][1] = v.y; xA[k][2] = v.z; xA[k][3] = v.w; }
          }
        }
        float sm[4] = {0.f, 0.f, 0.f, 0.f}, qq[4] = {0.f, 0.f, 0.f, 0.f};
        auto gelu = [&](auto nz2) {
          constexpr int NZ2 = nz2.value, R = 8 - NZ2, N = 8, D = NZ2 == 8 ? GM2 : NZ2 ? GMM : GM1;
          float th[32], gb = GB;
          uint32_t qa = 0, qb = 0;
          auto head = [&](int G) {
#pragma unroll
            for (int e = 0; e < 4; e++) { const float v = acc[4 * G + e]; th[4 * G + e] = tanh_fast(v * fmaf(v, v, gb)); }
          };
#pragma unroll
          for (int i = 0; i < D; i++) head((i + R) & 7);
#pragma unroll
          for (int i = 0; i < N; i++) {
            const int G = (i + R) & 7;
            if (i + D < N) head((i + D + R) & 7);
            float* z = acc + 4 * G;
#pragma unroll
            for (int e = 0; e < 4; e++) z[e] = fmaf(z[e], th[4 * G + e], z[e]);
            uint32_t pa = pack2(z[0], z[1]), pb = pack2(z[2], z[3]), tok;
            if (i < NZ2) {
#pragma unroll
              for (int e = 0; e < 4; e++) { sm[e] += z[e]; qq[e] = fmaf(z[e], z[e], qq[e]); }
              pa = hsub2(pa, off2); pb = hsub2(pb, off2);
              stg32(zd + i * 128, pa); stg32(zd + i * 128 + 9216, pb);
              tok = pa ^ pb ^ __float_as_uint(qq[1]);
            } else {
              if (NZ2 && G == 3) sts128(sb + SM_STG + tid * 16, qa, qb, pa, pb);
              else if (G & 1) stg128(z1d + (G >> 1) * 2048 + (NZ2 ? 24576 : 0), qa, qb, pa, pb);
              qa = pa; qb = pb;
              tok = pa ^ pb;
            }
            gb = __uint_as_float(tok * P.zero + __float_as_uint(GB));
          }
        };
        auto done = [&](int p) {
          wgmma_wait<0>();
          release(c.s);
          c.next();
          TRC(tr && p == 4, w, tb + 7);
          TRC(tr && p == 8, w, tb + 11);
          MCLK(p == 8, 6);
          SCLK(2 * p + 1);
          QCLK(10 + 3 * p);
        };
        auto pass = [&](int p, uint32_t dhi) {
          SCLK(2 * p);
          QCLK(8 + 3 * p);
          bwait(dhi, w);
          bar_sync(6 + w, 256);
          TRC(tr && p == 5, w, tb + 10);
          wgmma_fence();
#pragma unroll
          for (int kk = 0; kk < 36; kk++) mma(kk, PP3, w == 0 || p < 8);
          done(p);
        };
        done(0);
#pragma unroll 1
        for (int p = 1; p < 5; p++) {
          gelu(Int<8>{});
          zd += 1024;
          pass(p, p == 4 ? 0x80000040u : 0x40000040u);
        }
        gelu(Int<4>{});
        signal(EV_ZN);
        {
          const float a0 = qsum(sm[0] + sm[1]), a1 = qsum(sm[2] + sm[3]), q0 = qsum(qq[0] + qq[1]), q1 = qsum(qq[2] + qq[3]);
          const float ss = t ? a1 : a0, m = ss * (1.f / 288.f);
          ll_st128_if(t < 2, P.s->ZST + (rb * 2 + w) * 512 + j * 64 + 16 * q + 8 * t + g, m - blo(off2), fmaxf((t ? q1 : q0) - ss * m, 0.f), tag);
        }
        TRC(tr, w, tb + 8);
        TRC(tr, w, tb + 9);
#pragma unroll 1
        for (int p = 5;; p++) {
          pass(p, 0x40000040u);
          if (p == 8) break;
          gelu(Int<0>{});
          z1d += 8192;
        }
        signal(EV_Z1);
#pragma unroll
        for (int i = 0; i < 16; i++) zk[i] = pack2(acc[2 * i], acc[2 * i + 1]);
        SCLK(18);
        TRC(tr, w, tb + 12);
      }
      uint32_t hA[18][4];
      {
        float acc[144];
        const float c0 = __uint_as_float(lds32(sb + SM_OFF + 4));
#pragma unroll
        for (int i = 0; i < 144; i++) {
          asm volatile("fma.rn.f32 %0, %1, %2, %3;" : "=f"(acc[i]) : "f"(__uint_as_float(P.zero)), "f"((float)(i + 2)), "f"(c0));
        }
        uint32_t prev = 0;
        auto stage = [&](int kb, auto odd) {
          mbar_wait_c(bars + B_FULL + c.s * 8, c.ph);
          TRC(tr && kb == 0, w, tb + 13);
          SCLK(22 + kb);
          const uint32_t st = sb + c.s * ST_BYTES, rt = sb + SM_RT + kb * 128 + t * 8;
          uint64_t db = dsc2(dlo(st + ST_B, 4608), 0, 8 + P.zero);
          uint32_t a[4][4];
#pragma unroll
          for (int kk = 0; kk < 4; kk++) {
            uint32_t r[4];
            ldsm4(r, st + (aoff ^ (kk << 5)));
            const uint2 sc = lds64(rt + kk * 32);
            a[kk][0] = hmul2(__byte_perm(r[0], r[2], 0x5410), sc.x); a[kk][2] = hmul2(__byte_perm(r[0], r[2], 0x7632), sc.y);
            a[kk][1] = hmul2(__byte_perm(r[1], r[3], 0x5410), sc.x); a[kk][3] = hmul2(__byte_perm(r[1], r[3], 0x7632), sc.y);
          }
          if (!odd.value) {
            const float x = blo(zk[0]), y = bhi(zk[0]);
#pragma unroll
            for (int i = 0; i < 15; i++) zk[i] = zk[i + 1];
            zk[15] = pack2(fmaf(x, tanh_fast(x * fmaf(x, x, GB)), x), fmaf(y, tanh_fast(y * fmaf(y, y, GB)), y));
          }
          wgmma_fence();
#pragma unroll
          for (int i = 0; i < 8; i++) {
            const int kk = i & 3, hf = i >> 2;
            wgmma_rs_n144(acc + hf * 72, a[kk], db, 1);
            dadd(db, i == 3 ? 144u - 3 * 576 : 576 + P.zero);
            if (i == 0) { wgmma_commit(); wgmma_wait<1>(); release_if(kb, prev); }
            if (i == 3) wgmma_commit();
          }
          wgmma_commit();
          prev = c.s; c.next();
        };
        mbar_wait_c(bars + B_RT, L);
#pragma unroll 1
        for (int kb = 0; kb < 32; kb += 2) {
          if (kb == 8) mbar_wait_c(bars + B_RT1, L);
          MCLK((kb & 7) == 4, 10 + (kb >> 3));
          stage(kb, Int<0>{});
          stage(kb + 1, Int<1>{});
        }
        if (w == 1) bar_arrive(6, 256);
        HCLK(0);
        mbar_wait_c(bars + B_CV + w * 8, L);
        HCLK(1);
        const float gk = 0.5f / GA;
        const float c1 = __uint_as_float(lds32(sb + SM_OFF + 4));
        const float gb0 = -gk * (c1 + __uint_as_float(lds32(sb + SM_CV + w * 256 + (16 * q + g) * 4))), gb1 = -gk * (c1 + __uint_as_float(lds32(sb + SM_CV + w * 256 + (16 * q + g + 8) * 4)));
        mbar_wait_c(w ? bars + B_FULL + c.s * 8 : bars + B_ZB, w ? c.ph : L);
        HCLK(2);
        const uint32_t sx = c.s;
        c.next();
        const uint32_t zt = sb + tid * 16, zs = zt + sx * ST_BYTES + w * 24576;
        uint4 zz[18];
        auto zload = [&](int u) {
          if (ZW && u == ZW && P.zero) __nanosleep(0);
          if (u >= 12 && u < 16) zz[u] = make_uint4(zk[4 * u - 48], zk[4 * u - 47], zk[4 * u - 46], zk[4 * u - 45]); else zz[u] = lds128(u == 17 ? zt + SM_STG : zs + (u < 12 ? u : 12) * 2048);
        };
#pragma unroll
        for (int u = 0; u < ZA; u++) zload(u);
#pragma unroll
        for (int u = 0; u < 18; u++) {
          if (u == 0) { wgmma_wait<1>(); HCLK(3); }
          if (u == 9) {
            HCLK(4);
            wgmma_wait<0>();
            HCLK(5);
            release(prev);
            mbar_arrive_if(L == 0 && lane == 0, ev + EV_P4 * 8);
            TRC(tr, w, tb + 14);
            SCLK(54);
          }
          if (u + ZA < 18) zload(u + ZA);
          const uint4 z = zz[u];
          hA[u][0] = hmul2(z.x, pack2(fmaf(acc[8 * u], gk, gb0), fmaf(acc[8 * u + 1], gk, gb0)));
          hA[u][1] = hmul2(z.y, pack2(fmaf(acc[8 * u + 2], gk, gb1), fmaf(acc[8 * u + 3], gk, gb1)));
          hA[u][2] = hmul2(z.z, pack2(fmaf(acc[8 * u + 4], gk, gb0), fmaf(acc[8 * u + 5], gk, gb0)));
          hA[u][3] = hmul2(z.w, pack2(fmaf(acc[8 * u + 6], gk, gb1), fmaf(acc[8 * u + 7], gk, gb1)));
        }
        uint32_t dep = P.zero;
#pragma unroll
        for (int u = 0; u < 18; u++) dep &= hA[u][0];
        release(sx, dep);
        TRC(tr, w, tb + 15);
        HCLK(6);
      }
      {
        const uint32_t el = elect_one();
#pragma unroll 1
        for (int p = 0; p < 9; p++) {
          float acc[32];
          if (w == 0) mbar_wait_c(bars + B_FULL + c.s * 8, c.ph);
          uint64_t db = dsc2(dlo(sb + c.s * ST_BYTES + ST_B + (j & 1) * 4096, 0), 0, 0x40000040u + P.zero);
          HCLK(7 + 2 * p);
          bar_sync(6 + w, 256);
          wgmma_fence();
#pragma unroll
          for (int kk = 0; kk < 18; kk++) {
            wgmma_rs_n64(acc, hA[kk], db, kk != 0);
            dadd(db, kk == 15 ? 128 - (j & 1) * (36864 >> 4) : 128 + P.zero);
            if (kk == PPK && (w == 0 || p < 8)) bar_arrive(7 - w, 256);
          }
          wgmma_commit();
          const uint32_t d = sb + (p & 3) * ST_BYTES, cb = p + j >= 9 ? p + j - 9 : p + j;
          if (el) asm volatile("cp.async.bulk.wait_group.read 3;" ::: "memory");
          __syncwarp();
          wgmma_wait<0>();
          HCLK(8 + 2 * p);
          MCLK(p == 1 || p == 8, 7 + (p >> 3));
          TRC(tr && p == 8, w, tb + 16);
          release_if(L == 0 || p < 5, c.s);
          c.next();
#pragma unroll
          for (int u = 0; u < 4; u++)
            stsm4(d + (aoff ^ (u << 5)), pack2(acc[8 * u], acc[8 * u + 1]), pack2(acc[8 * u + 2], acc[8 * u + 3]), pack2(acc[8 * u + 4], acc[8 * u + 5]), pack2(acc[8 * u + 6], acc[8 * u + 7]));
          fence_async_s();
          __syncwarp();
          tma3d_red_p(el, &P.red[L], cb * 64, rb * 64 + q * 16, w, d + w * 8192 + q * 2048);
          TRC(tr && p == 8, w, tb + 17);
        }
        if (el) asm volatile("cp.async.bulk.wait_group 0;" ::: "memory");
        HCLK(25);
        MCLK(1, 9);
        if (L == 0) signal(EV_PT);
        TRC(tr, w, tb + 18);
      }
    }
  }
}

typedef CUresult (*EncodeFn)(CUtensorMap*, CUtensorMapDataType, cuuint32_t, void*, const cuuint64_t*, const cuuint64_t*, const cuuint32_t*,
                             const cuuint32_t*, CUtensorMapInterleave, CUtensorMapSwizzle, CUtensorMapL2promotion, CUtensorMapFloatOOBfill);

static void make_map(EncodeFn fn, CUtensorMap* m, const void* ptr, int rank, uint64_t d0, uint64_t d1, uint64_t d2, uint64_t s1, uint64_t s2,
                     uint32_t b0, uint32_t b1, uint32_t b2, CUtensorMapSwizzle swz) {
  cuuint64_t dims[3] = {d0, d1, d2}, strides[2] = {s1, s2};
  cuuint32_t box[3] = {b0, b1, b2}, es[3] = {1, 1, 1};
  fn(m, CU_TENSOR_MAP_DATA_TYPE_BFLOAT16, rank, const_cast<void*>(ptr), dims, strides, box, es, CU_TENSOR_MAP_INTERLEAVE_NONE, swz,
     CU_TENSOR_MAP_L2_PROMOTION_L2_128B, CU_TENSOR_MAP_FLOAT_OOB_FILL_NONE);
}

}

extern "C" void kernel_launch(void* const* d_in, const int* in_sizes, int n_in, void* d_out, int out_size) {
  using namespace mk;
  (void)in_sizes; (void)n_in; (void)out_size;
  static EncodeFn fn = nullptr;
  static Scratch* sc;
  if (!fn) {
    cudaGetSymbolAddress((void**)&sc, g_scratch);
    cudaDriverEntryPointQueryResult qr;
    cudaGetDriverEntryPoint("cuTensorMapEncodeTiled", (void**)&fn, cudaEnableDefault, &qr);
    cudaFuncSetAttribute(mega_kernel, cudaFuncAttributeMaxDynamicSharedMemorySize, SM_TOTAL);
  }
  Params p;
  p.wqkv = (const __nv_bfloat16*)d_in[1];
  p.w_in = (const __nv_bfloat16*)d_in[4];
  p.w_sp = (const __nv_bfloat16*)d_in[5];
  p.b_sp = (const __nv_bfloat16*)d_in[6];
  p.w_out = (const __nv_bfloat16*)d_in[7];
  p.zero = 0;
  p.s = sc;
  p.xs[0] = (uint8_t*)d_in[0];
  p.xs[1] = sc->X;
  p.xs[2] = (uint8_t*)d_out;
  make_map(fn, &p.wsp, p.w_sp, 3, 2048, 1024, 2, 8192, 4096, 64, 64, 2, CU_TENSOR_MAP_SWIZZLE_128B);
  for (int i = 0; i < 2; i++) {
    make_map(fn, &p.red[i], p.xs[i + 1], 3, DM, 1024, 2, 2304, 1152, 64, 16, 1, CU_TENSOR_MAP_SWIZZLE_128B);
    make_map(fn, &p.res[i], p.xs[i], 3, DM, 1024, 2, 2304, 1152, 144, 64, 1, CU_TENSOR_MAP_SWIZZLE_NONE);
  }
  make_map(fn, &p.psn, d_out, 3, DM, 1024, 2, 2304, 1152, 144, 4, 1, CU_TENSOR_MAP_SWIZZLE_NONE);
  for (int i = 0; i < 3; i++) make_map(fn, &p.act[i], p.xs[i], 3, DM, 1024, 2, 2304, 1152, 64, 64, 1, CU_TENSOR_MAP_SWIZZLE_128B);
  {
    cuuint64_t dims[4] = {8, 8, 72, 72}, strides[3] = {1152, 16, 9216};
    cuuint32_t box[4] = {8, 8, 9, 5}, es[4] = {1, 1, 1, 1};
    fn(&p.wo8, CU_TENSOR_MAP_DATA_TYPE_BFLOAT16, 4, d_in[2], dims, strides, box, es, CU_TENSOR_MAP_INTERLEAVE_NONE, CU_TENSOR_MAP_SWIZZLE_NONE,
       CU_TENSOR_MAP_L2_PROMOTION_L2_128B, CU_TENSOR_MAP_FLOAT_OOB_FILL_NONE);
  }
  for (int i = 0; i < 2; i++) {
    cuuint64_t dims[4] = {i ? 4608u : 2304u, 8, i ? 1u : 2u, 72}, strides[3] = {9216, 4608, 8 * 9216};
    cuuint32_t box[4] = {i ? 64u : 32u, 8, i ? 1u : 2u, 18}, es[4] = {1, 1, 1, 1};
    fn(i ? &p.win64 : &p.win, CU_TENSOR_MAP_DATA_TYPE_BFLOAT16, 4, d_in[4], dims, strides, box, es, CU_TENSOR_MAP_INTERLEAVE_NONE,
       i ? CU_TENSOR_MAP_SWIZZLE_128B : CU_TENSOR_MAP_SWIZZLE_64B, CU_TENSOR_MAP_L2_PROMOTION_L2_128B, CU_TENSOR_MAP_FLOAT_OOB_FILL_NONE);
  }
  make_map(fn, &p.wout, p.w_out, 2, 576, 2304, 1, 1152, 0, 64, 144, 1, CU_TENSOR_MAP_SWIZZLE_128B);
  mega_kernel<<<NGRID, 384, SM_TOTAL, cudaStreamPerThread>>>(p);
}
```

```cpp
#include <cuda_runtime.h>
#include <cuda.h>
#include <cuda_bf16.h>
#include <stdint.h>

#define MK_TRACE 0
#define MK_DBG 0
#define P5TRACE 0
#define LAG1 3
#define PP3 34
#define PP30 33
#define SPL 2
#define NAP 200
#define NAP0 8000
#define KS2 1
#define KS3 1
#define RL3 21
#define PAD 0
#define ZA 4
#define ZW 13
#define GA3 10
#define GB3 12
#define GM2 1
#define GMM 1
#define GM1 2
#define C0S 32.f
#define OFA 0.125f
#define OFK 2.f
#define PPK 16

namespace mk {

constexpr int SEQ = 2048, DM = 576, FH = 2304;
constexpr int NCTA = 128;
constexpr int NGRID = 132;
constexpr uint32_t ZB = 36864;
constexpr uint32_t WQ_SL = 72 * 3456;
constexpr uint32_t WO_SL = 72 * 1152;
constexpr float LN_EPS = 1e-5f;
constexpr float GA = 0.3292034911525734f, GB = 2.423681954311584f;

constexpr uint32_t ST_BYTES = 53248, ST_B = 16384, NST = 4;
constexpr uint32_t SM_STG = NST * ST_BYTES;
constexpr uint32_t SM_BAR = SM_STG + 2 * 9216;
constexpr uint32_t SM_OFF = SM_BAR + 1008;
constexpr uint32_t SM_TOTAL = SM_BAR + 1024;
constexpr uint32_t SM_RT = SM_STG + 4096, SM_CV = SM_STG + 12288, SM_WT = SM_CV + 512;
constexpr uint32_t SM_WOI = 44032, SM_CSQ = 49792, SM_XST = 50688;
constexpr uint32_t B_FULL = 0, B_EMPTY = 32, B_FULLA = 64, B_RES = 128, B_WT = 144, B_IMG = 160, B_WOI = 168, B_ZB = 176, B_GATE3 = 184, B_Z1 = 192, B_LAG = 200,
                   B_RT = 208, B_CSQ = 216, B_CV = 224, B_AD = 240, B_EVT = 272, B_RT1 = 368, B_XS = 624, B_XRW = 384, B_FA3 = 400, B_EA3 = 544;
enum { EV_PT = 0, EV_O = 1, EV_X1 = 2, EV_ZN = 3, EV_Z1 = 4, EV_P4 = 5, EV_N = 6 };

enum { FR_X2 = 0, FR_O = 1, FR_X1 = 3, FR_EP = 16, FJ = 32 * 32, FJ_WQ = 0, FJ_WO = 1, FJ_WQ0 = 2, FJ_ZN = 3, FJ_P4 = 5, FJ_EP = 16, F_N = FJ + 8 * 32 };

constexpr uint32_t POISON = 0xffffffffu;
struct Scratch {
  uint32_t flags[F_N];
  uint2 RT[SEQ];
  uint4 XST[2 * SEQ];
  uint4 ST1[SEQ * 8], ZST[SEQ * 8], HALO[32 * 8 * 6 * 32];
  float CSP[2 * NCTA * 216];
  uint8_t WQ[8 * WQ_SL], WO[8 * WO_SL];
  uint8_t O[32 * 2 * ZB];
  uint8_t X[SEQ * DM * 2];
  uint8_t Z[512 * ZB];
  uint4 RD[NCTA * 36 * 256];
};
__device__ __align__(1024) Scratch g_scratch;
#define SLOW(i) do {} while (0)

struct Params {
  const __nv_bfloat16 *wqkv;
  Scratch* s;
  uint32_t zero;
  const __nv_bfloat16 *w_in, *w_sp, *b_sp, *w_out;
  uint8_t* xs[3];
  CUtensorMap wo8, wsp, win, win64, wout;
  CUtensorMap act[3];
  CUtensorMap res[2];
  CUtensorMap red[2];
  CUtensorMap psn;
};

__device__ __forceinline__ uint32_t smem_u32(const void* p) { return (uint32_t)__cvta_generic_to_shared(p); }
__device__ __forceinline__ void mbar_init(uint32_t bar, uint32_t cnt) { asm volatile("mbarrier.init.shared::cta.b64 [%0], %1;" ::"r"(bar), "r"(cnt)); }
__device__ __forceinline__ void mbar_arrive(uint32_t bar) { asm volatile("mbarrier.arrive.shared::cta.b64 _, [%0];" ::"r"(bar) : "memory"); }
__device__ __forceinline__ void mbar_wait(uint32_t bar, uint32_t parity) {
  asm volatile(
      "{\n.reg .pred p;\n.reg .u32 c;\nmov.u32 c, 0;\nLAB_WAIT:\n"
      "mbarrier.try_wait.parity.shared::cta.b64 p, [%0], %1;\n@p bra LAB_DONE;\n"
      "add.u32 c, c, 1;\nsetp.lt.u32 p, c, 0x100000;\n@p bra LAB_WAIT;\ntrap;\nLAB_DONE:\n}" ::"r"(bar), "r"(parity)
      : "memory");
}
__device__ __forceinline__ void mbar_wait_c(uint32_t bar, uint32_t parity) {
  asm volatile("{\n.reg .pred p;\nLAB_WAIT:\nmbarrier.try_wait.parity.shared::cta.b64 p, [%0], %1;\n@!p bra LAB_WAIT;\n}" ::"r"(bar), "r"(parity) : "memory");
}
__device__ __forceinline__ void flag_wait(const uint32_t* f, uint32_t target) {
  asm volatile(
      "{\n.reg .pred p;\n.reg .u32 c, v;\nmov.u32 c, 0;\nLAB_WAIT:\n"
      "ld.relaxed.gpu.global.u32 v, [%0];\nsub.u32 v, v, %1;\nsetp.ge.s32 p, v, 0;\n@p bra LAB_DONE;\n"
      "add.u32 c, c, 1;\nsetp.lt.u32 p, c, 0x400000;\n@p bra LAB_WAIT;\ntrap;\nLAB_DONE:\nfence.acquire.gpu;\n}" ::"l"(f), "r"(target)
      : "memory");
}
__device__ __forceinline__ void fence_gpu() { asm volatile("fence.acq_rel.gpu;" ::: "memory"); }
__device__ __forceinline__ void fence_async_g() { asm volatile("fence.proxy.async.global;" ::: "memory"); }
__device__ __forceinline__ void fence_async_s() { asm volatile("fence.proxy.async.shared::cta;" ::: "memory"); }
__device__ __forceinline__ uint32_t elect_one() {
  uint32_t p; asm volatile("{\n.reg .pred P;\nelect.sync _|P, 0xffffffff;\nselp.u32 %0, 1, 0, P;\n}" : "=r"(p)); return p;
}
__device__ __forceinline__ void expect_tx_p(uint32_t el, uint32_t bar, uint32_t bytes) {
  asm volatile("{\n.reg .pred P;\nsetp.ne.u32 P, %2, 0;\n@P mbarrier.arrive.expect_tx.shared::cta.b64 _, [%0], %1;\n}" ::"r"(bar), "r"(bytes), "r"(el) : "memory");
}
__device__ __forceinline__ void bulk_load_p(uint32_t el, uint32_t dst, const void* src, uint32_t bytes, uint32_t bar) {
  asm volatile("{\n.reg .pred P;\nsetp.ne.u32 P, %4, 0;\n@P cp.async.bulk.shared::cluster.global.mbarrier::complete_tx::bytes [%0], [%1], %2, [%3];\n}" ::"r"(dst), "l"(src), "r"(bytes), "r"(bar), "r"(el) : "memory");
}
__device__ __forceinline__ uint64_t policy_evict_first() { uint64_t p; asm("createpolicy.fractional.L2::evict_first.b64 %0, 1.0;" : "=l"(p)); return p; }
__device__ __forceinline__ void bulk_load_h(uint32_t el, uint32_t dst, const void* src, uint32_t bytes, uint32_t bar, bool ef, uint64_t pol) {
  if (ef) {
    asm volatile("{\n.reg .pred P;\nsetp.ne.u32 P, %4, 0;\n@P cp.async.bulk.shared::cluster.global.mbarrier::complete_tx::bytes.L2::cache_hint [%0], [%1], %2, [%3], %5;\n}" ::"r"(dst), "l"(src), "r"(bytes), "r"(bar), "r"(el), "l"(pol) : "memory");
  } else {
    asm volatile("{\n.reg .pred P;\nsetp.ne.u32 P, %4, 0;\n@P cp.async.bulk.shared::cluster.global.mbarrier::complete_tx::bytes [%0], [%1], %2, [%3];\n}" ::"r"(dst), "l"(src), "r"(bytes), "r"(bar), "r"(el) : "memory");
  }
}
__device__ __forceinline__ void bulk_mc_h(uint32_t el, uint32_t dst, const void* src, uint32_t bytes, uint32_t bar, bool ef, uint64_t pol) {
  if (ef) {
    asm volatile("{\n.reg .pred P;\nsetp.ne.u32 P, %4, 0;\n@P cp.async.bulk.shared::cluster.global.mbarrier::complete_tx::bytes.multicast::cluster.L2::cache_hint [%0], [%1], %2, [%3], %5, %6;\n}" ::"r"(dst), "l"(src), "r"(bytes), "r"(bar), "r"(el), "h"((uint16_t)3), "l"(pol) : "memory");
  } else {
    asm volatile("{\n.reg .pred P;\nsetp.ne.u32 P, %4, 0;\n@P cp.async.bulk.shared::cluster.global.mbarrier::complete_tx::bytes.multicast::cluster [%0], [%1], %2, [%3], %5;\n}" ::"r"(dst), "l"(src), "r"(bytes), "r"(bar), "r"(el), "h"((uint16_t)3) : "memory");
  }
}
__device__ __forceinline__ void tma3d_h(uint32_t el, uint32_t dst, const CUtensorMap* m, int c0, int c1, int c2, uint32_t bar, bool ef, uint64_t pol) {
  if (ef) {
    asm volatile("{\n.reg .pred P;\nsetp.ne.u32 P, %6, 0;\n@P cp.async.bulk.tensor.3d.shared::cluster.global.mbarrier::complete_tx::bytes.L2::cache_hint [%0], [%1, {%3, %4, %5}], [%2], %7;\n}" ::"r"(dst), "l"(m), "r"(bar), "r"(c0), "r"(c1), "r"(c2), "r"(el), "l"(pol) : "memory");
  } else {
    asm volatile("{\n.reg .pred P;\nsetp.ne.u32 P, %6, 0;\n@P cp.async.bulk.tensor.3d.shared::cluster.global.mbarrier::complete_tx::bytes [%0], [%1, {%3, %4, %5}], [%2];\n}" ::"r"(dst), "l"(m), "r"(bar), "r"(c0), "r"(c1), "r"(c2), "r"(el) : "memory");
  }
}
__device__ __forceinline__ void tma2d_mc_h(uint32_t el, uint32_t dst, const CUtensorMap* m, int c0, int c1, uint32_t bar, bool ef, uint64_t pol) {
  if (ef) {
    asm volatile("{\n.reg .pred P;\nsetp.ne.u32 P, %5, 0;\n@P cp.async.bulk.tensor.2d.shared::cluster.global.mbarrier::complete_tx::bytes.multicast::cluster.L2::cache_hint [%0], [%1, {%3, %4}], [%2], %6, %7;\n}" ::"r"(dst), "l"(m), "r"(bar), "r"(c0), "r"(c1), "r"(el), "h"((uint16_t)3), "l"(pol) : "memory");
  } else {
    asm volatile("{\n.reg .pred P;\nsetp.ne.u32 P, %5, 0;\n@P cp.async.bulk.tensor.2d.shared::cluster.global.mbarrier::complete_tx::bytes.multicast::cluster [%0], [%1, {%3, %4}], [%2], %6;\n}" ::"r"(dst), "l"(m), "r"(bar), "r"(c0), "r"(c1), "r"(el), "h"((uint16_t)3) : "memory");
  }
}
__device__ __forceinline__ void tma4d_mc(uint32_t el, uint32_t dst, const CUtensorMap* m, int c0, int c3, uint32_t bar, uint64_t pol) {
  asm volatile("{\n.reg .pred P;\nsetp.ne.u32 P, %5, 0;\n@P cp.async.bulk.tensor.4d.shared::cluster.global.mbarrier::complete_tx::bytes.multicast::cluster.L2::cache_hint [%0], [%1, {%3, 0, 0, %4}], [%2], %6, %7;\n}" ::"r"(dst), "l"(m), "r"(bar), "r"(c0), "r"(c3), "r"(el), "h"((uint16_t)3), "l"(pol) : "memory");
}
__device__ __forceinline__ void mbar_arrive_cluster(uint32_t addr) { asm volatile("mbarrier.arrive.shared::cluster.b64 _, [%0];" ::"r"(addr) : "memory"); }
__device__ __forceinline__ void mbar_arrive_cluster_if(bool c, uint32_t addr) {
  asm volatile("{\n.reg .pred P;\nsetp.ne.u32 P, %1, 0;\n@P mbarrier.arrive.shared::cluster.b64 _, [%0];\n}" ::"r"(addr), "r"((uint32_t)c) : "memory");
}
__device__ __forceinline__ void mbar_arrive_if(bool c, uint32_t addr) {
  asm volatile("{\n.reg .pred P;\nsetp.ne.u32 P, %1, 0;\n@P mbarrier.arrive.shared::cta.b64 _, [%0];\n}" ::"r"(addr), "r"((uint32_t)c) : "memory");
}
__device__ __forceinline__ uint32_t mapa(uint32_t addr, uint32_t rank) { uint32_t r; asm("mapa.shared::cluster.u32 %0, %1, %2;" : "=r"(r) : "r"(addr), "r"(rank)); return r; }
__device__ __forceinline__ void bulk_store_p(uint32_t el, void* dst, uint32_t src, uint32_t bytes) {
  asm volatile("{\n.reg .pred P;\nsetp.ne.u32 P, %3, 0;\n@P cp.async.bulk.global.shared::cta.bulk_group [%0], [%1], %2;\n}" ::"l"(dst), "r"(src), "r"(bytes), "r"(el) : "memory");
}
__device__ __forceinline__ void flag_release_p(uint32_t el, uint32_t* f) {
  asm volatile("{\n.reg .pred P;\nsetp.ne.u32 P, %1, 0;\n@P red.release.gpu.global.add.u32 [%0], 1;\n}" ::"l"(f), "r"(el) : "memory");
}
__device__ __forceinline__ void flag_add_p(uint32_t el, uint32_t* f) {
  asm volatile("{\n.reg .pred P;\nsetp.ne.u32 P, %1, 0;\n@P red.relaxed.gpu.global.add.u32 [%0], 1;\n}" ::"l"(f), "r"(el) : "memory");
}
__device__ __forceinline__ void prefetch_l2(const void* src, uint32_t bytes) { asm volatile("cp.async.bulk.prefetch.L2.global [%0], %1;" ::"l"(src), "r"(bytes) : "memory"); }
__device__ __forceinline__ void prefetch_map(const CUtensorMap* m) { asm volatile("prefetch.tensormap [%0];" ::"l"(m) : "memory"); }
__device__ __forceinline__ void wgmma_fence() { asm volatile("wgmma.fence.sync.aligned;" ::: "memory"); }
__device__ __forceinline__ void wgmma_commit() { asm volatile("wgmma.commit_group.sync.aligned;" ::: "memory"); }
template <int N> __device__ __forceinline__ void wgmma_wait() { asm volatile("wgmma.wait_group.sync.aligned %0;" ::"n"(N) : "memory"); }
__device__ __forceinline__ uint32_t dlo(uint32_t addr, uint32_t lbo) { return ((addr & 0x3FFFF) >> 4) + ((lbo >> 4) << 16); }
template <uint32_t SBO, uint32_t SWZ> __device__ __forceinline__ uint64_t dsc(uint32_t lo, uint32_t off) {
  uint64_t d; asm("mov.b64 %0, {%1, %2};" : "=l"(d) : "r"(lo + (off >> 4)), "n"((SBO >> 4) | (SWZ << 30))); return d;
}
__device__ __forceinline__ uint64_t dsc2(uint32_t lo, uint32_t off, uint32_t hi) {
  uint64_t d; asm("mov.b64 %0, {%1, %2};" : "=l"(d) : "r"(lo + (off >> 4)), "r"(hi)); return d;
}
__device__ __forceinline__ uint64_t dat(uint64_t d, uint32_t off, uint32_t one) { uint64_t r; asm("mad.wide.u32 %0, %1, %2, %3;" : "=l"(r) : "r"(one), "r"(off >> 4), "l"(d)); return r; }
__device__ __forceinline__ void dadd(uint64_t& d, uint32_t v) {
  asm("{\n.reg .b32 lo, hi;\nmov.b64 {lo, hi}, %0;\nadd.u32 lo, lo, %1;\nmov.b64 %0, {lo, hi};\n}" : "+l"(d) : "r"(v));
}
template <int R> __device__ __forceinline__ void reg_alloc() { asm volatile("setmaxnreg.inc.sync.aligned.u32 %0;" ::"n"(R)); }
template <int R> __device__ __forceinline__ void reg_dealloc() { asm volatile("setmaxnreg.dec.sync.aligned.u32 %0;" ::"n"(R)); }
__device__ __forceinline__ void bar_sync(int id, int n) { asm volatile("bar.sync %0, %1;" ::"r"(id), "r"(n) : "memory"); }
__device__ __forceinline__ void bar_arrive(int id, int n) { asm volatile("bar.arrive %0, %1;" ::"r"(id), "r"(n) : "memory"); }
__device__ __forceinline__ void ldsm4(uint32_t* r, uint32_t addr) {
  asm volatile("ldmatrix.sync.aligned.m8n8.x4.shared.b16 {%0,%1,%2,%3}, [%4];" : "=r"(r[0]), "=r"(r[1]), "=r"(r[2]), "=r"(r[3]) : "r"(addr) : "memory");
}
__device__ __forceinline__ uint32_t movm(uint32_t a) { uint32_t d; asm volatile("movmatrix.sync.aligned.m8n8.trans.b16 %0, %1;" : "=r"(d) : "r"(a)); return d; }
__device__ __forceinline__ void mma16(float* c, uint32_t a0, uint32_t a1, uint32_t a2, uint32_t a3, uint32_t b0, uint32_t b1) {
  asm volatile("mma.sync.aligned.m16n8k16.row.col.f32.bf16.bf16.f32 {%0,%1,%2,%3}, {%4,%5,%6,%7}, {%8,%9}, {%10,%10,%10,%10};"
               : "=f"(c[0]), "=f"(c[1]), "=f"(c[2]), "=f"(c[3]) : "r"(a0), "r"(a1), "r"(a2), "r"(a3), "r"(b0), "r"(b1), "f"(0.f));
}
__device__ __forceinline__ void mma8(float* c, uint32_t a0, uint32_t a1, uint32_t b0) {
  asm volatile("mma.sync.aligned.m16n8k8.row.col.f32.bf16.bf16.f32 {%0,%1,%2,%3}, {%4,%5}, {%6}, {%0,%1,%2,%3};"
               : "+f"(c[0]), "+f"(c[1]), "+f"(c[2]), "+f"(c[3]) : "r"(a0), "r"(a1), "r"(b0));
}
__device__ __forceinline__ void widen(float* c, uint32_t a0, uint32_t a1, uint32_t eye) {
  asm volatile("mma.sync.aligned.m16n8k8.row.col.f32.bf16.bf16.f32 {%0,%1,%2,%3}, {%4,%5}, {%6}, {%7,%7,%7,%7};"
               : "=f"(c[0]), "=f"(c[1]), "=f"(c[2]), "=f"(c[3]) : "r"(a0), "r"(a1), "r"(eye), "f"(0.f));
}
__device__ __forceinline__ float rsq_fast(float x) { float y; asm("rsqrt.approx.ftz.f32 %0, %1;" : "=f"(y) : "f"(x)); return y; }
__device__ __forceinline__ uint32_t pack2(float lo, float hi) { uint32_t r; asm("cvt.rn.bf16x2.f32 %0, %1, %2;" : "=r"(r) : "f"(hi), "f"(lo)); return r; }
__device__ __forceinline__ float blo(uint32_t v) { return __uint_as_float(v << 16); }
__device__ __forceinline__ float bhi(uint32_t v) { return __uint_as_float(v & 0xffff0000u); }
__device__ __forceinline__ float tanh_fast(float x) { float y; asm("tanh.approx.f32 %0, %1;" : "=f"(y) : "f"(x)); return y; }
__device__ __forceinline__ float rcp_fast(float x) { float y; asm("rcp.approx.ftz.f32 %0, %1;" : "=f"(y) : "f"(x)); return y; }
__device__ __forceinline__ float ex2(float x) { float y; asm("ex2.approx.ftz.f32 %0, %1;" : "=f"(y) : "f"(x)); return y; }
__device__ __forceinline__ float qsum(float v) { v += __shfl_xor_sync(~0u, v, 1); v += __shfl_xor_sync(~0u, v, 2); return v; }
__device__ __forceinline__ float qmax(float v) { v = fmaxf(v, __shfl_xor_sync(~0u, v, 1)); v = fmaxf(v, __shfl_xor_sync(~0u, v, 2)); return v; }
__device__ __forceinline__ void stg32(void* p, uint32_t v) { asm volatile("st.global.u32 [%0], %1;" ::"l"(p), "r"(v) : "memory"); }
__device__ __forceinline__ void stg128(void* p, uint32_t a, uint32_t b, uint32_t c, uint32_t d) { asm volatile("st.global.v4.u32 [%0], {%1,%2,%3,%4};" ::"l"(p), "r"(a), "r"(b), "r"(c), "r"(d) : "memory"); }
__device__ __forceinline__ uint32_t ldcg32(const void* p) { uint32_t v; asm volatile("ld.global.L1::no_allocate.u32 %0, [%1];" : "=r"(v) : "l"(p) : "memory"); return v; }
__device__ __forceinline__ uint32_t ldgpu32(const void* p) { uint32_t v; asm volatile("ld.relaxed.gpu.global.u32 %0, [%1];" : "=r"(v) : "l"(p) : "memory"); return v; }
__device__ __forceinline__ uint32_t ldca32(const void* p) { uint32_t v; asm volatile("ld.global.ca.u32 %0, [%1];" : "=r"(v) : "l"(p) : "memory"); return v; }
__device__ __forceinline__ void stg128_if(bool c, void* p, uint32_t a, uint32_t b, uint32_t cc, uint32_t d) {
  asm volatile("{\n.reg .pred P;\nsetp.ne.u32 P, %5, 0;\n@P st.global.v4.u32 [%0], {%1,%2,%3,%4};\n}" ::"l"(p), "r"(a), "r"(b), "r"(cc), "r"(d), "r"((uint32_t)c) : "memory");
}
__device__ __forceinline__ uint2 lds64(uint32_t a) { uint2 v; asm volatile("ld.shared.v2.u32 {%0,%1}, [%2];" : "=r"(v.x), "=r"(v.y) : "r"(a) : "memory"); return v; }
__device__ __forceinline__ uint4 ldcg128(const void* p) { uint4 v; asm volatile("ld.global.cg.v4.u32 {%0,%1,%2,%3}, [%4];" : "=r"(v.x), "=r"(v.y), "=r"(v.z), "=r"(v.w) : "l"(p) : "memory"); return v; }
__device__ __forceinline__ uint32_t ldnc16(const void* p) { uint16_t v; asm volatile("ld.global.nc.u16 %0, [%1];" : "=h"(v) : "l"(p)); return v; }
__device__ __forceinline__ uint4 ldnc128(const void* p) { uint4 v; asm volatile("ld.global.nc.v4.u32 {%0,%1,%2,%3}, [%4];" : "=r"(v.x), "=r"(v.y), "=r"(v.z), "=r"(v.w) : "l"(p)); return v; }
__device__ __forceinline__ uint32_t hsub2(uint32_t a, uint32_t b) { uint32_t d; asm("sub.rn.bf16x2 %0, %1, %2;" : "=r"(d) : "r"(a), "r"(b)); return d; }
__device__ __forceinline__ void stg32_if(bool c, void* p, uint32_t v) {
  asm volatile("{\n.reg .pred P;\nsetp.ne.u32 P, %2, 0;\n@P st.global.u32 [%0], %1;\n}" ::"l"(p), "r"(v), "r"((uint32_t)c) : "memory");
}
__device__ __forceinline__ uint32_t hmul2(uint32_t a, uint32_t b) { uint32_t d; asm("mul.rn.bf16x2 %0, %1, %2;" : "=r"(d) : "r"(a), "r"(b)); return d; }
__device__ __forceinline__ void sts32(uint32_t a, uint32_t v) { asm volatile("st.shared.u32 [%0], %1;" ::"r"(a), "r"(v) : "memory"); }
__device__ __forceinline__ uint32_t lds32(uint32_t a) { uint32_t v; asm volatile("ld.shared.u32 %0, [%1];" : "=r"(v) : "r"(a) : "memory"); return v; }
__device__ __forceinline__ void sts128(uint32_t a, uint32_t x, uint32_t y, uint32_t z, uint32_t w) { asm volatile("st.shared.v4.u32 [%0], {%1,%2,%3,%4};" ::"r"(a), "r"(x), "r"(y), "r"(z), "r"(w) : "memory"); }
__device__ __forceinline__ uint4 lds128(uint32_t a) { uint4 v; asm volatile("ld.shared.v4.u32 {%0,%1,%2,%3}, [%4];" : "=r"(v.x), "=r"(v.y), "=r"(v.z), "=r"(v.w) : "r"(a) : "memory"); return v; }
__device__ __forceinline__ void ll_st64(uint2* p, uint32_t v, uint32_t tag) {
  asm volatile("{\n.reg .b64 r;\nmov.b64 r, {%1,%2};\nst.relaxed.gpu.global.b64 [%0], r;\n}" ::"l"(p), "r"(v), "r"(tag) : "memory");
}
__device__ __forceinline__ uint2 ll_ld64(const uint2* p) {
  uint2 v; asm volatile("{\n.reg .b64 r;\nld.relaxed.gpu.global.b64 r, [%2];\nmov.b64 {%0,%1}, r;\n}" : "=r"(v.x), "=r"(v.y) : "l"(p) : "memory"); return v;
}
__device__ __forceinline__ void ll_st128(uint4* p, float a, float b, uint32_t tag, float c = 0.f) {
  asm volatile("{\n.reg .b128 r;\n.reg .b64 lo, hi;\nmov.b64 lo, {%1,%2};\nmov.b64 hi, {%3,%4};\nmov.b128 r, {lo, hi};\nst.relaxed.gpu.global.b128 [%0], r;\n}" ::"l"(p), "r"(__float_as_uint(a)), "r"(__float_as_uint(b)), "r"(tag), "r"(__float_as_uint(c)) : "memory");
}
__device__ __forceinline__ uint4 ll_ld128(const uint4* p) {
  uint4 v; asm volatile("{\n.reg .b128 r;\n.reg .b64 lo, hi;\nld.relaxed.gpu.global.b128 r, [%4];\nmov.b128 {lo, hi}, r;\nmov.b64 {%0,%1}, lo;\nmov.b64 {%2,%3}, hi;\n}" : "=r"(v.x), "=r"(v.y), "=r"(v.z), "=r"(v.w) : "l"(p) : "memory"); return v;
}
__device__ __forceinline__ void publish_p(uint32_t el, uint32_t* f) {
  asm volatile("{\n.reg .pred P;\nsetp.ne.u32 P, %1, 0;\n@P cp.async.bulk.commit_group;\n@P cp.async.bulk.wait_group 0;\n@P red.release.gpu.global.add.u32 [%0], 1;\n}" ::"l"(f), "r"(el) : "memory");
}
__device__ __forceinline__ void tma3d_red_p(uint32_t el, const CUtensorMap* m, int c0, int c1, int c2, uint32_t src) {
  asm volatile("{\n.reg .pred P;\nsetp.ne.u32 P, %5, 0;\n@P cp.reduce.async.bulk.tensor.3d.global.shared::cta.add.tile.bulk_group [%0, {%2, %3, %4}], [%1];\n}" ::"l"(m), "r"(src), "r"(c0), "r"(c1), "r"(c2), "r"(el) : "memory");
}
__device__ __forceinline__ void stsm4(uint32_t addr, uint32_t a, uint32_t b, uint32_t c, uint32_t d) {
  asm volatile("stmatrix.sync.aligned.m8n8.x4.shared.b16 [%0], {%1,%2,%3,%4};" ::"r"(addr), "r"(a), "r"(b), "r"(c), "r"(d) : "memory");
}
__device__ __forceinline__ void sts64(uint32_t a, uint32_t x, uint32_t y) { asm volatile("st.shared.v2.u32 [%0], {%1,%2};" ::"r"(a), "r"(x), "r"(y) : "memory"); }
__device__ __forceinline__ void ll_st128_if(bool on, uint4* p, float a, float b, uint32_t tag) {
  asm volatile("{\n.reg .pred P;\n.reg .b128 r;\n.reg .b64 lo, hi;\nsetp.ne.u32 P, %4, 0;\nmov.b64 lo, {%1,%2};\nmov.b64 hi, {%3,%3};\nmov.b128 r, {lo, hi};\n@P st.relaxed.gpu.global.b128 [%0], r;\n}" ::"l"(p), "r"(__float_as_uint(a)), "r"(__float_as_uint(b)), "r"(tag), "r"((uint32_t)on) : "memory");
}
__device__ __forceinline__ uint4 ldnc128_if(bool c, const void* p) {
  uint4 v = make_uint4(0u, 0u, 0u, 0u);
  asm volatile("{\n.reg .pred P;\nsetp.ne.u32 P, %5, 0;\n@P ld.global.nc.v4.u32 {%0,%1,%2,%3}, [%4];\n}" : "+r"(v.x), "+r"(v.y), "+r"(v.z), "+r"(v.w) : "l"(p), "r"((uint32_t)c));
  return v;
}
__device__ __forceinline__ uint32_t hfma2(uint32_t a, uint32_t b, uint32_t c) { uint32_t d; asm("fma.rn.bf16x2 %0, %1, %2, %3;" : "=r"(d) : "r"(a), "r"(b), "r"(c)); return d; }
__device__ __forceinline__ float2 lds64f(uint32_t a) { float2 v; asm volatile("ld.shared.v2.f32 {%0,%1}, [%2];" : "=f"(v.x), "=f"(v.y) : "r"(a) : "memory"); return v; }
#define TRC(cond, role, idx) do {} while (0)
#define TRV(role, idx, v) do {} while (0)

#define ACLK_INIT do {} while (0)
#define ACLK(i) do {} while (0)
#define ACLK_OUT do {} while (0)
#define QCLK(i) do {} while (0)
#define PH 1
#define RCLK(i) do {} while (0)
#define RCLK_INIT do {} while (0)
#define RCLK_OUT do {} while (0)
#define SCLK(i) do {} while (0)
#define HCLK(i) do {} while (0)
#define MCLK(c, i) do {} while (0)
#define CKK(i) do {} while (0)
#define CKK_OUT do {} while (0)
#define PL 1
#define PCLK(i) do {} while (0)
#define PQ 1
#define CLK_INIT do {} while (0)
#define CLK(i) do {} while (0)
#define CLK_OUT do {} while (0)

__device__ __forceinline__ void wgmma_ss_n216(float* d, uint64_t da, uint64_t db, int scaleD) {
  asm volatile("{\n.reg .pred p;\nsetp.ne.b32 p, %110, 0;\nwgmma.mma_async.sync.aligned.m64n216k16.f32.bf16.bf16 "
    "{%0,%1,%2,%3,%4,%5,%6,%7,%8,%9,%10,%11,%12,%13,%14,%15,%16,%17,%18,%19,%20,%21,%22,%23,%24,%25,%26,%27,%28,%29,%30,%31,%32,%33,%34,%35,%36,%37,%38,%39,%40,%41,%42,%43,%44,%45,%46,%47,%48,%49,%50,%51,%52,%53,%54,%55,%56,%57,%58,%59,%60,%61,%62,%63,%64,%65,%66,%67,%68,%69,%70,%71,%72,%73,%74,%75,%76,%77,%78,%79,%80,%81,%82,%83,%84,%85,%86,%87,%88,%89,%90,%91,%92,%93,%94,%95,%96,%97,%98,%99,%100,%101,%102,%103,%104,%105,%106,%107}, "
    "%108, %109, p, 1, 1, 0, 1;\n}\n"
    : "+f"(d[0]), "+f"(d[1]), "+f"(d[2]), "+f"(d[3]), "+f"(d[4]), "+f"(d[5]), "+f"(d[6]), "+f"(d[7]), "+f"(d[8]), "+f"(d[9]), "+f"(d[10]), "+f"(d[11]), "+f"(d[12]), "+f"(d[13]), "+f"(d[14]), "+f"(d[15]), "+f"(d[16]), "+f"(d[17]), "+f"(d[18]), "+f"(d[19]), "+f"(d[20]), "+f"(d[21]), "+f"(d[22]), "+f"(d[23]), "+f"(d[24]), "+f"(d[25]), "+f"(d[26]), "+f"(d[27]), "+f"(d[28]), "+f"(d[29]), "+f"(d[30]), "+f"(d[31]), "+f"(d[32]), "+f"(d[33]), "+f"(d[34]), "+f"(d[35]), "+f"(d[36]), "+f"(d[37]), "+f"(d[38]), "+f"(d[39]), "+f"(d[40]), "+f"(d[41]), "+f"(d[42]), "+f"(d[43]), "+f"(d[44]), "+f"(d[45]), "+f"(d[46]), "+f"(d[47]), "+f"(d[48]), "+f"(d[49]), "+f"(d[50]), "+f"(d[51]), "+f"(d[52]), "+f"(d[53]), "+f"(d[54]), "+f"(d[55]), "+f"(d[56]), "+f"(d[57]), "+f"(d[58]), "+f"(d[59]), "+f"(d[60]), "+f"(d[61]), "+f"(d[62]), "+f"(d[63]), "+f"(d[64]), "+f"(d[65]), "+f"(d[66]), "+f"(d[67]), "+f"(d[68]), "+f"(d[69]), "+f"(d[70]), "+f"(d[71]), "+f"(d[72]), "+f"(d[73]), "+f"(d[74]), "+f"(d[75]), "+f"(d[76]), "+f"(d[77]), "+f"(d[78]), "+f"(d[79]), "+f"(d[80]), "+f"(d[81]), "+f"(d[82]), "+f"(d[83]), "+f"(d[84]), "+f"(d[85]), "+f"(d[86]), "+f"(d[87]), "+f"(d[88]), "+f"(d[89]), "+f"(d[90]), "+f"(d[91]), "+f"(d[92]), "+f"(d[93]), "+f"(d[94]), "+f"(d[95]), "+f"(d[96]), "+f"(d[97]), "+f"(d[98]), "+f"(d[99]), "+f"(d[100]), "+f"(d[101]), "+f"(d[102]), "+f"(d[103]), "+f"(d[104]), "+f"(d[105]), "+f"(d[106]), "+f"(d[107])
    : "l"(da), "l"(db), "r"(scaleD));
}
__device__ __forceinline__ void wgmma_ss_n72(float* d, uint64_t da, uint64_t db, int scaleD) {
  asm volatile("{\n.reg .pred p;\nsetp.ne.b32 p, %38, 0;\nwgmma.mma_async.sync.aligned.m64n72k16.f32.bf16.bf16 "
    "{%0,%1,%2,%3,%4,%5,%6,%7,%8,%9,%10,%11,%12,%13,%14,%15,%16,%17,%18,%19,%20,%21,%22,%23,%24,%25,%26,%27,%28,%29,%30,%31,%32,%33,%34,%35}, "
    "%36, %37, p, 1, 1, 0, 1;\n}\n"
    : "+f"(d[0]), "+f"(d[1]), "+f"(d[2]), "+f"(d[3]), "+f"(d[4]), "+f"(d[5]), "+f"(d[6]), "+f"(d[7]), "+f"(d[8]), "+f"(d[9]), "+f"(d[10]), "+f"(d[11]), "+f"(d[12]), "+f"(d[13]), "+f"(d[14]), "+f"(d[15]), "+f"(d[16]), "+f"(d[17]), "+f"(d[18]), "+f"(d[19]), "+f"(d[20]), "+f"(d[21]), "+f"(d[22]), "+f"(d[23]), "+f"(d[24]), "+f"(d[25]), "+f"(d[26]), "+f"(d[27]), "+f"(d[28]), "+f"(d[29]), "+f"(d[30]), "+f"(d[31]), "+f"(d[32]), "+f"(d[33]), "+f"(d[34]), "+f"(d[35])
    : "l"(da), "l"(db), "r"(scaleD));
}
__device__ __forceinline__ void wgmma_rs_n144(float* d, const uint32_t* a, uint64_t db, int scaleD) {
  asm volatile("{\n.reg .pred p;\nsetp.ne.b32 p, %77, 0;\nwgmma.mma_async.sync.aligned.m64n144k16.f32.bf16.bf16 "
    "{%0,%1,%2,%3,%4,%5,%6,%7,%8,%9,%10,%11,%12,%13,%14,%15,%16,%17,%18,%19,%20,%21,%22,%23,%24,%25,%26,%27,%28,%29,%30,%31,%32,%33,%34,%35,%36,%37,%38,%39,%40,%41,%42,%43,%44,%45,%46,%47,%48,%49,%50,%51,%52,%53,%54,%55,%56,%57,%58,%59,%60,%61,%62,%63,%64,%65,%66,%67,%68,%69,%70,%71}, "
    "{%72,%73,%74,%75}, %76, p, 1, 1, 1;\n}\n"
    : "+f"(d[0]), "+f"(d[1]), "+f"(d[2]), "+f"(d[3]), "+f"(d[4]), "+f"(d[5]), "+f"(d[6]), "+f"(d[7]), "+f"(d[8]), "+f"(d[9]), "+f"(d[10]), "+f"(d[11]), "+f"(d[12]), "+f"(d[13]), "+f"(d[14]), "+f"(d[15]), "+f"(d[16]), "+f"(d[17]), "+f"(d[18]), "+f"(d[19]), "+f"(d[20]), "+f"(d[21]), "+f"(d[22]), "+f"(d[23]), "+f"(d[24]), "+f"(d[25]), "+f"(d[26]), "+f"(d[27]), "+f"(d[28]), "+f"(d[29]), "+f"(d[30]), "+f"(d[31]), "+f"(d[32]), "+f"(d[33]), "+f"(d[34]), "+f"(d[35]), "+f"(d[36]), "+f"(d[37]), "+f"(d[38]), "+f"(d[39]), "+f"(d[40]), "+f"(d[41]), "+f"(d[42]), "+f"(d[43]), "+f"(d[44]), "+f"(d[45]), "+f"(d[46]), "+f"(d[47]), "+f"(d[48]), "+f"(d[49]), "+f"(d[50]), "+f"(d[51]), "+f"(d[52]), "+f"(d[53]), "+f"(d[54]), "+f"(d[55]), "+f"(d[56]), "+f"(d[57]), "+f"(d[58]), "+f"(d[59]), "+f"(d[60]), "+f"(d[61]), "+f"(d[62]), "+f"(d[63]), "+f"(d[64]), "+f"(d[65]), "+f"(d[66]), "+f"(d[67]), "+f"(d[68]), "+f"(d[69]), "+f"(d[70]), "+f"(d[71])
    : "r"(a[0]), "r"(a[1]), "r"(a[2]), "r"(a[3]), "l"(db), "r"(scaleD));
}
__device__ __forceinline__ void wgmma_rs_n64(float* d, const uint32_t* a, uint64_t db, int scaleD) {
  asm volatile("{\n.reg .pred p;\nsetp.ne.b32 p, %37, 0;\nwgmma.mma_async.sync.aligned.m64n64k16.f32.bf16.bf16 "
    "{%0,%1,%2,%3,%4,%5,%6,%7,%8,%9,%10,%11,%12,%13,%14,%15,%16,%17,%18,%19,%20,%21,%22,%23,%24,%25,%26,%27,%28,%29,%30,%31}, "
    "{%32,%33,%34,%35}, %36, p, 1, 1, 1;\n}\n"
    : "+f"(d[0]), "+f"(d[1]), "+f"(d[2]), "+f"(d[3]), "+f"(d[4]), "+f"(d[5]), "+f"(d[6]), "+f"(d[7]), "+f"(d[8]), "+f"(d[9]), "+f"(d[10]), "+f"(d[11]), "+f"(d[12]), "+f"(d[13]), "+f"(d[14]), "+f"(d[15]), "+f"(d[16]), "+f"(d[17]), "+f"(d[18]), "+f"(d[19]), "+f"(d[20]), "+f"(d[21]), "+f"(d[22]), "+f"(d[23]), "+f"(d[24]), "+f"(d[25]), "+f"(d[26]), "+f"(d[27]), "+f"(d[28]), "+f"(d[29]), "+f"(d[30]), "+f"(d[31])
    : "r"(a[0]), "r"(a[1]), "r"(a[2]), "r"(a[3]), "l"(db), "r"(scaleD));
}

template <int V> struct Int { static constexpr int value = V; };
struct Cur {
  uint32_t s, ph;
  __device__ __forceinline__ void next() { if (++s == NST) { s = 0; ph ^= 1; } }
};

#define z1_block(rb, w, j) (P.s->Z + ((rb) * 16 + (w) * 8 + (j)) * ZB)
#define z2_block(kb, j) (P.s->Z + (256 + (kb) * 8 + (j)) * ZB)
#define o_block(rb, w) (P.s->O + ((rb) * 2 + (w)) * (2 * ZB))
__device__ __forceinline__ void combine8(float m0, float q0, float m1, float q1, float n, float eps, float& mean, float& rstd) {
  mean = qsum(m0 + m1) * 0.125f;
  float d0 = m0 - mean, d1 = m1 - mean;
  float M2 = qsum(q0 + q1 + n * (d0 * d0 + d1 * d1));
  rstd = rsq_fast(fmaf(M2, 0.125f / n, eps));
}
__device__ __forceinline__ void stat_get(const uint4* zs, uint32_t tag, float n, float eps, float& m0, float& r0, float& m1, float& r1) {
  uint4 a0, a1, b0, b1;
#pragma unroll 1
  for (int it = 0; it < (1 << 20); it++) {
    a0 = ll_ld128(zs); a1 = ll_ld128(zs + 64); b0 = ll_ld128(zs + 8); b1 = ll_ld128(zs + 72);
    if (__all_sync(~0u, a0.z == tag && a1.z == tag && b0.z == tag && b1.z == tag)) break;
  }
  combine8(__uint_as_float(a0.x), __uint_as_float(a0.y), __uint_as_float(a1.x), __uint_as_float(a1.y), n, eps, m0, r0);
  combine8(__uint_as_float(b0.x), __uint_as_float(b0.y), __uint_as_float(b1.x), __uint_as_float(b1.y), n, eps, m1, r1);
}

__device__ __forceinline__ void rows_fetch(uint32_t el, uint32_t xr, const uint8_t* src, uint32_t bar) {
  expect_tx_p(el, bar, 9216);
#pragma unroll 1
  for (int r = 0; r < 8; r++) bulk_load_p(el, xr + r * 1152, src + r * (DM * 4), 1152, bar);
}
__device__ __forceinline__ void rows_stats(uint32_t xr, uint4* dst, uint32_t tag, int lane) {
  float s[2] = {0.f, 0.f}, q[4] = {0.f, 0.f, 0.f, 0.f};
  const uint32_t a0 = xr + (lane >> 2) * 1152 + (((lane & 3) * 2) ^ (lane >> 2)) * 16;
  uint4 n0 = lds128(a0), n1 = lds128(a0 ^ 16);
#pragma unroll 1
  for (int e = 1; e <= 9; e++) {
    const uint32_t x[8] = {n0.x, n0.y, n0.z, n0.w, n1.x, n1.y, n1.z, n1.w};
    if (e < 9) { n0 = lds128(a0 + e * 128); n1 = lds128((a0 ^ 16) + e * 128); }
#pragma unroll
    for (int u = 0; u < 8; u++) {
      const float lo = blo(x[u]), hi = bhi(x[u]);
      s[u & 1] += lo + hi; q[(u & 1) * 2] = fmaf(lo, lo, q[(u & 1) * 2]); q[(u & 1) * 2 + 1] = fmaf(hi, hi, q[(u & 1) * 2 + 1]);
    }
  }
  const float sx = s[0] + s[1], sq = (q[0] + q[1]) + (q[2] + q[3]);
  const float m = qsum(sx) * (-1.f / DM), r = rsq_fast(fmaxf(fmaf(qsum(sq), 1.f / DM, -m * m), 0.f) + LN_EPS);
  if ((lane & 3) == 0) ll_st128(dst + (lane >> 2) * 2, m, r, tag);
}

__device__ __forceinline__ void poison(const Params& P, uint32_t el, uint32_t src, const CUtensorMap* m, int rb, int j, int lane) {
#pragma unroll 1
  for (int u = lane; u < 72; u += 32) sts128(src + u * 16, POISON, POISON, POISON, POISON);
  fence_async_s();
  __syncwarp();
#pragma unroll 1
  for (int u = 0; u < 16; u++) {
    __nanosleep(NAP);
    bulk_store_p(el, o_block(rb, u >> 3) + j * 9216 + (u & 7) * 1152, src, 1152);
    asm volatile("{\n.reg .pred P;\nsetp.ne.u32 P, %5, 0;\n@P cp.async.bulk.tensor.3d.global.shared::cta.tile.bulk_group [%0, {%2, %3, %4}], [%1];\n}" ::"l"(m), "r"(src), "r"((j & 6) * 72), "r"(rb * 64 + u * 4), "r"(j & 1), "r"(el) : "memory");
  }
}
__device__ __forceinline__ void mma16acc(float* c, const uint32_t* a, uint32_t b0, uint32_t b1) {
  asm volatile("mma.sync.aligned.m16n8k16.row.col.f32.bf16.bf16.f32 {%0,%1,%2,%3}, {%4,%5,%6,%7}, {%8,%9}, {%0,%1,%2,%3};"
               : "+f"(c[0]), "+f"(c[1]), "+f"(c[2]), "+f"(c[3]) : "r"(a[0]), "r"(a[1]), "r"(a[2]), "r"(a[3]), "r"(b0), "r"(b1));
}
template <int KS, int NG, int AK, int AH, int BK, int BG, class F> __device__ __forceinline__ void redo(float* acc, const uint8_t* pa, const uint8_t* pb, F f) {
#pragma unroll 1
  for (int k = 0; k < 36; k += KS) {
    uint32_t a[4 * KS], b[2 * KS][NG];
#pragma unroll 1
    for (int it = 0; it < (1 << 20); it++) {
      bool ok = true;
#pragma unroll
      for (int e = 0; e < 4 * KS; e++) a[e] = ldgpu32(pa + (e >> 1) * AK + (e & 1) * AH);
#pragma unroll
      for (int e = 0; e < 2 * KS * NG; e++) b[e / NG][e % NG] = ldca32(pb + (e / NG) * BK + (e % NG) * BG);
#pragma unroll
      for (int e = 0; e < 4 * KS; e++) ok = ok && a[e] != POISON;
      if (__all_sync(~0u, ok)) break;
    }
#pragma unroll
    for (int e = 0; e < KS; e++) f(a + 4 * e, k + e);
#pragma unroll
    for (int e = 0; e < KS * NG; e++) mma16acc(acc + 4 * (e % NG), a + 4 * (e / NG), movm(b[2 * (e / NG)][e % NG]), movm(b[2 * (e / NG) + 1][e % NG]));
    pa += 2 * KS * AK; pb += 2 * KS * BK;
  }
}
__device__ __forceinline__ bool any_nan(float a, float b) {
  return __any_sync(~0u, a != a || b != b);
}

__global__ void __cluster_dims__(2, 1, 1) __launch_bounds__(384, 1) mega_kernel(const __grid_constant__ Params P) {
  extern __shared__ __align__(1024) uint8_t smem_raw[];
  uint32_t ckk[8];
  (void)ckk;
  CKK(0);
  const uint32_t sb = smem_u32(smem_raw);
  const uint32_t bars = sb + SM_BAR;
  int tid = threadIdx.x, lane = tid & 31;
  const int wid = __shfl_sync(~0u, tid >> 5, 0);
  if (tid == 256 && blockIdx.x < NCTA) prefetch_l2((const uint8_t*)P.wqkv + blockIdx.x * 6912, 6912);
  const int cl = blockIdx.x >> 1, tp = cl - 36, t7 = (tp * 37) >> 8;
  const int bid = (cl < 4 ? cl * 8 + 32 : tp < 0 ? cl - 4 : cl < 64 ? tp + t7 + 33 : cl) * 2 + (blockIdx.x & 1);
  if (bid >= NCTA) return;
  const int rb = bid & 15, j = bid >> 4;
  { const bool tr = (tid & 127) == 0 && tid < 256; const int w = tid >> 7; (void)tr; (void)w; TRC(tr, w, 0); }
  CKK(1);
  uint4 wv[5];
  const uint8_t* wsrc;
  {
    const int n8 = min(tid >> 3, 26), part = n8 / 9;
    const uint8_t* src = (const uint8_t*)P.wqkv + (8 * rb + (tid & 7)) * (3 * DM * 2) + (part * (DM - 72) + 72 * j + 8 * n8) * 2;
#pragma unroll
    for (int u = 0; u < SPL; u++) wv[u] = ldnc128_if(tid < 216, src + u * (128 * 3 * DM * 2));
    wsrc = src;
  }
  CKK(2);
  if (tid == 352) {
#pragma unroll
    for (int e = 0; e < 16; e++) mbar_init(bars + B_FULL + e * 8, (e >> 2) == 1 ? 16 : 1);
    mbar_init(bars + B_RES + 8, 8); mbar_init(bars + B_WT, 1); mbar_init(bars + B_WT + 8, 1); mbar_init(bars + B_IMG, 9);
    asm volatile("fence.mbarrier_init.release.cluster;" ::: "memory");
  }
  __syncthreads();

  if (wid >= 8) {
    reg_dealloc<40>();
    lane = __shfl_sync(~0u, lane, lane);
    const uint32_t el = elect_one();
    const uint64_t pol = policy_evict_first();
    uint32_t* const fj = P.s->flags + FJ + j * 32;
    if (wid == 8) {
      if (lane == 0) {
        mbar_init(bars + B_RES, 1); mbar_init(bars + B_WOI, 1); mbar_init(bars + B_ZB, 1); mbar_init(bars + B_GATE3, 3); mbar_init(bars + B_Z1, 1); mbar_init(bars + B_LAG, 4);
#pragma unroll
        for (int e = B_RT; e < B_XS + 16; e += 8) mbar_init(bars + e, e >= B_AD && e < B_EVT ? 2 : (e >= B_EVT && e < B_RT1) || (e >= B_EA3 && e < B_XS) ? 4 : 1);
        asm volatile("fence.mbarrier_init.release.cluster;" ::: "memory");
        mbar_arrive(bars + B_IMG);
      }
      __syncwarp();
#pragma unroll 1
      for (int i = 0; i < 12; i++) if (el) prefetch_map(&P.act[0] + (i < 7 ? i : i - 12));
      const uint32_t epoch = ldcg32(fj + FJ_EP + rb);
      const uint32_t rk = bid & 1;
      TRC(el, 2, 34);
      uint32_t dst = sb + ST_B + rk * 18432, full = bars + B_FULL, ph = 1;
      auto slot = [&](uint32_t bytes) {
        mbar_wait(full, ph);
        expect_tx_p(el, full, bytes);
        mbar_wait(full + (B_EMPTY - B_FULL), ph);
      };
      auto next = [&]() {
        const bool wrap = full == bars + B_FULL + 24;
        full += wrap ? -24 : 8; dst += wrap ? 0u - 3 * ST_BYTES : ST_BYTES; ph ^= wrap;
      };
#pragma unroll 1
      for (int L = 0; L < 2; L++) {
        const uint8_t* src = P.s->WQ + j * WQ_SL + rk * 13824;
        dst -= rk * 4608;
#pragma unroll 1
        for (int i = 0; i < 9; i++) {
          if (L == 0 && (i == 0 || i == 2 * SPL)) {
            flag_wait(fj + (i ? FJ_WQ : FJ_WQ0), (epoch + 1) * 16);
            fence_async_g();
            TRC(el, 2, i ? 47 : 45);
          }
          slot(27648);
          bulk_mc_h(el, dst, src, 13824, full, true, pol);
          src += 27648;
          next();
        }
        dst += rk * 4608;
        if (L == 0) {
#pragma unroll 1
          for (int u = 0; u < 2; u++) flag_wait(P.s->flags + FJ + (j ^ u) * 32 + FJ_WO, (epoch + 1) * 16);
          fence_async_g();
          TRC(el, 2, 46);
        }
        src = P.s->WO + ((j & 6) + rk) * WO_SL;
#pragma unroll 1
        for (int i = 0; i < 4; i++) {
          slot(ZB);
          bulk_mc_h(el, dst, src, 18432, full, true, pol);
          src += 18432;
          next();
        }
        slot(18432);
        bulk_mc_h(el, dst, src, 9216, full, true, pol);
        next();
        int col = (((9 * j + 1) >> 1) + 36) * 64;
        const CUtensorMap* map = &P.win64;
#pragma unroll 1
        for (int p = 0; p < 9; p++) {
          if (p == 1) mbar_wait(bars + B_FA3 + GA3 * 8, L);
          mbar_wait(full + (B_EMPTY - B_FULL), ph);
          tma4d_mc(el, dst, map, col, rk * 18, full + 8, pol);
          mbar_arrive_if(el, full);
          if (p + L == 0 && el) asm volatile("cp.async.bulk.prefetch.tensor.4d.L2.global [%0, {%1, 0, 0, %2}];\ncp.async.bulk.prefetch.tensor.4d.L2.global [%0, {%1, 0, 0, %3}];" ::"l"(map), "r"(col + 64), "r"(rk * 18), "r"(rk * 18 + 36) : "memory");
          next();
          if (p == 1) mbar_wait(bars + B_FA3 + GB3 * 8, L);
          slot(2 * ZB);
          tma4d_mc(el, dst, map, col, rk * 18 + 36, full, pol);
          next();
          col = p == 3 ? (9 * j + ((j & 1) ? 0 : 8)) * 32 : p == 4 ? ((9 * j + 1) >> 1) * 64 : col + 64;
          map = p == 3 ? &P.win : &P.win64;
        }
        TRC(el, 2, L * 16 + 6);
        flag_wait(fj + FJ_ZN + L, (epoch + 1) * 16);
        fence_async_g();
        TRC(el, 2, L * 16 + 7);
        src = z2_block(0, j) + rk * 18432;
#pragma unroll 1
        for (int i = 0; i < 32; i++) {
          if (i >= 4) mbar_wait(full + (B_AD - B_FULL), ((i >> 2) & 1) ^ 1);
          slot(ST_BYTES);
          bulk_mc_h(el, dst, src, 18432, full, true, pol);
          tma3d_h(el, dst - ST_B - rk * 18432, &P.wsp, i * 64, rb * 64, 0, full, true, pol);
          src += 8 * ZB;
          next();
        }
        mbar_wait(bars + B_Z1, L);
        fence_async_g();
        expect_tx_p(el, bars + B_ZB, 26624);
        mbar_wait(full + (B_AD - B_FULL), 1);
        slot(26624);
        bulk_load_h(el, dst - ST_B - rk * 18432, z1_block(rb, 0, j), 26624, bars + B_ZB, true, pol);
        bulk_load_h(el, dst - ST_B - rk * 18432 + 26624, z1_block(rb, 1, j), 26624, full, true, pol);
        next();
        col = j * 64;
#pragma unroll 1
        for (int i = 0; i < 9; i++) {
          if (i < 3) mbar_wait(full + (B_AD - B_FULL), 1);
          slot(ZB);
          tma2d_mc_h(el, dst, &P.wout, col, 288 * j + rk * 144, full, true, pol);
          col = col == 512 ? 0 : col + 64;
          next();
        }
      }
    } else if (wid < 11) {
      int w = wid - 9;
      TRC(el && w == 0, 2, 35);
      uint32_t t8 = (ldcg32(P.s->flags + (rb * 2 + w) * 32 + FR_EP + j) + 1) * 8;
      int bo = bid;
#define FRESH asm volatile("" : "+r"(lane), "+r"(w), "+r"(bo), "+r"(t8)); const int rb = bo & 15, j = bo >> 4; \
      uint32_t *const fr = P.s->flags + (rb * 2 + w) * 32, *const fj = P.s->flags + FJ + j * 32, *const fo = P.s->flags + (rb * 2 + (j & 1)) * 32 + L; \
      const uint32_t ev = bars + B_EVT + w * EV_N * 8, tag = (t8 >> 2) - 1 + L; (void)fr; (void)fj; (void)fo; (void)ev; (void)tag
      Cur c{0, 1};
#pragma unroll 1
      for (int L = 0; L < 2; L++) {
        {
          FRESH;
          uint4* const xs = P.s->XST + (rb * 2 + w) * 128;
          if (L) {
            mbar_wait(ev + EV_PT * 8, 0);
            TRC(el, 3, w * 32 + 16);
            flag_release_p(el, fr + FR_X2);
            TRC(el, 3, w * 32 + 17);
          }
#pragma unroll 1
          for (int i = 0; i < 9; i++) {
            const uint32_t full = bars + B_FULLA + w * 32 + c.s * 8, dst = sb + c.s * ST_BYTES + w * 8192;
            if (L == 0 && i == 4) {
              mbar_wait(bars + B_WT + w * 8, 0);
              TRC(el && w == 0, 2, 37);
              rows_stats(sb + SM_STG + w * 9216, xs + 16 * j, tag, lane);
              TRC(el && w == 0, 2, 38);
            }
            const uint32_t src = sb + (L ? 2 * ST_BYTES + SM_WOI : SM_STG + w * 9216);
            if (i == 4) {
#pragma unroll
              for (int u = 0; u < 6; u++) sts128(src + u * 512 + lane * 16, POISON, POISON, POISON, POISON);
              fence_async_s();
              __syncwarp();
            }
            mbar_wait(bars + B_EMPTY + c.s * 8, c.ph);
            if (i < L) { flag_wait(fr + FR_X2, t8); fence_async_g(); }
            tma3d_h(el, dst, &P.act[L], i * 64, rb * 64, w, full, false, pol);
            expect_tx_p(el, full, 8192);
            TRC(el && i < L, 3, w * 32 + 18);
            TRC(el && i + L + w == 0, 2, 36);
            c.next();
            if (i >= 4 && i < (L ? 5 : 8)) {
              int b = (rb * 2 + w) * 8 + j;
              asm volatile("" : "+r"(b));
              bulk_store_p(el, i == 4 ? (uint8_t*)P.s->HALO + b * 3072 : P.s->O + (b * 3 + i - 5) * 3072, src, 3072);
              if (i < 6) bulk_store_p(el, (i == 4 ? P.s->ST1 : P.s->ZST) + b * 64, src, 1024);
              if (i == 6) bulk_store_p(el, P.s->RT + b * 8, src, 64);
            }
            if (L == 0 && i == 3) rows_fetch(el, sb + SM_STG + w * 9216, P.xs[0] + (128 * rb + 16 * j + w) * (DM * 2), bars + B_WT + w * 8);
          }
          if (el) asm volatile("cp.async.bulk.commit_group;\ncp.async.bulk.wait_group 0;" ::: "memory");
          __syncwarp();
          if (L == 0) fence_gpu();
          const uint32_t tab = sb + L * (2 * ST_BYTES) + SM_XST + w * 512 + lane * 8;
          TRC(el, 3, w * 32 + L * 16 + 13);
#pragma unroll 1
          for (int it = 0; it < (1 << 22); it++) {
            const uint4 a = ll_ld128(xs + 2 * lane), b = ll_ld128(xs + 64 + 2 * lane);
            if (__all_sync(~0u, a.z == tag && b.z == tag)) { sts64(tab, a.x, a.y); sts64(tab + 256, b.x, b.y); break; }
          }
          __syncwarp();
          mbar_arrive_if(el, bars + B_XS + w * 8);
          TRC(el, 3, w * 32 + L * 16 + 14);
          if (w == 1) {
            mbar_wait(bars + B_XS, L);
            expect_tx_p(el, bars + B_RES, 18432);
            tma3d_h(el, sb + SM_STG, &P.res[L], (j & 6) * 72, rb * 64, j & 1, bars + B_RES, !L, pol);
          }
          if (L) flag_wait(fj + FJ_P4, t8 * 4);
        }
        {
          FRESH;
          const uint8_t* src = o_block(rb, j & 1) + w * 8192;
#pragma unroll 1
          for (int i = 0; i < 5; i++) {
            const uint32_t full = bars + B_FULLA + w * 32 + c.s * 8, dst = sb + c.s * ST_BYTES + w * 8192;
            const bool none = 2 * i + w > 8;
            mbar_wait(bars + B_EMPTY + c.s * 8, c.ph);
            expect_tx_p(el, full, none ? 0 : 8192);
            if (i == 0) {
              mbar_wait(bars + B_EMPTY + 16 * L, 0);
              mbar_wait(ev + EV_O * 8, L);
              TRC(el, 3, w * 32 + L * 16 + 3);
              flag_add_p(el, fr + FR_O + L);
              TRC(el, 3, w * 32 + L * 16 + 4);
              flag_wait(fo + FR_O, t8);
              fence_async_g();
            }
            if (!none) bulk_load_h(el, dst, src + i * 16384, 8192, full, true, pol);
            TRC(el && i == 0, 3, w * 32 + L * 16 + 5);
            c.next();
          }
        }
        {
          FRESH;
          expect_tx_p(lane < 9, bars + B_FA3 + (9 * w + lane) * 8, 8192);
          mbar_wait(ev + EV_X1 * 8, L);
          TRC(el, 3, w * 32 + L * 16 + 6);
          if (L) flag_add_p(el, fo + FR_X1); else flag_release_p(el, fo + FR_X1);
          mbar_arrive_if(el, bars + B_GATE3);
          TRC(el, 3, w * 32 + L * 16 + 7);
          mbar_arrive_if(lane < 2, bars + B_FULLA + w * 32 + ((c.s + lane) & 3) * 8);
#pragma unroll 1
          for (int kb = 0; kb < 9; kb++) {
            const int n = 9 * w + kb;
            const uint32_t dst = sb + ((n >> 1) & 3) * ST_BYTES + (n & 1) * 8192;
            if (kb == 0) { flag_wait(fr + FR_X1 + L, t8); fence_async_g(); }
            if (n >= 8) mbar_wait(bars + B_EA3 + (n - 8) * 8, L);
            tma3d_h(el, dst, &P.act[L + 1], kb * 64, rb * 64, w, bars + B_FA3 + n * 8, false, pol);
            TRC(el && kb == 0, 3, w * 32 + L * 16 + 8);
          }
          c.ph ^= ((c.s + 18) >> 2) & 1; c.s = (c.s + 18) & 3;
        }
        float cv;
        {
        FRESH;
        expect_tx_p(el, bars + B_WT + w * 8, 2048);
#pragma unroll 1
        for (int r = 0; r < 8; r++)
          bulk_load_p(el, sb + SM_WT + w * 2176 + r * 272, (const uint8_t*)P.w_sp + (size_t)(128 * rb + 16 * j + 2 * r + w) * (SEQ * 2) + 30 * 128, 256, bars + B_WT + w * 8);
        cv = (lane & 3) ? 0.f : -blo(ldnc16(P.b_sp + 128 * rb + 16 * j + 2 * (lane >> 2) + w));
        mbar_wait(bars + B_RT, L);
        mbar_wait(bars + B_WT + w * 8, L ^ 1);
        mbar_wait(ev + EV_Z1 * 8, L);
        const uint32_t ro = (w * 64 + 8 * j + (lane >> 2)) * 128, x0 = ((lane & 3) * 2) ^ (lane >> 2);
#pragma unroll 1
        for (int i = 0; i < 32; i++) {
          const bool tail = (i >> 1) == 4;
          const int kb = tail ? i + 22 : i < 8 ? i : i - 2;
          if (i == 8) mbar_wait(bars + B_RT1, L);
          if (!tail) mbar_wait(bars + B_FULL + c.s * 8, c.ph ^ 1);
#pragma unroll
          for (int e = 0; e < 2; e++) {
            const uint4 a = lds128(!tail ? sb + c.s * ST_BYTES + ro + ((x0 ^ e) << 4) : sb + SM_WT + w * 2176 + (lane >> 2) * 272 + (i - 8) * 128 + (lane & 3) * 32 + e * 16);
            const uint4 m = lds128(sb + SM_RT + 4096 + kb * 128 + (lane & 3) * 32 + e * 16);
            cv = fmaf(blo(a.x), blo(m.x), fmaf(bhi(a.x), bhi(m.x), fmaf(blo(a.y), blo(m.y), fmaf(bhi(a.y), bhi(m.y), cv))));
            cv = fmaf(blo(a.z), blo(m.z), fmaf(bhi(a.z), bhi(m.z), fmaf(blo(a.w), blo(m.w), fmaf(bhi(a.w), bhi(m.w), cv))));
          }
          if (!tail) {
            mbar_arrive_if(el, bars + B_AD + c.s * 8 + (__float_as_uint(cv) & P.zero));
            c.next();
          }
        }
        }
        TRC(el, 3, w * 32 + L * 16 + 11);
        FRESH;
        cv = qsum(cv);
        uint2* const cs = (uint2*)(P.s->XST + (rb * 2 + w) * 128 + 1);
        if ((lane & 3) == 0) ll_st64(cs + 32 * j + (lane >> 2) * 4, __float_as_uint(cv), tag);
#pragma unroll 1
        for (int it = 0; it < (1 << 22); it++) {
          const uint2 a = ll_ld64(cs + 4 * lane), b = ll_ld64(cs + 128 + 4 * lane);
          if (__all_sync(~0u, a.y == tag && b.y == tag)) { sts32(sb + SM_CV + w * 256 + lane * 4, a.x); sts32(sb + SM_CV + w * 256 + 128 + lane * 4, b.x); break; }
        }
        __syncwarp();
        if (el) mbar_arrive(bars + B_CV + w * 8);
        TRC(el, 3, w * 32 + L * 16 + 12);
#pragma unroll 1
        for (int kb = 30; kb < 32; kb++) {
          mbar_wait(bars + B_FULL + c.s * 8, c.ph ^ 1);
          if (el) mbar_arrive(bars + B_AD + c.s * 8);
          c.next();
        }
        c.ph ^= ((c.s + 10) >> 2) & 1; c.s = (c.s + 10) & 3;
        if (L == 0) {
          mbar_wait(ev + EV_P4 * 8, 0);
          flag_add_p(el, fj + FJ_P4);
          flag_add_p(el, fr + FR_EP + j);
        }
      }
    } else {
      const uint32_t epoch = ldcg32(fj + FJ_EP + rb);
      TRC(el, 2, 33);
      if (SPL) {
        mbar_wait(bars + B_RES + 8, 0);
        TRC(el, 2, 41);
        flag_release_p(el, fj + FJ_WQ0);
        TRC(el, 2, 42);
      }
      mbar_wait(bars + B_IMG, 0);
      TRC(el, 2, 39);
      flag_release_p(el, fj + FJ_WQ);
      TRC(el, 2, 40);
#pragma unroll 1
      for (int L = 0; L < 2; L++) {
        auto wo_fetch = [&]() {
          expect_tx_p(el, bars + B_WOI, 5760);
          asm volatile("{\n.reg .pred P;\nsetp.ne.u32 P, %5, 0;\n@P cp.async.bulk.tensor.4d.shared::cluster.global.mbarrier::complete_tx::bytes [%0], [%1, {0, 0, %3, %4}], [%2];\n}" ::"r"(sb + SM_WOI), "l"(&P.wo8), "r"(bars + B_WOI), "r"(9 * j), "r"((9 * rb) >> 1), "r"(el) : "memory");
        };
        float* const csf = P.s->CSP + (NCTA + bid) * 216;
        if (L == 0) {
          flag_wait(fj + FJ_WQ, (epoch + 1) * 16);
          fence_async_g();
          expect_tx_p(el, bars + B_XRW, 13824);
          bulk_load_p(el, sb + ST_BYTES + SM_WOI, P.s->CSP + j * 16 * 216, 6912, bars + B_XRW);
          bulk_load_p(el, sb + 2 * ST_BYTES + SM_WOI, P.s->CSP + (j * 16 + 8) * 216, 6912, bars + B_XRW);
          wo_fetch();
          mbar_wait(bars + B_XRW, 0);
#pragma unroll 1
          for (int f = lane; f < 54; f += 32) {
            float s[4] = {0.f, 0.f, 0.f, 0.f};
#pragma unroll 4
            for (int r = 0; r < 16; r++) {
              const uint4 v = lds128(sb + ST_BYTES + SM_WOI + (r >> 3) * ST_BYTES + (r & 7) * 864 + f * 16);
              s[0] += __uint_as_float(v.x); s[1] += __uint_as_float(v.y); s[2] += __uint_as_float(v.z); s[3] += __uint_as_float(v.w);
            }
            sts128(sb + SM_CSQ + f * 16, __float_as_uint(s[0]), __float_as_uint(s[1]), __float_as_uint(s[2]), __float_as_uint(s[3]));
            stg128(csf + f * 4, __float_as_uint(s[0]), __float_as_uint(s[1]), __float_as_uint(s[2]), __float_as_uint(s[3]));
          }
          __syncwarp();
          mbar_arrive_if(el, bars + B_CSQ);
        } else {
#pragma unroll 1
          for (int u = 0; u < 4; u++) {
            const int w = u & 1;
            if (u < 2) {
              flag_wait(P.s->flags + (rb * 2 + w) * 32 + FR_X2, (epoch + 1) * 8);
              fence_async_g();
              TRC(el, 2, 48 + u);
              rows_fetch(el, sb + SM_STG + w * 9216, P.xs[1] + (128 * rb + 16 * j + w) * (DM * 2), bars + B_XRW + w * 8);
            } else {
              if (u == 2) {
                expect_tx_p(el, bars + B_CSQ, 864);
                bulk_load_p(el, sb + 2 * ST_BYTES + SM_CSQ, csf, 864, bars + B_CSQ);
              }
              mbar_wait(bars + B_XRW + w * 8, w ^ 1);
              TRC(el, 2, 48 + u);
              rows_stats(sb + SM_STG + w * 9216, P.s->XST + (rb * 2 + w) * 128 + 16 * j, epoch * 2 + 2, lane);
              TRC(el, 2, 50 + u);
            }
          }
        }
        if (L == 0) {
          TRC(el, 2, 43);
          mbar_wait(bars + B_WOI, 0);
          bulk_store_p(el, P.s->WO + j * WO_SL + ((9 * rb) >> 1) * 1152, sb + SM_WOI, 5760);
          publish_p(el, fj + FJ_WO);
          TRC(el, 2, 44);
          const uint8_t* sp = lane < 16 ? (const uint8_t*)P.w_in + (30 * lane + 50) * (FH * 4) + FH * 2 + lane * 256 : (const uint8_t*)P.w_sp + (60 * lane) * (SEQ * 2) + lane * 64;
          float sq = 0.f;
#pragma unroll 1
          for (int u = 0; u < 4; u++) {
            const uint4 y = ldnc128(sp + u * 16);
            const uint32_t x[4] = {y.x, y.y, y.z, y.w};
#pragma unroll
            for (int e = 0; e < 4; e++) sq = fmaf(blo(x[e]), blo(x[e]), fmaf(bhi(x[e]), bhi(x[e]), sq));
          }
#pragma unroll 1
          for (int o = 8; o; o >>= 1) sq += __shfl_xor_sync(~0u, sq, o);
          sq *= lane < 16 ? 2.f * GA * GA * DM / 512.f : C0S * C0S * SEQ / 512.f;
          asm("sqrt.approx.f32 %0, %0;" : "+f"(sq));
          const float o0 = __shfl_sync(~0u, sq, 0), o1 = __shfl_sync(~0u, sq, 16);
          const float p2 = __uint_as_float(min(__float_as_uint(o0) & 0x7f800000u, 0x7e000000u)) * OFK, off = -p2 - fminf(OFA, 0.5f * p2);
          if (el) sts64(sb + SM_OFF, pack2(off, off), min(__float_as_uint(o1) & 0x7f800000u, 0x7e000000u) | 0x00400000u);
        }
        if (el) mbar_arrive(bars + B_GATE3);
        const uint32_t tag = epoch * 2 + L + 1;
        asm volatile("" : "+r"(lane));
        mbar_wait(bars + B_EVT + EV_ZN * 8, L);
        mbar_wait(bars + B_EVT + (EV_N + EV_ZN) * 8, L);
        flag_release_p(el, fj + FJ_ZN + L);
        TRC(el, 2, L * 16 + 8);
        {
          uint4 v[4];
#pragma unroll 1
          for (int it = 0; it < (1 << 22); it++) {
            bool ok = true;
#pragma unroll
            for (int u = 0; u < 4; u++) { v[u] = ll_ld128(P.s->ZST + (rb * 2 + ((lane >> 1) & 1)) * 512 + ((lane & 1) * 4 + u) * 64 + 8 * j + (lane >> 2)); ok = ok && v[u].z == tag; }
            if (__all_sync(~0u, ok)) break;
          }
          float mean = __uint_as_float(v[0].x) + __uint_as_float(v[1].x) + __uint_as_float(v[2].x) + __uint_as_float(v[3].x), M2 = 0.f;
          mean = (mean + __shfl_xor_sync(~0u, mean, 1)) * 0.125f;
#pragma unroll
          for (int u = 0; u < 4; u++) { const float d = __uint_as_float(v[u].x) - mean; M2 += fmaf(288.f * d, d, __uint_as_float(v[u].y)); }
          M2 += __shfl_xor_sync(~0u, M2, 1);
          const float rs = blo(pack2(rsq_fast(fmaf(M2, 1.f / FH, 4.f * GA * GA * LN_EPS)), 0.f));
          if (!(lane & 1)) ll_st64(P.s->RT + 128 * rb + 16 * j + (lane >> 1), pack2(rs, rs * mean), tag);
        }
        TRC(el, 2, L * 16 + 10);
#pragma unroll 1
        for (int b = 0; b < 8; b++) {
          uint4 v[4];
#pragma unroll 1
          for (int it = 0; it < (1 << 22); it++) {
            bool ok = true;
#pragma unroll
            for (int u = 0; u < 4; u++) { v[u] = ll_ld128((const uint4*)P.s->RT + b * 128 + u * 32 + lane); ok = ok && v[u].y == tag && v[u].w == tag; }
            if (__all_sync(~0u, ok)) break;
          }
#pragma unroll
          for (int u = 0; u < 4; u++) {
            const uint32_t rt = sb + SM_RT + b * 512 + u * 128, ro = (lane >> 3) * 32 + (lane & 3) * 8 + ((lane >> 2) & 1) * 2;
            sts32(rt + 4096 + lane * 4, __byte_perm(v[u].x, v[u].z, 0x7632));
            asm volatile("st.shared.u16 [%0], %1;\nst.shared.u16 [%0 + 4], %2;" ::"r"(rt + ro), "h"((uint16_t)v[u].x), "h"((uint16_t)v[u].z) : "memory");
          }
          __syncwarp();
          if (el && (b == 1 || b == 7)) mbar_arrive(bars + (b == 1 ? B_RT : B_RT1));
          TRC(el && b < 2, 2, L * 16 + 11 + b);
        }
        TRC(el, 2, L * 16 + 9);
        mbar_wait(bars + B_EVT + EV_Z1 * 8, L);
        mbar_wait(bars + B_EVT + (EV_N + EV_Z1) * 8, L);
        fence_gpu();
        if (el) mbar_arrive(bars + B_Z1);
        if (L == 0) {
          flag_add_p(el, fj + FJ_EP + rb);
          __nanosleep(NAP0);
          poison(P, el, sb + SM_STG + 17152, &P.psn, rb, j, lane);
          if (el) asm volatile("cp.async.bulk.commit_group;\ncp.async.bulk.wait_group 0;" ::: "memory");
          __syncwarp();
          fence_gpu();
        }
      }
    }
  } else {
    CKK(3);
    uint8_t* const wdst = P.s->WQ + j * WQ_SL + rb * 3456 + tid * 16;
#pragma unroll
    for (int u = 0; u < SPL; u++) stg128_if(tid < 216, wdst + u * (16 * 3456), wv[u].x, wv[u].y, wv[u].z, wv[u].w);
    __syncwarp();
    if (lane == 0) mbar_arrive(bars + B_RES + 8);
    CKK(4);
    auto repack2 = [&]() {
#pragma unroll
      for (int u = SPL; u < 5; u++) stg128_if((u < 4 || rb < 8) && tid < 216, wdst + u * (16 * 3456), wv[u].x, wv[u].y, wv[u].z, wv[u].w);
      float s[8];
#pragma unroll
      for (int e = 0; e < 8; e++) s[e] = 0.f;
#pragma unroll
      for (int u = 0; u < 5; u++) {
        uint32_t x[4] = {wv[u].x, wv[u].y, wv[u].z, wv[u].w};
        asm volatile("" : "+r"(x[0]), "+r"(x[1]), "+r"(x[2]), "+r"(x[3]));
#pragma unroll
        for (int e = 0; e < 4; e++) { s[2 * e] += blo(x[e]); s[2 * e + 1] += bhi(x[e]); }
      }
#pragma unroll
      for (int m = 4; m; m >>= 1) {
#pragma unroll
        for (int e = 0; e < m; e++) s[e] = ((tid & m) ? s[e + m] : s[e]) + __shfl_xor_sync(~0u, (tid & m) ? s[e] : s[e + m], m);
      }
      stg32_if(tid < 216, P.s->CSP + bid * 216 + tid, __float_as_uint(s[0]));
      __syncwarp();
      if (lane == 0) mbar_arrive(bars + B_IMG);
    };
    reg_alloc<232>();
    lane = __shfl_sync(~0u, lane, lane);
    tid = wid * 32 + lane;
    CKK(5);
#pragma unroll
    for (int v = SPL; v < 5; v++) wv[v] = ldnc128_if(tid < 216 && (v < 4 || rb < 8), wsrc + v * (128 * 3 * DM * 2));
    repack2();
    CKK(6);
    const int w = wid >> 2, q = wid & 3;
    int g = lane >> 2, t = lane & 3;
    const uint32_t ev = bars + B_EVT + w * EV_N * 8;
    const bool tr = (tid & 127) == 0;
    (void)tr;
    Cur c{0, 0};
    const uint32_t ebar = mapa(bars + B_EMPTY, (bid & 1) ^ (lane & 1));
    auto release = [&](uint32_t s, uint32_t dep = 0) { mbar_arrive_cluster_if(lane < 2, ebar + s * 8 + dep); };
    auto release_if = [&](bool on, uint32_t s) { mbar_arrive_cluster_if(lane < 2 && on, ebar + s * 8); };
    uint32_t ia = 0;
    auto wait_ab = [&]() { mbar_wait_c(bars + B_FULL + c.s * 8, c.ph); mbar_wait_c(bars + B_FULLA + w * 32 + c.s * 8, (ia >> 2) & 1); ia++; };

    auto yield_done = [&]() { if (w == 0 && lane == 0) mbar_arrive(bars + B_LAG); };
    auto signal = [&](int e) { __syncwarp(); mbar_arrive_if(lane == 0, ev + e * 8); };

    const uint32_t epoch = ldcg32(P.s->flags + (rb * 2 + w) * 32 + FR_EP + j);
    TRC(tr, w, 1);
    CKK(7);
    if (PAD && P.zero) {
#pragma unroll
      for (int i = 0; i < PAD; i++) asm volatile("st.shared.u32 [%0], %1;" ::"r"(sb + i * 20), "r"(tid) : "memory");
    }
    CKK_OUT;

#pragma unroll 1
    for (int L = 0; L < 2; L++) {
      const int tb = 2 + L * 24;
      asm volatile("" : "+r"(lane), "+r"(g), "+r"(t));
      (void)tb;
      ia = 0;
      const uint32_t tag = epoch * 2 + L + 1;
      uint32_t aoff = (w * 64 + q * 16 + (lane & 15)) * 128 + (((lane >> 4) ^ (lane & 7)) << 4);
      {
        uint32_t Pk[27][2];
        float sc0, sc1;
        const uint32_t att = sb + w * 8192 + q * 2048 + lane * 4;
        uint4* hp = P.s->HALO + ((((rb - (q == 0)) * 2 + w) * 8 + j) * 6) * 32 + lane;
        uint8_t* od = o_block(rb, w) + (9 * j) * 1024 + (2 * q) * 128 + lane * 4;
        ACLK_INIT;
        {
          float acc[108];
#pragma unroll
          for (int i = 0; i < 108; i++) acc[i] = 0.f;
          uint32_t prev = 0;
#pragma unroll 1
          for (int kb = 0; kb < 9; kb++) {
            const bool hold = w == 1 && kb == 9 - LAG1;
            if (hold) {
              wgmma_wait<0>();
              release(prev);
              mbar_wait_c(bars + B_LAG, L);
            }
            wait_ab();
            TRC(tr && kb == 0, w, tb + 0);
            MCLK(kb == 0, 0);
            PCLK(kb * 4);
            const uint32_t st = sb + c.s * ST_BYTES;
            uint64_t da = dsc2(dlo(st + w * 8192, 16), 0, 0x40000040u + P.zero), db = dsc2(dlo(st + ST_B, 3456), 0, 8 ^ P.zero);
            wgmma_fence();
#pragma unroll
            for (int kk = 0; kk < 4; kk++) {
              wgmma_ss_n216(acc, da, db, 1);
              dadd(da, 2); dadd(db, 432);
              if (kk == 0) { wgmma_commit(); wgmma_wait<1>(); release_if(kb > 0 && !hold, prev); }
            }
            wgmma_commit();
            if (kb == 7) yield_done();
            PCLK(kb * 4 + 1);
            PCLK(kb * 4 + 2);
            PCLK(kb * 4 + 3);
            prev = c.s; c.next();
          }
          const uint32_t cs = sb + prev * ST_BYTES + SM_CSQ + t * 8;
          mbar_wait_c(bars + B_CSQ, L);
          mbar_wait_c(bars + B_XS + w * 8, L);
          const float2 n0 = lds64f(sb + prev * ST_BYTES + SM_XST + w * 512 + (16 * q + g) * 8), n1 = lds64f(sb + prev * ST_BYTES + SM_XST + w * 512 + (16 * q + g + 8) * 8);
          const float m0 = n0.x, r0 = n0.y, m1 = n1.x, r1 = n1.y;
          float2 cv[27];
#pragma unroll
          for (int G = 0; G < 27; G++) cv[G] = lds64f(cs + G * 32);
          PCLK(36);
          wgmma_wait<0>();
          PCLK(37);
          {
            uint32_t dep = P.zero & __float_as_uint(m0) & __float_as_uint(m1);
#pragma unroll
            for (int G = 0; G < 27; G++) dep &= __float_as_uint(cv[G].x);
            release(prev, dep);
          }
          TRC(tr, w, tb + 1);
          MCLK(1, 1);
          ACLK(0);
#pragma unroll
          for (int G = 9; G < 27; G++) Pk[G][1] = pack2(fmaf(m1, cv[G].x, acc[4 * G + 2]) * r1, fmaf(m1, cv[G].y, acc[4 * G + 3]) * r1);
          if (q < 3) {
#pragma unroll
            for (int i = 0; i < 18; i++) sts32(att + (i >> 4) * ST_BYTES + (i & 15) * 128, Pk[9 + i][1]);
          } else if (rb < 15) {
#pragma unroll
            for (int i = 0; i < 6; i++) ll_st128(hp + i * 32, __uint_as_float(Pk[9 + 3 * i][1]), __uint_as_float(Pk[10 + 3 * i][1]), tag, __uint_as_float(Pk[11 + 3 * i][1]));
          }
#pragma unroll
          for (int G = 0; G < 27; G++) {
            if (G < 9) {
              Pk[G][0] = pack2(fmaf(m0, cv[G].x, acc[4 * G]), fmaf(m0, cv[G].y, acc[4 * G + 1]));
              Pk[G][1] = pack2(fmaf(m1, cv[G].x, acc[4 * G + 2]), fmaf(m1, cv[G].y, acc[4 * G + 3]));
            } else {
              Pk[G][0] = pack2(fmaf(m0, cv[G].x, acc[4 * G]) * r0, fmaf(m0, cv[G].y, acc[4 * G + 1]) * r0);
            }
          }
          sc0 = r0 * (0.23570226039551584f * 1.4426950408889634f); sc1 = r1 * (0.23570226039551584f * 1.4426950408889634f);
        }
        ACLK(1);
        constexpr int GA_[4] = {0, 2, 4, 7}, GB_[4] = {1, 3, 5, 8}, GC_[4] = {2, 4, 6, 6};
        float S1[4][4], S2[4][4];
        uint32_t qa[4][2], qc[4][2];
#pragma unroll
        for (int h = 0; h < 4; h++) {
#pragma unroll
          for (int r = 0; r < 2; r++) {
            qa[h][r] = (h == 0 || h == 3 || t >= h) ? Pk[GA_[h]][r] : 0u;
            qc[h][r] = (h == 3 ? t == 3 : t <= h) ? Pk[GC_[h]][r] : 0u;
          }
          mma16(S1[h], qa[h][0], qa[h][1], Pk[GB_[h]][0], Pk[GB_[h]][1], Pk[9 + GA_[h]][0], Pk[9 + GB_[h]][0]);
          mma16(S2[h], qa[h][0], qa[h][1], Pk[GB_[h]][0], Pk[GB_[h]][1], Pk[9 + GA_[h]][1], Pk[9 + GB_[h]][1]);
        }
#pragma unroll
        for (int h = 0; h < 4; h++) {
          mma8(S1[h], qc[h][0], qc[h][1], Pk[9 + GC_[h]][0]);
          mma8(S2[h], qc[h][0], qc[h][1], Pk[9 + GC_[h]][1]);
        }
        uint32_t V1[9], V2[9];
#pragma unroll
        for (int i = 0; i < 9; i++) { V1[i] = movm(Pk[18 + i][0]); V2[i] = movm(Pk[18 + i][1]); }
        const bool remote = q == 0 && rb > 0;
        uint4 hv[6];
#pragma unroll
        for (int i = 0; i < 6; i++) hv[i] = make_uint4(0u, 0u, tag, 0u);
        if (remote) {
#pragma unroll
          for (int i = 0; i < 6; i++) hv[i] = ll_ld128(hp + i * 32);
        }
        const bool up0 = 2 * t > g, up1 = 2 * t + 1 > g;
        const uint32_t mup = (up0 ? 0xffffu : 0u) | (up1 ? 0xffff0000u : 0u);
        auto finish = [&](const float (&x0)[4], const float (&x1)[4], uint32_t ma, const uint32_t (&Vb)[9], int hi) {
          uint32_t pa[4], pb[4];
          float rs[4];
#pragma unroll
          for (int h = 0; h < 4; h++) {
            const float m = qmax(fmaxf(x0[h], x1[h]));
            const uint32_t p = pack2(ex2(x0[h] - m), ex2(x1[h] - m));
            pa[h] = p & ma; pb[h] = p & ~ma;
          }
          if (!hi) mbar_arrive_if(lane == 0, ev + EV_O * 8 + (Vb[8] & pa[3] & P.zero));
#pragma unroll
          for (int h = 0; h < 4; h += 2) {
            float R[4];
            mma16(R, pa[h], pa[h + 1], pb[h], pb[h + 1], 0x3f803f80u, 0x3f803f80u);
            rs[h] = rcp_fast(R[0]); rs[h + 1] = rcp_fast(R[2]);
          }
#pragma unroll
          for (int i = 0; i < 9; i++) {
            const int h = 4 * i / 9, e = (h & 1) * 2;
            const bool split = i == 2 || i == 4 || i == 6, nx = split && 2 * t >= i;
            float O[4], N[4];
            mma16(O, pa[h & 2], pa[h | 1], pb[h & 2], pb[h | 1], V1[i], Vb[i]);
            if (i == 4) mma16(N, pa[2], pa[3], pb[2], pb[3], V1[i], Vb[i]); else { N[0] = O[2]; N[1] = O[3]; }
            const float r = nx ? rs[h + (split ? 1 : 0)] : rs[h];
            stg32(od + i * 1024 + hi * 128, pack2((nx ? N[0] : O[e]) * r, (nx ? N[1] : O[e + 1]) * r));
          }
        };
        {
          float x0[4], x1[4];
#pragma unroll
          for (int h = 0; h < 4; h++) { x0[h] = (up0 ? S1[h][2] : S2[h][2]) * sc1; x1[h] = (up1 ? S1[h][3] : S2[h][3]) * sc1; }
          finish(x0, x1, mup, V2, 1);
        }
        ACLK(2);
        bar_sync(1 + w, 128);
        uint32_t H[18];
        if (q > 0) {
#pragma unroll
          for (int i = 0; i < 18; i++) H[i] = lds32(att - 2048 + (i >> 4) * ST_BYTES + (i & 15) * 128);
        } else {
#pragma unroll 1
          for (int it = 0; it < (1 << 20); it++) {
            bool ok = true;
#pragma unroll
            for (int i = 0; i < 6; i++) ok = ok && hv[i].z == tag;
            if (__all_sync(~0u, ok)) break;
#pragma unroll
            for (int i = 0; i < 6; i++) hv[i] = ll_ld128(hp + i * 32);
          }
#pragma unroll
          for (int i = 0; i < 6; i++) { H[3 * i] = hv[i].x; H[3 * i + 1] = hv[i].y; H[3 * i + 2] = hv[i].w; }
        }
        float S0[4][4];
#pragma unroll
        for (int h = 0; h < 4; h++) {
          mma16(S0[h], qa[h][0], qa[h][1], Pk[GB_[h]][0], Pk[GB_[h]][1], H[GA_[h]], H[GB_[h]]);
        }
#pragma unroll
        for (int h = 0; h < 4; h++) mma8(S0[h], qc[h][0], qc[h][1], H[GC_[h]]);
        uint32_t V0[9];
#pragma unroll
        for (int i = 0; i < 9; i++) V0[i] = movm(H[9 + i]);
        ACLK(3);
        {
          const bool nohalo = (rb | q) == 0;
          const float b0 = up0 && nohalo ? -INFINITY : 0.f, b1 = up1 && nohalo ? -INFINITY : 0.f;
          float x0[4], x1[4];
#pragma unroll
          for (int h = 0; h < 4; h++) { x0[h] = fmaf(up0 ? S0[h][0] : S1[h][0], sc0, b0); x1[h] = fmaf(up1 ? S0[h][1] : S1[h][1], sc0, b1); }
          finish(x0, x1, ~mup, V0, 0);
        }
        ACLK(4);
        bar_arrive(3 + w, 256);
        ACLK_OUT;
        TRC(tr, w, tb + 2);
        MCLK(1, 2);
      }
      {
        float acc[36];
        const int hw = rb * 2 + (j & 1), js = (j & 6) + w;
        const uint32_t xt = sb + SM_STG + (16 * q + (lane & 15)) * 288 + (9 * w + (lane >> 4)) * 16, eye = (g >> 1) == t ? 0x3f80u << (g & 1) * 16 : 0u;
        uint32_t xm = xt ^ ((lane & 4) << 2), xl = sb + SM_STG + (2 * q + w) * 2304;
        uint32_t xl0 = xl + (lane >> 4) * 288 + (lane & 15) * 16, xl1 = xl + ((lane >> 1) & 7) * 288 + 256 + ((lane ^ (lane >> 3)) & 1) * 16;
        uint8_t* xd0 = P.xs[L + 1] + (128 * rb + 32 * q + 16 * w + (j & 1)) * (DM * 2) + (j & 6) * 144;
        uint8_t* xd1 = xd0 + (lane >> 1) * (DM * 4) + 256 + (lane & 1) * 16;
        xd0 += (lane >> 4) * (DM * 4) + (lane & 15) * 16;
        uint4* stp = P.s->ST1 + (hw * 8 + js) * 64 + 16 * q + g;
        asm volatile("" : "+r"(xm), "+r"(xl0), "+r"(xl1), "+l"(xd0), "+l"(xd1), "+l"(stp));
        mbar_wait_c(bars + B_RES, L);
        TRC(tr, w, tb + 21);
#pragma unroll
        for (int u = 0; u < 5; u++) {
          uint32_t r[4];
          ldsm4(r, xt + u * 32);
          widen(acc + 8 * u, r[0], r[1], eye);
          if (u < 4) widen(acc + 8 * u + 4, r[2], r[3], eye);
        }
        bar_sync(4 - w, 256);
        uint32_t prev = 0;
#pragma unroll 1
        for (int u = 0; u < 5; u++) {
          const uint32_t st = sb + c.s * ST_BYTES;
          uint64_t da = dsc2(dlo(st, 1024), 0, 8 + P.zero), db = dsc2(dlo(st + ST_B + w * 18432, 1152), 0, 8 ^ P.zero);
          mbar_wait_c(bars + B_FULL + c.s * 8, c.ph); mbar_wait_c(bars + B_FULLA + c.s * 8, (ia >> 2) & 1);
          TRC(tr && u == 0, w, tb + 3);
          MCLK(u == 0, 3);
          wgmma_fence();
#pragma unroll
          for (int kk = 0; kk < 4; kk++) { wgmma_ss_n72(acc, da, db, 1); dadd(da, 128); dadd(db, 144); }
          wgmma_commit();
          wgmma_wait<1>();
          release_if(u > 0, prev);
          mbar_wait_c(bars + B_FULLA + 32 + c.s * 8, (ia >> 2) & 1);
          ia++;
          if (u == 4) break;
          wgmma_fence();
#pragma unroll
          for (int kk = 4; kk < 8; kk++) { wgmma_ss_n72(acc, da, db, 1); dadd(da, 128); dadd(db, 144); }
          wgmma_commit();
          prev = c.s; c.next();
        }
        RCLK_INIT;
        wgmma_wait<0>();
        RCLK(0);
        release(c.s);
        c.next();
        if (__builtin_expect(any_nan(acc[0], acc[2]), 0)) {
          SLOW(L);
          const uint8_t* xr = P.xs[L] + (uint32_t)((128 * rb + 32 * q + 2 * g + (j & 1)) * (DM * 2) + js * 144 + t * 4);
#pragma unroll
          for (int i = 0; i < 9; i++) widen(acc + 4 * i, ldgpu32(xr + i * 16), ldgpu32(xr + i * 16 + DM * 32), eye);
          redo<KS2, 9, 1024, 128, 1152, 128>(acc, P.s->O + (uint32_t)(hw * (2 * ZB) + q * 256 + lane * 4), P.s->WO + (uint32_t)(js * WO_SL + lane * 4), [](uint32_t*, int) {});
        }
        TRC(tr && P5TRACE != 5, w, tb + 4);
        MCLK(1, 4);
        uint32_t pk[18];
#pragma unroll
        for (int i = 0; i < 18; i++) pk[i] = pack2(acc[2 * i], acc[2 * i + 1]);
#pragma unroll
        for (int u = 0; u < 4; u++) stsm4(xm + u * 32, pk[4 * u], pk[4 * u + 1], pk[4 * u + 2], pk[4 * u + 3]);
        asm volatile("stmatrix.sync.aligned.m8n8.x2.shared.b16 [%0], {%1,%2};" ::"r"(xm + 128), "r"(pk[16]), "r"(pk[17]) : "memory");
        float sm[4], q0[4], q1[4];
        widen(sm, pk[16], pk[17], 0x3f803f80u); widen(q0, pk[16], pk[17], pk[16]); widen(q1, pk[16], pk[17], pk[17]);
#pragma unroll
        for (int u = 0; u < 4; u++) {
          mma16acc(sm, pk + 4 * u, 0x3f803f80u, 0x3f803f80u);
          mma8(q0, pk[4 * u], pk[4 * u + 1], pk[4 * u]); mma8(q1, pk[4 * u], pk[4 * u + 1], pk[4 * u + 1]);
          mma8(q0, pk[4 * u + 2], pk[4 * u + 3], pk[4 * u + 2]); mma8(q1, pk[4 * u + 2], pk[4 * u + 3], pk[4 * u + 3]);
        }
        auto stats = [&]() {
#pragma unroll
          for (int h = 0; h < 2; h++) {
            const float ss = sm[2 * h], m = ss * (1.f / 72.f), qq = h ? ((g & 1) ? q1[3] : q1[2]) : (g & 1) ? q0[1] : q0[0];
            ll_st128_if(eye, stp + 8 * h, m, fmaxf(qq - ss * m, 0.f), tag);
          }
        };
        RCLK(1);
        bar_sync(8 + q, 64);
        RCLK(2);
        uint4 v[5];
#pragma unroll
        for (int u = 0; u < 5; u++) v[u] = lds128(u < 4 ? (xl0 ^ ((u & 2) << 3)) + u * 576 : xl1);
        stats();
#pragma unroll
        for (int u = 0; u < 5; u++) stg128_if(u < 4 || lane < 16, u < 4 ? xd0 + u * (DM * 8) : xd1, v[u].x, v[u].y, v[u].z, v[u].w);
        RCLK(3);
        signal(EV_X1);
        RCLK(4);
        RCLK(5);
        TRC(tr, w, tb + 5);
        RCLK(6);
        RCLK_OUT;
      }
      uint32_t zk[16];
      {
        uint32_t xA[36][4];
        float acc[32];
        uint32_t s0, one, off2;
        uint8_t *z1d, *zd;
        uint64_t db;
        auto bwait = [&](uint32_t dhi, bool skip) {
          s0 = c.s;
          c.next();
          if (!skip) mbar_wait_c(bars + B_FULL + c.s * 8, c.ph);
          db = dsc2(dlo(sb + s0 * ST_BYTES + ST_B, 512) - 3, 0, dhi); one = (c.s ^ P.zero) & 1;
        };
        auto mma = [&](int kk, int pp, bool hand) {
          wgmma_rs_n64(acc, xA[kk], dat(db, (kk / 18) * ST_BYTES + (kk % 18) * 2048 + 48, one), kk != 0);
          if (kk == pp && hand) bar_arrive(7 - w, 256);
          if (kk == 17 || kk == 35) wgmma_commit();
          if (kk == RL3) { wgmma_commit(); wgmma_wait<1>(); release(s0); }
        };
        {
          bwait(0x40000040u, false);
          mbar_wait_c(bars + B_GATE3, L);
          float mean0, mean1, rs0, rs1;
          stat_get(P.s->ST1 + ((rb * 2 + w) * 8 + 2 * t) * 64 + 16 * q + g, tag, 72.f, LN_EPS, mean0, rs0, mean1, rs1);
          const uint32_t ns0 = pack2(GA * rs0, GA * rs0), ns1 = pack2(GA * rs1, GA * rs1);
          const uint32_t nb0 = pack2(-mean0 * blo(ns0), -mean0 * blo(ns0)), nb1 = pack2(-mean1 * blo(ns1), -mean1 * blo(ns1));
          const uint32_t al = sb + (aoff & 8191);
#pragma unroll
          for (int kb = 0; kb <= 9; kb++) {
            if (kb < 9) {
              mbar_wait_c(bars + B_FA3 + (9 * w + kb) * 8, L);
              TRC(tr && kb == 0, w, tb + 6);
              MCLK(kb == 0, 5);
              if (kb == 0) SCLK(0);
              QCLK(kb);
              const uint32_t at = al + (w ? (((kb + 1) >> 1) & 3) * ST_BYTES + ((kb + 1) & 1) * 8192 : ((kb >> 1) & 3) * ST_BYTES + (kb & 1) * 8192);
#pragma unroll
              for (int kk = 4 * kb; kk < 4 * kb + 4; kk++) ldsm4(xA[kk], at ^ ((kk & 3) << 5));
            }
            if (kb == 0) continue;
            const uint32_t dep = xA[4 * kb - 4][0] & xA[4 * kb - 3][0] & xA[4 * kb - 2][0] & xA[4 * kb - 1][0] & P.zero;
            mbar_arrive_if(lane == 0 && (kb == 1 || w == 0), bars + B_EA3 + (9 * w + kb - 1) * 8 + dep);
#pragma unroll
            for (int kk = 4 * kb - 4; kk < 4 * kb; kk++) {
#pragma unroll
              for (int e = 0; e < 4; e++) xA[kk][e] = hfma2(xA[kk][e], (e & 1) ? ns1 : ns0, (e & 1) ? nb1 : nb0);
            }
            wgmma_fence();
#pragma unroll
            for (int kk = 4 * kb - 4; kk < 4 * kb; kk++) mma(kk, PP30, w);
          }
          off2 = lds32(sb + SM_OFF);
          z1d = z1_block(rb, w, j) + (tid & 127) * 16;
          zd = z2_block(2 * rb + (q >> 1), j) + (4 * (q & 1) + w) * 4608 + ((g & 3) * 2 + (g >> 2)) * 16 + t * 4;
          asm volatile("" : "+l"(z1d), "+l"(zd));
          wgmma_wait<0>();
          if (__builtin_expect(any_nan(acc[0], acc[2]), 0)) {
            SLOW(2 + L);
            uint4* rd = P.s->RD + (uint32_t)(bid * (36 * 256) + tid);
            asm volatile("" : "+l"(rd));
            const uint8_t* xr = P.xs[L + 1] + (uint32_t)((128 * rb + 32 * q + 2 * g + w) * (DM * 2) + t * 4);
            const uint32_t any[8] = {ns0, ns1, nb0, nb1, (uint32_t)lane, (uint32_t)tid, (uint32_t)g, (uint32_t)t};
#pragma unroll
            for (int i = 0; i < 8; i++) widen(acc + 4 * i, 0u, 0u, any[i]);
            redo<KS3, 8, 16, DM * 32, FH * 32, 16>(acc, xr, (const uint8_t*)P.w_in + (uint32_t)(g * (FH * 4) + (((9 * j + 1) >> 1) + 36) * 128 + t * 4),
                                              [&](uint32_t* a, int k) {
#pragma unroll
                                                for (int e = 0; e < 4; e++) a[e] = hfma2(a[e], (e & 1) ? ns1 : ns0, (e & 1) ? nb1 : nb0);
                                                stg128(rd + k * 256, a[0], a[1], a[2], a[3]);
                                              });
#pragma unroll
            for (int k = 0; k < 36; k++) { const uint4 v = ldcg128(rd + k * 256); xA[k][0] = v.x; xA[k][1] = v.y; xA[k][2] = v.z; xA[k][3] = v.w; }
          }
        }
        float sm[4] = {0.f, 0.f, 0.f, 0.f}, qq[4] = {0.f, 0.f, 0.f, 0.f};
        auto gelu = [&](auto nz2) {
          constexpr int NZ2 = nz2.value, R = 8 - NZ2, N = 8, D = NZ2 == 8 ? GM2 : NZ2 ? GMM : GM1;
          float th[32], gb = GB;
          uint32_t qa = 0, qb = 0;
          auto head = [&](int G) {
#pragma unroll
            for (int e = 0; e < 4; e++) { const float v = acc[4 * G + e]; th[4 * G + e] = tanh_fast(v * fmaf(v, v, gb)); }
          };
#pragma unroll
          for (int i = 0; i < D; i++) head((i + R) & 7);
#pragma unroll
          for (int i = 0; i < N; i++) {
            const int G = (i + R) & 7;
            if (i + D < N) head((i + D + R) & 7);
            float* z = acc + 4 * G;
#pragma unroll
            for (int e = 0; e < 4; e++) z[e] = fmaf(z[e], th[4 * G + e], z[e]);
            uint32_t pa = pack2(z[0], z[1]), pb = pack2(z[2], z[3]), tok;
            if (i < NZ2) {
#pragma unroll
              for (int e = 0; e < 4; e++) { sm[e] += z[e]; qq[e] = fmaf(z[e], z[e], qq[e]); }
              pa = hsub2(pa, off2); pb = hsub2(pb, off2);
              stg32(zd + i * 128, pa); stg32(zd + i * 128 + 9216, pb);
              tok = pa ^ pb ^ __float_as_uint(qq[1]);
            } else {
              if (NZ2 && G == 3) sts128(sb + SM_STG + tid * 16, qa, qb, pa, pb);
              else if (G & 1) stg128(z1d + (G >> 1) * 2048 + (NZ2 ? 24576 : 0), qa, qb, pa, pb);
              qa = pa; qb = pb;
              tok = pa ^ pb;
            }
            gb = __uint_as_float(tok * P.zero + __float_as_uint(GB));
          }
        };
        auto done = [&](int p) {
          wgmma_wait<0>();
          release(c.s);
          c.next();
          TRC(tr && p == 4, w, tb + 7);
          TRC(tr && p == 8, w, tb + 11);
          MCLK(p == 8, 6);
          SCLK(2 * p + 1);
          QCLK(10 + 3 * p);
        };
        auto pass = [&](int p, uint32_t dhi) {
          SCLK(2 * p);
          QCLK(8 + 3 * p);
          bwait(dhi, w);
          bar_sync(6 + w, 256);
          TRC(tr && p == 5, w, tb + 10);
          wgmma_fence();
#pragma unroll
          for (int kk = 0; kk < 36; kk++) mma(kk, PP3, w == 0 || p < 8);
          done(p);
        };
        done(0);
#pragma unroll 1
        for (int p = 1; p < 5; p++) {
          gelu(Int<8>{});
          zd += 1024;
          pass(p, p == 4 ? 0x80000040u : 0x40000040u);
        }
        gelu(Int<4>{});
        signal(EV_ZN);
        {
          const float a0 = qsum(sm[0] + sm[1]), a1 = qsum(sm[2] + sm[3]), q0 = qsum(qq[0] + qq[1]), q1 = qsum(qq[2] + qq[3]);
          const float ss = t ? a1 : a0, m = ss * (1.f / 288.f);
          ll_st128_if(t < 2, P.s->ZST + (rb * 2 + w) * 512 + j * 64 + 16 * q + 8 * t + g, m - blo(off2), fmaxf((t ? q1 : q0) - ss * m, 0.f), tag);
        }
        TRC(tr, w, tb + 8);
        TRC(tr, w, tb + 9);
#pragma unroll 1
        for (int p = 5;; p++) {
          pass(p, 0x40000040u);
          if (p == 8) break;
          gelu(Int<0>{});
          z1d += 8192;
        }
        signal(EV_Z1);
#pragma unroll
        for (int i = 0; i < 16; i++) zk[i] = pack2(acc[2 * i], acc[2 * i + 1]);
        SCLK(18);
        TRC(tr, w, tb + 12);
      }
      uint32_t hA[18][4];
      {
        float acc[144];
        const float c0 = __uint_as_float(lds32(sb + SM_OFF + 4));
#pragma unroll
        for (int i = 0; i < 144; i++) {
          asm volatile("fma.rn.f32 %0, %1, %2, %3;" : "=f"(acc[i]) : "f"(__uint_as_float(P.zero)), "f"((float)(i + 2)), "f"(c0));
        }
        uint32_t prev = 0;
        auto stage = [&](int kb, auto odd) {
          mbar_wait_c(bars + B_FULL + c.s * 8, c.ph);
          TRC(tr && kb == 0, w, tb + 13);
          SCLK(22 + kb);
          const uint32_t st = sb + c.s * ST_BYTES, rt = sb + SM_RT + kb * 128 + t * 8;
          uint64_t db = dsc2(dlo(st + ST_B, 4608), 0, 8 + P.zero);
          uint32_t a[4][4];
#pragma unroll
          for (int kk = 0; kk < 4; kk++) {
            uint32_t r[4];
            ldsm4(r, st + (aoff ^ (kk << 5)));
            const uint2 sc = lds64(rt + kk * 32);
            a[kk][0] = hmul2(__byte_perm(r[0], r[2], 0x5410), sc.x); a[kk][2] = hmul2(__byte_perm(r[0], r[2], 0x7632), sc.y);
            a[kk][1] = hmul2(__byte_perm(r[1], r[3], 0x5410), sc.x); a[kk][3] = hmul2(__byte_perm(r[1], r[3], 0x7632), sc.y);
          }
          if (!odd.value) {
            const float x = blo(zk[0]), y = bhi(zk[0]);
#pragma unroll
            for (int i = 0; i < 15; i++) zk[i] = zk[i + 1];
            zk[15] = pack2(fmaf(x, tanh_fast(x * fmaf(x, x, GB)), x), fmaf(y, tanh_fast(y * fmaf(y, y, GB)), y));
          }
          wgmma_fence();
#pragma unroll
          for (int i = 0; i < 8; i++) {
            const int kk = i & 3, hf = i >> 2;
            wgmma_rs_n144(acc + hf * 72, a[kk], db, 1);
            dadd(db, i == 3 ? 144u - 3 * 576 : 576 + P.zero);
            if (i == 0) { wgmma_commit(); wgmma_wait<1>(); release_if(kb, prev); }
            if (i == 3) wgmma_commit();
          }
          wgmma_commit();
          prev = c.s; c.next();
        };
        mbar_wait_c(bars + B_RT, L);
#pragma unroll 1
        for (int kb = 0; kb < 32; kb += 2) {
          if (kb == 8) mbar_wait_c(bars + B_RT1, L);
          MCLK((kb & 7) == 4, 10 + (kb >> 3));
          stage(kb, Int<0>{});
          stage(kb + 1, Int<1>{});
        }
        if (w == 1) bar_arrive(6, 256);
        HCLK(0);
        mbar_wait_c(bars + B_CV + w * 8, L);
        HCLK(1);
        const float gk = 0.5f / GA;
        const float c1 = __uint_as_float(lds32(sb + SM_OFF + 4));
        const float gb0 = -gk * (c1 + __uint_as_float(lds32(sb + SM_CV + w * 256 + (16 * q + g) * 4))), gb1 = -gk * (c1 + __uint_as_float(lds32(sb + SM_CV + w * 256 + (16 * q + g + 8) * 4)));
        mbar_wait_c(w ? bars + B_FULL + c.s * 8 : bars + B_ZB, w ? c.ph : L);
        HCLK(2);
        const uint32_t sx = c.s;
        c.next();
        const uint32_t zt = sb + tid * 16, zs = zt + sx * ST_BYTES + w * 24576;
        uint4 zz[18];
        auto zload = [&](int u) {
          if (ZW && u == ZW && P.zero) __nanosleep(0);
          if (u >= 12 && u < 16) zz[u] = make_uint4(zk[4 * u - 48], zk[4 * u - 47], zk[4 * u - 46], zk[4 * u - 45]); else zz[u] = lds128(u == 17 ? zt + SM_STG : zs + (u < 12 ? u : 12) * 2048);
        };
#pragma unroll
        for (int u = 0; u < ZA; u++) zload(u);
#pragma unroll
        for (int u = 0; u < 18; u++) {
          if (u == 0) { wgmma_wait<1>(); HCLK(3); }
          if (u == 9) {
            HCLK(4);
            wgmma_wait<0>();
            HCLK(5);
            release(prev);
            mbar_arrive_if(L == 0 && lane == 0, ev + EV_P4 * 8);
            TRC(tr, w, tb + 14);
            SCLK(54);
          }
          if (u + ZA < 18) zload(u + ZA);
          const uint4 z = zz[u];
          hA[u][0] = hmul2(z.x, pack2(fmaf(acc[8 * u], gk, gb0), fmaf(acc[8 * u + 1], gk, gb0)));
          hA[u][1] = hmul2(z.y, pack2(fmaf(acc[8 * u + 2], gk, gb1), fmaf(acc[8 * u + 3], gk, gb1)));
          hA[u][2] = hmul2(z.z, pack2(fmaf(acc[8 * u + 4], gk, gb0), fmaf(acc[8 * u + 5], gk, gb0)));
          hA[u][3] = hmul2(z.w, pack2(fmaf(acc[8 * u + 6], gk, gb1), fmaf(acc[8 * u + 7], gk, gb1)));
        }
        uint32_t dep = P.zero;
#pragma unroll
        for (int u = 0; u < 18; u++) dep &= hA[u][0];
        release(sx, dep);
        TRC(tr, w, tb + 15);
        HCLK(6);
      }
      {
        const uint32_t el = elect_one();
#pragma unroll 1
        for (int p = 0; p < 9; p++) {
          float acc[32];
          if (w == 0) mbar_wait_c(bars + B_FULL + c.s * 8, c.ph);
          uint64_t db = dsc2(dlo(sb + c.s * ST_BYTES + ST_B + (j & 1) * 4096, 0), 0, 0x40000040u + P.zero);
          HCLK(7 + 2 * p);
          bar_sync(6 + w, 256);
          wgmma_fence();
#pragma unroll
          for (int kk = 0; kk < 18; kk++) {
            wgmma_rs_n64(acc, hA[kk], db, kk != 0);
            dadd(db, kk == 15 ? 128 - (j & 1) * (36864 >> 4) : 128 + P.zero);
            if (kk == PPK && (w == 0 || p < 8)) bar_arrive(7 - w, 256);
          }
          wgmma_commit();
          const uint32_t d = sb + (p & 3) * ST_BYTES, cb = p + j >= 9 ? p + j - 9 : p + j;
          if (el) asm volatile("cp.async.bulk.commit_group;\ncp.async.bulk.wait_group.read 3;" ::: "memory");
          __syncwarp();
          wgmma_wait<0>();
          HCLK(8 + 2 * p);
          MCLK(p == 1 || p == 8, 7 + (p >> 3));
          TRC(tr && p == 8, w, tb + 16);
          release_if(L == 0 || p < 5, c.s);
          c.next();
#pragma unroll
          for (int u = 0; u < 4; u++)
            stsm4(d + (aoff ^ (u << 5)), pack2(acc[8 * u], acc[8 * u + 1]), pack2(acc[8 * u + 2], acc[8 * u + 3]), pack2(acc[8 * u + 4], acc[8 * u + 5]), pack2(acc[8 * u + 6], acc[8 * u + 7]));
          fence_async_s();
          __syncwarp();
          tma3d_red_p(el, &P.red[L], cb * 64, rb * 64 + q * 16, w, d + w * 8192 + q * 2048);
          TRC(tr && p == 8, w, tb + 17);
        }
        if (el) asm volatile("cp.async.bulk.commit_group;\ncp.async.bulk.wait_group 0;" ::: "memory");
        HCLK(25);
        MCLK(1, 9);
        if (L == 0) signal(EV_PT);
        TRC(tr, w, tb + 18);
      }
    }
  }
}

typedef CUresult (*EncodeFn)(CUtensorMap*, CUtensorMapDataType, cuuint32_t, void*, const cuuint64_t*, const cuuint64_t*, const cuuint32_t*,
                             const cuuint32_t*, CUtensorMapInterleave, CUtensorMapSwizzle, CUtensorMapL2promotion, CUtensorMapFloatOOBfill);

static void make_map(EncodeFn fn, CUtensorMap* m, const void* ptr, int rank, uint64_t d0, uint64_t d1, uint64_t d2, uint64_t s1, uint64_t s2,
                     uint32_t b0, uint32_t b1, uint32_t b2, CUtensorMapSwizzle swz) {
  cuuint64_t dims[3] = {d0, d1, d2}, strides[2] = {s1, s2};
  cuuint32_t box[3] = {b0, b1, b2}, es[3] = {1, 1, 1};
  fn(m, CU_TENSOR_MAP_DATA_TYPE_BFLOAT16, rank, const_cast<void*>(ptr), dims, strides, box, es, CU_TENSOR_MAP_INTERLEAVE_NONE, swz,
     CU_TENSOR_MAP_L2_PROMOTION_L2_128B, CU_TENSOR_MAP_FLOAT_OOB_FILL_NONE);
}

}

extern "C" void kernel_launch(void* const* d_in, const int* in_sizes, int n_in, void* d_out, int out_size) {
  using namespace mk;
  (void)in_sizes; (void)n_in; (void)out_size;
  static EncodeFn fn = nullptr;
  static Scratch* sc;
  if (!fn) {
    cudaGetSymbolAddress((void**)&sc, g_scratch);
    cudaDriverEntryPointQueryResult qr;
    cudaGetDriverEntryPoint("cuTensorMapEncodeTiled", (void**)&fn, cudaEnableDefault, &qr);
    cudaFuncSetAttribute(mega_kernel, cudaFuncAttributeMaxDynamicSharedMemorySize, SM_TOTAL);
  }
  Params p;
  p.wqkv = (const __nv_bfloat16*)d_in[1];
  p.w_in = (const __nv_bfloat16*)d_in[4];
  p.w_sp = (const __nv_bfloat16*)d_in[5];
  p.b_sp = (const __nv_bfloat16*)d_in[6];
  p.w_out = (const __nv_bfloat16*)d_in[7];
  p.zero = 0;
  p.s = sc;
  p.xs[0] = (uint8_t*)d_in[0];
  p.xs[1] = sc->X;
  p.xs[2] = (uint8_t*)d_out;
  make_map(fn, &p.wsp, p.w_sp, 3, 2048, 1024, 2, 8192, 4096, 64, 64, 2, CU_TENSOR_MAP_SWIZZLE_128B);
  for (int i = 0; i < 2; i++) {
    make_map(fn, &p.red[i], p.xs[i + 1], 3, DM, 1024, 2, 2304, 1152, 64, 16, 1, CU_TENSOR_MAP_SWIZZLE_128B);
    make_map(fn, &p.res[i], p.xs[i], 3, DM, 1024, 2, 2304, 1152, 144, 64, 1, CU_TENSOR_MAP_SWIZZLE_NONE);
  }
  make_map(fn, &p.psn, d_out, 3, DM, 1024, 2, 2304, 1152, 144, 4, 1, CU_TENSOR_MAP_SWIZZLE_NONE);
  for (int i = 0; i < 3; i++) make_map(fn, &p.act[i], p.xs[i], 3, DM, 1024, 2, 2304, 1152, 64, 64, 1, CU_TENSOR_MAP_SWIZZLE_128B);
  {
    cuuint64_t dims[4] = {8, 8, 72, 72}, strides[3] = {1152, 16, 9216};
    cuuint32_t box[4] = {8, 8, 9, 5}, es[4] = {1, 1, 1, 1};
    fn(&p.wo8, CU_TENSOR_MAP_DATA_TYPE_BFLOAT16, 4, d_in[2], dims, strides, box, es, CU_TENSOR_MAP_INTERLEAVE_NONE, CU_TENSOR_MAP_SWIZZLE_NONE,
       CU_TENSOR_MAP_L2_PROMOTION_L2_128B, CU_TENSOR_MAP_FLOAT_OOB_FILL_NONE);
  }
  for (int i = 0; i < 2; i++) {
    cuuint64_t dims[4] = {i ? 4608u : 2304u, 8, i ? 1u : 2u, 72}, strides[3] = {9216, 4608, 8 * 9216};
    cuuint32_t box[4] = {i ? 64u : 32u, 8, i ? 1u : 2u, 18}, es[4] = {1, 1, 1, 1};
    fn(i ? &p.win64 : &p.win, CU_TENSOR_MAP_DATA_TYPE_BFLOAT16, 4, d_in[4], dims, strides, box, es, CU_TENSOR_MAP_INTERLEAVE_NONE,
       i ? CU_TENSOR_MAP_SWIZZLE_128B : CU_TENSOR_MAP_SWIZZLE_64B, CU_TENSOR_MAP_L2_PROMOTION_L2_128B, CU_TENSOR_MAP_FLOAT_OOB_FILL_NONE);
  }
  make_map(fn, &p.wout, p.w_out, 2, 576, 2304, 1, 1152, 0, 64, 144, 1, CU_TENSOR_MAP_SWIZZLE_128B);
  mega_kernel<<<NGRID, 384, SM_TOTAL, cudaStreamPerThread>>>(p);
}
```

```cpp
#include <cuda_runtime.h>
#include <cuda.h>
#include <cuda_bf16.h>
#include <stdint.h>

#define MK_TRACE 0
#define MK_DBG 0
#define P5TRACE 0
#define LAG1 3
#define PP3 34
#define PP30 33
#define SPL 2
#define NAP 200
#define NAP0 8000
#define KS2 1
#define KS3 1
#define RL3 21
#define PAD 0
#define ZA 4
#define ZW 13
#define GA3 10
#define GB3 12
#define GM2 1
#define GMM 1
#define GM1 2
#define C0S 32.f
#define OFA 0.125f
#define OFK 2.f
#define PPK 16

namespace mk {

constexpr int SEQ = 2048, DM = 576, FH = 2304;
constexpr int NCTA = 128;
constexpr int NGRID = 132;
constexpr uint32_t ZB = 36864;
constexpr uint32_t WQ_SL = 72 * 3456;
constexpr uint32_t WO_SL = 72 * 1152;
constexpr float LN_EPS = 1e-5f;
constexpr float GA = 0.3292034911525734f, GB = 2.423681954311584f;

constexpr uint32_t ST_BYTES = 53248, ST_B = 16384, NST = 4;
constexpr uint32_t SM_STG = NST * ST_BYTES;
constexpr uint32_t SM_BAR = SM_STG + 2 * 9216;
constexpr uint32_t SM_OFF = SM_BAR + 1008;
constexpr uint32_t SM_TOTAL = SM_BAR + 1024;
constexpr uint32_t SM_RT = SM_STG + 4096, SM_CV = SM_STG + 12288, SM_WT = SM_CV + 512;
constexpr uint32_t SM_WOI = 44032, SM_CSQ = 49792, SM_XST = 50688;
constexpr uint32_t B_FULL = 0, B_EMPTY = 32, B_FULLA = 64, B_RES = 128, B_WT = 144, B_IMG = 160, B_WOI = 168, B_ZB = 176, B_GATE3 = 184, B_Z1 = 192, B_LAG = 200,
                   B_RT = 208, B_CSQ = 216, B_CV = 224, B_AD = 240, B_EVT = 272, B_RT1 = 368, B_XS = 624, B_XRW = 384, B_FA3 = 400, B_EA3 = 544;
enum { EV_PT = 0, EV_O = 1, EV_X1 = 2, EV_ZN = 3, EV_Z1 = 4, EV_P4 = 5, EV_N = 6 };

enum { FR_X2 = 0, FR_O = 1, FR_X1 = 3, FR_EP = 16, FJ = 32 * 32, FJ_WQ = 0, FJ_WO = 1, FJ_WQ0 = 2, FJ_ZN = 3, FJ_P4 = 5, FJ_EP = 16, F_N = FJ + 8 * 32 };

constexpr uint32_t POISON = 0xffffffffu;
struct Scratch {
  uint32_t flags[F_N];
  uint2 RT[SEQ];
  uint4 XST[2 * SEQ];
  uint4 ST1[SEQ * 8], ZST[SEQ * 8], HALO[32 * 8 * 6 * 32];
  float CSP[2 * NCTA * 216];
  uint8_t WQ[8 * WQ_SL], WO[8 * WO_SL];
  uint8_t O[32 * 2 * ZB];
  uint8_t X[SEQ * DM * 2];
  uint8_t Z[512 * ZB];
  uint4 RD[NCTA * 36 * 256];
};
__device__ __align__(1024) Scratch g_scratch;
#define SLOW(i) do {} while (0)

struct Params {
  const __nv_bfloat16 *wqkv;
  Scratch* s;
  uint32_t zero;
  const __nv_bfloat16 *w_in, *w_sp, *b_sp, *w_out;
  uint8_t* xs[3];
  CUtensorMap wo8, wsp, win, win64, wout;
  CUtensorMap act[3];
  CUtensorMap res[2];
  CUtensorMap red[2];
  CUtensorMap psn;
};

__device__ __forceinline__ uint32_t smem_u32(const void* p) { return (uint32_t)__cvta_generic_to_shared(p); }
__device__ __forceinline__ void mbar_init(uint32_t bar, uint32_t cnt) { asm volatile("mbarrier.init.shared::cta.b64 [%0], %1;" ::"r"(bar), "r"(cnt)); }
__device__ __forceinline__ void mbar_arrive(uint32_t bar) { asm volatile("mbarrier.arrive.shared::cta.b64 _, [%0];" ::"r"(bar) : "memory"); }
__device__ __forceinline__ void mbar_wait(uint32_t bar, uint32_t parity) {
  asm volatile(
      "{\n.reg .pred p;\n.reg .u32 c;\nmov.u32 c, 0;\nLAB_WAIT:\n"
      "mbarrier.try_wait.parity.shared::cta.b64 p, [%0], %1;\n@p bra LAB_DONE;\n"
      "add.u32 c, c, 1;\nsetp.lt.u32 p, c, 0x100000;\n@p bra LAB_WAIT;\ntrap;\nLAB_DONE:\n}" ::"r"(bar), "r"(parity)
      : "memory");
}
__device__ __forceinline__ void mbar_wait_c(uint32_t bar, uint32_t parity) {
  asm volatile("{\n.reg .pred p;\nLAB_WAIT:\nmbarrier.try_wait.parity.shared::cta.b64 p, [%0], %1;\n@!p bra LAB_WAIT;\n}" ::"r"(bar), "r"(parity) : "memory");
}
__device__ __forceinline__ void flag_wait(const uint32_t* f, uint32_t target) {
  asm volatile(
      "{\n.reg .pred p;\n.reg .u32 c, v;\nmov.u32 c, 0;\nLAB_WAIT:\n"
      "ld.relaxed.gpu.global.u32 v, [%0];\nsub.u32 v, v, %1;\nsetp.ge.s32 p, v, 0;\n@p bra LAB_DONE;\n"
      "add.u32 c, c, 1;\nsetp.lt.u32 p, c, 0x400000;\n@p bra LAB_WAIT;\ntrap;\nLAB_DONE:\nfence.acquire.gpu;\n}" ::"l"(f), "r"(target)
      : "memory");
}
__device__ __forceinline__ void fence_gpu() { asm volatile("fence.acq_rel.gpu;" ::: "memory"); }
__device__ __forceinline__ void fence_async_g() { asm volatile("fence.proxy.async.global;" ::: "memory"); }
__device__ __forceinline__ void fence_async_s() { asm volatile("fence.proxy.async.shared::cta;" ::: "memory"); }
__device__ __forceinline__ uint32_t elect_one() {
  uint32_t p; asm volatile("{\n.reg .pred P;\nelect.sync _|P, 0xffffffff;\nselp.u32 %0, 1, 0, P;\n}" : "=r"(p)); return p;
}
__device__ __forceinline__ void expect_tx_p(uint32_t el, uint32_t bar, uint32_t bytes) {
  asm volatile("{\n.reg .pred P;\nsetp.ne.u32 P, %2, 0;\n@P mbarrier.arrive.expect_tx.shared::cta.b64 _, [%0], %1;\n}" ::"r"(bar), "r"(bytes), "r"(el) : "memory");
}
__device__ __forceinline__ void bulk_load_p(uint32_t el, uint32_t dst, const void* src, uint32_t bytes, uint32_t bar) {
  asm volatile("{\n.reg .pred P;\nsetp.ne.u32 P, %4, 0;\n@P cp.async.bulk.shared::cluster.global.mbarrier::complete_tx::bytes [%0], [%1], %2, [%3];\n}" ::"r"(dst), "l"(src), "r"(bytes), "r"(bar), "r"(el) : "memory");
}
__device__ __forceinline__ uint64_t policy_evict_first() { uint64_t p; asm("createpolicy.fractional.L2::evict_first.b64 %0, 1.0;" : "=l"(p)); return p; }
__device__ __forceinline__ void bulk_load_h(uint32_t el, uint32_t dst, const void* src, uint32_t bytes, uint32_t bar, bool ef, uint64_t pol) {
  if (ef) {
    asm volatile("{\n.reg .pred P;\nsetp.ne.u32 P, %4, 0;\n@P cp.async.bulk.shared::cluster.global.mbarrier::complete_tx::bytes.L2::cache_hint [%0], [%1], %2, [%3], %5;\n}" ::"r"(dst), "l"(src), "r"(bytes), "r"(bar), "r"(el), "l"(pol) : "memory");
  } else {
    asm volatile("{\n.reg .pred P;\nsetp.ne.u32 P, %4, 0;\n@P cp.async.bulk.shared::cluster.global.mbarrier::complete_tx::bytes [%0], [%1], %2, [%3];\n}" ::"r"(dst), "l"(src), "r"(bytes), "r"(bar), "r"(el) : "memory");
  }
}
__device__ __forceinline__ void bulk_mc_h(uint32_t el, uint32_t dst, const void* src, uint32_t bytes, uint32_t bar, bool ef, uint64_t pol) {
  if (ef) {
    asm volatile("{\n.reg .pred P;\nsetp.ne.u32 P, %4, 0;\n@P cp.async.bulk.shared::cluster.global.mbarrier::complete_tx::bytes.multicast::cluster.L2::cache_hint [%0], [%1], %2, [%3], %5, %6;\n}" ::"r"(dst), "l"(src), "r"(bytes), "r"(bar), "r"(el), "h"((uint16_t)3), "l"(pol) : "memory");
  } else {
    asm volatile("{\n.reg .pred P;\nsetp.ne.u32 P, %4, 0;\n@P cp.async.bulk.shared::cluster.global.mbarrier::complete_tx::bytes.multicast::cluster [%0], [%1], %2, [%3], %5;\n}" ::"r"(dst), "l"(src), "r"(bytes), "r"(bar), "r"(el), "h"((uint16_t)3) : "memory");
  }
}
__device__ __forceinline__ void tma3d_h(uint32_t el, uint32_t dst, const CUtensorMap* m, int c0, int c1, int c2, uint32_t bar, bool ef, uint64_t pol) {
  if (ef) {
    asm volatile("{\n.reg .pred P;\nsetp.ne.u32 P, %6, 0;\n@P cp.async.bulk.tensor.3d.shared::cluster.global.mbarrier::complete_tx::bytes.L2::cache_hint [%0], [%1, {%3, %4, %5}], [%2], %7;\n}" ::"r"(dst), "l"(m), "r"(bar), "r"(c0), "r"(c1), "r"(c2), "r"(el), "l"(pol) : "memory");
  } else {
    asm volatile("{\n.reg .pred P;\nsetp.ne.u32 P, %6, 0;\n@P cp.async.bulk.tensor.3d.shared::cluster.global.mbarrier::complete_tx::bytes [%0], [%1, {%3, %4, %5}], [%2];\n}" ::"r"(dst), "l"(m), "r"(bar), "r"(c0), "r"(c1), "r"(c2), "r"(el) : "memory");
  }
}
__device__ __forceinline__ void tma2d_mc_h(uint32_t el, uint32_t dst, const CUtensorMap* m, int c0, int c1, uint32_t bar, bool ef, uint64_t pol) {
  if (ef) {
    asm volatile("{\n.reg .pred P;\nsetp.ne.u32 P, %5, 0;\n@P cp.async.bulk.tensor.2d.shared::cluster.global.mbarrier::complete_tx::bytes.multicast::cluster.L2::cache_hint [%0], [%1, {%3, %4}], [%2], %6, %7;\n}" ::"r"(dst), "l"(m), "r"(bar), "r"(c0), "r"(c1), "r"(el), "h"((uint16_t)3), "l"(pol) : "memory");
  } else {
    asm volatile("{\n.reg .pred P;\nsetp.ne.u32 P, %5, 0;\n@P cp.async.bulk.tensor.2d.shared::cluster.global.mbarrier::complete_tx::bytes.multicast::cluster [%0], [%1, {%3, %4}], [%2], %6;\n}" ::"r"(dst), "l"(m), "r"(bar), "r"(c0), "r"(c1), "r"(el), "h"((uint16_t)3) : "memory");
  }
}
__device__ __forceinline__ void tma4d_mc(uint32_t el, uint32_t dst, const CUtensorMap* m, int c0, int c3, uint32_t bar, uint64_t pol) {
  asm volatile("{\n.reg .pred P;\nsetp.ne.u32 P, %5, 0;\n@P cp.async.bulk.tensor.4d.shared::cluster.global.mbarrier::complete_tx::bytes.multicast::cluster.L2::cache_hint [%0], [%1, {%3, 0, 0, %4}], [%2], %6, %7;\n}" ::"r"(dst), "l"(m), "r"(bar), "r"(c0), "r"(c3), "r"(el), "h"((uint16_t)3), "l"(pol) : "memory");
}
__device__ __forceinline__ void mbar_arrive_cluster(uint32_t addr) { asm volatile("mbarrier.arrive.shared::cluster.b64 _, [%0];" ::"r"(addr) : "memory"); }
__device__ __forceinline__ void mbar_arrive_cluster_if(bool c, uint32_t addr) {
  asm volatile("{\n.reg .pred P;\nsetp.ne.u32 P, %1, 0;\n@P mbarrier.arrive.shared::cluster.b64 _, [%0];\n}" ::"r"(addr), "r"((uint32_t)c) : "memory");
}
__device__ __forceinline__ void mbar_arrive_if(bool c, uint32_t addr) {
  asm volatile("{\n.reg .pred P;\nsetp.ne.u32 P, %1, 0;\n@P mbarrier.arrive.shared::cta.b64 _, [%0];\n}" ::"r"(addr), "r"((uint32_t)c) : "memory");
}
__device__ __forceinline__ uint32_t mapa(uint32_t addr, uint32_t rank) { uint32_t r; asm("mapa.shared::cluster.u32 %0, %1, %2;" : "=r"(r) : "r"(addr), "r"(rank)); return r; }
__device__ __forceinline__ void bulk_store_p(uint32_t el, void* dst, uint32_t src, uint32_t bytes) {
  asm volatile("{\n.reg .pred P;\nsetp.ne.u32 P, %3, 0;\n@P cp.async.bulk.global.shared::cta.bulk_group [%0], [%1], %2;\n}" ::"l"(dst), "r"(src), "r"(bytes), "r"(el) : "memory");
}
__device__ __forceinline__ void flag_release_p(uint32_t el, uint32_t* f) {
  asm volatile("{\n.reg .pred P;\nsetp.ne.u32 P, %1, 0;\n@P red.release.gpu.global.add.u32 [%0], 1;\n}" ::"l"(f), "r"(el) : "memory");
}
__device__ __forceinline__ void flag_add_p(uint32_t el, uint32_t* f) {
  asm volatile("{\n.reg .pred P;\nsetp.ne.u32 P, %1, 0;\n@P red.relaxed.gpu.global.add.u32 [%0], 1;\n}" ::"l"(f), "r"(el) : "memory");
}
__device__ __forceinline__ void prefetch_l2(const void* src, uint32_t bytes) { asm volatile("cp.async.bulk.prefetch.L2.global [%0], %1;" ::"l"(src), "r"(bytes) : "memory"); }
__device__ __forceinline__ void prefetch_map(const CUtensorMap* m) { asm volatile("prefetch.tensormap [%0];" ::"l"(m) : "memory"); }
__device__ __forceinline__ void wgmma_fence() { asm volatile("wgmma.fence.sync.aligned;" ::: "memory"); }
__device__ __forceinline__ void wgmma_commit() { asm volatile("wgmma.commit_group.sync.aligned;" ::: "memory"); }
template <int N> __device__ __forceinline__ void wgmma_wait() { asm volatile("wgmma.wait_group.sync.aligned %0;" ::"n"(N) : "memory"); }
__device__ __forceinline__ uint32_t dlo(uint32_t addr, uint32_t lbo) { return ((addr & 0x3FFFF) >> 4) + ((lbo >> 4) << 16); }
template <uint32_t SBO, uint32_t SWZ> __device__ __forceinline__ uint64_t dsc(uint32_t lo, uint32_t off) {
  uint64_t d; asm("mov.b64 %0, {%1, %2};" : "=l"(d) : "r"(lo + (off >> 4)), "n"((SBO >> 4) | (SWZ << 30))); return d;
}
__device__ __forceinline__ uint64_t dsc2(uint32_t lo, uint32_t off, uint32_t hi) {
  uint64_t d; asm("mov.b64 %0, {%1, %2};" : "=l"(d) : "r"(lo + (off >> 4)), "r"(hi)); return d;
}
__device__ __forceinline__ uint64_t dat(uint64_t d, uint32_t off, uint32_t one) { uint64_t r; asm("mad.wide.u32 %0, %1, %2, %3;" : "=l"(r) : "r"(one), "r"(off >> 4), "l"(d)); return r; }
__device__ __forceinline__ void dadd(uint64_t& d, uint32_t v) {
  asm("{\n.reg .b32 lo, hi;\nmov.b64 {lo, hi}, %0;\nadd.u32 lo, lo, %1;\nmov.b64 %0, {lo, hi};\n}" : "+l"(d) : "r"(v));
}
template <int R> __device__ __forceinline__ void reg_alloc() { asm volatile("setmaxnreg.inc.sync.aligned.u32 %0;" ::"n"(R)); }
template <int R> __device__ __forceinline__ void reg_dealloc() { asm volatile("setmaxnreg.dec.sync.aligned.u32 %0;" ::"n"(R)); }
__device__ __forceinline__ void bar_sync(int id, int n) { asm volatile("bar.sync %0, %1;" ::"r"(id), "r"(n) : "memory"); }
__device__ __forceinline__ void bar_arrive(int id, int n) { asm volatile("bar.arrive %0, %1;" ::"r"(id), "r"(n) : "memory"); }
__device__ __forceinline__ void ldsm4(uint32_t* r, uint32_t addr) {
  asm volatile("ldmatrix.sync.aligned.m8n8.x4.shared.b16 {%0,%1,%2,%3}, [%4];" : "=r"(r[0]), "=r"(r[1]), "=r"(r[2]), "=r"(r[3]) : "r"(addr) : "memory");
}
__device__ __forceinline__ uint32_t movm(uint32_t a) { uint32_t d; asm volatile("movmatrix.sync.aligned.m8n8.trans.b16 %0, %1;" : "=r"(d) : "r"(a)); return d; }
__device__ __forceinline__ void mma16(float* c, uint32_t a0, uint32_t a1, uint32_t a2, uint32_t a3, uint32_t b0, uint32_t b1) {
  asm volatile("mma.sync.aligned.m16n8k16.row.col.f32.bf16.bf16.f32 {%0,%1,%2,%3}, {%4,%5,%6,%7}, {%8,%9}, {%10,%10,%10,%10};"
               : "=f"(c[0]), "=f"(c[1]), "=f"(c[2]), "=f"(c[3]) : "r"(a0), "r"(a1), "r"(a2), "r"(a3), "r"(b0), "r"(b1), "f"(0.f));
}
__device__ __forceinline__ void mma8(float* c, uint32_t a0, uint32_t a1, uint32_t b0) {
  asm volatile("mma.sync.aligned.m16n8k8.row.col.f32.bf16.bf16.f32 {%0,%1,%2,%3}, {%4,%5}, {%6}, {%0,%1,%2,%3};"
               : "+f"(c[0]), "+f"(c[1]), "+f"(c[2]), "+f"(c[3]) : "r"(a0), "r"(a1), "r"(b0));
}
__device__ __forceinline__ void widen(float* c, uint32_t a0, uint32_t a1, uint32_t eye) {
  asm volatile("mma.sync.aligned.m16n8k8.row.col.f32.bf16.bf16.f32 {%0,%1,%2,%3}, {%4,%5}, {%6}, {%7,%7,%7,%7};"
               : "=f"(c[0]), "=f"(c[1]), "=f"(c[2]), "=f"(c[3]) : "r"(a0), "r"(a1), "r"(eye), "f"(0.f));
}
__device__ __forceinline__ float rsq_fast(float x) { float y; asm("rsqrt.approx.ftz.f32 %0, %1;" : "=f"(y) : "f"(x)); return y; }
__device__ __forceinline__ uint32_t pack2(float lo, float hi) { uint32_t r; asm("cvt.rn.bf16x2.f32 %0, %1, %2;" : "=r"(r) : "f"(hi), "f"(lo)); return r; }
__device__ __forceinline__ float blo(uint32_t v) { return __uint_as_float(v << 16); }
__device__ __forceinline__ float bhi(uint32_t v) { return __uint_as_float(v & 0xffff0000u); }
__device__ __forceinline__ float tanh_fast(float x) { float y; asm("tanh.approx.f32 %0, %1;" : "=f"(y) : "f"(x)); return y; }
__device__ __forceinline__ float rcp_fast(float x) { float y; asm("rcp.approx.ftz.f32 %0, %1;" : "=f"(y) : "f"(x)); return y; }
__device__ __forceinline__ float ex2(float x) { float y; asm("ex2.approx.ftz.f32 %0, %1;" : "=f"(y) : "f"(x)); return y; }
__device__ __forceinline__ float qsum(float v) { v += __shfl_xor_sync(~0u, v, 1); v += __shfl_xor_sync(~0u, v, 2); return v; }
__device__ __forceinline__ float qmax(float v) { v = fmaxf(v, __shfl_xor_sync(~0u, v, 1)); v = fmaxf(v, __shfl_xor_sync(~0u, v, 2)); return v; }
__device__ __forceinline__ void stg32(void* p, uint32_t v) { asm volatile("st.global.u32 [%0], %1;" ::"l"(p), "r"(v) : "memory"); }
__device__ __forceinline__ void stg128(void* p, uint32_t a, uint32_t b, uint32_t c, uint32_t d) { asm volatile("st.global.v4.u32 [%0], {%1,%2,%3,%4};" ::"l"(p), "r"(a), "r"(b), "r"(c), "r"(d) : "memory"); }
__device__ __forceinline__ uint32_t ldcg32(const void* p) { uint32_t v; asm volatile("ld.global.L1::no_allocate.u32 %0, [%1];" : "=r"(v) : "l"(p) : "memory"); return v; }
__device__ __forceinline__ uint32_t ldgpu32(const void* p) { uint32_t v; asm volatile("ld.relaxed.gpu.global.u32 %0, [%1];" : "=r"(v) : "l"(p) : "memory"); return v; }
__device__ __forceinline__ uint32_t ldca32(const void* p) { uint32_t v; asm volatile("ld.global.ca.u32 %0, [%1];" : "=r"(v) : "l"(p) : "memory"); return v; }
__device__ __forceinline__ void stg128_if(bool c, void* p, uint32_t a, uint32_t b, uint32_t cc, uint32_t d) {
  asm volatile("{\n.reg .pred P;\nsetp.ne.u32 P, %5, 0;\n@P st.global.v4.u32 [%0], {%1,%2,%3,%4};\n}" ::"l"(p), "r"(a), "r"(b), "r"(cc), "r"(d), "r"((uint32_t)c) : "memory");
}
__device__ __forceinline__ uint2 lds64(uint32_t a) { uint2 v; asm volatile("ld.shared.v2.u32 {%0,%1}, [%2];" : "=r"(v.x), "=r"(v.y) : "r"(a) : "memory"); return v; }
__device__ __forceinline__ uint4 ldcg128(const void* p) { uint4 v; asm volatile("ld.global.cg.v4.u32 {%0,%1,%2,%3}, [%4];" : "=r"(v.x), "=r"(v.y), "=r"(v.z), "=r"(v.w) : "l"(p) : "memory"); return v; }
__device__ __forceinline__ uint32_t ldnc16(const void* p) { uint16_t v; asm volatile("ld.global.nc.u16 %0, [%1];" : "=h"(v) : "l"(p)); return v; }
__device__ __forceinline__ uint4 ldnc128(const void* p) { uint4 v; asm volatile("ld.global.nc.v4.u32 {%0,%1,%2,%3}, [%4];" : "=r"(v.x), "=r"(v.y), "=r"(v.z), "=r"(v.w) : "l"(p)); return v; }
__device__ __forceinline__ uint32_t hsub2(uint32_t a, uint32_t b) { uint32_t d; asm("sub.rn.bf16x2 %0, %1, %2;" : "=r"(d) : "r"(a), "r"(b)); return d; }
__device__ __forceinline__ void stg32_if(bool c, void* p, uint32_t v) {
  asm volatile("{\n.reg .pred P;\nsetp.ne.u32 P, %2, 0;\n@P st.global.u32 [%0], %1;\n}" ::"l"(p), "r"(v), "r"((uint32_t)c) : "memory");
}
__device__ __forceinline__ uint32_t hmul2(uint32_t a, uint32_t b) { uint32_t d; asm("mul.rn.bf16x2 %0, %1, %2;" : "=r"(d) : "r"(a), "r"(b)); return d; }
__device__ __forceinline__ void sts32(uint32_t a, uint32_t v) { asm volatile("st.shared.u32 [%0], %1;" ::"r"(a), "r"(v) : "memory"); }
__device__ __forceinline__ uint32_t lds32(uint32_t a) { uint32_t v; asm volatile("ld.shared.u32 %0, [%1];" : "=r"(v) : "r"(a) : "memory"); return v; }
__device__ __forceinline__ void sts128(uint32_t a, uint32_t x, uint32_t y, uint32_t z, uint32_t w) { asm volatile("st.shared.v4.u32 [%0], {%1,%2,%3,%4};" ::"r"(a), "r"(x), "r"(y), "r"(z), "r"(w) : "memory"); }
__device__ __forceinline__ uint4 lds128(uint32_t a) { uint4 v; asm volatile("ld.shared.v4.u32 {%0,%1,%2,%3}, [%4];" : "=r"(v.x), "=r"(v.y), "=r"(v.z), "=r"(v.w) : "r"(a) : "memory"); return v; }
__device__ __forceinline__ void ll_st64(uint2* p, uint32_t v, uint32_t tag) {
  asm volatile("{\n.reg .b64 r;\nmov.b64 r, {%1,%2};\nst.relaxed.gpu.global.b64 [%0], r;\n}" ::"l"(p), "r"(v), "r"(tag) : "memory");
}
__device__ __forceinline__ uint2 ll_ld64(const uint2* p) {
  uint2 v; asm volatile("{\n.reg .b64 r;\nld.relaxed.gpu.global.b64 r, [%2];\nmov.b64 {%0,%1}, r;\n}" : "=r"(v.x), "=r"(v.y) : "l"(p) : "memory"); return v;
}
__device__ __forceinline__ void ll_st128(uint4* p, float a, float b, uint32_t tag, float c = 0.f) {
  asm volatile("{\n.reg .b128 r;\n.reg .b64 lo, hi;\nmov.b64 lo, {%1,%2};\nmov.b64 hi, {%3,%4};\nmov.b128 r, {lo, hi};\nst.relaxed.gpu.global.b128 [%0], r;\n}" ::"l"(p), "r"(__float_as_uint(a)), "r"(__float_as_uint(b)), "r"(tag), "r"(__float_as_uint(c)) : "memory");
}
__device__ __forceinline__ uint4 ll_ld128(const uint4* p) {
  uint4 v; asm volatile("{\n.reg .b128 r;\n.reg .b64 lo, hi;\nld.relaxed.gpu.global.b128 r, [%4];\nmov.b128 {lo, hi}, r;\nmov.b64 {%0,%1}, lo;\nmov.b64 {%2,%3}, hi;\n}" : "=r"(v.x), "=r"(v.y), "=r"(v.z), "=r"(v.w) : "l"(p) : "memory"); return v;
}
__device__ __forceinline__ void publish_p(uint32_t el, uint32_t* f) {
  asm volatile("{\n.reg .pred P;\nsetp.ne.u32 P, %1, 0;\n@P cp.async.bulk.commit_group;\n@P cp.async.bulk.wait_group 0;\n@P red.release.gpu.global.add.u32 [%0], 1;\n}" ::"l"(f), "r"(el) : "memory");
}
__device__ __forceinline__ void tma3d_red_p(uint32_t el, const CUtensorMap* m, int c0, int c1, int c2, uint32_t src) {
  asm volatile("{\n.reg .pred P;\nsetp.ne.u32 P, %5, 0;\n@P cp.reduce.async.bulk.tensor.3d.global.shared::cta.add.tile.bulk_group [%0, {%2, %3, %4}], [%1];\n}" ::"l"(m), "r"(src), "r"(c0), "r"(c1), "r"(c2), "r"(el) : "memory");
}
__device__ __forceinline__ void stsm4(uint32_t addr, uint32_t a, uint32_t b, uint32_t c, uint32_t d) {
  asm volatile("stmatrix.sync.aligned.m8n8.x4.shared.b16 [%0], {%1,%2,%3,%4};" ::"r"(addr), "r"(a), "r"(b), "r"(c), "r"(d) : "memory");
}
__device__ __forceinline__ void sts64(uint32_t a, uint32_t x, uint32_t y) { asm volatile("st.shared.v2.u32 [%0], {%1,%2};" ::"r"(a), "r"(x), "r"(y) : "memory"); }
__device__ __forceinline__ void ll_st128_if(bool on, uint4* p, float a, float b, uint32_t tag) {
  asm volatile("{\n.reg .pred P;\n.reg .b128 r;\n.reg .b64 lo, hi;\nsetp.ne.u32 P, %4, 0;\nmov.b64 lo, {%1,%2};\nmov.b64 hi, {%3,%3};\nmov.b128 r, {lo, hi};\n@P st.relaxed.gpu.global.b128 [%0], r;\n}" ::"l"(p), "r"(__float_as_uint(a)), "r"(__float_as_uint(b)), "r"(tag), "r"((uint32_t)on) : "memory");
}
__device__ __forceinline__ uint4 ldnc128_if(bool c, const void* p) {
  uint4 v = make_uint4(0u, 0u, 0u, 0u);
  asm volatile("{\n.reg .pred P;\nsetp.ne.u32 P, %5, 0;\n@P ld.global.nc.v4.u32 {%0,%1,%2,%3}, [%4];\n}" : "+r"(v.x), "+r"(v.y), "+r"(v.z), "+r"(v.w) : "l"(p), "r"((uint32_t)c));
  return v;
}
__device__ __forceinline__ uint32_t hfma2(uint32_t a, uint32_t b, uint32_t c) { uint32_t d; asm("fma.rn.bf16x2 %0, %1, %2, %3;" : "=r"(d) : "r"(a), "r"(b), "r"(c)); return d; }
__device__ __forceinline__ float2 lds64f(uint32_t a) { float2 v; asm volatile("ld.shared.v2.f32 {%0,%1}, [%2];" : "=f"(v.x), "=f"(v.y) : "r"(a) : "memory"); return v; }
#define TRC(cond, role, idx) do {} while (0)
#define TRV(role, idx, v) do {} while (0)

#define ACLK_INIT do {} while (0)
#define ACLK(i) do {} while (0)
#define ACLK_OUT do {} while (0)
#define QCLK(i) do {} while (0)
#define PH 1
#define RCLK(i) do {} while (0)
#define RCLK_INIT do {} while (0)
#define RCLK_OUT do {} while (0)
#define SCLK(i) do {} while (0)
#define HCLK(i) do {} while (0)
#define MCLK(c, i) do {} while (0)
#define CKK(i) do {} while (0)
#define CKK_OUT do {} while (0)
#define XCLK(i) do {} while (0)
#define PL 1
#define PCLK(i) do {} while (0)
#define PQ 1
#define CLK_INIT do {} while (0)
#define CLK(i) do {} while (0)
#define CLK_OUT do {} while (0)

__device__ __forceinline__ void wgmma_ss_n216(float* d, uint64_t da, uint64_t db, int scaleD) {
  asm volatile("{\n.reg .pred p;\nsetp.ne.b32 p, %110, 0;\nwgmma.mma_async.sync.aligned.m64n216k16.f32.bf16.bf16 "
    "{%0,%1,%2,%3,%4,%5,%6,%7,%8,%9,%10,%11,%12,%13,%14,%15,%16,%17,%18,%19,%20,%21,%22,%23,%24,%25,%26,%27,%28,%29,%30,%31,%32,%33,%34,%35,%36,%37,%38,%39,%40,%41,%42,%43,%44,%45,%46,%47,%48,%49,%50,%51,%52,%53,%54,%55,%56,%57,%58,%59,%60,%61,%62,%63,%64,%65,%66,%67,%68,%69,%70,%71,%72,%73,%74,%75,%76,%77,%78,%79,%80,%81,%82,%83,%84,%85,%86,%87,%88,%89,%90,%91,%92,%93,%94,%95,%96,%97,%98,%99,%100,%101,%102,%103,%104,%105,%106,%107}, "
    "%108, %109, p, 1, 1, 0, 1;\n}\n"
    : "+f"(d[0]), "+f"(d[1]), "+f"(d[2]), "+f"(d[3]), "+f"(d[4]), "+f"(d[5]), "+f"(d[6]), "+f"(d[7]), "+f"(d[8]), "+f"(d[9]), "+f"(d[10]), "+f"(d[11]), "+f"(d[12]), "+f"(d[13]), "+f"(d[14]), "+f"(d[15]), "+f"(d[16]), "+f"(d[17]), "+f"(d[18]), "+f"(d[19]), "+f"(d[20]), "+f"(d[21]), "+f"(d[22]), "+f"(d[23]), "+f"(d[24]), "+f"(d[25]), "+f"(d[26]), "+f"(d[27]), "+f"(d[28]), "+f"(d[29]), "+f"(d[30]), "+f"(d[31]), "+f"(d[32]), "+f"(d[33]), "+f"(d[34]), "+f"(d[35]), "+f"(d[36]), "+f"(d[37]), "+f"(d[38]), "+f"(d[39]), "+f"(d[40]), "+f"(d[41]), "+f"(d[42]), "+f"(d[43]), "+f"(d[44]), "+f"(d[45]), "+f"(d[46]), "+f"(d[47]), "+f"(d[48]), "+f"(d[49]), "+f"(d[50]), "+f"(d[51]), "+f"(d[52]), "+f"(d[53]), "+f"(d[54]), "+f"(d[55]), "+f"(d[56]), "+f"(d[57]), "+f"(d[58]), "+f"(d[59]), "+f"(d[60]), "+f"(d[61]), "+f"(d[62]), "+f"(d[63]), "+f"(d[64]), "+f"(d[65]), "+f"(d[66]), "+f"(d[67]), "+f"(d[68]), "+f"(d[69]), "+f"(d[70]), "+f"(d[71]), "+f"(d[72]), "+f"(d[73]), "+f"(d[74]), "+f"(d[75]), "+f"(d[76]), "+f"(d[77]), "+f"(d[78]), "+f"(d[79]), "+f"(d[80]), "+f"(d[81]), "+f"(d[82]), "+f"(d[83]), "+f"(d[84]), "+f"(d[85]), "+f"(d[86]), "+f"(d[87]), "+f"(d[88]), "+f"(d[89]), "+f"(d[90]), "+f"(d[91]), "+f"(d[92]), "+f"(d[93]), "+f"(d[94]), "+f"(d[95]), "+f"(d[96]), "+f"(d[97]), "+f"(d[98]), "+f"(d[99]), "+f"(d[100]), "+f"(d[101]), "+f"(d[102]), "+f"(d[103]), "+f"(d[104]), "+f"(d[105]), "+f"(d[106]), "+f"(d[107])
    : "l"(da), "l"(db), "r"(scaleD));
}
__device__ __forceinline__ void wgmma_ss_n72(float* d, uint64_t da, uint64_t db, int scaleD) {
  asm volatile("{\n.reg .pred p;\nsetp.ne.b32 p, %38, 0;\nwgmma.mma_async.sync.aligned.m64n72k16.f32.bf16.bf16 "
    "{%0,%1,%2,%3,%4,%5,%6,%7,%8,%9,%10,%11,%12,%13,%14,%15,%16,%17,%18,%19,%20,%21,%22,%23,%24,%25,%26,%27,%28,%29,%30,%31,%32,%33,%34,%35}, "
    "%36, %37, p, 1, 1, 0, 1;\n}\n"
    : "+f"(d[0]), "+f"(d[1]), "+f"(d[2]), "+f"(d[3]), "+f"(d[4]), "+f"(d[5]), "+f"(d[6]), "+f"(d[7]), "+f"(d[8]), "+f"(d[9]), "+f"(d[10]), "+f"(d[11]), "+f"(d[12]), "+f"(d[13]), "+f"(d[14]), "+f"(d[15]), "+f"(d[16]), "+f"(d[17]), "+f"(d[18]), "+f"(d[19]), "+f"(d[20]), "+f"(d[21]), "+f"(d[22]), "+f"(d[23]), "+f"(d[24]), "+f"(d[25]), "+f"(d[26]), "+f"(d[27]), "+f"(d[28]), "+f"(d[29]), "+f"(d[30]), "+f"(d[31]), "+f"(d[32]), "+f"(d[33]), "+f"(d[34]), "+f"(d[35])
    : "l"(da), "l"(db), "r"(scaleD));
}
__device__ __forceinline__ void wgmma_rs_n144(float* d, const uint32_t* a, uint64_t db, int scaleD) {
  asm volatile("{\n.reg .pred p;\nsetp.ne.b32 p, %77, 0;\nwgmma.mma_async.sync.aligned.m64n144k16.f32.bf16.bf16 "
    "{%0,%1,%2,%3,%4,%5,%6,%7,%8,%9,%10,%11,%12,%13,%14,%15,%16,%17,%18,%19,%20,%21,%22,%23,%24,%25,%26,%27,%28,%29,%30,%31,%32,%33,%34,%35,%36,%37,%38,%39,%40,%41,%42,%43,%44,%45,%46,%47,%48,%49,%50,%51,%52,%53,%54,%55,%56,%57,%58,%59,%60,%61,%62,%63,%64,%65,%66,%67,%68,%69,%70,%71}, "
    "{%72,%73,%74,%75}, %76, p, 1, 1, 1;\n}\n"
    : "+f"(d[0]), "+f"(d[1]), "+f"(d[2]), "+f"(d[3]), "+f"(d[4]), "+f"(d[5]), "+f"(d[6]), "+f"(d[7]), "+f"(d[8]), "+f"(d[9]), "+f"(d[10]), "+f"(d[11]), "+f"(d[12]), "+f"(d[13]), "+f"(d[14]), "+f"(d[15]), "+f"(d[16]), "+f"(d[17]), "+f"(d[18]), "+f"(d[19]), "+f"(d[20]), "+f"(d[21]), "+f"(d[22]), "+f"(d[23]), "+f"(d[24]), "+f"(d[25]), "+f"(d[26]), "+f"(d[27]), "+f"(d[28]), "+f"(d[29]), "+f"(d[30]), "+f"(d[31]), "+f"(d[32]), "+f"(d[33]), "+f"(d[34]), "+f"(d[35]), "+f"(d[36]), "+f"(d[37]), "+f"(d[38]), "+f"(d[39]), "+f"(d[40]), "+f"(d[41]), "+f"(d[42]), "+f"(d[43]), "+f"(d[44]), "+f"(d[45]), "+f"(d[46]), "+f"(d[47]), "+f"(d[48]), "+f"(d[49]), "+f"(d[50]), "+f"(d[51]), "+f"(d[52]), "+f"(d[53]), "+f"(d[54]), "+f"(d[55]), "+f"(d[56]), "+f"(d[57]), "+f"(d[58]), "+f"(d[59]), "+f"(d[60]), "+f"(d[61]), "+f"(d[62]), "+f"(d[63]), "+f"(d[64]), "+f"(d[65]), "+f"(d[66]), "+f"(d[67]), "+f"(d[68]), "+f"(d[69]), "+f"(d[70]), "+f"(d[71])
    : "r"(a[0]), "r"(a[1]), "r"(a[2]), "r"(a[3]), "l"(db), "r"(scaleD));
}
__device__ __forceinline__ void wgmma_rs_n64(float* d, const uint32_t* a, uint64_t db, int scaleD) {
  asm volatile("{\n.reg .pred p;\nsetp.ne.b32 p, %37, 0;\nwgmma.mma_async.sync.aligned.m64n64k16.f32.bf16.bf16 "
    "{%0,%1,%2,%3,%4,%5,%6,%7,%8,%9,%10,%11,%12,%13,%14,%15,%16,%17,%18,%19,%20,%21,%22,%23,%24,%25,%26,%27,%28,%29,%30,%31}, "
    "{%32,%33,%34,%35}, %36, p, 1, 1, 1;\n}\n"
    : "+f"(d[0]), "+f"(d[1]), "+f"(d[2]), "+f"(d[3]), "+f"(d[4]), "+f"(d[5]), "+f"(d[6]), "+f"(d[7]), "+f"(d[8]), "+f"(d[9]), "+f"(d[10]), "+f"(d[11]), "+f"(d[12]), "+f"(d[13]), "+f"(d[14]), "+f"(d[15]), "+f"(d[16]), "+f"(d[17]), "+f"(d[18]), "+f"(d[19]), "+f"(d[20]), "+f"(d[21]), "+f"(d[22]), "+f"(d[23]), "+f"(d[24]), "+f"(d[25]), "+f"(d[26]), "+f"(d[27]), "+f"(d[28]), "+f"(d[29]), "+f"(d[30]), "+f"(d[31])
    : "r"(a[0]), "r"(a[1]), "r"(a[2]), "r"(a[3]), "l"(db), "r"(scaleD));
}

template <int V> struct Int { static constexpr int value = V; };
struct Cur {
  uint32_t s, ph;
  __device__ __forceinline__ void next() { if (++s == NST) { s = 0; ph ^= 1; } }
};

#define z1_block(rb, w, j) (P.s->Z + ((rb) * 16 + (w) * 8 + (j)) * ZB)
#define z2_block(kb, j) (P.s->Z + (256 + (kb) * 8 + (j)) * ZB)
#define o_block(rb, w) (P.s->O + ((rb) * 2 + (w)) * (2 * ZB))
__device__ __forceinline__ void combine8(float m0, float q0, float m1, float q1, float n, float eps, float& mean, float& rstd) {
  mean = qsum(m0 + m1) * 0.125f;
  float d0 = m0 - mean, d1 = m1 - mean;
  float M2 = qsum(q0 + q1 + n * (d0 * d0 + d1 * d1));
  rstd = rsq_fast(fmaf(M2, 0.125f / n, eps));
}
__device__ __forceinline__ void stat_get(const uint4* zs, uint32_t tag, float n, float eps, float& m0, float& r0, float& m1, float& r1) {
  uint4 a0, a1, b0, b1;
#pragma unroll 1
  for (int it = 0; it < (1 << 20); it++) {
    a0 = ll_ld128(zs); a1 = ll_ld128(zs + 64); b0 = ll_ld128(zs + 8); b1 = ll_ld128(zs + 72);
    if (__all_sync(~0u, a0.z == tag && a1.z == tag && b0.z == tag && b1.z == tag)) break;
  }
  combine8(__uint_as_float(a0.x), __uint_as_float(a0.y), __uint_as_float(a1.x), __uint_as_float(a1.y), n, eps, m0, r0);
  combine8(__uint_as_float(b0.x), __uint_as_float(b0.y), __uint_as_float(b1.x), __uint_as_float(b1.y), n, eps, m1, r1);
}

__device__ __forceinline__ void rows_fetch(uint32_t el, uint32_t xr, const uint8_t* src, uint32_t bar) {
  expect_tx_p(el, bar, 9216);
#pragma unroll 1
  for (int r = 0; r < 8; r++) bulk_load_p(el, xr + r * 1152, src + r * (DM * 4), 1152, bar);
}
__device__ __forceinline__ void rows_stats(uint32_t xr, uint4* dst, uint32_t tag, int lane) {
  float s[2] = {0.f, 0.f}, q[4] = {0.f, 0.f, 0.f, 0.f};
  const uint32_t a0 = xr + (lane >> 2) * 1152 + (((lane & 3) * 2) ^ (lane >> 2)) * 16;
  uint4 n0 = lds128(a0), n1 = lds128(a0 ^ 16);
#pragma unroll 1
  for (int e = 1; e <= 9; e++) {
    const uint32_t x[8] = {n0.x, n0.y, n0.z, n0.w, n1.x, n1.y, n1.z, n1.w};
    if (e < 9) { n0 = lds128(a0 + e * 128); n1 = lds128((a0 ^ 16) + e * 128); }
#pragma unroll
    for (int u = 0; u < 8; u++) {
      const float lo = blo(x[u]), hi = bhi(x[u]);
      s[u & 1] += lo + hi; q[(u & 1) * 2] = fmaf(lo, lo, q[(u & 1) * 2]); q[(u & 1) * 2 + 1] = fmaf(hi, hi, q[(u & 1) * 2 + 1]);
    }
  }
  const float sx = s[0] + s[1], sq = (q[0] + q[1]) + (q[2] + q[3]);
  const float m = qsum(sx) * (-1.f / DM), r = rsq_fast(fmaxf(fmaf(qsum(sq), 1.f / DM, -m * m), 0.f) + LN_EPS);
  if ((lane & 3) == 0) ll_st128(dst + (lane >> 2) * 2, m, r, tag);
}

__device__ __forceinline__ void poison(const Params& P, uint32_t el, uint32_t src, const CUtensorMap* m, int rb, int j, int lane) {
#pragma unroll 1
  for (int u = lane; u < 72; u += 32) sts128(src + u * 16, POISON, POISON, POISON, POISON);
  fence_async_s();
  __syncwarp();
#pragma unroll 1
  for (int u = 0; u < 16; u++) {
    __nanosleep(NAP);
    bulk_store_p(el, o_block(rb, u >> 3) + j * 9216 + (u & 7) * 1152, src, 1152);
    asm volatile("{\n.reg .pred P;\nsetp.ne.u32 P, %5, 0;\n@P cp.async.bulk.tensor.3d.global.shared::cta.tile.bulk_group [%0, {%2, %3, %4}], [%1];\n}" ::"l"(m), "r"(src), "r"((j & 6) * 72), "r"(rb * 64 + u * 4), "r"(j & 1), "r"(el) : "memory");
  }
}
__device__ __forceinline__ void mma16acc(float* c, const uint32_t* a, uint32_t b0, uint32_t b1) {
  asm volatile("mma.sync.aligned.m16n8k16.row.col.f32.bf16.bf16.f32 {%0,%1,%2,%3}, {%4,%5,%6,%7}, {%8,%9}, {%0,%1,%2,%3};"
               : "+f"(c[0]), "+f"(c[1]), "+f"(c[2]), "+f"(c[3]) : "r"(a[0]), "r"(a[1]), "r"(a[2]), "r"(a[3]), "r"(b0), "r"(b1));
}
template <int KS, int NG, int AK, int AH, int BK, int BG, class F> __device__ __forceinline__ void redo(float* acc, const uint8_t* pa, const uint8_t* pb, F f) {
#pragma unroll 1
  for (int k = 0; k < 36; k += KS) {
    uint32_t a[4 * KS], b[2 * KS][NG];
#pragma unroll 1
    for (int it = 0; it < (1 << 20); it++) {
      bool ok = true;
#pragma unroll
      for (int e = 0; e < 4 * KS; e++) a[e] = ldgpu32(pa + (e >> 1) * AK + (e & 1) * AH);
#pragma unroll
      for (int e = 0; e < 2 * KS * NG; e++) b[e / NG][e % NG] = ldca32(pb + (e / NG) * BK + (e % NG) * BG);
#pragma unroll
      for (int e = 0; e < 4 * KS; e++) ok = ok && a[e] != POISON;
      if (__all_sync(~0u, ok)) break;
    }
#pragma unroll
    for (int e = 0; e < KS; e++) f(a + 4 * e, k + e);
#pragma unroll
    for (int e = 0; e < KS * NG; e++) mma16acc(acc + 4 * (e % NG), a + 4 * (e / NG), movm(b[2 * (e / NG)][e % NG]), movm(b[2 * (e / NG) + 1][e % NG]));
    pa += 2 * KS * AK; pb += 2 * KS * BK;
  }
}
__device__ __forceinline__ bool any_nan(float a, float b) {
  return __any_sync(~0u, a != a || b != b);
}

__global__ void __cluster_dims__(2, 1, 1) __launch_bounds__(384, 1) mega_kernel(const __grid_constant__ Params P) {
  extern __shared__ __align__(1024) uint8_t smem_raw[];
  uint32_t ckk[8];
  (void)ckk;
  CKK(0);
  const uint32_t sb = smem_u32(smem_raw);
  const uint32_t bars = sb + SM_BAR;
  int tid = threadIdx.x, lane = tid & 31;
  const int wid = __shfl_sync(~0u, tid >> 5, 0);
  if (tid == 256 && blockIdx.x < NCTA) prefetch_l2((const uint8_t*)P.wqkv + blockIdx.x * 6912, 6912);
  const int cl = blockIdx.x >> 1, tp = cl - 36, t7 = (tp * 37) >> 8;
  const int bid = (cl < 4 ? cl * 8 + 32 : tp < 0 ? cl - 4 : cl < 64 ? tp + t7 + 33 : cl) * 2 + (blockIdx.x & 1);
  if (bid >= NCTA) return;
  const int rb = bid & 15, j = bid >> 4;
  { const bool tr = (tid & 127) == 0 && tid < 256; const int w = tid >> 7; (void)tr; (void)w; TRC(tr, w, 0); }
  CKK(1);
  uint4 wv[5];
  const uint8_t* wsrc;
  {
    const int n8 = min(tid >> 3, 26), part = n8 / 9;
    const uint8_t* src = (const uint8_t*)P.wqkv + (8 * rb + (tid & 7)) * (3 * DM * 2) + (part * (DM - 72) + 72 * j + 8 * n8) * 2;
#pragma unroll
    for (int u = 0; u < SPL; u++) wv[u] = ldnc128_if(tid < 216, src + u * (128 * 3 * DM * 2));
    wsrc = src;
  }
  CKK(2);
  if (tid == 352) {
#pragma unroll
    for (int e = 0; e < 16; e++) mbar_init(bars + B_FULL + e * 8, (e >> 2) == 1 ? 16 : 1);
    mbar_init(bars + B_RES + 8, 8); mbar_init(bars + B_WT, 1); mbar_init(bars + B_WT + 8, 1); mbar_init(bars + B_IMG, 9);
    asm volatile("fence.mbarrier_init.release.cluster;" ::: "memory");
  }
  __syncthreads();

  if (wid >= 8) {
    reg_dealloc<40>();
    lane = __shfl_sync(~0u, lane, lane);
    const uint32_t el = elect_one();
    const uint64_t pol = policy_evict_first();
    uint32_t* const fj = P.s->flags + FJ + j * 32;
    if (wid == 8) {
      if (lane == 0) {
        mbar_init(bars + B_RES, 1); mbar_init(bars + B_WOI, 1); mbar_init(bars + B_ZB, 1); mbar_init(bars + B_GATE3, 3); mbar_init(bars + B_Z1, 1); mbar_init(bars + B_LAG, 4);
#pragma unroll
        for (int e = B_RT; e < B_XS + 16; e += 8) mbar_init(bars + e, e >= B_AD && e < B_EVT ? 2 : (e >= B_EVT && e < B_RT1) || (e >= B_EA3 && e < B_XS) ? 4 : 1);
        asm volatile("fence.mbarrier_init.release.cluster;" ::: "memory");
        mbar_arrive(bars + B_IMG);
      }
      __syncwarp();
#pragma unroll 1
      for (int i = 0; i < 12; i++) if (el) prefetch_map(&P.act[0] + (i < 7 ? i : i - 12));
      const uint32_t epoch = ldcg32(fj + FJ_EP + rb);
      const uint32_t rk = bid & 1;
      TRC(el, 2, 34);
      uint32_t dst = sb + ST_B + rk * 18432, full = bars + B_FULL, ph = 1;
      auto slot = [&](uint32_t bytes) {
        mbar_wait(full, ph);
        expect_tx_p(el, full, bytes);
        mbar_wait(full + (B_EMPTY - B_FULL), ph);
      };
      auto next = [&]() {
        const bool wrap = full == bars + B_FULL + 24;
        full += wrap ? -24 : 8; dst += wrap ? 0u - 3 * ST_BYTES : ST_BYTES; ph ^= wrap;
      };
#pragma unroll 1
      for (int L = 0; L < 2; L++) {
        const uint8_t* src = P.s->WQ + j * WQ_SL + rk * 13824;
        dst -= rk * 4608;
#pragma unroll 1
        for (int i = 0; i < 9; i++) {
          if (L == 0 && (i == 0 || i == 2 * SPL)) {
            flag_wait(fj + (i ? FJ_WQ : FJ_WQ0), (epoch + 1) * 16);
            fence_async_g();
            TRC(el, 2, i ? 47 : 45);
          }
          slot(27648);
          bulk_mc_h(el, dst, src, 13824, full, true, pol);
          src += 27648;
          next();
        }
        dst += rk * 4608;
        if (L == 0) {
#pragma unroll 1
          for (int u = 0; u < 2; u++) flag_wait(P.s->flags + FJ + (j ^ u) * 32 + FJ_WO, (epoch + 1) * 16);
          fence_async_g();
          TRC(el, 2, 46);
        }
        src = P.s->WO + ((j & 6) + rk) * WO_SL;
#pragma unroll 1
        for (int i = 0; i < 4; i++) {
          slot(ZB);
          bulk_mc_h(el, dst, src, 18432, full, true, pol);
          src += 18432;
          next();
        }
        slot(18432);
        bulk_mc_h(el, dst, src, 9216, full, true, pol);
        next();
        int col = (((9 * j + 1) >> 1) + 36) * 64;
        const CUtensorMap* map = &P.win64;
#pragma unroll 1
        for (int p = 0; p < 9; p++) {
          if (p == 1) mbar_wait(bars + B_FA3 + GA3 * 8, L);
          mbar_wait(full + (B_EMPTY - B_FULL), ph);
          tma4d_mc(el, dst, map, col, rk * 18, full + 8, pol);
          mbar_arrive_if(el, full);
          if (p + L == 0 && el) asm volatile("cp.async.bulk.prefetch.tensor.4d.L2.global [%0, {%1, 0, 0, %2}];\ncp.async.bulk.prefetch.tensor.4d.L2.global [%0, {%1, 0, 0, %3}];" ::"l"(map), "r"(col + 64), "r"(rk * 18), "r"(rk * 18 + 36) : "memory");
          next();
          if (p == 1) mbar_wait(bars + B_FA3 + GB3 * 8, L);
          slot(2 * ZB);
          tma4d_mc(el, dst, map, col, rk * 18 + 36, full, pol);
          next();
          col = p == 3 ? (9 * j + ((j & 1) ? 0 : 8)) * 32 : p == 4 ? ((9 * j + 1) >> 1) * 64 : col + 64;
          map = p == 3 ? &P.win : &P.win64;
        }
        TRC(el, 2, L * 16 + 6);
        flag_wait(fj + FJ_ZN + L, (epoch + 1) * 16);
        fence_async_g();
        TRC(el, 2, L * 16 + 7);
        src = z2_block(0, j) + rk * 18432;
#pragma unroll 1
        for (int i = 0; i < 32; i++) {
          if (i >= 4) mbar_wait(full + (B_AD - B_FULL), ((i >> 2) & 1) ^ 1);
          slot(ST_BYTES);
          bulk_mc_h(el, dst, src, 18432, full, true, pol);
          tma3d_h(el, dst - ST_B - rk * 18432, &P.wsp, i * 64, rb * 64, 0, full, true, pol);
          src += 8 * ZB;
          next();
        }
        mbar_wait(bars + B_Z1, L);
        fence_async_g();
        expect_tx_p(el, bars + B_ZB, 26624);
        mbar_wait(full + (B_AD - B_FULL), 1);
        slot(26624);
        bulk_load_h(el, dst - ST_B - rk * 18432, z1_block(rb, 0, j), 26624, bars + B_ZB, true, pol);
        bulk_load_h(el, dst - ST_B - rk * 18432 + 26624, z1_block(rb, 1, j), 26624, full, true, pol);
        next();
        col = j * 64;
#pragma unroll 1
        for (int i = 0; i < 9; i++) {
          if (i < 3) mbar_wait(full + (B_AD - B_FULL), 1);
          slot(ZB);
          tma2d_mc_h(el, dst, &P.wout, col, 288 * j + rk * 144, full, true, pol);
          col = col == 512 ? 0 : col + 64;
          next();
        }
      }
    } else if (wid < 11) {
      int w = wid - 9;
      TRC(el && w == 0, 2, 35);
      uint32_t t8 = (ldcg32(P.s->flags + (rb * 2 + w) * 32 + FR_EP + j) + 1) * 8;
      int bo = bid;
#define FRESH asm volatile("" : "+r"(lane), "+r"(w), "+r"(bo), "+r"(t8)); const int rb = bo & 15, j = bo >> 4; \
      uint32_t *const fr = P.s->flags + (rb * 2 + w) * 32, *const fj = P.s->flags + FJ + j * 32, *const fo = P.s->flags + (rb * 2 + (j & 1)) * 32 + L; \
      const uint32_t ev = bars + B_EVT + w * EV_N * 8, tag = (t8 >> 2) - 1 + L; (void)fr; (void)fj; (void)fo; (void)ev; (void)tag
      Cur c{0, 1};
#pragma unroll 1
      for (int L = 0; L < 2; L++) {
        {
          FRESH;
          uint4* const xs = P.s->XST + (rb * 2 + w) * 128;
          if (L) {
            mbar_wait(ev + EV_PT * 8, 0);
            TRC(el, 3, w * 32 + 16);
            flag_release_p(el, fr + FR_X2);
            TRC(el, 3, w * 32 + 17);
          }
#pragma unroll 1
          for (int i = 0; i < 9; i++) {
            const uint32_t full = bars + B_FULLA + w * 32 + c.s * 8, dst = sb + c.s * ST_BYTES + w * 8192;
            if (L == 0 && i == 4) {
              mbar_wait(bars + B_WT + w * 8, 0);
              TRC(el && w == 0, 2, 37);
              rows_stats(sb + SM_STG + w * 9216, xs + 16 * j, tag, lane);
              TRC(el && w == 0, 2, 38);
            }
            const uint32_t src = sb + (L ? 2 * ST_BYTES + SM_WOI : SM_STG + w * 9216);
            if (i == 4) {
#pragma unroll
              for (int u = 0; u < 6; u++) sts128(src + u * 512 + lane * 16, POISON, POISON, POISON, POISON);
              fence_async_s();
              __syncwarp();
            }
            mbar_wait(bars + B_EMPTY + c.s * 8, c.ph);
            if (i < L) { flag_wait(fr + FR_X2, t8); fence_async_g(); }
            tma3d_h(el, dst, &P.act[L], i * 64, rb * 64, w, full, false, pol);
            expect_tx_p(el, full, 8192);
            TRC(el && i < L, 3, w * 32 + 18);
            TRC(el && i + L + w == 0, 2, 36);
            c.next();
            if (i >= 4 && i < (L ? 5 : 8)) {
              int b = (rb * 2 + w) * 8 + j;
              asm volatile("" : "+r"(b));
              bulk_store_p(el, i == 4 ? (uint8_t*)P.s->HALO + b * 3072 : P.s->O + (b * 3 + i - 5) * 3072, src, 3072);
              if (i < 6) bulk_store_p(el, (i == 4 ? P.s->ST1 : P.s->ZST) + b * 64, src, 1024);
              if (i == 6) bulk_store_p(el, P.s->RT + b * 8, src, 64);
            }
            if (L == 0 && i == 3) rows_fetch(el, sb + SM_STG + w * 9216, P.xs[0] + (128 * rb + 16 * j + w) * (DM * 2), bars + B_WT + w * 8);
          }
          if (el) asm volatile("cp.async.bulk.commit_group;\ncp.async.bulk.wait_group 0;" ::: "memory");
          __syncwarp();
          if (L == 0) fence_gpu();
          const uint32_t tab = sb + L * (2 * ST_BYTES) + SM_XST + w * 512 + lane * 8;
          TRC(el, 3, w * 32 + L * 16 + 13);
#pragma unroll 1
          for (int it = 0; it < (1 << 22); it++) {
            const uint4 a = ll_ld128(xs + 2 * lane), b = ll_ld128(xs + 64 + 2 * lane);
            if (__all_sync(~0u, a.z == tag && b.z == tag)) { sts64(tab, a.x, a.y); sts64(tab + 256, b.x, b.y); break; }
          }
          __syncwarp();
          mbar_arrive_if(el, bars + B_XS + w * 8);
          TRC(el, 3, w * 32 + L * 16 + 14);
          if (w == 1) {
            mbar_wait(bars + B_XS, L);
            expect_tx_p(el, bars + B_RES, 18432);
            tma3d_h(el, sb + SM_STG, &P.res[L], (j & 6) * 72, rb * 64, j & 1, bars + B_RES, !L, pol);
          }
          if (L) flag_wait(fj + FJ_P4, t8 * 4);
        }
        {
          FRESH;
          const uint8_t* src = o_block(rb, j & 1) + w * 8192;
#pragma unroll 1
          for (int i = 0; i < 5; i++) {
            const uint32_t full = bars + B_FULLA + w * 32 + c.s * 8, dst = sb + c.s * ST_BYTES + w * 8192;
            const bool none = 2 * i + w > 8;
            mbar_wait(bars + B_EMPTY + c.s * 8, c.ph);
            expect_tx_p(el, full, none ? 0 : 8192);
            if (i == 0) {
              mbar_wait(bars + B_EMPTY + 16 * L, 0);
              mbar_wait(ev + EV_O * 8, L);
              TRC(el, 3, w * 32 + L * 16 + 3);
              flag_add_p(el, fr + FR_O + L);
              TRC(el, 3, w * 32 + L * 16 + 4);
              flag_wait(fo + FR_O, t8);
              fence_async_g();
            }
            if (!none) bulk_load_h(el, dst, src + i * 16384, 8192, full, true, pol);
            TRC(el && i == 0, 3, w * 32 + L * 16 + 5);
            c.next();
          }
        }
        {
          FRESH;
          expect_tx_p(lane < 9, bars + B_FA3 + (9 * w + lane) * 8, 8192);
          mbar_wait(ev + EV_X1 * 8, L);
          TRC(el, 3, w * 32 + L * 16 + 6);
          if (L) flag_add_p(el, fo + FR_X1); else flag_release_p(el, fo + FR_X1);
          mbar_arrive_if(el, bars + B_GATE3);
          TRC(el, 3, w * 32 + L * 16 + 7);
          mbar_arrive_if(lane < 2, bars + B_FULLA + w * 32 + ((c.s + lane) & 3) * 8);
#pragma unroll 1
          for (int kb = 0; kb < 9; kb++) {
            const int n = 9 * w + kb;
            const uint32_t dst = sb + ((n >> 1) & 3) * ST_BYTES + (n & 1) * 8192;
            if (kb == 0) { flag_wait(fr + FR_X1 + L, t8); fence_async_g(); }
            if (n >= 8) mbar_wait(bars + B_EA3 + (n - 8) * 8, L);
            tma3d_h(el, dst, &P.act[L + 1], kb * 64, rb * 64, w, bars + B_FA3 + n * 8, false, pol);
            TRC(el && kb == 0, 3, w * 32 + L * 16 + 8);
          }
          c.ph ^= ((c.s + 18) >> 2) & 1; c.s = (c.s + 18) & 3;
        }
        float cv;
        {
        FRESH;
        expect_tx_p(el, bars + B_WT + w * 8, 2048);
#pragma unroll 1
        for (int r = 0; r < 8; r++)
          bulk_load_p(el, sb + SM_WT + w * 2176 + r * 272, (const uint8_t*)P.w_sp + (size_t)(128 * rb + 16 * j + 2 * r + w) * (SEQ * 2) + 30 * 128, 256, bars + B_WT + w * 8);
        cv = (lane & 3) ? 0.f : -blo(ldnc16(P.b_sp + 128 * rb + 16 * j + 2 * (lane >> 2) + w));
        mbar_wait(bars + B_RT, L);
        mbar_wait(bars + B_WT + w * 8, L ^ 1);
        mbar_wait(ev + EV_Z1 * 8, L);
        const uint32_t ro = (w * 64 + 8 * j + (lane >> 2)) * 128, x0 = ((lane & 3) * 2) ^ (lane >> 2);
#pragma unroll 1
        for (int i = 0; i < 32; i++) {
          const bool tail = (i >> 1) == 4;
          const int kb = tail ? i + 22 : i < 8 ? i : i - 2;
          if (i == 8) mbar_wait(bars + B_RT1, L);
          if (!tail) mbar_wait(bars + B_FULL + c.s * 8, c.ph ^ 1);
#pragma unroll
          for (int e = 0; e < 2; e++) {
            const uint4 a = lds128(!tail ? sb + c.s * ST_BYTES + ro + ((x0 ^ e) << 4) : sb + SM_WT + w * 2176 + (lane >> 2) * 272 + (i - 8) * 128 + (lane & 3) * 32 + e * 16);
            const uint4 m = lds128(sb + SM_RT + 4096 + kb * 128 + (lane & 3) * 32 + e * 16);
            cv = fmaf(blo(a.x), blo(m.x), fmaf(bhi(a.x), bhi(m.x), fmaf(blo(a.y), blo(m.y), fmaf(bhi(a.y), bhi(m.y), cv))));
            cv = fmaf(blo(a.z), blo(m.z), fmaf(bhi(a.z), bhi(m.z), fmaf(blo(a.w), blo(m.w), fmaf(bhi(a.w), bhi(m.w), cv))));
          }
          if (!tail) {
            mbar_arrive_if(el, bars + B_AD + c.s * 8 + (__float_as_uint(cv) & P.zero));
            c.next();
          }
        }
        }
        TRC(el, 3, w * 32 + L * 16 + 11);
        FRESH;
        cv = qsum(cv);
        uint2* const cs = (uint2*)(P.s->XST + (rb * 2 + w) * 128 + 1);
        if ((lane & 3) == 0) ll_st64(cs + 32 * j + (lane >> 2) * 4, __float_as_uint(cv), tag);
#pragma unroll 1
        for (int it = 0; it < (1 << 22); it++) {
          const uint2 a = ll_ld64(cs + 4 * lane), b = ll_ld64(cs + 128 + 4 * lane);
          if (__all_sync(~0u, a.y == tag && b.y == tag)) { sts32(sb + SM_CV + w * 256 + lane * 4, a.x); sts32(sb + SM_CV + w * 256 + 128 + lane * 4, b.x); break; }
        }
        __syncwarp();
        if (el) mbar_arrive(bars + B_CV + w * 8);
        TRC(el, 3, w * 32 + L * 16 + 12);
#pragma unroll 1
        for (int kb = 30; kb < 32; kb++) {
          mbar_wait(bars + B_FULL + c.s * 8, c.ph ^ 1);
          if (el) mbar_arrive(bars + B_AD + c.s * 8);
          c.next();
        }
        c.ph ^= ((c.s + 10) >> 2) & 1; c.s = (c.s + 10) & 3;
        if (L == 0) {
          mbar_wait(ev + EV_P4 * 8, 0);
          flag_add_p(el, fj + FJ_P4);
          flag_add_p(el, fr + FR_EP + j);
        }
      }
    } else {
      const uint32_t epoch = ldcg32(fj + FJ_EP + rb);
      TRC(el, 2, 33);
      if (SPL) {
        mbar_wait(bars + B_RES + 8, 0);
        TRC(el, 2, 41);
        flag_release_p(el, fj + FJ_WQ0);
        TRC(el, 2, 42);
      }
      mbar_wait(bars + B_IMG, 0);
      TRC(el, 2, 39);
      flag_release_p(el, fj + FJ_WQ);
      TRC(el, 2, 40);
#pragma unroll 1
      for (int L = 0; L < 2; L++) {
        auto wo_fetch = [&]() {
          expect_tx_p(el, bars + B_WOI, 5760);
          asm volatile("{\n.reg .pred P;\nsetp.ne.u32 P, %5, 0;\n@P cp.async.bulk.tensor.4d.shared::cluster.global.mbarrier::complete_tx::bytes [%0], [%1, {0, 0, %3, %4}], [%2];\n}" ::"r"(sb + SM_WOI), "l"(&P.wo8), "r"(bars + B_WOI), "r"(9 * j), "r"((9 * rb) >> 1), "r"(el) : "memory");
        };
        float* const csf = P.s->CSP + (NCTA + bid) * 216;
        if (L == 0) {
          flag_wait(fj + FJ_WQ, (epoch + 1) * 16);
          fence_async_g();
          expect_tx_p(el, bars + B_XRW, 13824);
          bulk_load_p(el, sb + ST_BYTES + SM_WOI, P.s->CSP + j * 16 * 216, 6912, bars + B_XRW);
          bulk_load_p(el, sb + 2 * ST_BYTES + SM_WOI, P.s->CSP + (j * 16 + 8) * 216, 6912, bars + B_XRW);
          wo_fetch();
          mbar_wait(bars + B_XRW, 0);
#pragma unroll 1
          for (int f = lane; f < 54; f += 32) {
            float s[4] = {0.f, 0.f, 0.f, 0.f};
#pragma unroll 4
            for (int r = 0; r < 16; r++) {
              const uint4 v = lds128(sb + ST_BYTES + SM_WOI + (r >> 3) * ST_BYTES + (r & 7) * 864 + f * 16);
              s[0] += __uint_as_float(v.x); s[1] += __uint_as_float(v.y); s[2] += __uint_as_float(v.z); s[3] += __uint_as_float(v.w);
            }
            sts128(sb + SM_CSQ + f * 16, __float_as_uint(s[0]), __float_as_uint(s[1]), __float_as_uint(s[2]), __float_as_uint(s[3]));
            stg128(csf + f * 4, __float_as_uint(s[0]), __float_as_uint(s[1]), __float_as_uint(s[2]), __float_as_uint(s[3]));
          }
          __syncwarp();
          mbar_arrive_if(el, bars + B_CSQ);
        } else {
#pragma unroll 1
          for (int u = 0; u < 4; u++) {
            const int w = u & 1;
            if (u < 2) {
              flag_wait(P.s->flags + (rb * 2 + w) * 32 + FR_X2, (epoch + 1) * 8);
              fence_async_g();
              TRC(el, 2, 48 + u);
              rows_fetch(el, sb + SM_STG + w * 9216, P.xs[1] + (128 * rb + 16 * j + w) * (DM * 2), bars + B_XRW + w * 8);
            } else {
              if (u == 2) {
                expect_tx_p(el, bars + B_CSQ, 864);
                bulk_load_p(el, sb + 2 * ST_BYTES + SM_CSQ, csf, 864, bars + B_CSQ);
              }
              mbar_wait(bars + B_XRW + w * 8, w ^ 1);
              TRC(el, 2, 48 + u);
              rows_stats(sb + SM_STG + w * 9216, P.s->XST + (rb * 2 + w) * 128 + 16 * j, epoch * 2 + 2, lane);
              TRC(el, 2, 50 + u);
            }
          }
        }
        if (L == 0) {
          TRC(el, 2, 43);
          mbar_wait(bars + B_WOI, 0);
          bulk_store_p(el, P.s->WO + j * WO_SL + ((9 * rb) >> 1) * 1152, sb + SM_WOI, 5760);
          publish_p(el, fj + FJ_WO);
          TRC(el, 2, 44);
          const uint8_t* sp = lane < 16 ? (const uint8_t*)P.w_in + (30 * lane + 50) * (FH * 4) + FH * 2 + lane * 256 : (const uint8_t*)P.w_sp + (60 * lane) * (SEQ * 2) + lane * 64;
          float sq = 0.f;
#pragma unroll 1
          for (int u = 0; u < 4; u++) {
            const uint4 y = ldnc128(sp + u * 16);
            const uint32_t x[4] = {y.x, y.y, y.z, y.w};
#pragma unroll
            for (int e = 0; e < 4; e++) sq = fmaf(blo(x[e]), blo(x[e]), fmaf(bhi(x[e]), bhi(x[e]), sq));
          }
#pragma unroll 1
          for (int o = 8; o; o >>= 1) sq += __shfl_xor_sync(~0u, sq, o);
          sq *= lane < 16 ? 2.f * GA * GA * DM / 512.f : C0S * C0S * SEQ / 512.f;
          asm("sqrt.approx.f32 %0, %0;" : "+f"(sq));
          const float o0 = __shfl_sync(~0u, sq, 0), o1 = __shfl_sync(~0u, sq, 16);
          const float p2 = __uint_as_float(min(__float_as_uint(o0) & 0x7f800000u, 0x7e000000u)) * OFK, off = -p2 - fminf(OFA, 0.5f * p2);
          if (el) sts64(sb + SM_OFF, pack2(off, off), min(__float_as_uint(o1) & 0x7f800000u, 0x7e000000u) | 0x00400000u);
        }
        if (el) mbar_arrive(bars + B_GATE3);
        const uint32_t tag = epoch * 2 + L + 1;
        asm volatile("" : "+r"(lane));
        mbar_wait(bars + B_EVT + EV_ZN * 8, L);
        mbar_wait(bars + B_EVT + (EV_N + EV_ZN) * 8, L);
        flag_release_p(el, fj + FJ_ZN + L);
        TRC(el, 2, L * 16 + 8);
        {
          uint4 v[4];
#pragma unroll 1
          for (int it = 0; it < (1 << 22); it++) {
            bool ok = true;
#pragma unroll
            for (int u = 0; u < 4; u++) { v[u] = ll_ld128(P.s->ZST + (rb * 2 + ((lane >> 1) & 1)) * 512 + ((lane & 1) * 4 + u) * 64 + 8 * j + (lane >> 2)); ok = ok && v[u].z == tag; }
            if (__all_sync(~0u, ok)) break;
          }
          float mean = __uint_as_float(v[0].x) + __uint_as_float(v[1].x) + __uint_as_float(v[2].x) + __uint_as_float(v[3].x), M2 = 0.f;
          mean = (mean + __shfl_xor_sync(~0u, mean, 1)) * 0.125f;
#pragma unroll
          for (int u = 0; u < 4; u++) { const float d = __uint_as_float(v[u].x) - mean; M2 += fmaf(288.f * d, d, __uint_as_float(v[u].y)); }
          M2 += __shfl_xor_sync(~0u, M2, 1);
          const float rs = blo(pack2(rsq_fast(fmaf(M2, 1.f / FH, 4.f * GA * GA * LN_EPS)), 0.f));
          if (!(lane & 1)) ll_st64(P.s->RT + 128 * rb + 16 * j + (lane >> 1), pack2(rs, rs * mean), tag);
        }
        TRC(el, 2, L * 16 + 10);
#pragma unroll 1
        for (int b = 0; b < 8; b++) {
          uint4 v[4];
#pragma unroll 1
          for (int it = 0; it < (1 << 22); it++) {
            bool ok = true;
#pragma unroll
            for (int u = 0; u < 4; u++) { v[u] = ll_ld128((const uint4*)P.s->RT + b * 128 + u * 32 + lane); ok = ok && v[u].y == tag && v[u].w == tag; }
            if (__all_sync(~0u, ok)) break;
          }
#pragma unroll
          for (int u = 0; u < 4; u++) {
            const uint32_t rt = sb + SM_RT + b * 512 + u * 128, ro = (lane >> 3) * 32 + (lane & 3) * 8 + ((lane >> 2) & 1) * 2;
            sts32(rt + 4096 + lane * 4, __byte_perm(v[u].x, v[u].z, 0x7632));
            asm volatile("st.shared.u16 [%0], %1;\nst.shared.u16 [%0 + 4], %2;" ::"r"(rt + ro), "h"((uint16_t)v[u].x), "h"((uint16_t)v[u].z) : "memory");
          }
          __syncwarp();
          if (el && (b == 1 || b == 7)) mbar_arrive(bars + (b == 1 ? B_RT : B_RT1));
          TRC(el && b < 2, 2, L * 16 + 11 + b);
        }
        TRC(el, 2, L * 16 + 9);
        mbar_wait(bars + B_EVT + EV_Z1 * 8, L);
        mbar_wait(bars + B_EVT + (EV_N + EV_Z1) * 8, L);
        fence_gpu();
        if (el) mbar_arrive(bars + B_Z1);
        if (L == 0) {
          flag_add_p(el, fj + FJ_EP + rb);
          __nanosleep(NAP0);
          poison(P, el, sb + SM_STG + 17152, &P.psn, rb, j, lane);
          if (el) asm volatile("cp.async.bulk.commit_group;\ncp.async.bulk.wait_group 0;" ::: "memory");
          __syncwarp();
          fence_gpu();
        }
      }
    }
  } else {
    CKK(3);
    uint8_t* const wdst = P.s->WQ + j * WQ_SL + rb * 3456 + tid * 16;
#pragma unroll
    for (int u = 0; u < SPL; u++) stg128_if(tid < 216, wdst + u * (16 * 3456), wv[u].x, wv[u].y, wv[u].z, wv[u].w);
    __syncwarp();
    if (lane == 0) mbar_arrive(bars + B_RES + 8);
    CKK(4);
    auto repack2 = [&]() {
#pragma unroll
      for (int u = SPL; u < 5; u++) stg128_if((u < 4 || rb < 8) && tid < 216, wdst + u * (16 * 3456), wv[u].x, wv[u].y, wv[u].z, wv[u].w);
      float s[8];
#pragma unroll
      for (int e = 0; e < 8; e++) s[e] = 0.f;
#pragma unroll
      for (int u = 0; u < 5; u++) {
        uint32_t x[4] = {wv[u].x, wv[u].y, wv[u].z, wv[u].w};
        asm volatile("" : "+r"(x[0]), "+r"(x[1]), "+r"(x[2]), "+r"(x[3]));
#pragma unroll
        for (int e = 0; e < 4; e++) { s[2 * e] += blo(x[e]); s[2 * e + 1] += bhi(x[e]); }
      }
#pragma unroll
      for (int m = 4; m; m >>= 1) {
#pragma unroll
        for (int e = 0; e < m; e++) s[e] = ((tid & m) ? s[e + m] : s[e]) + __shfl_xor_sync(~0u, (tid & m) ? s[e] : s[e + m], m);
      }
      stg32_if(tid < 216, P.s->CSP + bid * 216 + tid, __float_as_uint(s[0]));
      __syncwarp();
      if (lane == 0) mbar_arrive(bars + B_IMG);
    };
    reg_alloc<232>();
    lane = __shfl_sync(~0u, lane, lane);
    tid = wid * 32 + lane;
    CKK(5);
#pragma unroll
    for (int v = SPL; v < 5; v++) wv[v] = ldnc128_if(tid < 216 && (v < 4 || rb < 8), wsrc + v * (128 * 3 * DM * 2));
    repack2();
    CKK(6);
    const int w = wid >> 2, q = wid & 3;
    int g = lane >> 2, t = lane & 3;
    const uint32_t ev = bars + B_EVT + w * EV_N * 8;
    const bool tr = (tid & 127) == 0;
    (void)tr;
    Cur c{0, 0};
    const uint32_t ebar = mapa(bars + B_EMPTY, (bid & 1) ^ (lane & 1));
    auto release = [&](uint32_t s, uint32_t dep = 0) { mbar_arrive_cluster_if(lane < 2, ebar + s * 8 + dep); };
    auto release_if = [&](bool on, uint32_t s) { mbar_arrive_cluster_if(lane < 2 && on, ebar + s * 8); };
    uint32_t ia = 0;
    auto wait_ab = [&]() { mbar_wait_c(bars + B_FULL + c.s * 8, c.ph); mbar_wait_c(bars + B_FULLA + w * 32 + c.s * 8, (ia >> 2) & 1); ia++; };

    auto yield_done = [&]() { if (w == 0 && lane == 0) mbar_arrive(bars + B_LAG); };
    auto signal = [&](int e) { __syncwarp(); mbar_arrive_if(lane == 0, ev + e * 8); };

    const uint32_t epoch = ldcg32(P.s->flags + (rb * 2 + w) * 32 + FR_EP + j);
    TRC(tr, w, 1);
    CKK(7);
    if (PAD && P.zero) {
#pragma unroll
      for (int i = 0; i < PAD; i++) asm volatile("st.shared.u32 [%0], %1;" ::"r"(sb + i * 20), "r"(tid) : "memory");
    }
    CKK_OUT;

#pragma unroll 1
    for (int L = 0; L < 2; L++) {
      const int tb = 2 + L * 24;
      asm volatile("" : "+r"(lane), "+r"(g), "+r"(t));
      (void)tb;
      ia = 0;
      const uint32_t tag = epoch * 2 + L + 1;
      uint32_t aoff = (w * 64 + q * 16 + (lane & 15)) * 128 + (((lane >> 4) ^ (lane & 7)) << 4);
      {
        uint32_t Pk[27][2];
        float sc0, sc1;
        const uint32_t att = sb + w * 8192 + q * 2048 + lane * 4;
        uint4* hp = P.s->HALO + ((((rb - (q == 0)) * 2 + w) * 8 + j) * 6) * 32 + lane;
        uint8_t* od = o_block(rb, w) + (9 * j) * 1024 + (2 * q) * 128 + lane * 4;
        ACLK_INIT;
        {
          float acc[108];
#pragma unroll
          for (int i = 0; i < 108; i++) acc[i] = 0.f;
          uint32_t prev = 0;
#pragma unroll 1
          for (int kb = 0; kb < 9; kb++) {
            const bool hold = w == 1 && kb == 9 - LAG1;
            if (hold) {
              wgmma_wait<0>();
              release(prev);
              mbar_wait_c(bars + B_LAG, L);
            }
            wait_ab();
            TRC(tr && kb == 0, w, tb + 0);
            MCLK(kb == 0, 0);
            PCLK(kb * 4);
            const uint32_t st = sb + c.s * ST_BYTES;
            uint64_t da = dsc2(dlo(st + w * 8192, 16), 0, 0x40000040u + P.zero), db = dsc2(dlo(st + ST_B, 3456), 0, 8 ^ P.zero);
            wgmma_fence();
#pragma unroll
            for (int kk = 0; kk < 4; kk++) {
              wgmma_ss_n216(acc, da, db, 1);
              dadd(da, 2); dadd(db, 432);
              if (kk == 0) { wgmma_commit(); wgmma_wait<1>(); release_if(kb > 0 && !hold, prev); }
            }
            wgmma_commit();
            if (kb == 7) yield_done();
            PCLK(kb * 4 + 1);
            PCLK(kb * 4 + 2);
            PCLK(kb * 4 + 3);
            prev = c.s; c.next();
          }
          const uint32_t cs = sb + prev * ST_BYTES + SM_CSQ + t * 8;
          mbar_wait_c(bars + B_CSQ, L);
          mbar_wait_c(bars + B_XS + w * 8, L);
          const float2 n0 = lds64f(sb + prev * ST_BYTES + SM_XST + w * 512 + (16 * q + g) * 8), n1 = lds64f(sb + prev * ST_BYTES + SM_XST + w * 512 + (16 * q + g + 8) * 8);
          const float m0 = n0.x, r0 = n0.y, m1 = n1.x, r1 = n1.y;
          float2 cv[27];
#pragma unroll
          for (int G = 0; G < 27; G++) cv[G] = lds64f(cs + G * 32);
          PCLK(36);
          wgmma_wait<0>();
          PCLK(37);
          {
            uint32_t dep = P.zero & __float_as_uint(m0) & __float_as_uint(m1);
#pragma unroll
            for (int G = 0; G < 27; G++) dep &= __float_as_uint(cv[G].x);
            release(prev, dep);
          }
          TRC(tr, w, tb + 1);
          MCLK(1, 1);
          ACLK(0);
#pragma unroll
          for (int G = 9; G < 27; G++) Pk[G][1] = pack2(fmaf(m1, cv[G].x, acc[4 * G + 2]) * r1, fmaf(m1, cv[G].y, acc[4 * G + 3]) * r1);
          if (q < 3) {
#pragma unroll
            for (int i = 0; i < 18; i++) sts32(att + (i >> 4) * ST_BYTES + (i & 15) * 128, Pk[9 + i][1]);
          } else if (rb < 15) {
#pragma unroll
            for (int i = 0; i < 6; i++) ll_st128(hp + i * 32, __uint_as_float(Pk[9 + 3 * i][1]), __uint_as_float(Pk[10 + 3 * i][1]), tag, __uint_as_float(Pk[11 + 3 * i][1]));
          }
#pragma unroll
          for (int G = 0; G < 27; G++) {
            if (G < 9) {
              Pk[G][0] = pack2(fmaf(m0, cv[G].x, acc[4 * G]), fmaf(m0, cv[G].y, acc[4 * G + 1]));
              Pk[G][1] = pack2(fmaf(m1, cv[G].x, acc[4 * G + 2]), fmaf(m1, cv[G].y, acc[4 * G + 3]));
            } else {
              Pk[G][0] = pack2(fmaf(m0, cv[G].x, acc[4 * G]) * r0, fmaf(m0, cv[G].y, acc[4 * G + 1]) * r0);
            }
          }
          sc0 = r0 * (0.23570226039551584f * 1.4426950408889634f); sc1 = r1 * (0.23570226039551584f * 1.4426950408889634f);
        }
        ACLK(1);
        constexpr int GA_[4] = {0, 2, 4, 7}, GB_[4] = {1, 3, 5, 8}, GC_[4] = {2, 4, 6, 6};
        float S1[4][4], S2[4][4];
        uint32_t qa[4][2], qc[4][2];
#pragma unroll
        for (int h = 0; h < 4; h++) {
#pragma unroll
          for (int r = 0; r < 2; r++) {
            qa[h][r] = (h == 0 || h == 3 || t >= h) ? Pk[GA_[h]][r] : 0u;
            qc[h][r] = (h == 3 ? t == 3 : t <= h) ? Pk[GC_[h]][r] : 0u;
          }
          mma16(S1[h], qa[h][0], qa[h][1], Pk[GB_[h]][0], Pk[GB_[h]][1], Pk[9 + GA_[h]][0], Pk[9 + GB_[h]][0]);
          mma16(S2[h], qa[h][0], qa[h][1], Pk[GB_[h]][0], Pk[GB_[h]][1], Pk[9 + GA_[h]][1], Pk[9 + GB_[h]][1]);
        }
#pragma unroll
        for (int h = 0; h < 4; h++) {
          mma8(S1[h], qc[h][0], qc[h][1], Pk[9 + GC_[h]][0]);
          mma8(S2[h], qc[h][0], qc[h][1], Pk[9 + GC_[h]][1]);
        }
        uint32_t V1[9], V2[9];
#pragma unroll
        for (int i = 0; i < 9; i++) { V1[i] = movm(Pk[18 + i][0]); V2[i] = movm(Pk[18 + i][1]); }
        const bool remote = q == 0 && rb > 0;
        uint4 hv[6];
#pragma unroll
        for (int i = 0; i < 6; i++) hv[i] = make_uint4(0u, 0u, tag, 0u);
        if (remote) {
#pragma unroll
          for (int i = 0; i < 6; i++) hv[i] = ll_ld128(hp + i * 32);
        }
        const bool up0 = 2 * t > g, up1 = 2 * t + 1 > g;
        const uint32_t mup = (up0 ? 0xffffu : 0u) | (up1 ? 0xffff0000u : 0u);
        auto finish = [&](const float (&x0)[4], const float (&x1)[4], uint32_t ma, const uint32_t (&Vb)[9], int hi) {
          uint32_t pa[4], pb[4];
          float rs[4];
#pragma unroll
          for (int h = 0; h < 4; h++) {
            const float m = qmax(fmaxf(x0[h], x1[h]));
            const uint32_t p = pack2(ex2(x0[h] - m), ex2(x1[h] - m));
            pa[h] = p & ma; pb[h] = p & ~ma;
          }
          if (!hi) mbar_arrive_if(lane == 0, ev + EV_O * 8 + (Vb[8] & pa[3] & P.zero));
#pragma unroll
          for (int h = 0; h < 4; h += 2) {
            float R[4];
            mma16(R, pa[h], pa[h + 1], pb[h], pb[h + 1], 0x3f803f80u, 0x3f803f80u);
            rs[h] = rcp_fast(R[0]); rs[h + 1] = rcp_fast(R[2]);
          }
#pragma unroll
          for (int i = 0; i < 9; i++) {
            const int h = 4 * i / 9, e = (h & 1) * 2;
            const bool split = i == 2 || i == 4 || i == 6, nx = split && 2 * t >= i;
            float O[4], N[4];
            mma16(O, pa[h & 2], pa[h | 1], pb[h & 2], pb[h | 1], V1[i], Vb[i]);
            if (i == 4) mma16(N, pa[2], pa[3], pb[2], pb[3], V1[i], Vb[i]); else { N[0] = O[2]; N[1] = O[3]; }
            const float r = nx ? rs[h + (split ? 1 : 0)] : rs[h];
            stg32(od + i * 1024 + hi * 128, pack2((nx ? N[0] : O[e]) * r, (nx ? N[1] : O[e + 1]) * r));
          }
        };
        {
          float x0[4], x1[4];
#pragma unroll
          for (int h = 0; h < 4; h++) { x0[h] = (up0 ? S1[h][2] : S2[h][2]) * sc1; x1[h] = (up1 ? S1[h][3] : S2[h][3]) * sc1; }
          finish(x0, x1, mup, V2, 1);
        }
        ACLK(2);
        bar_sync(1 + w, 128);
        uint32_t H[18];
        if (q > 0) {
#pragma unroll
          for (int i = 0; i < 18; i++) H[i] = lds32(att - 2048 + (i >> 4) * ST_BYTES + (i & 15) * 128);
        } else {
#pragma unroll 1
          for (int it = 0; it < (1 << 20); it++) {
            bool ok = true;
#pragma unroll
            for (int i = 0; i < 6; i++) ok = ok && hv[i].z == tag;
            if (__all_sync(~0u, ok)) break;
#pragma unroll
            for (int i = 0; i < 6; i++) hv[i] = ll_ld128(hp + i * 32);
          }
#pragma unroll
          for (int i = 0; i < 6; i++) { H[3 * i] = hv[i].x; H[3 * i + 1] = hv[i].y; H[3 * i + 2] = hv[i].w; }
        }
        float S0[4][4];
#pragma unroll
        for (int h = 0; h < 4; h++) {
          mma16(S0[h], qa[h][0], qa[h][1], Pk[GB_[h]][0], Pk[GB_[h]][1], H[GA_[h]], H[GB_[h]]);
        }
#pragma unroll
        for (int h = 0; h < 4; h++) mma8(S0[h], qc[h][0], qc[h][1], H[GC_[h]]);
        uint32_t V0[9];
#pragma unroll
        for (int i = 0; i < 9; i++) V0[i] = movm(H[9 + i]);
        ACLK(3);
        {
          const bool nohalo = (rb | q) == 0;
          const float b0 = up0 && nohalo ? -INFINITY : 0.f, b1 = up1 && nohalo ? -INFINITY : 0.f;
          float x0[4], x1[4];
#pragma unroll
          for (int h = 0; h < 4; h++) { x0[h] = fmaf(up0 ? S0[h][0] : S1[h][0], sc0, b0); x1[h] = fmaf(up1 ? S0[h][1] : S1[h][1], sc0, b1); }
          finish(x0, x1, ~mup, V0, 0);
        }
        ACLK(4);
        bar_arrive(3 + w, 256);
        ACLK_OUT;
        TRC(tr, w, tb + 2);
        MCLK(1, 2);
      }
      {
        float acc[36];
        const int hw = rb * 2 + (j & 1), js = (j & 6) + w;
        const uint32_t xt = sb + SM_STG + (16 * q + (lane & 15)) * 288 + (9 * w + (lane >> 4)) * 16, eye = (g >> 1) == t ? 0x3f80u << (g & 1) * 16 : 0u;
        uint32_t xm = xt ^ ((lane & 4) << 2), xl = sb + SM_STG + (2 * q + w) * 2304;
        uint32_t xl0 = xl + (lane >> 4) * 288 + (lane & 15) * 16, xl1 = xl + ((lane >> 1) & 7) * 288 + 256 + ((lane ^ (lane >> 3)) & 1) * 16;
        uint8_t* xd0 = P.xs[L + 1] + (128 * rb + 32 * q + 16 * w + (j & 1)) * (DM * 2) + (j & 6) * 144;
        uint8_t* xd1 = xd0 + (lane >> 1) * (DM * 4) + 256 + (lane & 1) * 16;
        xd0 += (lane >> 4) * (DM * 4) + (lane & 15) * 16;
        uint4* stp = P.s->ST1 + (hw * 8 + js) * 64 + 16 * q + g;
        asm volatile("" : "+r"(xm), "+r"(xl0), "+r"(xl1), "+l"(xd0), "+l"(xd1), "+l"(stp));
        mbar_wait_c(bars + B_RES, L);
        TRC(tr, w, tb + 21);
#pragma unroll
        for (int u = 0; u < 5; u++) {
          uint32_t r[4];
          ldsm4(r, xt + u * 32);
          widen(acc + 8 * u, r[0], r[1], eye);
          if (u < 4) widen(acc + 8 * u + 4, r[2], r[3], eye);
        }
        bar_sync(4 - w, 256);
        uint32_t prev = 0;
#pragma unroll 1
        for (int u = 0; u < 5; u++) {
          const uint32_t st = sb + c.s * ST_BYTES;
          uint64_t da = dsc2(dlo(st, 1024), 0, 8 + P.zero), db = dsc2(dlo(st + ST_B + w * 18432, 1152), 0, 8 ^ P.zero);
          mbar_wait_c(bars + B_FULL + c.s * 8, c.ph); mbar_wait_c(bars + B_FULLA + c.s * 8, (ia >> 2) & 1);
          TRC(tr && u == 0, w, tb + 3);
          MCLK(u == 0, 3);
          wgmma_fence();
#pragma unroll
          for (int kk = 0; kk < 4; kk++) { wgmma_ss_n72(acc, da, db, 1); dadd(da, 128); dadd(db, 144); }
          wgmma_commit();
          wgmma_wait<1>();
          release_if(u > 0, prev);
          mbar_wait_c(bars + B_FULLA + 32 + c.s * 8, (ia >> 2) & 1);
          ia++;
          if (u == 4) break;
          wgmma_fence();
#pragma unroll
          for (int kk = 4; kk < 8; kk++) { wgmma_ss_n72(acc, da, db, 1); dadd(da, 128); dadd(db, 144); }
          wgmma_commit();
          prev = c.s; c.next();
        }
        RCLK_INIT;
        wgmma_wait<0>();
        RCLK(0);
        release(c.s);
        c.next();
        if (__builtin_expect(any_nan(acc[0], acc[2]), 0)) {
          SLOW(L);
          const uint8_t* xr = P.xs[L] + (uint32_t)((128 * rb + 32 * q + 2 * g + (j & 1)) * (DM * 2) + js * 144 + t * 4);
#pragma unroll
          for (int i = 0; i < 9; i++) widen(acc + 4 * i, ldgpu32(xr + i * 16), ldgpu32(xr + i * 16 + DM * 32), eye);
          redo<KS2, 9, 1024, 128, 1152, 128>(acc, P.s->O + (uint32_t)(hw * (2 * ZB) + q * 256 + lane * 4), P.s->WO + (uint32_t)(js * WO_SL + lane * 4), [](uint32_t*, int) {});
        }
        TRC(tr && P5TRACE != 5, w, tb + 4);
        MCLK(1, 4);
        XCLK(0);
        uint32_t pk[18];
#pragma unroll
        for (int i = 0; i < 18; i++) pk[i] = pack2(acc[2 * i], acc[2 * i + 1]);
#pragma unroll
        for (int u = 0; u < 4; u++) stsm4(xm + u * 32, pk[4 * u], pk[4 * u + 1], pk[4 * u + 2], pk[4 * u + 3]);
        asm volatile("stmatrix.sync.aligned.m8n8.x2.shared.b16 [%0], {%1,%2};" ::"r"(xm + 128), "r"(pk[16]), "r"(pk[17]) : "memory");
        float sm[4], q0[4], q1[4];
        widen(sm, pk[16], pk[17], 0x3f803f80u); widen(q0, pk[16], pk[17], pk[16]); widen(q1, pk[16], pk[17], pk[17]);
#pragma unroll
        for (int u = 0; u < 4; u++) {
          mma16acc(sm, pk + 4 * u, 0x3f803f80u, 0x3f803f80u);
          mma8(q0, pk[4 * u], pk[4 * u + 1], pk[4 * u]); mma8(q1, pk[4 * u], pk[4 * u + 1], pk[4 * u + 1]);
          mma8(q0, pk[4 * u + 2], pk[4 * u + 3], pk[4 * u + 2]); mma8(q1, pk[4 * u + 2], pk[4 * u + 3], pk[4 * u + 3]);
        }
        auto stats = [&]() {
#pragma unroll
          for (int h = 0; h < 2; h++) {
            const float ss = sm[2 * h], m = ss * (1.f / 72.f), qq = h ? ((g & 1) ? q1[3] : q1[2]) : (g & 1) ? q0[1] : q0[0];
            ll_st128_if(eye, stp + 8 * h, m, fmaxf(qq - ss * m, 0.f), tag);
          }
        };
        RCLK(1);
        bar_sync(8 + q, 64);
        RCLK(2);
        uint4 v[5];
#pragma unroll
        for (int u = 0; u < 5; u++) v[u] = lds128(u < 4 ? (xl0 ^ ((u & 2) << 3)) + u * 576 : xl1);
        stats();
#pragma unroll
        for (int u = 0; u < 5; u++) stg128_if(u < 4 || lane < 16, u < 4 ? xd0 + u * (DM * 8) : xd1, v[u].x, v[u].y, v[u].z, v[u].w);
        RCLK(3);
        signal(EV_X1);
        RCLK(4);
        RCLK(5);
        TRC(tr, w, tb + 5);
        RCLK(6);
        RCLK_OUT;
      }
      uint32_t zk[16];
      {
        uint32_t xA[36][4];
        float acc[32];
        uint32_t s0, one, off2;
        uint8_t *z1d, *zd;
        uint64_t db;
        auto bwait = [&](uint32_t dhi, bool skip) {
          s0 = c.s;
          c.next();
          if (!skip) mbar_wait_c(bars + B_FULL + c.s * 8, c.ph);
          db = dsc2(dlo(sb + s0 * ST_BYTES + ST_B, 512) - 3, 0, dhi); one = (c.s ^ P.zero) & 1;
        };
        auto mma = [&](int kk, int pp, bool hand) {
          wgmma_rs_n64(acc, xA[kk], dat(db, (kk / 18) * ST_BYTES + (kk % 18) * 2048 + 48, one), kk != 0);
          if (kk == pp && hand) bar_arrive(7 - w, 256);
          if (kk == 17 || kk == 35) wgmma_commit();
          if (kk == RL3) { wgmma_commit(); wgmma_wait<1>(); release(s0); }
        };
        {
          XCLK(1);
          bwait(0x40000040u, false);
          XCLK(2);
          mbar_wait_c(bars + B_GATE3, L);
          XCLK(3);
          float mean0, mean1, rs0, rs1;
          stat_get(P.s->ST1 + ((rb * 2 + w) * 8 + 2 * t) * 64 + 16 * q + g, tag, 72.f, LN_EPS, mean0, rs0, mean1, rs1);
          const uint32_t ns0 = pack2(GA * rs0, GA * rs0), ns1 = pack2(GA * rs1, GA * rs1);
          const uint32_t nb0 = pack2(-mean0 * blo(ns0), -mean0 * blo(ns0)), nb1 = pack2(-mean1 * blo(ns1), -mean1 * blo(ns1));
          if (ns0 + nb1 != 0x12345) XCLK(4);
          const uint32_t al = sb + (aoff & 8191);
#pragma unroll
          for (int kb = 0; kb <= 9; kb++) {
            if (kb < 9) {
              mbar_wait_c(bars + B_FA3 + (9 * w + kb) * 8, L);
              TRC(tr && kb == 0, w, tb + 6);
              MCLK(kb == 0, 5);
              if (kb < 2) XCLK(5 + kb);
              if (kb == 0) SCLK(0);
              QCLK(kb);
              const uint32_t at = al + (w ? (((kb + 1) >> 1) & 3) * ST_BYTES + ((kb + 1) & 1) * 8192 : ((kb >> 1) & 3) * ST_BYTES + (kb & 1) * 8192);
#pragma unroll
              for (int kk = 4 * kb; kk < 4 * kb + 4; kk++) ldsm4(xA[kk], at ^ ((kk & 3) << 5));
            }
            if (kb == 0) continue;
            const uint32_t dep = xA[4 * kb - 4][0] & xA[4 * kb - 3][0] & xA[4 * kb - 2][0] & xA[4 * kb - 1][0] & P.zero;
            mbar_arrive_if(lane == 0 && (kb == 1 || w == 0), bars + B_EA3 + (9 * w + kb - 1) * 8 + dep);
#pragma unroll
            for (int kk = 4 * kb - 4; kk < 4 * kb; kk++) {
#pragma unroll
              for (int e = 0; e < 4; e++) xA[kk][e] = hfma2(xA[kk][e], (e & 1) ? ns1 : ns0, (e & 1) ? nb1 : nb0);
            }
            wgmma_fence();
#pragma unroll
            for (int kk = 4 * kb - 4; kk < 4 * kb; kk++) mma(kk, PP30, w);
          }
          off2 = lds32(sb + SM_OFF);
          z1d = z1_block(rb, w, j) + (tid & 127) * 16;
          zd = z2_block(2 * rb + (q >> 1), j) + (4 * (q & 1) + w) * 4608 + ((g & 3) * 2 + (g >> 2)) * 16 + t * 4;
          asm volatile("" : "+l"(z1d), "+l"(zd));
          wgmma_wait<0>();
          if (__builtin_expect(any_nan(acc[0], acc[2]), 0)) {
            SLOW(2 + L);
            uint4* rd = P.s->RD + (uint32_t)(bid * (36 * 256) + tid);
            asm volatile("" : "+l"(rd));
            const uint8_t* xr = P.xs[L + 1] + (uint32_t)((128 * rb + 32 * q + 2 * g + w) * (DM * 2) + t * 4);
            const uint32_t any[8] = {ns0, ns1, nb0, nb1, (uint32_t)lane, (uint32_t)tid, (uint32_t)g, (uint32_t)t};
#pragma unroll
            for (int i = 0; i < 8; i++) widen(acc + 4 * i, 0u, 0u, any[i]);
            redo<KS3, 8, 16, DM * 32, FH * 32, 16>(acc, xr, (const uint8_t*)P.w_in + (uint32_t)(g * (FH * 4) + (((9 * j + 1) >> 1) + 36) * 128 + t * 4),
                                              [&](uint32_t* a, int k) {
#pragma unroll
                                                for (int e = 0; e < 4; e++) a[e] = hfma2(a[e], (e & 1) ? ns1 : ns0, (e & 1) ? nb1 : nb0);
                                                stg128(rd + k * 256, a[0], a[1], a[2], a[3]);
                                              });
#pragma unroll
            for (int k = 0; k < 36; k++) { const uint4 v = ldcg128(rd + k * 256); xA[k][0] = v.x; xA[k][1] = v.y; xA[k][2] = v.z; xA[k][3] = v.w; }
          }
        }
        float sm[4] = {0.f, 0.f, 0.f, 0.f}, qq[4] = {0.f, 0.f, 0.f, 0.f};
        auto gelu = [&](auto nz2) {
          constexpr int NZ2 = nz2.value, R = 8 - NZ2, N = 8, D = NZ2 == 8 ? GM2 : NZ2 ? GMM : GM1;
          float th[32], gb = GB;
          uint32_t qa = 0, qb = 0;
          auto head = [&](int G) {
#pragma unroll
            for (int e = 0; e < 4; e++) { const float v = acc[4 * G + e]; th[4 * G + e] = tanh_fast(v * fmaf(v, v, gb)); }
          };
#pragma unroll
          for (int i = 0; i < D; i++) head((i + R) & 7);
#pragma unroll
          for (int i = 0; i < N; i++) {
            const int G = (i + R) & 7;
            if (i + D < N) head((i + D + R) & 7);
            float* z = acc + 4 * G;
#pragma unroll
            for (int e = 0; e < 4; e++) z[e] = fmaf(z[e], th[4 * G + e], z[e]);
            uint32_t pa = pack2(z[0], z[1]), pb = pack2(z[2], z[3]), tok;
            if (i < NZ2) {
#pragma unroll
              for (int e = 0; e < 4; e++) { sm[e] += z[e]; qq[e] = fmaf(z[e], z[e], qq[e]); }
              pa = hsub2(pa, off2); pb = hsub2(pb, off2);
              stg32(zd + i * 128, pa); stg32(zd + i * 128 + 9216, pb);
              tok = pa ^ pb ^ __float_as_uint(qq[1]);
            } else {
              if (NZ2 && G == 3) sts128(sb + SM_STG + tid * 16, qa, qb, pa, pb);
              else if (G & 1) stg128(z1d + (G >> 1) * 2048 + (NZ2 ? 24576 : 0), qa, qb, pa, pb);
              qa = pa; qb = pb;
              tok = pa ^ pb;
            }
            gb = __uint_as_float(tok * P.zero + __float_as_uint(GB));
          }
        };
        auto done = [&](int p) {
          wgmma_wait<0>();
          release(c.s);
          c.next();
          TRC(tr && p == 4, w, tb + 7);
          TRC(tr && p == 8, w, tb + 11);
          MCLK(p == 8, 6);
          SCLK(2 * p + 1);
          QCLK(10 + 3 * p);
        };
        auto pass = [&](int p, uint32_t dhi) {
          SCLK(2 * p);
          QCLK(8 + 3 * p);
          bwait(dhi, w);
          bar_sync(6 + w, 256);
          TRC(tr && p == 5, w, tb + 10);
          wgmma_fence();
#pragma unroll
          for (int kk = 0; kk < 36; kk++) mma(kk, PP3, w == 0 || p < 8);
          done(p);
        };
        done(0);
#pragma unroll 1
        for (int p = 1; p < 5; p++) {
          gelu(Int<8>{});
          zd += 1024;
          pass(p, p == 4 ? 0x80000040u : 0x40000040u);
        }
        gelu(Int<4>{});
        signal(EV_ZN);
        {
          const float a0 = qsum(sm[0] + sm[1]), a1 = qsum(sm[2] + sm[3]), q0 = qsum(qq[0] + qq[1]), q1 = qsum(qq[2] + qq[3]);
          const float ss = t ? a1 : a0, m = ss * (1.f / 288.f);
          ll_st128_if(t < 2, P.s->ZST + (rb * 2 + w) * 512 + j * 64 + 16 * q + 8 * t + g, m - blo(off2), fmaxf((t ? q1 : q0) - ss * m, 0.f), tag);
        }
        TRC(tr, w, tb + 8);
        TRC(tr, w, tb + 9);
#pragma unroll 1
        for (int p = 5;; p++) {
          pass(p, 0x40000040u);
          if (p == 8) break;
          gelu(Int<0>{});
          z1d += 8192;
        }
        signal(EV_Z1);
#pragma unroll
        for (int i = 0; i < 16; i++) zk[i] = pack2(acc[2 * i], acc[2 * i + 1]);
        SCLK(18);
        TRC(tr, w, tb + 12);
      }
      uint32_t hA[18][4];
      {
        float acc[144];
        const float c0 = __uint_as_float(lds32(sb + SM_OFF + 4));
#pragma unroll
        for (int i = 0; i < 144; i++) {
          asm volatile("fma.rn.f32 %0, %1, %2, %3;" : "=f"(acc[i]) : "f"(__uint_as_float(P.zero)), "f"((float)(i + 2)), "f"(c0));
        }
        uint32_t prev = 0;
        auto stage = [&](int kb, auto odd) {
          mbar_wait_c(bars + B_FULL + c.s * 8, c.ph);
          TRC(tr && kb == 0, w, tb + 13);
          SCLK(22 + kb);
          const uint32_t st = sb + c.s * ST_BYTES, rt = sb + SM_RT + kb * 128 + t * 8;
          uint64_t db = dsc2(dlo(st + ST_B, 4608), 0, 8 + P.zero);
          uint32_t a[4][4];
#pragma unroll
          for (int kk = 0; kk < 4; kk++) {
            uint32_t r[4];
            ldsm4(r, st + (aoff ^ (kk << 5)));
            const uint2 sc = lds64(rt + kk * 32);
            a[kk][0] = hmul2(__byte_perm(r[0], r[2], 0x5410), sc.x); a[kk][2] = hmul2(__byte_perm(r[0], r[2], 0x7632), sc.y);
            a[kk][1] = hmul2(__byte_perm(r[1], r[3], 0x5410), sc.x); a[kk][3] = hmul2(__byte_perm(r[1], r[3], 0x7632), sc.y);
          }
          if (!odd.value) {
            const float x = blo(zk[0]), y = bhi(zk[0]);
#pragma unroll
            for (int i = 0; i < 15; i++) zk[i] = zk[i + 1];
            zk[15] = pack2(fmaf(x, tanh_fast(x * fmaf(x, x, GB)), x), fmaf(y, tanh_fast(y * fmaf(y, y, GB)), y));
          }
          wgmma_fence();
#pragma unroll
          for (int i = 0; i < 8; i++) {
            const int kk = i & 3, hf = i >> 2;
            wgmma_rs_n144(acc + hf * 72, a[kk], db, 1);
            dadd(db, i == 3 ? 144u - 3 * 576 : 576 + P.zero);
            if (i == 0) { wgmma_commit(); wgmma_wait<1>(); release_if(kb, prev); }
            if (i == 3) wgmma_commit();
          }
          wgmma_commit();
          prev = c.s; c.next();
        };
        mbar_wait_c(bars + B_RT, L);
#pragma unroll 1
        for (int kb = 0; kb < 32; kb += 2) {
          if (kb == 8) mbar_wait_c(bars + B_RT1, L);
          MCLK((kb & 7) == 4, 10 + (kb >> 3));
          stage(kb, Int<0>{});
          stage(kb + 1, Int<1>{});
        }
        if (w == 1) bar_arrive(6, 256);
        HCLK(0);
        mbar_wait_c(bars + B_CV + w * 8, L);
        HCLK(1);
        const float gk = 0.5f / GA;
        const float c1 = __uint_as_float(lds32(sb + SM_OFF + 4));
        const float gb0 = -gk * (c1 + __uint_as_float(lds32(sb + SM_CV + w * 256 + (16 * q + g) * 4))), gb1 = -gk * (c1 + __uint_as_float(lds32(sb + SM_CV + w * 256 + (16 * q + g + 8) * 4)));
        mbar_wait_c(w ? bars + B_FULL + c.s * 8 : bars + B_ZB, w ? c.ph : L);
        HCLK(2);
        const uint32_t sx = c.s;
        c.next();
        const uint32_t zt = sb + tid * 16, zs = zt + sx * ST_BYTES + w * 24576;
        uint4 zz[18];
        auto zload = [&](int u) {
          if (ZW && u == ZW && P.zero) __nanosleep(0);
          if (u >= 12 && u < 16) zz[u] = make_uint4(zk[4 * u - 48], zk[4 * u - 47], zk[4 * u - 46], zk[4 * u - 45]); else zz[u] = lds128(u == 17 ? zt + SM_STG : zs + (u < 12 ? u : 12) * 2048);
        };
#pragma unroll
        for (int u = 0; u < ZA; u++) zload(u);
#pragma unroll
        for (int u = 0; u < 18; u++) {
          if (u == 0) { wgmma_wait<1>(); HCLK(3); }
          if (u == 9) {
            HCLK(4);
            wgmma_wait<0>();
            HCLK(5);
            release(prev);
            mbar_arrive_if(L == 0 && lane == 0, ev + EV_P4 * 8);
            TRC(tr, w, tb + 14);
            SCLK(54);
          }
          if (u + ZA < 18) zload(u + ZA);
          const uint4 z = zz[u];
          hA[u][0] = hmul2(z.x, pack2(fmaf(acc[8 * u], gk, gb0), fmaf(acc[8 * u + 1], gk, gb0)));
          hA[u][1] = hmul2(z.y, pack2(fmaf(acc[8 * u + 2], gk, gb1), fmaf(acc[8 * u + 3], gk, gb1)));
          hA[u][2] = hmul2(z.z, pack2(fmaf(acc[8 * u + 4], gk, gb0), fmaf(acc[8 * u + 5], gk, gb0)));
          hA[u][3] = hmul2(z.w, pack2(fmaf(acc[8 * u + 6], gk, gb1), fmaf(acc[8 * u + 7], gk, gb1)));
        }
        uint32_t dep = P.zero;
#pragma unroll
        for (int u = 0; u < 18; u++) dep &= hA[u][0];
        release(sx, dep);
        TRC(tr, w, tb + 15);
        HCLK(6);
      }
      {
        const uint32_t el = elect_one();
#pragma unroll 1
        for (int p = 0; p < 9; p++) {
          float acc[32];
          if (w == 0) mbar_wait_c(bars + B_FULL + c.s * 8, c.ph);
          uint64_t db = dsc2(dlo(sb + c.s * ST_BYTES + ST_B + (j & 1) * 4096, 0), 0, 0x40000040u + P.zero);
          HCLK(7 + 2 * p);
          bar_sync(6 + w, 256);
          wgmma_fence();
#pragma unroll
          for (int kk = 0; kk < 18; kk++) {
            wgmma_rs_n64(acc, hA[kk], db, kk != 0);
            dadd(db, kk == 15 ? 128 - (j & 1) * (36864 >> 4) : 128 + P.zero);
            if (kk == PPK && (w == 0 || p < 8)) bar_arrive(7 - w, 256);
          }
          wgmma_commit();
          const uint32_t d = sb + (p & 3) * ST_BYTES, cb = p + j >= 9 ? p + j - 9 : p + j;
          if (el) asm volatile("cp.async.bulk.commit_group;\ncp.async.bulk.wait_group.read 3;" ::: "memory");
          __syncwarp();
          wgmma_wait<0>();
          HCLK(8 + 2 * p);
          MCLK(p == 1 || p == 8, 7 + (p >> 3));
          TRC(tr && p == 8, w, tb + 16);
          release_if(L == 0 || p < 5, c.s);
          c.next();
#pragma unroll
          for (int u = 0; u < 4; u++)
            stsm4(d + (aoff ^ (u << 5)), pack2(acc[8 * u], acc[8 * u + 1]), pack2(acc[8 * u + 2], acc[8 * u + 3]), pack2(acc[8 * u + 4], acc[8 * u + 5]), pack2(acc[8 * u + 6], acc[8 * u + 7]));
          fence_async_s();
          __syncwarp();
          tma3d_red_p(el, &P.red[L], cb * 64, rb * 64 + q * 16, w, d + w * 8192 + q * 2048);
          TRC(tr && p == 8, w, tb + 17);
        }
        if (el) asm volatile("cp.async.bulk.commit_group;\ncp.async.bulk.wait_group 0;" ::: "memory");
        HCLK(25);
        MCLK(1, 9);
        if (L == 0) signal(EV_PT);
        TRC(tr, w, tb + 18);
      }
    }
  }
}

typedef CUresult (*EncodeFn)(CUtensorMap*, CUtensorMapDataType, cuuint32_t, void*, const cuuint64_t*, const cuuint64_t*, const cuuint32_t*,
                             const cuuint32_t*, CUtensorMapInterleave, CUtensorMapSwizzle, CUtensorMapL2promotion, CUtensorMapFloatOOBfill);

static void make_map(EncodeFn fn, CUtensorMap* m, const void* ptr, int rank, uint64_t d0, uint64_t d1, uint64_t d2, uint64_t s1, uint64_t s2,
                     uint32_t b0, uint32_t b1, uint32_t b2, CUtensorMapSwizzle swz) {
  cuuint64_t dims[3] = {d0, d1, d2}, strides[2] = {s1, s2};
  cuuint32_t box[3] = {b0, b1, b2}, es[3] = {1, 1, 1};
  fn(m, CU_TENSOR_MAP_DATA_TYPE_BFLOAT16, rank, const_cast<void*>(ptr), dims, strides, box, es, CU_TENSOR_MAP_INTERLEAVE_NONE, swz,
     CU_TENSOR_MAP_L2_PROMOTION_L2_128B, CU_TENSOR_MAP_FLOAT_OOB_FILL_NONE);
}

}

extern "C" void kernel_launch(void* const* d_in, const int* in_sizes, int n_in, void* d_out, int out_size) {
  using namespace mk;
  (void)in_sizes; (void)n_in; (void)out_size;
  static EncodeFn fn = nullptr;
  static Scratch* sc;
  if (!fn) {
    cudaGetSymbolAddress((void**)&sc, g_scratch);
    cudaDriverEntryPointQueryResult qr;
    cudaGetDriverEntryPoint("cuTensorMapEncodeTiled", (void**)&fn, cudaEnableDefault, &qr);
    cudaFuncSetAttribute(mega_kernel, cudaFuncAttributeMaxDynamicSharedMemorySize, SM_TOTAL);
  }
  Params p;
  p.wqkv = (const __nv_bfloat16*)d_in[1];
  p.w_in = (const __nv_bfloat16*)d_in[4];
  p.w_sp = (const __nv_bfloat16*)d_in[5];
  p.b_sp = (const __nv_bfloat16*)d_in[6];
  p.w_out = (const __nv_bfloat16*)d_in[7];
  p.zero = 0;
  p.s = sc;
  p.xs[0] = (uint8_t*)d_in[0];
  p.xs[1] = sc->X;
  p.xs[2] = (uint8_t*)d_out;
  make_map(fn, &p.wsp, p.w_sp, 3, 2048, 1024, 2, 8192, 4096, 64, 64, 2, CU_TENSOR_MAP_SWIZZLE_128B);
  for (int i = 0; i < 2; i++) {
    make_map(fn, &p.red[i], p.xs[i + 1], 3, DM, 1024, 2, 2304, 1152, 64, 16, 1, CU_TENSOR_MAP_SWIZZLE_128B);
    make_map(fn, &p.res[i], p.xs[i], 3, DM, 1024, 2, 2304, 1152, 144, 64, 1, CU_TENSOR_MAP_SWIZZLE_NONE);
  }
  make_map(fn, &p.psn, d_out, 3, DM, 1024, 2, 2304, 1152, 144, 4, 1, CU_TENSOR_MAP_SWIZZLE_NONE);
  for (int i = 0; i < 3; i++) make_map(fn, &p.act[i], p.xs[i], 3, DM, 1024, 2, 2304, 1152, 64, 64, 1, CU_TENSOR_MAP_SWIZZLE_128B);
  {
    cuuint64_t dims[4] = {8, 8, 72, 72}, strides[3] = {1152, 16, 9216};
    cuuint32_t box[4] = {8, 8, 9, 5}, es[4] = {1, 1, 1, 1};
    fn(&p.wo8, CU_TENSOR_MAP_DATA_TYPE_BFLOAT16, 4, d_in[2], dims, strides, box, es, CU_TENSOR_MAP_INTERLEAVE_NONE, CU_TENSOR_MAP_SWIZZLE_NONE,
       CU_TENSOR_MAP_L2_PROMOTION_L2_128B, CU_TENSOR_MAP_FLOAT_OOB_FILL_NONE);
  }
  for (int i = 0; i < 2; i++) {
    cuuint64_t dims[4] = {i ? 4608u : 2304u, 8, i ? 1u : 2u, 72}, strides[3] = {9216, 4608, 8 * 9216};
    cuuint32_t box[4] = {i ? 64u : 32u, 8, i ? 1u : 2u, 18}, es[4] = {1, 1, 1, 1};
    fn(i ? &p.win64 : &p.win, CU_TENSOR_MAP_DATA_TYPE_BFLOAT16, 4, d_in[4], dims, strides, box, es, CU_TENSOR_MAP_INTERLEAVE_NONE,
       i ? CU_TENSOR_MAP_SWIZZLE_128B : CU_TENSOR_MAP_SWIZZLE_64B, CU_TENSOR_MAP_L2_PROMOTION_L2_128B, CU_TENSOR_MAP_FLOAT_OOB_FILL_NONE);
  }
  make_map(fn, &p.wout, p.w_out, 2, 576, 2304, 1, 1152, 0, 64, 144, 1, CU_TENSOR_MAP_SWIZZLE_128B);
  mega_kernel<<<NGRID, 384, SM_TOTAL, cudaStreamPerThread>>>(p);
}
```

```cpp
#include <cuda_runtime.h>
#include <cuda.h>
#include <cuda_bf16.h>
#include <stdint.h>

#define LAG1 3
#define PP3 34
#define PP30 33
#define SPL 2
#define NAP 200
#define NAP0 8000
#define KS2 1
#define KS3 1
#define RL3 21
#define ZA 4
#define ZW 13
#define GA3 10
#define GB3 12
#define GM2 1
#define GMM 1
#define GM1 2
#define C0S 32.f
#define OFA 0.125f
#define OFK 2.f
#define PPK 16

namespace mk {

constexpr int SEQ = 2048, DM = 576, FH = 2304;
constexpr int NCTA = 128;
constexpr int NGRID = 132;
constexpr uint32_t ZB = 36864;
constexpr uint32_t WQ_SL = 72 * 3456;
constexpr uint32_t WO_SL = 72 * 1152;
constexpr float LN_EPS = 1e-5f;
constexpr float GA = 0.3292034911525734f, GB = 2.423681954311584f;

constexpr uint32_t ST_BYTES = 53248, ST_B = 16384, NST = 4;
constexpr uint32_t SM_STG = NST * ST_BYTES;
constexpr uint32_t SM_BAR = SM_STG + 2 * 9216;
constexpr uint32_t SM_OFF = SM_BAR + 1008;
constexpr uint32_t SM_TOTAL = SM_BAR + 1024;
constexpr uint32_t SM_RT = SM_STG + 4096, SM_CV = SM_STG + 12288, SM_WT = SM_CV + 512;
constexpr uint32_t SM_WOI = 44032, SM_CSQ = 49792, SM_XST = 50688;
constexpr uint32_t B_FULL = 0, B_EMPTY = 32, B_FULLA = 64, B_RES = 128, B_WT = 144, B_IMG = 160, B_WOI = 168, B_ZB = 176, B_GATE3 = 184, B_Z1 = 192, B_LAG = 200,
                   B_RT = 208, B_CSQ = 216, B_CV = 224, B_AD = 240, B_EVT = 272, B_RT1 = 368, B_XS = 624, B_XRW = 384, B_FA3 = 400, B_EA3 = 544;
enum { EV_PT = 0, EV_O = 1, EV_X1 = 2, EV_ZN = 3, EV_Z1 = 4, EV_P4 = 5, EV_N = 6 };

enum { FR_X2 = 0, FR_O = 1, FR_X1 = 3, FR_EP = 16, FJ = 32 * 32, FJ_WQ = 0, FJ_WO = 1, FJ_WQ0 = 2, FJ_ZN = 3, FJ_P4 = 5, FJ_EP = 16, F_N = FJ + 8 * 32 };

constexpr uint32_t POISON = 0xffffffffu;
struct Scratch {
  uint32_t flags[F_N];
  uint2 RT[SEQ];
  uint4 XST[2 * SEQ];
  uint4 ST1[SEQ * 8], ZST[SEQ * 8], HALO[32 * 8 * 6 * 32];
  float CSP[2 * NCTA * 216];
  uint8_t WQ[8 * WQ_SL], WO[8 * WO_SL];
  uint8_t O[32 * 2 * ZB];
  uint8_t X[SEQ * DM * 2];
  uint8_t Z[512 * ZB];
  uint4 RD[NCTA * 36 * 256];
};
__device__ __align__(1024) Scratch g_scratch;

struct Params {
  const __nv_bfloat16 *wqkv;
  Scratch* s;
  uint32_t zero;
  const __nv_bfloat16 *w_in, *w_sp, *b_sp, *w_out;
  uint8_t* xs[3];
  CUtensorMap wo8, wsp, win, win64, wout;
  CUtensorMap act[3];
  CUtensorMap res[2];
  CUtensorMap red[2];
  CUtensorMap psn;
};

__device__ __forceinline__ uint32_t smem_u32(const void* p) { return (uint32_t)__cvta_generic_to_shared(p); }
__device__ __forceinline__ void mbar_init(uint32_t bar, uint32_t cnt) { asm volatile("mbarrier.init.shared::cta.b64 [%0], %1;" ::"r"(bar), "r"(cnt)); }
__device__ __forceinline__ void mbar_arrive(uint32_t bar) { asm volatile("mbarrier.arrive.shared::cta.b64 _, [%0];" ::"r"(bar) : "memory"); }
__device__ __forceinline__ void mbar_wait(uint32_t bar, uint32_t parity) {
  asm volatile(
      "{\n.reg .pred p;\n.reg .u32 c;\nmov.u32 c, 0;\nLAB_WAIT:\n"
      "mbarrier.try_wait.parity.shared::cta.b64 p, [%0], %1;\n@p bra LAB_DONE;\n"
      "add.u32 c, c, 1;\nsetp.lt.u32 p, c, 0x100000;\n@p bra LAB_WAIT;\ntrap;\nLAB_DONE:\n}" ::"r"(bar), "r"(parity)
      : "memory");
}
__device__ __forceinline__ void mbar_wait_c(uint32_t bar, uint32_t parity) {
  asm volatile("{\n.reg .pred p;\nLAB_WAIT:\nmbarrier.try_wait.parity.shared::cta.b64 p, [%0], %1;\n@!p bra LAB_WAIT;\n}" ::"r"(bar), "r"(parity) : "memory");
}
__device__ __forceinline__ void flag_wait(const uint32_t* f, uint32_t target) {
  asm volatile(
      "{\n.reg .pred p;\n.reg .u32 c, v;\nmov.u32 c, 0;\nLAB_WAIT:\n"
      "ld.relaxed.gpu.global.u32 v, [%0];\nsub.u32 v, v, %1;\nsetp.ge.s32 p, v, 0;\n@p bra LAB_DONE;\n"
      "add.u32 c, c, 1;\nsetp.lt.u32 p, c, 0x400000;\n@p bra LAB_WAIT;\ntrap;\nLAB_DONE:\nfence.acquire.gpu;\n}" ::"l"(f), "r"(target)
      : "memory");
}
__device__ __forceinline__ void fence_gpu() { asm volatile("fence.acq_rel.gpu;" ::: "memory"); }
__device__ __forceinline__ void fence_async_g() { asm volatile("fence.proxy.async.global;" ::: "memory"); }
__device__ __forceinline__ void fence_async_s() { asm volatile("fence.proxy.async.shared::cta;" ::: "memory"); }
__device__ __forceinline__ uint32_t elect_one() {
  uint32_t p; asm volatile("{\n.reg .pred P;\nelect.sync _|P, 0xffffffff;\nselp.u32 %0, 1, 0, P;\n}" : "=r"(p)); return p;
}
__device__ __forceinline__ void expect_tx_p(uint32_t el, uint32_t bar, uint32_t bytes) {
  asm volatile("{\n.reg .pred P;\nsetp.ne.u32 P, %2, 0;\n@P mbarrier.arrive.expect_tx.shared::cta.b64 _, [%0], %1;\n}" ::"r"(bar), "r"(bytes), "r"(el) : "memory");
}
__device__ __forceinline__ void bulk_load_p(uint32_t el, uint32_t dst, const void* src, uint32_t bytes, uint32_t bar) {
  asm volatile("{\n.reg .pred P;\nsetp.ne.u32 P, %4, 0;\n@P cp.async.bulk.shared::cluster.global.mbarrier::complete_tx::bytes [%0], [%1], %2, [%3];\n}" ::"r"(dst), "l"(src), "r"(bytes), "r"(bar), "r"(el) : "memory");
}
__device__ __forceinline__ uint64_t policy_evict_first() { uint64_t p; asm("createpolicy.fractional.L2::evict_first.b64 %0, 1.0;" : "=l"(p)); return p; }
__device__ __forceinline__ void bulk_load_h(uint32_t el, uint32_t dst, const void* src, uint32_t bytes, uint32_t bar, bool ef, uint64_t pol) {
  if (ef) {
    asm volatile("{\n.reg .pred P;\nsetp.ne.u32 P, %4, 0;\n@P cp.async.bulk.shared::cluster.global.mbarrier::complete_tx::bytes.L2::cache_hint [%0], [%1], %2, [%3], %5;\n}" ::"r"(dst), "l"(src), "r"(bytes), "r"(bar), "r"(el), "l"(pol) : "memory");
  } else {
    asm volatile("{\n.reg .pred P;\nsetp.ne.u32 P, %4, 0;\n@P cp.async.bulk.shared::cluster.global.mbarrier::complete_tx::bytes [%0], [%1], %2, [%3];\n}" ::"r"(dst), "l"(src), "r"(bytes), "r"(bar), "r"(el) : "memory");
  }
}
__device__ __forceinline__ void bulk_mc_h(uint32_t el, uint32_t dst, const void* src, uint32_t bytes, uint32_t bar, bool ef, uint64_t pol) {
  if (ef) {
    asm volatile("{\n.reg .pred P;\nsetp.ne.u32 P, %4, 0;\n@P cp.async.bulk.shared::cluster.global.mbarrier::complete_tx::bytes.multicast::cluster.L2::cache_hint [%0], [%1], %2, [%3], %5, %6;\n}" ::"r"(dst), "l"(src), "r"(bytes), "r"(bar), "r"(el), "h"((uint16_t)3), "l"(pol) : "memory");
  } else {
    asm volatile("{\n.reg .pred P;\nsetp.ne.u32 P, %4, 0;\n@P cp.async.bulk.shared::cluster.global.mbarrier::complete_tx::bytes.multicast::cluster [%0], [%1], %2, [%3], %5;\n}" ::"r"(dst), "l"(src), "r"(bytes), "r"(bar), "r"(el), "h"((uint16_t)3) : "memory");
  }
}
__device__ __forceinline__ void tma3d_h(uint32_t el, uint32_t dst, const CUtensorMap* m, int c0, int c1, int c2, uint32_t bar, bool ef, uint64_t pol) {
  if (ef) {
    asm volatile("{\n.reg .pred P;\nsetp.ne.u32 P, %6, 0;\n@P cp.async.bulk.tensor.3d.shared::cluster.global.mbarrier::complete_tx::bytes.L2::cache_hint [%0], [%1, {%3, %4, %5}], [%2], %7;\n}" ::"r"(dst), "l"(m), "r"(bar), "r"(c0), "r"(c1), "r"(c2), "r"(el), "l"(pol) : "memory");
  } else {
    asm volatile("{\n.reg .pred P;\nsetp.ne.u32 P, %6, 0;\n@P cp.async.bulk.tensor.3d.shared::cluster.global.mbarrier::complete_tx::bytes [%0], [%1, {%3, %4, %5}], [%2];\n}" ::"r"(dst), "l"(m), "r"(bar), "r"(c0), "r"(c1), "r"(c2), "r"(el) : "memory");
  }
}
__device__ __forceinline__ void tma2d_mc_h(uint32_t el, uint32_t dst, const CUtensorMap* m, int c0, int c1, uint32_t bar, bool ef, uint64_t pol) {
  if (ef) {
    asm volatile("{\n.reg .pred P;\nsetp.ne.u32 P, %5, 0;\n@P cp.async.bulk.tensor.2d.shared::cluster.global.mbarrier::complete_tx::bytes.multicast::cluster.L2::cache_hint [%0], [%1, {%3, %4}], [%2], %6, %7;\n}" ::"r"(dst), "l"(m), "r"(bar), "r"(c0), "r"(c1), "r"(el), "h"((uint16_t)3), "l"(pol) : "memory");
  } else {
    asm volatile("{\n.reg .pred P;\nsetp.ne.u32 P, %5, 0;\n@P cp.async.bulk.tensor.2d.shared::cluster.global.mbarrier::complete_tx::bytes.multicast::cluster [%0], [%1, {%3, %4}], [%2], %6;\n}" ::"r"(dst), "l"(m), "r"(bar), "r"(c0), "r"(c1), "r"(el), "h"((uint16_t)3) : "memory");
  }
}
__device__ __forceinline__ void tma4d_mc(uint32_t el, uint32_t dst, const CUtensorMap* m, int c0, int c3, uint32_t bar, uint64_t pol) {
  asm volatile("{\n.reg .pred P;\nsetp.ne.u32 P, %5, 0;\n@P cp.async.bulk.tensor.4d.shared::cluster.global.mbarrier::complete_tx::bytes.multicast::cluster.L2::cache_hint [%0], [%1, {%3, 0, 0, %4}], [%2], %6, %7;\n}" ::"r"(dst), "l"(m), "r"(bar), "r"(c0), "r"(c3), "r"(el), "h"((uint16_t)3), "l"(pol) : "memory");
}
__device__ __forceinline__ void mbar_arrive_cluster_if(bool c, uint32_t addr) {
  asm volatile("{\n.reg .pred P;\nsetp.ne.u32 P, %1, 0;\n@P mbarrier.arrive.shared::cluster.b64 _, [%0];\n}" ::"r"(addr), "r"((uint32_t)c) : "memory");
}
__device__ __forceinline__ void mbar_arrive_if(bool c, uint32_t addr) {
  asm volatile("{\n.reg .pred P;\nsetp.ne.u32 P, %1, 0;\n@P mbarrier.arrive.shared::cta.b64 _, [%0];\n}" ::"r"(addr), "r"((uint32_t)c) : "memory");
}
__device__ __forceinline__ uint32_t mapa(uint32_t addr, uint32_t rank) { uint32_t r; asm("mapa.shared::cluster.u32 %0, %1, %2;" : "=r"(r) : "r"(addr), "r"(rank)); return r; }
__device__ __forceinline__ void bulk_store_p(uint32_t el, void* dst, uint32_t src, uint32_t bytes) {
  asm volatile("{\n.reg .pred P;\nsetp.ne.u32 P, %3, 0;\n@P cp.async.bulk.global.shared::cta.bulk_group [%0], [%1], %2;\n}" ::"l"(dst), "r"(src), "r"(bytes), "r"(el) : "memory");
}
__device__ __forceinline__ void flag_release_p(uint32_t el, uint32_t* f) {
  asm volatile("{\n.reg .pred P;\nsetp.ne.u32 P, %1, 0;\n@P red.release.gpu.global.add.u32 [%0], 1;\n}" ::"l"(f), "r"(el) : "memory");
}
__device__ __forceinline__ void flag_add_p(uint32_t el, uint32_t* f) {
  asm volatile("{\n.reg .pred P;\nsetp.ne.u32 P, %1, 0;\n@P red.relaxed.gpu.global.add.u32 [%0], 1;\n}" ::"l"(f), "r"(el) : "memory");
}
__device__ __forceinline__ void prefetch_l2(const void* src, uint32_t bytes) { asm volatile("cp.async.bulk.prefetch.L2.global [%0], %1;" ::"l"(src), "r"(bytes) : "memory"); }
__device__ __forceinline__ void prefetch_map(const CUtensorMap* m) { asm volatile("prefetch.tensormap [%0];" ::"l"(m) : "memory"); }
__device__ __forceinline__ void wgmma_fence() { asm volatile("wgmma.fence.sync.aligned;" ::: "memory"); }
__device__ __forceinline__ void wgmma_commit() { asm volatile("wgmma.commit_group.sync.aligned;" ::: "memory"); }
template <int N> __device__ __forceinline__ void wgmma_wait() { asm volatile("wgmma.wait_group.sync.aligned %0;" ::"n"(N) : "memory"); }
__device__ __forceinline__ uint32_t dlo(uint32_t addr, uint32_t lbo) { return ((addr & 0x3FFFF) >> 4) + ((lbo >> 4) << 16); }
__device__ __forceinline__ uint64_t dsc2(uint32_t lo, uint32_t off, uint32_t hi) {
  uint64_t d; asm("mov.b64 %0, {%1, %2};" : "=l"(d) : "r"(lo + (off >> 4)), "r"(hi)); return d;
}
__device__ __forceinline__ uint64_t dat(uint64_t d, uint32_t off, uint32_t one) { uint64_t r; asm("mad.wide.u32 %0, %1, %2, %3;" : "=l"(r) : "r"(one), "r"(off >> 4), "l"(d)); return r; }
__device__ __forceinline__ void dadd(uint64_t& d, uint32_t v) {
  asm("{\n.reg .b32 lo, hi;\nmov.b64 {lo, hi}, %0;\nadd.u32 lo, lo, %1;\nmov.b64 %0, {lo, hi};\n}" : "+l"(d) : "r"(v));
}
template <int R> __device__ __forceinline__ void reg_alloc() { asm volatile("setmaxnreg.inc.sync.aligned.u32 %0;" ::"n"(R)); }
template <int R> __device__ __forceinline__ void reg_dealloc() { asm volatile("setmaxnreg.dec.sync.aligned.u32 %0;" ::"n"(R)); }
__device__ __forceinline__ void bar_sync(int id, int n) { asm volatile("bar.sync %0, %1;" ::"r"(id), "r"(n) : "memory"); }
__device__ __forceinline__ void bar_arrive(int id, int n) { asm volatile("bar.arrive %0, %1;" ::"r"(id), "r"(n) : "memory"); }
__device__ __forceinline__ void ldsm4(uint32_t* r, uint32_t addr) {
  asm volatile("ldmatrix.sync.aligned.m8n8.x4.shared.b16 {%0,%1,%2,%3}, [%4];" : "=r"(r[0]), "=r"(r[1]), "=r"(r[2]), "=r"(r[3]) : "r"(addr) : "memory");
}
__device__ __forceinline__ uint32_t movm(uint32_t a) { uint32_t d; asm volatile("movmatrix.sync.aligned.m8n8.trans.b16 %0, %1;" : "=r"(d) : "r"(a)); return d; }
__device__ __forceinline__ void mma16(float* c, uint32_t a0, uint32_t a1, uint32_t a2, uint32_t a3, uint32_t b0, uint32_t b1) {
  asm volatile("mma.sync.aligned.m16n8k16.row.col.f32.bf16.bf16.f32 {%0,%1,%2,%3}, {%4,%5,%6,%7}, {%8,%9}, {%10,%10,%10,%10};"
               : "=f"(c[0]), "=f"(c[1]), "=f"(c[2]), "=f"(c[3]) : "r"(a0), "r"(a1), "r"(a2), "r"(a3), "r"(b0), "r"(b1), "f"(0.f));
}
__device__ __forceinline__ void mma8(float* c, uint32_t a0, uint32_t a1, uint32_t b0) {
  asm volatile("mma.sync.aligned.m16n8k8.row.col.f32.bf16.bf16.f32 {%0,%1,%2,%3}, {%4,%5}, {%6}, {%0,%1,%2,%3};"
               : "+f"(c[0]), "+f"(c[1]), "+f"(c[2]), "+f"(c[3]) : "r"(a0), "r"(a1), "r"(b0));
}
__device__ __forceinline__ void widen(float* c, uint32_t a0, uint32_t a1, uint32_t eye) {
  asm volatile("mma.sync.aligned.m16n8k8.row.col.f32.bf16.bf16.f32 {%0,%1,%2,%3}, {%4,%5}, {%6}, {%7,%7,%7,%7};"
               : "=f"(c[0]), "=f"(c[1]), "=f"(c[2]), "=f"(c[3]) : "r"(a0), "r"(a1), "r"(eye), "f"(0.f));
}
__device__ __forceinline__ float rsq_fast(float x) { float y; asm("rsqrt.approx.ftz.f32 %0, %1;" : "=f"(y) : "f"(x)); return y; }
__device__ __forceinline__ uint32_t pack2(float lo, float hi) { uint32_t r; asm("cvt.rn.bf16x2.f32 %0, %1, %2;" : "=r"(r) : "f"(hi), "f"(lo)); return r; }
__device__ __forceinline__ float blo(uint32_t v) { return __uint_as_float(v << 16); }
__device__ __forceinline__ float bhi(uint32_t v) { return __uint_as_float(v & 0xffff0000u); }
__device__ __forceinline__ float tanh_fast(float x) { float y; asm("tanh.approx.f32 %0, %1;" : "=f"(y) : "f"(x)); return y; }
__device__ __forceinline__ float rcp_fast(float x) { float y; asm("rcp.approx.ftz.f32 %0, %1;" : "=f"(y) : "f"(x)); return y; }
__device__ __forceinline__ float ex2(float x) { float y; asm("ex2.approx.ftz.f32 %0, %1;" : "=f"(y) : "f"(x)); return y; }
__device__ __forceinline__ float qsum(float v) { v += __shfl_xor_sync(~0u, v, 1); v += __shfl_xor_sync(~0u, v, 2); return v; }
__device__ __forceinline__ float qmax(float v) { v = fmaxf(v, __shfl_xor_sync(~0u, v, 1)); v = fmaxf(v, __shfl_xor_sync(~0u, v, 2)); return v; }
__device__ __forceinline__ void stg32(void* p, uint32_t v) { asm volatile("st.global.u32 [%0], %1;" ::"l"(p), "r"(v) : "memory"); }
__device__ __forceinline__ void stg128(void* p, uint32_t a, uint32_t b, uint32_t c, uint32_t d) { asm volatile("st.global.v4.u32 [%0], {%1,%2,%3,%4};" ::"l"(p), "r"(a), "r"(b), "r"(c), "r"(d) : "memory"); }
__device__ __forceinline__ uint32_t ldcg32(const void* p) { uint32_t v; asm volatile("ld.global.L1::no_allocate.u32 %0, [%1];" : "=r"(v) : "l"(p) : "memory"); return v; }
__device__ __forceinline__ uint32_t ldgpu32(const void* p) { uint32_t v; asm volatile("ld.relaxed.gpu.global.u32 %0, [%1];" : "=r"(v) : "l"(p) : "memory"); return v; }
__device__ __forceinline__ uint32_t ldca32(const void* p) { uint32_t v; asm volatile("ld.global.ca.u32 %0, [%1];" : "=r"(v) : "l"(p) : "memory"); return v; }
__device__ __forceinline__ void stg128_if(bool c, void* p, uint32_t a, uint32_t b, uint32_t cc, uint32_t d) {
  asm volatile("{\n.reg .pred P;\nsetp.ne.u32 P, %5, 0;\n@P st.global.v4.u32 [%0], {%1,%2,%3,%4};\n}" ::"l"(p), "r"(a), "r"(b), "r"(cc), "r"(d), "r"((uint32_t)c) : "memory");
}
__device__ __forceinline__ uint2 lds64(uint32_t a) { uint2 v; asm volatile("ld.shared.v2.u32 {%0,%1}, [%2];" : "=r"(v.x), "=r"(v.y) : "r"(a) : "memory"); return v; }
__device__ __forceinline__ uint4 ldcg128(const void* p) { uint4 v; asm volatile("ld.global.cg.v4.u32 {%0,%1,%2,%3}, [%4];" : "=r"(v.x), "=r"(v.y), "=r"(v.z), "=r"(v.w) : "l"(p) : "memory"); return v; }
__device__ __forceinline__ uint32_t ldnc16(const void* p) { uint16_t v; asm volatile("ld.global.nc.u16 %0, [%1];" : "=h"(v) : "l"(p)); return v; }
__device__ __forceinline__ uint4 ldnc128(const void* p) { uint4 v; asm volatile("ld.global.nc.v4.u32 {%0,%1,%2,%3}, [%4];" : "=r"(v.x), "=r"(v.y), "=r"(v.z), "=r"(v.w) : "l"(p)); return v; }
__device__ __forceinline__ uint32_t hsub2(uint32_t a, uint32_t b) { uint32_t d; asm("sub.rn.bf16x2 %0, %1, %2;" : "=r"(d) : "r"(a), "r"(b)); return d; }
__device__ __forceinline__ void stg32_if(bool c, void* p, uint32_t v) {
  asm volatile("{\n.reg .pred P;\nsetp.ne.u32 P, %2, 0;\n@P st.global.u32 [%0], %1;\n}" ::"l"(p), "r"(v), "r"((uint32_t)c) : "memory");
}
__device__ __forceinline__ uint32_t hmul2(uint32_t a, uint32_t b) { uint32_t d; asm("mul.rn.bf16x2 %0, %1, %2;" : "=r"(d) : "r"(a), "r"(b)); return d; }
__device__ __forceinline__ void sts32(uint32_t a, uint32_t v) { asm volatile("st.shared.u32 [%0], %1;" ::"r"(a), "r"(v) : "memory"); }
__device__ __forceinline__ uint32_t lds32(uint32_t a) { uint32_t v; asm volatile("ld.shared.u32 %0, [%1];" : "=r"(v) : "r"(a) : "memory"); return v; }
__device__ __forceinline__ void sts128(uint32_t a, uint32_t x, uint32_t y, uint32_t z, uint32_t w) { asm volatile("st.shared.v4.u32 [%0], {%1,%2,%3,%4};" ::"r"(a), "r"(x), "r"(y), "r"(z), "r"(w) : "memory"); }
__device__ __forceinline__ uint4 lds128(uint32_t a) { uint4 v; asm volatile("ld.shared.v4.u32 {%0,%1,%2,%3}, [%4];" : "=r"(v.x), "=r"(v.y), "=r"(v.z), "=r"(v.w) : "r"(a) : "memory"); return v; }
__device__ __forceinline__ void ll_st64(uint2* p, uint32_t v, uint32_t tag) {
  asm volatile("{\n.reg .b64 r;\nmov.b64 r, {%1,%2};\nst.relaxed.gpu.global.b64 [%0], r;\n}" ::"l"(p), "r"(v), "r"(tag) : "memory");
}
__device__ __forceinline__ uint2 ll_ld64(const uint2* p) {
  uint2 v; asm volatile("{\n.reg .b64 r;\nld.relaxed.gpu.global.b64 r, [%2];\nmov.b64 {%0,%1}, r;\n}" : "=r"(v.x), "=r"(v.y) : "l"(p) : "memory"); return v;
}
__device__ __forceinline__ void ll_st128(uint4* p, float a, float b, uint32_t tag, float c = 0.f) {
  asm volatile("{\n.reg .b128 r;\n.reg .b64 lo, hi;\nmov.b64 lo, {%1,%2};\nmov.b64 hi, {%3,%4};\nmov.b128 r, {lo, hi};\nst.relaxed.gpu.global.b128 [%0], r;\n}" ::"l"(p), "r"(__float_as_uint(a)), "r"(__float_as_uint(b)), "r"(tag), "r"(__float_as_uint(c)) : "memory");
}
__device__ __forceinline__ uint4 ll_ld128(const uint4* p) {
  uint4 v; asm volatile("{\n.reg .b128 r;\n.reg .b64 lo, hi;\nld.relaxed.gpu.global.b128 r, [%4];\nmov.b128 {lo, hi}, r;\nmov.b64 {%0,%1}, lo;\nmov.b64 {%2,%3}, hi;\n}" : "=r"(v.x), "=r"(v.y), "=r"(v.z), "=r"(v.w) : "l"(p) : "memory"); return v;
}
__device__ __forceinline__ void publish_p(uint32_t el, uint32_t* f) {
  asm volatile("{\n.reg .pred P;\nsetp.ne.u32 P, %1, 0;\n@P cp.async.bulk.commit_group;\n@P cp.async.bulk.wait_group 0;\n@P red.release.gpu.global.add.u32 [%0], 1;\n}" ::"l"(f), "r"(el) : "memory");
}
__device__ __forceinline__ void tma3d_red_p(uint32_t el, const CUtensorMap* m, int c0, int c1, int c2, uint32_t src) {
  asm volatile("{\n.reg .pred P;\nsetp.ne.u32 P, %5, 0;\n@P cp.reduce.async.bulk.tensor.3d.global.shared::cta.add.tile.bulk_group [%0, {%2, %3, %4}], [%1];\n}" ::"l"(m), "r"(src), "r"(c0), "r"(c1), "r"(c2), "r"(el) : "memory");
}
__device__ __forceinline__ void stsm4(uint32_t addr, uint32_t a, uint32_t b, uint32_t c, uint32_t d) {
  asm volatile("stmatrix.sync.aligned.m8n8.x4.shared.b16 [%0], {%1,%2,%3,%4};" ::"r"(addr), "r"(a), "r"(b), "r"(c), "r"(d) : "memory");
}
__device__ __forceinline__ void sts64(uint32_t a, uint32_t x, uint32_t y) { asm volatile("st.shared.v2.u32 [%0], {%1,%2};" ::"r"(a), "r"(x), "r"(y) : "memory"); }
__device__ __forceinline__ void ll_st128_if(bool on, uint4* p, float a, float b, uint32_t tag) {
  asm volatile("{\n.reg .pred P;\n.reg .b128 r;\n.reg .b64 lo, hi;\nsetp.ne.u32 P, %4, 0;\nmov.b64 lo, {%1,%2};\nmov.b64 hi, {%3,%3};\nmov.b128 r, {lo, hi};\n@P st.relaxed.gpu.global.b128 [%0], r;\n}" ::"l"(p), "r"(__float_as_uint(a)), "r"(__float_as_uint(b)), "r"(tag), "r"((uint32_t)on) : "memory");
}
__device__ __forceinline__ uint4 ldnc128_if(bool c, const void* p) {
  uint4 v = make_uint4(0u, 0u, 0u, 0u);
  asm volatile("{\n.reg .pred P;\nsetp.ne.u32 P, %5, 0;\n@P ld.global.nc.v4.u32 {%0,%1,%2,%3}, [%4];\n}" : "+r"(v.x), "+r"(v.y), "+r"(v.z), "+r"(v.w) : "l"(p), "r"((uint32_t)c));
  return v;
}
__device__ __forceinline__ uint32_t hfma2(uint32_t a, uint32_t b, uint32_t c) { uint32_t d; asm("fma.rn.bf16x2 %0, %1, %2, %3;" : "=r"(d) : "r"(a), "r"(b), "r"(c)); return d; }
__device__ __forceinline__ float2 lds64f(uint32_t a) { float2 v; asm volatile("ld.shared.v2.f32 {%0,%1}, [%2];" : "=f"(v.x), "=f"(v.y) : "r"(a) : "memory"); return v; }

__device__ __forceinline__ void wgmma_ss_n216(float* d, uint64_t da, uint64_t db, int scaleD) {
  asm volatile("{\n.reg .pred p;\nsetp.ne.b32 p, %110, 0;\nwgmma.mma_async.sync.aligned.m64n216k16.f32.bf16.bf16 "
    "{%0,%1,%2,%3,%4,%5,%6,%7,%8,%9,%10,%11,%12,%13,%14,%15,%16,%17,%18,%19,%20,%21,%22,%23,%24,%25,%26,%27,%28,%29,%30,%31,%32,%33,%34,%35,%36,%37,%38,%39,%40,%41,%42,%43,%44,%45,%46,%47,%48,%49,%50,%51,%52,%53,%54,%55,%56,%57,%58,%59,%60,%61,%62,%63,%64,%65,%66,%67,%68,%69,%70,%71,%72,%73,%74,%75,%76,%77,%78,%79,%80,%81,%82,%83,%84,%85,%86,%87,%88,%89,%90,%91,%92,%93,%94,%95,%96,%97,%98,%99,%100,%101,%102,%103,%104,%105,%106,%107}, "
    "%108, %109, p, 1, 1, 0, 1;\n}\n"
    : "+f"(d[0]), "+f"(d[1]), "+f"(d[2]), "+f"(d[3]), "+f"(d[4]), "+f"(d[5]), "+f"(d[6]), "+f"(d[7]), "+f"(d[8]), "+f"(d[9]), "+f"(d[10]), "+f"(d[11]), "+f"(d[12]), "+f"(d[13]), "+f"(d[14]), "+f"(d[15]), "+f"(d[16]), "+f"(d[17]), "+f"(d[18]), "+f"(d[19]), "+f"(d[20]), "+f"(d[21]), "+f"(d[22]), "+f"(d[23]), "+f"(d[24]), "+f"(d[25]), "+f"(d[26]), "+f"(d[27]), "+f"(d[28]), "+f"(d[29]), "+f"(d[30]), "+f"(d[31]), "+f"(d[32]), "+f"(d[33]), "+f"(d[34]), "+f"(d[35]), "+f"(d[36]), "+f"(d[37]), "+f"(d[38]), "+f"(d[39]), "+f"(d[40]), "+f"(d[41]), "+f"(d[42]), "+f"(d[43]), "+f"(d[44]), "+f"(d[45]), "+f"(d[46]), "+f"(d[47]), "+f"(d[48]), "+f"(d[49]), "+f"(d[50]), "+f"(d[51]), "+f"(d[52]), "+f"(d[53]), "+f"(d[54]), "+f"(d[55]), "+f"(d[56]), "+f"(d[57]), "+f"(d[58]), "+f"(d[59]), "+f"(d[60]), "+f"(d[61]), "+f"(d[62]), "+f"(d[63]), "+f"(d[64]), "+f"(d[65]), "+f"(d[66]), "+f"(d[67]), "+f"(d[68]), "+f"(d[69]), "+f"(d[70]), "+f"(d[71]), "+f"(d[72]), "+f"(d[73]), "+f"(d[74]), "+f"(d[75]), "+f"(d[76]), "+f"(d[77]), "+f"(d[78]), "+f"(d[79]), "+f"(d[80]), "+f"(d[81]), "+f"(d[82]), "+f"(d[83]), "+f"(d[84]), "+f"(d[85]), "+f"(d[86]), "+f"(d[87]), "+f"(d[88]), "+f"(d[89]), "+f"(d[90]), "+f"(d[91]), "+f"(d[92]), "+f"(d[93]), "+f"(d[94]), "+f"(d[95]), "+f"(d[96]), "+f"(d[97]), "+f"(d[98]), "+f"(d[99]), "+f"(d[100]), "+f"(d[101]), "+f"(d[102]), "+f"(d[103]), "+f"(d[104]), "+f"(d[105]), "+f"(d[106]), "+f"(d[107])
    : "l"(da), "l"(db), "r"(scaleD));
}
__device__ __forceinline__ void wgmma_ss_n72(float* d, uint64_t da, uint64_t db, int scaleD) {
  asm volatile("{\n.reg .pred p;\nsetp.ne.b32 p, %38, 0;\nwgmma.mma_async.sync.aligned.m64n72k16.f32.bf16.bf16 "
    "{%0,%1,%2,%3,%4,%5,%6,%7,%8,%9,%10,%11,%12,%13,%14,%15,%16,%17,%18,%19,%20,%21,%22,%23,%24,%25,%26,%27,%28,%29,%30,%31,%32,%33,%34,%35}, "
    "%36, %37, p, 1, 1, 0, 1;\n}\n"
    : "+f"(d[0]), "+f"(d[1]), "+f"(d[2]), "+f"(d[3]), "+f"(d[4]), "+f"(d[5]), "+f"(d[6]), "+f"(d[7]), "+f"(d[8]), "+f"(d[9]), "+f"(d[10]), "+f"(d[11]), "+f"(d[12]), "+f"(d[13]), "+f"(d[14]), "+f"(d[15]), "+f"(d[16]), "+f"(d[17]), "+f"(d[18]), "+f"(d[19]), "+f"(d[20]), "+f"(d[21]), "+f"(d[22]), "+f"(d[23]), "+f"(d[24]), "+f"(d[25]), "+f"(d[26]), "+f"(d[27]), "+f"(d[28]), "+f"(d[29]), "+f"(d[30]), "+f"(d[31]), "+f"(d[32]), "+f"(d[33]), "+f"(d[34]), "+f"(d[35])
    : "l"(da), "l"(db), "r"(scaleD));
}
__device__ __forceinline__ void wgmma_rs_n144(float* d, const uint32_t* a, uint64_t db, int scaleD) {
  asm volatile("{\n.reg .pred p;\nsetp.ne.b32 p, %77, 0;\nwgmma.mma_async.sync.aligned.m64n144k16.f32.bf16.bf16 "
    "{%0,%1,%2,%3,%4,%5,%6,%7,%8,%9,%10,%11,%12,%13,%14,%15,%16,%17,%18,%19,%20,%21,%22,%23,%24,%25,%26,%27,%28,%29,%30,%31,%32,%33,%34,%35,%36,%37,%38,%39,%40,%41,%42,%43,%44,%45,%46,%47,%48,%49,%50,%51,%52,%53,%54,%55,%56,%57,%58,%59,%60,%61,%62,%63,%64,%65,%66,%67,%68,%69,%70,%71}, "
    "{%72,%73,%74,%75}, %76, p, 1, 1, 1;\n}\n"
    : "+f"(d[0]), "+f"(d[1]), "+f"(d[2]), "+f"(d[3]), "+f"(d[4]), "+f"(d[5]), "+f"(d[6]), "+f"(d[7]), "+f"(d[8]), "+f"(d[9]), "+f"(d[10]), "+f"(d[11]), "+f"(d[12]), "+f"(d[13]), "+f"(d[14]), "+f"(d[15]), "+f"(d[16]), "+f"(d[17]), "+f"(d[18]), "+f"(d[19]), "+f"(d[20]), "+f"(d[21]), "+f"(d[22]), "+f"(d[23]), "+f"(d[24]), "+f"(d[25]), "+f"(d[26]), "+f"(d[27]), "+f"(d[28]), "+f"(d[29]), "+f"(d[30]), "+f"(d[31]), "+f"(d[32]), "+f"(d[33]), "+f"(d[34]), "+f"(d[35]), "+f"(d[36]), "+f"(d[37]), "+f"(d[38]), "+f"(d[39]), "+f"(d[40]), "+f"(d[41]), "+f"(d[42]), "+f"(d[43]), "+f"(d[44]), "+f"(d[45]), "+f"(d[46]), "+f"(d[47]), "+f"(d[48]), "+f"(d[49]), "+f"(d[50]), "+f"(d[51]), "+f"(d[52]), "+f"(d[53]), "+f"(d[54]), "+f"(d[55]), "+f"(d[56]), "+f"(d[57]), "+f"(d[58]), "+f"(d[59]), "+f"(d[60]), "+f"(d[61]), "+f"(d[62]), "+f"(d[63]), "+f"(d[64]), "+f"(d[65]), "+f"(d[66]), "+f"(d[67]), "+f"(d[68]), "+f"(d[69]), "+f"(d[70]), "+f"(d[71])
    : "r"(a[0]), "r"(a[1]), "r"(a[2]), "r"(a[3]), "l"(db), "r"(scaleD));
}
__device__ __forceinline__ void wgmma_rs_n64(float* d, const uint32_t* a, uint64_t db, int scaleD) {
  asm volatile("{\n.reg .pred p;\nsetp.ne.b32 p, %37, 0;\nwgmma.mma_async.sync.aligned.m64n64k16.f32.bf16.bf16 "
    "{%0,%1,%2,%3,%4,%5,%6,%7,%8,%9,%10,%11,%12,%13,%14,%15,%16,%17,%18,%19,%20,%21,%22,%23,%24,%25,%26,%27,%28,%29,%30,%31}, "
    "{%32,%33,%34,%35}, %36, p, 1, 1, 1;\n}\n"
    : "+f"(d[0]), "+f"(d[1]), "+f"(d[2]), "+f"(d[3]), "+f"(d[4]), "+f"(d[5]), "+f"(d[6]), "+f"(d[7]), "+f"(d[8]), "+f"(d[9]), "+f"(d[10]), "+f"(d[11]), "+f"(d[12]), "+f"(d[13]), "+f"(d[14]), "+f"(d[15]), "+f"(d[16]), "+f"(d[17]), "+f"(d[18]), "+f"(d[19]), "+f"(d[20]), "+f"(d[21]), "+f"(d[22]), "+f"(d[23]), "+f"(d[24]), "+f"(d[25]), "+f"(d[26]), "+f"(d[27]), "+f"(d[28]), "+f"(d[29]), "+f"(d[30]), "+f"(d[31])
    : "r"(a[0]), "r"(a[1]), "r"(a[2]), "r"(a[3]), "l"(db), "r"(scaleD));
}

template <int V> struct Int { static constexpr int value = V; };
struct Cur {
  uint32_t s, ph;
  __device__ __forceinline__ void next() { if (++s == NST) { s = 0; ph ^= 1; } }
};

#define z1_block(rb, w, j) (P.s->Z + ((rb) * 16 + (w) * 8 + (j)) * ZB)
#define z2_block(kb, j) (P.s->Z + (256 + (kb) * 8 + (j)) * ZB)
#define o_block(rb, w) (P.s->O + ((rb) * 2 + (w)) * (2 * ZB))
__device__ __forceinline__ void combine8(float m0, float q0, float m1, float q1, float n, float eps, float& mean, float& rstd) {
  mean = qsum(m0 + m1) * 0.125f;
  float d0 = m0 - mean, d1 = m1 - mean;
  float M2 = qsum(q0 + q1 + n * (d0 * d0 + d1 * d1));
  rstd = rsq_fast(fmaf(M2, 0.125f / n, eps));
}
__device__ __forceinline__ void stat_get(const uint4* zs, uint32_t tag, float n, float eps, float& m0, float& r0, float& m1, float& r1) {
  uint4 a0, a1, b0, b1;
#pragma unroll 1
  for (int it = 0; it < (1 << 20); it++) {
    a0 = ll_ld128(zs); a1 = ll_ld128(zs + 64); b0 = ll_ld128(zs + 8); b1 = ll_ld128(zs + 72);
    if (__all_sync(~0u, a0.z == tag && a1.z == tag && b0.z == tag && b1.z == tag)) break;
  }
  combine8(__uint_as_float(a0.x), __uint_as_float(a0.y), __uint_as_float(a1.x), __uint_as_float(a1.y), n, eps, m0, r0);
  combine8(__uint_as_float(b0.x), __uint_as_float(b0.y), __uint_as_float(b1.x), __uint_as_float(b1.y), n, eps, m1, r1);
}

__device__ __forceinline__ void rows_fetch(uint32_t el, uint32_t xr, const uint8_t* src, uint32_t bar) {
  expect_tx_p(el, bar, 9216);
#pragma unroll 1
  for (int r = 0; r < 8; r++) bulk_load_p(el, xr + r * 1152, src + r * (DM * 4), 1152, bar);
}
__device__ __forceinline__ void rows_stats(uint32_t xr, uint4* dst, uint32_t tag, int lane) {
  float s[2] = {0.f, 0.f}, q[4] = {0.f, 0.f, 0.f, 0.f};
  const uint32_t a0 = xr + (lane >> 2) * 1152 + (((lane & 3) * 2) ^ (lane >> 2)) * 16;
  uint4 n0 = lds128(a0), n1 = lds128(a0 ^ 16);
#pragma unroll 1
  for (int e = 1; e <= 9; e++) {
    const uint32_t x[8] = {n0.x, n0.y, n0.z, n0.w, n1.x, n1.y, n1.z, n1.w};
    if (e < 9) { n0 = lds128(a0 + e * 128); n1 = lds128((a0 ^ 16) + e * 128); }
#pragma unroll
    for (int u = 0; u < 8; u++) {
      const float lo = blo(x[u]), hi = bhi(x[u]);
      s[u & 1] += lo + hi; q[(u & 1) * 2] = fmaf(lo, lo, q[(u & 1) * 2]); q[(u & 1) * 2 + 1] = fmaf(hi, hi, q[(u & 1) * 2 + 1]);
    }
  }
  const float sx = s[0] + s[1], sq = (q[0] + q[1]) + (q[2] + q[3]);
  const float m = qsum(sx) * (-1.f / DM), r = rsq_fast(fmaxf(fmaf(qsum(sq), 1.f / DM, -m * m), 0.f) + LN_EPS);
  if ((lane & 3) == 0) ll_st128(dst + (lane >> 2) * 2, m, r, tag);
}

__device__ __forceinline__ void poison(const Params& P, uint32_t el, uint32_t src, const CUtensorMap* m, int rb, int j, int lane) {
#pragma unroll 1
  for (int u = lane; u < 72; u += 32) sts128(src + u * 16, POISON, POISON, POISON, POISON);
  fence_async_s();
  __syncwarp();
#pragma unroll 1
  for (int u = 0; u < 16; u++) {
    __nanosleep(NAP);
    bulk_store_p(el, o_block(rb, u >> 3) + j * 9216 + (u & 7) * 1152, src, 1152);
    asm volatile("{\n.reg .pred P;\nsetp.ne.u32 P, %5, 0;\n@P cp.async.bulk.tensor.3d.global.shared::cta.tile.bulk_group [%0, {%2, %3, %4}], [%1];\n}" ::"l"(m), "r"(src), "r"((j & 6) * 72), "r"(rb * 64 + u * 4), "r"(j & 1), "r"(el) : "memory");
  }
}
__device__ __forceinline__ void mma16acc(float* c, const uint32_t* a, uint32_t b0, uint32_t b1) {
  asm volatile("mma.sync.aligned.m16n8k16.row.col.f32.bf16.bf16.f32 {%0,%1,%2,%3}, {%4,%5,%6,%7}, {%8,%9}, {%0,%1,%2,%3};"
               : "+f"(c[0]), "+f"(c[1]), "+f"(c[2]), "+f"(c[3]) : "r"(a[0]), "r"(a[1]), "r"(a[2]), "r"(a[3]), "r"(b0), "r"(b1));
}
template <int KS, int NG, int AK, int AH, int BK, int BG, class F> __device__ __forceinline__ void redo(float* acc, const uint8_t* pa, const uint8_t* pb, F f) {
#pragma unroll 1
  for (int k = 0; k < 36; k += KS) {
    uint32_t a[4 * KS], b[2 * KS][NG];
#pragma unroll 1
    for (int it = 0; it < (1 << 20); it++) {
      bool ok = true;
#pragma unroll
      for (int e = 0; e < 4 * KS; e++) a[e] = ldgpu32(pa + (e >> 1) * AK + (e & 1) * AH);
#pragma unroll
      for (int e = 0; e < 2 * KS * NG; e++) b[e / NG][e % NG] = ldca32(pb + (e / NG) * BK + (e % NG) * BG);
#pragma unroll
      for (int e = 0; e < 4 * KS; e++) ok = ok && a[e] != POISON;
      if (__all_sync(~0u, ok)) break;
    }
#pragma unroll
    for (int e = 0; e < KS; e++) f(a + 4 * e, k + e);
#pragma unroll
    for (int e = 0; e < KS * NG; e++) mma16acc(acc + 4 * (e % NG), a + 4 * (e / NG), movm(b[2 * (e / NG)][e % NG]), movm(b[2 * (e / NG) + 1][e % NG]));
    pa += 2 * KS * AK; pb += 2 * KS * BK;
  }
}
__device__ __forceinline__ bool any_nan(float a, float b) {
  return __any_sync(~0u, a != a || b != b);
}

__global__ void __cluster_dims__(2, 1, 1) __launch_bounds__(384, 1) mega_kernel(const __grid_constant__ Params P) {
  extern __shared__ __align__(1024) uint8_t smem_raw[];
  const uint32_t sb = smem_u32(smem_raw);
  const uint32_t bars = sb + SM_BAR;
  int tid = threadIdx.x, lane = tid & 31;
  const int wid = __shfl_sync(~0u, tid >> 5, 0);
  if (tid == 256 && blockIdx.x < NCTA) prefetch_l2((const uint8_t*)P.wqkv + blockIdx.x * 6912, 6912);
  const int cl = blockIdx.x >> 1, tp = cl - 36, t7 = (tp * 37) >> 8;
  const int bid = (cl < 4 ? cl * 8 + 32 : tp < 0 ? cl - 4 : cl < 64 ? tp + t7 + 33 : cl) * 2 + (blockIdx.x & 1);
  if (bid >= NCTA) return;
  const int rb = bid & 15, j = bid >> 4;
  uint4 wv[5];
  const uint8_t* wsrc;
  {
    const int n8 = min(tid >> 3, 26), part = n8 / 9;
    const uint8_t* src = (const uint8_t*)P.wqkv + (8 * rb + (tid & 7)) * (3 * DM * 2) + (part * (DM - 72) + 72 * j + 8 * n8) * 2;
#pragma unroll
    for (int u = 0; u < SPL; u++) wv[u] = ldnc128_if(tid < 216, src + u * (128 * 3 * DM * 2));
    wsrc = src;
  }
  if (tid == 352) {
#pragma unroll
    for (int e = 0; e < 16; e++) mbar_init(bars + B_FULL + e * 8, (e >> 2) == 1 ? 16 : 1);
    mbar_init(bars + B_RES + 8, 8); mbar_init(bars + B_WT, 1); mbar_init(bars + B_WT + 8, 1); mbar_init(bars + B_IMG, 9);
    asm volatile("fence.mbarrier_init.release.cluster;" ::: "memory");
  }
  __syncthreads();

  if (wid >= 8) {
    reg_dealloc<40>();
    lane = __shfl_sync(~0u, lane, lane);
    const uint32_t el = elect_one();
    const uint64_t pol = policy_evict_first();
    uint32_t* const fj = P.s->flags + FJ + j * 32;
    if (wid == 8) {
      if (lane == 0) {
        mbar_init(bars + B_RES, 1); mbar_init(bars + B_WOI, 1); mbar_init(bars + B_ZB, 1); mbar_init(bars + B_GATE3, 3); mbar_init(bars + B_Z1, 1); mbar_init(bars + B_LAG, 4);
#pragma unroll
        for (int e = B_RT; e < B_XS + 16; e += 8) mbar_init(bars + e, e >= B_AD && e < B_EVT ? 2 : (e >= B_EVT && e < B_RT1) || (e >= B_EA3 && e < B_XS) ? 4 : 1);
        asm volatile("fence.mbarrier_init.release.cluster;" ::: "memory");
        mbar_arrive(bars + B_IMG);
      }
      __syncwarp();
#pragma unroll 1
      for (int i = 0; i < 12; i++) if (el) prefetch_map(&P.act[0] + (i < 7 ? i : i - 12));
      const uint32_t epoch = ldcg32(fj + FJ_EP + rb);
      const uint32_t rk = bid & 1;
      uint32_t dst = sb + ST_B + rk * 18432, full = bars + B_FULL, ph = 1;
      auto slot = [&](uint32_t bytes) {
        mbar_wait(full, ph);
        expect_tx_p(el, full, bytes);
        mbar_wait(full + (B_EMPTY - B_FULL), ph);
      };
      auto next = [&]() {
        const bool wrap = full == bars + B_FULL + 24;
        full += wrap ? -24 : 8; dst += wrap ? 0u - 3 * ST_BYTES : ST_BYTES; ph ^= wrap;
      };
#pragma unroll 1
      for (int L = 0; L < 2; L++) {
        const uint8_t* src = P.s->WQ + j * WQ_SL + rk * 13824;
        dst -= rk * 4608;
#pragma unroll 1
        for (int i = 0; i < 9; i++) {
          if (L == 0 && (i == 0 || i == 2 * SPL)) {
            flag_wait(fj + (i ? FJ_WQ : FJ_WQ0), (epoch + 1) * 16);
            fence_async_g();
          }
          slot(27648);
          bulk_mc_h(el, dst, src, 13824, full, true, pol);
          src += 27648;
          next();
        }
        dst += rk * 4608;
        if (L == 0) {
#pragma unroll 1
          for (int u = 0; u < 2; u++) flag_wait(P.s->flags + FJ + (j ^ u) * 32 + FJ_WO, (epoch + 1) * 16);
          fence_async_g();
        }
        src = P.s->WO + ((j & 6) + rk) * WO_SL;
#pragma unroll 1
        for (int i = 0; i < 4; i++) {
          slot(ZB);
          bulk_mc_h(el, dst, src, 18432, full, true, pol);
          src += 18432;
          next();
        }
        if (L == 0 && rb < 8 && el)
          asm volatile("cp.async.bulk.prefetch.tensor.4d.L2.global [%0, {%1, 0, 0, %2}];" ::"l"(&P.win64), "r"((((9 * j + 1) >> 1) + 36 + (rb >> 2)) * 64), "r"((rb & 3) * 18) : "memory");
        slot(18432);
        bulk_mc_h(el, dst, src, 9216, full, true, pol);
        next();
        int col = (((9 * j + 1) >> 1) + 36) * 64;
        const CUtensorMap* map = &P.win64;
#pragma unroll 1
        for (int p = 0; p < 9; p++) {
          if (p == 1) mbar_wait(bars + B_FA3 + GA3 * 8, L);
          mbar_wait(full + (B_EMPTY - B_FULL), ph);
          tma4d_mc(el, dst, map, col, rk * 18, full + 8, pol);
          mbar_arrive_if(el, full);
          next();
          if (p == 1) mbar_wait(bars + B_FA3 + GB3 * 8, L);
          slot(2 * ZB);
          tma4d_mc(el, dst, map, col, rk * 18 + 36, full, pol);
          next();
          col = p == 3 ? (9 * j + ((j & 1) ? 0 : 8)) * 32 : p == 4 ? ((9 * j + 1) >> 1) * 64 : col + 64;
          map = p == 3 ? &P.win : &P.win64;
        }
        flag_wait(fj + FJ_ZN + L, (epoch + 1) * 16);
        fence_async_g();
        src = z2_block(0, j) + rk * 18432;
#pragma unroll 1
        for (int i = 0; i < 32; i++) {
          if (i >= 4) mbar_wait(full + (B_AD - B_FULL), ((i >> 2) & 1) ^ 1);
          slot(ST_BYTES);
          bulk_mc_h(el, dst, src, 18432, full, true, pol);
          tma3d_h(el, dst - ST_B - rk * 18432, &P.wsp, i * 64, rb * 64, 0, full, true, pol);
          src += 8 * ZB;
          next();
        }
        mbar_wait(bars + B_Z1, L);
        fence_async_g();
        expect_tx_p(el, bars + B_ZB, 26624);
        mbar_wait(full + (B_AD - B_FULL), 1);
        slot(26624);
        bulk_load_h(el, dst - ST_B - rk * 18432, z1_block(rb, 0, j), 26624, bars + B_ZB, true, pol);
        bulk_load_h(el, dst - ST_B - rk * 18432 + 26624, z1_block(rb, 1, j), 26624, full, true, pol);
        next();
        col = j * 64;
#pragma unroll 1
        for (int i = 0; i < 9; i++) {
          if (i < 3) mbar_wait(full + (B_AD - B_FULL), 1);
          slot(ZB);
          tma2d_mc_h(el, dst, &P.wout, col, 288 * j + rk * 144, full, true, pol);
          col = col == 512 ? 0 : col + 64;
          next();
        }
      }
    } else if (wid < 11) {
      int w = wid - 9;
      uint32_t t8 = (ldcg32(P.s->flags + (rb * 2 + w) * 32 + FR_EP + j) + 1) * 8;
      int bo = bid;
#define FRESH asm volatile("" : "+r"(lane), "+r"(w), "+r"(bo), "+r"(t8)); const int rb = bo & 15, j = bo >> 4; \
      uint32_t *const fr = P.s->flags + (rb * 2 + w) * 32, *const fj = P.s->flags + FJ + j * 32, *const fo = P.s->flags + (rb * 2 + (j & 1)) * 32 + L; \
      const uint32_t ev = bars + B_EVT + w * EV_N * 8, tag = (t8 >> 2) - 1 + L; (void)fr; (void)fj; (void)fo; (void)ev; (void)tag
      Cur c{0, 1};
#pragma unroll 1
      for (int L = 0; L < 2; L++) {
        {
          FRESH;
          uint4* const xs = P.s->XST + (rb * 2 + w) * 128;
          if (L) {
            mbar_wait(ev + EV_PT * 8, 0);
            flag_release_p(el, fr + FR_X2);
          }
#pragma unroll 1
          for (int i = 0; i < 9; i++) {
            const uint32_t full = bars + B_FULLA + w * 32 + c.s * 8, dst = sb + c.s * ST_BYTES + w * 8192;
            if (L == 0 && i == 4) {
              mbar_wait(bars + B_WT + w * 8, 0);
              rows_stats(sb + SM_STG + w * 9216, xs + 16 * j, tag, lane);
            }
            const uint32_t src = sb + (L ? 2 * ST_BYTES + SM_WOI : SM_STG + w * 9216);
            if (i == 4) {
#pragma unroll
              for (int u = 0; u < 6; u++) sts128(src + u * 512 + lane * 16, POISON, POISON, POISON, POISON);
              fence_async_s();
              __syncwarp();
            }
            mbar_wait(bars + B_EMPTY + c.s * 8, c.ph);
            if (i < L) { flag_wait(fr + FR_X2, t8); fence_async_g(); }
            tma3d_h(el, dst, &P.act[L], i * 64, rb * 64, w, full, false, pol);
            expect_tx_p(el, full, 8192);
            c.next();
            if (i >= 4 && i < (L ? 5 : 8)) {
              int b = (rb * 2 + w) * 8 + j;
              asm volatile("" : "+r"(b));
              bulk_store_p(el, i == 4 ? (uint8_t*)P.s->HALO + b * 3072 : P.s->O + (b * 3 + i - 5) * 3072, src, 3072);
              if (i < 6) bulk_store_p(el, (i == 4 ? P.s->ST1 : P.s->ZST) + b * 64, src, 1024);
              if (i == 6) bulk_store_p(el, P.s->RT + b * 8, src, 64);
            }
            if (L == 0 && i == 3) rows_fetch(el, sb + SM_STG + w * 9216, P.xs[0] + (128 * rb + 16 * j + w) * (DM * 2), bars + B_WT + w * 8);
          }
          if (el) asm volatile("cp.async.bulk.commit_group;\ncp.async.bulk.wait_group 0;" ::: "memory");
          __syncwarp();
          if (L == 0) fence_gpu();
          const uint32_t tab = sb + L * (2 * ST_BYTES) + SM_XST + w * 512 + lane * 8;
#pragma unroll 1
          for (int it = 0; it < (1 << 22); it++) {
            const uint4 a = ll_ld128(xs + 2 * lane), b = ll_ld128(xs + 64 + 2 * lane);
            if (__all_sync(~0u, a.z == tag && b.z == tag)) { sts64(tab, a.x, a.y); sts64(tab + 256, b.x, b.y); break; }
          }
          __syncwarp();
          mbar_arrive_if(el, bars + B_XS + w * 8);
          if (w == 1) {
            mbar_wait(bars + B_XS, L);
            expect_tx_p(el, bars + B_RES, 18432);
            tma3d_h(el, sb + SM_STG, &P.res[L], (j & 6) * 72, rb * 64, j & 1, bars + B_RES, !L, pol);
          }
          if (L) flag_wait(fj + FJ_P4, t8 * 4);
        }
        {
          FRESH;
          const uint8_t* src = o_block(rb, j & 1) + w * 8192;
#pragma unroll 1
          for (int i = 0; i < 5; i++) {
            const uint32_t full = bars + B_FULLA + w * 32 + c.s * 8, dst = sb + c.s * ST_BYTES + w * 8192;
            const bool none = 2 * i + w > 8;
            mbar_wait(bars + B_EMPTY + c.s * 8, c.ph);
            expect_tx_p(el, full, none ? 0 : 8192);
            if (i == 0) {
              mbar_wait(bars + B_EMPTY + 16 * L, 0);
              mbar_wait(ev + EV_O * 8, L);
              flag_add_p(el, fr + FR_O + L);
              flag_wait(fo + FR_O, t8);
              fence_async_g();
            }
            if (!none) bulk_load_h(el, dst, src + i * 16384, 8192, full, true, pol);
            c.next();
          }
        }
        {
          FRESH;
          expect_tx_p(lane < 9, bars + B_FA3 + (9 * w + lane) * 8, 8192);
          mbar_wait(ev + EV_X1 * 8, L);
          if (L) flag_add_p(el, fo + FR_X1); else flag_release_p(el, fo + FR_X1);
          mbar_arrive_if(el, bars + B_GATE3);
          mbar_arrive_if(lane < 2, bars + B_FULLA + w * 32 + ((c.s + lane) & 3) * 8);
#pragma unroll 1
          for (int kb = 0; kb < 9; kb++) {
            const int n = 9 * w + kb;
            const uint32_t dst = sb + ((n >> 1) & 3) * ST_BYTES + (n & 1) * 8192;
            if (kb == 0) { flag_wait(fr + FR_X1 + L, t8); fence_async_g(); }
            if (n >= 8) mbar_wait(bars + B_EA3 + (n - 8) * 8, L);
            tma3d_h(el, dst, &P.act[L + 1], kb * 64, rb * 64, w, bars + B_FA3 + n * 8, false, pol);
          }
          c.ph ^= ((c.s + 18) >> 2) & 1; c.s = (c.s + 18) & 3;
        }
        float cv;
        {
        FRESH;
        expect_tx_p(el, bars + B_WT + w * 8, 2048);
#pragma unroll 1
        for (int r = 0; r < 8; r++)
          bulk_load_p(el, sb + SM_WT + w * 2176 + r * 272, (const uint8_t*)P.w_sp + (size_t)(128 * rb + 16 * j + 2 * r + w) * (SEQ * 2) + 30 * 128, 256, bars + B_WT + w * 8);
        cv = (lane & 3) ? 0.f : -blo(ldnc16(P.b_sp + 128 * rb + 16 * j + 2 * (lane >> 2) + w));
        mbar_wait(bars + B_RT, L);
        mbar_wait(bars + B_WT + w * 8, L ^ 1);
        mbar_wait(ev + EV_Z1 * 8, L);
        const uint32_t ro = (w * 64 + 8 * j + (lane >> 2)) * 128, x0 = ((lane & 3) * 2) ^ (lane >> 2);
#pragma unroll 1
        for (int i = 0; i < 32; i++) {
          const bool tail = (i >> 1) == 4;
          const int kb = tail ? i + 22 : i < 8 ? i : i - 2;
          if (i == 8) mbar_wait(bars + B_RT1, L);
          if (!tail) mbar_wait(bars + B_FULL + c.s * 8, c.ph ^ 1);
#pragma unroll
          for (int e = 0; e < 2; e++) {
            const uint4 a = lds128(!tail ? sb + c.s * ST_BYTES + ro + ((x0 ^ e) << 4) : sb + SM_WT + w * 2176 + (lane >> 2) * 272 + (i - 8) * 128 + (lane & 3) * 32 + e * 16);
            const uint4 m = lds128(sb + SM_RT + 4096 + kb * 128 + (lane & 3) * 32 + e * 16);
            cv = fmaf(blo(a.x), blo(m.x), fmaf(bhi(a.x), bhi(m.x), fmaf(blo(a.y), blo(m.y), fmaf(bhi(a.y), bhi(m.y), cv))));
            cv = fmaf(blo(a.z), blo(m.z), fmaf(bhi(a.z), bhi(m.z), fmaf(blo(a.w), blo(m.w), fmaf(bhi(a.w), bhi(m.w), cv))));
          }
          if (!tail) {
            mbar_arrive_if(el, bars + B_AD + c.s * 8 + (__float_as_uint(cv) & P.zero));
            c.next();
          }
        }
        }
        FRESH;
        cv = qsum(cv);
        uint2* const cs = (uint2*)(P.s->XST + (rb * 2 + w) * 128 + 1);
        if ((lane & 3) == 0) ll_st64(cs + 32 * j + (lane >> 2) * 4, __float_as_uint(cv), tag);
#pragma unroll 1
        for (int it = 0; it < (1 << 22); it++) {
          const uint2 a = ll_ld64(cs + 4 * lane), b = ll_ld64(cs + 128 + 4 * lane);
          if (__all_sync(~0u, a.y == tag && b.y == tag)) { sts32(sb + SM_CV + w * 256 + lane * 4, a.x); sts32(sb + SM_CV + w * 256 + 128 + lane * 4, b.x); break; }
        }
        __syncwarp();
        if (el) mbar_arrive(bars + B_CV + w * 8);
#pragma unroll 1
        for (int kb = 30; kb < 32; kb++) {
          mbar_wait(bars + B_FULL + c.s * 8, c.ph ^ 1);
          if (el) mbar_arrive(bars + B_AD + c.s * 8);
          c.next();
        }
        c.ph ^= ((c.s + 10) >> 2) & 1; c.s = (c.s + 10) & 3;
        if (L == 0) {
          mbar_wait(ev + EV_P4 * 8, 0);
          flag_add_p(el, fj + FJ_P4);
          flag_add_p(el, fr + FR_EP + j);
        }
      }
    } else {
      const uint32_t epoch = ldcg32(fj + FJ_EP + rb);
      if (SPL) {
        mbar_wait(bars + B_RES + 8, 0);
        flag_release_p(el, fj + FJ_WQ0);
      }
      mbar_wait(bars + B_IMG, 0);
      flag_release_p(el, fj + FJ_WQ);
#pragma unroll 1
      for (int L = 0; L < 2; L++) {
        auto wo_fetch = [&]() {
          expect_tx_p(el, bars + B_WOI, 5760);
          asm volatile("{\n.reg .pred P;\nsetp.ne.u32 P, %5, 0;\n@P cp.async.bulk.tensor.4d.shared::cluster.global.mbarrier::complete_tx::bytes [%0], [%1, {0, 0, %3, %4}], [%2];\n}" ::"r"(sb + SM_WOI), "l"(&P.wo8), "r"(bars + B_WOI), "r"(9 * j), "r"((9 * rb) >> 1), "r"(el) : "memory");
        };
        float* const csf = P.s->CSP + (NCTA + bid) * 216;
        if (L == 0) {
          flag_wait(fj + FJ_WQ, (epoch + 1) * 16);
          fence_async_g();
          expect_tx_p(el, bars + B_XRW, 13824);
          bulk_load_p(el, sb + ST_BYTES + SM_WOI, P.s->CSP + j * 16 * 216, 6912, bars + B_XRW);
          bulk_load_p(el, sb + 2 * ST_BYTES + SM_WOI, P.s->CSP + (j * 16 + 8) * 216, 6912, bars + B_XRW);
          wo_fetch();
          mbar_wait(bars + B_XRW, 0);
#pragma unroll 1
          for (int f = lane; f < 54; f += 32) {
            float s[4] = {0.f, 0.f, 0.f, 0.f};
#pragma unroll 4
            for (int r = 0; r < 16; r++) {
              const uint4 v = lds128(sb + ST_BYTES + SM_WOI + (r >> 3) * ST_BYTES + (r & 7) * 864 + f * 16);
              s[0] += __uint_as_float(v.x); s[1] += __uint_as_float(v.y); s[2] += __uint_as_float(v.z); s[3] += __uint_as_float(v.w);
            }
            sts128(sb + SM_CSQ + f * 16, __float_as_uint(s[0]), __float_as_uint(s[1]), __float_as_uint(s[2]), __float_as_uint(s[3]));
            stg128(csf + f * 4, __float_as_uint(s[0]), __float_as_uint(s[1]), __float_as_uint(s[2]), __float_as_uint(s[3]));
          }
          __syncwarp();
          mbar_arrive_if(el, bars + B_CSQ);
        } else {
#pragma unroll 1
          for (int u = 0; u < 4; u++) {
            const int w = u & 1;
            if (u < 2) {
              flag_wait(P.s->flags + (rb * 2 + w) * 32 + FR_X2, (epoch + 1) * 8);
              fence_async_g();
              rows_fetch(el, sb + SM_STG + w * 9216, P.xs[1] + (128 * rb + 16 * j + w) * (DM * 2), bars + B_XRW + w * 8);
            } else {
              if (u == 2) {
                expect_tx_p(el, bars + B_CSQ, 864);
                bulk_load_p(el, sb + 2 * ST_BYTES + SM_CSQ, csf, 864, bars + B_CSQ);
              }
              mbar_wait(bars + B_XRW + w * 8, w ^ 1);
              rows_stats(sb + SM_STG + w * 9216, P.s->XST + (rb * 2 + w) * 128 + 16 * j, epoch * 2 + 2, lane);
            }
          }
        }
        if (L == 0) {
          mbar_wait(bars + B_WOI, 0);
          bulk_store_p(el, P.s->WO + j * WO_SL + ((9 * rb) >> 1) * 1152, sb + SM_WOI, 5760);
          publish_p(el, fj + FJ_WO);
          const uint8_t* sp = lane < 16 ? (const uint8_t*)P.w_in + (30 * lane + 50) * (FH * 4) + FH * 2 + lane * 256 : (const uint8_t*)P.w_sp + (60 * lane) * (SEQ * 2) + lane * 64;
          float sq = 0.f;
#pragma unroll 1
          for (int u = 0; u < 4; u++) {
            const uint4 y = ldnc128(sp + u * 16);
            const uint32_t x[4] = {y.x, y.y, y.z, y.w};
#pragma unroll
            for (int e = 0; e < 4; e++) sq = fmaf(blo(x[e]), blo(x[e]), fmaf(bhi(x[e]), bhi(x[e]), sq));
          }
#pragma unroll 1
          for (int o = 8; o; o >>= 1) sq += __shfl_xor_sync(~0u, sq, o);
          sq *= lane < 16 ? 2.f * GA * GA * DM / 512.f : C0S * C0S * SEQ / 512.f;
          asm("sqrt.approx.f32 %0, %0;" : "+f"(sq));
          const float o0 = __shfl_sync(~0u, sq, 0), o1 = __shfl_sync(~0u, sq, 16);
          const float p2 = __uint_as_float(min(__float_as_uint(o0) & 0x7f800000u, 0x7e000000u)) * OFK, off = -p2 - fminf(OFA, 0.5f * p2);
          if (el) sts64(sb + SM_OFF, pack2(off, off), min(__float_as_uint(o1) & 0x7f800000u, 0x7e000000u) | 0x00400000u);
        }
        if (el) mbar_arrive(bars + B_GATE3);
        const uint32_t tag = epoch * 2 + L + 1;
        asm volatile("" : "+r"(lane));
        mbar_wait(bars + B_EVT + EV_ZN * 8, L);
        mbar_wait(bars + B_EVT + (EV_N + EV_ZN) * 8, L);
        flag_release_p(el, fj + FJ_ZN + L);
        {
          uint4 v[4];
#pragma unroll 1
          for (int it = 0; it < (1 << 22); it++) {
            bool ok = true;
#pragma unroll
            for (int u = 0; u < 4; u++) { v[u] = ll_ld128(P.s->ZST + (rb * 2 + ((lane >> 1) & 1)) * 512 + ((lane & 1) * 4 + u) * 64 + 8 * j + (lane >> 2)); ok = ok && v[u].z == tag; }
            if (__all_sync(~0u, ok)) break;
          }
          float mean = __uint_as_float(v[0].x) + __uint_as_float(v[1].x) + __uint_as_float(v[2].x) + __uint_as_float(v[3].x), M2 = 0.f;
          mean = (mean + __shfl_xor_sync(~0u, mean, 1)) * 0.125f;
#pragma unroll
          for (int u = 0; u < 4; u++) { const float d = __uint_as_float(v[u].x) - mean; M2 += fmaf(288.f * d, d, __uint_as_float(v[u].y)); }
          M2 += __shfl_xor_sync(~0u, M2, 1);
          const float rs = blo(pack2(rsq_fast(fmaf(M2, 1.f / FH, 4.f * GA * GA * LN_EPS)), 0.f));
          if (!(lane & 1)) ll_st64(P.s->RT + 128 * rb + 16 * j + (lane >> 1), pack2(rs, rs * mean), tag);
        }
#pragma unroll 1
        for (int b = 0; b < 8; b++) {
          uint4 v[4];
#pragma unroll 1
          for (int it = 0; it < (1 << 22); it++) {
            bool ok = true;
#pragma unroll
            for (int u = 0; u < 4; u++) { v[u] = ll_ld128((const uint4*)P.s->RT + b * 128 + u * 32 + lane); ok = ok && v[u].y == tag && v[u].w == tag; }
            if (__all_sync(~0u, ok)) break;
          }
#pragma unroll
          for (int u = 0; u < 4; u++) {
            const uint32_t rt = sb + SM_RT + b * 512 + u * 128, ro = (lane >> 3) * 32 + (lane & 3) * 8 + ((lane >> 2) & 1) * 2;
            sts32(rt + 4096 + lane * 4, __byte_perm(v[u].x, v[u].z, 0x7632));
            asm volatile("st.shared.u16 [%0], %1;\nst.shared.u16 [%0 + 4], %2;" ::"r"(rt + ro), "h"((uint16_t)v[u].x), "h"((uint16_t)v[u].z) : "memory");
          }
          __syncwarp();
          if (el && (b == 1 || b == 7)) mbar_arrive(bars + (b == 1 ? B_RT : B_RT1));
        }
        mbar_wait(bars + B_EVT + EV_Z1 * 8, L);
        mbar_wait(bars + B_EVT + (EV_N + EV_Z1) * 8, L);
        fence_gpu();
        if (el) mbar_arrive(bars + B_Z1);
        if (L == 0) {
          flag_add_p(el, fj + FJ_EP + rb);
          __nanosleep(NAP0);
          poison(P, el, sb + SM_STG + 17152, &P.psn, rb, j, lane);
          if (el) asm volatile("cp.async.bulk.commit_group;\ncp.async.bulk.wait_group 0;" ::: "memory");
          __syncwarp();
          fence_gpu();
        }
      }
    }
  } else {
    uint8_t* const wdst = P.s->WQ + j * WQ_SL + rb * 3456 + tid * 16;
#pragma unroll
    for (int u = 0; u < SPL; u++) stg128_if(tid < 216, wdst + u * (16 * 3456), wv[u].x, wv[u].y, wv[u].z, wv[u].w);
    __syncwarp();
    if (lane == 0) mbar_arrive(bars + B_RES + 8);
    auto repack2 = [&]() {
#pragma unroll
      for (int u = SPL; u < 5; u++) stg128_if((u < 4 || rb < 8) && tid < 216, wdst + u * (16 * 3456), wv[u].x, wv[u].y, wv[u].z, wv[u].w);
      float s[8];
#pragma unroll
      for (int e = 0; e < 8; e++) s[e] = 0.f;
#pragma unroll
      for (int u = 0; u < 5; u++) {
        uint32_t x[4] = {wv[u].x, wv[u].y, wv[u].z, wv[u].w};
        asm volatile("" : "+r"(x[0]), "+r"(x[1]), "+r"(x[2]), "+r"(x[3]));
#pragma unroll
        for (int e = 0; e < 4; e++) { s[2 * e] += blo(x[e]); s[2 * e + 1] += bhi(x[e]); }
      }
#pragma unroll
      for (int m = 4; m; m >>= 1) {
#pragma unroll
        for (int e = 0; e < m; e++) s[e] = ((tid & m) ? s[e + m] : s[e]) + __shfl_xor_sync(~0u, (tid & m) ? s[e] : s[e + m], m);
      }
      stg32_if(tid < 216, P.s->CSP + bid * 216 + tid, __float_as_uint(s[0]));
      __syncwarp();
      if (lane == 0) mbar_arrive(bars + B_IMG);
    };
    reg_alloc<232>();
    lane = __shfl_sync(~0u, lane, lane);
    tid = wid * 32 + lane;
#pragma unroll
    for (int v = SPL; v < 5; v++) wv[v] = ldnc128_if(tid < 216 && (v < 4 || rb < 8), wsrc + v * (128 * 3 * DM * 2));
    repack2();
    const int w = wid >> 2, q = wid & 3;
    int g = lane >> 2, t = lane & 3;
    const uint32_t ev = bars + B_EVT + w * EV_N * 8;
    Cur c{0, 0};
    const uint32_t ebar = mapa(bars + B_EMPTY, (bid & 1) ^ (lane & 1));
    auto release = [&](uint32_t s, uint32_t dep = 0) { mbar_arrive_cluster_if(lane < 2, ebar + s * 8 + dep); };
    auto release_if = [&](bool on, uint32_t s) { mbar_arrive_cluster_if(lane < 2 && on, ebar + s * 8); };
    uint32_t ia = 0;
    auto wait_ab = [&]() { mbar_wait_c(bars + B_FULL + c.s * 8, c.ph); mbar_wait_c(bars + B_FULLA + w * 32 + c.s * 8, (ia >> 2) & 1); ia++; };

    auto yield_done = [&]() { if (w == 0 && lane == 0) mbar_arrive(bars + B_LAG); };
    auto signal = [&](int e) { __syncwarp(); mbar_arrive_if(lane == 0, ev + e * 8); };

    const uint32_t epoch = ldcg32(P.s->flags + (rb * 2 + w) * 32 + FR_EP + j);

#pragma unroll 1
    for (int L = 0; L < 2; L++) {
      asm volatile("" : "+r"(lane), "+r"(g), "+r"(t));
      ia = 0;
      const uint32_t tag = epoch * 2 + L + 1;
      uint32_t aoff = (w * 64 + q * 16 + (lane & 15)) * 128 + (((lane >> 4) ^ (lane & 7)) << 4);
      {
        uint32_t Pk[27][2];
        float sc0, sc1;
        const uint32_t att = sb + w * 8192 + q * 2048 + lane * 4;
        uint4* hp = P.s->HALO + ((((rb - (q == 0)) * 2 + w) * 8 + j) * 6) * 32 + lane;
        uint8_t* od = o_block(rb, w) + (9 * j) * 1024 + (2 * q) * 128 + lane * 4;
        {
          float acc[108];
#pragma unroll
          for (int i = 0; i < 108; i++) acc[i] = 0.f;
          uint32_t prev = 0;
#pragma unroll 1
          for (int kb = 0; kb < 9; kb++) {
            const bool hold = w == 1 && kb == 9 - LAG1;
            if (hold) {
              wgmma_wait<0>();
              release(prev);
              mbar_wait_c(bars + B_LAG, L);
            }
            wait_ab();
            const uint32_t st = sb + c.s * ST_BYTES;
            uint64_t da = dsc2(dlo(st + w * 8192, 16), 0, 0x40000040u + P.zero), db = dsc2(dlo(st + ST_B, 3456), 0, 8 ^ P.zero);
            wgmma_fence();
#pragma unroll
            for (int kk = 0; kk < 4; kk++) {
              wgmma_ss_n216(acc, da, db, 1);
              dadd(da, 2); dadd(db, 432);
              if (kk == 0) { wgmma_commit(); wgmma_wait<1>(); release_if(kb > 0 && !hold, prev); }
            }
            wgmma_commit();
            if (kb == 7) yield_done();
            prev = c.s; c.next();
          }
          const uint32_t cs = sb + prev * ST_BYTES + SM_CSQ + t * 8;
          mbar_wait_c(bars + B_CSQ, L);
          mbar_wait_c(bars + B_XS + w * 8, L);
          const float2 n0 = lds64f(sb + prev * ST_BYTES + SM_XST + w * 512 + (16 * q + g) * 8), n1 = lds64f(sb + prev * ST_BYTES + SM_XST + w * 512 + (16 * q + g + 8) * 8);
          const float m0 = n0.x, r0 = n0.y, m1 = n1.x, r1 = n1.y;
          float2 cv[27];
#pragma unroll
          for (int G = 0; G < 27; G++) cv[G] = lds64f(cs + G * 32);
          wgmma_wait<0>();
          {
            uint32_t dep = P.zero & __float_as_uint(m0) & __float_as_uint(m1);
#pragma unroll
            for (int G = 0; G < 27; G++) dep &= __float_as_uint(cv[G].x);
            release(prev, dep);
          }
#pragma unroll
          for (int G = 9; G < 27; G++) Pk[G][1] = pack2(fmaf(m1, cv[G].x, acc[4 * G + 2]) * r1, fmaf(m1, cv[G].y, acc[4 * G + 3]) * r1);
          if (q < 3) {
#pragma unroll
            for (int i = 0; i < 18; i++) sts32(att + (i >> 4) * ST_BYTES + (i & 15) * 128, Pk[9 + i][1]);
          } else if (rb < 15) {
#pragma unroll
            for (int i = 0; i < 6; i++) ll_st128(hp + i * 32, __uint_as_float(Pk[9 + 3 * i][1]), __uint_as_float(Pk[10 + 3 * i][1]), tag, __uint_as_float(Pk[11 + 3 * i][1]));
          }
#pragma unroll
          for (int G = 0; G < 27; G++) {
            if (G < 9) {
              Pk[G][0] = pack2(fmaf(m0, cv[G].x, acc[4 * G]), fmaf(m0, cv[G].y, acc[4 * G + 1]));
              Pk[G][1] = pack2(fmaf(m1, cv[G].x, acc[4 * G + 2]), fmaf(m1, cv[G].y, acc[4 * G + 3]));
            } else {
              Pk[G][0] = pack2(fmaf(m0, cv[G].x, acc[4 * G]) * r0, fmaf(m0, cv[G].y, acc[4 * G + 1]) * r0);
            }
          }
          sc0 = r0 * (0.23570226039551584f * 1.4426950408889634f); sc1 = r1 * (0.23570226039551584f * 1.4426950408889634f);
        }
        constexpr int GA_[4] = {0, 2, 4, 7}, GB_[4] = {1, 3, 5, 8}, GC_[4] = {2, 4, 6, 6};
        float S1[4][4], S2[4][4];
        uint32_t qa[4][2], qc[4][2];
#pragma unroll
        for (int h = 0; h < 4; h++) {
#pragma unroll
          for (int r = 0; r < 2; r++) {
            qa[h][r] = (h == 0 || h == 3 || t >= h) ? Pk[GA_[h]][r] : 0u;
            qc[h][r] = (h == 3 ? t == 3 : t <= h) ? Pk[GC_[h]][r] : 0u;
          }
          mma16(S1[h], qa[h][0], qa[h][1], Pk[GB_[h]][0], Pk[GB_[h]][1], Pk[9 + GA_[h]][0], Pk[9 + GB_[h]][0]);
          mma16(S2[h], qa[h][0], qa[h][1], Pk[GB_[h]][0], Pk[GB_[h]][1], Pk[9 + GA_[h]][1], Pk[9 + GB_[h]][1]);
        }
#pragma unroll
        for (int h = 0; h < 4; h++) {
          mma8(S1[h], qc[h][0], qc[h][1], Pk[9 + GC_[h]][0]);
          mma8(S2[h], qc[h][0], qc[h][1], Pk[9 + GC_[h]][1]);
        }
        uint32_t V1[9], V2[9];
#pragma unroll
        for (int i = 0; i < 9; i++) { V1[i] = movm(Pk[18 + i][0]); V2[i] = movm(Pk[18 + i][1]); }
        const bool remote = q == 0 && rb > 0;
        uint4 hv[6];
#pragma unroll
        for (int i = 0; i < 6; i++) hv[i] = make_uint4(0u, 0u, tag, 0u);
        if (remote) {
#pragma unroll
          for (int i = 0; i < 6; i++) hv[i] = ll_ld128(hp + i * 32);
        }
        const bool up0 = 2 * t > g, up1 = 2 * t + 1 > g;
        const uint32_t mup = (up0 ? 0xffffu : 0u) | (up1 ? 0xffff0000u : 0u);
        auto finish = [&](const float (&x0)[4], const float (&x1)[4], uint32_t ma, const uint32_t (&Vb)[9], int hi) {
          uint32_t pa[4], pb[4];
          float rs[4];
#pragma unroll
          for (int h = 0; h < 4; h++) {
            const float m = qmax(fmaxf(x0[h], x1[h]));
            const uint32_t p = pack2(ex2(x0[h] - m), ex2(x1[h] - m));
            pa[h] = p & ma; pb[h] = p & ~ma;
          }
          if (!hi) mbar_arrive_if(lane == 0, ev + EV_O * 8 + (Vb[8] & pa[3] & P.zero));
#pragma unroll
          for (int h = 0; h < 4; h += 2) {
            float R[4];
            mma16(R, pa[h], pa[h + 1], pb[h], pb[h + 1], 0x3f803f80u, 0x3f803f80u);
            rs[h] = rcp_fast(R[0]); rs[h + 1] = rcp_fast(R[2]);
          }
#pragma unroll
          for (int i = 0; i < 9; i++) {
            const int h = 4 * i / 9, e = (h & 1) * 2;
            const bool split = i == 2 || i == 4 || i == 6, nx = split && 2 * t >= i;
            float O[4], N[4];
            mma16(O, pa[h & 2], pa[h | 1], pb[h & 2], pb[h | 1], V1[i], Vb[i]);
            if (i == 4) mma16(N, pa[2], pa[3], pb[2], pb[3], V1[i], Vb[i]); else { N[0] = O[2]; N[1] = O[3]; }
            const float r = nx ? rs[h + (split ? 1 : 0)] : rs[h];
            stg32(od + i * 1024 + hi * 128, pack2((nx ? N[0] : O[e]) * r, (nx ? N[1] : O[e + 1]) * r));
          }
        };
        {
          float x0[4], x1[4];
#pragma unroll
          for (int h = 0; h < 4; h++) { x0[h] = (up0 ? S1[h][2] : S2[h][2]) * sc1; x1[h] = (up1 ? S1[h][3] : S2[h][3]) * sc1; }
          finish(x0, x1, mup, V2, 1);
        }
        bar_sync(1 + w, 128);
        uint32_t H[18];
        if (q > 0) {
#pragma unroll
          for (int i = 0; i < 18; i++) H[i] = lds32(att - 2048 + (i >> 4) * ST_BYTES + (i & 15) * 128);
        } else {
#pragma unroll 1
          for (int it = 0; it < (1 << 20); it++) {
            bool ok = true;
#pragma unroll
            for (int i = 0; i < 6; i++) ok = ok && hv[i].z == tag;
            if (__all_sync(~0u, ok)) break;
#pragma unroll
            for (int i = 0; i < 6; i++) hv[i] = ll_ld128(hp + i * 32);
          }
#pragma unroll
          for (int i = 0; i < 6; i++) { H[3 * i] = hv[i].x; H[3 * i + 1] = hv[i].y; H[3 * i + 2] = hv[i].w; }
        }
        float S0[4][4];
#pragma unroll
        for (int h = 0; h < 4; h++) {
          mma16(S0[h], qa[h][0], qa[h][1], Pk[GB_[h]][0], Pk[GB_[h]][1], H[GA_[h]], H[GB_[h]]);
        }
#pragma unroll
        for (int h = 0; h < 4; h++) mma8(S0[h], qc[h][0], qc[h][1], H[GC_[h]]);
        uint32_t V0[9];
#pragma unroll
        for (int i = 0; i < 9; i++) V0[i] = movm(H[9 + i]);
        {
          const bool nohalo = (rb | q) == 0;
          const float b0 = up0 && nohalo ? -INFINITY : 0.f, b1 = up1 && nohalo ? -INFINITY : 0.f;
          float x0[4], x1[4];
#pragma unroll
          for (int h = 0; h < 4; h++) { x0[h] = fmaf(up0 ? S0[h][0] : S1[h][0], sc0, b0); x1[h] = fmaf(up1 ? S0[h][1] : S1[h][1], sc0, b1); }
          finish(x0, x1, ~mup, V0, 0);
        }
        bar_arrive(3 + w, 256);
      }
      {
        float acc[36];
        const int hw = rb * 2 + (j & 1), js = (j & 6) + w;
        const uint32_t xt = sb + SM_STG + (16 * q + (lane & 15)) * 288 + (9 * w + (lane >> 4)) * 16, eye = (g >> 1) == t ? 0x3f80u << (g & 1) * 16 : 0u;
        uint32_t xm = xt ^ ((lane & 4) << 2), xl = sb + SM_STG + (2 * q + w) * 2304;
        uint32_t xl0 = xl + (lane >> 4) * 288 + (lane & 15) * 16, xl1 = xl + ((lane >> 1) & 7) * 288 + 256 + ((lane ^ (lane >> 3)) & 1) * 16;
        uint8_t* xd0 = P.xs[L + 1] + (128 * rb + 32 * q + 16 * w + (j & 1)) * (DM * 2) + (j & 6) * 144;
        uint8_t* xd1 = xd0 + (lane >> 1) * (DM * 4) + 256 + (lane & 1) * 16;
        xd0 += (lane >> 4) * (DM * 4) + (lane & 15) * 16;
        uint4* stp = P.s->ST1 + (hw * 8 + js) * 64 + 16 * q + g;
        asm volatile("" : "+r"(xm), "+r"(xl0), "+r"(xl1), "+l"(xd0), "+l"(xd1), "+l"(stp));
        mbar_wait_c(bars + B_RES, L);
#pragma unroll
        for (int u = 0; u < 5; u++) {
          uint32_t r[4];
          ldsm4(r, xt + u * 32);
          widen(acc + 8 * u, r[0], r[1], eye);
          if (u < 4) widen(acc + 8 * u + 4, r[2], r[3], eye);
        }
        bar_sync(4 - w, 256);
        uint32_t prev = 0;
#pragma unroll 1
        for (int u = 0; u < 5; u++) {
          const uint32_t st = sb + c.s * ST_BYTES;
          uint64_t da = dsc2(dlo(st, 1024), 0, 8 + P.zero), db = dsc2(dlo(st + ST_B + w * 18432, 1152), 0, 8 ^ P.zero);
          mbar_wait_c(bars + B_FULL + c.s * 8, c.ph); mbar_wait_c(bars + B_FULLA + c.s * 8, (ia >> 2) & 1);
          wgmma_fence();
#pragma unroll
          for (int kk = 0; kk < 4; kk++) { wgmma_ss_n72(acc, da, db, 1); dadd(da, 128); dadd(db, 144); }
          wgmma_commit();
          wgmma_wait<1>();
          release_if(u > 0, prev);
          mbar_wait_c(bars + B_FULLA + 32 + c.s * 8, (ia >> 2) & 1);
          ia++;
          if (u == 4) break;
          wgmma_fence();
#pragma unroll
          for (int kk = 4; kk < 8; kk++) { wgmma_ss_n72(acc, da, db, 1); dadd(da, 128); dadd(db, 144); }
          wgmma_commit();
          prev = c.s; c.next();
        }
        wgmma_wait<0>();
        release(c.s);
        c.next();
        if (__builtin_expect(any_nan(acc[0], acc[2]), 0)) {
          const uint8_t* xr = P.xs[L] + (uint32_t)((128 * rb + 32 * q + 2 * g + (j & 1)) * (DM * 2) + js * 144 + t * 4);
#pragma unroll
          for (int i = 0; i < 9; i++) widen(acc + 4 * i, ldgpu32(xr + i * 16), ldgpu32(xr + i * 16 + DM * 32), eye);
          redo<KS2, 9, 1024, 128, 1152, 128>(acc, P.s->O + (uint32_t)(hw * (2 * ZB) + q * 256 + lane * 4), P.s->WO + (uint32_t)(js * WO_SL + lane * 4), [](uint32_t*, int) {});
        }
        uint32_t pk[18];
#pragma unroll
        for (int i = 0; i < 18; i++) pk[i] = pack2(acc[2 * i], acc[2 * i + 1]);
#pragma unroll
        for (int u = 0; u < 4; u++) stsm4(xm + u * 32, pk[4 * u], pk[4 * u + 1], pk[4 * u + 2], pk[4 * u + 3]);
        asm volatile("stmatrix.sync.aligned.m8n8.x2.shared.b16 [%0], {%1,%2};" ::"r"(xm + 128), "r"(pk[16]), "r"(pk[17]) : "memory");
        float sm[4], q0[4], q1[4];
        widen(sm, pk[16], pk[17], 0x3f803f80u); widen(q0, pk[16], pk[17], pk[16]); widen(q1, pk[16], pk[17], pk[17]);
#pragma unroll
        for (int u = 0; u < 4; u++) {
          mma16acc(sm, pk + 4 * u, 0x3f803f80u, 0x3f803f80u);
          mma8(q0, pk[4 * u], pk[4 * u + 1], pk[4 * u]); mma8(q1, pk[4 * u], pk[4 * u + 1], pk[4 * u + 1]);
          mma8(q0, pk[4 * u + 2], pk[4 * u + 3], pk[4 * u + 2]); mma8(q1, pk[4 * u + 2], pk[4 * u + 3], pk[4 * u + 3]);
        }
        auto stats = [&]() {
#pragma unroll
          for (int h = 0; h < 2; h++) {
            const float ss = sm[2 * h], m = ss * (1.f / 72.f), qq = h ? ((g & 1) ? q1[3] : q1[2]) : (g & 1) ? q0[1] : q0[0];
            ll_st128_if(eye, stp + 8 * h, m, fmaxf(qq - ss * m, 0.f), tag);
          }
        };
        bar_sync(8 + q, 64);
        uint4 v[5];
#pragma unroll
        for (int u = 0; u < 5; u++) v[u] = lds128(u < 4 ? (xl0 ^ ((u & 2) << 3)) + u * 576 : xl1);
        stats();
#pragma unroll
        for (int u = 0; u < 5; u++) stg128_if(u < 4 || lane < 16, u < 4 ? xd0 + u * (DM * 8) : xd1, v[u].x, v[u].y, v[u].z, v[u].w);
        signal(EV_X1);
      }
      uint32_t zk[16];
      {
        uint32_t xA[36][4];
        float acc[32];
        uint32_t s0, one, off2;
        uint8_t *z1d, *zd;
        uint64_t db;
        auto bwait = [&](uint32_t dhi, bool skip) {
          s0 = c.s;
          c.next();
          if (!skip) mbar_wait_c(bars + B_FULL + c.s * 8, c.ph);
          db = dsc2(dlo(sb + s0 * ST_BYTES + ST_B, 512) - 3, 0, dhi); one = (c.s ^ P.zero) & 1;
        };
        auto mma = [&](int kk, int pp, bool hand) {
          wgmma_rs_n64(acc, xA[kk], dat(db, (kk / 18) * ST_BYTES + (kk % 18) * 2048 + 48, one), kk != 0);
          if (kk == pp && hand) bar_arrive(7 - w, 256);
          if (kk == 17 || kk == 35) wgmma_commit();
          if (kk == RL3) { wgmma_commit(); wgmma_wait<1>(); release(s0); }
        };
        {
          bwait(0x40000040u, false);
          mbar_wait_c(bars + B_GATE3, L);
          float mean0, mean1, rs0, rs1;
          stat_get(P.s->ST1 + ((rb * 2 + w) * 8 + 2 * t) * 64 + 16 * q + g, tag, 72.f, LN_EPS, mean0, rs0, mean1, rs1);
          const uint32_t ns0 = pack2(GA * rs0, GA * rs0), ns1 = pack2(GA * rs1, GA * rs1);
          const uint32_t nb0 = pack2(-mean0 * blo(ns0), -mean0 * blo(ns0)), nb1 = pack2(-mean1 * blo(ns1), -mean1 * blo(ns1));
          const uint32_t al = sb + (aoff & 8191);
#pragma unroll
          for (int kb = 0; kb <= 9; kb++) {
            if (kb < 9) {
              mbar_wait_c(bars + B_FA3 + (9 * w + kb) * 8, L);
              const uint32_t at = al + (w ? (((kb + 1) >> 1) & 3) * ST_BYTES + ((kb + 1) & 1) * 8192 : ((kb >> 1) & 3) * ST_BYTES + (kb & 1) * 8192);
#pragma unroll
              for (int kk = 4 * kb; kk < 4 * kb + 4; kk++) ldsm4(xA[kk], at ^ ((kk & 3) << 5));
            }
            if (kb == 0) continue;
            const uint32_t dep = xA[4 * kb - 4][0] & xA[4 * kb - 3][0] & xA[4 * kb - 2][0] & xA[4 * kb - 1][0] & P.zero;
            mbar_arrive_if(lane == 0 && (kb == 1 || w == 0), bars + B_EA3 + (9 * w + kb - 1) * 8 + dep);
#pragma unroll
            for (int kk = 4 * kb - 4; kk < 4 * kb; kk++) {
#pragma unroll
              for (int e = 0; e < 4; e++) xA[kk][e] = hfma2(xA[kk][e], (e & 1) ? ns1 : ns0, (e & 1) ? nb1 : nb0);
            }
            wgmma_fence();
#pragma unroll
            for (int kk = 4 * kb - 4; kk < 4 * kb; kk++) mma(kk, PP30, w);
          }
          off2 = lds32(sb + SM_OFF);
          z1d = z1_block(rb, w, j) + (tid & 127) * 16;
          zd = z2_block(2 * rb + (q >> 1), j) + (4 * (q & 1) + w) * 4608 + ((g & 3) * 2 + (g >> 2)) * 16 + t * 4;
          asm volatile("" : "+l"(z1d), "+l"(zd));
          wgmma_wait<0>();
          if (__builtin_expect(any_nan(acc[0], acc[2]), 0)) {
            uint4* rd = P.s->RD + (uint32_t)(bid * (36 * 256) + tid);
            asm volatile("" : "+l"(rd));
            const uint8_t* xr = P.xs[L + 1] + (uint32_t)((128 * rb + 32 * q + 2 * g + w) * (DM * 2) + t * 4);
            const uint32_t any[8] = {ns0, ns1, nb0, nb1, (uint32_t)lane, (uint32_t)tid, (uint32_t)g, (uint32_t)t};
#pragma unroll
            for (int i = 0; i < 8; i++) widen(acc + 4 * i, 0u, 0u, any[i]);
            redo<KS3, 8, 16, DM * 32, FH * 32, 16>(acc, xr, (const uint8_t*)P.w_in + (uint32_t)(g * (FH * 4) + (((9 * j + 1) >> 1) + 36) * 128 + t * 4),
                                              [&](uint32_t* a, int k) {
#pragma unroll
                                                for (int e = 0; e < 4; e++) a[e] = hfma2(a[e], (e & 1) ? ns1 : ns0, (e & 1) ? nb1 : nb0);
                                                stg128(rd + k * 256, a[0], a[1], a[2], a[3]);
                                              });
#pragma unroll
            for (int k = 0; k < 36; k++) { const uint4 v = ldcg128(rd + k * 256); xA[k][0] = v.x; xA[k][1] = v.y; xA[k][2] = v.z; xA[k][3] = v.w; }
          }
        }
        float sm[4] = {0.f, 0.f, 0.f, 0.f}, qq[4] = {0.f, 0.f, 0.f, 0.f};
        auto gelu = [&](auto nz2) {
          constexpr int NZ2 = nz2.value, R = 8 - NZ2, N = 8, D = NZ2 == 8 ? GM2 : NZ2 ? GMM : GM1;
          float th[32], gb = GB;
          uint32_t qa = 0, qb = 0;
          auto head = [&](int G) {
#pragma unroll
            for (int e = 0; e < 4; e++) { const float v = acc[4 * G + e]; th[4 * G + e] = tanh_fast(v * fmaf(v, v, gb)); }
          };
#pragma unroll
          for (int i = 0; i < D; i++) head((i + R) & 7);
#pragma unroll
          for (int i = 0; i < N; i++) {
            const int G = (i + R) & 7;
            if (i + D < N) head((i + D + R) & 7);
            float* z = acc + 4 * G;
#pragma unroll
            for (int e = 0; e < 4; e++) z[e] = fmaf(z[e], th[4 * G + e], z[e]);
            uint32_t pa = pack2(z[0], z[1]), pb = pack2(z[2], z[3]), tok;
            if (i < NZ2) {
#pragma unroll
              for (int e = 0; e < 4; e++) { sm[e] += z[e]; qq[e] = fmaf(z[e], z[e], qq[e]); }
              pa = hsub2(pa, off2); pb = hsub2(pb, off2);
              stg32(zd + i * 128, pa); stg32(zd + i * 128 + 9216, pb);
              tok = pa ^ pb ^ __float_as_uint(qq[1]);
            } else {
              if (NZ2 && G == 3) sts128(sb + SM_STG + tid * 16, qa, qb, pa, pb);
              else if (G & 1) stg128(z1d + (G >> 1) * 2048 + (NZ2 ? 24576 : 0), qa, qb, pa, pb);
              qa = pa; qb = pb;
              tok = pa ^ pb;
            }
            gb = __uint_as_float(tok * P.zero + __float_as_uint(GB));
          }
        };
        auto done = [&](int p) {
          wgmma_wait<0>();
          release(c.s);
          c.next();
        };
        auto pass = [&](int p, uint32_t dhi) {
          bwait(dhi, w);
          bar_sync(6 + w, 256);
          wgmma_fence();
#pragma unroll
          for (int kk = 0; kk < 36; kk++) mma(kk, PP3, w == 0 || p < 8);
          done(p);
        };
        done(0);
#pragma unroll 1
        for (int p = 1; p < 5; p++) {
          gelu(Int<8>{});
          zd += 1024;
          pass(p, p == 4 ? 0x80000040u : 0x40000040u);
        }
        gelu(Int<4>{});
        signal(EV_ZN);
        {
          const float a0 = qsum(sm[0] + sm[1]), a1 = qsum(sm[2] + sm[3]), q0 = qsum(qq[0] + qq[1]), q1 = qsum(qq[2] + qq[3]);
          const float ss = t ? a1 : a0, m = ss * (1.f / 288.f);
          ll_st128_if(t < 2, P.s->ZST + (rb * 2 + w) * 512 + j * 64 + 16 * q + 8 * t + g, m - blo(off2), fmaxf((t ? q1 : q0) - ss * m, 0.f), tag);
        }
#pragma unroll 1
        for (int p = 5;; p++) {
          pass(p, 0x40000040u);
          if (p == 8) break;
          gelu(Int<0>{});
          z1d += 8192;
        }
        signal(EV_Z1);
#pragma unroll
        for (int i = 0; i < 16; i++) zk[i] = pack2(acc[2 * i], acc[2 * i + 1]);
      }
      uint32_t hA[18][4];
      {
        float acc[144];
        const float c0 = __uint_as_float(lds32(sb + SM_OFF + 4));
#pragma unroll
        for (int i = 0; i < 144; i++) {
          asm volatile("fma.rn.f32 %0, %1, %2, %3;" : "=f"(acc[i]) : "f"(__uint_as_float(P.zero)), "f"((float)(i + 2)), "f"(c0));
        }
        uint32_t prev = 0;
        auto stage = [&](int kb, auto odd) {
          mbar_wait_c(bars + B_FULL + c.s * 8, c.ph);
          const uint32_t st = sb + c.s * ST_BYTES, rt = sb + SM_RT + kb * 128 + t * 8;
          uint64_t db = dsc2(dlo(st + ST_B, 4608), 0, 8 + P.zero);
          uint32_t a[4][4];
#pragma unroll
          for (int kk = 0; kk < 4; kk++) {
            uint32_t r[4];
            ldsm4(r, st + (aoff ^ (kk << 5)));
            const uint2 sc = lds64(rt + kk * 32);
            a[kk][0] = hmul2(__byte_perm(r[0], r[2], 0x5410), sc.x); a[kk][2] = hmul2(__byte_perm(r[0], r[2], 0x7632), sc.y);
            a[kk][1] = hmul2(__byte_perm(r[1], r[3], 0x5410), sc.x); a[kk][3] = hmul2(__byte_perm(r[1], r[3], 0x7632), sc.y);
          }
          if (!odd.value) {
            const float x = blo(zk[0]), y = bhi(zk[0]);
#pragma unroll
            for (int i = 0; i < 15; i++) zk[i] = zk[i + 1];
            zk[15] = pack2(fmaf(x, tanh_fast(x * fmaf(x, x, GB)), x), fmaf(y, tanh_fast(y * fmaf(y, y, GB)), y));
          }
          wgmma_fence();
#pragma unroll
          for (int i = 0; i < 8; i++) {
            const int kk = i & 3, hf = i >> 2;
            wgmma_rs_n144(acc + hf * 72, a[kk], db, 1);
            dadd(db, i == 3 ? 144u - 3 * 576 : 576 + P.zero);
            if (i == 0) { wgmma_commit(); wgmma_wait<1>(); release_if(kb, prev); }
            if (i == 3) wgmma_commit();
          }
          wgmma_commit();
          prev = c.s; c.next();
        };
        mbar_wait_c(bars + B_RT, L);
#pragma unroll 1
        for (int kb = 0; kb < 32; kb += 2) {
          if (kb == 8) mbar_wait_c(bars + B_RT1, L);
          stage(kb, Int<0>{});
          stage(kb + 1, Int<1>{});
        }
        if (w == 1) bar_arrive(6, 256);
        mbar_wait_c(bars + B_CV + w * 8, L);
        const float gk = 0.5f / GA;
        const float c1 = __uint_as_float(lds32(sb + SM_OFF + 4));
        const float gb0 = -gk * (c1 + __uint_as_float(lds32(sb + SM_CV + w * 256 + (16 * q + g) * 4))), gb1 = -gk * (c1 + __uint_as_float(lds32(sb + SM_CV + w * 256 + (16 * q + g + 8) * 4)));
        mbar_wait_c(w ? bars + B_FULL + c.s * 8 : bars + B_ZB, w ? c.ph : L);
        const uint32_t sx = c.s;
        c.next();
        const uint32_t zt = sb + tid * 16, zs = zt + sx * ST_BYTES + w * 24576;
        uint4 zz[18];
        auto zload = [&](int u) {
          if (ZW && u == ZW && P.zero) __nanosleep(0);
          if (u >= 12 && u < 16) zz[u] = make_uint4(zk[4 * u - 48], zk[4 * u - 47], zk[4 * u - 46], zk[4 * u - 45]); else zz[u] = lds128(u == 17 ? zt + SM_STG : zs + (u < 12 ? u : 12) * 2048);
        };
#pragma unroll
        for (int u = 0; u < ZA; u++) zload(u);
#pragma unroll
        for (int u = 0; u < 18; u++) {
          if (u == 0) { wgmma_wait<1>(); }
          if (u == 9) {
            wgmma_wait<0>();
            release(prev);
            mbar_arrive_if(L == 0 && lane == 0, ev + EV_P4 * 8);
          }
          if (u + ZA < 18) zload(u + ZA);
          const uint4 z = zz[u];
          hA[u][0] = hmul2(z.x, pack2(fmaf(acc[8 * u], gk, gb0), fmaf(acc[8 * u + 1], gk, gb0)));
          hA[u][1] = hmul2(z.y, pack2(fmaf(acc[8 * u + 2], gk, gb1), fmaf(acc[8 * u + 3], gk, gb1)));
          hA[u][2] = hmul2(z.z, pack2(fmaf(acc[8 * u + 4], gk, gb0), fmaf(acc[8 * u + 5], gk, gb0)));
          hA[u][3] = hmul2(z.w, pack2(fmaf(acc[8 * u + 6], gk, gb1), fmaf(acc[8 * u + 7], gk, gb1)));
        }
        uint32_t dep = P.zero;
#pragma unroll
        for (int u = 0; u < 18; u++) dep &= hA[u][0];
        release(sx, dep);
      }
      {
        const uint32_t el = elect_one();
#pragma unroll 1
        for (int p = 0; p < 9; p++) {
          float acc[32];
          if (w == 0) mbar_wait_c(bars + B_FULL + c.s * 8, c.ph);
          uint64_t db = dsc2(dlo(sb + c.s * ST_BYTES + ST_B + (j & 1) * 4096, 0), 0, 0x40000040u + P.zero);
          bar_sync(6 + w, 256);
          wgmma_fence();
#pragma unroll
          for (int kk = 0; kk < 18; kk++) {
            wgmma_rs_n64(acc, hA[kk], db, kk != 0);
            dadd(db, kk == 15 ? 128 - (j & 1) * (36864 >> 4) : 128 + P.zero);
            if (kk == PPK && (w == 0 || p < 8)) bar_arrive(7 - w, 256);
          }
          wgmma_commit();
          const uint32_t d = sb + (p & 3) * ST_BYTES, cb = p + j >= 9 ? p + j - 9 : p + j;
          if (el) asm volatile("cp.async.bulk.commit_group;\ncp.async.bulk.wait_group.read 3;" ::: "memory");
          __syncwarp();
          wgmma_wait<0>();
          release_if(L == 0 || p < 5, c.s);
          c.next();
#pragma unroll
          for (int u = 0; u < 4; u++)
            stsm4(d + (aoff ^ (u << 5)), pack2(acc[8 * u], acc[8 * u + 1]), pack2(acc[8 * u + 2], acc[8 * u + 3]), pack2(acc[8 * u + 4], acc[8 * u + 5]), pack2(acc[8 * u + 6], acc[8 * u + 7]));
          fence_async_s();
          __syncwarp();
          tma3d_red_p(el, &P.red[L], cb * 64, rb * 64 + q * 16, w, d + w * 8192 + q * 2048);
        }
        if (el) asm volatile("cp.async.bulk.commit_group;\ncp.async.bulk.wait_group 0;" ::: "memory");
        if (L == 0) signal(EV_PT);
      }
    }
  }
}

typedef CUresult (*EncodeFn)(CUtensorMap*, CUtensorMapDataType, cuuint32_t, void*, const cuuint64_t*, const cuuint64_t*, const cuuint32_t*,
                             const cuuint32_t*, CUtensorMapInterleave, CUtensorMapSwizzle, CUtensorMapL2promotion, CUtensorMapFloatOOBfill);

static void make_map(EncodeFn fn, CUtensorMap* m, const void* ptr, int rank, uint64_t d0, uint64_t d1, uint64_t d2, uint64_t s1, uint64_t s2,
                     uint32_t b0, uint32_t b1, uint32_t b2, CUtensorMapSwizzle swz) {
  cuuint64_t dims[3] = {d0, d1, d2}, strides[2] = {s1, s2};
  cuuint32_t box[3] = {b0, b1, b2}, es[3] = {1, 1, 1};
  fn(m, CU_TENSOR_MAP_DATA_TYPE_BFLOAT16, rank, const_cast<void*>(ptr), dims, strides, box, es, CU_TENSOR_MAP_INTERLEAVE_NONE, swz,
     CU_TENSOR_MAP_L2_PROMOTION_L2_128B, CU_TENSOR_MAP_FLOAT_OOB_FILL_NONE);
}

}

extern "C" void kernel_launch(void* const* d_in, const int* in_sizes, int n_in, void* d_out, int out_size) {
  using namespace mk;
  (void)in_sizes; (void)n_in; (void)out_size;
  static EncodeFn fn = nullptr;
  static Scratch* sc;
  if (!fn) {
    cudaGetSymbolAddress((void**)&sc, g_scratch);
    cudaDriverEntryPointQueryResult qr;
    cudaGetDriverEntryPoint("cuTensorMapEncodeTiled", (void**)&fn, cudaEnableDefault, &qr);
    cudaFuncSetAttribute(mega_kernel, cudaFuncAttributeMaxDynamicSharedMemorySize, SM_TOTAL);
  }
  Params p;
  p.wqkv = (const __nv_bfloat16*)d_in[1];
  p.w_in = (const __nv_bfloat16*)d_in[4];
  p.w_sp = (const __nv_bfloat16*)d_in[5];
  p.b_sp = (const __nv_bfloat16*)d_in[6];
  p.w_out = (const __nv_bfloat16*)d_in[7];
  p.zero = 0;
  p.s = sc;
  p.xs[0] = (uint8_t*)d_in[0];
  p.xs[1] = sc->X;
  p.xs[2] = (uint8_t*)d_out;
  make_map(fn, &p.wsp, p.w_sp, 3, 2048, 1024, 2, 8192, 4096, 64, 64, 2, CU_TENSOR_MAP_SWIZZLE_128B);
  for (int i = 0; i < 2; i++) {
    make_map(fn, &p.red[i], p.xs[i + 1], 3, DM, 1024, 2, 2304, 1152, 64, 16, 1, CU_TENSOR_MAP_SWIZZLE_128B);
    make_map(fn, &p.res[i], p.xs[i], 3, DM, 1024, 2, 2304, 1152, 144, 64, 1, CU_TENSOR_MAP_SWIZZLE_NONE);
  }
  make_map(fn, &p.psn, d_out, 3, DM, 1024, 2, 2304, 1152, 144, 4, 1, CU_TENSOR_MAP_SWIZZLE_NONE);
  for (int i = 0; i < 3; i++) make_map(fn, &p.act[i], p.xs[i], 3, DM, 1024, 2, 2304, 1152, 64, 64, 1, CU_TENSOR_MAP_SWIZZLE_128B);
  {
    cuuint64_t dims[4] = {8, 8, 72, 72}, strides[3] = {1152, 16, 9216};
    cuuint32_t box[4] = {8, 8, 9, 5}, es[4] = {1, 1, 1, 1};
    fn(&p.wo8, CU_TENSOR_MAP_DATA_TYPE_BFLOAT16, 4, d_in[2], dims, strides, box, es, CU_TENSOR_MAP_INTERLEAVE_NONE, CU_TENSOR_MAP_SWIZZLE_NONE,
       CU_TENSOR_MAP_L2_PROMOTION_L2_128B, CU_TENSOR_MAP_FLOAT_OOB_FILL_NONE);
  }
  for (int i = 0; i < 2; i++) {
    cuuint64_t dims[4] = {i ? 4608u : 2304u, 8, i ? 1u : 2u, 72}, strides[3] = {9216, 4608, 8 * 9216};
    cuuint32_t box[4] = {i ? 64u : 32u, 8, i ? 1u : 2u, 18}, es[4] = {1, 1, 1, 1};
    fn(i ? &p.win64 : &p.win, CU_TENSOR_MAP_DATA_TYPE_BFLOAT16, 4, d_in[4], dims, strides, box, es, CU_TENSOR_MAP_INTERLEAVE_NONE,
       i ? CU_TENSOR_MAP_SWIZZLE_128B : CU_TENSOR_MAP_SWIZZLE_64B, CU_TENSOR_MAP_L2_PROMOTION_L2_128B, CU_TENSOR_MAP_FLOAT_OOB_FILL_NONE);
  }
  make_map(fn, &p.wout, p.w_out, 2, 576, 2304, 1, 1152, 0, 64, 144, 1, CU_TENSOR_MAP_SWIZZLE_128B);
  mega_kernel<<<NGRID, 384, SM_TOTAL, cudaStreamPerThread>>>(p);
}
```

```cpp
#include <cuda_runtime.h>
#include <cuda.h>
#include <cuda_bf16.h>
#include <stdint.h>

#define LAG1 3
#define PP3 34
#define PP30 33
#define SPL 2
#define NAP 200
#define NAP0 8000
#define KS2 1
#define KS3 1
#define RL3 21
#define ZA 4
#define ZW 13
#define GA3 10
#define GB3 12
#define GM2 1
#define GMM 1
#define GM1 2
#define C0S 128.f
#define OFA 0.125f
#define OFK 2.f
#define PPK 16

namespace mk {

constexpr int SEQ = 2048, DM = 576, FH = 2304;
constexpr int NCTA = 128;
constexpr int NGRID = 132;
constexpr uint32_t ZB = 36864;
constexpr uint32_t WQ_SL = 72 * 3456;
constexpr uint32_t WO_SL = 72 * 1152;
constexpr float LN_EPS = 1e-5f;
constexpr float GA = 0.3292034911525734f, GB = 2.423681954311584f;

constexpr uint32_t ST_BYTES = 53248, ST_B = 16384, NST = 4;
constexpr uint32_t SM_STG = NST * ST_BYTES;
constexpr uint32_t SM_BAR = SM_STG + 2 * 9216;
constexpr uint32_t SM_OFF = SM_BAR + 1008;
constexpr uint32_t SM_TOTAL = SM_BAR + 1024;
constexpr uint32_t SM_RT = SM_STG + 4096, SM_CV = SM_STG + 12288, SM_WT = SM_CV + 512;
constexpr uint32_t SM_WOI = 44032, SM_CSQ = 49792, SM_XST = 50688;
constexpr uint32_t B_FULL = 0, B_EMPTY = 32, B_FULLA = 64, B_RES = 128, B_WT = 144, B_IMG = 160, B_WOI = 168, B_ZB = 176, B_GATE3 = 184, B_Z1 = 192, B_LAG = 200,
                   B_RT = 208, B_CSQ = 216, B_CV = 224, B_AD = 240, B_EVT = 272, B_RT1 = 368, B_XS = 624, B_XRW = 384, B_FA3 = 400, B_EA3 = 544;
enum { EV_PT = 0, EV_O = 1, EV_X1 = 2, EV_ZN = 3, EV_Z1 = 4, EV_P4 = 5, EV_N = 6 };

enum { FR_X2 = 0, FR_O = 1, FR_X1 = 3, FR_EP = 16, FJ = 32 * 32, FJ_WQ = 0, FJ_WO = 1, FJ_WQ0 = 2, FJ_ZN = 3, FJ_P4 = 5, FJ_EP = 16, F_N = FJ + 8 * 32 };

constexpr uint32_t POISON = 0xffffffffu;
struct Scratch {
  uint32_t flags[F_N];
  uint2 RT[SEQ];
  uint4 XST[2 * SEQ];
  uint4 ST1[SEQ * 8], ZST[SEQ * 8], HALO[32 * 8 * 6 * 32];
  float CSP[2 * NCTA * 216];
  uint8_t WQ[8 * WQ_SL], WO[8 * WO_SL];
  uint8_t O[32 * 2 * ZB];
  uint8_t X[SEQ * DM * 2];
  uint8_t Z[512 * ZB];
  uint4 RD[NCTA * 36 * 256];
};
__device__ __align__(1024) Scratch g_scratch;

struct Head {
  const __nv_bfloat16* wqkv;
  Scratch* s;
  uint32_t zero;
  uint8_t* xs[3];
};
struct Params {
  const __nv_bfloat16 *w_in, *w_sp, *b_sp, *w_out;
  CUtensorMap wo8, wsp, win, win64, wout;
  CUtensorMap act[3];
  CUtensorMap res[2];
  CUtensorMap red[2];
  CUtensorMap psn;
};

__device__ __forceinline__ uint32_t smem_u32(const void* p) { return (uint32_t)__cvta_generic_to_shared(p); }
__device__ __forceinline__ void mbar_init(uint32_t bar, uint32_t cnt) { asm volatile("mbarrier.init.shared::cta.b64 [%0], %1;" ::"r"(bar), "r"(cnt)); }
__device__ __forceinline__ void mbar_arrive(uint32_t bar) { asm volatile("mbarrier.arrive.shared::cta.b64 _, [%0];" ::"r"(bar) : "memory"); }
__device__ __forceinline__ void mbar_wait(uint32_t bar, uint32_t parity) {
  asm volatile(
      "{\n.reg .pred p;\n.reg .u32 c;\nmov.u32 c, 0;\nLAB_WAIT:\n"
      "mbarrier.try_wait.parity.shared::cta.b64 p, [%0], %1;\n@p bra LAB_DONE;\n"
      "add.u32 c, c, 1;\nsetp.lt.u32 p, c, 0x100000;\n@p bra LAB_WAIT;\ntrap;\nLAB_DONE:\n}" ::"r"(bar), "r"(parity)
      : "memory");
}
__device__ __forceinline__ void mbar_wait_c(uint32_t bar, uint32_t parity) {
  asm volatile("{\n.reg .pred p;\nLAB_WAIT:\nmbarrier.try_wait.parity.shared::cta.b64 p, [%0], %1;\n@!p bra LAB_WAIT;\n}" ::"r"(bar), "r"(parity) : "memory");
}
__device__ __forceinline__ void flag_wait(const uint32_t* f, uint32_t target) {
  asm volatile(
      "{\n.reg .pred p;\n.reg .u32 c, v;\nmov.u32 c, 0;\nLAB_WAIT:\n"
      "ld.relaxed.gpu.global.u32 v, [%0];\nsub.u32 v, v, %1;\nsetp.ge.s32 p, v, 0;\n@p bra LAB_DONE;\n"
      "add.u32 c, c, 1;\nsetp.lt.u32 p, c, 0x400000;\n@p bra LAB_WAIT;\ntrap;\nLAB_DONE:\nfence.acquire.gpu;\n}" ::"l"(f), "r"(target)
      : "memory");
}
__device__ __forceinline__ void fence_gpu() { asm volatile("fence.acq_rel.gpu;" ::: "memory"); }
__device__ __forceinline__ void fence_async_g() { asm volatile("fence.proxy.async.global;" ::: "memory"); }
__device__ __forceinline__ void fence_async_s() { asm volatile("fence.proxy.async.shared::cta;" ::: "memory"); }
__device__ __forceinline__ uint32_t elect_one() {
  uint32_t p; asm volatile("{\n.reg .pred P;\nelect.sync _|P, 0xffffffff;\nselp.u32 %0, 1, 0, P;\n}" : "=r"(p)); return p;
}
__device__ __forceinline__ void expect_tx_p(uint32_t el, uint32_t bar, uint32_t bytes) {
  asm volatile("{\n.reg .pred P;\nsetp.ne.u32 P, %2, 0;\n@P mbarrier.arrive.expect_tx.shared::cta.b64 _, [%0], %1;\n}" ::"r"(bar), "r"(bytes), "r"(el) : "memory");
}
__device__ __forceinline__ void bulk_load_p(uint32_t el, uint32_t dst, const void* src, uint32_t bytes, uint32_t bar) {
  asm volatile("{\n.reg .pred P;\nsetp.ne.u32 P, %4, 0;\n@P cp.async.bulk.shared::cluster.global.mbarrier::complete_tx::bytes [%0], [%1], %2, [%3];\n}" ::"r"(dst), "l"(src), "r"(bytes), "r"(bar), "r"(el) : "memory");
}
__device__ __forceinline__ uint64_t policy_evict_first() { uint64_t p; asm("createpolicy.fractional.L2::evict_first.b64 %0, 1.0;" : "=l"(p)); return p; }
__device__ __forceinline__ void bulk_load_h(uint32_t el, uint32_t dst, const void* src, uint32_t bytes, uint32_t bar, bool ef, uint64_t pol) {
  if (ef) {
    asm volatile("{\n.reg .pred P;\nsetp.ne.u32 P, %4, 0;\n@P cp.async.bulk.shared::cluster.global.mbarrier::complete_tx::bytes.L2::cache_hint [%0], [%1], %2, [%3], %5;\n}" ::"r"(dst), "l"(src), "r"(bytes), "r"(bar), "r"(el), "l"(pol) : "memory");
  } else {
    asm volatile("{\n.reg .pred P;\nsetp.ne.u32 P, %4, 0;\n@P cp.async.bulk.shared::cluster.global.mbarrier::complete_tx::bytes [%0], [%1], %2, [%3];\n}" ::"r"(dst), "l"(src), "r"(bytes), "r"(bar), "r"(el) : "memory");
  }
}
__device__ __forceinline__ void bulk_mc_h(uint32_t el, uint32_t dst, const void* src, uint32_t bytes, uint32_t bar, bool ef, uint64_t pol) {
  if (ef) {
    asm volatile("{\n.reg .pred P;\nsetp.ne.u32 P, %4, 0;\n@P cp.async.bulk.shared::cluster.global.mbarrier::complete_tx::bytes.multicast::cluster.L2::cache_hint [%0], [%1], %2, [%3], %5, %6;\n}" ::"r"(dst), "l"(src), "r"(bytes), "r"(bar), "r"(el), "h"((uint16_t)3), "l"(pol) : "memory");
  } else {
    asm volatile("{\n.reg .pred P;\nsetp.ne.u32 P, %4, 0;\n@P cp.async.bulk.shared::cluster.global.mbarrier::complete_tx::bytes.multicast::cluster [%0], [%1], %2, [%3], %5;\n}" ::"r"(dst), "l"(src), "r"(bytes), "r"(bar), "r"(el), "h"((uint16_t)3) : "memory");
  }
}
__device__ __forceinline__ void tma3d_h(uint32_t el, uint32_t dst, const CUtensorMap* m, int c0, int c1, int c2, uint32_t bar, bool ef, uint64_t pol) {
  if (ef) {
    asm volatile("{\n.reg .pred P;\nsetp.ne.u32 P, %6, 0;\n@P cp.async.bulk.tensor.3d.shared::cluster.global.mbarrier::complete_tx::bytes.L2::cache_hint [%0], [%1, {%3, %4, %5}], [%2], %7;\n}" ::"r"(dst), "l"(m), "r"(bar), "r"(c0), "r"(c1), "r"(c2), "r"(el), "l"(pol) : "memory");
  } else {
    asm volatile("{\n.reg .pred P;\nsetp.ne.u32 P, %6, 0;\n@P cp.async.bulk.tensor.3d.shared::cluster.global.mbarrier::complete_tx::bytes [%0], [%1, {%3, %4, %5}], [%2];\n}" ::"r"(dst), "l"(m), "r"(bar), "r"(c0), "r"(c1), "r"(c2), "r"(el) : "memory");
  }
}
__device__ __forceinline__ void tma2d_mc_h(uint32_t el, uint32_t dst, const CUtensorMap* m, int c0, int c1, uint32_t bar, bool ef, uint64_t pol) {
  if (ef) {
    asm volatile("{\n.reg .pred P;\nsetp.ne.u32 P, %5, 0;\n@P cp.async.bulk.tensor.2d.shared::cluster.global.mbarrier::complete_tx::bytes.multicast::cluster.L2::cache_hint [%0], [%1, {%3, %4}], [%2], %6, %7;\n}" ::"r"(dst), "l"(m), "r"(bar), "r"(c0), "r"(c1), "r"(el), "h"((uint16_t)3), "l"(pol) : "memory");
  } else {
    asm volatile("{\n.reg .pred P;\nsetp.ne.u32 P, %5, 0;\n@P cp.async.bulk.tensor.2d.shared::cluster.global.mbarrier::complete_tx::bytes.multicast::cluster [%0], [%1, {%3, %4}], [%2], %6;\n}" ::"r"(dst), "l"(m), "r"(bar), "r"(c0), "r"(c1), "r"(el), "h"((uint16_t)3) : "memory");
  }
}
__device__ __forceinline__ void tma4d_mc(uint32_t el, uint32_t dst, const CUtensorMap* m, int c0, int c3, uint32_t bar, uint64_t pol) {
  asm volatile("{\n.reg .pred P;\nsetp.ne.u32 P, %5, 0;\n@P cp.async.bulk.tensor.4d.shared::cluster.global.mbarrier::complete_tx::bytes.multicast::cluster.L2::cache_hint [%0], [%1, {%3, 0, 0, %4}], [%2], %6, %7;\n}" ::"r"(dst), "l"(m), "r"(bar), "r"(c0), "r"(c3), "r"(el), "h"((uint16_t)3), "l"(pol) : "memory");
}
__device__ __forceinline__ void mbar_arrive_cluster_if(bool c, uint32_t addr) {
  asm volatile("{\n.reg .pred P;\nsetp.ne.u32 P, %1, 0;\n@P mbarrier.arrive.shared::cluster.b64 _, [%0];\n}" ::"r"(addr), "r"((uint32_t)c) : "memory");
}
__device__ __forceinline__ void mbar_arrive_if(bool c, uint32_t addr) {
  asm volatile("{\n.reg .pred P;\nsetp.ne.u32 P, %1, 0;\n@P mbarrier.arrive.shared::cta.b64 _, [%0];\n}" ::"r"(addr), "r"((uint32_t)c) : "memory");
}
__device__ __forceinline__ uint32_t mapa(uint32_t addr, uint32_t rank) { uint32_t r; asm("mapa.shared::cluster.u32 %0, %1, %2;" : "=r"(r) : "r"(addr), "r"(rank)); return r; }
__device__ __forceinline__ void bulk_store_p(uint32_t el, void* dst, uint32_t src, uint32_t bytes) {
  asm volatile("{\n.reg .pred P;\nsetp.ne.u32 P, %3, 0;\n@P cp.async.bulk.global.shared::cta.bulk_group [%0], [%1], %2;\n}" ::"l"(dst), "r"(src), "r"(bytes), "r"(el) : "memory");
}
__device__ __forceinline__ void flag_release_p(uint32_t el, uint32_t* f) {
  asm volatile("{\n.reg .pred P;\nsetp.ne.u32 P, %1, 0;\n@P red.release.gpu.global.add.u32 [%0], 1;\n}" ::"l"(f), "r"(el) : "memory");
}
__device__ __forceinline__ void flag_add_p(uint32_t el, uint32_t* f) {
  asm volatile("{\n.reg .pred P;\nsetp.ne.u32 P, %1, 0;\n@P red.relaxed.gpu.global.add.u32 [%0], 1;\n}" ::"l"(f), "r"(el) : "memory");
}
__device__ __forceinline__ void prefetch_l2(const void* src, uint32_t bytes) { asm volatile("cp.async.bulk.prefetch.L2.global [%0], %1;" ::"l"(src), "r"(bytes) : "memory"); }
__device__ __forceinline__ void prefetch_map(const CUtensorMap* m) { asm volatile("prefetch.tensormap [%0];" ::"l"(m) : "memory"); }
__device__ __forceinline__ void wgmma_fence() { asm volatile("wgmma.fence.sync.aligned;" ::: "memory"); }
__device__ __forceinline__ void wgmma_commit() { asm volatile("wgmma.commit_group.sync.aligned;" ::: "memory"); }
template <int N> __device__ __forceinline__ void wgmma_wait() { asm volatile("wgmma.wait_group.sync.aligned %0;" ::"n"(N) : "memory"); }
__device__ __forceinline__ uint32_t dlo(uint32_t addr, uint32_t lbo) { return ((addr & 0x3FFFF) >> 4) + ((lbo >> 4) << 16); }
__device__ __forceinline__ uint64_t dsc2(uint32_t lo, uint32_t off, uint32_t hi) {
  uint64_t d; asm("mov.b64 %0, {%1, %2};" : "=l"(d) : "r"(lo + (off >> 4)), "r"(hi)); return d;
}
__device__ __forceinline__ uint64_t dat(uint64_t d, uint32_t off, uint32_t one) { uint64_t r; asm("mad.wide.u32 %0, %1, %2, %3;" : "=l"(r) : "r"(one), "r"(off >> 4), "l"(d)); return r; }
__device__ __forceinline__ void dadd(uint64_t& d, uint32_t v) {
  asm("{\n.reg .b32 lo, hi;\nmov.b64 {lo, hi}, %0;\nadd.u32 lo, lo, %1;\nmov.b64 %0, {lo, hi};\n}" : "+l"(d) : "r"(v));
}
template <int R> __device__ __forceinline__ void reg_alloc() { asm volatile("setmaxnreg.inc.sync.aligned.u32 %0;" ::"n"(R)); }
template <int R> __device__ __forceinline__ void reg_dealloc() { asm volatile("setmaxnreg.dec.sync.aligned.u32 %0;" ::"n"(R)); }
__device__ __forceinline__ void bar_sync(int id, int n) { asm volatile("bar.sync %0, %1;" ::"r"(id), "r"(n) : "memory"); }
__device__ __forceinline__ void bar_arrive(int id, int n) { asm volatile("bar.arrive %0, %1;" ::"r"(id), "r"(n) : "memory"); }
__device__ __forceinline__ void ldsm4(uint32_t* r, uint32_t addr) {
  asm volatile("ldmatrix.sync.aligned.m8n8.x4.shared.b16 {%0,%1,%2,%3}, [%4];" : "=r"(r[0]), "=r"(r[1]), "=r"(r[2]), "=r"(r[3]) : "r"(addr) : "memory");
}
__device__ __forceinline__ uint32_t movm(uint32_t a) { uint32_t d; asm volatile("movmatrix.sync.aligned.m8n8.trans.b16 %0, %1;" : "=r"(d) : "r"(a)); return d; }
__device__ __forceinline__ void mma16(float* c, uint32_t a0, uint32_t a1, uint32_t a2, uint32_t a3, uint32_t b0, uint32_t b1) {
  asm volatile("mma.sync.aligned.m16n8k16.row.col.f32.bf16.bf16.f32 {%0,%1,%2,%3}, {%4,%5,%6,%7}, {%8,%9}, {%10,%10,%10,%10};"
               : "=f"(c[0]), "=f"(c[1]), "=f"(c[2]), "=f"(c[3]) : "r"(a0), "r"(a1), "r"(a2), "r"(a3), "r"(b0), "r"(b1), "f"(0.f));
}
__device__ __forceinline__ void mma8(float* c, uint32_t a0, uint32_t a1, uint32_t b0) {
  asm volatile("mma.sync.aligned.m16n8k8.row.col.f32.bf16.bf16.f32 {%0,%1,%2,%3}, {%4,%5}, {%6}, {%0,%1,%2,%3};"
               : "+f"(c[0]), "+f"(c[1]), "+f"(c[2]), "+f"(c[3]) : "r"(a0), "r"(a1), "r"(b0));
}
__device__ __forceinline__ void widen(float* c, uint32_t a0, uint32_t a1, uint32_t eye) {
  asm volatile("mma.sync.aligned.m16n8k8.row.col.f32.bf16.bf16.f32 {%0,%1,%2,%3}, {%4,%5}, {%6}, {%7,%7,%7,%7};"
               : "=f"(c[0]), "=f"(c[1]), "=f"(c[2]), "=f"(c[3]) : "r"(a0), "r"(a1), "r"(eye), "f"(0.f));
}
__device__ __forceinline__ float rsq_fast(float x) { float y; asm("rsqrt.approx.ftz.f32 %0, %1;" : "=f"(y) : "f"(x)); return y; }
__device__ __forceinline__ uint32_t pack2(float lo, float hi) { uint32_t r; asm("cvt.rn.bf16x2.f32 %0, %1, %2;" : "=r"(r) : "f"(hi), "f"(lo)); return r; }
__device__ __forceinline__ float blo(uint32_t v) { return __uint_as_float(v << 16); }
__device__ __forceinline__ float bhi(uint32_t v) { return __uint_as_float(v & 0xffff0000u); }
__device__ __forceinline__ float tanh_fast(float x) { float y; asm("tanh.approx.f32 %0, %1;" : "=f"(y) : "f"(x)); return y; }
__device__ __forceinline__ float rcp_fast(float x) { float y; asm("rcp.approx.ftz.f32 %0, %1;" : "=f"(y) : "f"(x)); return y; }
__device__ __forceinline__ float ex2(float x) { float y; asm("ex2.approx.ftz.f32 %0, %1;" : "=f"(y) : "f"(x)); return y; }
__device__ __forceinline__ float qsum(float v) { v += __shfl_xor_sync(~0u, v, 1); v += __shfl_xor_sync(~0u, v, 2); return v; }
__device__ __forceinline__ float qmax(float v) { v = fmaxf(v, __shfl_xor_sync(~0u, v, 1)); v = fmaxf(v, __shfl_xor_sync(~0u, v, 2)); return v; }
__device__ __forceinline__ void stg32(void* p, uint32_t v) { asm volatile("st.global.u32 [%0], %1;" ::"l"(p), "r"(v) : "memory"); }
__device__ __forceinline__ void stg128(void* p, uint32_t a, uint32_t b, uint32_t c, uint32_t d) { asm volatile("st.global.v4.u32 [%0], {%1,%2,%3,%4};" ::"l"(p), "r"(a), "r"(b), "r"(c), "r"(d) : "memory"); }
__device__ __forceinline__ uint32_t ldcg32(const void* p) { uint32_t v; asm volatile("ld.global.L1::no_allocate.u32 %0, [%1];" : "=r"(v) : "l"(p) : "memory"); return v; }
__device__ __forceinline__ uint32_t ldgpu32(const void* p) { uint32_t v; asm volatile("ld.relaxed.gpu.global.u32 %0, [%1];" : "=r"(v) : "l"(p) : "memory"); return v; }
__device__ __forceinline__ uint32_t ldca32(const void* p) { uint32_t v; asm volatile("ld.global.ca.u32 %0, [%1];" : "=r"(v) : "l"(p) : "memory"); return v; }
__device__ __forceinline__ void stg128_if(bool c, void* p, uint32_t a, uint32_t b, uint32_t cc, uint32_t d) {
  asm volatile("{\n.reg .pred P;\nsetp.ne.u32 P, %5, 0;\n@P st.global.v4.u32 [%0], {%1,%2,%3,%4};\n}" ::"l"(p), "r"(a), "r"(b), "r"(cc), "r"(d), "r"((uint32_t)c) : "memory");
}
__device__ __forceinline__ uint2 lds64(uint32_t a) { uint2 v; asm volatile("ld.shared.v2.u32 {%0,%1}, [%2];" : "=r"(v.x), "=r"(v.y) : "r"(a) : "memory"); return v; }
__device__ __forceinline__ uint4 ldcg128(const void* p) { uint4 v; asm volatile("ld.global.cg.v4.u32 {%0,%1,%2,%3}, [%4];" : "=r"(v.x), "=r"(v.y), "=r"(v.z), "=r"(v.w) : "l"(p) : "memory"); return v; }
__device__ __forceinline__ uint32_t ldnc16(const void* p) { uint16_t v; asm volatile("ld.global.nc.u16 %0, [%1];" : "=h"(v) : "l"(p)); return v; }
__device__ __forceinline__ uint4 ldnc128(const void* p) { uint4 v; asm volatile("ld.global.nc.v4.u32 {%0,%1,%2,%3}, [%4];" : "=r"(v.x), "=r"(v.y), "=r"(v.z), "=r"(v.w) : "l"(p)); return v; }
__device__ __forceinline__ uint32_t hsub2(uint32_t a, uint32_t b) { uint32_t d; asm("sub.rn.bf16x2 %0, %1, %2;" : "=r"(d) : "r"(a), "r"(b)); return d; }
__device__ __forceinline__ void stg32_if(bool c, void* p, uint32_t v) {
  asm volatile("{\n.reg .pred P;\nsetp.ne.u32 P, %2, 0;\n@P st.global.u32 [%0], %1;\n}" ::"l"(p), "r"(v), "r"((uint32_t)c) : "memory");
}
__device__ __forceinline__ uint32_t hmul2(uint32_t a, uint32_t b) { uint32_t d; asm("mul.rn.bf16x2 %0, %1, %2;" : "=r"(d) : "r"(a), "r"(b)); return d; }
__device__ __forceinline__ void sts32(uint32_t a, uint32_t v) { asm volatile("st.shared.u32 [%0], %1;" ::"r"(a), "r"(v) : "memory"); }
__device__ __forceinline__ uint32_t lds32(uint32_t a) { uint32_t v; asm volatile("ld.shared.u32 %0, [%1];" : "=r"(v) : "r"(a) : "memory"); return v; }
__device__ __forceinline__ void sts128(uint32_t a, uint32_t x, uint32_t y, uint32_t z, uint32_t w) { asm volatile("st.shared.v4.u32 [%0], {%1,%2,%3,%4};" ::"r"(a), "r"(x), "r"(y), "r"(z), "r"(w) : "memory"); }
__device__ __forceinline__ uint4 lds128(uint32_t a) { uint4 v; asm volatile("ld.shared.v4.u32 {%0,%1,%2,%3}, [%4];" : "=r"(v.x), "=r"(v.y), "=r"(v.z), "=r"(v.w) : "r"(a) : "memory"); return v; }
__device__ __forceinline__ void ll_st64(uint2* p, uint32_t v, uint32_t tag) {
  asm volatile("{\n.reg .b64 r;\nmov.b64 r, {%1,%2};\nst.relaxed.gpu.global.b64 [%0], r;\n}" ::"l"(p), "r"(v), "r"(tag) : "memory");
}
__device__ __forceinline__ uint2 ll_ld64(const uint2* p) {
  uint2 v; asm volatile("{\n.reg .b64 r;\nld.relaxed.gpu.global.b64 r, [%2];\nmov.b64 {%0,%1}, r;\n}" : "=r"(v.x), "=r"(v.y) : "l"(p) : "memory"); return v;
}
__device__ __forceinline__ void ll_st128(uint4* p, float a, float b, uint32_t tag, float c = 0.f) {
  asm volatile("{\n.reg .b128 r;\n.reg .b64 lo, hi;\nmov.b64 lo, {%1,%2};\nmov.b64 hi, {%3,%4};\nmov.b128 r, {lo, hi};\nst.relaxed.gpu.global.b128 [%0], r;\n}" ::"l"(p), "r"(__float_as_uint(a)), "r"(__float_as_uint(b)), "r"(tag), "r"(__float_as_uint(c)) : "memory");
}
__device__ __forceinline__ uint4 ll_ld128(const uint4* p) {
  uint4 v; asm volatile("{\n.reg .b128 r;\n.reg .b64 lo, hi;\nld.relaxed.gpu.global.b128 r, [%4];\nmov.b128 {lo, hi}, r;\nmov.b64 {%0,%1}, lo;\nmov.b64 {%2,%3}, hi;\n}" : "=r"(v.x), "=r"(v.y), "=r"(v.z), "=r"(v.w) : "l"(p) : "memory"); return v;
}
__device__ __forceinline__ void publish_p(uint32_t el, uint32_t* f) {
  asm volatile("{\n.reg .pred P;\nsetp.ne.u32 P, %1, 0;\n@P cp.async.bulk.commit_group;\n@P cp.async.bulk.wait_group 0;\n@P red.release.gpu.global.add.u32 [%0], 1;\n}" ::"l"(f), "r"(el) : "memory");
}
__device__ __forceinline__ void tma3d_red_p(uint32_t el, const CUtensorMap* m, int c0, int c1, int c2, uint32_t src) {
  asm volatile("{\n.reg .pred P;\nsetp.ne.u32 P, %5, 0;\n@P cp.reduce.async.bulk.tensor.3d.global.shared::cta.add.tile.bulk_group [%0, {%2, %3, %4}], [%1];\n}" ::"l"(m), "r"(src), "r"(c0), "r"(c1), "r"(c2), "r"(el) : "memory");
}
__device__ __forceinline__ void stsm4(uint32_t addr, uint32_t a, uint32_t b, uint32_t c, uint32_t d) {
  asm volatile("stmatrix.sync.aligned.m8n8.x4.shared.b16 [%0], {%1,%2,%3,%4};" ::"r"(addr), "r"(a), "r"(b), "r"(c), "r"(d) : "memory");
}
__device__ __forceinline__ void sts64(uint32_t a, uint32_t x, uint32_t y) { asm volatile("st.shared.v2.u32 [%0], {%1,%2};" ::"r"(a), "r"(x), "r"(y) : "memory"); }
__device__ __forceinline__ void ll_st128_if(bool on, uint4* p, float a, float b, uint32_t tag) {
  asm volatile("{\n.reg .pred P;\n.reg .b128 r;\n.reg .b64 lo, hi;\nsetp.ne.u32 P, %4, 0;\nmov.b64 lo, {%1,%2};\nmov.b64 hi, {%3,%3};\nmov.b128 r, {lo, hi};\n@P st.relaxed.gpu.global.b128 [%0], r;\n}" ::"l"(p), "r"(__float_as_uint(a)), "r"(__float_as_uint(b)), "r"(tag), "r"((uint32_t)on) : "memory");
}
__device__ __forceinline__ uint4 ldnc128_if(bool c, const void* p) {
  uint4 v = make_uint4(0u, 0u, 0u, 0u);
  asm volatile("{\n.reg .pred P;\nsetp.ne.u32 P, %5, 0;\n@P ld.global.nc.v4.u32 {%0,%1,%2,%3}, [%4];\n}" : "+r"(v.x), "+r"(v.y), "+r"(v.z), "+r"(v.w) : "l"(p), "r"((uint32_t)c));
  return v;
}
__device__ __forceinline__ uint32_t hfma2(uint32_t a, uint32_t b, uint32_t c) { uint32_t d; asm("fma.rn.bf16x2 %0, %1, %2, %3;" : "=r"(d) : "r"(a), "r"(b), "r"(c)); return d; }
__device__ __forceinline__ float2 lds64f(uint32_t a) { float2 v; asm volatile("ld.shared.v2.f32 {%0,%1}, [%2];" : "=f"(v.x), "=f"(v.y) : "r"(a) : "memory"); return v; }

__device__ __forceinline__ void wgmma_ss_n216(float* d, uint64_t da, uint64_t db, int scaleD) {
  asm volatile("{\n.reg .pred p;\nsetp.ne.b32 p, %110, 0;\nwgmma.mma_async.sync.aligned.m64n216k16.f32.bf16.bf16 "
    "{%0,%1,%2,%3,%4,%5,%6,%7,%8,%9,%10,%11,%12,%13,%14,%15,%16,%17,%18,%19,%20,%21,%22,%23,%24,%25,%26,%27,%28,%29,%30,%31,%32,%33,%34,%35,%36,%37,%38,%39,%40,%41,%42,%43,%44,%45,%46,%47,%48,%49,%50,%51,%52,%53,%54,%55,%56,%57,%58,%59,%60,%61,%62,%63,%64,%65,%66,%67,%68,%69,%70,%71,%72,%73,%74,%75,%76,%77,%78,%79,%80,%81,%82,%83,%84,%85,%86,%87,%88,%89,%90,%91,%92,%93,%94,%95,%96,%97,%98,%99,%100,%101,%102,%103,%104,%105,%106,%107}, "
    "%108, %109, p, 1, 1, 0, 1;\n}\n"
    : "+f"(d[0]), "+f"(d[1]), "+f"(d[2]), "+f"(d[3]), "+f"(d[4]), "+f"(d[5]), "+f"(d[6]), "+f"(d[7]), "+f"(d[8]), "+f"(d[9]), "+f"(d[10]), "+f"(d[11]), "+f"(d[12]), "+f"(d[13]), "+f"(d[14]), "+f"(d[15]), "+f"(d[16]), "+f"(d[17]), "+f"(d[18]), "+f"(d[19]), "+f"(d[20]), "+f"(d[21]), "+f"(d[22]), "+f"(d[23]), "+f"(d[24]), "+f"(d[25]), "+f"(d[26]), "+f"(d[27]), "+f"(d[28]), "+f"(d[29]), "+f"(d[30]), "+f"(d[31]), "+f"(d[32]), "+f"(d[33]), "+f"(d[34]), "+f"(d[35]), "+f"(d[36]), "+f"(d[37]), "+f"(d[38]), "+f"(d[39]), "+f"(d[40]), "+f"(d[41]), "+f"(d[42]), "+f"(d[43]), "+f"(d[44]), "+f"(d[45]), "+f"(d[46]), "+f"(d[47]), "+f"(d[48]), "+f"(d[49]), "+f"(d[50]), "+f"(d[51]), "+f"(d[52]), "+f"(d[53]), "+f"(d[54]), "+f"(d[55]), "+f"(d[56]), "+f"(d[57]), "+f"(d[58]), "+f"(d[59]), "+f"(d[60]), "+f"(d[61]), "+f"(d[62]), "+f"(d[63]), "+f"(d[64]), "+f"(d[65]), "+f"(d[66]), "+f"(d[67]), "+f"(d[68]), "+f"(d[69]), "+f"(d[70]), "+f"(d[71]), "+f"(d[72]), "+f"(d[73]), "+f"(d[74]), "+f"(d[75]), "+f"(d[76]), "+f"(d[77]), "+f"(d[78]), "+f"(d[79]), "+f"(d[80]), "+f"(d[81]), "+f"(d[82]), "+f"(d[83]), "+f"(d[84]), "+f"(d[85]), "+f"(d[86]), "+f"(d[87]), "+f"(d[88]), "+f"(d[89]), "+f"(d[90]), "+f"(d[91]), "+f"(d[92]), "+f"(d[93]), "+f"(d[94]), "+f"(d[95]), "+f"(d[96]), "+f"(d[97]), "+f"(d[98]), "+f"(d[99]), "+f"(d[100]), "+f"(d[101]), "+f"(d[102]), "+f"(d[103]), "+f"(d[104]), "+f"(d[105]), "+f"(d[106]), "+f"(d[107])
    : "l"(da), "l"(db), "r"(scaleD));
}
__device__ __forceinline__ void wgmma_ss_n72(float* d, uint64_t da, uint64_t db, int scaleD) {
  asm volatile("{\n.reg .pred p;\nsetp.ne.b32 p, %38, 0;\nwgmma.mma_async.sync.aligned.m64n72k16.f32.bf16.bf16 "
    "{%0,%1,%2,%3,%4,%5,%6,%7,%8,%9,%10,%11,%12,%13,%14,%15,%16,%17,%18,%19,%20,%21,%22,%23,%24,%25,%26,%27,%28,%29,%30,%31,%32,%33,%34,%35}, "
    "%36, %37, p, 1, 1, 0, 1;\n}\n"
    : "+f"(d[0]), "+f"(d[1]), "+f"(d[2]), "+f"(d[3]), "+f"(d[4]), "+f"(d[5]), "+f"(d[6]), "+f"(d[7]), "+f"(d[8]), "+f"(d[9]), "+f"(d[10]), "+f"(d[11]), "+f"(d[12]), "+f"(d[13]), "+f"(d[14]), "+f"(d[15]), "+f"(d[16]), "+f"(d[17]), "+f"(d[18]), "+f"(d[19]), "+f"(d[20]), "+f"(d[21]), "+f"(d[22]), "+f"(d[23]), "+f"(d[24]), "+f"(d[25]), "+f"(d[26]), "+f"(d[27]), "+f"(d[28]), "+f"(d[29]), "+f"(d[30]), "+f"(d[31]), "+f"(d[32]), "+f"(d[33]), "+f"(d[34]), "+f"(d[35])
    : "l"(da), "l"(db), "r"(scaleD));
}
__device__ __forceinline__ void wgmma_rs_n144(float* d, const uint32_t* a, uint64_t db, int scaleD) {
  asm volatile("{\n.reg .pred p;\nsetp.ne.b32 p, %77, 0;\nwgmma.mma_async.sync.aligned.m64n144k16.f32.bf16.bf16 "
    "{%0,%1,%2,%3,%4,%5,%6,%7,%8,%9,%10,%11,%12,%13,%14,%15,%16,%17,%18,%19,%20,%21,%22,%23,%24,%25,%26,%27,%28,%29,%30,%31,%32,%33,%34,%35,%36,%37,%38,%39,%40,%41,%42,%43,%44,%45,%46,%47,%48,%49,%50,%51,%52,%53,%54,%55,%56,%57,%58,%59,%60,%61,%62,%63,%64,%65,%66,%67,%68,%69,%70,%71}, "
    "{%72,%73,%74,%75}, %76, p, 1, 1, 1;\n}\n"
    : "+f"(d[0]), "+f"(d[1]), "+f"(d[2]), "+f"(d[3]), "+f"(d[4]), "+f"(d[5]), "+f"(d[6]), "+f"(d[7]), "+f"(d[8]), "+f"(d[9]), "+f"(d[10]), "+f"(d[11]), "+f"(d[12]), "+f"(d[13]), "+f"(d[14]), "+f"(d[15]), "+f"(d[16]), "+f"(d[17]), "+f"(d[18]), "+f"(d[19]), "+f"(d[20]), "+f"(d[21]), "+f"(d[22]), "+f"(d[23]), "+f"(d[24]), "+f"(d[25]), "+f"(d[26]), "+f"(d[27]), "+f"(d[28]), "+f"(d[29]), "+f"(d[30]), "+f"(d[31]), "+f"(d[32]), "+f"(d[33]), "+f"(d[34]), "+f"(d[35]), "+f"(d[36]), "+f"(d[37]), "+f"(d[38]), "+f"(d[39]), "+f"(d[40]), "+f"(d[41]), "+f"(d[42]), "+f"(d[43]), "+f"(d[44]), "+f"(d[45]), "+f"(d[46]), "+f"(d[47]), "+f"(d[48]), "+f"(d[49]), "+f"(d[50]), "+f"(d[51]), "+f"(d[52]), "+f"(d[53]), "+f"(d[54]), "+f"(d[55]), "+f"(d[56]), "+f"(d[57]), "+f"(d[58]), "+f"(d[59]), "+f"(d[60]), "+f"(d[61]), "+f"(d[62]), "+f"(d[63]), "+f"(d[64]), "+f"(d[65]), "+f"(d[66]), "+f"(d[67]), "+f"(d[68]), "+f"(d[69]), "+f"(d[70]), "+f"(d[71])
    : "r"(a[0]), "r"(a[1]), "r"(a[2]), "r"(a[3]), "l"(db), "r"(scaleD));
}
__device__ __forceinline__ void wgmma_rs_n64(float* d, const uint32_t* a, uint64_t db, int scaleD) {
  asm volatile("{\n.reg .pred p;\nsetp.ne.b32 p, %37, 0;\nwgmma.mma_async.sync.aligned.m64n64k16.f32.bf16.bf16 "
    "{%0,%1,%2,%3,%4,%5,%6,%7,%8,%9,%10,%11,%12,%13,%14,%15,%16,%17,%18,%19,%20,%21,%22,%23,%24,%25,%26,%27,%28,%29,%30,%31}, "
    "{%32,%33,%34,%35}, %36, p, 1, 1, 1;\n}\n"
    : "+f"(d[0]), "+f"(d[1]), "+f"(d[2]), "+f"(d[3]), "+f"(d[4]), "+f"(d[5]), "+f"(d[6]), "+f"(d[7]), "+f"(d[8]), "+f"(d[9]), "+f"(d[10]), "+f"(d[11]), "+f"(d[12]), "+f"(d[13]), "+f"(d[14]), "+f"(d[15]), "+f"(d[16]), "+f"(d[17]), "+f"(d[18]), "+f"(d[19]), "+f"(d[20]), "+f"(d[21]), "+f"(d[22]), "+f"(d[23]), "+f"(d[24]), "+f"(d[25]), "+f"(d[26]), "+f"(d[27]), "+f"(d[28]), "+f"(d[29]), "+f"(d[30]), "+f"(d[31])
    : "r"(a[0]), "r"(a[1]), "r"(a[2]), "r"(a[3]), "l"(db), "r"(scaleD));
}

template <int V> struct Int { static constexpr int value = V; };
struct Cur {
  uint32_t s, ph;
  __device__ __forceinline__ void next() { if (++s == NST) { s = 0; ph ^= 1; } }
};

#define z1_block(rb, w, j) (Q.s->Z + ((rb) * 16 + (w) * 8 + (j)) * ZB)
#define z2_block(kb, j) (Q.s->Z + (256 + (kb) * 8 + (j)) * ZB)
#define o_block(rb, w) (Q.s->O + ((rb) * 2 + (w)) * (2 * ZB))
__device__ __forceinline__ void combine8(float m0, float q0, float m1, float q1, float n, float eps, float& mean, float& rstd) {
  mean = qsum(m0 + m1) * 0.125f;
  float d0 = m0 - mean, d1 = m1 - mean;
  float M2 = qsum(q0 + q1 + n * (d0 * d0 + d1 * d1));
  rstd = rsq_fast(fmaf(M2, 0.125f / n, eps));
}
__device__ __forceinline__ void stat_get(const uint4* zs, uint32_t tag, float n, float eps, float& m0, float& r0, float& m1, float& r1) {
  uint4 a0, a1, b0, b1;
#pragma unroll 1
  for (int it = 0; it < (1 << 20); it++) {
    a0 = ll_ld128(zs); a1 = ll_ld128(zs + 64); b0 = ll_ld128(zs + 8); b1 = ll_ld128(zs + 72);
    if (__all_sync(~0u, a0.z == tag && a1.z == tag && b0.z == tag && b1.z == tag)) break;
  }
  combine8(__uint_as_float(a0.x), __uint_as_float(a0.y), __uint_as_float(a1.x), __uint_as_float(a1.y), n, eps, m0, r0);
  combine8(__uint_as_float(b0.x), __uint_as_float(b0.y), __uint_as_float(b1.x), __uint_as_float(b1.y), n, eps, m1, r1);
}

__device__ __forceinline__ void rows_fetch(uint32_t el, uint32_t xr, const uint8_t* src, uint32_t bar) {
  expect_tx_p(el, bar, 9216);
#pragma unroll 1
  for (int r = 0; r < 8; r++) bulk_load_p(el, xr + r * 1152, src + r * (DM * 4), 1152, bar);
}
__device__ __forceinline__ void rows_stats(uint32_t xr, uint4* dst, uint32_t tag, int lane) {
  float s[2] = {0.f, 0.f}, q[4] = {0.f, 0.f, 0.f, 0.f};
  const uint32_t a0 = xr + (lane >> 2) * 1152 + (((lane & 3) * 2) ^ (lane >> 2)) * 16;
  uint4 n0 = lds128(a0), n1 = lds128(a0 ^ 16);
#pragma unroll 1
  for (int e = 1; e <= 9; e++) {
    const uint32_t x[8] = {n0.x, n0.y, n0.z, n0.w, n1.x, n1.y, n1.z, n1.w};
    if (e < 9) { n0 = lds128(a0 + e * 128); n1 = lds128((a0 ^ 16) + e * 128); }
#pragma unroll
    for (int u = 0; u < 8; u++) {
      const float lo = blo(x[u]), hi = bhi(x[u]);
      s[u & 1] += lo + hi; q[(u & 1) * 2] = fmaf(lo, lo, q[(u & 1) * 2]); q[(u & 1) * 2 + 1] = fmaf(hi, hi, q[(u & 1) * 2 + 1]);
    }
  }
  const float sx = s[0] + s[1], sq = (q[0] + q[1]) + (q[2] + q[3]);
  const float m = qsum(sx) * (-1.f / DM), r = rsq_fast(fmaxf(fmaf(qsum(sq), 1.f / DM, -m * m), 0.f) + LN_EPS);
  if ((lane & 3) == 0) ll_st128(dst + (lane >> 2) * 2, m, r, tag);
}

__device__ __forceinline__ void poison(const Head& Q, uint32_t el, uint32_t src, const CUtensorMap* m, int rb, int j, int lane) {
#pragma unroll 1
  for (int u = lane; u < 72; u += 32) sts128(src + u * 16, POISON, POISON, POISON, POISON);
  fence_async_s();
  __syncwarp();
#pragma unroll 1
  for (int u = 0; u < 16; u++) {
    __nanosleep(NAP);
    bulk_store_p(el, o_block(rb, u >> 3) + j * 9216 + (u & 7) * 1152, src, 1152);
    asm volatile("{\n.reg .pred P;\nsetp.ne.u32 P, %5, 0;\n@P cp.async.bulk.tensor.3d.global.shared::cta.tile.bulk_group [%0, {%2, %3, %4}], [%1];\n}" ::"l"(m), "r"(src), "r"((j & 6) * 72), "r"(rb * 64 + u * 4), "r"(j & 1), "r"(el) : "memory");
  }
}
__device__ __forceinline__ void mma16acc(float* c, const uint32_t* a, uint32_t b0, uint32_t b1) {
  asm volatile("mma.sync.aligned.m16n8k16.row.col.f32.bf16.bf16.f32 {%0,%1,%2,%3}, {%4,%5,%6,%7}, {%8,%9}, {%0,%1,%2,%3};"
               : "+f"(c[0]), "+f"(c[1]), "+f"(c[2]), "+f"(c[3]) : "r"(a[0]), "r"(a[1]), "r"(a[2]), "r"(a[3]), "r"(b0), "r"(b1));
}
template <int KS, int NG, int AK, int AH, int BK, int BG, class F> __device__ __forceinline__ void redo(float* acc, const uint8_t* pa, const uint8_t* pb, F f) {
#pragma unroll 1
  for (int k = 0; k < 36; k += KS) {
    uint32_t a[4 * KS], b[2 * KS][NG];
#pragma unroll 1
    for (int it = 0; it < (1 << 20); it++) {
      bool ok = true;
#pragma unroll
      for (int e = 0; e < 4 * KS; e++) a[e] = ldgpu32(pa + (e >> 1) * AK + (e & 1) * AH);
#pragma unroll
      for (int e = 0; e < 2 * KS * NG; e++) b[e / NG][e % NG] = ldca32(pb + (e / NG) * BK + (e % NG) * BG);
#pragma unroll
      for (int e = 0; e < 4 * KS; e++) ok = ok && a[e] != POISON;
      if (__all_sync(~0u, ok)) break;
    }
#pragma unroll
    for (int e = 0; e < KS; e++) f(a + 4 * e, k + e);
#pragma unroll
    for (int e = 0; e < KS * NG; e++) mma16acc(acc + 4 * (e % NG), a + 4 * (e / NG), movm(b[2 * (e / NG)][e % NG]), movm(b[2 * (e / NG) + 1][e % NG]));
    pa += 2 * KS * AK; pb += 2 * KS * BK;
  }
}
__device__ __forceinline__ bool any_nan(float a, float b) {
  return __any_sync(~0u, a != a || b != b);
}

__global__ void __cluster_dims__(2, 1, 1) __launch_bounds__(384, 1) mega_kernel(const __grid_constant__ Head Q, const __grid_constant__ Params P) {
  extern __shared__ __align__(1024) uint8_t smem_raw[];
  const uint32_t sb = smem_u32(smem_raw);
  const uint32_t bars = sb + SM_BAR;
  int tid = threadIdx.x, lane = tid & 31;
  const int wid = __shfl_sync(~0u, tid >> 5, 0);
  if (tid == 256 && blockIdx.x < NCTA) prefetch_l2((const uint8_t*)Q.wqkv + blockIdx.x * 6912, 6912);
  const int cl = blockIdx.x >> 1, tp = cl - 36, t7 = (tp * 37) >> 8;
  const int bid = (cl < 4 ? cl * 8 + 32 : tp < 0 ? cl - 4 : cl < 64 ? tp + t7 + 33 : cl) * 2 + (blockIdx.x & 1);
  if (bid >= NCTA) return;
  const int rb = bid & 15, j = bid >> 4;
  uint4 wv[5];
  const uint8_t* wsrc;
  {
    const int n8 = min(tid >> 3, 26), part = n8 / 9;
    const uint8_t* src = (const uint8_t*)Q.wqkv + (8 * rb + (tid & 7)) * (3 * DM * 2) + (part * (DM - 72) + 72 * j + 8 * n8) * 2;
#pragma unroll
    for (int u = 0; u < SPL; u++) wv[u] = ldnc128_if(tid < 216, src + u * (128 * 3 * DM * 2));
    wsrc = src;
  }
  if (tid == 352) {
#pragma unroll
    for (int e = 0; e < 16; e++) mbar_init(bars + B_FULL + e * 8, (e >> 2) == 1 ? 16 : 1);
    mbar_init(bars + B_RES + 8, 8); mbar_init(bars + B_WT, 1); mbar_init(bars + B_WT + 8, 1); mbar_init(bars + B_IMG, 9);
    asm volatile("fence.mbarrier_init.release.cluster;" ::: "memory");
  }
  __syncthreads();

  if (wid >= 8) {
    reg_dealloc<40>();
    lane = __shfl_sync(~0u, lane, lane);
    const uint32_t el = elect_one();
    const uint64_t pol = policy_evict_first();
    uint32_t* const fj = Q.s->flags + FJ + j * 32;
    if (wid == 8) {
      if (lane == 0) {
        mbar_init(bars + B_RES, 1); mbar_init(bars + B_WOI, 1); mbar_init(bars + B_ZB, 1); mbar_init(bars + B_GATE3, 3); mbar_init(bars + B_Z1, 1); mbar_init(bars + B_LAG, 4);
#pragma unroll
        for (int e = B_RT; e < B_XS + 16; e += 8) mbar_init(bars + e, e >= B_AD && e < B_EVT ? 2 : (e >= B_EVT && e < B_RT1) || (e >= B_EA3 && e < B_XS) ? 4 : 1);
        asm volatile("fence.mbarrier_init.release.cluster;" ::: "memory");
        mbar_arrive(bars + B_IMG);
      }
      __syncwarp();
#pragma unroll 1
      for (int i = 0; i < 12; i++) if (el) prefetch_map(&P.act[0] + (i < 7 ? i : i - 12));
      const uint32_t epoch = ldcg32(fj + FJ_EP + rb);
      const uint32_t rk = bid & 1;
      uint32_t dst = sb + ST_B + rk * 18432, full = bars + B_FULL, ph = 1;
      auto slot = [&](uint32_t bytes) {
        mbar_wait(full, ph);
        expect_tx_p(el, full, bytes);
        mbar_wait(full + (B_EMPTY - B_FULL), ph);
      };
      auto next = [&]() {
        const bool wrap = full == bars + B_FULL + 24;
        full += wrap ? -24 : 8; dst += wrap ? 0u - 3 * ST_BYTES : ST_BYTES; ph ^= wrap;
      };
#pragma unroll 1
      for (int L = 0; L < 2; L++) {
        const uint8_t* src = Q.s->WQ + j * WQ_SL + rk * 13824;
        dst -= rk * 4608;
#pragma unroll 1
        for (int i = 0; i < 9; i++) {
          if (L == 0 && (i == 0 || i == 2 * SPL)) {
            flag_wait(fj + (i ? FJ_WQ : FJ_WQ0), (epoch + 1) * 16);
            fence_async_g();
          }
          slot(27648);
          bulk_mc_h(el, dst, src, 13824, full, true, pol);
          src += 27648;
          next();
        }
        dst += rk * 4608;
        if (L == 0) {
#pragma unroll 1
          for (int u = 0; u < 2; u++) flag_wait(Q.s->flags + FJ + (j ^ u) * 32 + FJ_WO, (epoch + 1) * 16);
          fence_async_g();
        }
        src = Q.s->WO + ((j & 6) + rk) * WO_SL;
#pragma unroll 1
        for (int i = 0; i < 4; i++) {
          slot(ZB);
          bulk_mc_h(el, dst, src, 18432, full, true, pol);
          src += 18432;
          next();
        }
        if (L == 0 && rb < 8 && el)
          asm volatile("cp.async.bulk.prefetch.tensor.4d.L2.global [%0, {%1, 0, 0, %2}];" ::"l"(&P.win64), "r"((((9 * j + 1) >> 1) + 36 + (rb >> 2)) * 64), "r"((rb & 3) * 18) : "memory");
        slot(18432);
        bulk_mc_h(el, dst, src, 9216, full, true, pol);
        next();
        int col = (((9 * j + 1) >> 1) + 36) * 64;
        const CUtensorMap* map = &P.win64;
#pragma unroll 1
        for (int p = 0; p < 9; p++) {
          if (p == 1) mbar_wait(bars + B_FA3 + GA3 * 8, L);
          mbar_wait(full + (B_EMPTY - B_FULL), ph);
          tma4d_mc(el, dst, map, col, rk * 18, full + 8, pol);
          mbar_arrive_if(el, full);
          next();
          if (p == 1) mbar_wait(bars + B_FA3 + GB3 * 8, L);
          slot(2 * ZB);
          tma4d_mc(el, dst, map, col, rk * 18 + 36, full, pol);
          next();
          col = p == 3 ? (9 * j + ((j & 1) ? 0 : 8)) * 32 : p == 4 ? ((9 * j + 1) >> 1) * 64 : col + 64;
          map = p == 3 ? &P.win : &P.win64;
        }
        flag_wait(fj + FJ_ZN + L, (epoch + 1) * 16);
        fence_async_g();
        src = z2_block(0, j) + rk * 18432;
#pragma unroll 1
        for (int i = 0; i < 32; i++) {
          if (i >= 4) mbar_wait(full + (B_AD - B_FULL), ((i >> 2) & 1) ^ 1);
          slot(ST_BYTES);
          bulk_mc_h(el, dst, src, 18432, full, true, pol);
          tma3d_h(el, dst - ST_B - rk * 18432, &P.wsp, i * 64, rb * 64, 0, full, true, pol);
          src += 8 * ZB;
          next();
        }
        mbar_wait(bars + B_Z1, L);
        fence_async_g();
        expect_tx_p(el, bars + B_ZB, 26624);
        mbar_wait(full + (B_AD - B_FULL), 1);
        slot(26624);
        bulk_load_h(el, dst - ST_B - rk * 18432, z1_block(rb, 0, j), 26624, bars + B_ZB, true, pol);
        bulk_load_h(el, dst - ST_B - rk * 18432 + 26624, z1_block(rb, 1, j), 26624, full, true, pol);
        next();
        col = j * 64;
#pragma unroll 1
        for (int i = 0; i < 9; i++) {
          if (i < 3) mbar_wait(full + (B_AD - B_FULL), 1);
          slot(ZB);
          tma2d_mc_h(el, dst, &P.wout, col, 288 * j + rk * 144, full, true, pol);
          col = col == 512 ? 0 : col + 64;
          next();
        }
      }
    } else if (wid < 11) {
      int w = wid - 9;
      uint32_t t8 = (ldcg32(Q.s->flags + (rb * 2 + w) * 32 + FR_EP + j) + 1) * 8;
      int bo = bid;
#define FRESH asm volatile("" : "+r"(lane), "+r"(w), "+r"(bo), "+r"(t8)); const int rb = bo & 15, j = bo >> 4; \
      uint32_t *const fr = Q.s->flags + (rb * 2 + w) * 32, *const fj = Q.s->flags + FJ + j * 32, *const fo = Q.s->flags + (rb * 2 + (j & 1)) * 32 + L; \
      const uint32_t ev = bars + B_EVT + w * EV_N * 8, tag = (t8 >> 2) - 1 + L; (void)fr; (void)fj; (void)fo; (void)ev; (void)tag
      Cur c{0, 1};
#pragma unroll 1
      for (int L = 0; L < 2; L++) {
        {
          FRESH;
          uint4* const xs = Q.s->XST + (rb * 2 + w) * 128;
          if (L) {
            mbar_wait(ev + EV_PT * 8, 0);
            flag_release_p(el, fr + FR_X2);
          }
#pragma unroll 1
          for (int i = 0; i < 9; i++) {
            const uint32_t full = bars + B_FULLA + w * 32 + c.s * 8, dst = sb + c.s * ST_BYTES + w * 8192;
            if (L == 0 && i == 4) {
              mbar_wait(bars + B_WT + w * 8, 0);
              rows_stats(sb + SM_STG + w * 9216, xs + 16 * j, tag, lane);
            }
            const uint32_t src = sb + (L ? 2 * ST_BYTES + SM_WOI : SM_STG + w * 9216);
            if (i == 4) {
#pragma unroll
              for (int u = 0; u < 6; u++) sts128(src + u * 512 + lane * 16, POISON, POISON, POISON, POISON);
              fence_async_s();
              __syncwarp();
            }
            mbar_wait(bars + B_EMPTY + c.s * 8, c.ph);
            if (i < L) { flag_wait(fr + FR_X2, t8); fence_async_g(); }
            tma3d_h(el, dst, &P.act[L], i * 64, rb * 64, w, full, false, pol);
            expect_tx_p(el, full, 8192);
            c.next();
            if (i >= 4 && i < (L ? 5 : 8)) {
              int b = (rb * 2 + w) * 8 + j;
              asm volatile("" : "+r"(b));
              bulk_store_p(el, i == 4 ? (uint8_t*)Q.s->HALO + b * 3072 : Q.s->O + (b * 3 + i - 5) * 3072, src, 3072);
              if (i < 6) bulk_store_p(el, (i == 4 ? Q.s->ST1 : Q.s->ZST) + b * 64, src, 1024);
              if (i == 6) bulk_store_p(el, Q.s->RT + b * 8, src, 64);
            }
            if (L == 0 && i == 3) rows_fetch(el, sb + SM_STG + w * 9216, Q.xs[0] + (128 * rb + 16 * j + w) * (DM * 2), bars + B_WT + w * 8);
          }
          if (el) asm volatile("cp.async.bulk.commit_group;\ncp.async.bulk.wait_group 0;" ::: "memory");
          __syncwarp();
          if (L == 0) fence_gpu();
          const uint32_t tab = sb + L * (2 * ST_BYTES) + SM_XST + w * 512 + lane * 8;
#pragma unroll 1
          for (int it = 0; it < (1 << 22); it++) {
            const uint4 a = ll_ld128(xs + 2 * lane), b = ll_ld128(xs + 64 + 2 * lane);
            if (__all_sync(~0u, a.z == tag && b.z == tag)) { sts64(tab, a.x, a.y); sts64(tab + 256, b.x, b.y); break; }
          }
          __syncwarp();
          mbar_arrive_if(el, bars + B_XS + w * 8);
          if (w == 1) {
            mbar_wait(bars + B_XS, L);
            expect_tx_p(el, bars + B_RES, 18432);
            tma3d_h(el, sb + SM_STG, &P.res[L], (j & 6) * 72, rb * 64, j & 1, bars + B_RES, !L, pol);
          }
          if (L) flag_wait(fj + FJ_P4, t8 * 4);
        }
        {
          FRESH;
          const uint8_t* src = o_block(rb, j & 1) + w * 8192;
#pragma unroll 1
          for (int i = 0; i < 5; i++) {
            const uint32_t full = bars + B_FULLA + w * 32 + c.s * 8, dst = sb + c.s * ST_BYTES + w * 8192;
            const bool none = 2 * i + w > 8;
            mbar_wait(bars + B_EMPTY + c.s * 8, c.ph);
            expect_tx_p(el, full, none ? 0 : 8192);
            if (i == 0) {
              mbar_wait(bars + B_EMPTY + 16 * L, 0);
              mbar_wait(ev + EV_O * 8, L);
              flag_add_p(el, fr + FR_O + L);
              flag_wait(fo + FR_O, t8);
              fence_async_g();
            }
            if (!none) bulk_load_h(el, dst, src + i * 16384, 8192, full, true, pol);
            c.next();
          }
        }
        {
          FRESH;
          expect_tx_p(lane < 9, bars + B_FA3 + (9 * w + lane) * 8, 8192);
          mbar_wait(ev + EV_X1 * 8, L);
          if (L) flag_add_p(el, fo + FR_X1); else flag_release_p(el, fo + FR_X1);
          mbar_arrive_if(el, bars + B_GATE3);
          mbar_arrive_if(lane < 2, bars + B_FULLA + w * 32 + ((c.s + lane) & 3) * 8);
#pragma unroll 1
          for (int kb = 0; kb < 9; kb++) {
            const int n = 9 * w + kb;
            const uint32_t dst = sb + ((n >> 1) & 3) * ST_BYTES + (n & 1) * 8192;
            if (kb == 0) { flag_wait(fr + FR_X1 + L, t8); fence_async_g(); }
            if (n >= 8) mbar_wait(bars + B_EA3 + (n - 8) * 8, L);
            tma3d_h(el, dst, &P.act[L + 1], kb * 64, rb * 64, w, bars + B_FA3 + n * 8, false, pol);
          }
          c.ph ^= ((c.s + 18) >> 2) & 1; c.s = (c.s + 18) & 3;
        }
        float cv;
        {
        FRESH;
        expect_tx_p(el, bars + B_WT + w * 8, 2048);
#pragma unroll 1
        for (int r = 0; r < 8; r++)
          bulk_load_p(el, sb + SM_WT + w * 2176 + r * 272, (const uint8_t*)P.w_sp + (size_t)(128 * rb + 16 * j + 2 * r + w) * (SEQ * 2) + 30 * 128, 256, bars + B_WT + w * 8);
        cv = (lane & 3) ? 0.f : -blo(ldnc16(P.b_sp + 128 * rb + 16 * j + 2 * (lane >> 2) + w));
        mbar_wait(bars + B_RT, L);
        mbar_wait(bars + B_WT + w * 8, L ^ 1);
        mbar_wait(ev + EV_Z1 * 8, L);
        const uint32_t ro = (w * 64 + 8 * j + (lane >> 2)) * 128, x0 = ((lane & 3) * 2) ^ (lane >> 2);
#pragma unroll 1
        for (int i = 0; i < 32; i++) {
          const bool tail = (i >> 1) == 4;
          const int kb = tail ? i + 22 : i < 8 ? i : i - 2;
          if (i == 8) mbar_wait(bars + B_RT1, L);
          if (!tail) mbar_wait(bars + B_FULL + c.s * 8, c.ph ^ 1);
#pragma unroll
          for (int e = 0; e < 2; e++) {
            const uint4 a = lds128(!tail ? sb + c.s * ST_BYTES + ro + ((x0 ^ e) << 4) : sb + SM_WT + w * 2176 + (lane >> 2) * 272 + (i - 8) * 128 + (lane & 3) * 32 + e * 16);
            const uint4 m = lds128(sb + SM_RT + 4096 + kb * 128 + (lane & 3) * 32 + e * 16);
            cv = fmaf(blo(a.x), blo(m.x), fmaf(bhi(a.x), bhi(m.x), fmaf(blo(a.y), blo(m.y), fmaf(bhi(a.y), bhi(m.y), cv))));
            cv = fmaf(blo(a.z), blo(m.z), fmaf(bhi(a.z), bhi(m.z), fmaf(blo(a.w), blo(m.w), fmaf(bhi(a.w), bhi(m.w), cv))));
          }
          if (!tail) {
            mbar_arrive_if(el, bars + B_AD + c.s * 8 + (__float_as_uint(cv) & Q.zero));
            c.next();
          }
        }
        }
        FRESH;
        cv = qsum(cv);
        uint2* const cs = (uint2*)(Q.s->XST + (rb * 2 + w) * 128 + 1);
        if ((lane & 3) == 0) ll_st64(cs + 32 * j + (lane >> 2) * 4, __float_as_uint(cv), tag);
#pragma unroll 1
        for (int it = 0; it < (1 << 22); it++) {
          const uint2 a = ll_ld64(cs + 4 * lane), b = ll_ld64(cs + 128 + 4 * lane);
          if (__all_sync(~0u, a.y == tag && b.y == tag)) { sts32(sb + SM_CV + w * 256 + lane * 4, a.x); sts32(sb + SM_CV + w * 256 + 128 + lane * 4, b.x); break; }
        }
        __syncwarp();
        if (el) mbar_arrive(bars + B_CV + w * 8);
#pragma unroll 1
        for (int kb = 30; kb < 32; kb++) {
          mbar_wait(bars + B_FULL + c.s * 8, c.ph ^ 1);
          if (el) mbar_arrive(bars + B_AD + c.s * 8);
          c.next();
        }
        c.ph ^= ((c.s + 10) >> 2) & 1; c.s = (c.s + 10) & 3;
        if (L == 0) {
          mbar_wait(ev + EV_P4 * 8, 0);
          flag_add_p(el, fj + FJ_P4);
          flag_add_p(el, fr + FR_EP + j);
        }
      }
    } else {
      const uint32_t epoch = ldcg32(fj + FJ_EP + rb);
      if (SPL) {
        mbar_wait(bars + B_RES + 8, 0);
        flag_release_p(el, fj + FJ_WQ0);
      }
      mbar_wait(bars + B_IMG, 0);
      flag_release_p(el, fj + FJ_WQ);
#pragma unroll 1
      for (int L = 0; L < 2; L++) {
        auto wo_fetch = [&]() {
          expect_tx_p(el, bars + B_WOI, 5760);
          asm volatile("{\n.reg .pred P;\nsetp.ne.u32 P, %5, 0;\n@P cp.async.bulk.tensor.4d.shared::cluster.global.mbarrier::complete_tx::bytes [%0], [%1, {0, 0, %3, %4}], [%2];\n}" ::"r"(sb + SM_WOI), "l"(&P.wo8), "r"(bars + B_WOI), "r"(9 * j), "r"((9 * rb) >> 1), "r"(el) : "memory");
        };
        float* const csf = Q.s->CSP + (NCTA + bid) * 216;
        if (L == 0) {
          flag_wait(fj + FJ_WQ, (epoch + 1) * 16);
          fence_async_g();
          expect_tx_p(el, bars + B_XRW, 13824);
          bulk_load_p(el, sb + ST_BYTES + SM_WOI, Q.s->CSP + j * 16 * 216, 6912, bars + B_XRW);
          bulk_load_p(el, sb + 2 * ST_BYTES + SM_WOI, Q.s->CSP + (j * 16 + 8) * 216, 6912, bars + B_XRW);
          wo_fetch();
          mbar_wait(bars + B_XRW, 0);
#pragma unroll 1
          for (int f = lane; f < 54; f += 32) {
            float s[4] = {0.f, 0.f, 0.f, 0.f};
#pragma unroll 4
            for (int r = 0; r < 16; r++) {
              const uint4 v = lds128(sb + ST_BYTES + SM_WOI + (r >> 3) * ST_BYTES + (r & 7) * 864 + f * 16);
              s[0] += __uint_as_float(v.x); s[1] += __uint_as_float(v.y); s[2] += __uint_as_float(v.z); s[3] += __uint_as_float(v.w);
            }
            sts128(sb + SM_CSQ + f * 16, __float_as_uint(s[0]), __float_as_uint(s[1]), __float_as_uint(s[2]), __float_as_uint(s[3]));
            stg128(csf + f * 4, __float_as_uint(s[0]), __float_as_uint(s[1]), __float_as_uint(s[2]), __float_as_uint(s[3]));
          }
          __syncwarp();
          mbar_arrive_if(el, bars + B_CSQ);
        } else {
#pragma unroll 1
          for (int u = 0; u < 4; u++) {
            const int w = u & 1;
            if (u < 2) {
              flag_wait(Q.s->flags + (rb * 2 + w) * 32 + FR_X2, (epoch + 1) * 8);
              fence_async_g();
              rows_fetch(el, sb + SM_STG + w * 9216, Q.xs[1] + (128 * rb + 16 * j + w) * (DM * 2), bars + B_XRW + w * 8);
            } else {
              if (u == 2) {
                expect_tx_p(el, bars + B_CSQ, 864);
                bulk_load_p(el, sb + 2 * ST_BYTES + SM_CSQ, csf, 864, bars + B_CSQ);
              }
              mbar_wait(bars + B_XRW + w * 8, w ^ 1);
              rows_stats(sb + SM_STG + w * 9216, Q.s->XST + (rb * 2 + w) * 128 + 16 * j, epoch * 2 + 2, lane);
            }
          }
        }
        if (L == 0) {
          mbar_wait(bars + B_WOI, 0);
          bulk_store_p(el, Q.s->WO + j * WO_SL + ((9 * rb) >> 1) * 1152, sb + SM_WOI, 5760);
          publish_p(el, fj + FJ_WO);
          const uint8_t* sp = lane < 16 ? (const uint8_t*)P.w_in + (30 * lane + 50) * (FH * 4) + FH * 2 + lane * 256 : (const uint8_t*)P.w_sp + (60 * lane) * (SEQ * 2) + lane * 64;
          float sq = 0.f;
#pragma unroll 1
          for (int u = 0; u < 4; u++) {
            const uint4 y = ldnc128(sp + u * 16);
            const uint32_t x[4] = {y.x, y.y, y.z, y.w};
#pragma unroll
            for (int e = 0; e < 4; e++) sq = fmaf(blo(x[e]), blo(x[e]), fmaf(bhi(x[e]), bhi(x[e]), sq));
          }
#pragma unroll 1
          for (int o = 8; o; o >>= 1) sq += __shfl_xor_sync(~0u, sq, o);
          sq *= lane < 16 ? 2.f * GA * GA * DM / 512.f : C0S * C0S * SEQ / 512.f;
          asm("sqrt.approx.f32 %0, %0;" : "+f"(sq));
          const float o0 = __shfl_sync(~0u, sq, 0), o1 = __shfl_sync(~0u, sq, 16);
          const float p2 = __uint_as_float(min(__float_as_uint(o0) & 0x7f800000u, 0x7e000000u)) * OFK, off = -p2 - fminf(OFA, 0.5f * p2);
          if (el) sts64(sb + SM_OFF, pack2(off, off), min(__float_as_uint(o1) & 0x7f800000u, 0x7e000000u) | 0x00400000u);
        }
        if (el) mbar_arrive(bars + B_GATE3);
        const uint32_t tag = epoch * 2 + L + 1;
        asm volatile("" : "+r"(lane));
        mbar_wait(bars + B_EVT + EV_ZN * 8, L);
        mbar_wait(bars + B_EVT + (EV_N + EV_ZN) * 8, L);
        flag_release_p(el, fj + FJ_ZN + L);
        {
          uint4 v[4];
#pragma unroll 1
          for (int it = 0; it < (1 << 22); it++) {
            bool ok = true;
#pragma unroll
            for (int u = 0; u < 4; u++) { v[u] = ll_ld128(Q.s->ZST + (rb * 2 + ((lane >> 1) & 1)) * 512 + ((lane & 1) * 4 + u) * 64 + 8 * j + (lane >> 2)); ok = ok && v[u].z == tag; }
            if (__all_sync(~0u, ok)) break;
          }
          float mean = __uint_as_float(v[0].x) + __uint_as_float(v[1].x) + __uint_as_float(v[2].x) + __uint_as_float(v[3].x), M2 = 0.f;
          mean = (mean + __shfl_xor_sync(~0u, mean, 1)) * 0.125f;
#pragma unroll
          for (int u = 0; u < 4; u++) { const float d = __uint_as_float(v[u].x) - mean; M2 += fmaf(288.f * d, d, __uint_as_float(v[u].y)); }
          M2 += __shfl_xor_sync(~0u, M2, 1);
          const float rs = blo(pack2(rsq_fast(fmaf(M2, 1.f / FH, 4.f * GA * GA * LN_EPS)), 0.f));
          if (!(lane & 1)) ll_st64(Q.s->RT + 128 * rb + 16 * j + (lane >> 1), pack2(rs, rs * mean), tag);
        }
#pragma unroll 1
        for (int b = 0; b < 8; b++) {
          uint4 v[4];
#pragma unroll 1
          for (int it = 0; it < (1 << 22); it++) {
            bool ok = true;
#pragma unroll
            for (int u = 0; u < 4; u++) { v[u] = ll_ld128((const uint4*)Q.s->RT + b * 128 + u * 32 + lane); ok = ok && v[u].y == tag && v[u].w == tag; }
            if (__all_sync(~0u, ok)) break;
          }
#pragma unroll
          for (int u = 0; u < 4; u++) {
            const uint32_t rt = sb + SM_RT + b * 512 + u * 128, ro = (lane >> 3) * 32 + (lane & 3) * 8 + ((lane >> 2) & 1) * 2;
            sts32(rt + 4096 + lane * 4, __byte_perm(v[u].x, v[u].z, 0x7632));
            asm volatile("st.shared.u16 [%0], %1;\nst.shared.u16 [%0 + 4], %2;" ::"r"(rt + ro), "h"((uint16_t)v[u].x), "h"((uint16_t)v[u].z) : "memory");
          }
          __syncwarp();
          if (el && (b == 1 || b == 7)) mbar_arrive(bars + (b == 1 ? B_RT : B_RT1));
        }
        mbar_wait(bars + B_EVT + EV_Z1 * 8, L);
        mbar_wait(bars + B_EVT + (EV_N + EV_Z1) * 8, L);
        fence_gpu();
        if (el) mbar_arrive(bars + B_Z1);
        if (L == 0) {
          flag_add_p(el, fj + FJ_EP + rb);
          __nanosleep(NAP0);
          poison(Q, el, sb + SM_STG + 17152, &P.psn, rb, j, lane);
          if (el) asm volatile("cp.async.bulk.commit_group;\ncp.async.bulk.wait_group 0;" ::: "memory");
          __syncwarp();
          fence_gpu();
        }
      }
    }
  } else {
    uint8_t* const wdst = Q.s->WQ + j * WQ_SL + rb * 3456 + tid * 16;
#pragma unroll
    for (int u = 0; u < SPL; u++) stg128_if(tid < 216, wdst + u * (16 * 3456), wv[u].x, wv[u].y, wv[u].z, wv[u].w);
    __syncwarp();
    if (lane == 0) mbar_arrive(bars + B_RES + 8);
    auto repack2 = [&]() {
#pragma unroll
      for (int u = SPL; u < 5; u++) stg128_if((u < 4 || rb < 8) && tid < 216, wdst + u * (16 * 3456), wv[u].x, wv[u].y, wv[u].z, wv[u].w);
      float s[8];
#pragma unroll
      for (int e = 0; e < 8; e++) s[e] = 0.f;
#pragma unroll
      for (int u = 0; u < 5; u++) {
        uint32_t x[4] = {wv[u].x, wv[u].y, wv[u].z, wv[u].w};
        asm volatile("" : "+r"(x[0]), "+r"(x[1]), "+r"(x[2]), "+r"(x[3]));
#pragma unroll
        for (int e = 0; e < 4; e++) { s[2 * e] += blo(x[e]); s[2 * e + 1] += bhi(x[e]); }
      }
#pragma unroll
      for (int m = 4; m; m >>= 1) {
#pragma unroll
        for (int e = 0; e < m; e++) s[e] = ((tid & m) ? s[e + m] : s[e]) + __shfl_xor_sync(~0u, (tid & m) ? s[e] : s[e + m], m);
      }
      stg32_if(tid < 216, Q.s->CSP + bid * 216 + tid, __float_as_uint(s[0]));
      __syncwarp();
      if (lane == 0) mbar_arrive(bars + B_IMG);
    };
    reg_alloc<232>();
    lane = __shfl_sync(~0u, lane, lane);
    tid = wid * 32 + lane;
#pragma unroll
    for (int v = SPL; v < 5; v++) wv[v] = ldnc128_if(tid < 216 && (v < 4 || rb < 8), wsrc + v * (128 * 3 * DM * 2));
    repack2();
    const int w = wid >> 2, q = wid & 3;
    int g = lane >> 2, t = lane & 3;
    const uint32_t ev = bars + B_EVT + w * EV_N * 8;
    Cur c{0, 0};
    const uint32_t ebar = mapa(bars + B_EMPTY, (bid & 1) ^ (lane & 1));
    auto release = [&](uint32_t s, uint32_t dep = 0) { mbar_arrive_cluster_if(lane < 2, ebar + s * 8 + dep); };
    auto release_if = [&](bool on, uint32_t s) { mbar_arrive_cluster_if(lane < 2 && on, ebar + s * 8); };
    uint32_t ia = 0;
    auto wait_ab = [&]() { mbar_wait_c(bars + B_FULL + c.s * 8, c.ph); mbar_wait_c(bars + B_FULLA + w * 32 + c.s * 8, (ia >> 2) & 1); ia++; };

    auto yield_done = [&]() { if (w == 0 && lane == 0) mbar_arrive(bars + B_LAG); };
    auto signal = [&](int e) { __syncwarp(); mbar_arrive_if(lane == 0, ev + e * 8); };

    const uint32_t epoch = ldcg32(Q.s->flags + (rb * 2 + w) * 32 + FR_EP + j);

#pragma unroll 1
    for (int L = 0; L < 2; L++) {
      asm volatile("" : "+r"(lane), "+r"(g), "+r"(t));
      ia = 0;
      const uint32_t tag = epoch * 2 + L + 1;
      uint32_t aoff = (w * 64 + q * 16 + (lane & 15)) * 128 + (((lane >> 4) ^ (lane & 7)) << 4);
      {
        uint32_t Pk[27][2];
        float sc0, sc1;
        const uint32_t att = sb + w * 8192 + q * 2048 + lane * 4;
        uint4* hp = Q.s->HALO + ((((rb - (q == 0)) * 2 + w) * 8 + j) * 6) * 32 + lane;
        uint8_t* od = o_block(rb, w) + (9 * j) * 1024 + (2 * q) * 128 + lane * 4;
        {
          float acc[108];
#pragma unroll
          for (int i = 0; i < 108; i++) acc[i] = 0.f;
          uint32_t prev = 0;
#pragma unroll 1
          for (int kb = 0; kb < 9; kb++) {
            const bool hold = w == 1 && kb == 9 - LAG1;
            if (hold) {
              wgmma_wait<0>();
              release(prev);
              mbar_wait_c(bars + B_LAG, L);
            }
            wait_ab();
            const uint32_t st = sb + c.s * ST_BYTES;
            uint64_t da = dsc2(dlo(st + w * 8192, 16), 0, 0x40000040u + Q.zero), db = dsc2(dlo(st + ST_B, 3456), 0, 8 ^ Q.zero);
            wgmma_fence();
#pragma unroll
            for (int kk = 0; kk < 4; kk++) {
              wgmma_ss_n216(acc, da, db, 1);
              dadd(da, 2); dadd(db, 432);
              if (kk == 0) { wgmma_commit(); wgmma_wait<1>(); release_if(kb > 0 && !hold, prev); }
            }
            wgmma_commit();
            if (kb == 7) yield_done();
            prev = c.s; c.next();
          }
          const uint32_t cs = sb + prev * ST_BYTES + SM_CSQ + t * 8;
          mbar_wait_c(bars + B_CSQ, L);
          mbar_wait_c(bars + B_XS + w * 8, L);
          const float2 n0 = lds64f(sb + prev * ST_BYTES + SM_XST + w * 512 + (16 * q + g) * 8), n1 = lds64f(sb + prev * ST_BYTES + SM_XST + w * 512 + (16 * q + g + 8) * 8);
          const float m0 = n0.x, r0 = n0.y, m1 = n1.x, r1 = n1.y;
          float2 cv[27];
#pragma unroll
          for (int G = 0; G < 27; G++) cv[G] = lds64f(cs + G * 32);
          wgmma_wait<0>();
          {
            uint32_t dep = Q.zero & __float_as_uint(m0) & __float_as_uint(m1);
#pragma unroll
            for (int G = 0; G < 27; G++) dep &= __float_as_uint(cv[G].x);
            release(prev, dep);
          }
#pragma unroll
          for (int G = 9; G < 27; G++) Pk[G][1] = pack2(fmaf(m1, cv[G].x, acc[4 * G + 2]) * r1, fmaf(m1, cv[G].y, acc[4 * G + 3]) * r1);
          if (q < 3) {
#pragma unroll
            for (int i = 0; i < 18; i++) sts32(att + (i >> 4) * ST_BYTES + (i & 15) * 128, Pk[9 + i][1]);
          } else if (rb < 15) {
#pragma unroll
            for (int i = 0; i < 6; i++) ll_st128(hp + i * 32, __uint_as_float(Pk[9 + 3 * i][1]), __uint_as_float(Pk[10 + 3 * i][1]), tag, __uint_as_float(Pk[11 + 3 * i][1]));
          }
#pragma unroll
          for (int G = 0; G < 27; G++) {
            if (G < 9) {
              Pk[G][0] = pack2(fmaf(m0, cv[G].x, acc[4 * G]), fmaf(m0, cv[G].y, acc[4 * G + 1]));
              Pk[G][1] = pack2(fmaf(m1, cv[G].x, acc[4 * G + 2]), fmaf(m1, cv[G].y, acc[4 * G + 3]));
            } else {
              Pk[G][0] = pack2(fmaf(m0, cv[G].x, acc[4 * G]) * r0, fmaf(m0, cv[G].y, acc[4 * G + 1]) * r0);
            }
          }
          sc0 = r0 * (0.23570226039551584f * 1.4426950408889634f); sc1 = r1 * (0.23570226039551584f * 1.4426950408889634f);
        }
        constexpr int GA_[4] = {0, 2, 4, 7}, GB_[4] = {1, 3, 5, 8}, GC_[4] = {2, 4, 6, 6};
        float S1[4][4], S2[4][4];
        uint32_t qa[4][2], qc[4][2];
#pragma unroll
        for (int h = 0; h < 4; h++) {
#pragma unroll
          for (int r = 0; r < 2; r++) {
            qa[h][r] = (h == 0 || h == 3 || t >= h) ? Pk[GA_[h]][r] : 0u;
            qc[h][r] = (h == 3 ? t == 3 : t <= h) ? Pk[GC_[h]][r] : 0u;
          }
          mma16(S1[h], qa[h][0], qa[h][1], Pk[GB_[h]][0], Pk[GB_[h]][1], Pk[9 + GA_[h]][0], Pk[9 + GB_[h]][0]);
          mma16(S2[h], qa[h][0], qa[h][1], Pk[GB_[h]][0], Pk[GB_[h]][1], Pk[9 + GA_[h]][1], Pk[9 + GB_[h]][1]);
        }
#pragma unroll
        for (int h = 0; h < 4; h++) {
          mma8(S1[h], qc[h][0], qc[h][1], Pk[9 + GC_[h]][0]);
          mma8(S2[h], qc[h][0], qc[h][1], Pk[9 + GC_[h]][1]);
        }
        uint32_t V1[9], V2[9];
#pragma unroll
        for (int i = 0; i < 9; i++) { V1[i] = movm(Pk[18 + i][0]); V2[i] = movm(Pk[18 + i][1]); }
        const bool remote = q == 0 && rb > 0;
        uint4 hv[6];
#pragma unroll
        for (int i = 0; i < 6; i++) hv[i] = make_uint4(0u, 0u, tag, 0u);
        if (remote) {
#pragma unroll
          for (int i = 0; i < 6; i++) hv[i] = ll_ld128(hp + i * 32);
        }
        const bool up0 = 2 * t > g, up1 = 2 * t + 1 > g;
        const uint32_t mup = (up0 ? 0xffffu : 0u) | (up1 ? 0xffff0000u : 0u);
        auto finish = [&](const float (&x0)[4], const float (&x1)[4], uint32_t ma, const uint32_t (&Vb)[9], int hi) {
          uint32_t pa[4], pb[4];
          float rs[4];
#pragma unroll
          for (int h = 0; h < 4; h++) {
            const float m = qmax(fmaxf(x0[h], x1[h]));
            const uint32_t p = pack2(ex2(x0[h] - m), ex2(x1[h] - m));
            pa[h] = p & ma; pb[h] = p & ~ma;
          }
          if (!hi) mbar_arrive_if(lane == 0, ev + EV_O * 8 + (Vb[8] & pa[3] & Q.zero));
#pragma unroll
          for (int h = 0; h < 4; h += 2) {
            float R[4];
            mma16(R, pa[h], pa[h + 1], pb[h], pb[h + 1], 0x3f803f80u, 0x3f803f80u);
            rs[h] = rcp_fast(R[0]); rs[h + 1] = rcp_fast(R[2]);
          }
#pragma unroll
          for (int i = 0; i < 9; i++) {
            const int h = 4 * i / 9, e = (h & 1) * 2;
            const bool split = i == 2 || i == 4 || i == 6, nx = split && 2 * t >= i;
            float O[4], N[4];
            mma16(O, pa[h & 2], pa[h | 1], pb[h & 2], pb[h | 1], V1[i], Vb[i]);
            if (i == 4) mma16(N, pa[2], pa[3], pb[2], pb[3], V1[i], Vb[i]); else { N[0] = O[2]; N[1] = O[3]; }
            const float r = nx ? rs[h + (split ? 1 : 0)] : rs[h];
            stg32(od + i * 1024 + hi * 128, pack2((nx ? N[0] : O[e]) * r, (nx ? N[1] : O[e + 1]) * r));
          }
        };
        {
          float x0[4], x1[4];
#pragma unroll
          for (int h = 0; h < 4; h++) { x0[h] = (up0 ? S1[h][2] : S2[h][2]) * sc1; x1[h] = (up1 ? S1[h][3] : S2[h][3]) * sc1; }
          finish(x0, x1, mup, V2, 1);
        }
        bar_sync(1 + w, 128);
        uint32_t H[18];
        if (q > 0) {
#pragma unroll
          for (int i = 0; i < 18; i++) H[i] = lds32(att - 2048 + (i >> 4) * ST_BYTES + (i & 15) * 128);
        } else {
#pragma unroll 1
          for (int it = 0; it < (1 << 20); it++) {
            bool ok = true;
#pragma unroll
            for (int i = 0; i < 6; i++) ok = ok && hv[i].z == tag;
            if (__all_sync(~0u, ok)) break;
#pragma unroll
            for (int i = 0; i < 6; i++) hv[i] = ll_ld128(hp + i * 32);
          }
#pragma unroll
          for (int i = 0; i < 6; i++) { H[3 * i] = hv[i].x; H[3 * i + 1] = hv[i].y; H[3 * i + 2] = hv[i].w; }
        }
        float S0[4][4];
#pragma unroll
        for (int h = 0; h < 4; h++) {
          mma16(S0[h], qa[h][0], qa[h][1], Pk[GB_[h]][0], Pk[GB_[h]][1], H[GA_[h]], H[GB_[h]]);
        }
#pragma unroll
        for (int h = 0; h < 4; h++) mma8(S0[h], qc[h][0], qc[h][1], H[GC_[h]]);
        uint32_t V0[9];
#pragma unroll
        for (int i = 0; i < 9; i++) V0[i] = movm(H[9 + i]);
        {
          const bool nohalo = (rb | q) == 0;
          const float b0 = up0 && nohalo ? -INFINITY : 0.f, b1 = up1 && nohalo ? -INFINITY : 0.f;
          float x0[4], x1[4];
#pragma unroll
          for (int h = 0; h < 4; h++) { x0[h] = fmaf(up0 ? S0[h][0] : S1[h][0], sc0, b0); x1[h] = fmaf(up1 ? S0[h][1] : S1[h][1], sc0, b1); }
          finish(x0, x1, ~mup, V0, 0);
        }
        bar_arrive(3 + w, 256);
      }
      {
        float acc[36];
        const int hw = rb * 2 + (j & 1), js = (j & 6) + w;
        const uint32_t xt = sb + SM_STG + (16 * q + (lane & 15)) * 288 + (9 * w + (lane >> 4)) * 16, eye = (g >> 1) == t ? 0x3f80u << (g & 1) * 16 : 0u;
        uint32_t xm = xt ^ ((lane & 4) << 2), xl = sb + SM_STG + (2 * q + w) * 2304;
        uint32_t xl0 = xl + (lane >> 4) * 288 + (lane & 15) * 16, xl1 = xl + ((lane >> 1) & 7) * 288 + 256 + ((lane ^ (lane >> 3)) & 1) * 16;
        uint8_t* xd0 = Q.xs[L + 1] + (128 * rb + 32 * q + 16 * w + (j & 1)) * (DM * 2) + (j & 6) * 144;
        uint8_t* xd1 = xd0 + (lane >> 1) * (DM * 4) + 256 + (lane & 1) * 16;
        xd0 += (lane >> 4) * (DM * 4) + (lane & 15) * 16;
        uint4* stp = Q.s->ST1 + (hw * 8 + js) * 64 + 16 * q + g;
        asm volatile("" : "+r"(xm), "+r"(xl0), "+r"(xl1), "+l"(xd0), "+l"(xd1), "+l"(stp));
        mbar_wait_c(bars + B_RES, L);
#pragma unroll
        for (int u = 0; u < 5; u++) {
          uint32_t r[4];
          ldsm4(r, xt + u * 32);
          widen(acc + 8 * u, r[0], r[1], eye);
          if (u < 4) widen(acc + 8 * u + 4, r[2], r[3], eye);
        }
        bar_sync(4 - w, 256);
        uint32_t prev = 0;
#pragma unroll 1
        for (int u = 0; u < 5; u++) {
          const uint32_t st = sb + c.s * ST_BYTES;
          uint64_t da = dsc2(dlo(st, 1024), 0, 8 + Q.zero), db = dsc2(dlo(st + ST_B + w * 18432, 1152), 0, 8 ^ Q.zero);
          mbar_wait_c(bars + B_FULL + c.s * 8, c.ph); mbar_wait_c(bars + B_FULLA + c.s * 8, (ia >> 2) & 1);
          wgmma_fence();
#pragma unroll
          for (int kk = 0; kk < 4; kk++) { wgmma_ss_n72(acc, da, db, 1); dadd(da, 128); dadd(db, 144); }
          wgmma_commit();
          wgmma_wait<1>();
          release_if(u > 0, prev);
          mbar_wait_c(bars + B_FULLA + 32 + c.s * 8, (ia >> 2) & 1);
          ia++;
          if (u == 4) break;
          wgmma_fence();
#pragma unroll
          for (int kk = 4; kk < 8; kk++) { wgmma_ss_n72(acc, da, db, 1); dadd(da, 128); dadd(db, 144); }
          wgmma_commit();
          prev = c.s; c.next();
        }
        wgmma_wait<0>();
        release(c.s);
        c.next();
        if (__builtin_expect(any_nan(acc[0], acc[2]), 0)) {
          const uint8_t* xr = Q.xs[L] + (uint32_t)((128 * rb + 32 * q + 2 * g + (j & 1)) * (DM * 2) + js * 144 + t * 4);
#pragma unroll
          for (int i = 0; i < 9; i++) widen(acc + 4 * i, ldgpu32(xr + i * 16), ldgpu32(xr + i * 16 + DM * 32), eye);
          redo<KS2, 9, 1024, 128, 1152, 128>(acc, Q.s->O + (uint32_t)(hw * (2 * ZB) + q * 256 + lane * 4), Q.s->WO + (uint32_t)(js * WO_SL + lane * 4), [](uint32_t*, int) {});
        }
        uint32_t pk[18];
#pragma unroll
        for (int i = 0; i < 18; i++) pk[i] = pack2(acc[2 * i], acc[2 * i + 1]);
#pragma unroll
        for (int u = 0; u < 4; u++) stsm4(xm + u * 32, pk[4 * u], pk[4 * u + 1], pk[4 * u + 2], pk[4 * u + 3]);
        asm volatile("stmatrix.sync.aligned.m8n8.x2.shared.b16 [%0], {%1,%2};" ::"r"(xm + 128), "r"(pk[16]), "r"(pk[17]) : "memory");
        float sm[4], q0[4], q1[4];
        widen(sm, pk[16], pk[17], 0x3f803f80u); widen(q0, pk[16], pk[17], pk[16]); widen(q1, pk[16], pk[17], pk[17]);
#pragma unroll
        for (int u = 0; u < 4; u++) {
          mma16acc(sm, pk + 4 * u, 0x3f803f80u, 0x3f803f80u);
          mma8(q0, pk[4 * u], pk[4 * u + 1], pk[4 * u]); mma8(q1, pk[4 * u], pk[4 * u + 1], pk[4 * u + 1]);
          mma8(q0, pk[4 * u + 2], pk[4 * u + 3], pk[4 * u + 2]); mma8(q1, pk[4 * u + 2], pk[4 * u + 3], pk[4 * u + 3]);
        }
        auto stats = [&]() {
#pragma unroll
          for (int h = 0; h < 2; h++) {
            const float ss = sm[2 * h], m = ss * (1.f / 72.f), qq = h ? ((g & 1) ? q1[3] : q1[2]) : (g & 1) ? q0[1] : q0[0];
            ll_st128_if(eye, stp + 8 * h, m, fmaxf(qq - ss * m, 0.f), tag);
          }
        };
        bar_sync(8 + q, 64);
        uint4 v[5];
#pragma unroll
        for (int u = 0; u < 5; u++) v[u] = lds128(u < 4 ? (xl0 ^ ((u & 2) << 3)) + u * 576 : xl1);
        stats();
#pragma unroll
        for (int u = 0; u < 5; u++) stg128_if(u < 4 || lane < 16, u < 4 ? xd0 + u * (DM * 8) : xd1, v[u].x, v[u].y, v[u].z, v[u].w);
        signal(EV_X1);
      }
      uint32_t zk[16];
      {
        uint32_t xA[36][4];
        float acc[32];
        uint32_t s0, one, off2;
        uint8_t *z1d, *zd;
        uint64_t db;
        auto bwait = [&](uint32_t dhi, bool skip) {
          s0 = c.s;
          c.next();
          if (!skip) mbar_wait_c(bars + B_FULL + c.s * 8, c.ph);
          db = dsc2(dlo(sb + s0 * ST_BYTES + ST_B, 512) - 3, 0, dhi); one = (c.s ^ Q.zero) & 1;
        };
        auto mma = [&](int kk, int pp, bool hand) {
          wgmma_rs_n64(acc, xA[kk], dat(db, (kk / 18) * ST_BYTES + (kk % 18) * 2048 + 48, one), kk != 0);
          if (kk == pp && hand) bar_arrive(7 - w, 256);
          if (kk == 17 || kk == 35) wgmma_commit();
          if (kk == RL3) { wgmma_commit(); wgmma_wait<1>(); release(s0); }
        };
        {
          bwait(0x40000040u, false);
          mbar_wait_c(bars + B_GATE3, L);
          float mean0, mean1, rs0, rs1;
          stat_get(Q.s->ST1 + ((rb * 2 + w) * 8 + 2 * t) * 64 + 16 * q + g, tag, 72.f, LN_EPS, mean0, rs0, mean1, rs1);
          const uint32_t ns0 = pack2(GA * rs0, GA * rs0), ns1 = pack2(GA * rs1, GA * rs1);
          const uint32_t nb0 = pack2(-mean0 * blo(ns0), -mean0 * blo(ns0)), nb1 = pack2(-mean1 * blo(ns1), -mean1 * blo(ns1));
          const uint32_t al = sb + (aoff & 8191);
#pragma unroll
          for (int kb = 0; kb <= 9; kb++) {
            if (kb < 9) {
              mbar_wait_c(bars + B_FA3 + (9 * w + kb) * 8, L);
              const uint32_t at = al + (w ? (((kb + 1) >> 1) & 3) * ST_BYTES + ((kb + 1) & 1) * 8192 : ((kb >> 1) & 3) * ST_BYTES + (kb & 1) * 8192);
#pragma unroll
              for (int kk = 4 * kb; kk < 4 * kb + 4; kk++) ldsm4(xA[kk], at ^ ((kk & 3) << 5));
            }
            if (kb == 0) continue;
            const uint32_t dep = xA[4 * kb - 4][0] & xA[4 * kb - 3][0] & xA[4 * kb - 2][0] & xA[4 * kb - 1][0] & Q.zero;
            mbar_arrive_if(lane == 0 && (kb == 1 || w == 0), bars + B_EA3 + (9 * w + kb - 1) * 8 + dep);
#pragma unroll
            for (int kk = 4 * kb - 4; kk < 4 * kb; kk++) {
#pragma unroll
              for (int e = 0; e < 4; e++) xA[kk][e] = hfma2(xA[kk][e], (e & 1) ? ns1 : ns0, (e & 1) ? nb1 : nb0);
            }
            wgmma_fence();
#pragma unroll
            for (int kk = 4 * kb - 4; kk < 4 * kb; kk++) mma(kk, PP30, w);
          }
          off2 = lds32(sb + SM_OFF);
          z1d = z1_block(rb, w, j) + (tid & 127) * 16;
          zd = z2_block(2 * rb + (q >> 1), j) + (4 * (q & 1) + w) * 4608 + ((g & 3) * 2 + (g >> 2)) * 16 + t * 4;
          asm volatile("" : "+l"(z1d), "+l"(zd));
          wgmma_wait<0>();
          if (__builtin_expect(any_nan(acc[0], acc[2]), 0)) {
            uint4* rd = Q.s->RD + (uint32_t)(bid * (36 * 256) + tid);
            asm volatile("" : "+l"(rd));
            const uint8_t* xr = Q.xs[L + 1] + (uint32_t)((128 * rb + 32 * q + 2 * g + w) * (DM * 2) + t * 4);
            const uint32_t any[8] = {ns0, ns1, nb0, nb1, (uint32_t)lane, (uint32_t)tid, (uint32_t)g, (uint32_t)t};
#pragma unroll
            for (int i = 0; i < 8; i++) widen(acc + 4 * i, 0u, 0u, any[i]);
            redo<KS3, 8, 16, DM * 32, FH * 32, 16>(acc, xr, (const uint8_t*)P.w_in + (uint32_t)(g * (FH * 4) + (((9 * j + 1) >> 1) + 36) * 128 + t * 4),
                                              [&](uint32_t* a, int k) {
#pragma unroll
                                                for (int e = 0; e < 4; e++) a[e] = hfma2(a[e], (e & 1) ? ns1 : ns0, (e & 1) ? nb1 : nb0);
                                                stg128(rd + k * 256, a[0], a[1], a[2], a[3]);
                                              });
#pragma unroll
            for (int k = 0; k < 36; k++) { const uint4 v = ldcg128(rd + k * 256); xA[k][0] = v.x; xA[k][1] = v.y; xA[k][2] = v.z; xA[k][3] = v.w; }
          }
        }
        float sm[4] = {0.f, 0.f, 0.f, 0.f}, qq[4] = {0.f, 0.f, 0.f, 0.f};
        auto gelu = [&](auto nz2) {
          constexpr int NZ2 = nz2.value, R = 8 - NZ2, N = 8, D = NZ2 == 8 ? GM2 : NZ2 ? GMM : GM1;
          float th[32], gb = GB;
          uint32_t qa = 0, qb = 0;
          auto head = [&](int G) {
#pragma unroll
            for (int e = 0; e < 4; e++) { const float v = acc[4 * G + e]; th[4 * G + e] = tanh_fast(v * fmaf(v, v, gb)); }
          };
#pragma unroll
          for (int i = 0; i < D; i++) head((i + R) & 7);
#pragma unroll
          for (int i = 0; i < N; i++) {
            const int G = (i + R) & 7;
            if (i + D < N) head((i + D + R) & 7);
            float* z = acc + 4 * G;
#pragma unroll
            for (int e = 0; e < 4; e++) z[e] = fmaf(z[e], th[4 * G + e], z[e]);
            uint32_t pa = pack2(z[0], z[1]), pb = pack2(z[2], z[3]), tok;
            if (i < NZ2) {
#pragma unroll
              for (int e = 0; e < 4; e++) { sm[e] += z[e]; qq[e] = fmaf(z[e], z[e], qq[e]); }
              pa = hsub2(pa, off2); pb = hsub2(pb, off2);
              stg32(zd + i * 128, pa); stg32(zd + i * 128 + 9216, pb);
              tok = pa ^ pb ^ __float_as_uint(qq[1]);
            } else {
              if (NZ2 && G == 3) sts128(sb + SM_STG + tid * 16, qa, qb, pa, pb);
              else if (G & 1) stg128(z1d + (G >> 1) * 2048 + (NZ2 ? 24576 : 0), qa, qb, pa, pb);
              qa = pa; qb = pb;
              tok = pa ^ pb;
            }
            gb = __uint_as_float(tok * Q.zero + __float_as_uint(GB));
          }
        };
        auto done = [&](int p) {
          wgmma_wait<0>();
          release(c.s);
          c.next();
        };
        auto pass = [&](int p, uint32_t dhi) {
          bwait(dhi, w);
          bar_sync(6 + w, 256);
          wgmma_fence();
#pragma unroll
          for (int kk = 0; kk < 36; kk++) mma(kk, PP3, w == 0 || p < 8);
          done(p);
        };
        done(0);
#pragma unroll 1
        for (int p = 1; p < 5; p++) {
          gelu(Int<8>{});
          zd += 1024;
          pass(p, p == 4 ? 0x80000040u : 0x40000040u);
        }
        gelu(Int<4>{});
        signal(EV_ZN);
        {
          const float a0 = qsum(sm[0] + sm[1]), a1 = qsum(sm[2] + sm[3]), q0 = qsum(qq[0] + qq[1]), q1 = qsum(qq[2] + qq[3]);
          const float ss = t ? a1 : a0, m = ss * (1.f / 288.f);
          ll_st128_if(t < 2, Q.s->ZST + (rb * 2 + w) * 512 + j * 64 + 16 * q + 8 * t + g, m - blo(off2), fmaxf((t ? q1 : q0) - ss * m, 0.f), tag);
        }
#pragma unroll 1
        for (int p = 5;; p++) {
          pass(p, 0x40000040u);
          if (p == 8) break;
          gelu(Int<0>{});
          z1d += 8192;
        }
        signal(EV_Z1);
#pragma unroll
        for (int i = 0; i < 16; i++) zk[i] = pack2(acc[2 * i], acc[2 * i + 1]);
      }
      uint32_t hA[18][4];
      {
        float acc[144];
        const float c0 = __uint_as_float(lds32(sb + SM_OFF + 4));
#pragma unroll
        for (int i = 0; i < 144; i++) {
          asm volatile("fma.rn.f32 %0, %1, %2, %3;" : "=f"(acc[i]) : "f"(__uint_as_float(Q.zero)), "f"((float)(i + 2)), "f"(c0));
        }
        uint32_t prev = 0;
        auto stage = [&](int kb, auto odd) {
          mbar_wait_c(bars + B_FULL + c.s * 8, c.ph);
          const uint32_t st = sb + c.s * ST_BYTES, rt = sb + SM_RT + kb * 128 + t * 8;
          uint64_t db = dsc2(dlo(st + ST_B, 4608), 0, 8 + Q.zero);
          uint32_t a[4][4];
#pragma unroll
          for (int kk = 0; kk < 4; kk++) {
            uint32_t r[4];
            ldsm4(r, st + (aoff ^ (kk << 5)));
            const uint2 sc = lds64(rt + kk * 32);
            a[kk][0] = hmul2(__byte_perm(r[0], r[2], 0x5410), sc.x); a[kk][2] = hmul2(__byte_perm(r[0], r[2], 0x7632), sc.y);
            a[kk][1] = hmul2(__byte_perm(r[1], r[3], 0x5410), sc.x); a[kk][3] = hmul2(__byte_perm(r[1], r[3], 0x7632), sc.y);
          }
          if (!odd.value) {
            const float x = blo(zk[0]), y = bhi(zk[0]);
#pragma unroll
            for (int i = 0; i < 15; i++) zk[i] = zk[i + 1];
            zk[15] = pack2(fmaf(x, tanh_fast(x * fmaf(x, x, GB)), x), fmaf(y, tanh_fast(y * fmaf(y, y, GB)), y));
          }
          wgmma_fence();
#pragma unroll
          for (int i = 0; i < 8; i++) {
            const int kk = i & 3, hf = i >> 2;
            wgmma_rs_n144(acc + hf * 72, a[kk], db, 1);
            dadd(db, i == 3 ? 144u - 3 * 576 : 576 + Q.zero);
            if (i == 0) { wgmma_commit(); wgmma_wait<1>(); release_if(kb, prev); }
            if (i == 3) wgmma_commit();
          }
          wgmma_commit();
          prev = c.s; c.next();
        };
        mbar_wait_c(bars + B_RT, L);
#pragma unroll 1
        for (int kb = 0; kb < 32; kb += 2) {
          if (kb == 8) mbar_wait_c(bars + B_RT1, L);
          stage(kb, Int<0>{});
          stage(kb + 1, Int<1>{});
        }
        if (w == 1) bar_arrive(6, 256);
        mbar_wait_c(bars + B_CV + w * 8, L);
        const float gk = 0.5f / GA;
        const float c1 = __uint_as_float(lds32(sb + SM_OFF + 4));
        const float gb0 = -gk * (c1 + __uint_as_float(lds32(sb + SM_CV + w * 256 + (16 * q + g) * 4))), gb1 = -gk * (c1 + __uint_as_float(lds32(sb + SM_CV + w * 256 + (16 * q + g + 8) * 4)));
        mbar_wait_c(w ? bars + B_FULL + c.s * 8 : bars + B_ZB, w ? c.ph : L);
        const uint32_t sx = c.s;
        c.next();
        const uint32_t zt = sb + tid * 16, zs = zt + sx * ST_BYTES + w * 24576;
        uint4 zz[18];
        auto zload = [&](int u) {
          if (ZW && u == ZW && Q.zero) __nanosleep(0);
          if (u >= 12 && u < 16) zz[u] = make_uint4(zk[4 * u - 48], zk[4 * u - 47], zk[4 * u - 46], zk[4 * u - 45]); else zz[u] = lds128(u == 17 ? zt + SM_STG : zs + (u < 12 ? u : 12) * 2048);
        };
#pragma unroll
        for (int u = 0; u < ZA; u++) zload(u);
#pragma unroll
        for (int u = 0; u < 18; u++) {
          if (u == 0) { wgmma_wait<1>(); }
          if (u == 9) {
            wgmma_wait<0>();
            release(prev);
            mbar_arrive_if(L == 0 && lane == 0, ev + EV_P4 * 8);
          }
          if (u + ZA < 18) zload(u + ZA);
          const uint4 z = zz[u];
          hA[u][0] = hmul2(z.x, pack2(fmaf(acc[8 * u], gk, gb0), fmaf(acc[8 * u + 1], gk, gb0)));
          hA[u][1] = hmul2(z.y, pack2(fmaf(acc[8 * u + 2], gk, gb1), fmaf(acc[8 * u + 3], gk, gb1)));
          hA[u][2] = hmul2(z.z, pack2(fmaf(acc[8 * u + 4], gk, gb0), fmaf(acc[8 * u + 5], gk, gb0)));
          hA[u][3] = hmul2(z.w, pack2(fmaf(acc[8 * u + 6], gk, gb1), fmaf(acc[8 * u + 7], gk, gb1)));
        }
        uint32_t dep = Q.zero;
#pragma unroll
        for (int u = 0; u < 18; u++) dep &= hA[u][0];
        release(sx, dep);
      }
      {
        const uint32_t el = elect_one();
#pragma unroll 1
        for (int p = 0; p < 9; p++) {
          float acc[32];
          if (w == 0) mbar_wait_c(bars + B_FULL + c.s * 8, c.ph);
          uint64_t db = dsc2(dlo(sb + c.s * ST_BYTES + ST_B + (j & 1) * 4096, 0), 0, 0x40000040u + Q.zero);
          bar_sync(6 + w, 256);
          wgmma_fence();
#pragma unroll
          for (int kk = 0; kk < 18; kk++) {
            wgmma_rs_n64(acc, hA[kk], db, kk != 0);
            dadd(db, kk == 15 ? 128 - (j & 1) * (36864 >> 4) : 128 + Q.zero);
            if (kk == PPK && (w == 0 || p < 8)) bar_arrive(7 - w, 256);
          }
          wgmma_commit();
          const uint32_t d = sb + (p & 3) * ST_BYTES, cb = p + j >= 9 ? p + j - 9 : p + j;
          if (el) asm volatile("cp.async.bulk.commit_group;\ncp.async.bulk.wait_group.read 3;" ::: "memory");
          __syncwarp();
          wgmma_wait<0>();
          release_if(L == 0 || p < 5, c.s);
          c.next();
#pragma unroll
          for (int u = 0; u < 4; u++)
            stsm4(d + (aoff ^ (u << 5)), pack2(acc[8 * u], acc[8 * u + 1]), pack2(acc[8 * u + 2], acc[8 * u + 3]), pack2(acc[8 * u + 4], acc[8 * u + 5]), pack2(acc[8 * u + 6], acc[8 * u + 7]));
          fence_async_s();
          __syncwarp();
          tma3d_red_p(el, &P.red[L], cb * 64, rb * 64 + q * 16, w, d + w * 8192 + q * 2048);
        }
        if (el) asm volatile("cp.async.bulk.commit_group;\ncp.async.bulk.wait_group 0;" ::: "memory");
        if (L == 0) signal(EV_PT);
      }
    }
  }
}

typedef CUresult (*EncodeFn)(CUtensorMap*, CUtensorMapDataType, cuuint32_t, void*, const cuuint64_t*, const cuuint64_t*, const cuuint32_t*,
                             const cuuint32_t*, CUtensorMapInterleave, CUtensorMapSwizzle, CUtensorMapL2promotion, CUtensorMapFloatOOBfill);

static void make_map(EncodeFn fn, CUtensorMap* m, const void* ptr, int rank, uint64_t d0, uint64_t d1, uint64_t d2, uint64_t s1, uint64_t s2,
                     uint32_t b0, uint32_t b1, uint32_t b2, CUtensorMapSwizzle swz) {
  cuuint64_t dims[3] = {d0, d1, d2}, strides[2] = {s1, s2};
  cuuint32_t box[3] = {b0, b1, b2}, es[3] = {1, 1, 1};
  fn(m, CU_TENSOR_MAP_DATA_TYPE_BFLOAT16, rank, const_cast<void*>(ptr), dims, strides, box, es, CU_TENSOR_MAP_INTERLEAVE_NONE, swz,
     CU_TENSOR_MAP_L2_PROMOTION_L2_128B, CU_TENSOR_MAP_FLOAT_OOB_FILL_NONE);
}

}

extern "C" void kernel_launch(void* const* d_in, const int* in_sizes, int n_in, void* d_out, int out_size) {
  using namespace mk;
  (void)in_sizes; (void)n_in; (void)out_size;
  static EncodeFn fn = nullptr;
  static Scratch* sc;
  if (!fn) {
    cudaGetSymbolAddress((void**)&sc, g_scratch);
    cudaDriverEntryPointQueryResult qr;
    cudaGetDriverEntryPoint("cuTensorMapEncodeTiled", (void**)&fn, cudaEnableDefault, &qr);
    cudaFuncSetAttribute(mega_kernel, cudaFuncAttributeMaxDynamicSharedMemorySize, SM_TOTAL);
  }
  Head h;
  Params p;
  h.wqkv = (const __nv_bfloat16*)d_in[1];
  p.w_in = (const __nv_bfloat16*)d_in[4];
  p.w_sp = (const __nv_bfloat16*)d_in[5];
  p.b_sp = (const __nv_bfloat16*)d_in[6];
  p.w_out = (const __nv_bfloat16*)d_in[7];
  h.zero = 0;
  h.s = sc;
  h.xs[0] = (uint8_t*)d_in[0];
  h.xs[1] = sc->X;
  h.xs[2] = (uint8_t*)d_out;
  make_map(fn, &p.wsp, p.w_sp, 3, 2048, 1024, 2, 8192, 4096, 64, 64, 2, CU_TENSOR_MAP_SWIZZLE_128B);
  for (int i = 0; i < 2; i++) {
    make_map(fn, &p.red[i], h.xs[i + 1], 3, DM, 1024, 2, 2304, 1152, 64, 16, 1, CU_TENSOR_MAP_SWIZZLE_128B);
    make_map(fn, &p.res[i], h.xs[i], 3, DM, 1024, 2, 2304, 1152, 144, 64, 1, CU_TENSOR_MAP_SWIZZLE_NONE);
  }
  make_map(fn, &p.psn, d_out, 3, DM, 1024, 2, 2304, 1152, 144, 4, 1, CU_TENSOR_MAP_SWIZZLE_NONE);
  for (int i = 0; i < 3; i++) make_map(fn, &p.act[i], h.xs[i], 3, DM, 1024, 2, 2304, 1152, 64, 64, 1, CU_TENSOR_MAP_SWIZZLE_128B);
  {
    cuuint64_t dims[4] = {8, 8, 72, 72}, strides[3] = {1152, 16, 9216};
    cuuint32_t box[4] = {8, 8, 9, 5}, es[4] = {1, 1, 1, 1};
    fn(&p.wo8, CU_TENSOR_MAP_DATA_TYPE_BFLOAT16, 4, d_in[2], dims, strides, box, es, CU_TENSOR_MAP_INTERLEAVE_NONE, CU_TENSOR_MAP_SWIZZLE_NONE,
       CU_TENSOR_MAP_L2_PROMOTION_L2_128B, CU_TENSOR_MAP_FLOAT_OOB_FILL_NONE);
  }
  for (int i = 0; i < 2; i++) {
    cuuint64_t dims[4] = {i ? 4608u : 2304u, 8, i ? 1u : 2u, 72}, strides[3] = {9216, 4608, 8 * 9216};
    cuuint32_t box[4] = {i ? 64u : 32u, 8, i ? 1u : 2u, 18}, es[4] = {1, 1, 1, 1};
    fn(i ? &p.win64 : &p.win, CU_TENSOR_MAP_DATA_TYPE_BFLOAT16, 4, d_in[4], dims, strides, box, es, CU_TENSOR_MAP_INTERLEAVE_NONE,
       i ? CU_TENSOR_MAP_SWIZZLE_128B : CU_TENSOR_MAP_SWIZZLE_64B, CU_TENSOR_MAP_L2_PROMOTION_L2_128B, CU_TENSOR_MAP_FLOAT_OOB_FILL_NONE);
  }
  make_map(fn, &p.wout, p.w_out, 2, 576, 2304, 1, 1152, 0, 64, 144, 1, CU_TENSOR_MAP_SWIZZLE_128B);
  mega_kernel<<<NGRID, 384, SM_TOTAL, cudaStreamPerThread>>>(h, p);
}
```
